```python
import torch

def _softmax(x, axis=-1):
    return torch.softmax(x, dim=axis)
def _gelu(x):
    return torch.nn.functional.gelu(x, approximate="tanh")
def _silu(x):
    return torch.nn.functional.silu(x)
def _sigmoid(x):
    return torch.sigmoid(x)
def _layernorm(x, axis=-1, eps=1e-5):
    m = x.mean(dim=axis, keepdim=True)
    v = x.var(dim=axis, keepdim=True, unbiased=False)
    return (x - m) / torch.sqrt(v + eps)
def _scatter_add(tgt, idx, src, axis=0):
    return tgt.clone().index_add_(axis, idx, src)
def _segment_sum(src, seg, n):
    out = torch.zeros((n,) + src.shape[1:], dtype=src.dtype)
    return out.index_add_(0, seg, src)
def _pad(x, pw):
    flat = tuple(v for pair in reversed(pw) for v in pair)
    return torch.nn.functional.pad(x, flat)

kernel_name = 'interleave_layers__sliding_local_dilated__ssm_conv_s4__prompt'

def setup_inputs():

    _w = (lambda a: (lambda t: t.to(torch.bfloat16) if t.is_floating_point() else t)(torch.as_tensor(a)))
    def _A_setup():
        B, S, D = 1, 2048, 512
        return {
            "x": _w((lambda *s: torch.randn(*s, dtype=torch.bfloat16) * 0.05)(B, S, D)),
            "wqkv": _w((lambda *s: torch.randn(*s, dtype=torch.bfloat16) * 0.05)(D, 3 * D)),
            "wo": _w((lambda *s: torch.randn(*s, dtype=torch.bfloat16) * 0.05)(D, D)),
        }
    _A_in = _A_setup()

    def _B_setup():
        B, L, D, N = 1, 2048, 512, 128
        A_re = -(lambda _x: torch.exp(torch.as_tensor(_x)))((lambda *s: torch.randn(*s, dtype=torch.bfloat16) * 3.2)(D, N))
        A_im = torch.pi * (lambda *s: torch.randn(*s, dtype=torch.bfloat16) * 0.1)(D, N)
        B_re = (lambda *s: torch.randn(*s, dtype=torch.bfloat16) * 0.1)(D, N)
        B_im = (lambda *s: torch.randn(*s, dtype=torch.bfloat16) * 0.1)(D, N)
        C_re = (lambda *s: torch.randn(*s, dtype=torch.bfloat16) * 0.1)(D, N)
        C_im = (lambda *s: torch.randn(*s, dtype=torch.bfloat16) * 0.1)(D, N)
        log_dt = (lambda *s: torch.randn(*s, dtype=torch.bfloat16) * 0.1)(D) * 0.5 - 4.0
        Dskip = (lambda *s: torch.randn(*s, dtype=torch.bfloat16) * 0.1)(D)
        return {
            "u": _w((lambda *s: torch.randn(*s, dtype=torch.bfloat16) * 0.05)(B, L, D)),
            "A_re": _w(A_re),
            "A_im": _w(A_im),
            "B_re": _w(B_re),
            "B_im": _w(B_im),
            "C_re": _w(C_re),
            "C_im": _w(C_im),
            "log_dt": _w(log_dt),
            "Dskip": _w(Dskip),
        }
    _B_in = _B_setup()

    return {
        "A_x": _A_in["x"],
        "A_wqkv": _A_in["wqkv"],
        "A_wo": _A_in["wo"],
        "B_u": _B_in["u"],
        "B_A_re": _B_in["A_re"],
        "B_A_im": _B_in["A_im"],
        "B_B_re": _B_in["B_re"],
        "B_B_im": _B_in["B_im"],
        "B_C_re": _B_in["C_re"],
        "B_C_im": _B_in["C_im"],
        "B_log_dt": _B_in["log_dt"],
        "B_Dskip": _B_in["Dskip"],
    }

def reference(A_x, A_wqkv, A_wo, B_u, B_A_re, B_A_im, B_B_re, B_B_im, B_C_re, B_C_im, B_log_dt, B_Dskip):
    def _A_ref(x, wqkv, wo):
        B, S, D = x.shape
        H = 32; Dh = D // H
        W, dil = 8, 2
        qkv = (lambda x, *d: x.permute(*d))((x @ wqkv).reshape(B, S, 3, H, Dh), 2, 0, 3, 1, 4)
        q, k, v = qkv[0], qkv[1], qkv[2]
        scale = Dh ** -0.5
        pos = torch.arange(S)
        off = torch.arange(W) * dil
        idx = pos[:, None] - off[None, :]
        mask = idx >= 0
        idx_c = torch.where(mask, idx, 0).reshape(-1)
        kg = k[:, :, idx_c, :].reshape(B, H, S, W, Dh)
        vg = v[:, :, idx_c, :].reshape(B, H, S, W, Dh)
        logits = torch.einsum("bhsd,bhswd->bhsw", q, kg) * scale
        logits = torch.where(mask[None, None, :, :], logits, -1e9)
        attn = _softmax(logits, axis=-1)
        o = torch.einsum("bhsw,bhswd->bhsd", attn, vg)
        return (lambda x, *d: x.permute(*d))(o, 0, 2, 1, 3).reshape(B, S, D) @ wo

    def _B_ref(u, A_re, A_im, B_re, B_im, C_re, C_im, log_dt, Dskip):
        Bsz, L, D = u.shape
        dt = torch.exp(log_dt)[:, None]
        A = A_re + 1j * A_im
        Bc = B_re + 1j * B_im
        Cc = C_re + 1j * C_im
        logdA = dt * A
        dB = dt * Bc
        l = (lambda x, dt: x.to(dt))(torch.arange(L), A_re.dtype)
        P = torch.exp(logdA[:, :, None] * l[None, None, :])
        K = torch.einsum("dn,dnl,dn->dl", Cc, P, dB).real
        L2 = 2 * L
        Kp = _pad(K, ((0, 0), (0, L)))
        up = (lambda x, *d: x.permute(*d))(u, 0, 2, 1)
        up = _pad(up, ((0, 0), (0, 0), (0, L)))
        Kf = (lambda x, axes=(-2,-1): torch.fft.rfft2(x.float(), dim=axes))(Kp[:, None, :], axes=(-2, -1))
        Uf = (lambda x, axes=(-2,-1): torch.fft.rfft2(x.float(), dim=axes))(up[:, :, None, :], axes=(-2, -1))
        Yf = Uf * Kf[None, :, :, :]
        y = (lambda x, s, axes=(-2,-1): torch.fft.irfft2(x, s=s, dim=axes).to(torch.bfloat16))(Yf, (1, L2), axes=(-2, -1))[:, :, 0, :L]
        y = (lambda x, *d: x.permute(*d))(y, 0, 2, 1) + u * Dskip[None, None, :]
        return y

    x = A_x
    x = x + _A_ref(_layernorm(x, axis=-1), A_wqkv, A_wo)
    x = x + _B_ref(_layernorm(x, axis=-1), B_A_re, B_A_im, B_B_re, B_B_im, B_C_re, B_C_im, B_log_dt, B_Dskip)
    x = x + _A_ref(_layernorm(x, axis=-1), A_wqkv, A_wo)
    x = x + _B_ref(_layernorm(x, axis=-1), B_A_re, B_A_im, B_B_re, B_B_im, B_C_re, B_C_im, B_log_dt, B_Dskip)
    return x
```

```cpp
#include <cuda_runtime.h>
#include <cuda_bf16.h>
#include <cuda.h>
#include <stdint.h>

typedef __nv_bfloat16 bf16;

constexpr int LSEQ = 2048;
constexpr int DM = 512;
constexpr int NCTA = 128;
constexpr int NTHREADS = 512;
#define RR 0
#define KG_PRE 0
#define CS_LATE 0
#define KG_LAST 1
#define X_JIT 0
#define KG_GATE 2
#define R_CONS 192
#define R_HELP 88

constexpr int SM_X = 0;
constexpr int SM_W = 131072;
constexpr int SM_KVX = SM_W;
constexpr int SM_OST = SM_W + 32768;
constexpr int SM_R = 196608;
constexpr int SM_T = 212992;
constexpr int SM_KC = 217088;
constexpr int KC_STRIDE = 648;
constexpr int SM_CS = SM_KC + 4 * KC_STRIDE * 2;
constexpr int SM_RED = SM_CS + 768;
constexpr int SM_EP = SM_RED + 256;
constexpr int SM_BAR = SM_RED + 272;
constexpr int SM_T2 = SM_BAR + 768;
constexpr int SM_HALO = SM_T2 + 4096;
constexpr int SM_TOTAL = SM_HALO + 4096;
static_assert(SM_TOTAL <= 232448, "shared memory");

constexpr int CV_UH = 140 * 16;
constexpr int CV_PECH = 1120 * 4;
constexpr int CV_PBW = 2112 * 2;
constexpr int CV_CH = 27136;
__host__ __device__ constexpr int cv_u(int lc) { return SM_X + (lc >> 1) * 65536 + (lc & 1) * CV_CH; }
__host__ __device__ constexpr int cv_pe(int lc) { return cv_u(lc) + 2 * CV_UH; }
__host__ __device__ constexpr int cv_pb(int lc) { return cv_pe(lc) + CV_PECH; }
__host__ __device__ constexpr int cv_wt(int lc) { return cv_pb(lc) + 4 * CV_PBW; }
__host__ __device__ constexpr int cv_pf(int lc) { return cv_pe(lc); }
__host__ __device__ constexpr int cv_se(int lc) { return SM_X + (lc >> 1) * 65536 + 2 * CV_CH + (lc & 1) * 4096; }
__host__ __device__ constexpr int cv_so(int lc) { return cv_se(lc) + 2048; }
static_assert(2 * CV_CH + 8192 <= 65536 && CV_CH % 256 == 0 && cv_wt(0) + 1152 <= CV_CH, "conv buffers");
__host__ __device__ constexpr int cv_chan(int cta, int lc) { return 2 * cta + (lc & 1) + 256 * (lc >> 1); }

enum {
  B_XF = 0,
  B_KVF = 8,
  B_KVE = 16,
  B_AD = 26,
  B_U2 = 25,
  B_S2 = 30,
  B_U1 = 28,
  B_S1 = 29,
  B_OST = 24,
  B_WOF = 36,
  B_OF = 44,
  B_RF = 52,
  B_R1 = 53,
  B_HF = 54,
  B_CSF = 55,
  B_QDONE = 56,
  B_PDONE = 57,
  B_Z0 = 58,
  B_PE = 59,
  B_GB = 60,
  B_TF = 61,
  B_EP = 62,
  B_ZF = 63,
  B_COUNT = 64
};

enum {
  C_CS = 0,
  C_G0 = 44,
  C_G1A = 2,
  C_G1B = 1,
  C_G2 = 3,
  C_O = 4,
  C_F = 36,
  C_COUNT = 45
};

__device__ unsigned g_cnt[C_COUNT * 32];
__device__ __align__(1024) bf16 g_O[LSEQ * DM];
__device__ __align__(1024) bf16 g_xT[4 * DM * LSEQ];
__device__ __align__(1024) float g_stats[2 * LSEQ * 2];
__device__ __align__(1024) uint2 g_colsum[3 * DM];
__device__ __align__(1024) uint4 g_halo[2 * 16 * 8 * 384];
__device__ __align__(1024) uint4 g_part[2 * 16 * 8 * 128];
#define TS(i) do { } while (0)

#define LTS(i) do { } while (0)

struct Params {
  CUtensorMap mapO, mapXT, mapOut, mapX128, mapWo128, mapO128, mapW3, mapXT3;
  const bf16 *wqkv, *a_re, *a_im, *b_re, *b_im, *c_re, *c_im, *log_dt, *dskip;
  int stop;
};

__device__ __forceinline__ uint32_t s32(const void* p) { return (uint32_t)__cvta_generic_to_shared(p); }
__device__ __forceinline__ void mbar_init(uint32_t b, int c) { asm volatile("mbarrier.init.shared::cta.b64 [%0], %1;" ::"r"(b), "r"(c) : "memory"); }
__device__ __forceinline__ void mbar_expect(uint32_t b, int bytes) { asm volatile("mbarrier.arrive.expect_tx.shared::cta.b64 _, [%0], %1;" ::"r"(b), "r"(bytes) : "memory"); }
__device__ __forceinline__ void mbar_arrive(uint32_t b) { asm volatile("mbarrier.arrive.shared::cta.b64 _, [%0];" ::"r"(b) : "memory"); }
__device__ __forceinline__ void mbar_wait(uint32_t b, int parity) {
  asm volatile("{\n.reg .pred p;\nWAIT_LOOP:\nmbarrier.try_wait.parity.shared::cta.b64 p, [%0], %1;\n@p bra WAIT_DONE;\nbra WAIT_LOOP;\nWAIT_DONE:\n}" ::"r"(b), "r"(parity) : "memory");
}
__device__ __forceinline__ int opaque_tid() { int v; asm volatile("mov.u32 %0, %%tid.x;" : "=r"(v)); return v; }
__device__ __forceinline__ bool elect_one() {
  uint32_t r;
  asm volatile("{\n.reg .pred p;\nelect.sync _|p, 0xffffffff;\nselp.u32 %0, 1, 0, p;\n}" : "=r"(r));
  return r != 0;
}
__device__ __forceinline__ void tma_ld(uint32_t dst, const CUtensorMap* m, int c0, int c1, uint32_t bar) {
  asm volatile("cp.async.bulk.tensor.2d.shared::cluster.global.mbarrier::complete_tx::bytes [%0], [%1, {%3, %4}], [%2];"
               ::"r"(dst), "l"(m), "r"(bar), "r"(c0), "r"(c1) : "memory");
}
__device__ __forceinline__ void tma_ld3(uint32_t dst, const CUtensorMap* m, int c0, int c1, int c2, uint32_t bar) {
  asm volatile("cp.async.bulk.tensor.3d.shared::cluster.global.mbarrier::complete_tx::bytes [%0], [%1, {%3, %4, %5}], [%2];"
               ::"r"(dst), "l"(m), "r"(bar), "r"(c0), "r"(c1), "r"(c2) : "memory");
}
__device__ __forceinline__ void tma_prefetch2(const CUtensorMap* m, int c0, int c1) {
  asm volatile("cp.async.bulk.prefetch.tensor.2d.L2.global.tile [%0, {%1, %2}];" ::"l"(m), "r"(c0), "r"(c1) : "memory");
}
__device__ __forceinline__ void tma_prefetch3(const CUtensorMap* m, int c0, int c1, int c2) {
  asm volatile("cp.async.bulk.prefetch.tensor.3d.L2.global.tile [%0, {%1, %2, %3}];" ::"l"(m), "r"(c0), "r"(c1), "r"(c2) : "memory");
}
__device__ __forceinline__ void tma_st(const CUtensorMap* m, int c0, int c1, uint32_t src) {
  asm volatile("cp.async.bulk.tensor.2d.global.shared::cta.bulk_group [%0, {%2, %3}], [%1];" ::"l"(m), "r"(src), "r"(c0), "r"(c1) : "memory");
}
__device__ __forceinline__ void bulk_ld(uint32_t dst, const void* src, int bytes, uint32_t bar) {
  asm volatile("cp.async.bulk.shared::cluster.global.mbarrier::complete_tx::bytes [%0], [%1], %2, [%3];" ::"r"(dst), "l"(src), "r"(bytes), "r"(bar) : "memory");
}
__device__ __forceinline__ void bulk_st(void* dst, uint32_t src, int bytes) {
  asm volatile("cp.async.bulk.global.shared::cta.bulk_group [%0], [%1], %2;" ::"l"(dst), "r"(src), "r"(bytes) : "memory");
}
__device__ __forceinline__ void bulk_red_add_f32(void* dst, uint32_t src, int bytes) {
  asm volatile("cp.reduce.async.bulk.global.shared::cta.bulk_group.add.f32 [%0], [%1], %2;" ::"l"(dst), "r"(src), "r"(bytes) : "memory");
}
__device__ __forceinline__ void bulk_commit() { asm volatile("cp.async.bulk.commit_group;" ::: "memory"); }
__device__ __forceinline__ void bulk_wait_all() { asm volatile("cp.async.bulk.wait_group 0;" ::: "memory"); }
__device__ __forceinline__ void fence_async_smem() { asm volatile("fence.proxy.async.shared::cta;" ::: "memory"); }
__device__ __forceinline__ void fence_async_global() { asm volatile("fence.proxy.async.global;" ::: "memory"); }
__device__ __forceinline__ void bar_sync(int id, int n) { asm volatile("bar.sync %0, %1;" ::"r"(id), "r"(n) : "memory"); }
__device__ __forceinline__ void bar_arrive(int id, int n) { asm volatile("bar.arrive %0, %1;" ::"r"(id), "r"(n) : "memory"); }
__device__ __forceinline__ void wg_fence() { asm volatile("wgmma.fence.sync.aligned;" ::: "memory"); }
__device__ __forceinline__ void wg_commit() { asm volatile("wgmma.commit_group.sync.aligned;" ::: "memory"); }
template <int N> __device__ __forceinline__ void wg_wait() { asm volatile("wgmma.wait_group.sync.aligned %0;" ::"n"(N) : "memory"); }
__device__ __forceinline__ uint64_t mkdesc(uint32_t addr, uint32_t lbo, uint32_t sbo, int sw) {
  return (uint64_t)((addr & 0x3FFFF) >> 4) | ((uint64_t)(lbo >> 4) << 16) | ((uint64_t)(sbo >> 4) << 32) | ((uint64_t)sw << 62);
}
__device__ __forceinline__ void ldsm4(uint32_t* r, uint32_t a) {
  asm volatile("ldmatrix.sync.aligned.m8n8.x4.shared.b16 {%0,%1,%2,%3}, [%4];" : "=r"(r[0]), "=r"(r[1]), "=r"(r[2]), "=r"(r[3]) : "r"(a) : "memory");
}
__device__ __forceinline__ void ldsm4t(uint32_t* r, uint32_t a) {
  asm volatile("ldmatrix.sync.aligned.m8n8.x4.trans.shared.b16 {%0,%1,%2,%3}, [%4];" : "=r"(r[0]), "=r"(r[1]), "=r"(r[2]), "=r"(r[3]) : "r"(a) : "memory");
}
__device__ __forceinline__ void stsm4(uint32_t a, uint32_t r0, uint32_t r1, uint32_t r2, uint32_t r3) {
  asm volatile("stmatrix.sync.aligned.m8n8.x4.shared.b16 [%0], {%1,%2,%3,%4};" ::"r"(a), "r"(r0), "r"(r1), "r"(r2), "r"(r3) : "memory");
}
__device__ __forceinline__ void stsm4t(uint32_t a, uint32_t r0, uint32_t r1, uint32_t r2, uint32_t r3) {
  asm volatile("stmatrix.sync.aligned.m8n8.x4.trans.shared.b16 [%0], {%1,%2,%3,%4};" ::"r"(a), "r"(r0), "r"(r1), "r"(r2), "r"(r3) : "memory");
}
__device__ __forceinline__ uint32_t movm_t(uint32_t a) { uint32_t r; asm volatile("movmatrix.sync.aligned.m8n8.trans.b16 %0, %1;" : "=r"(r) : "r"(a)); return r; }
__device__ __forceinline__ uint32_t lds32(uint32_t a) { uint32_t v; asm volatile("ld.shared.b32 %0, [%1];" : "=r"(v) : "r"(a) : "memory"); return v; }
__device__ __forceinline__ float2 lds64f(uint32_t a) { float2 v; asm volatile("ld.shared.v2.f32 {%0,%1}, [%2];" : "=f"(v.x), "=f"(v.y) : "r"(a) : "memory"); return v; }
__device__ __forceinline__ float4 lds128f(uint32_t a) { float4 v; asm volatile("ld.shared.v4.f32 {%0,%1,%2,%3}, [%4];" : "=f"(v.x), "=f"(v.y), "=f"(v.z), "=f"(v.w) : "r"(a) : "memory"); return v; }
__device__ __forceinline__ uint4 lds128(uint32_t a) { uint4 v; asm volatile("ld.shared.v4.b32 {%0,%1,%2,%3}, [%4];" : "=r"(v.x), "=r"(v.y), "=r"(v.z), "=r"(v.w) : "r"(a) : "memory"); return v; }
__device__ __forceinline__ void sts128(uint32_t a, uint4 v) { asm volatile("st.shared.v4.b32 [%0], {%1,%2,%3,%4};" ::"r"(a), "r"(v.x), "r"(v.y), "r"(v.z), "r"(v.w) : "memory"); }
__device__ __forceinline__ void sts128f(uint32_t a, float x, float y, float z, float w) { asm volatile("st.shared.v4.f32 [%0], {%1,%2,%3,%4};" ::"r"(a), "f"(x), "f"(y), "f"(z), "f"(w) : "memory"); }
__device__ __forceinline__ void sts32f(uint32_t a, float v) { asm volatile("st.shared.f32 [%0], %1;" ::"r"(a), "f"(v) : "memory"); }
__device__ __forceinline__ void sts16(uint32_t a, uint16_t v) { asm volatile("st.shared.u16 [%0], %1;" ::"r"(a), "h"(v) : "memory"); }
__device__ __forceinline__ uint32_t lds16(uint32_t a) { uint16_t v; asm volatile("ld.shared.u16 %0, [%1];" : "=h"(v) : "r"(a) : "memory"); return v; }
__device__ __forceinline__ uint32_t packbf(float lo, float hi) { uint32_t r; asm("cvt.rn.bf16x2.f32 %0, %1, %2;" : "=r"(r) : "f"(hi), "f"(lo)); return r; }
__device__ __forceinline__ float bf_lo(uint32_t v) { return __uint_as_float(v << 16); }
__device__ __forceinline__ float bf_hi(uint32_t v) { return __uint_as_float(v & 0xffff0000u); }
__device__ __forceinline__ float ex2(float x) { float r; asm("ex2.approx.ftz.f32 %0, %1;" : "=f"(r) : "f"(x)); return r; }
__device__ __forceinline__ float rsqrt_approx(float x) { float r; asm("rsqrt.approx.ftz.f32 %0, %1;" : "=f"(r) : "f"(x)); return r; }
__device__ __forceinline__ float rcp_approx(float x) { float r; asm("rcp.approx.ftz.f32 %0, %1;" : "=f"(r) : "f"(x)); return r; }
__device__ __forceinline__ void mma_bf16(float* d, const uint32_t* a, uint32_t b0, uint32_t b1) {
  asm("mma.sync.aligned.m16n8k16.row.col.f32.bf16.bf16.f32 {%0,%1,%2,%3}, {%4,%5,%6,%7}, {%8,%9}, {%0,%1,%2,%3};"
               : "+f"(d[0]), "+f"(d[1]), "+f"(d[2]), "+f"(d[3]) : "r"(a[0]), "r"(a[1]), "r"(a[2]), "r"(a[3]), "r"(b0), "r"(b1));
}
__device__ __forceinline__ void red_release(unsigned* p) { asm volatile("red.release.gpu.global.add.u32 [%0], 1;" ::"l"(p) : "memory"); }
__device__ __forceinline__ void red_relaxed(unsigned* p) { asm volatile("red.relaxed.gpu.global.add.u32 [%0], 1;" ::"l"(p) : "memory"); }
__device__ __forceinline__ unsigned ld_relaxed(const unsigned* p) { unsigned v; asm volatile("ld.relaxed.gpu.global.u32 %0, [%1];" : "=r"(v) : "l"(p) : "memory"); return v; }
__device__ __forceinline__ void spin_until(const unsigned* p, unsigned target) {
  int it = 0;
  while ((int)(ld_relaxed(p) - target) < 0) {
    if (++it > (1 << 23)) __trap();
  }
}
__device__ __forceinline__ uint4 ldcg128(const void* p) { uint4 v; asm volatile("ld.global.cg.v4.b32 {%0,%1,%2,%3}, [%4];" : "=r"(v.x), "=r"(v.y), "=r"(v.z), "=r"(v.w) : "l"(p) : "memory"); return v; }
__device__ __forceinline__ uint4 ld_tagged(const uint4* p) { uint4 v; asm volatile("ld.relaxed.gpu.global.v4.u32 {%0,%1,%2,%3}, [%4];" : "=r"(v.x), "=r"(v.y), "=r"(v.z), "=r"(v.w) : "l"(p) : "memory"); return v; }
__device__ __forceinline__ void st_tagged(uint4* p, uint32_t a, uint32_t b, uint32_t tag) { asm volatile("st.relaxed.gpu.global.v4.u32 [%0], {%1,%2,%3,%2};" ::"l"(p), "r"(a), "r"(tag), "r"(b) : "memory"); }
__device__ __forceinline__ void st_tagged3(uint4* p, uint32_t a, uint32_t b, uint32_t c, uint32_t tag) { asm volatile("st.relaxed.gpu.global.v4.u32 [%0], {%1,%2,%3,%4};" ::"l"(p), "r"(a), "r"(b), "r"(c), "r"(tag) : "memory"); }
__device__ __forceinline__ uint4 poll_tagged(const uint4* p, uint32_t tag) {
  uint4 v = ld_tagged(p);
  int it = 0;
  while (v.y != tag || v.w != tag) {
    if (++it > (1 << 22)) __trap();
    v = ld_tagged(p);
  }
  return v;
}
__device__ __forceinline__ uint32_t hadd2(uint32_t a, uint32_t b) { uint32_t r; asm("add.rn.bf16x2 %0, %1, %2;" : "=r"(r) : "r"(a), "r"(b)); return r; }
__device__ __forceinline__ uint32_t hmul2(uint32_t a, uint32_t b) { uint32_t r; asm("mul.rn.bf16x2 %0, %1, %2;" : "=r"(r) : "r"(a), "r"(b)); return r; }

template<int N,int TB> __device__ __forceinline__ void wgmma_rs(float* d, const uint32_t* a, uint64_t db, int sd);
template<int N,int TA,int TB> __device__ __forceinline__ void wgmma_ss(float* d, uint64_t da, uint64_t db, int sd);
template<> __device__ __forceinline__ void wgmma_rs<128,0>(float* d, const uint32_t* a, uint64_t db, int sd) {
  asm volatile("{\n.reg .pred p;\nsetp.ne.b32 p, %69, 0;\nwgmma.mma_async.sync.aligned.m64n128k16.f32.bf16.bf16 {%0,%1,%2,%3,%4,%5,%6,%7,%8,%9,%10,%11,%12,%13,%14,%15,%16,%17,%18,%19,%20,%21,%22,%23,%24,%25,%26,%27,%28,%29,%30,%31,%32,%33,%34,%35,%36,%37,%38,%39,%40,%41,%42,%43,%44,%45,%46,%47,%48,%49,%50,%51,%52,%53,%54,%55,%56,%57,%58,%59,%60,%61,%62,%63}, {%64,%65,%66,%67}, %68, p, 1, 1, 0;\n}\n"
   : "+f"(d[0]),"+f"(d[1]),"+f"(d[2]),"+f"(d[3]),"+f"(d[4]),"+f"(d[5]),"+f"(d[6]),"+f"(d[7]),"+f"(d[8]),"+f"(d[9]),"+f"(d[10]),"+f"(d[11]),"+f"(d[12]),"+f"(d[13]),"+f"(d[14]),"+f"(d[15]),"+f"(d[16]),"+f"(d[17]),"+f"(d[18]),"+f"(d[19]),"+f"(d[20]),"+f"(d[21]),"+f"(d[22]),"+f"(d[23]),"+f"(d[24]),"+f"(d[25]),"+f"(d[26]),"+f"(d[27]),"+f"(d[28]),"+f"(d[29]),"+f"(d[30]),"+f"(d[31]),"+f"(d[32]),"+f"(d[33]),"+f"(d[34]),"+f"(d[35]),"+f"(d[36]),"+f"(d[37]),"+f"(d[38]),"+f"(d[39]),"+f"(d[40]),"+f"(d[41]),"+f"(d[42]),"+f"(d[43]),"+f"(d[44]),"+f"(d[45]),"+f"(d[46]),"+f"(d[47]),"+f"(d[48]),"+f"(d[49]),"+f"(d[50]),"+f"(d[51]),"+f"(d[52]),"+f"(d[53]),"+f"(d[54]),"+f"(d[55]),"+f"(d[56]),"+f"(d[57]),"+f"(d[58]),"+f"(d[59]),"+f"(d[60]),"+f"(d[61]),"+f"(d[62]),"+f"(d[63])
   : "r"(a[0]), "r"(a[1]), "r"(a[2]), "r"(a[3]), "l"(db), "r"(sd));
}
template<> __device__ __forceinline__ void wgmma_rs<112,0>(float* d, const uint32_t* a, uint64_t db, int sd) {
  asm volatile("{\n.reg .pred p;\nsetp.ne.b32 p, %61, 0;\nwgmma.mma_async.sync.aligned.m64n112k16.f32.bf16.bf16 {%0,%1,%2,%3,%4,%5,%6,%7,%8,%9,%10,%11,%12,%13,%14,%15,%16,%17,%18,%19,%20,%21,%22,%23,%24,%25,%26,%27,%28,%29,%30,%31,%32,%33,%34,%35,%36,%37,%38,%39,%40,%41,%42,%43,%44,%45,%46,%47,%48,%49,%50,%51,%52,%53,%54,%55}, {%56,%57,%58,%59}, %60, p, 1, 1, 0;\n}\n"
   : "+f"(d[0]),"+f"(d[1]),"+f"(d[2]),"+f"(d[3]),"+f"(d[4]),"+f"(d[5]),"+f"(d[6]),"+f"(d[7]),"+f"(d[8]),"+f"(d[9]),"+f"(d[10]),"+f"(d[11]),"+f"(d[12]),"+f"(d[13]),"+f"(d[14]),"+f"(d[15]),"+f"(d[16]),"+f"(d[17]),"+f"(d[18]),"+f"(d[19]),"+f"(d[20]),"+f"(d[21]),"+f"(d[22]),"+f"(d[23]),"+f"(d[24]),"+f"(d[25]),"+f"(d[26]),"+f"(d[27]),"+f"(d[28]),"+f"(d[29]),"+f"(d[30]),"+f"(d[31]),"+f"(d[32]),"+f"(d[33]),"+f"(d[34]),"+f"(d[35]),"+f"(d[36]),"+f"(d[37]),"+f"(d[38]),"+f"(d[39]),"+f"(d[40]),"+f"(d[41]),"+f"(d[42]),"+f"(d[43]),"+f"(d[44]),"+f"(d[45]),"+f"(d[46]),"+f"(d[47]),"+f"(d[48]),"+f"(d[49]),"+f"(d[50]),"+f"(d[51]),"+f"(d[52]),"+f"(d[53]),"+f"(d[54]),"+f"(d[55])
   : "r"(a[0]), "r"(a[1]), "r"(a[2]), "r"(a[3]), "l"(db), "r"(sd));
}
template<> __device__ __forceinline__ void wgmma_rs<104,0>(float* d, const uint32_t* a, uint64_t db, int sd) {
  asm volatile("{\n.reg .pred p;\nsetp.ne.b32 p, %57, 0;\nwgmma.mma_async.sync.aligned.m64n104k16.f32.bf16.bf16 {%0,%1,%2,%3,%4,%5,%6,%7,%8,%9,%10,%11,%12,%13,%14,%15,%16,%17,%18,%19,%20,%21,%22,%23,%24,%25,%26,%27,%28,%29,%30,%31,%32,%33,%34,%35,%36,%37,%38,%39,%40,%41,%42,%43,%44,%45,%46,%47,%48,%49,%50,%51}, {%52,%53,%54,%55}, %56, p, 1, 1, 0;\n}\n"
   : "+f"(d[0]),"+f"(d[1]),"+f"(d[2]),"+f"(d[3]),"+f"(d[4]),"+f"(d[5]),"+f"(d[6]),"+f"(d[7]),"+f"(d[8]),"+f"(d[9]),"+f"(d[10]),"+f"(d[11]),"+f"(d[12]),"+f"(d[13]),"+f"(d[14]),"+f"(d[15]),"+f"(d[16]),"+f"(d[17]),"+f"(d[18]),"+f"(d[19]),"+f"(d[20]),"+f"(d[21]),"+f"(d[22]),"+f"(d[23]),"+f"(d[24]),"+f"(d[25]),"+f"(d[26]),"+f"(d[27]),"+f"(d[28]),"+f"(d[29]),"+f"(d[30]),"+f"(d[31]),"+f"(d[32]),"+f"(d[33]),"+f"(d[34]),"+f"(d[35]),"+f"(d[36]),"+f"(d[37]),"+f"(d[38]),"+f"(d[39]),"+f"(d[40]),"+f"(d[41]),"+f"(d[42]),"+f"(d[43]),"+f"(d[44]),"+f"(d[45]),"+f"(d[46]),"+f"(d[47]),"+f"(d[48]),"+f"(d[49]),"+f"(d[50]),"+f"(d[51])
   : "r"(a[0]), "r"(a[1]), "r"(a[2]), "r"(a[3]), "l"(db), "r"(sd));
}
template<> __device__ __forceinline__ void wgmma_rs<96,0>(float* d, const uint32_t* a, uint64_t db, int sd) {
  asm volatile("{\n.reg .pred p;\nsetp.ne.b32 p, %53, 0;\nwgmma.mma_async.sync.aligned.m64n96k16.f32.bf16.bf16 {%0,%1,%2,%3,%4,%5,%6,%7,%8,%9,%10,%11,%12,%13,%14,%15,%16,%17,%18,%19,%20,%21,%22,%23,%24,%25,%26,%27,%28,%29,%30,%31,%32,%33,%34,%35,%36,%37,%38,%39,%40,%41,%42,%43,%44,%45,%46,%47}, {%48,%49,%50,%51}, %52, p, 1, 1, 0;\n}\n"
   : "+f"(d[0]),"+f"(d[1]),"+f"(d[2]),"+f"(d[3]),"+f"(d[4]),"+f"(d[5]),"+f"(d[6]),"+f"(d[7]),"+f"(d[8]),"+f"(d[9]),"+f"(d[10]),"+f"(d[11]),"+f"(d[12]),"+f"(d[13]),"+f"(d[14]),"+f"(d[15]),"+f"(d[16]),"+f"(d[17]),"+f"(d[18]),"+f"(d[19]),"+f"(d[20]),"+f"(d[21]),"+f"(d[22]),"+f"(d[23]),"+f"(d[24]),"+f"(d[25]),"+f"(d[26]),"+f"(d[27]),"+f"(d[28]),"+f"(d[29]),"+f"(d[30]),"+f"(d[31]),"+f"(d[32]),"+f"(d[33]),"+f"(d[34]),"+f"(d[35]),"+f"(d[36]),"+f"(d[37]),"+f"(d[38]),"+f"(d[39]),"+f"(d[40]),"+f"(d[41]),"+f"(d[42]),"+f"(d[43]),"+f"(d[44]),"+f"(d[45]),"+f"(d[46]),"+f"(d[47])
   : "r"(a[0]), "r"(a[1]), "r"(a[2]), "r"(a[3]), "l"(db), "r"(sd));
}
template<> __device__ __forceinline__ void wgmma_rs<88,0>(float* d, const uint32_t* a, uint64_t db, int sd) {
  asm volatile("{\n.reg .pred p;\nsetp.ne.b32 p, %49, 0;\nwgmma.mma_async.sync.aligned.m64n88k16.f32.bf16.bf16 {%0,%1,%2,%3,%4,%5,%6,%7,%8,%9,%10,%11,%12,%13,%14,%15,%16,%17,%18,%19,%20,%21,%22,%23,%24,%25,%26,%27,%28,%29,%30,%31,%32,%33,%34,%35,%36,%37,%38,%39,%40,%41,%42,%43}, {%44,%45,%46,%47}, %48, p, 1, 1, 0;\n}\n"
   : "+f"(d[0]),"+f"(d[1]),"+f"(d[2]),"+f"(d[3]),"+f"(d[4]),"+f"(d[5]),"+f"(d[6]),"+f"(d[7]),"+f"(d[8]),"+f"(d[9]),"+f"(d[10]),"+f"(d[11]),"+f"(d[12]),"+f"(d[13]),"+f"(d[14]),"+f"(d[15]),"+f"(d[16]),"+f"(d[17]),"+f"(d[18]),"+f"(d[19]),"+f"(d[20]),"+f"(d[21]),"+f"(d[22]),"+f"(d[23]),"+f"(d[24]),"+f"(d[25]),"+f"(d[26]),"+f"(d[27]),"+f"(d[28]),"+f"(d[29]),"+f"(d[30]),"+f"(d[31]),"+f"(d[32]),"+f"(d[33]),"+f"(d[34]),"+f"(d[35]),"+f"(d[36]),"+f"(d[37]),"+f"(d[38]),"+f"(d[39]),"+f"(d[40]),"+f"(d[41]),"+f"(d[42]),"+f"(d[43])
   : "r"(a[0]), "r"(a[1]), "r"(a[2]), "r"(a[3]), "l"(db), "r"(sd));
}
template<> __device__ __forceinline__ void wgmma_rs<80,0>(float* d, const uint32_t* a, uint64_t db, int sd) {
  asm volatile("{\n.reg .pred p;\nsetp.ne.b32 p, %45, 0;\nwgmma.mma_async.sync.aligned.m64n80k16.f32.bf16.bf16 {%0,%1,%2,%3,%4,%5,%6,%7,%8,%9,%10,%11,%12,%13,%14,%15,%16,%17,%18,%19,%20,%21,%22,%23,%24,%25,%26,%27,%28,%29,%30,%31,%32,%33,%34,%35,%36,%37,%38,%39}, {%40,%41,%42,%43}, %44, p, 1, 1, 0;\n}\n"
   : "+f"(d[0]),"+f"(d[1]),"+f"(d[2]),"+f"(d[3]),"+f"(d[4]),"+f"(d[5]),"+f"(d[6]),"+f"(d[7]),"+f"(d[8]),"+f"(d[9]),"+f"(d[10]),"+f"(d[11]),"+f"(d[12]),"+f"(d[13]),"+f"(d[14]),"+f"(d[15]),"+f"(d[16]),"+f"(d[17]),"+f"(d[18]),"+f"(d[19]),"+f"(d[20]),"+f"(d[21]),"+f"(d[22]),"+f"(d[23]),"+f"(d[24]),"+f"(d[25]),"+f"(d[26]),"+f"(d[27]),"+f"(d[28]),"+f"(d[29]),"+f"(d[30]),"+f"(d[31]),"+f"(d[32]),"+f"(d[33]),"+f"(d[34]),"+f"(d[35]),"+f"(d[36]),"+f"(d[37]),"+f"(d[38]),"+f"(d[39])
   : "r"(a[0]), "r"(a[1]), "r"(a[2]), "r"(a[3]), "l"(db), "r"(sd));
}
template<> __device__ __forceinline__ void wgmma_rs<72,0>(float* d, const uint32_t* a, uint64_t db, int sd) {
  asm volatile("{\n.reg .pred p;\nsetp.ne.b32 p, %41, 0;\nwgmma.mma_async.sync.aligned.m64n72k16.f32.bf16.bf16 {%0,%1,%2,%3,%4,%5,%6,%7,%8,%9,%10,%11,%12,%13,%14,%15,%16,%17,%18,%19,%20,%21,%22,%23,%24,%25,%26,%27,%28,%29,%30,%31,%32,%33,%34,%35}, {%36,%37,%38,%39}, %40, p, 1, 1, 0;\n}\n"
   : "+f"(d[0]),"+f"(d[1]),"+f"(d[2]),"+f"(d[3]),"+f"(d[4]),"+f"(d[5]),"+f"(d[6]),"+f"(d[7]),"+f"(d[8]),"+f"(d[9]),"+f"(d[10]),"+f"(d[11]),"+f"(d[12]),"+f"(d[13]),"+f"(d[14]),"+f"(d[15]),"+f"(d[16]),"+f"(d[17]),"+f"(d[18]),"+f"(d[19]),"+f"(d[20]),"+f"(d[21]),"+f"(d[22]),"+f"(d[23]),"+f"(d[24]),"+f"(d[25]),"+f"(d[26]),"+f"(d[27]),"+f"(d[28]),"+f"(d[29]),"+f"(d[30]),"+f"(d[31]),"+f"(d[32]),"+f"(d[33]),"+f"(d[34]),"+f"(d[35])
   : "r"(a[0]), "r"(a[1]), "r"(a[2]), "r"(a[3]), "l"(db), "r"(sd));
}
template<> __device__ __forceinline__ void wgmma_rs<64,0>(float* d, const uint32_t* a, uint64_t db, int sd) {
  asm volatile("{\n.reg .pred p;\nsetp.ne.b32 p, %37, 0;\nwgmma.mma_async.sync.aligned.m64n64k16.f32.bf16.bf16 {%0,%1,%2,%3,%4,%5,%6,%7,%8,%9,%10,%11,%12,%13,%14,%15,%16,%17,%18,%19,%20,%21,%22,%23,%24,%25,%26,%27,%28,%29,%30,%31}, {%32,%33,%34,%35}, %36, p, 1, 1, 0;\n}\n"
   : "+f"(d[0]),"+f"(d[1]),"+f"(d[2]),"+f"(d[3]),"+f"(d[4]),"+f"(d[5]),"+f"(d[6]),"+f"(d[7]),"+f"(d[8]),"+f"(d[9]),"+f"(d[10]),"+f"(d[11]),"+f"(d[12]),"+f"(d[13]),"+f"(d[14]),"+f"(d[15]),"+f"(d[16]),"+f"(d[17]),"+f"(d[18]),"+f"(d[19]),"+f"(d[20]),"+f"(d[21]),"+f"(d[22]),"+f"(d[23]),"+f"(d[24]),"+f"(d[25]),"+f"(d[26]),"+f"(d[27]),"+f"(d[28]),"+f"(d[29]),"+f"(d[30]),"+f"(d[31])
   : "r"(a[0]), "r"(a[1]), "r"(a[2]), "r"(a[3]), "l"(db), "r"(sd));
}
template<> __device__ __forceinline__ void wgmma_rs<56,0>(float* d, const uint32_t* a, uint64_t db, int sd) {
  asm volatile("{\n.reg .pred p;\nsetp.ne.b32 p, %33, 0;\nwgmma.mma_async.sync.aligned.m64n56k16.f32.bf16.bf16 {%0,%1,%2,%3,%4,%5,%6,%7,%8,%9,%10,%11,%12,%13,%14,%15,%16,%17,%18,%19,%20,%21,%22,%23,%24,%25,%26,%27}, {%28,%29,%30,%31}, %32, p, 1, 1, 0;\n}\n"
   : "+f"(d[0]),"+f"(d[1]),"+f"(d[2]),"+f"(d[3]),"+f"(d[4]),"+f"(d[5]),"+f"(d[6]),"+f"(d[7]),"+f"(d[8]),"+f"(d[9]),"+f"(d[10]),"+f"(d[11]),"+f"(d[12]),"+f"(d[13]),"+f"(d[14]),"+f"(d[15]),"+f"(d[16]),"+f"(d[17]),"+f"(d[18]),"+f"(d[19]),"+f"(d[20]),"+f"(d[21]),"+f"(d[22]),"+f"(d[23]),"+f"(d[24]),"+f"(d[25]),"+f"(d[26]),"+f"(d[27])
   : "r"(a[0]), "r"(a[1]), "r"(a[2]), "r"(a[3]), "l"(db), "r"(sd));
}
template<> __device__ __forceinline__ void wgmma_rs<48,0>(float* d, const uint32_t* a, uint64_t db, int sd) {
  asm volatile("{\n.reg .pred p;\nsetp.ne.b32 p, %29, 0;\nwgmma.mma_async.sync.aligned.m64n48k16.f32.bf16.bf16 {%0,%1,%2,%3,%4,%5,%6,%7,%8,%9,%10,%11,%12,%13,%14,%15,%16,%17,%18,%19,%20,%21,%22,%23}, {%24,%25,%26,%27}, %28, p, 1, 1, 0;\n}\n"
   : "+f"(d[0]),"+f"(d[1]),"+f"(d[2]),"+f"(d[3]),"+f"(d[4]),"+f"(d[5]),"+f"(d[6]),"+f"(d[7]),"+f"(d[8]),"+f"(d[9]),"+f"(d[10]),"+f"(d[11]),"+f"(d[12]),"+f"(d[13]),"+f"(d[14]),"+f"(d[15]),"+f"(d[16]),"+f"(d[17]),"+f"(d[18]),"+f"(d[19]),"+f"(d[20]),"+f"(d[21]),"+f"(d[22]),"+f"(d[23])
   : "r"(a[0]), "r"(a[1]), "r"(a[2]), "r"(a[3]), "l"(db), "r"(sd));
}
template<> __device__ __forceinline__ void wgmma_rs<40,0>(float* d, const uint32_t* a, uint64_t db, int sd) {
  asm volatile("{\n.reg .pred p;\nsetp.ne.b32 p, %25, 0;\nwgmma.mma_async.sync.aligned.m64n40k16.f32.bf16.bf16 {%0,%1,%2,%3,%4,%5,%6,%7,%8,%9,%10,%11,%12,%13,%14,%15,%16,%17,%18,%19}, {%20,%21,%22,%23}, %24, p, 1, 1, 0;\n}\n"
   : "+f"(d[0]),"+f"(d[1]),"+f"(d[2]),"+f"(d[3]),"+f"(d[4]),"+f"(d[5]),"+f"(d[6]),"+f"(d[7]),"+f"(d[8]),"+f"(d[9]),"+f"(d[10]),"+f"(d[11]),"+f"(d[12]),"+f"(d[13]),"+f"(d[14]),"+f"(d[15]),"+f"(d[16]),"+f"(d[17]),"+f"(d[18]),"+f"(d[19])
   : "r"(a[0]), "r"(a[1]), "r"(a[2]), "r"(a[3]), "l"(db), "r"(sd));
}
template<> __device__ __forceinline__ void wgmma_rs<32,0>(float* d, const uint32_t* a, uint64_t db, int sd) {
  asm volatile("{\n.reg .pred p;\nsetp.ne.b32 p, %21, 0;\nwgmma.mma_async.sync.aligned.m64n32k16.f32.bf16.bf16 {%0,%1,%2,%3,%4,%5,%6,%7,%8,%9,%10,%11,%12,%13,%14,%15}, {%16,%17,%18,%19}, %20, p, 1, 1, 0;\n}\n"
   : "+f"(d[0]),"+f"(d[1]),"+f"(d[2]),"+f"(d[3]),"+f"(d[4]),"+f"(d[5]),"+f"(d[6]),"+f"(d[7]),"+f"(d[8]),"+f"(d[9]),"+f"(d[10]),"+f"(d[11]),"+f"(d[12]),"+f"(d[13]),"+f"(d[14]),"+f"(d[15])
   : "r"(a[0]), "r"(a[1]), "r"(a[2]), "r"(a[3]), "l"(db), "r"(sd));
}
template<> __device__ __forceinline__ void wgmma_rs<24,0>(float* d, const uint32_t* a, uint64_t db, int sd) {
  asm volatile("{\n.reg .pred p;\nsetp.ne.b32 p, %17, 0;\nwgmma.mma_async.sync.aligned.m64n24k16.f32.bf16.bf16 {%0,%1,%2,%3,%4,%5,%6,%7,%8,%9,%10,%11}, {%12,%13,%14,%15}, %16, p, 1, 1, 0;\n}\n"
   : "+f"(d[0]),"+f"(d[1]),"+f"(d[2]),"+f"(d[3]),"+f"(d[4]),"+f"(d[5]),"+f"(d[6]),"+f"(d[7]),"+f"(d[8]),"+f"(d[9]),"+f"(d[10]),"+f"(d[11])
   : "r"(a[0]), "r"(a[1]), "r"(a[2]), "r"(a[3]), "l"(db), "r"(sd));
}
template<> __device__ __forceinline__ void wgmma_rs<16,0>(float* d, const uint32_t* a, uint64_t db, int sd) {
  asm volatile("{\n.reg .pred p;\nsetp.ne.b32 p, %13, 0;\nwgmma.mma_async.sync.aligned.m64n16k16.f32.bf16.bf16 {%0,%1,%2,%3,%4,%5,%6,%7}, {%8,%9,%10,%11}, %12, p, 1, 1, 0;\n}\n"
   : "+f"(d[0]),"+f"(d[1]),"+f"(d[2]),"+f"(d[3]),"+f"(d[4]),"+f"(d[5]),"+f"(d[6]),"+f"(d[7])
   : "r"(a[0]), "r"(a[1]), "r"(a[2]), "r"(a[3]), "l"(db), "r"(sd));
}
template<> __device__ __forceinline__ void wgmma_rs<8,0>(float* d, const uint32_t* a, uint64_t db, int sd) {
  asm volatile("{\n.reg .pred p;\nsetp.ne.b32 p, %9, 0;\nwgmma.mma_async.sync.aligned.m64n8k16.f32.bf16.bf16 {%0,%1,%2,%3}, {%4,%5,%6,%7}, %8, p, 1, 1, 0;\n}\n"
   : "+f"(d[0]),"+f"(d[1]),"+f"(d[2]),"+f"(d[3])
   : "r"(a[0]), "r"(a[1]), "r"(a[2]), "r"(a[3]), "l"(db), "r"(sd));
}
template<> __device__ __forceinline__ void wgmma_rs<16,1>(float* d, const uint32_t* a, uint64_t db, int sd) {
  asm volatile("{\n.reg .pred p;\nsetp.ne.b32 p, %13, 0;\nwgmma.mma_async.sync.aligned.m64n16k16.f32.bf16.bf16 {%0,%1,%2,%3,%4,%5,%6,%7}, {%8,%9,%10,%11}, %12, p, 1, 1, 1;\n}\n"
   : "+f"(d[0]),"+f"(d[1]),"+f"(d[2]),"+f"(d[3]),"+f"(d[4]),"+f"(d[5]),"+f"(d[6]),"+f"(d[7])
   : "r"(a[0]), "r"(a[1]), "r"(a[2]), "r"(a[3]), "l"(db), "r"(sd));
}
template<> __device__ __forceinline__ void wgmma_ss<64,0,1>(float* d, uint64_t da, uint64_t db, int sd) {
  asm volatile("{\n.reg .pred p;\nsetp.ne.b32 p, %34, 0;\nwgmma.mma_async.sync.aligned.m64n64k16.f32.bf16.bf16 {%0,%1,%2,%3,%4,%5,%6,%7,%8,%9,%10,%11,%12,%13,%14,%15,%16,%17,%18,%19,%20,%21,%22,%23,%24,%25,%26,%27,%28,%29,%30,%31}, %32, %33, p, 1, 1, 0, 1;\n}\n"
   : "+f"(d[0]),"+f"(d[1]),"+f"(d[2]),"+f"(d[3]),"+f"(d[4]),"+f"(d[5]),"+f"(d[6]),"+f"(d[7]),"+f"(d[8]),"+f"(d[9]),"+f"(d[10]),"+f"(d[11]),"+f"(d[12]),"+f"(d[13]),"+f"(d[14]),"+f"(d[15]),"+f"(d[16]),"+f"(d[17]),"+f"(d[18]),"+f"(d[19]),"+f"(d[20]),"+f"(d[21]),"+f"(d[22]),"+f"(d[23]),"+f"(d[24]),"+f"(d[25]),"+f"(d[26]),"+f"(d[27]),"+f"(d[28]),"+f"(d[29]),"+f"(d[30]),"+f"(d[31])
   : "l"(da), "l"(db), "r"(sd));
}
template<> __device__ __forceinline__ void wgmma_ss<192,0,1>(float* d, uint64_t da, uint64_t db, int sd) {
  asm volatile("{\n.reg .pred p;\nsetp.ne.b32 p, %98, 0;\nwgmma.mma_async.sync.aligned.m64n192k16.f32.bf16.bf16 {%0,%1,%2,%3,%4,%5,%6,%7,%8,%9,%10,%11,%12,%13,%14,%15,%16,%17,%18,%19,%20,%21,%22,%23,%24,%25,%26,%27,%28,%29,%30,%31,%32,%33,%34,%35,%36,%37,%38,%39,%40,%41,%42,%43,%44,%45,%46,%47,%48,%49,%50,%51,%52,%53,%54,%55,%56,%57,%58,%59,%60,%61,%62,%63,%64,%65,%66,%67,%68,%69,%70,%71,%72,%73,%74,%75,%76,%77,%78,%79,%80,%81,%82,%83,%84,%85,%86,%87,%88,%89,%90,%91,%92,%93,%94,%95}, %96, %97, p, 1, 1, 0, 1;\n}\n"
   : "+f"(d[0]),"+f"(d[1]),"+f"(d[2]),"+f"(d[3]),"+f"(d[4]),"+f"(d[5]),"+f"(d[6]),"+f"(d[7]),"+f"(d[8]),"+f"(d[9]),"+f"(d[10]),"+f"(d[11]),"+f"(d[12]),"+f"(d[13]),"+f"(d[14]),"+f"(d[15]),"+f"(d[16]),"+f"(d[17]),"+f"(d[18]),"+f"(d[19]),"+f"(d[20]),"+f"(d[21]),"+f"(d[22]),"+f"(d[23]),"+f"(d[24]),"+f"(d[25]),"+f"(d[26]),"+f"(d[27]),"+f"(d[28]),"+f"(d[29]),"+f"(d[30]),"+f"(d[31]),"+f"(d[32]),"+f"(d[33]),"+f"(d[34]),"+f"(d[35]),"+f"(d[36]),"+f"(d[37]),"+f"(d[38]),"+f"(d[39]),"+f"(d[40]),"+f"(d[41]),"+f"(d[42]),"+f"(d[43]),"+f"(d[44]),"+f"(d[45]),"+f"(d[46]),"+f"(d[47]),"+f"(d[48]),"+f"(d[49]),"+f"(d[50]),"+f"(d[51]),"+f"(d[52]),"+f"(d[53]),"+f"(d[54]),"+f"(d[55]),"+f"(d[56]),"+f"(d[57]),"+f"(d[58]),"+f"(d[59]),"+f"(d[60]),"+f"(d[61]),"+f"(d[62]),"+f"(d[63]),"+f"(d[64]),"+f"(d[65]),"+f"(d[66]),"+f"(d[67]),"+f"(d[68]),"+f"(d[69]),"+f"(d[70]),"+f"(d[71]),"+f"(d[72]),"+f"(d[73]),"+f"(d[74]),"+f"(d[75]),"+f"(d[76]),"+f"(d[77]),"+f"(d[78]),"+f"(d[79]),"+f"(d[80]),"+f"(d[81]),"+f"(d[82]),"+f"(d[83]),"+f"(d[84]),"+f"(d[85]),"+f"(d[86]),"+f"(d[87]),"+f"(d[88]),"+f"(d[89]),"+f"(d[90]),"+f"(d[91]),"+f"(d[92]),"+f"(d[93]),"+f"(d[94]),"+f"(d[95])
   : "l"(da), "l"(db), "r"(sd));
}
template<> __device__ __forceinline__ void wgmma_ss<192,1,1>(float* d, uint64_t da, uint64_t db, int sd) {
  asm volatile("{\n.reg .pred p;\nsetp.ne.b32 p, %98, 0;\nwgmma.mma_async.sync.aligned.m64n192k16.f32.bf16.bf16 {%0,%1,%2,%3,%4,%5,%6,%7,%8,%9,%10,%11,%12,%13,%14,%15,%16,%17,%18,%19,%20,%21,%22,%23,%24,%25,%26,%27,%28,%29,%30,%31,%32,%33,%34,%35,%36,%37,%38,%39,%40,%41,%42,%43,%44,%45,%46,%47,%48,%49,%50,%51,%52,%53,%54,%55,%56,%57,%58,%59,%60,%61,%62,%63,%64,%65,%66,%67,%68,%69,%70,%71,%72,%73,%74,%75,%76,%77,%78,%79,%80,%81,%82,%83,%84,%85,%86,%87,%88,%89,%90,%91,%92,%93,%94,%95}, %96, %97, p, 1, 1, 1, 1;\n}\n"
   : "+f"(d[0]),"+f"(d[1]),"+f"(d[2]),"+f"(d[3]),"+f"(d[4]),"+f"(d[5]),"+f"(d[6]),"+f"(d[7]),"+f"(d[8]),"+f"(d[9]),"+f"(d[10]),"+f"(d[11]),"+f"(d[12]),"+f"(d[13]),"+f"(d[14]),"+f"(d[15]),"+f"(d[16]),"+f"(d[17]),"+f"(d[18]),"+f"(d[19]),"+f"(d[20]),"+f"(d[21]),"+f"(d[22]),"+f"(d[23]),"+f"(d[24]),"+f"(d[25]),"+f"(d[26]),"+f"(d[27]),"+f"(d[28]),"+f"(d[29]),"+f"(d[30]),"+f"(d[31]),"+f"(d[32]),"+f"(d[33]),"+f"(d[34]),"+f"(d[35]),"+f"(d[36]),"+f"(d[37]),"+f"(d[38]),"+f"(d[39]),"+f"(d[40]),"+f"(d[41]),"+f"(d[42]),"+f"(d[43]),"+f"(d[44]),"+f"(d[45]),"+f"(d[46]),"+f"(d[47]),"+f"(d[48]),"+f"(d[49]),"+f"(d[50]),"+f"(d[51]),"+f"(d[52]),"+f"(d[53]),"+f"(d[54]),"+f"(d[55]),"+f"(d[56]),"+f"(d[57]),"+f"(d[58]),"+f"(d[59]),"+f"(d[60]),"+f"(d[61]),"+f"(d[62]),"+f"(d[63]),"+f"(d[64]),"+f"(d[65]),"+f"(d[66]),"+f"(d[67]),"+f"(d[68]),"+f"(d[69]),"+f"(d[70]),"+f"(d[71]),"+f"(d[72]),"+f"(d[73]),"+f"(d[74]),"+f"(d[75]),"+f"(d[76]),"+f"(d[77]),"+f"(d[78]),"+f"(d[79]),"+f"(d[80]),"+f"(d[81]),"+f"(d[82]),"+f"(d[83]),"+f"(d[84]),"+f"(d[85]),"+f"(d[86]),"+f"(d[87]),"+f"(d[88]),"+f"(d[89]),"+f"(d[90]),"+f"(d[91]),"+f"(d[92]),"+f"(d[93]),"+f"(d[94]),"+f"(d[95])
   : "l"(da), "l"(db), "r"(sd));
}

#define HOLD 0
template <bool TR>
__device__ __forceinline__ void gemm_section(float* acc, float& mean0, float& mean1, float& rstd0, float& rstd1,
                                             uint32_t sb, int layer, int rb, int hg, int wg, int w, int lane) {
  const uint32_t bar = sb + SM_BAR;
  const int g = lane >> 2, t = lane & 3;
  const bool leader = (w == 0) && (lane == 0);
  const int row0 = 64 * wg + 16 * w;
  auto issue = [&](int c, int slot) {
    mbar_wait(bar + 8 * (B_XF + c), layer);
    mbar_wait(bar + 8 * (B_KVF + c), layer);
    const uint64_t da = mkdesc(sb + SM_X + c * 16384 + wg * 8192, TR ? 8192 : 16, 1024, 1);
    const uint64_t db = mkdesc(sb + SM_W + slot * 24576, 8192, 1024, 1);
    wg_fence();
#pragma unroll
    for (int ks = 0; ks < 4; ks++) wgmma_ss<192, TR ? 1 : 0, 1>(acc, da + (TR ? ks * 128 : ks * 2), db + ks * 128, (c | ks) != 0);
    wg_commit();
  };
  auto step = [&](int c, int slot) {
    issue(c, slot);
    wg_wait<1>();
    if (leader) mbar_arrive(bar + 8 * (B_KVE + c - 1));
  };
  issue(0, 0);
  if (threadIdx.x == 0) TS(2 + layer * 20 + 0);
  step(1, 1); step(2, 2); step(3, 0);
  issue(4, 1);
  mbar_wait(bar + 8 * B_EP, 0);
  const uint32_t tag = 2 * lds32(sb + SM_EP) + layer + 1;
  {
    mbar_wait(bar + 8 * (B_XF + hg), layer);
    uint32_t A[16];
    const uint32_t xb = sb + SM_X + hg * 16384 + wg * 8192;
#pragma unroll
    for (int ks = 0; ks < 4; ks++) {
      if (!TR) {
        const int row = 16 * w + (lane & 15), kc = 2 * ks + (lane >> 4);
        ldsm4(&A[4 * ks], xb + row * 128 + ((kc ^ (row & 7)) << 4));
      } else {
        const int k = 16 * ks + (lane & 7) + 8 * (lane >> 4), pc = 2 * w + ((lane >> 3) & 1);
        ldsm4t(&A[4 * ks], xb + k * 128 + ((pc ^ (k & 7)) << 4));
      }
    }
    float s0 = 0.f, q0 = 0.f, s1 = 0.f, q1 = 0.f;
#pragma unroll
    for (int i = 0; i < 16; i += 2) {
      const float a = bf_lo(A[i]), b = bf_hi(A[i]), c_ = bf_lo(A[i + 1]), d = bf_hi(A[i + 1]);
      s0 += a + b; q0 = fmaf(a, a, q0); q0 = fmaf(b, b, q0);
      s1 += c_ + d; q1 = fmaf(c_, c_, q1); q1 = fmaf(d, d, q1);
    }
#pragma unroll
    for (int o = 1; o <= 2; o <<= 1) {
      s0 += __shfl_xor_sync(~0u, s0, o); q0 += __shfl_xor_sync(~0u, q0, o);
      s1 += __shfl_xor_sync(~0u, s1, o); q1 += __shfl_xor_sync(~0u, q1, o);
    }
    if (t < 2)
      st_tagged(&g_part[(rb * 8 + hg) * 128 + row0 + g + 8 * t], __float_as_uint(t ? s1 : s0), __float_as_uint(t ? q1 : q0), tag);
  }
  wg_wait<1>();
  if (leader) mbar_arrive(bar + 8 * (B_KVE + 3));
  step(5, 2);
  issue(6, 0);
  wg_wait<1>();
  const uint4* psrc = &g_part[(rb * 8 + 2 * t) * 128 + row0 + g];
  uint4 a0 = ld_tagged(psrc), a1 = ld_tagged(psrc + 8), b0 = ld_tagged(psrc + 128), b1 = ld_tagged(psrc + 136);
  if (wg == 0) bar_sync(5, 256);
  issue(7, 1);
  if (wg == 1) bar_arrive(5, 256);
  int it = 0;
  while (!__all_sync(~0u, a0.y == tag && a0.w == tag && a1.y == tag && a1.w == tag && b0.y == tag && b0.w == tag && b1.y == tag && b1.w == tag) &&
         ++it < (1 << 20)) {
    a0 = ld_tagged(psrc); a1 = ld_tagged(psrc + 8); b0 = ld_tagged(psrc + 128); b1 = ld_tagged(psrc + 136);
  }
  float s0 = __uint_as_float(a0.x) + __uint_as_float(b0.x), q0 = __uint_as_float(a0.z) + __uint_as_float(b0.z);
  float s1 = __uint_as_float(a1.x) + __uint_as_float(b1.x), q1 = __uint_as_float(a1.z) + __uint_as_float(b1.z);
#pragma unroll
  for (int o = 1; o <= 2; o <<= 1) {
    s0 += __shfl_xor_sync(~0u, s0, o); q0 += __shfl_xor_sync(~0u, q0, o);
    s1 += __shfl_xor_sync(~0u, s1, o); q1 += __shfl_xor_sync(~0u, q1, o);
  }
  mean0 = s0 * (1.f / DM); mean1 = s1 * (1.f / DM);
  rstd0 = rsqrt_approx(fmaxf(q0 * (1.f / DM) - mean0 * mean0, 0.f) + 1e-5f);
  rstd1 = rsqrt_approx(fmaxf(q1 * (1.f / DM) - mean1 * mean1, 0.f) + 1e-5f);
  mbar_wait(bar + 8 * B_CSF, 0);
  wg_wait<0>();
}

__device__ __forceinline__ void attn_phase(const Params& p, uint32_t sb, int layer, int rb, int hg, int wg, int w) {
  const int lane = opaque_tid() & 31;
  const int g = lane >> 2, t = lane & 3;
  const uint32_t bar = sb + SM_BAR;
  const int row0 = 64 * wg + 16 * w;
  const bool leader = (w == 0) && (lane == 0);
  float acc[96];
  float2 cs[24];
  float mean0, mean1, rstd0, rstd1;
  if (layer) gemm_section<true>(acc, mean0, mean1, rstd0, rstd1, sb, layer, rb, hg, wg, w, lane);
  else gemm_section<false>(acc, mean0, mean1, rstd0, rstd1, sb, layer, rb, hg, wg, w, lane);
  const uint32_t tag = 2 * lds32(sb + SM_EP) + layer + 1;
  if (threadIdx.x == 0) TS(2 + layer * 20 + 1);
  if (leader) mbar_arrive(bar + 8 * B_QDONE);
#pragma unroll
  for (int j = 8; j < 24; j++) cs[j] = lds64f(sb + SM_CS + 4 * (8 * j + 2 * t));

  uint32_t kb[4][8], vb[4][8], qa[4][4];
  {
    const float nm0 = -mean0 * rstd0, nm1 = -mean1 * rstd1;
    const int st_row = row0 + (lane & 7) + 8 * ((lane >> 3) & 1);
    const uint32_t st_base = sb + SM_KVX + st_row * 256;
    const bool sender = (wg == 1 && w == 3 && rb < 15);
    uint4* halo = &g_halo[(rb * 8 + hg) * 384 + lane];
    if (wg == 0 && w == 3) bar_sync(6, 64);
    uint32_t r[4][2][4];
#pragma unroll
    for (int h = 0; h < 4; h++) {
#pragma unroll
      for (int kv = 0; kv < 2; kv++) {
#pragma unroll
        for (int dh = 0; dh < 2; dh++) {
          const int j = 8 + kv * 8 + 2 * h + dh;
          const float2 c2 = cs[j];
          const float v0 = fmaf(acc[4 * j + 0], rstd0, nm0 * c2.x), v1 = fmaf(acc[4 * j + 1], rstd0, nm0 * c2.y);
          const float v2 = fmaf(acc[4 * j + 2], rstd1, nm1 * c2.x), v3 = fmaf(acc[4 * j + 3], rstd1, nm1 * c2.y);
          r[h][kv][2 * dh] = packbf(v0, v1);
          r[h][kv][2 * dh + 1] = packbf(v2, v3);
        }
      }
      if (sender) {
        st_tagged3(halo + (3 * h) * 32, r[h][0][0], r[h][0][1], r[h][0][2], tag);
        st_tagged3(halo + (3 * h + 1) * 32, r[h][0][3], r[h][1][0], r[h][1][1], tag);
        st_tagged3(halo + (3 * h + 2) * 32, r[h][1][2], r[h][1][3], 0u, tag);
      }
    }
    if (wg == 1 && w == 3) bar_arrive(6, 64);
    if (layer == 1 && threadIdx.x == 224) TS(47);
#pragma unroll
    for (int j = 0; j < 8; j++) cs[j] = lds64f(sb + SM_CS + 4 * (8 * j + 2 * t));
    mbar_wait(bar + 8 * B_QDONE, layer);
#pragma unroll
    for (int h = 0; h < 4; h++) {
#pragma unroll
      for (int kv = 0; kv < 2; kv++) {
        const int chunk = 4 * h + 2 * kv + (lane >> 4);
        stsm4(st_base + (((chunk & 8) | ((chunk ^ st_row) & 7)) << 4), r[h][kv][0], r[h][kv][1], r[h][kv][2], r[h][kv][3]);
      }
      kb[h][4] = r[h][0][0]; kb[h][5] = r[h][0][2]; kb[h][6] = r[h][0][1]; kb[h][7] = r[h][0][3];
      vb[h][4] = movm_t(r[h][1][0]); vb[h][5] = movm_t(r[h][1][1]); vb[h][6] = movm_t(r[h][1][2]); vb[h][7] = movm_t(r[h][1][3]);
    }
    if (layer == 1 && threadIdx.x == 0) TS(45);
#pragma unroll
    for (int h = 0; h < 4; h++) {
#pragma unroll
      for (int dh = 0; dh < 2; dh++) {
        const int j = 2 * h + dh;
        const float2 c2 = cs[j];
        qa[h][2 * dh] = packbf(fmaf(-mean0, c2.x, acc[4 * j + 0]), fmaf(-mean0, c2.y, acc[4 * j + 1]));
        qa[h][2 * dh + 1] = packbf(fmaf(-mean1, c2.x, acc[4 * j + 2]), fmaf(-mean1, c2.y, acc[4 * j + 3]));
      }
    }
  }
  bar_sync(1, 256);
  if (threadIdx.x == 0) TS(2 + layer * 20 + 2);
  {
    const uint32_t own_base = sb + SM_KVX + row0 * 256;
    const int mi = lane >> 3;
    const int r = 8 * (mi >> 1) + (lane & 7), r2 = 8 * (mi & 1) + (lane & 7);
    if (row0 != 0) {
#pragma unroll
      for (int h = 0; h < 4; h++) {
        const int ch = 4 * h + (mi & 1), ch2 = 4 * h + 2 + (mi >> 1);
        ldsm4(&kb[h][0], own_base - 16 * 256 + r * 256 + (((ch & 8) | ((ch ^ r) & 7)) << 4));
        ldsm4t(&vb[h][0], own_base - 16 * 256 + r2 * 256 + (((ch2 & 8) | ((ch2 ^ r2) & 7)) << 4));
      }
    } else if (rb > 0) {
      const uint4* src = &g_halo[((rb - 1) * 8 + hg) * 384 + lane];
      uint4 hv[12];
      int it = 0;
      bool ok;
      do {
        ok = true;
#pragma unroll
        for (int i = 0; i < 12; i++) hv[i] = ld_tagged(src + i * 32);
#pragma unroll
        for (int i = 0; i < 12; i++) ok = ok && hv[i].w == tag;
      } while (!__all_sync(~0u, ok) && ++it < (1 << 20));
      if (lane == 0) mbar_arrive(bar + 8 * B_HF);
#pragma unroll
      for (int h = 0; h < 4; h++) {
        kb[h][0] = hv[3 * h].x; kb[h][1] = hv[3 * h].z; kb[h][2] = hv[3 * h].y; kb[h][3] = hv[3 * h + 1].x;
        vb[h][0] = movm_t(hv[3 * h + 1].y); vb[h][1] = movm_t(hv[3 * h + 1].z);
        vb[h][2] = movm_t(hv[3 * h + 2].x); vb[h][3] = movm_t(hv[3 * h + 2].y);
      }
    } else {
#pragma unroll
      for (int h = 0; h < 4; h++)
#pragma unroll
        for (int k = 0; k < 4; k++) kb[h][k] = vb[h][k] = 0u;
    }
    if (threadIdx.x == 0) TS(2 + layer * 20 + 4);
  }

  const bool first = (rb == 0 && wg == 0 && w == 0);
  const int e = t - (g >> 1);
  const bool par = g & 1, epos = e >= 1;
  const uint32_t pmask = par ? 0xffff0000u : 0x0000ffffu;
  const uint32_t mB0 = epos ? pmask : 0u, mB1 = epos ? 0u : pmask;
  const float cl2 = 0.25f * 1.4426950408889634f;
  const float sc0 = rstd0 * cl2, sc1 = rstd1 * cl2;
  const float NEG = -INFINITY;
  float vA0[4], vB0[4], vA1[4], vB1[4];
#pragma unroll
  for (int h = 0; h < 4; h++) {
    float S[4][4];
#pragma unroll
    for (int j = 0; j < 4; j++) {
      S[j][0] = S[j][1] = S[j][2] = S[j][3] = 0.f;
      mma_bf16(S[j], qa[h], kb[h][2 * j], kb[h][2 * j + 1]);
    }
    vA0[h] = par ? S[1][1] : S[1][0];
    vB0[h] = epos ? (par ? S[0][1] : S[0][0]) : (par ? S[2][1] : S[2][0]);
    vA1[h] = par ? S[2][3] : S[2][2];
    vB1[h] = epos ? (par ? S[1][3] : S[1][2]) : (par ? S[3][3] : S[3][2]);
    if (first) { vA0[h] = NEG; if (epos) { vB0[h] = NEG; vB1[h] = NEG; } }
  }
  float m0[4], m1[4];
#pragma unroll
  for (int h = 0; h < 4; h++) { m0[h] = fmaxf(vA0[h], vB0[h]); m1[h] = fmaxf(vA1[h], vB1[h]); }
#pragma unroll
  for (int o = 1; o <= 2; o <<= 1) {
#pragma unroll
    for (int h = 0; h < 4; h++) {
      m0[h] = fmaxf(m0[h], __shfl_xor_sync(~0u, m0[h], o));
      m1[h] = fmaxf(m1[h], __shfl_xor_sync(~0u, m1[h], o));
    }
  }
  float O0[4][4], O1[4][4], Z[4][4];
#pragma unroll
  for (int h = 0; h < 4; h++) {
    const float mm0 = -m0[h] * sc0, mm1 = -m1[h] * sc1;
    const float pA0 = ex2(fmaf(vA0[h], sc0, mm0)), pB0 = ex2(fmaf(vB0[h], sc0, mm0));
    const float pA1 = ex2(fmaf(vA1[h], sc1, mm1)), pB1 = ex2(fmaf(vB1[h], sc1, mm1));
    const uint32_t hA0 = packbf(pA0, pA0), hB0 = packbf(pB0, pB0), hA1 = packbf(pA1, pA1), hB1 = packbf(pB1, pB1);
    const uint32_t P0[4] = {hB0 & mB0, 0u, hA0 & pmask, hB1 & mB0};
    const uint32_t P1[4] = {hB0 & mB1, hA1 & pmask, 0u, hB1 & mB1};
#pragma unroll
    for (int k = 0; k < 4; k++) O0[h][k] = O1[h][k] = Z[h][k] = 0.f;
    mma_bf16(O0[h], P0, vb[h][0], vb[h][1]); mma_bf16(O1[h], P0, vb[h][2], vb[h][3]); mma_bf16(Z[h], P0, 0x3f803f80u, 0x3f803f80u);
    mma_bf16(O0[h], P1, vb[h][4], vb[h][5]); mma_bf16(O1[h], P1, vb[h][6], vb[h][7]); mma_bf16(Z[h], P1, 0x3f803f80u, 0x3f803f80u);
  }
  const uint32_t ob = sb + SM_OST + wg * 8192;
  const int o_row = 16 * w + (lane & 7) + 8 * ((lane >> 3) & 1);
#pragma unroll
  for (int h = 0; h < 4; h++) {
    const float i0 = rcp_approx(Z[h][0]), i1 = rcp_approx(Z[h][2]);
    const int ch = 2 * h + (lane >> 4);
    stsm4(ob + o_row * 128 + ((ch ^ (o_row & 7)) << 4), packbf(O0[h][0] * i0, O0[h][1] * i0), packbf(O0[h][2] * i1, O0[h][3] * i1),
          packbf(O1[h][0] * i0, O1[h][1] * i0), packbf(O1[h][2] * i1, O1[h][3] * i1));
  }
  if (threadIdx.x == 0) TS(2 + layer * 20 + 5);
  fence_async_smem();
  bar_sync(2 + wg, 128);
  if (w == 0 && elect_one()) {
    tma_st(&p.mapO, hg * 64, rb * 128 + wg * 64, ob);
    bulk_commit();
    mbar_arrive(bar + 8 * B_AD);
    bulk_wait_all();
    red_relaxed(&g_cnt[(C_O + rb) * 32]);
    mbar_arrive(bar + 8 * B_OST);
    if (threadIdx.x == 0) TS(2 + layer * 20 + 6);
  }
}

__device__ __forceinline__ void proj_phase(const Params& p, uint32_t sb, int layer, int rb, int q, int wg, int w) {
  const int lane = opaque_tid() & 31;
  const bool TR = layer != 0;
  const int t = lane & 3;
  const uint32_t bar = sb + SM_BAR;
  const uint32_t rbx = sb + SM_R + wg * 8192;
  uint32_t res[16];
  mbar_wait(bar + 8 * B_RF, layer);
  if (threadIdx.x == 0) TS(2 + layer * 20 + 7);
  if (!TR) {
#pragma unroll
    for (int j = 0; j < 8; j += 2) {
      const int mi = lane >> 3;
      const int row = 16 * w + (lane & 7) + 8 * (mi & 1), ch = j + (mi >> 1);
      ldsm4(&res[2 * j], rbx + row * 128 + ((ch ^ (row & 7)) << 4));
    }
  } else {
#pragma unroll
    for (int j = 0; j < 8; j += 2) {
      const int mi = lane >> 3;
      const int line = 8 * (j + (mi >> 1)) + (lane & 7), pc = 2 * w + (mi & 1);
      ldsm4t(&res[2 * j], rbx + line * 128 + ((pc ^ (line & 7)) << 4));
    }
  }
  bar_sync(2 + wg, 128);
  float acc[32];
#pragma unroll 1
  for (int c = 0; c < 8; c++) {
    if ((c & 1) == 0) mbar_wait(bar + 8 * (B_WOF + (c >> 1)), layer);
    mbar_wait(bar + 8 * (B_OF + c), layer);
    if (c == 0 && threadIdx.x == 0) TS(2 + layer * 20 + 8);
    const uint64_t da = mkdesc(sb + (c < 4 ? SM_X + 65536 + c * 16384 : SM_W + (c - 4) * 16384) + wg * 8192, 16, 1024, 1);
    const uint64_t db = mkdesc(sb + SM_X + c * 8192, 8192, 1024, 1);
    wg_fence();
#pragma unroll
    for (int ks = 0; ks < 4; ks++) wgmma_ss<64, 0, 1>(acc, da + ks * 2, db + ks * 128, (c | ks) != 0);
    wg_commit();
  }
  wg_wait<0>();
  if (threadIdx.x == 0) TS(2 + layer * 20 + 9);
  if (lane == 0 && w == 0) mbar_arrive(bar + 8 * B_PDONE);
  float s0 = 0.f, q0 = 0.f, s1 = 0.f, q1 = 0.f;
  uint32_t o[16];
#pragma unroll
  for (int j = 0; j < 8; j++) {
    const uint32_t r0 = res[2 * j], r1 = res[2 * j + 1];
    o[2 * j] = packbf(acc[4 * j] + bf_lo(r0), acc[4 * j + 1] + bf_hi(r0));
    o[2 * j + 1] = packbf(acc[4 * j + 2] + bf_lo(r1), acc[4 * j + 3] + bf_hi(r1));
    const float a = bf_lo(o[2 * j]), b = bf_hi(o[2 * j]), c = bf_lo(o[2 * j + 1]), d = bf_hi(o[2 * j + 1]);
    s0 += a + b; q0 = fmaf(a, a, q0); q0 = fmaf(b, b, q0);
    s1 += c + d; q1 = fmaf(c, c, q1); q1 = fmaf(d, d, q1);
  }
#pragma unroll
  for (int j = 0; j < 8; j += 2) {
    const int mi = lane >> 3;
    const int line = 8 * (j + (mi >> 1)) + (lane & 7), pc = 2 * w + (mi & 1);
    stsm4t(rbx + line * 128 + ((pc ^ (line & 7)) << 4), o[2 * j], o[2 * j + 1], o[2 * j + 2], o[2 * j + 3]);
  }
#pragma unroll
  for (int o2 = 1; o2 <= 2; o2 <<= 1) {
    s0 += __shfl_xor_sync(~0u, s0, o2); q0 += __shfl_xor_sync(~0u, q0, o2);
    s1 += __shfl_xor_sync(~0u, s1, o2); q1 += __shfl_xor_sync(~0u, q1, o2);
  }
  const uint32_t stg = sb + SM_HALO + wg * 512;
  {
    const int row = 16 * w + (lane >> 2) + 8 * (t >> 1);
    const float v = (t == 0) ? s0 : (t == 1) ? q0 : (t == 2) ? s1 : q1;
    sts32f(stg + 4 * (((((row & 7) >> 1) * 8 + (row >> 3)) << 2) + (row & 1) * 2 + (t & 1)), v);
  }
  fence_async_smem();
  bar_sync(2 + wg, 128);
  if (w == 0 && elect_one()) {
    mbar_wait(bar + 8 * B_ZF, 0);
    tma_st(&p.mapXT, rb * 128 + wg * 64, (2 * layer) * DM + q * 64, rbx);
    bulk_red_add_f32(g_stats + layer * LSEQ * 2 + (rb * 2 + wg) * 128, stg, 512);
    bulk_commit();
    bulk_wait_all();
    red_relaxed(&g_cnt[(layer ? C_G2 : C_G0) * 32]);
    if (threadIdx.x == 0) TS(2 + layer * 20 + 10);
  }
}

template <int B> __device__ __forceinline__ void conv_load(uint32_t* A, uint32_t pe) {
#pragma unroll
  for (int i = 0; i < (B == 0 ? 5 : 4); i++) {
    const int m = B + 4 * i;
    A[4 * i + 2] = lds32(pe + 4 * (64 * m - 8));
    A[4 * i + 0] = lds32(pe + 4 * (64 * m));
    A[4 * i + 1] = lds32(pe + 4 * (64 * m + 8));
    asm volatile("mov.b32 %0, %1;" : "=r"(A[4 * i + 3]) : "r"(A[4 * i + 0]));
  }
}
template <int B> __device__ __forceinline__ void conv_mma(float* acc, const uint32_t* A, uint64_t d) {
  constexpr int R = (B >= 2) ? 8 : 0;
  wgmma_rs<128, 0>(acc, A + 0, d + (uint64_t)(4 * (B + 0)), B != 0);
  wgmma_rs<112 - R, 0>(acc, A + 4, d + (uint64_t)(4 * (B + 4)), 1);
  wgmma_rs<96 - R, 0>(acc, A + 8, d + (uint64_t)(4 * (B + 8)), 1);
  wgmma_rs<80 - R, 0>(acc, A + 12, d + (uint64_t)(4 * (B + 12)), 1);
  if (B == 0) wgmma_rs<64, 0>(acc, A + 16, d + (uint64_t)(4 * 16), 1);
}
__device__ __forceinline__ void far_mma(float* FE, const uint32_t* AE, uint64_t de, float* FO, const uint32_t* AO, uint64_t d_o) {
#pragma unroll
  for (int k = 0; k < 4; k++) {
    wgmma_rs<16, 1>(FE, AE + 4 * k, de + 32 * k, k != 0);
    wgmma_rs<16, 1>(FO, AO + 4 * k, d_o + 32 * k, k != 0);
  }
}
__device__ __forceinline__ void far_load(uint32_t* a, uint32_t wt) {
  uint32_t e[9];
#pragma unroll
  for (int k = 0; k < 9; k++) e[k] = lds32(wt - 32 * k);
#pragma unroll
  for (int s = 0; s < 4; s++) {
    asm volatile("mov.b32 %0, %1;" : "=r"(a[4 * s + 0]) : "r"(e[2 * s + 1]));
    asm volatile("mov.b32 %0, %1;" : "=r"(a[4 * s + 1]) : "r"(e[2 * s]));
    asm volatile("mov.b32 %0, %1;" : "=r"(a[4 * s + 2]) : "r"(e[2 * s + 2]));
    asm volatile("mov.b32 %0, %1;" : "=r"(a[4 * s + 3]) : "r"(e[2 * s + 1]));
  }
}
__device__ __forceinline__ void conv_sums(uint32_t sb, int lc, int ht) {
  const int m = ht - 1;
  uint4 v[2][3];
#pragma unroll
  for (int c = 0; c < 2; c++)
#pragma unroll
    for (int k = 0; k < 3; k++) {
      const int mm = m - 1 + k;
      v[c][k] = lds128(sb + cv_u(lc + c) + (mm >= 0 ? (mm & 1) * CV_UH + (127 - (mm >> 1)) * 16 : 128 * 16));
    }
  const int ce = m + 2, co = m + 1;
#pragma unroll
  for (int c = 0; c < 2; c++) {
    const uint32_t x[8] = {v[c][0].z, v[c][0].w, v[c][1].x, v[c][1].y, v[c][1].z, v[c][1].w, v[c][2].x, v[c][2].y};
    float pv[16];
#pragma unroll
    for (int k = 0; k < 8; k++) { pv[2 * k] = bf_lo(x[k]); pv[2 * k + 1] = bf_hi(x[k]); }
    float t2[15], t4[13], s9[8], s7[8];
#pragma unroll
    for (int i = 0; i < 15; i++) t2[i] = pv[i] + pv[i + 1];
#pragma unroll
    for (int i = 0; i < 13; i++) t4[i] = t2[i] + t2[i + 2];
#pragma unroll
    for (int i = 0; i < 8; i++) {
      s9[i] = (t4[i] + t4[i + 4]) + pv[i + 8];
      s7[i] = (t4[i + 1] + t2[i + 5]) + pv[i + 7];
    }
    const uint4 e4 = make_uint4(packbf(s9[0], s9[1]), packbf(s9[2], s9[3]), packbf(s9[4], s9[5]), packbf(s9[6], s9[7]));
    if (ce < 128) sts128(sb + cv_se(lc + c) + (ce >> 1) * 32 + (((ce & 1) ^ ((ce >> 3) & 1)) << 4), e4);
    else sts128(sb + cv_se(lc + c), make_uint4(0, 0, 0, 0));
    sts128(sb + cv_so(lc + c) + (co >> 1) * 32 + (((co & 1) ^ ((co >> 3) & 1)) << 4),
           make_uint4(packbf(s7[0], s7[1]), packbf(s7[2], s7[3]), packbf(s7[4], s7[5]), packbf(s7[6], s7[7])));
  }
}

template <bool BATCH>
__device__ __forceinline__ void conv_epi(uint32_t sb, int ch, int c0, uint32_t dv) {
  if constexpr (!BATCH) {
#pragma unroll
    for (int u = 0; u < 2; u++) {
      const int c = c0 + 128 * u;
      const uint32_t pb = sb + cv_pb(ch) + (c ^ ((c >> 3) & 1)) * 16;
      uint4 v0 = lds128(pb);
      const uint4 v1 = lds128(pb + CV_PBW), v2 = lds128(pb + 2 * CV_PBW), v3 = lds128(pb + 3 * CV_PBW);
      if (u == 1) {
        const uint4 f = lds128(sb + cv_pf(ch) + c0 * 16);
        v0.x = hadd2(v0.x, f.x); v0.y = hadd2(v0.y, f.y); v0.z = hadd2(v0.z, f.z); v0.w = hadd2(v0.w, f.w);
      }
      const uint4 xr = lds128(sb + SM_R + ch * 4096 + c * 16);
      const uint4 ur = lds128(sb + cv_u(ch) + (c & 1) * CV_UH + (127 - (c >> 1)) * 16);
      uint4 o;
      o.x = hadd2(xr.x, hadd2(hadd2(hadd2(v0.x, v1.x), hadd2(v2.x, v3.x)), hmul2(ur.x, dv)));
      o.y = hadd2(xr.y, hadd2(hadd2(hadd2(v0.y, v1.y), hadd2(v2.y, v3.y)), hmul2(ur.y, dv)));
      o.z = hadd2(xr.z, hadd2(hadd2(hadd2(v0.z, v1.z), hadd2(v2.z, v3.z)), hmul2(ur.z, dv)));
      o.w = hadd2(xr.w, hadd2(hadd2(hadd2(v0.w, v1.w), hadd2(v2.w, v3.w)), hmul2(ur.w, dv)));
      sts128(sb + SM_R + ch * 4096 + c * 16, o);
    }
  } else {
  uint4 v[2][4], xr[2], ur[2];
#pragma unroll
  for (int u = 0; u < 2; u++) {
    const int c = c0 + 128 * u;
    const uint32_t pb = sb + cv_pb(ch) + (c ^ ((c >> 3) & 1)) * 16;
#pragma unroll
    for (int k = 0; k < 4; k++) v[u][k] = lds128(pb + k * CV_PBW);
    xr[u] = lds128(sb + SM_R + ch * 4096 + c * 16);
    ur[u] = lds128(sb + cv_u(ch) + (c & 1) * CV_UH + (127 - (c >> 1)) * 16);
  }
  {
    const uint4 f = lds128(sb + cv_pf(ch) + c0 * 16);
    v[1][0].x = hadd2(v[1][0].x, f.x); v[1][0].y = hadd2(v[1][0].y, f.y); v[1][0].z = hadd2(v[1][0].z, f.z); v[1][0].w = hadd2(v[1][0].w, f.w);
  }
#pragma unroll
  for (int u = 0; u < 2; u++) {
    uint4 o;
    o.x = hadd2(xr[u].x, hadd2(hadd2(hadd2(v[u][0].x, v[u][1].x), hadd2(v[u][2].x, v[u][3].x)), hmul2(ur[u].x, dv)));
    o.y = hadd2(xr[u].y, hadd2(hadd2(hadd2(v[u][0].y, v[u][1].y), hadd2(v[u][2].y, v[u][3].y)), hmul2(ur[u].y, dv)));
    o.z = hadd2(xr[u].z, hadd2(hadd2(hadd2(v[u][0].z, v[u][1].z), hadd2(v[u][2].z, v[u][3].z)), hmul2(ur[u].z, dv)));
    o.w = hadd2(xr[u].w, hadd2(hadd2(hadd2(v[u][0].w, v[u][1].w), hadd2(v[u][2].w, v[u][3].w)), hmul2(ur[u].w, dv)));
    sts128(sb + SM_R + ch * 4096 + (c0 + 128 * u) * 16, o);
  }
  }
}
__device__ __forceinline__ void conv_publish(uint32_t sb, int layer, int cta, int ch, int nch) {
  bf16* xout = g_xT + (size_t)(2 * layer + 1) * DM * LSEQ + (size_t)cv_chan(cta, ch) * LSEQ;
  bulk_st(xout, sb + SM_R + ch * 4096, 4096 * nch);
  bulk_commit();
  bulk_wait_all();
  red_relaxed(&g_cnt[layer ? (C_F + (ch >> 1) * 4 + (cta >> 5)) * 32 : C_G1A * 32 + (ch >> 1)]);
}

struct PrepIn { uint4 xr[2], st[4]; };
__device__ __forceinline__ PrepIn conv_prep_load(int layer, int cta, int c, int cl) {
  const bf16* xin = g_xT + (size_t)(2 * layer) * DM * LSEQ;
  PrepIn in;
#pragma unroll
  for (int i = 0; i < 2; i++) in.xr[i] = ldcg128(xin + (size_t)cv_chan(cta, cl + i) * LSEQ + c * 8);
#pragma unroll
  for (int i = 0; i < 4; i++) in.st[i] = ldcg128(g_stats + layer * LSEQ * 2 + ((c >> 3) * 4 + i) * 32 + (c & 7) * 4);
  return in;
}
__device__ __forceinline__ void conv_prep_finish(uint32_t sb, const PrepIn& in, int c, int cl) {
  float mean[8], rstd[8];
#pragma unroll
  for (int i = 0; i < 4; i++) {
    const float m0 = __uint_as_float(in.st[i].x) * (1.f / DM), m1 = __uint_as_float(in.st[i].z) * (1.f / DM);
    mean[2 * i] = m0; mean[2 * i + 1] = m1;
    rstd[2 * i] = rsqrt_approx(fmaxf(__uint_as_float(in.st[i].y) * (1.f / DM) - m0 * m0, 0.f) + 1e-5f);
    rstd[2 * i + 1] = rsqrt_approx(fmaxf(__uint_as_float(in.st[i].w) * (1.f / DM) - m1 * m1, 0.f) + 1e-5f);
  }
  const int a = c >> 1, h = c & 1;
#pragma unroll
  for (int i = 0; i < 2; i++) {
    const uint32_t x[4] = {in.xr[i].x, in.xr[i].y, in.xr[i].z, in.xr[i].w};
    uint32_t u[4];
#pragma unroll
    for (int k = 0; k < 4; k++)
      u[k] = packbf((bf_lo(x[k]) - mean[2 * k]) * rstd[2 * k], (bf_hi(x[k]) - mean[2 * k + 1]) * rstd[2 * k + 1]);
    sts128(sb + cv_u(cl + i) + h * CV_UH + (127 - a) * 16, make_uint4(u[0], u[1], u[2], u[3]));
    sts128(sb + SM_R + (cl + i) * 4096 + c * 16, in.xr[i]);
  }
}

__device__ __forceinline__ void conv_phase(const Params& p, uint32_t sb, int layer, int cta) {
  const int tid = opaque_tid();
  const int wg = __shfl_sync(~0u, tid >> 7, 0), w = __shfl_sync(~0u, (tid >> 5) & 3, 0);
  const uint32_t bar = sb + SM_BAR;
  const uint32_t dv = (uint32_t)__bfloat16_as_ushort(p.dskip[cv_chan(cta, 2 + wg)]) * 0x10001u;
  mbar_wait(bar + 8 * B_GB, layer);
  if (threadIdx.x == 0) TS(2 + layer * 20 + 11);
  {
    const PrepIn in = conv_prep_load(layer, cta, tid, 0);
    mbar_wait(bar + 8 * B_PE, layer);
    if (threadIdx.x == 0) TS(2 + layer * 20 + 12);
    conv_prep_finish(sb, in, tid, 0);
  }
  {
    if (tid < 96) {
      const int ch = tid / 24, h2 = (tid / 12) & 1, qq = tid % 12;
      sts128(sb + cv_u(ch) + h2 * CV_UH + (128 + qq) * 16, make_uint4(0, 0, 0, 0));
    } else if (tid >= 128 && tid < 176) {
      const int i = tid - 128, ch = i / 12, q2 = i % 12;
      const int w2 = q2 < 2 ? 1 : q2 < 6 ? 2 : 3, cc = q2 < 2 ? q2 : q2 < 6 ? q2 - 2 : q2 - 6;
      sts128(sb + cv_pb(ch) + w2 * CV_PBW + cc * 16, make_uint4(0, 0, 0, 0));
    }
  }
  mbar_arrive(bar + 8 * B_U1);
  uint32_t A0[20], A1[16];
  {
    const int l1 = opaque_tid() & 31;
    conv_load<0>(A0, sb + cv_pe(wg) + 4 * (16 + 16 * w + (l1 >> 2) - 2 * (l1 & 3)));
  }
  fence_async_smem();
  bar_sync(1, 256);
  if (threadIdx.x == 0) TS(2 + layer * 20 + 13);
#pragma unroll 1
  for (int r = 0; r < 2; r++) {
    const int ch = 2 * r + wg;
    float acc[64];
    const uint64_t d = mkdesc(sb + cv_u(ch), CV_UH, 128, 0);
    const int l1 = opaque_tid() & 31;
    const uint32_t pe = sb + cv_pe(ch) + 4 * (16 + 16 * w + (l1 >> 2) - 2 * (l1 & 3));
    float FE[8], FO[8];
    uint32_t AE[16];
    wg_fence(); conv_mma<0>(acc, A0, d); wg_commit();
    conv_load<1>(A1, pe);
    wg_fence(); conv_mma<1>(acc, A1, d); wg_commit(); if (r == RR && layer == 1 && threadIdx.x == 0) TS(19);
    wg_wait<1>();
    conv_load<2>(A0, pe);
    wg_fence(); conv_mma<2>(acc, A0, d); wg_commit(); if (r == RR && layer == 1 && threadIdx.x == 0) TS(21);
    wg_wait<1>();
    conv_load<3>(A1, pe);
    wg_fence(); conv_mma<3>(acc, A1, d); wg_commit(); if (r == RR && layer == 1 && threadIdx.x == 0) TS(58);
    wg_wait<1>();
    {
      const int l4 = opaque_tid() & 31;
      const uint32_t wt = sb + cv_wt(ch) + 4 * (73 + 16 * w + (l4 >> 2) - 2 * (l4 & 3));
      far_load(AE, wt);
      far_load(A0, wt + 576 - 4);
    }
    mbar_wait(bar + 8 * (r == 0 ? B_S1 : B_S2), layer);
    wg_fence();
    far_mma(FE, AE, mkdesc(sb + cv_se(ch), 256, 256, 3), FO, A0, mkdesc(sb + cv_so(ch), 256, 256, 3));
    wg_commit(); if (r == RR && layer == 1 && threadIdx.x == 0) TS(59);
    wg_wait<0>(); if (r == RR && layer == 1 && threadIdx.x == 0) TS(60);
    conv_load<0>(A0, pe + (r == 0 ? 65536 : 0));
    {
      const int l3 = opaque_tid() & 31;
      const uint32_t pf = sb + cv_pf(ch) + 2 * (16 * (16 * w + (l3 >> 2)) + 2 * (l3 & 3));
#pragma unroll
      for (int k = 0; k < 4; k++)
        asm volatile("st.shared.u32 [%0], %1;" ::"r"(pf + (k & 1) * 256 + (k >> 1) * 16), "r"(packbf(FE[2 * k] + FO[2 * k], FE[2 * k + 1] + FO[2 * k + 1])) : "memory");
    }
    const uint32_t pb = sb + cv_pb(ch) + w * CV_PBW;
    const int l2 = opaque_tid() & 31;
#pragma unroll
    for (int j = 0; j < 16; j += 2) {
      const int mt = l2 >> 3;
      const int a = 127 - (8 * (j + (mt >> 1)) + (l2 & 7));
      int c = 2 * (a + w) + (mt & 1);
      c ^= (c >> 3) & 1;
      stsm4t(pb + c * 16, packbf(acc[4 * j], acc[4 * j + 1]), packbf(acc[4 * j + 2], acc[4 * j + 3]),
             packbf(acc[4 * j + 4], acc[4 * j + 5]), packbf(acc[4 * j + 6], acc[4 * j + 7]));
    }
    if (threadIdx.x == 0) TS(2 + layer * 20 + 14 + r);
    if (r == 0) { mbar_arrive(bar + 8 * B_R1); mbar_wait(bar + 8 * B_U2, layer); }
  }
  bar_sync(2 + wg, 128);
  {
    const int i = opaque_tid() & 127;
    conv_epi<false>(sb, 2 + wg, i, dv);
  }
  fence_async_smem();
  bar_sync(2 + wg, 128);
  if (w == 0 && elect_one()) {
    conv_publish(sb, layer, cta, 2 + wg, 1);
    if (threadIdx.x == 0) TS(2 + layer * 20 + 16);
  }
}

__device__ __forceinline__ void final_phase(const Params& p, uint32_t sb, int cta, int wg, int w) {
  const int lane = opaque_tid() & 31;
  const uint32_t bar = sb + SM_BAR;
  mbar_wait(bar + 8 * B_TF, 0);
  if (threadIdx.x == 0) TS(42);
  const uint32_t src = sb + SM_W + wg * 8192, dst = sb + SM_W + 16384 + wg * 8192;
  const int mi = lane >> 3;
#pragma unroll
  for (int j = 0; j < 8; j += 2) {
    uint32_t r[4];
    const int line = 8 * (j + (mi >> 1)) + (lane & 7), pc = 2 * w + (mi & 1);
    ldsm4t(r, src + line * 128 + ((pc ^ (line & 7)) << 4));
    const int row = 16 * w + (lane & 7) + 8 * (mi & 1), ch = j + (mi >> 1);
    stsm4(dst + row * 128 + ((ch ^ (row & 7)) << 4), r[0], r[1], r[2], r[3]);
  }
  fence_async_smem();
  bar_sync(2 + wg, 128);
  if (w == 0 && elect_one()) {
    tma_st(&p.mapOut, (cta >> 4) * 64, (cta & 15) * 128 + wg * 64, dst);
    bulk_commit();
    asm volatile("cp.async.bulk.wait_group.read 0;" ::: "memory");
    if (threadIdx.x == 0) TS(43);
    if (threadIdx.x == 0) LTS(1);
  }
}

struct cplx { float r, i; };
__device__ __forceinline__ cplx cmul(cplx a, cplx b) { return {fmaf(a.r, b.r, -a.i * b.i), fmaf(a.r, b.i, a.i * b.r)}; }
__device__ __forceinline__ cplx csqr(cplx a) { return {fmaf(a.r, a.r, -a.i * a.i), (a.r + a.r) * a.i}; }
__device__ __forceinline__ cplx cexp_l(float ar2, float ai, float l) {
  const float m = ex2(ar2 * l);
  const float x = ai * l;
  return {m * __cosf(x), m * __sinf(x)};
}

template <int N> __device__ __forceinline__ void halve(float* s, int lane) {
  const bool up = (lane & (2 * N)) != 0;
#pragma unroll
  for (int i = 0; i < N; i++) {
    const float keep = up ? s[i + N] : s[i], send = up ? s[i] : s[i + N];
    s[i] = keep + __shfl_xor_sync(~0u, send, 2 * N);
  }
}
__device__ __forceinline__ void colsum_part(const Params& p, uint32_t sb, int cta, int ht, uint32_t tag) {
  if (cta >= 96) return;
  uint4 v[4][2];
#pragma unroll
  for (int r = 0; r < 4; r++)
#pragma unroll
    for (int i = 0; i < 2; i++) v[r][i] = *(const uint4*)(p.wqkv + (size_t)(ht + 128 * r) * 1536 + cta * 16 + i * 8);
  float s[16];
#pragma unroll
  for (int i = 0; i < 16; i++) s[i] = 0.f;
#pragma unroll
  for (int r = 0; r < 4; r++)
#pragma unroll
    for (int i = 0; i < 2; i++) {
      const uint32_t x[4] = {v[r][i].x, v[r][i].y, v[r][i].z, v[r][i].w};
#pragma unroll
      for (int k = 0; k < 4; k++) { s[8 * i + 2 * k] += bf_lo(x[k]); s[8 * i + 2 * k + 1] += bf_hi(x[k]); }
    }
  const int lane = ht & 31, w = ht >> 5;
  halve<8>(s, lane); halve<4>(s, lane); halve<2>(s, lane); halve<1>(s, lane);
  s[0] += __shfl_xor_sync(~0u, s[0], 1);
  if ((lane & 1) == 0) sts32f(sb + SM_RED + (w * 16 + (lane >> 1)) * 4, s[0]);
  bar_sync(4, 128);
  if (ht < 16) {
    float tot = 0.f;
#pragma unroll
    for (int k = 0; k < 4; k++) tot += __uint_as_float(lds32(sb + SM_RED + (k * 16 + ht) * 4));
    asm volatile("st.relaxed.gpu.global.v2.u32 [%0], {%1,%2};" ::"l"(&g_colsum[cta * 16 + ht]), "r"(__float_as_uint(tot)), "r"(tag) : "memory");
  }
}

__device__ __forceinline__ uint32_t packh(float lo, float hi) { uint32_t r; asm("cvt.rn.f16x2.f32 %0, %1, %2;" : "=r"(r) : "f"(hi), "f"(lo)); return r; }
__device__ __forceinline__ void mma_f16(float* d, uint32_t a0, uint32_t a1, uint32_t a2, uint32_t a3, uint32_t b0, uint32_t b1) {
  asm volatile("mma.sync.aligned.m16n8k16.row.col.f32.f16.f16.f32 {%0,%1,%2,%3}, {%4,%5,%6,%7}, {%8,%9}, {%0,%1,%2,%3};"
      : "+f"(d[0]), "+f"(d[1]), "+f"(d[2]), "+f"(d[3]) : "r"(a0), "r"(a1), "r"(a2), "r"(a3), "r"(b0), "r"(b1));
}
struct HSeed { uint32_t r, i; };
__device__ __forceinline__ HSeed hseed(cplx s) { return {packh(s.r, s.r), packh(s.i, s.i)}; }
__device__ __forceinline__ void hcmul(uint32_t& o_r, uint32_t& o_i, uint32_t br, uint32_t bi, HSeed s) {
  asm("{\n.reg .b32 t, u;\nmul.rn.f16x2 t, %3, %5;\nneg.f16x2 t, t;\nmul.rn.f16x2 u, %3, %4;\nfma.rn.f16x2 %0, %2, %4, t;\nfma.rn.f16x2 %1, %2, %5, u;\n}"
      : "=&r"(o_r), "=&r"(o_i) : "r"(br), "r"(bi), "r"(s.r), "r"(s.i));
}
struct HTile { uint32_t r[4], i[4]; };
__device__ __forceinline__ void tile_set(HTile& t, int k, cplx a, cplx b) { t.r[k] = packh(a.r, b.r); t.i[k] = packh(a.i, b.i); }
__device__ __forceinline__ void tile_upper(HTile& t, HSeed s) { hcmul(t.r[2], t.i[2], t.r[0], t.i[0], s); hcmul(t.r[3], t.i[3], t.r[1], t.i[1], s); }
__device__ __forceinline__ HTile tile_shift(const HTile& t, HSeed s) {
  HTile o;
#pragma unroll
  for (int k = 0; k < 4; k++) hcmul(o.r[k], o.i[k], t.r[k], t.i[k], s);
  return o;
}
__device__ __forceinline__ void tile_put(const HTile& t, uint32_t a) {
  sts128(a, make_uint4(t.r[0], t.r[1], t.r[2], t.r[3]));
  sts128(a + 512, make_uint4(t.i[0], t.i[1], t.i[2], t.i[3]));
}
__device__ __forceinline__ HTile tile_get(uint32_t a) { HTile o; ldsm4t(o.r, a); ldsm4t(o.i, a + 512); return o; }
__device__ __forceinline__ void tile_mma(float* T, const HTile& a0, const HTile& a1, const HTile& b) {
  mma_f16(T, a0.r[0], a0.r[1], a0.r[2], a0.r[3], b.r[0], b.r[1]);
  mma_f16(T, a0.i[0], a0.i[1], a0.i[2], a0.i[3], b.i[0], b.i[1]);
  mma_f16(T, a1.r[0], a1.r[1], a1.r[2], a1.r[3], b.r[2], b.r[3]);
  mma_f16(T, a1.i[0], a1.i[1], a1.i[2], a1.i[3], b.i[2], b.i[3]);
}
__device__ __forceinline__ void tile_mma2(float* T, float* U, const HTile& a0, const HTile& a1, const HTile& b, const HTile& c) {
  mma_f16(T, a0.r[0], a0.r[1], a0.r[2], a0.r[3], b.r[0], b.r[1]);
  mma_f16(U, a0.r[0], a0.r[1], a0.r[2], a0.r[3], c.r[0], c.r[1]);
  mma_f16(T, a0.i[0], a0.i[1], a0.i[2], a0.i[3], b.i[0], b.i[1]);
  mma_f16(U, a0.i[0], a0.i[1], a0.i[2], a0.i[3], c.i[0], c.i[1]);
  mma_f16(T, a1.r[0], a1.r[1], a1.r[2], a1.r[3], b.r[2], b.r[3]);
  mma_f16(U, a1.r[0], a1.r[1], a1.r[2], a1.r[3], c.r[2], c.r[3]);
  mma_f16(T, a1.i[0], a1.i[1], a1.i[2], a1.i[3], b.i[2], b.i[3]);
  mma_f16(U, a1.i[0], a1.i[1], a1.i[2], a1.i[3], c.i[2], c.i[3]);
}
__device__ __forceinline__ void kgen_unit(uint32_t tab, uint32_t taba, float ar2, float ai, cplx c, float (&T)[5][4]) {
  const cplx z1 = cexp_l(ar2, ai, 1.f), z16 = cexp_l(ar2, ai, 16.f), z256 = cexp_l(ar2, ai, 256.f);
  HTile a0, a1, b0, b1;
  {
    const cplx y1 = {z16.r, -z16.i}, y2 = csqr(y1), y3 = cmul(y2, y1), y4 = csqr(y2), y5 = cmul(y4, y1), y6 = csqr(y3), y7 = cmul(y4, y3);
    HTile t;
    tile_set(t, 0, {1.f, 0.f}, y1); tile_set(t, 1, y2, y3); tile_set(t, 2, y4, y5); tile_set(t, 3, y6, y7);
    const HTile u = tile_shift(t, hseed(csqr(y4)));
    __syncwarp();
    tile_put(t, tab); tile_put(u, tab + 1024);
    __syncwarp();
    a0 = tile_get(taba); a1 = tile_get(taba + 256);
  }
  const cplx z2 = csqr(z1), z4 = csqr(z2), z8 = csqr(z4);
  const HSeed h8 = hseed(z8);
  const cplx d = cmul(c, z256), e = cmul(d, z256);
  {
    const cplx z512 = csqr(z256), f = cmul(e, z512), f8 = cmul(f, z8), f16 = cmul(f, z16), e4 = cmul(e, z4);
    HTile t, u;
    tile_set(t, 0, e4, cmul(e, z8)); tile_set(t, 1, cmul(e4, z8), cmul(e, z16));
    tile_upper(t, hseed(z256));
    tile_set(u, 0, f8, f16); tile_set(u, 1, cmul(f8, z256), cmul(f16, z256));
    tile_upper(u, hseed(z512));
    __syncwarp();
    tile_put(t, tab); tile_put(u, tab + 1024);
    __syncwarp();
    b0 = tile_get(tab); b1 = tile_get(tab + 1024);
  }
  {
    const cplx d2 = cmul(d, z2), d4 = cmul(d, z4);
    HTile t;
    tile_set(t, 0, d2, d4); tile_set(t, 1, cmul(d2, z4), cmul(d, z8));
    tile_upper(t, h8);
    __syncwarp();
    tile_put(t, tab);
    __syncwarp();
    tile_mma2(T[3], T[4], a0, a1, b0, b1);
    b0 = tile_get(tab);
  }
  {
    const cplx c1 = cmul(c, z1), c2 = cmul(c, z2), c3 = cmul(c1, z2), c4 = cmul(c, z4);
    HTile t;
    tile_set(t, 0, c1, c2); tile_set(t, 1, c3, c4); tile_set(t, 2, cmul(c1, z4), cmul(c2, z4)); tile_set(t, 3, cmul(c3, z4), cmul(c4, z4));
    const HTile u = tile_shift(t, h8);
    __syncwarp();
    tile_put(t, tab); tile_put(u, tab + 1024);
    __syncwarp();
    tile_mma(T[2], a0, a1, b0);
    b0 = tile_get(tab); b1 = tile_get(tab + 1024);
    tile_mma2(T[0], T[1], a0, a1, b0, b1);
  }
}
struct ModeIn { uint2 ar, ai, br, bi, cr, ci; };
__device__ __forceinline__ ModeIn load_modes(const Params& p, int idx) {
  return {*(const uint2*)(p.a_re + idx), *(const uint2*)(p.a_im + idx), *(const uint2*)(p.b_re + idx),
          *(const uint2*)(p.b_im + idx), *(const uint2*)(p.c_re + idx), *(const uint2*)(p.c_im + idx)};
}
__device__ __forceinline__ float bf_el(uint2 v, int k) { const uint32_t x = (k & 2) ? v.y : v.x; return (k & 1) ? bf_hi(x) : bf_lo(x); }
struct KGen { float4 cur; float T[5][4]; };
__device__ __forceinline__ uint32_t kgen_slot(uint32_t sb, int ht, int u) {
  return sb + (u < 3 ? SM_KC + (ht >> 5) * (KC_STRIDE * 2) + (u - 1) * 512 + (ht & 31) * 16 + 16 : SM_HALO + 1024 + ht * 16);
}
__device__ __forceinline__ void kgen_setup(KGen& s, uint32_t sb, int cta, int ht, const ModeIn& in, bf16 logdt) {
  const float dt = __bfloat162float(__float2bfloat16_rn(expf(__bfloat162float(logdt))));
  float mx = 0.f, k0 = 0.f, ar2[4];
  cplx c[4];
#pragma unroll
  for (int k = 0; k < 4; k++) {
    ar2[k] = (dt * bf_el(in.ar, k)) * 1.4426950408889634f;
    c[k] = cmul({bf_el(in.cr, k), bf_el(in.ci, k)}, {dt * bf_el(in.br, k), dt * bf_el(in.bi, k)});
    k0 += c[k].r;
    mx = fmaxf(mx, fmaxf(fabsf(c[k].r), fabsf(c[k].i)) * ex2(fmaxf(ar2[k] * 2048.f, 0.f)));
  }
  const int ex = min(max(267 - (int)(__reduce_max_sync(~0u, __float_as_uint(mx)) >> 23), 1), 253);
  const float sc = __uint_as_float(ex << 23);
#pragma unroll
  for (int o = 16; o > 0; o >>= 1) k0 += __shfl_xor_sync(~0u, k0, o);
  if ((ht & 31) == 0) {
    const uint32_t kc = sb + SM_KC + (ht >> 5) * (KC_STRIDE * 2);
    sts16(kc, __bfloat16_as_ushort(__float2bfloat16_rn(k0)));
    sts16(kc + 641 * 2, 0);
    sts32f(kc + 644 * 2, __uint_as_float((254 - ex) << 23));
  }
  s.cur = make_float4(ar2[0], dt * bf_el(in.ai, 0), c[0].r * sc, c[0].i * sc);
#pragma unroll
  for (int k = 1; k < 4; k++) sts128f(kgen_slot(sb, ht, k), ar2[k], dt * bf_el(in.ai, k), c[k].r * sc, c[k].i * sc);
#pragma unroll
  for (int i = 0; i < 5; i++) s.T[i][0] = s.T[i][1] = s.T[i][2] = s.T[i][3] = 0.f;
}
__device__ __forceinline__ void kgen_finish(KGen& s, uint32_t sb, int cta, int ht) {
  const int w = ht >> 5, lane = ht & 31, g = lane >> 2, t = lane & 3;
  const uint32_t kc = sb + SM_KC + w * KC_STRIDE * 2;
  __syncwarp();
  const float inv = __uint_as_float(lds32(kc + 644 * 2));
  auto put = [&](int idx, float v) {
    sts16(kc + idx * 2, __bfloat16_as_ushort(__float2bfloat16_rn(v)));
  };
#pragma unroll
  for (int hi = 0; hi < 2; hi++)
#pragma unroll
    for (int lo = 0; lo < 2; lo++) {
      const int i = g + 8 * hi, j = 2 * t + lo, e = 2 * hi + lo;
      put(16 * i + 1 + j, s.T[0][e] * inv);
      put(16 * i + 9 + j, s.T[1][e] * inv);
      put(257 + 8 * i + j, s.T[2][e] * inv);
      put(385 + 4 * i + (j & 3) + 64 * (j >> 2), s.T[3][e] * inv);
      put(513 + 2 * i + lo + 32 * t, s.T[4][e] * inv);
    }
}

__device__ __forceinline__ void expand_taps(uint32_t sb, int ht) {
  const int ch = ht >> 5, lane = ht & 31;
  const uint32_t kc = sb + SM_KC + ch * KC_STRIDE * 2;
  const uint32_t dst0 = sb + cv_pe(ch);
  auto put = [&](int G, uint32_t v0, uint32_t v1, uint32_t v2, uint32_t v3, uint32_t v4, uint32_t v5, uint32_t v6, uint32_t v7, uint32_t v8) {
    const uint32_t dst = dst0 + G * 32;
    sts128(dst, make_uint4(v1 | (v0 << 16), v2 | (v1 << 16), v3 | (v2 << 16), v4 | (v3 << 16)));
    sts128(dst + 16, make_uint4(v5 | (v4 << 16), v6 | (v5 << 16), v7 | (v6 << 16), v8 | (v7 << 16)));
  };
  {
    const uint4 q = lds128(kc + lane * 16);
    const uint32_t pv = lane ? lds16(kc + lane * 16 - 2) : 0u;
    const uint32_t dst = dst0 + (lane + 2) * 32;
    sts128(dst, make_uint4(__byte_perm(q.x, pv, 0x5410), __byte_perm(q.x, q.x, 0x1032), __byte_perm(q.y, q.x, 0x7610), __byte_perm(q.y, q.y, 0x1032)));
    sts128(dst + 16, make_uint4(__byte_perm(q.z, q.y, 0x7610), __byte_perm(q.z, q.z, 0x1032), __byte_perm(q.w, q.z, 0x7610), __byte_perm(q.w, q.w, 0x1032)));
    if (lane < 4) sts128(dst0 + lane * 16, make_uint4(0, 0, 0, 0));
  }
  uint32_t a[5], b[2][3], ve[5][2], vo[5][2];
  {
    const uint32_t s1 = kc + 2 * (256 + 4 * lane);
#pragma unroll
    for (int k = 0; k < 5; k++) a[k] = lds16(s1 + 2 * k);
#pragma unroll
    for (int u = 0; u < 2; u++) {
      const uint32_t s2 = kc + 2 * (384 + 2 * (lane + 32 * u));
#pragma unroll
      for (int k = 0; k < 3; k++) b[u][k] = lds16(s2 + 2 * k);
    }
#pragma unroll
    for (int u = 0; u < 5; u++) {
      const int x = lane + 32 * u;
#pragma unroll
      for (int k = 0; k < 2; k++) {
        const int pp = x - k;
        ve[u][k] = (pp >= 65 && pp <= 128) ? lds16(kc + 2 * (384 + 2 * pp)) : 0u;
        vo[u][k] = (pp >= 64 && pp <= 127) ? lds16(kc + 2 * (385 + 2 * pp)) : 0u;
      }
    }
  }
  const uint32_t k255 = lds16(kc + 2 * 255), k1024 = lds16(kc + 2 * 512);
  put(34 + lane, lane == 0 ? k255 : a[0], a[0], a[0], a[1], a[2], a[2], a[2], a[3], a[4]);
#pragma unroll
  for (int u = 0; u < 2; u++) put(66 + lane + 32 * u, b[u][0], b[u][0], b[u][0], b[u][0], b[u][1], b[u][1], b[u][1], b[u][2], b[u][2]);
  if (lane < 10) {
    const uint32_t v = lane == 0 ? k1024 : 0u;
    put(130 + lane, v, v, v, v, v, v, 0u, 0u, 0u);
  }
  const uint32_t wt = sb + cv_wt(ch);
#pragma unroll
  for (int u = 0; u < 5; u++) {
    const int x = lane + 32 * u;
    if (x < 144) {
      asm volatile("st.shared.u32 [%0], %1;" ::"r"(wt + 4 * x), "r"(ve[u][0] | (ve[u][1] << 16)) : "memory");
      asm volatile("st.shared.u32 [%0], %1;" ::"r"(wt + 576 + 4 * x), "r"(vo[u][0] | (vo[u][1] << 16)) : "memory");
    }
  }
}

template <bool SMID> __device__ __forceinline__ int role_id() {
  uint32_t v;
  if (!SMID) { asm volatile("mov.u32 %0, %%ctaid.x;" : "=r"(v)); return v; }
  asm volatile("mov.u32 %0, %%smid;" : "=r"(v));
  const int tp = v >> 1;
  int gq, pos;
  if (tp < 32) { gq = tp & 7; pos = tp >> 3; }
  else if (tp < 60) { const int u = tp - 32, q = (u * 37) >> 8; gq = 1 + u - 7 * q; pos = 4 + q; }
  else if (tp < 62) { gq = 8; pos = tp - 60; }
  else { gq = 0; pos = tp - 58; }
  return __shfl_sync(~0u, gq * 16 + pos * 2 + (v & 1), 0);
}
__device__ __forceinline__ int role_rb(int cta) { return ((cta >> 4) & 3) * 4 + ((cta >> 2) & 3); }
__device__ __forceinline__ int role_hg(int cta) { return (cta >> 6) * 4 + (cta & 3); }
__device__ __forceinline__ int role_rb2(int cta) { return cta >> 3; }
__device__ __forceinline__ int role_q2(int cta) { return cta & 7; }

template <bool SMID> __global__ void __launch_bounds__(NTHREADS, 1) fused_kernel(const __grid_constant__ Params p) {
  extern __shared__ __align__(1024) uint8_t smem[];
  const uint32_t sb = s32(smem);
  const int tid = threadIdx.x, lane = tid & 31;
  const int warp = __shfl_sync(~0u, tid >> 5, 0);
  const int cta0 = role_id<SMID>();
  if (SMID && cta0 >= NCTA) {
    if (tid == 0) spin_until(&g_cnt[C_CS * 32], (ld_relaxed(&g_cnt[C_CS * 32]) / NCTA + 1) * NCTA);
    return;
  }
  const uint32_t bar = sb + SM_BAR;

  if (tid == 0) TS(0);
  if (warp < 4 && elect_one()) {
    const int rb = role_rb(cta0), hg = role_hg(cta0);
#pragma unroll
    for (int q = 0; q < 4; q++) {
      if (warp == q) {
#pragma unroll
        for (int i = 16 * q; i < 16 * q + 16 && i < B_COUNT; i++) {
          int cnt = 1;
          if ((i >= B_KVE && i < B_KVE + 8) || i == B_QDONE || i == B_PDONE || i == B_OST || i == B_AD) cnt = 2;
          if (i == B_Z0 || i == B_PE || i == B_U2) cnt = 128;
          if (i == B_R1 || i == B_U1) cnt = 256;
          if (i == B_S1 || i == B_S2) cnt = 128;
          mbar_init(bar + 8 * i, cnt);
        }
      }
    }
    asm volatile("fence.mbarrier_init.release.cluster;" ::: "memory");
    if (warp == 0) {
      fence_async_smem();
      const int kc = 0;
      mbar_expect(bar + 8 * B_XF, 16384);
      tma_ld(sb + SM_X, &p.mapX128, kc, rb * 128, bar + 8 * B_XF);
      mbar_expect(bar + 8 * B_KVF, 24576);
      tma_ld3(sb + SM_W, &p.mapW3, hg * 64, kc, 0, bar + 8 * B_KVF);
      mbar_expect(bar + 8 * (B_XF + 1), 16384);
      tma_ld(sb + SM_X + 16384, &p.mapX128, 64, rb * 128, bar + 8 * (B_XF + 1));
      mbar_expect(bar + 8 * (B_KVF + 1), 24576);
      tma_ld3(sb + SM_W + 24576, &p.mapW3, hg * 64, 64, 0, bar + 8 * (B_KVF + 1));
      TS(56);
    }
  }

  if (warp < 8) {
    bar_sync(0, NTHREADS);
    if (tid == 0) TS(1);
    asm volatile("setmaxnreg.inc.sync.aligned.u32 %0;" ::"n"(R_CONS));
    const int cw = __shfl_sync(~0u, opaque_tid() >> 5, 0);
    const int wg = cw >> 2, w = cw & 3;
    const int cta = role_id<SMID>();
    if (tid == 0) TS(54);
#pragma unroll 1
    for (int layer = 0; layer < 2; layer++) {
      attn_phase(p, sb, layer, role_rb(cta), role_hg(cta), wg, w);
      if (p.stop == 1 + 3 * layer) return;
      proj_phase(p, sb, layer, role_rb2(cta), role_q2(cta), wg, w);
      if (p.stop == 2 + 3 * layer) return;
      conv_phase(p, sb, layer, cta);
      if (p.stop == 3 + 3 * layer) return;
    }
    final_phase(p, sb, cta, wg, w);
  } else if (warp < 12) {
    asm volatile("setmaxnreg.dec.sync.aligned.u32 %0;" ::"n"(R_HELP));
    const int ht = tid - 256;
    const int cta = role_id<SMID>(), rb = role_rb(cta), hg = role_hg(cta);
    unsigned ep0 = 0;
    if (ht == 0) ep0 = ld_relaxed(&g_cnt[C_CS * 32]);
    const ModeIn min0 = load_modes(p, cv_chan(cta, ht >> 5) * 128 + (ht & 31) * 4);
    const bf16 logdt0 = p.log_dt[cv_chan(cta, ht >> 5)];
    bar_sync(0, NTHREADS);
    if (ht == 0) {
      asm volatile("st.shared.u32 [%0], %1;" ::"r"(sb + SM_EP), "r"(ep0 / NCTA) : "memory");
      mbar_arrive(bar + 8 * B_EP);
    }
    if (hg == 0) {
      *(float4*)(g_stats + (ht >> 6) * LSEQ * 2 + rb * 256 + (ht & 63) * 4) = make_float4(0.f, 0.f, 0.f, 0.f);
    }
    mbar_arrive(bar + 8 * B_Z0);
    mbar_wait(bar + 8 * B_EP, 0);
    colsum_part(p, sb, cta, ht, lds32(sb + SM_EP) + 1);
    if (ht == 0) TS(50);
    {
      KGen kg;
      const uint32_t tab0 = sb + ((ht >> 5) < 2 ? SM_T : SM_T2 - 4096) + (ht >> 5) * 2048;
      const uint32_t tab = tab0 + (ht & 31) * 16, taba = tab0 + ((ht >> 3) & 1) * 1024 + (((ht >> 1) & 8) + (ht & 7)) * 16;
      kgen_setup(kg, sb, cta, ht, min0, logdt0);
#pragma unroll 1
      for (int u = 0; u < 4; u++) {
        if (u == KG_PRE) {
          if (ht == 0) TS(39);
          mbar_wait(bar + 8 * B_AD, 0);
          if (ht == 0) TS(41);
        }
        if (u == 3) mbar_wait(bar + 8 * B_PDONE, 0);
        kgen_unit(tab, taba, kg.cur.x, kg.cur.y, {kg.cur.z, kg.cur.w}, kg.T);
        kg.cur = lds128f(kgen_slot(sb, opaque_tid() - 256, u + 1));
      }
      kgen_finish(kg, sb, cta, opaque_tid() - 256);
    }
    if (ht == 0) TS(51);
    bar_sync(4, 128);
#pragma unroll 1
    for (int layer = 0; layer < 2; layer++) {
      if (p.stop <= 1 + 3 * layer) return;
      mbar_wait(bar + 8 * B_PDONE, layer);
      expand_taps(sb, opaque_tid() - 256);
      if (ht == 0) TS(52 + layer);
      mbar_arrive(bar + 8 * B_PE);
      if (p.stop <= 2 + 3 * layer) return;
      mbar_wait(bar + 8 * B_GB, layer);
      {
        const int h0 = opaque_tid() - 256;
        const PrepIn in0 = conv_prep_load(layer, cta, h0, 2), in1 = conv_prep_load(layer, cta, h0 + 128, 2);
        conv_prep_finish(sb, in0, h0, 2);
        conv_prep_finish(sb, in1, h0 + 128, 2);
      }
      fence_async_smem();
      mbar_arrive(bar + 8 * B_U2);
      if (layer == 1 && ht == 0) TS(62);
      mbar_wait(bar + 8 * B_U1, layer);
      conv_sums(sb, 0, opaque_tid() - 256);
      fence_async_smem();
      mbar_arrive(bar + 8 * B_S1);
      if (layer == 1 && ht == 0) TS(46);
      bar_sync(4, 128);
      conv_sums(sb, 2, opaque_tid() - 256);
      fence_async_smem();
      mbar_arrive(bar + 8 * B_S2);
      const uint32_t dv0 = (uint32_t)__bfloat16_as_ushort(p.dskip[cv_chan(cta, 0)]) * 0x10001u;
      const uint32_t dv1 = (uint32_t)__bfloat16_as_ushort(p.dskip[cv_chan(cta, 1)]) * 0x10001u;
      mbar_wait(bar + 8 * B_R1, layer);
      conv_epi<true>(sb, 0, ht, dv0);
      conv_epi<true>(sb, 1, ht, dv1);
      fence_async_smem();
      bar_sync(4, 128);
      if (ht < 32 && elect_one()) { conv_publish(sb, layer, cta, 0, 2); }
    }
  } else {
    asm volatile("setmaxnreg.dec.sync.aligned.u32 40;");
    const int cta = role_id<SMID>(), rb = role_rb(cta), hg = role_hg(cta), rb2 = role_rb2(cta), q2 = role_q2(cta);
    bar_sync(0, NTHREADS);
    if (warp == 12) {
      if (elect_one()) {
        unsigned epoch = 0;
#pragma unroll 1
        for (int layer = 0; layer < 2; layer++) {
          auto ld_x = [&](int c) {
            const uint32_t b = bar + 8 * (B_XF + c);
            const int kc = c;
            mbar_expect(b, 16384);
            if (layer == 0) tma_ld(sb + SM_X + c * 16384, &p.mapX128, kc * 64, rb * 128, b);
            else tma_ld3(sb + SM_X + c * 16384, &p.mapXT3, 0, DM + kc * 64, rb * 2, b);
          };
          auto ld_w = [&](int c, int slot) {
            const uint32_t b = bar + 8 * (B_KVF + c);
            mbar_expect(b, 24576);
            tma_ld3(sb + SM_W + slot * 24576, &p.mapW3, hg * 64, c * 64, 0, b);
          };
          if (layer == 0) {
            TS(55);
            ld_x(2); ld_w(2, 2);
            ld_x(3);
            if (rb < 5) tma_prefetch3(&p.mapW3, hg * 64, (3 + rb) * 64, 0);
#pragma unroll 1
            for (int c = 4; c < 8; c++) ld_x(c);
            mbar_wait(bar + 8 * (B_KVF + 2), 0);
            if (rb2 < 4) tma_prefetch2(&p.mapWo128, q2 * 64, rb2 * 128);
            asm volatile("prefetch.tensormap [%0];" ::"l"(&p.mapO) : "memory");
            asm volatile("prefetch.tensormap [%0];" ::"l"(&p.mapO128) : "memory");
            asm volatile("prefetch.tensormap [%0];" ::"l"(&p.mapXT) : "memory");
            asm volatile("prefetch.tensormap [%0];" ::"l"(&p.mapXT3) : "memory");
            asm volatile("prefetch.tensormap [%0];" ::"l"(&p.mapOut) : "memory");
            mbar_wait(bar + 8 * B_EP, 0);
            epoch = lds32(sb + SM_EP);
          } else {
            mbar_wait(bar + 8 * B_PDONE, 0);
            ld_w(0, 0); ld_w(1, 1);
            spin_until(&g_cnt[C_G1A * 32], (epoch + 1) * NCTA);
            fence_async_global();
            fence_async_smem();
            ld_x(0); ld_x(1); ld_x(2); ld_w(2, 2); ld_x(3);
            mbar_wait(bar + 8 * B_KVE, 1);
            ld_w(3, 0);
            spin_until(&g_cnt[C_G1A * 32 + 1], (epoch + 1) * 2 * NCTA);
            TS(44);
            fence_async_global();
            fence_async_smem();
#pragma unroll 1
            for (int c = 4; c < 8; c++) ld_x(c);
          }
          {
            int slot = layer;
#pragma unroll 1
            for (int c = 3 + layer; c < 8; c++) {
              mbar_wait(bar + 8 * (B_KVE + c - 3), layer);
              ld_w(c, slot);
              slot = slot == 2 ? 0 : slot + 1;
            }
          }
          if (p.stop <= 1 + 3 * layer) return;
          mbar_wait(bar + 8 * B_QDONE, layer);
          if (rb > 0) mbar_wait(bar + 8 * B_HF, layer);
#pragma unroll 1
          for (int c = 0; c < 4; c++) {
            const uint32_t b = bar + 8 * (B_WOF + c);
            mbar_expect(b, 16384);
            tma_ld(sb + SM_X + c * 16384, &p.mapWo128, q2 * 64, c * 128, b);
          }
          {
            const uint32_t b = bar + 8 * B_RF;
            mbar_expect(b, 16384);
            if (layer == 0) tma_ld(sb + SM_R, &p.mapX128, q2 * 64, rb2 * 128, b);
            else tma_ld3(sb + SM_R, &p.mapXT3, 0, DM + q2 * 64, rb2 * 2, b);
          }
          spin_until(&g_cnt[(C_O + rb2) * 32], (2 * epoch + layer + 1) * 16);
          mbar_wait(bar + 8 * B_OST, layer);
          fence_async_global();
#pragma unroll 1
          for (int c = 0; c < 8; c++) {
            const uint32_t b = bar + 8 * (B_OF + c);
            mbar_expect(b, 16384);
            tma_ld(sb + (c < 4 ? SM_X + 65536 + c * 16384 : SM_W + (c - 4) * 16384), &p.mapO128, c * 64, rb2 * 128, b);
          }
          if (p.stop <= 3 + 3 * layer) return;
        }
        spin_until(&g_cnt[(C_F + (cta >> 4)) * 32], (epoch + 1) * (cta < 64 ? 32 : 64));
        fence_async_global();
        mbar_expect(bar + 8 * B_TF, 16384);
        tma_ld3(sb + SM_W, &p.mapXT3, 0, 3 * DM + (cta >> 4) * 64, (cta & 15) * 2, bar + 8 * B_TF);
      }
    } else if (warp == 14) {
      mbar_wait(bar + 8 * B_EP, 0);
      const unsigned epoch = lds32(sb + SM_EP);
      {
        uint2 v[6];
        bool ok;
        int it = 0;
        do {
          ok = true;
#pragma unroll
          for (int i = 0; i < 6; i++) {
            const int k = lane + 32 * i;
            asm volatile("ld.relaxed.gpu.global.v2.u32 {%0,%1}, [%2];" : "=r"(v[i].x), "=r"(v[i].y) : "l"(&g_colsum[(k >> 6) * 512 + hg * 64 + (k & 63)]) : "memory");
            ok = ok && v[i].y == epoch + 1;
          }
          if (++it > (1 << 22)) __trap();
        } while (!__all_sync(~0u, ok));
#pragma unroll
        for (int i = 0; i < 6; i++) sts32f(sb + SM_CS + 4 * (lane + 32 * i), __uint_as_float(v[i].x));
      }
      __syncwarp();
      if (lane == 0) {
        mbar_arrive(bar + 8 * B_CSF);
        TS(40);
        mbar_wait(bar + 8 * B_Z0, 0);
        red_release(&g_cnt[C_CS * 32]);
        spin_until(&g_cnt[C_CS * 32], (epoch + 1) * NCTA);
        mbar_arrive(bar + 8 * B_ZF);
#pragma unroll 1
        for (int layer = 0; layer < 2; layer++) {
          if (p.stop <= 1 + 3 * layer) return;
          spin_until(&g_cnt[(layer ? C_G2 : C_G0) * 32], (epoch + 1) * 256);
          mbar_arrive(bar + 8 * B_GB);
        }
      }
    }
  }
}

typedef CUresult (*EncodeFn)(CUtensorMap*, CUtensorMapDataType, cuuint32_t, void*, const cuuint64_t*, const cuuint64_t*,
                             const cuuint32_t*, const cuuint32_t*, CUtensorMapInterleave, CUtensorMapSwizzle,
                             CUtensorMapL2promotion, CUtensorMapFloatOOBfill);

static void make_map(EncodeFn enc, CUtensorMap* m, void* ptr, uint64_t cols, uint64_t rows, uint32_t box_rows) {
  cuuint64_t dims[2] = {cols, rows};
  cuuint64_t strides[1] = {cols * 2};
  cuuint32_t box[2] = {64, box_rows};
  cuuint32_t es[2] = {1, 1};
  enc(m, CU_TENSOR_MAP_DATA_TYPE_BFLOAT16, 2, ptr, dims, strides, box, es, CU_TENSOR_MAP_INTERLEAVE_NONE,
      CU_TENSOR_MAP_SWIZZLE_128B, CU_TENSOR_MAP_L2_PROMOTION_L2_128B, CU_TENSOR_MAP_FLOAT_OOB_FILL_NONE);
}
static void make_map3(EncodeFn enc, CUtensorMap* m, void* ptr, uint64_t d0, uint64_t cols, uint64_t rows, uint64_t blk_stride,
                      uint64_t nblocks, uint32_t nblk) {
  cuuint64_t dims[3] = {d0, rows, nblocks};
  cuuint64_t strides[2] = {cols * 2, blk_stride * 2};
  cuuint32_t box[3] = {64, 64, nblk};
  cuuint32_t es[3] = {1, 1, 1};
  enc(m, CU_TENSOR_MAP_DATA_TYPE_BFLOAT16, 3, ptr, dims, strides, box, es, CU_TENSOR_MAP_INTERLEAVE_NONE,
      CU_TENSOR_MAP_SWIZZLE_128B, CU_TENSOR_MAP_L2_PROMOTION_L2_128B, CU_TENSOR_MAP_FLOAT_OOB_FILL_NONE);
}

extern "C" void kernel_launch(void* const* d_in, const int* in_sizes, int n_in, void* d_out, int out_size) {
  static Params prm;
  static void* cached[13] = {nullptr};
  static bool attr_done = false, by_smid = false;
  bool same = attr_done && cached[12] == d_out;
  for (int i = 0; i < 12 && same; i++) same = cached[i] == d_in[i];
  if (!same) {
    void* fn = nullptr;
    cudaDriverEntryPointQueryResult qr;
    cudaGetDriverEntryPoint("cuTensorMapEncodeTiled", &fn, cudaEnableDefault, &qr);
    EncodeFn enc = (EncodeFn)fn;
    void *pO, *pXT;
    cudaGetSymbolAddress(&pO, g_O);
    cudaGetSymbolAddress(&pXT, g_xT);
    make_map(enc, &prm.mapO, pO, DM, LSEQ, 64);
    make_map(enc, &prm.mapXT, pXT, LSEQ, 4 * DM, 64);
    make_map(enc, &prm.mapOut, d_out, DM, LSEQ, 64);
    make_map(enc, &prm.mapX128, d_in[0], DM, LSEQ, 128);
    make_map(enc, &prm.mapWo128, d_in[2], DM, DM, 128);
    make_map(enc, &prm.mapO128, pO, DM, LSEQ, 128);
    make_map3(enc, &prm.mapW3, d_in[1], DM, 3 * DM, DM, DM, 3, 3);
    make_map3(enc, &prm.mapXT3, pXT, 64, LSEQ, 4 * DM, 64, 32, 2);
    prm.wqkv = (const bf16*)d_in[1];
    prm.a_re = (const bf16*)d_in[4]; prm.a_im = (const bf16*)d_in[5];
    prm.b_re = (const bf16*)d_in[6]; prm.b_im = (const bf16*)d_in[7];
    prm.c_re = (const bf16*)d_in[8]; prm.c_im = (const bf16*)d_in[9];
    prm.log_dt = (const bf16*)d_in[10]; prm.dskip = (const bf16*)d_in[11];
    int dev = 0, sms = 0;
    cudaGetDevice(&dev);
    cudaDeviceGetAttribute(&sms, cudaDevAttrMultiProcessorCount, dev);
    by_smid = sms == 132;
    cudaFuncSetAttribute(fused_kernel<true>, cudaFuncAttributeMaxDynamicSharedMemorySize, SM_TOTAL);
    cudaFuncSetAttribute(fused_kernel<false>, cudaFuncAttributeMaxDynamicSharedMemorySize, SM_TOTAL);
    for (int i = 0; i < 12; i++) cached[i] = d_in[i];
    cached[12] = d_out;
    attr_done = true;
  }
  prm.stop = 100;
    if (by_smid) fused_kernel<true><<<132, NTHREADS, SM_TOTAL>>>(prm);
  else fused_kernel<false><<<NCTA, NTHREADS, SM_TOTAL>>>(prm);
}
```

```cpp
#include <cuda_runtime.h>
#include <cuda_bf16.h>
#include <cuda.h>
#include <stdint.h>

typedef __nv_bfloat16 bf16;

constexpr int LSEQ = 2048;
constexpr int DM = 512;
constexpr int NCTA = 128;
constexpr int NTHREADS = 512;
#define RR 0
#define KG_PRE 0
#define CS_LATE 0
#define KG_LAST 1
#define X_JIT 0
#define KG_GATE 2
#define R_CONS 192
#define R_HELP 88

constexpr int SM_X = 0;
constexpr int SM_W = 131072;
constexpr int SM_KVX = SM_W;
constexpr int SM_OST = SM_W + 32768;
constexpr int SM_R = 196608;
constexpr int SM_T = 212992;
constexpr int SM_KC = 217088;
constexpr int KC_STRIDE = 648;
constexpr int SM_CS = SM_KC + 4 * KC_STRIDE * 2;
constexpr int SM_RED = SM_CS + 768;
constexpr int SM_EP = SM_RED + 256;
constexpr int SM_BAR = SM_RED + 272;
constexpr int SM_T2 = SM_BAR + 832;
constexpr int SM_HALO = SM_T2 + 4096;
constexpr int SM_TOTAL = SM_HALO + 4096;
static_assert(SM_TOTAL <= 232448, "shared memory");

constexpr int CV_UH = 140 * 16;
constexpr int CV_PECH = 1120 * 4;
constexpr int CV_PBW = 2112 * 2;
__host__ __device__ constexpr int cv_s(int lc) { return SM_X + lc * 32768; }
__host__ __device__ constexpr int cv_u(int lc) { return cv_s(lc) + 4096; }
__host__ __device__ constexpr int cv_pe(int lc) { return cv_u(lc) + 2 * CV_UH; }
__host__ __device__ constexpr int cv_pb(int lc) { return cv_pe(lc) + CV_PECH; }
__host__ __device__ constexpr int cv_ft(int lc) { return cv_pb(lc) + 4 * CV_PBW; }
static_assert(cv_ft(0) + 1024 <= 32768, "conv buffers");
__host__ __device__ constexpr int cv_chan(int cta, int lc) { return cta + 128 * lc; }

enum {
  B_XF = 0,
  B_KVF = 8,
  B_KVE = 16,
  B_AD = 21,
  B_OST = 22,
  B_RF = 23,
  B_U = 24,
  B_S = 28,
  B_T = 32,
  B_WOF = 36,
  B_E = 40,
  B_OF = 44,
  B_P = 64,
  B_HF = 54,
  B_CSF = 55,
  B_QDONE = 56,
  B_PDONE = 57,
  B_Z0 = 58,
  B_PE = 59,
  B_GB = 60,
  B_EP = 62,
  B_ZF = 63,
  B_COUNT = 68
};

enum {
  C_CS = 0,
  C_G0 = 1,
  C_G1 = 2,
  C_G2 = 3,
  C_O = 4,
  C_F = 20,
  C_COUNT = 24
};

__device__ unsigned g_cnt[C_COUNT * 32];
__device__ __align__(1024) bf16 g_O[LSEQ * DM];
__device__ __align__(1024) bf16 g_xT[4 * DM * LSEQ];
__device__ __align__(1024) float g_stats[2 * LSEQ * 2];
__device__ __align__(1024) uint2 g_colsum[3 * DM];
__device__ __align__(1024) uint4 g_halo[2 * 16 * 8 * 384];
__device__ __align__(1024) uint4 g_part[2 * 16 * 8 * 128];
#define TS(i) do { } while (0)

#define FTS(i) do { } while (0)
#define LTS(i) do { } while (0)

struct Params {
  CUtensorMap mapO, mapXT, mapX128, mapWo128, mapO128, mapW3, mapXT3;
  const bf16 *wqkv, *a_re, *a_im, *b_re, *b_im, *c_re, *c_im, *log_dt, *dskip;
  bf16* out;
  int stop;
};

__device__ __forceinline__ uint32_t s32(const void* p) { return (uint32_t)__cvta_generic_to_shared(p); }
__device__ __forceinline__ void mbar_init(uint32_t b, int c) { asm volatile("mbarrier.init.shared::cta.b64 [%0], %1;" ::"r"(b), "r"(c) : "memory"); }
__device__ __forceinline__ void mbar_expect(uint32_t b, int bytes) { asm volatile("mbarrier.arrive.expect_tx.shared::cta.b64 _, [%0], %1;" ::"r"(b), "r"(bytes) : "memory"); }
__device__ __forceinline__ void mbar_arrive(uint32_t b) { asm volatile("mbarrier.arrive.shared::cta.b64 _, [%0];" ::"r"(b) : "memory"); }
__device__ __forceinline__ void mbar_arrive_if(uint32_t b, bool c) {
  asm volatile("{\n.reg .pred p;\nsetp.ne.u32 p, %1, 0;\n@p mbarrier.arrive.shared::cta.b64 _, [%0];\n}" ::"r"(b), "r"((uint32_t)c) : "memory");
}
__device__ __forceinline__ void mbar_wait(uint32_t b, int parity) {
  asm volatile("{\n.reg .pred p;\nWAIT_LOOP:\nmbarrier.try_wait.parity.shared::cta.b64 p, [%0], %1;\n@p bra WAIT_DONE;\nbra WAIT_LOOP;\nWAIT_DONE:\n}" ::"r"(b), "r"(parity) : "memory");
}
__device__ __forceinline__ int opaque_tid() { int v; asm volatile("mov.u32 %0, %%tid.x;" : "=r"(v)); return v; }
__device__ __forceinline__ bool elect_one() {
  uint32_t r;
  asm volatile("{\n.reg .pred p;\nelect.sync _|p, 0xffffffff;\nselp.u32 %0, 1, 0, p;\n}" : "=r"(r));
  return r != 0;
}
__device__ __forceinline__ void tma_ld(uint32_t dst, const CUtensorMap* m, int c0, int c1, uint32_t bar) {
  asm volatile("cp.async.bulk.tensor.2d.shared::cluster.global.mbarrier::complete_tx::bytes [%0], [%1, {%3, %4}], [%2];"
               ::"r"(dst), "l"(m), "r"(bar), "r"(c0), "r"(c1) : "memory");
}
__device__ __forceinline__ void tma_ld3(uint32_t dst, const CUtensorMap* m, int c0, int c1, int c2, uint32_t bar) {
  asm volatile("cp.async.bulk.tensor.3d.shared::cluster.global.mbarrier::complete_tx::bytes [%0], [%1, {%3, %4, %5}], [%2];"
               ::"r"(dst), "l"(m), "r"(bar), "r"(c0), "r"(c1), "r"(c2) : "memory");
}
__device__ __forceinline__ void tma_prefetch2(const CUtensorMap* m, int c0, int c1) {
  asm volatile("cp.async.bulk.prefetch.tensor.2d.L2.global.tile [%0, {%1, %2}];" ::"l"(m), "r"(c0), "r"(c1) : "memory");
}
__device__ __forceinline__ void tma_prefetch3(const CUtensorMap* m, int c0, int c1, int c2) {
  asm volatile("cp.async.bulk.prefetch.tensor.3d.L2.global.tile [%0, {%1, %2, %3}];" ::"l"(m), "r"(c0), "r"(c1), "r"(c2) : "memory");
}
__device__ __forceinline__ void tma_st(const CUtensorMap* m, int c0, int c1, uint32_t src) {
  asm volatile("cp.async.bulk.tensor.2d.global.shared::cta.bulk_group [%0, {%2, %3}], [%1];" ::"l"(m), "r"(src), "r"(c0), "r"(c1) : "memory");
}
__device__ __forceinline__ void bulk_ld(uint32_t dst, const void* src, int bytes, uint32_t bar) {
  asm volatile("cp.async.bulk.shared::cluster.global.mbarrier::complete_tx::bytes [%0], [%1], %2, [%3];" ::"r"(dst), "l"(src), "r"(bytes), "r"(bar) : "memory");
}
__device__ __forceinline__ void bulk_st(void* dst, uint32_t src, int bytes) {
  asm volatile("cp.async.bulk.global.shared::cta.bulk_group [%0], [%1], %2;" ::"l"(dst), "r"(src), "r"(bytes) : "memory");
}
__device__ __forceinline__ void bulk_red_add_f32(void* dst, uint32_t src, int bytes) {
  asm volatile("cp.reduce.async.bulk.global.shared::cta.bulk_group.add.f32 [%0], [%1], %2;" ::"l"(dst), "r"(src), "r"(bytes) : "memory");
}
__device__ __forceinline__ void bulk_commit() { asm volatile("cp.async.bulk.commit_group;" ::: "memory"); }
__device__ __forceinline__ void bulk_wait_all() { asm volatile("cp.async.bulk.wait_group 0;" ::: "memory"); }
__device__ __forceinline__ void fence_async_smem() { asm volatile("fence.proxy.async.shared::cta;" ::: "memory"); }
__device__ __forceinline__ void fence_async_global() { asm volatile("fence.proxy.async.global;" ::: "memory"); }
__device__ __forceinline__ void bar_sync(int id, int n) { asm volatile("bar.sync %0, %1;" ::"r"(id), "r"(n) : "memory"); }
__device__ __forceinline__ void bar_arrive(int id, int n) { asm volatile("bar.arrive %0, %1;" ::"r"(id), "r"(n) : "memory"); }
__device__ __forceinline__ void wg_fence() { asm volatile("wgmma.fence.sync.aligned;" ::: "memory"); }
__device__ __forceinline__ void wg_commit() { asm volatile("wgmma.commit_group.sync.aligned;" ::: "memory"); }
template <int N> __device__ __forceinline__ void wg_wait() { asm volatile("wgmma.wait_group.sync.aligned %0;" ::"n"(N) : "memory"); }
__device__ __forceinline__ uint64_t mkdesc(uint32_t addr, uint32_t lbo, uint32_t sbo, int sw) {
  return (uint64_t)((addr & 0x3FFFF) >> 4) | ((uint64_t)(lbo >> 4) << 16) | ((uint64_t)(sbo >> 4) << 32) | ((uint64_t)sw << 62);
}
__device__ __forceinline__ void ldsm4(uint32_t* r, uint32_t a) {
  asm volatile("ldmatrix.sync.aligned.m8n8.x4.shared.b16 {%0,%1,%2,%3}, [%4];" : "=r"(r[0]), "=r"(r[1]), "=r"(r[2]), "=r"(r[3]) : "r"(a) : "memory");
}
__device__ __forceinline__ void ldsm4t(uint32_t* r, uint32_t a) {
  asm volatile("ldmatrix.sync.aligned.m8n8.x4.trans.shared.b16 {%0,%1,%2,%3}, [%4];" : "=r"(r[0]), "=r"(r[1]), "=r"(r[2]), "=r"(r[3]) : "r"(a) : "memory");
}
__device__ __forceinline__ void stsm4(uint32_t a, uint32_t r0, uint32_t r1, uint32_t r2, uint32_t r3) {
  asm volatile("stmatrix.sync.aligned.m8n8.x4.shared.b16 [%0], {%1,%2,%3,%4};" ::"r"(a), "r"(r0), "r"(r1), "r"(r2), "r"(r3) : "memory");
}
__device__ __forceinline__ void stsm4t(uint32_t a, uint32_t r0, uint32_t r1, uint32_t r2, uint32_t r3) {
  asm volatile("stmatrix.sync.aligned.m8n8.x4.trans.shared.b16 [%0], {%1,%2,%3,%4};" ::"r"(a), "r"(r0), "r"(r1), "r"(r2), "r"(r3) : "memory");
}
__device__ __forceinline__ uint32_t movm_t(uint32_t a) { uint32_t r; asm volatile("movmatrix.sync.aligned.m8n8.trans.b16 %0, %1;" : "=r"(r) : "r"(a)); return r; }
__device__ __forceinline__ uint32_t lds32(uint32_t a) { uint32_t v; asm volatile("ld.shared.b32 %0, [%1];" : "=r"(v) : "r"(a) : "memory"); return v; }
__device__ __forceinline__ float2 lds64f(uint32_t a) { float2 v; asm volatile("ld.shared.v2.f32 {%0,%1}, [%2];" : "=f"(v.x), "=f"(v.y) : "r"(a) : "memory"); return v; }
__device__ __forceinline__ float4 lds128f(uint32_t a) { float4 v; asm volatile("ld.shared.v4.f32 {%0,%1,%2,%3}, [%4];" : "=f"(v.x), "=f"(v.y), "=f"(v.z), "=f"(v.w) : "r"(a) : "memory"); return v; }
__device__ __forceinline__ uint4 lds128(uint32_t a) { uint4 v; asm volatile("ld.shared.v4.b32 {%0,%1,%2,%3}, [%4];" : "=r"(v.x), "=r"(v.y), "=r"(v.z), "=r"(v.w) : "r"(a) : "memory"); return v; }
__device__ __forceinline__ void sts128(uint32_t a, uint4 v) { asm volatile("st.shared.v4.b32 [%0], {%1,%2,%3,%4};" ::"r"(a), "r"(v.x), "r"(v.y), "r"(v.z), "r"(v.w) : "memory"); }
__device__ __forceinline__ void sts128f(uint32_t a, float x, float y, float z, float w) { asm volatile("st.shared.v4.f32 [%0], {%1,%2,%3,%4};" ::"r"(a), "f"(x), "f"(y), "f"(z), "f"(w) : "memory"); }
__device__ __forceinline__ void sts32f(uint32_t a, float v) { asm volatile("st.shared.f32 [%0], %1;" ::"r"(a), "f"(v) : "memory"); }
__device__ __forceinline__ void sts16(uint32_t a, uint16_t v) { asm volatile("st.shared.u16 [%0], %1;" ::"r"(a), "h"(v) : "memory"); }
__device__ __forceinline__ uint32_t lds16(uint32_t a) { uint16_t v; asm volatile("ld.shared.u16 %0, [%1];" : "=h"(v) : "r"(a) : "memory"); return v; }
__device__ __forceinline__ uint32_t packbf(float lo, float hi) { uint32_t r; asm("cvt.rn.bf16x2.f32 %0, %1, %2;" : "=r"(r) : "f"(hi), "f"(lo)); return r; }
__device__ __forceinline__ float bf_lo(uint32_t v) { return __uint_as_float(v << 16); }
__device__ __forceinline__ float bf_hi(uint32_t v) { return __uint_as_float(v & 0xffff0000u); }
__device__ __forceinline__ float ex2(float x) { float r; asm("ex2.approx.ftz.f32 %0, %1;" : "=f"(r) : "f"(x)); return r; }
__device__ __forceinline__ float rsqrt_approx(float x) { float r; asm("rsqrt.approx.ftz.f32 %0, %1;" : "=f"(r) : "f"(x)); return r; }
__device__ __forceinline__ float rcp_approx(float x) { float r; asm("rcp.approx.ftz.f32 %0, %1;" : "=f"(r) : "f"(x)); return r; }
__device__ __forceinline__ void mma_bf16(float* d, const uint32_t* a, uint32_t b0, uint32_t b1) {
  asm("mma.sync.aligned.m16n8k16.row.col.f32.bf16.bf16.f32 {%0,%1,%2,%3}, {%4,%5,%6,%7}, {%8,%9}, {%0,%1,%2,%3};"
               : "+f"(d[0]), "+f"(d[1]), "+f"(d[2]), "+f"(d[3]) : "r"(a[0]), "r"(a[1]), "r"(a[2]), "r"(a[3]), "r"(b0), "r"(b1));
}
__device__ __forceinline__ void red_release(unsigned* p) { asm volatile("red.release.gpu.global.add.u32 [%0], 1;" ::"l"(p) : "memory"); }
__device__ __forceinline__ void red_relaxed(unsigned* p) { asm volatile("red.relaxed.gpu.global.add.u32 [%0], 1;" ::"l"(p) : "memory"); }
__device__ __forceinline__ unsigned ld_relaxed(const unsigned* p) { unsigned v; asm volatile("ld.relaxed.gpu.global.u32 %0, [%1];" : "=r"(v) : "l"(p) : "memory"); return v; }
__device__ __forceinline__ void spin_until(const unsigned* p, unsigned target) {
  int it = 0;
  while ((int)(ld_relaxed(p) - target) < 0) {
    if (++it > (1 << 23)) __trap();
  }
}
__device__ __forceinline__ uint4 ldcg128(const void* p) { uint4 v; asm volatile("ld.global.cg.v4.b32 {%0,%1,%2,%3}, [%4];" : "=r"(v.x), "=r"(v.y), "=r"(v.z), "=r"(v.w) : "l"(p) : "memory"); return v; }
__device__ __forceinline__ uint4 ld_tagged(const uint4* p) { uint4 v; asm volatile("ld.relaxed.gpu.global.v4.u32 {%0,%1,%2,%3}, [%4];" : "=r"(v.x), "=r"(v.y), "=r"(v.z), "=r"(v.w) : "l"(p) : "memory"); return v; }
__device__ __forceinline__ void st_tagged(uint4* p, uint32_t a, uint32_t b, uint32_t tag) { asm volatile("st.relaxed.gpu.global.v4.u32 [%0], {%1,%2,%3,%2};" ::"l"(p), "r"(a), "r"(tag), "r"(b) : "memory"); }
__device__ __forceinline__ void st_tagged3(uint4* p, uint32_t a, uint32_t b, uint32_t c, uint32_t tag) { asm volatile("st.relaxed.gpu.global.v4.u32 [%0], {%1,%2,%3,%4};" ::"l"(p), "r"(a), "r"(b), "r"(c), "r"(tag) : "memory"); }
__device__ __forceinline__ uint4 poll_tagged(const uint4* p, uint32_t tag) {
  uint4 v = ld_tagged(p);
  int it = 0;
  while (v.y != tag || v.w != tag) {
    if (++it > (1 << 22)) __trap();
    v = ld_tagged(p);
  }
  return v;
}
__device__ __forceinline__ uint32_t hadd2(uint32_t a, uint32_t b) { uint32_t r; asm("add.rn.bf16x2 %0, %1, %2;" : "=r"(r) : "r"(a), "r"(b)); return r; }
__device__ __forceinline__ uint32_t hmul2(uint32_t a, uint32_t b) { uint32_t r; asm("mul.rn.bf16x2 %0, %1, %2;" : "=r"(r) : "r"(a), "r"(b)); return r; }

template<int N,int TB> __device__ __forceinline__ void wgmma_rs(float* d, const uint32_t* a, uint64_t db, int sd);
template<int N,int TA,int TB> __device__ __forceinline__ void wgmma_ss(float* d, uint64_t da, uint64_t db, int sd);
template<> __device__ __forceinline__ void wgmma_rs<128,0>(float* d, const uint32_t* a, uint64_t db, int sd) {
  asm volatile("{\n.reg .pred p;\nsetp.ne.b32 p, %69, 0;\nwgmma.mma_async.sync.aligned.m64n128k16.f32.bf16.bf16 {%0,%1,%2,%3,%4,%5,%6,%7,%8,%9,%10,%11,%12,%13,%14,%15,%16,%17,%18,%19,%20,%21,%22,%23,%24,%25,%26,%27,%28,%29,%30,%31,%32,%33,%34,%35,%36,%37,%38,%39,%40,%41,%42,%43,%44,%45,%46,%47,%48,%49,%50,%51,%52,%53,%54,%55,%56,%57,%58,%59,%60,%61,%62,%63}, {%64,%65,%66,%67}, %68, p, 1, 1, 0;\n}\n"
   : "+f"(d[0]),"+f"(d[1]),"+f"(d[2]),"+f"(d[3]),"+f"(d[4]),"+f"(d[5]),"+f"(d[6]),"+f"(d[7]),"+f"(d[8]),"+f"(d[9]),"+f"(d[10]),"+f"(d[11]),"+f"(d[12]),"+f"(d[13]),"+f"(d[14]),"+f"(d[15]),"+f"(d[16]),"+f"(d[17]),"+f"(d[18]),"+f"(d[19]),"+f"(d[20]),"+f"(d[21]),"+f"(d[22]),"+f"(d[23]),"+f"(d[24]),"+f"(d[25]),"+f"(d[26]),"+f"(d[27]),"+f"(d[28]),"+f"(d[29]),"+f"(d[30]),"+f"(d[31]),"+f"(d[32]),"+f"(d[33]),"+f"(d[34]),"+f"(d[35]),"+f"(d[36]),"+f"(d[37]),"+f"(d[38]),"+f"(d[39]),"+f"(d[40]),"+f"(d[41]),"+f"(d[42]),"+f"(d[43]),"+f"(d[44]),"+f"(d[45]),"+f"(d[46]),"+f"(d[47]),"+f"(d[48]),"+f"(d[49]),"+f"(d[50]),"+f"(d[51]),"+f"(d[52]),"+f"(d[53]),"+f"(d[54]),"+f"(d[55]),"+f"(d[56]),"+f"(d[57]),"+f"(d[58]),"+f"(d[59]),"+f"(d[60]),"+f"(d[61]),"+f"(d[62]),"+f"(d[63])
   : "r"(a[0]), "r"(a[1]), "r"(a[2]), "r"(a[3]), "l"(db), "r"(sd));
}
template<> __device__ __forceinline__ void wgmma_rs<120,0>(float* d, const uint32_t* a, uint64_t db, int sd) {
  asm volatile("{\n.reg .pred p;\nsetp.ne.b32 p, %65, 0;\nwgmma.mma_async.sync.aligned.m64n120k16.f32.bf16.bf16 {%0,%1,%2,%3,%4,%5,%6,%7,%8,%9,%10,%11,%12,%13,%14,%15,%16,%17,%18,%19,%20,%21,%22,%23,%24,%25,%26,%27,%28,%29,%30,%31,%32,%33,%34,%35,%36,%37,%38,%39,%40,%41,%42,%43,%44,%45,%46,%47,%48,%49,%50,%51,%52,%53,%54,%55,%56,%57,%58,%59}, {%60,%61,%62,%63}, %64, p, 1, 1, 0;\n}\n"
   : "+f"(d[0]),"+f"(d[1]),"+f"(d[2]),"+f"(d[3]),"+f"(d[4]),"+f"(d[5]),"+f"(d[6]),"+f"(d[7]),"+f"(d[8]),"+f"(d[9]),"+f"(d[10]),"+f"(d[11]),"+f"(d[12]),"+f"(d[13]),"+f"(d[14]),"+f"(d[15]),"+f"(d[16]),"+f"(d[17]),"+f"(d[18]),"+f"(d[19]),"+f"(d[20]),"+f"(d[21]),"+f"(d[22]),"+f"(d[23]),"+f"(d[24]),"+f"(d[25]),"+f"(d[26]),"+f"(d[27]),"+f"(d[28]),"+f"(d[29]),"+f"(d[30]),"+f"(d[31]),"+f"(d[32]),"+f"(d[33]),"+f"(d[34]),"+f"(d[35]),"+f"(d[36]),"+f"(d[37]),"+f"(d[38]),"+f"(d[39]),"+f"(d[40]),"+f"(d[41]),"+f"(d[42]),"+f"(d[43]),"+f"(d[44]),"+f"(d[45]),"+f"(d[46]),"+f"(d[47]),"+f"(d[48]),"+f"(d[49]),"+f"(d[50]),"+f"(d[51]),"+f"(d[52]),"+f"(d[53]),"+f"(d[54]),"+f"(d[55]),"+f"(d[56]),"+f"(d[57]),"+f"(d[58]),"+f"(d[59])
   : "r"(a[0]), "r"(a[1]), "r"(a[2]), "r"(a[3]), "l"(db), "r"(sd));
}
template<> __device__ __forceinline__ void wgmma_rs<112,0>(float* d, const uint32_t* a, uint64_t db, int sd) {
  asm volatile("{\n.reg .pred p;\nsetp.ne.b32 p, %61, 0;\nwgmma.mma_async.sync.aligned.m64n112k16.f32.bf16.bf16 {%0,%1,%2,%3,%4,%5,%6,%7,%8,%9,%10,%11,%12,%13,%14,%15,%16,%17,%18,%19,%20,%21,%22,%23,%24,%25,%26,%27,%28,%29,%30,%31,%32,%33,%34,%35,%36,%37,%38,%39,%40,%41,%42,%43,%44,%45,%46,%47,%48,%49,%50,%51,%52,%53,%54,%55}, {%56,%57,%58,%59}, %60, p, 1, 1, 0;\n}\n"
   : "+f"(d[0]),"+f"(d[1]),"+f"(d[2]),"+f"(d[3]),"+f"(d[4]),"+f"(d[5]),"+f"(d[6]),"+f"(d[7]),"+f"(d[8]),"+f"(d[9]),"+f"(d[10]),"+f"(d[11]),"+f"(d[12]),"+f"(d[13]),"+f"(d[14]),"+f"(d[15]),"+f"(d[16]),"+f"(d[17]),"+f"(d[18]),"+f"(d[19]),"+f"(d[20]),"+f"(d[21]),"+f"(d[22]),"+f"(d[23]),"+f"(d[24]),"+f"(d[25]),"+f"(d[26]),"+f"(d[27]),"+f"(d[28]),"+f"(d[29]),"+f"(d[30]),"+f"(d[31]),"+f"(d[32]),"+f"(d[33]),"+f"(d[34]),"+f"(d[35]),"+f"(d[36]),"+f"(d[37]),"+f"(d[38]),"+f"(d[39]),"+f"(d[40]),"+f"(d[41]),"+f"(d[42]),"+f"(d[43]),"+f"(d[44]),"+f"(d[45]),"+f"(d[46]),"+f"(d[47]),"+f"(d[48]),"+f"(d[49]),"+f"(d[50]),"+f"(d[51]),"+f"(d[52]),"+f"(d[53]),"+f"(d[54]),"+f"(d[55])
   : "r"(a[0]), "r"(a[1]), "r"(a[2]), "r"(a[3]), "l"(db), "r"(sd));
}
template<> __device__ __forceinline__ void wgmma_rs<104,0>(float* d, const uint32_t* a, uint64_t db, int sd) {
  asm volatile("{\n.reg .pred p;\nsetp.ne.b32 p, %57, 0;\nwgmma.mma_async.sync.aligned.m64n104k16.f32.bf16.bf16 {%0,%1,%2,%3,%4,%5,%6,%7,%8,%9,%10,%11,%12,%13,%14,%15,%16,%17,%18,%19,%20,%21,%22,%23,%24,%25,%26,%27,%28,%29,%30,%31,%32,%33,%34,%35,%36,%37,%38,%39,%40,%41,%42,%43,%44,%45,%46,%47,%48,%49,%50,%51}, {%52,%53,%54,%55}, %56, p, 1, 1, 0;\n}\n"
   : "+f"(d[0]),"+f"(d[1]),"+f"(d[2]),"+f"(d[3]),"+f"(d[4]),"+f"(d[5]),"+f"(d[6]),"+f"(d[7]),"+f"(d[8]),"+f"(d[9]),"+f"(d[10]),"+f"(d[11]),"+f"(d[12]),"+f"(d[13]),"+f"(d[14]),"+f"(d[15]),"+f"(d[16]),"+f"(d[17]),"+f"(d[18]),"+f"(d[19]),"+f"(d[20]),"+f"(d[21]),"+f"(d[22]),"+f"(d[23]),"+f"(d[24]),"+f"(d[25]),"+f"(d[26]),"+f"(d[27]),"+f"(d[28]),"+f"(d[29]),"+f"(d[30]),"+f"(d[31]),"+f"(d[32]),"+f"(d[33]),"+f"(d[34]),"+f"(d[35]),"+f"(d[36]),"+f"(d[37]),"+f"(d[38]),"+f"(d[39]),"+f"(d[40]),"+f"(d[41]),"+f"(d[42]),"+f"(d[43]),"+f"(d[44]),"+f"(d[45]),"+f"(d[46]),"+f"(d[47]),"+f"(d[48]),"+f"(d[49]),"+f"(d[50]),"+f"(d[51])
   : "r"(a[0]), "r"(a[1]), "r"(a[2]), "r"(a[3]), "l"(db), "r"(sd));
}
template<> __device__ __forceinline__ void wgmma_rs<96,0>(float* d, const uint32_t* a, uint64_t db, int sd) {
  asm volatile("{\n.reg .pred p;\nsetp.ne.b32 p, %53, 0;\nwgmma.mma_async.sync.aligned.m64n96k16.f32.bf16.bf16 {%0,%1,%2,%3,%4,%5,%6,%7,%8,%9,%10,%11,%12,%13,%14,%15,%16,%17,%18,%19,%20,%21,%22,%23,%24,%25,%26,%27,%28,%29,%30,%31,%32,%33,%34,%35,%36,%37,%38,%39,%40,%41,%42,%43,%44,%45,%46,%47}, {%48,%49,%50,%51}, %52, p, 1, 1, 0;\n}\n"
   : "+f"(d[0]),"+f"(d[1]),"+f"(d[2]),"+f"(d[3]),"+f"(d[4]),"+f"(d[5]),"+f"(d[6]),"+f"(d[7]),"+f"(d[8]),"+f"(d[9]),"+f"(d[10]),"+f"(d[11]),"+f"(d[12]),"+f"(d[13]),"+f"(d[14]),"+f"(d[15]),"+f"(d[16]),"+f"(d[17]),"+f"(d[18]),"+f"(d[19]),"+f"(d[20]),"+f"(d[21]),"+f"(d[22]),"+f"(d[23]),"+f"(d[24]),"+f"(d[25]),"+f"(d[26]),"+f"(d[27]),"+f"(d[28]),"+f"(d[29]),"+f"(d[30]),"+f"(d[31]),"+f"(d[32]),"+f"(d[33]),"+f"(d[34]),"+f"(d[35]),"+f"(d[36]),"+f"(d[37]),"+f"(d[38]),"+f"(d[39]),"+f"(d[40]),"+f"(d[41]),"+f"(d[42]),"+f"(d[43]),"+f"(d[44]),"+f"(d[45]),"+f"(d[46]),"+f"(d[47])
   : "r"(a[0]), "r"(a[1]), "r"(a[2]), "r"(a[3]), "l"(db), "r"(sd));
}
template<> __device__ __forceinline__ void wgmma_rs<88,0>(float* d, const uint32_t* a, uint64_t db, int sd) {
  asm volatile("{\n.reg .pred p;\nsetp.ne.b32 p, %49, 0;\nwgmma.mma_async.sync.aligned.m64n88k16.f32.bf16.bf16 {%0,%1,%2,%3,%4,%5,%6,%7,%8,%9,%10,%11,%12,%13,%14,%15,%16,%17,%18,%19,%20,%21,%22,%23,%24,%25,%26,%27,%28,%29,%30,%31,%32,%33,%34,%35,%36,%37,%38,%39,%40,%41,%42,%43}, {%44,%45,%46,%47}, %48, p, 1, 1, 0;\n}\n"
   : "+f"(d[0]),"+f"(d[1]),"+f"(d[2]),"+f"(d[3]),"+f"(d[4]),"+f"(d[5]),"+f"(d[6]),"+f"(d[7]),"+f"(d[8]),"+f"(d[9]),"+f"(d[10]),"+f"(d[11]),"+f"(d[12]),"+f"(d[13]),"+f"(d[14]),"+f"(d[15]),"+f"(d[16]),"+f"(d[17]),"+f"(d[18]),"+f"(d[19]),"+f"(d[20]),"+f"(d[21]),"+f"(d[22]),"+f"(d[23]),"+f"(d[24]),"+f"(d[25]),"+f"(d[26]),"+f"(d[27]),"+f"(d[28]),"+f"(d[29]),"+f"(d[30]),"+f"(d[31]),"+f"(d[32]),"+f"(d[33]),"+f"(d[34]),"+f"(d[35]),"+f"(d[36]),"+f"(d[37]),"+f"(d[38]),"+f"(d[39]),"+f"(d[40]),"+f"(d[41]),"+f"(d[42]),"+f"(d[43])
   : "r"(a[0]), "r"(a[1]), "r"(a[2]), "r"(a[3]), "l"(db), "r"(sd));
}
template<> __device__ __forceinline__ void wgmma_rs<80,0>(float* d, const uint32_t* a, uint64_t db, int sd) {
  asm volatile("{\n.reg .pred p;\nsetp.ne.b32 p, %45, 0;\nwgmma.mma_async.sync.aligned.m64n80k16.f32.bf16.bf16 {%0,%1,%2,%3,%4,%5,%6,%7,%8,%9,%10,%11,%12,%13,%14,%15,%16,%17,%18,%19,%20,%21,%22,%23,%24,%25,%26,%27,%28,%29,%30,%31,%32,%33,%34,%35,%36,%37,%38,%39}, {%40,%41,%42,%43}, %44, p, 1, 1, 0;\n}\n"
   : "+f"(d[0]),"+f"(d[1]),"+f"(d[2]),"+f"(d[3]),"+f"(d[4]),"+f"(d[5]),"+f"(d[6]),"+f"(d[7]),"+f"(d[8]),"+f"(d[9]),"+f"(d[10]),"+f"(d[11]),"+f"(d[12]),"+f"(d[13]),"+f"(d[14]),"+f"(d[15]),"+f"(d[16]),"+f"(d[17]),"+f"(d[18]),"+f"(d[19]),"+f"(d[20]),"+f"(d[21]),"+f"(d[22]),"+f"(d[23]),"+f"(d[24]),"+f"(d[25]),"+f"(d[26]),"+f"(d[27]),"+f"(d[28]),"+f"(d[29]),"+f"(d[30]),"+f"(d[31]),"+f"(d[32]),"+f"(d[33]),"+f"(d[34]),"+f"(d[35]),"+f"(d[36]),"+f"(d[37]),"+f"(d[38]),"+f"(d[39])
   : "r"(a[0]), "r"(a[1]), "r"(a[2]), "r"(a[3]), "l"(db), "r"(sd));
}
template<> __device__ __forceinline__ void wgmma_rs<72,0>(float* d, const uint32_t* a, uint64_t db, int sd) {
  asm volatile("{\n.reg .pred p;\nsetp.ne.b32 p, %41, 0;\nwgmma.mma_async.sync.aligned.m64n72k16.f32.bf16.bf16 {%0,%1,%2,%3,%4,%5,%6,%7,%8,%9,%10,%11,%12,%13,%14,%15,%16,%17,%18,%19,%20,%21,%22,%23,%24,%25,%26,%27,%28,%29,%30,%31,%32,%33,%34,%35}, {%36,%37,%38,%39}, %40, p, 1, 1, 0;\n}\n"
   : "+f"(d[0]),"+f"(d[1]),"+f"(d[2]),"+f"(d[3]),"+f"(d[4]),"+f"(d[5]),"+f"(d[6]),"+f"(d[7]),"+f"(d[8]),"+f"(d[9]),"+f"(d[10]),"+f"(d[11]),"+f"(d[12]),"+f"(d[13]),"+f"(d[14]),"+f"(d[15]),"+f"(d[16]),"+f"(d[17]),"+f"(d[18]),"+f"(d[19]),"+f"(d[20]),"+f"(d[21]),"+f"(d[22]),"+f"(d[23]),"+f"(d[24]),"+f"(d[25]),"+f"(d[26]),"+f"(d[27]),"+f"(d[28]),"+f"(d[29]),"+f"(d[30]),"+f"(d[31]),"+f"(d[32]),"+f"(d[33]),"+f"(d[34]),"+f"(d[35])
   : "r"(a[0]), "r"(a[1]), "r"(a[2]), "r"(a[3]), "l"(db), "r"(sd));
}
template<> __device__ __forceinline__ void wgmma_rs<64,0>(float* d, const uint32_t* a, uint64_t db, int sd) {
  asm volatile("{\n.reg .pred p;\nsetp.ne.b32 p, %37, 0;\nwgmma.mma_async.sync.aligned.m64n64k16.f32.bf16.bf16 {%0,%1,%2,%3,%4,%5,%6,%7,%8,%9,%10,%11,%12,%13,%14,%15,%16,%17,%18,%19,%20,%21,%22,%23,%24,%25,%26,%27,%28,%29,%30,%31}, {%32,%33,%34,%35}, %36, p, 1, 1, 0;\n}\n"
   : "+f"(d[0]),"+f"(d[1]),"+f"(d[2]),"+f"(d[3]),"+f"(d[4]),"+f"(d[5]),"+f"(d[6]),"+f"(d[7]),"+f"(d[8]),"+f"(d[9]),"+f"(d[10]),"+f"(d[11]),"+f"(d[12]),"+f"(d[13]),"+f"(d[14]),"+f"(d[15]),"+f"(d[16]),"+f"(d[17]),"+f"(d[18]),"+f"(d[19]),"+f"(d[20]),"+f"(d[21]),"+f"(d[22]),"+f"(d[23]),"+f"(d[24]),"+f"(d[25]),"+f"(d[26]),"+f"(d[27]),"+f"(d[28]),"+f"(d[29]),"+f"(d[30]),"+f"(d[31])
   : "r"(a[0]), "r"(a[1]), "r"(a[2]), "r"(a[3]), "l"(db), "r"(sd));
}
template<> __device__ __forceinline__ void wgmma_ss<64,0,1>(float* d, uint64_t da, uint64_t db, int sd) {
  asm volatile("{\n.reg .pred p;\nsetp.ne.b32 p, %34, 0;\nwgmma.mma_async.sync.aligned.m64n64k16.f32.bf16.bf16 {%0,%1,%2,%3,%4,%5,%6,%7,%8,%9,%10,%11,%12,%13,%14,%15,%16,%17,%18,%19,%20,%21,%22,%23,%24,%25,%26,%27,%28,%29,%30,%31}, %32, %33, p, 1, 1, 0, 1;\n}\n"
   : "+f"(d[0]),"+f"(d[1]),"+f"(d[2]),"+f"(d[3]),"+f"(d[4]),"+f"(d[5]),"+f"(d[6]),"+f"(d[7]),"+f"(d[8]),"+f"(d[9]),"+f"(d[10]),"+f"(d[11]),"+f"(d[12]),"+f"(d[13]),"+f"(d[14]),"+f"(d[15]),"+f"(d[16]),"+f"(d[17]),"+f"(d[18]),"+f"(d[19]),"+f"(d[20]),"+f"(d[21]),"+f"(d[22]),"+f"(d[23]),"+f"(d[24]),"+f"(d[25]),"+f"(d[26]),"+f"(d[27]),"+f"(d[28]),"+f"(d[29]),"+f"(d[30]),"+f"(d[31])
   : "l"(da), "l"(db), "r"(sd));
}
template<> __device__ __forceinline__ void wgmma_ss<64,1,1>(float* d, uint64_t da, uint64_t db, int sd) {
  asm volatile("{\n.reg .pred p;\nsetp.ne.b32 p, %34, 0;\nwgmma.mma_async.sync.aligned.m64n64k16.f32.bf16.bf16 {%0,%1,%2,%3,%4,%5,%6,%7,%8,%9,%10,%11,%12,%13,%14,%15,%16,%17,%18,%19,%20,%21,%22,%23,%24,%25,%26,%27,%28,%29,%30,%31}, %32, %33, p, 1, 1, 1, 1;\n}\n"
   : "+f"(d[0]),"+f"(d[1]),"+f"(d[2]),"+f"(d[3]),"+f"(d[4]),"+f"(d[5]),"+f"(d[6]),"+f"(d[7]),"+f"(d[8]),"+f"(d[9]),"+f"(d[10]),"+f"(d[11]),"+f"(d[12]),"+f"(d[13]),"+f"(d[14]),"+f"(d[15]),"+f"(d[16]),"+f"(d[17]),"+f"(d[18]),"+f"(d[19]),"+f"(d[20]),"+f"(d[21]),"+f"(d[22]),"+f"(d[23]),"+f"(d[24]),"+f"(d[25]),"+f"(d[26]),"+f"(d[27]),"+f"(d[28]),"+f"(d[29]),"+f"(d[30]),"+f"(d[31])
   : "l"(da), "l"(db), "r"(sd));
}
template<> __device__ __forceinline__ void wgmma_ss<192,0,1>(float* d, uint64_t da, uint64_t db, int sd) {
  asm volatile("{\n.reg .pred p;\nsetp.ne.b32 p, %98, 0;\nwgmma.mma_async.sync.aligned.m64n192k16.f32.bf16.bf16 {%0,%1,%2,%3,%4,%5,%6,%7,%8,%9,%10,%11,%12,%13,%14,%15,%16,%17,%18,%19,%20,%21,%22,%23,%24,%25,%26,%27,%28,%29,%30,%31,%32,%33,%34,%35,%36,%37,%38,%39,%40,%41,%42,%43,%44,%45,%46,%47,%48,%49,%50,%51,%52,%53,%54,%55,%56,%57,%58,%59,%60,%61,%62,%63,%64,%65,%66,%67,%68,%69,%70,%71,%72,%73,%74,%75,%76,%77,%78,%79,%80,%81,%82,%83,%84,%85,%86,%87,%88,%89,%90,%91,%92,%93,%94,%95}, %96, %97, p, 1, 1, 0, 1;\n}\n"
   : "+f"(d[0]),"+f"(d[1]),"+f"(d[2]),"+f"(d[3]),"+f"(d[4]),"+f"(d[5]),"+f"(d[6]),"+f"(d[7]),"+f"(d[8]),"+f"(d[9]),"+f"(d[10]),"+f"(d[11]),"+f"(d[12]),"+f"(d[13]),"+f"(d[14]),"+f"(d[15]),"+f"(d[16]),"+f"(d[17]),"+f"(d[18]),"+f"(d[19]),"+f"(d[20]),"+f"(d[21]),"+f"(d[22]),"+f"(d[23]),"+f"(d[24]),"+f"(d[25]),"+f"(d[26]),"+f"(d[27]),"+f"(d[28]),"+f"(d[29]),"+f"(d[30]),"+f"(d[31]),"+f"(d[32]),"+f"(d[33]),"+f"(d[34]),"+f"(d[35]),"+f"(d[36]),"+f"(d[37]),"+f"(d[38]),"+f"(d[39]),"+f"(d[40]),"+f"(d[41]),"+f"(d[42]),"+f"(d[43]),"+f"(d[44]),"+f"(d[45]),"+f"(d[46]),"+f"(d[47]),"+f"(d[48]),"+f"(d[49]),"+f"(d[50]),"+f"(d[51]),"+f"(d[52]),"+f"(d[53]),"+f"(d[54]),"+f"(d[55]),"+f"(d[56]),"+f"(d[57]),"+f"(d[58]),"+f"(d[59]),"+f"(d[60]),"+f"(d[61]),"+f"(d[62]),"+f"(d[63]),"+f"(d[64]),"+f"(d[65]),"+f"(d[66]),"+f"(d[67]),"+f"(d[68]),"+f"(d[69]),"+f"(d[70]),"+f"(d[71]),"+f"(d[72]),"+f"(d[73]),"+f"(d[74]),"+f"(d[75]),"+f"(d[76]),"+f"(d[77]),"+f"(d[78]),"+f"(d[79]),"+f"(d[80]),"+f"(d[81]),"+f"(d[82]),"+f"(d[83]),"+f"(d[84]),"+f"(d[85]),"+f"(d[86]),"+f"(d[87]),"+f"(d[88]),"+f"(d[89]),"+f"(d[90]),"+f"(d[91]),"+f"(d[92]),"+f"(d[93]),"+f"(d[94]),"+f"(d[95])
   : "l"(da), "l"(db), "r"(sd));
}
template<> __device__ __forceinline__ void wgmma_ss<192,1,1>(float* d, uint64_t da, uint64_t db, int sd) {
  asm volatile("{\n.reg .pred p;\nsetp.ne.b32 p, %98, 0;\nwgmma.mma_async.sync.aligned.m64n192k16.f32.bf16.bf16 {%0,%1,%2,%3,%4,%5,%6,%7,%8,%9,%10,%11,%12,%13,%14,%15,%16,%17,%18,%19,%20,%21,%22,%23,%24,%25,%26,%27,%28,%29,%30,%31,%32,%33,%34,%35,%36,%37,%38,%39,%40,%41,%42,%43,%44,%45,%46,%47,%48,%49,%50,%51,%52,%53,%54,%55,%56,%57,%58,%59,%60,%61,%62,%63,%64,%65,%66,%67,%68,%69,%70,%71,%72,%73,%74,%75,%76,%77,%78,%79,%80,%81,%82,%83,%84,%85,%86,%87,%88,%89,%90,%91,%92,%93,%94,%95}, %96, %97, p, 1, 1, 1, 1;\n}\n"
   : "+f"(d[0]),"+f"(d[1]),"+f"(d[2]),"+f"(d[3]),"+f"(d[4]),"+f"(d[5]),"+f"(d[6]),"+f"(d[7]),"+f"(d[8]),"+f"(d[9]),"+f"(d[10]),"+f"(d[11]),"+f"(d[12]),"+f"(d[13]),"+f"(d[14]),"+f"(d[15]),"+f"(d[16]),"+f"(d[17]),"+f"(d[18]),"+f"(d[19]),"+f"(d[20]),"+f"(d[21]),"+f"(d[22]),"+f"(d[23]),"+f"(d[24]),"+f"(d[25]),"+f"(d[26]),"+f"(d[27]),"+f"(d[28]),"+f"(d[29]),"+f"(d[30]),"+f"(d[31]),"+f"(d[32]),"+f"(d[33]),"+f"(d[34]),"+f"(d[35]),"+f"(d[36]),"+f"(d[37]),"+f"(d[38]),"+f"(d[39]),"+f"(d[40]),"+f"(d[41]),"+f"(d[42]),"+f"(d[43]),"+f"(d[44]),"+f"(d[45]),"+f"(d[46]),"+f"(d[47]),"+f"(d[48]),"+f"(d[49]),"+f"(d[50]),"+f"(d[51]),"+f"(d[52]),"+f"(d[53]),"+f"(d[54]),"+f"(d[55]),"+f"(d[56]),"+f"(d[57]),"+f"(d[58]),"+f"(d[59]),"+f"(d[60]),"+f"(d[61]),"+f"(d[62]),"+f"(d[63]),"+f"(d[64]),"+f"(d[65]),"+f"(d[66]),"+f"(d[67]),"+f"(d[68]),"+f"(d[69]),"+f"(d[70]),"+f"(d[71]),"+f"(d[72]),"+f"(d[73]),"+f"(d[74]),"+f"(d[75]),"+f"(d[76]),"+f"(d[77]),"+f"(d[78]),"+f"(d[79]),"+f"(d[80]),"+f"(d[81]),"+f"(d[82]),"+f"(d[83]),"+f"(d[84]),"+f"(d[85]),"+f"(d[86]),"+f"(d[87]),"+f"(d[88]),"+f"(d[89]),"+f"(d[90]),"+f"(d[91]),"+f"(d[92]),"+f"(d[93]),"+f"(d[94]),"+f"(d[95])
   : "l"(da), "l"(db), "r"(sd));
}

#define HOLD 0
template <bool TR>
__device__ __forceinline__ void gemm_section(float* acc, float& mean0, float& mean1, float& rstd0, float& rstd1,
                                             uint32_t sb, int layer, int rb, int hg, int wg, int w, int lane) {
  const uint32_t bar = sb + SM_BAR;
  const int g = lane >> 2, t = lane & 3;
  const bool leader = (w == 0) && (lane == 0);
  const int row0 = 64 * wg + 16 * w;
  auto issue = [&](int c, int slot) {
    mbar_wait(bar + 8 * (B_XF + c), layer);
    mbar_wait(bar + 8 * (B_KVF + c), layer);
    const uint64_t da = mkdesc(sb + SM_X + c * 16384 + wg * 8192, TR ? 8192 : 16, 1024, 1);
    const uint64_t db = mkdesc(sb + SM_W + slot * 24576, 8192, 1024, 1);
    wg_fence();
#pragma unroll
    for (int ks = 0; ks < 4; ks++) wgmma_ss<192, TR ? 1 : 0, 1>(acc, da + (TR ? ks * 128 : ks * 2), db + ks * 128, (c | ks) != 0);
    wg_commit();
  };
  auto step = [&](int c, int slot) {
    issue(c, slot);
    wg_wait<1>();
    if (leader) mbar_arrive(bar + 8 * (B_KVE + c - 1));
  };
  issue(0, 0);
  if (threadIdx.x == 0) TS(2 + layer * 20 + 0);
  if (threadIdx.x == 128 && layer == 1) TS(60);
  step(1, 1); step(2, 2); step(3, 0);
  issue(4, 1);
  mbar_wait(bar + 8 * B_EP, 0);
  const uint32_t tag = 2 * lds32(sb + SM_EP) + layer + 1;
  {
    mbar_wait(bar + 8 * (B_XF + hg), layer);
    uint32_t A[16];
    const uint32_t xb = sb + SM_X + hg * 16384 + wg * 8192;
#pragma unroll
    for (int ks = 0; ks < 4; ks++) {
      if (!TR) {
        const int row = 16 * w + (lane & 15), kc = 2 * ks + (lane >> 4);
        ldsm4(&A[4 * ks], xb + row * 128 + ((kc ^ (row & 7)) << 4));
      } else {
        const int k = 16 * ks + (lane & 7) + 8 * (lane >> 4), pc = 2 * w + ((lane >> 3) & 1);
        ldsm4t(&A[4 * ks], xb + k * 128 + ((pc ^ (k & 7)) << 4));
      }
    }
    float s0 = 0.f, q0 = 0.f, s1 = 0.f, q1 = 0.f;
#pragma unroll
    for (int i = 0; i < 16; i += 2) {
      const float a = bf_lo(A[i]), b = bf_hi(A[i]), c_ = bf_lo(A[i + 1]), d = bf_hi(A[i + 1]);
      s0 += a + b; q0 = fmaf(a, a, q0); q0 = fmaf(b, b, q0);
      s1 += c_ + d; q1 = fmaf(c_, c_, q1); q1 = fmaf(d, d, q1);
    }
#pragma unroll
    for (int o = 1; o <= 2; o <<= 1) {
      s0 += __shfl_xor_sync(~0u, s0, o); q0 += __shfl_xor_sync(~0u, q0, o);
      s1 += __shfl_xor_sync(~0u, s1, o); q1 += __shfl_xor_sync(~0u, q1, o);
    }
    if (t < 2)
      st_tagged(&g_part[(rb * 8 + hg) * 128 + row0 + g + 8 * t], __float_as_uint(t ? s1 : s0), __float_as_uint(t ? q1 : q0), tag);
  }
  wg_wait<1>();
  if (leader) mbar_arrive(bar + 8 * (B_KVE + 3));
  step(5, 2);
  issue(6, 0);
  wg_wait<1>();
  const uint4* psrc = &g_part[(rb * 8 + 2 * t) * 128 + row0 + g];
  uint4 a0 = ld_tagged(psrc), a1 = ld_tagged(psrc + 8), b0 = ld_tagged(psrc + 128), b1 = ld_tagged(psrc + 136);
  if (wg == 0) bar_sync(5, 256);
  issue(7, 1);
  if (wg == 1) bar_arrive(5, 256);
  int it = 0;
  while (!__all_sync(~0u, a0.y == tag && a0.w == tag && a1.y == tag && a1.w == tag && b0.y == tag && b0.w == tag && b1.y == tag && b1.w == tag) &&
         ++it < (1 << 20)) {
    a0 = ld_tagged(psrc); a1 = ld_tagged(psrc + 8); b0 = ld_tagged(psrc + 128); b1 = ld_tagged(psrc + 136);
  }
  float s0 = __uint_as_float(a0.x) + __uint_as_float(b0.x), q0 = __uint_as_float(a0.z) + __uint_as_float(b0.z);
  float s1 = __uint_as_float(a1.x) + __uint_as_float(b1.x), q1 = __uint_as_float(a1.z) + __uint_as_float(b1.z);
#pragma unroll
  for (int o = 1; o <= 2; o <<= 1) {
    s0 += __shfl_xor_sync(~0u, s0, o); q0 += __shfl_xor_sync(~0u, q0, o);
    s1 += __shfl_xor_sync(~0u, s1, o); q1 += __shfl_xor_sync(~0u, q1, o);
  }
  mean0 = s0 * (1.f / DM); mean1 = s1 * (1.f / DM);
  rstd0 = rsqrt_approx(fmaxf(q0 * (1.f / DM) - mean0 * mean0, 0.f) + 1e-5f);
  rstd1 = rsqrt_approx(fmaxf(q1 * (1.f / DM) - mean1 * mean1, 0.f) + 1e-5f);
  mbar_wait(bar + 8 * B_CSF, 0);
  wg_wait<0>();
}

__device__ __forceinline__ void attn_phase(const Params& p, uint32_t sb, int layer, int rb, int hg, int wg, int w) {
  const int lane = opaque_tid() & 31;
  const int g = lane >> 2, t = lane & 3;
  const uint32_t bar = sb + SM_BAR;
  const int row0 = 64 * wg + 16 * w;
  const bool leader = (w == 0) && (lane == 0);
  float acc[96];
  float2 cs[24];
  float mean0, mean1, rstd0, rstd1;
  if (layer) gemm_section<true>(acc, mean0, mean1, rstd0, rstd1, sb, layer, rb, hg, wg, w, lane);
  else gemm_section<false>(acc, mean0, mean1, rstd0, rstd1, sb, layer, rb, hg, wg, w, lane);
  const uint32_t tag = 2 * lds32(sb + SM_EP) + layer + 1;
  if (threadIdx.x == 0) TS(2 + layer * 20 + 1);
  if (leader) mbar_arrive(bar + 8 * B_QDONE);
#pragma unroll
  for (int j = 8; j < 24; j++) cs[j] = lds64f(sb + SM_CS + 4 * (8 * j + 2 * t));

  uint32_t kb[4][8], vb[4][8], qa[4][4];
  {
    const float nm0 = -mean0 * rstd0, nm1 = -mean1 * rstd1;
    const int st_row = row0 + (lane & 7) + 8 * ((lane >> 3) & 1);
    const uint32_t st_base = sb + SM_KVX + st_row * 256;
    const bool sender = (wg == 1 && w == 3 && rb < 15);
    uint4* halo = &g_halo[(rb * 8 + hg) * 384 + lane];
    if (wg == 0 && w == 3) bar_sync(6, 64);
    uint32_t r[4][2][4];
#pragma unroll
    for (int h = 0; h < 4; h++) {
#pragma unroll
      for (int kv = 0; kv < 2; kv++) {
#pragma unroll
        for (int dh = 0; dh < 2; dh++) {
          const int j = 8 + kv * 8 + 2 * h + dh;
          const float2 c2 = cs[j];
          const float v0 = fmaf(acc[4 * j + 0], rstd0, nm0 * c2.x), v1 = fmaf(acc[4 * j + 1], rstd0, nm0 * c2.y);
          const float v2 = fmaf(acc[4 * j + 2], rstd1, nm1 * c2.x), v3 = fmaf(acc[4 * j + 3], rstd1, nm1 * c2.y);
          r[h][kv][2 * dh] = packbf(v0, v1);
          r[h][kv][2 * dh + 1] = packbf(v2, v3);
        }
      }
      if (sender) {
        st_tagged3(halo + (3 * h) * 32, r[h][0][0], r[h][0][1], r[h][0][2], tag);
        st_tagged3(halo + (3 * h + 1) * 32, r[h][0][3], r[h][1][0], r[h][1][1], tag);
        st_tagged3(halo + (3 * h + 2) * 32, r[h][1][2], r[h][1][3], 0u, tag);
      }
    }
    if (wg == 1 && w == 3) bar_arrive(6, 64);
    if (layer == 1 && threadIdx.x == 224) TS(47);
#pragma unroll
    for (int j = 0; j < 8; j++) cs[j] = lds64f(sb + SM_CS + 4 * (8 * j + 2 * t));
    mbar_wait(bar + 8 * B_QDONE, layer);
#pragma unroll
    for (int h = 0; h < 4; h++) {
#pragma unroll
      for (int kv = 0; kv < 2; kv++) {
        const int chunk = 4 * h + 2 * kv + (lane >> 4);
        stsm4(st_base + (((chunk & 8) | ((chunk ^ st_row) & 7)) << 4), r[h][kv][0], r[h][kv][1], r[h][kv][2], r[h][kv][3]);
      }
      kb[h][4] = r[h][0][0]; kb[h][5] = r[h][0][2]; kb[h][6] = r[h][0][1]; kb[h][7] = r[h][0][3];
      vb[h][4] = movm_t(r[h][1][0]); vb[h][5] = movm_t(r[h][1][1]); vb[h][6] = movm_t(r[h][1][2]); vb[h][7] = movm_t(r[h][1][3]);
    }
    if (layer == 1 && threadIdx.x == 0) TS(45);
#pragma unroll
    for (int h = 0; h < 4; h++) {
#pragma unroll
      for (int dh = 0; dh < 2; dh++) {
        const int j = 2 * h + dh;
        const float2 c2 = cs[j];
        qa[h][2 * dh] = packbf(fmaf(-mean0, c2.x, acc[4 * j + 0]), fmaf(-mean0, c2.y, acc[4 * j + 1]));
        qa[h][2 * dh + 1] = packbf(fmaf(-mean1, c2.x, acc[4 * j + 2]), fmaf(-mean1, c2.y, acc[4 * j + 3]));
      }
    }
  }
  bar_sync(1, 256);
  if (threadIdx.x == 0) TS(2 + layer * 20 + 2);
  {
    const uint32_t own_base = sb + SM_KVX + row0 * 256;
    const int mi = lane >> 3;
    const int r = 8 * (mi >> 1) + (lane & 7), r2 = 8 * (mi & 1) + (lane & 7);
    if (row0 != 0) {
#pragma unroll
      for (int h = 0; h < 4; h++) {
        const int ch = 4 * h + (mi & 1), ch2 = 4 * h + 2 + (mi >> 1);
        ldsm4(&kb[h][0], own_base - 16 * 256 + r * 256 + (((ch & 8) | ((ch ^ r) & 7)) << 4));
        ldsm4t(&vb[h][0], own_base - 16 * 256 + r2 * 256 + (((ch2 & 8) | ((ch2 ^ r2) & 7)) << 4));
      }
    } else if (rb > 0) {
      const uint4* src = &g_halo[((rb - 1) * 8 + hg) * 384 + lane];
      uint4 hv[12];
      int it = 0;
      bool ok;
      do {
        ok = true;
#pragma unroll
        for (int i = 0; i < 12; i++) hv[i] = ld_tagged(src + i * 32);
#pragma unroll
        for (int i = 0; i < 12; i++) ok = ok && hv[i].w == tag;
      } while (!__all_sync(~0u, ok) && ++it < (1 << 20));
      if (lane == 0) mbar_arrive(bar + 8 * B_HF);
#pragma unroll
      for (int h = 0; h < 4; h++) {
        kb[h][0] = hv[3 * h].x; kb[h][1] = hv[3 * h].z; kb[h][2] = hv[3 * h].y; kb[h][3] = hv[3 * h + 1].x;
        vb[h][0] = movm_t(hv[3 * h + 1].y); vb[h][1] = movm_t(hv[3 * h + 1].z);
        vb[h][2] = movm_t(hv[3 * h + 2].x); vb[h][3] = movm_t(hv[3 * h + 2].y);
      }
    } else {
#pragma unroll
      for (int h = 0; h < 4; h++)
#pragma unroll
        for (int k = 0; k < 4; k++) kb[h][k] = vb[h][k] = 0u;
    }
    if (threadIdx.x == 0) TS(2 + layer * 20 + 4);
  }

  const bool first = (rb == 0 && wg == 0 && w == 0);
  const int e = t - (g >> 1);
  const bool par = g & 1, epos = e >= 1;
  const uint32_t pmask = par ? 0xffff0000u : 0x0000ffffu;
  const uint32_t mB0 = epos ? pmask : 0u, mB1 = epos ? 0u : pmask;
  const float cl2 = 0.25f * 1.4426950408889634f;
  const float sc0 = rstd0 * cl2, sc1 = rstd1 * cl2;
  const float NEG = -INFINITY;
  float vA0[4], vB0[4], vA1[4], vB1[4];
#pragma unroll
  for (int h = 0; h < 4; h++) {
    float S[4][4];
#pragma unroll
    for (int j = 0; j < 4; j++) {
      S[j][0] = S[j][1] = S[j][2] = S[j][3] = 0.f;
      mma_bf16(S[j], qa[h], kb[h][2 * j], kb[h][2 * j + 1]);
    }
    vA0[h] = par ? S[1][1] : S[1][0];
    vB0[h] = epos ? (par ? S[0][1] : S[0][0]) : (par ? S[2][1] : S[2][0]);
    vA1[h] = par ? S[2][3] : S[2][2];
    vB1[h] = epos ? (par ? S[1][3] : S[1][2]) : (par ? S[3][3] : S[3][2]);
    if (first) { vA0[h] = NEG; if (epos) { vB0[h] = NEG; vB1[h] = NEG; } }
  }
  float m0[4], m1[4];
#pragma unroll
  for (int h = 0; h < 4; h++) { m0[h] = fmaxf(vA0[h], vB0[h]); m1[h] = fmaxf(vA1[h], vB1[h]); }
#pragma unroll
  for (int o = 1; o <= 2; o <<= 1) {
#pragma unroll
    for (int h = 0; h < 4; h++) {
      m0[h] = fmaxf(m0[h], __shfl_xor_sync(~0u, m0[h], o));
      m1[h] = fmaxf(m1[h], __shfl_xor_sync(~0u, m1[h], o));
    }
  }
  float O0[4][4], O1[4][4], Z[4][4];
#pragma unroll
  for (int h = 0; h < 4; h++) {
    const float mm0 = -m0[h] * sc0, mm1 = -m1[h] * sc1;
    const float pA0 = ex2(fmaf(vA0[h], sc0, mm0)), pB0 = ex2(fmaf(vB0[h], sc0, mm0));
    const float pA1 = ex2(fmaf(vA1[h], sc1, mm1)), pB1 = ex2(fmaf(vB1[h], sc1, mm1));
    const uint32_t hA0 = packbf(pA0, pA0), hB0 = packbf(pB0, pB0), hA1 = packbf(pA1, pA1), hB1 = packbf(pB1, pB1);
    const uint32_t P0[4] = {hB0 & mB0, 0u, hA0 & pmask, hB1 & mB0};
    const uint32_t P1[4] = {hB0 & mB1, hA1 & pmask, 0u, hB1 & mB1};
#pragma unroll
    for (int k = 0; k < 4; k++) O0[h][k] = O1[h][k] = Z[h][k] = 0.f;
    mma_bf16(O0[h], P0, vb[h][0], vb[h][1]); mma_bf16(O1[h], P0, vb[h][2], vb[h][3]); mma_bf16(Z[h], P0, 0x3f803f80u, 0x3f803f80u);
    mma_bf16(O0[h], P1, vb[h][4], vb[h][5]); mma_bf16(O1[h], P1, vb[h][6], vb[h][7]); mma_bf16(Z[h], P1, 0x3f803f80u, 0x3f803f80u);
  }
  const uint32_t ob = sb + SM_OST + wg * 8192;
  const int o_row = 16 * w + (lane & 7) + 8 * ((lane >> 3) & 1);
#pragma unroll
  for (int h = 0; h < 4; h++) {
    const float i0 = rcp_approx(Z[h][0]), i1 = rcp_approx(Z[h][2]);
    const int ch = 2 * h + (lane >> 4);
    stsm4(ob + o_row * 128 + ((ch ^ (o_row & 7)) << 4), packbf(O0[h][0] * i0, O0[h][1] * i0), packbf(O0[h][2] * i1, O0[h][3] * i1),
          packbf(O1[h][0] * i0, O1[h][1] * i0), packbf(O1[h][2] * i1, O1[h][3] * i1));
  }
  if (threadIdx.x == 0) TS(2 + layer * 20 + 5);
  fence_async_smem();
  bar_sync(2 + wg, 128);
  if (w == 0 && elect_one()) {
    tma_st(&p.mapO, hg * 64, rb * 128 + wg * 64, ob);
    bulk_commit();
    mbar_arrive(bar + 8 * B_AD);
    bulk_wait_all();
    red_relaxed(&g_cnt[(C_O + rb) * 32]);
    mbar_arrive(bar + 8 * B_OST);
    if (threadIdx.x == 0) TS(2 + layer * 20 + 6);
  }
}

__device__ __forceinline__ void proj_phase(const Params& p, uint32_t sb, int layer, int rb, int q, int wg, int w) {
  const int lane = opaque_tid() & 31;
  const bool TR = layer != 0;
  const int t = lane & 3;
  const uint32_t bar = sb + SM_BAR;
  const uint32_t rbx = sb + SM_R + wg * 8192;
  uint32_t res[16];
  mbar_wait(bar + 8 * B_RF, layer);
  if (threadIdx.x == 0) TS(2 + layer * 20 + 7);
  if (!TR) {
#pragma unroll
    for (int j = 0; j < 8; j += 2) {
      const int mi = lane >> 3;
      const int row = 16 * w + (lane & 7) + 8 * (mi & 1), ch = j + (mi >> 1);
      ldsm4(&res[2 * j], rbx + row * 128 + ((ch ^ (row & 7)) << 4));
    }
  } else {
#pragma unroll
    for (int j = 0; j < 8; j += 2) {
      const int mi = lane >> 3;
      const int line = 8 * (j + (mi >> 1)) + (lane & 7), pc = 2 * w + (mi & 1);
      ldsm4t(&res[2 * j], rbx + line * 128 + ((pc ^ (line & 7)) << 4));
    }
  }
  bar_sync(2 + wg, 128);
  float acc[32];
#pragma unroll
  for (int i = 0; i < 32; i++) acc[i] = 0.f;
#pragma unroll 1
  for (int c = 0; c < 8; c++) {
    if ((c & 1) == 0) mbar_wait(bar + 8 * (B_WOF + (c >> 1)), layer);
    mbar_wait(bar + 8 * (B_OF + c), layer);
    if (c == 0 && threadIdx.x == 0) TS(2 + layer * 20 + 8);
    const uint64_t da = mkdesc(sb + (c < 4 ? SM_X + 65536 + c * 16384 : SM_W + (c - 4) * 16384) + wg * 8192, 16, 1024, 1);
    const uint64_t db = mkdesc(sb + SM_X + c * 8192, 8192, 1024, 1);
    wg_fence();
#pragma unroll
    for (int ks = 0; ks < 4; ks++) wgmma_ss<64, 0, 1>(acc, da + ks * 2, db + ks * 128, 1);
    wg_commit();
  }
  wg_wait<0>();
  if (threadIdx.x == 0) TS(2 + layer * 20 + 9);
  if (lane == 0 && w == 0) mbar_arrive(bar + 8 * B_PDONE);
  float s0 = 0.f, q0 = 0.f, s1 = 0.f, q1 = 0.f;
  uint32_t o[16];
#pragma unroll
  for (int j = 0; j < 8; j++) {
    const uint32_t r0 = res[2 * j], r1 = res[2 * j + 1];
    o[2 * j] = packbf(acc[4 * j] + bf_lo(r0), acc[4 * j + 1] + bf_hi(r0));
    o[2 * j + 1] = packbf(acc[4 * j + 2] + bf_lo(r1), acc[4 * j + 3] + bf_hi(r1));
    const float a = bf_lo(o[2 * j]), b = bf_hi(o[2 * j]), c = bf_lo(o[2 * j + 1]), d = bf_hi(o[2 * j + 1]);
    s0 += a + b; q0 = fmaf(a, a, q0); q0 = fmaf(b, b, q0);
    s1 += c + d; q1 = fmaf(c, c, q1); q1 = fmaf(d, d, q1);
  }
#pragma unroll
  for (int j = 0; j < 8; j += 2) {
    const int mi = lane >> 3;
    const int line = 8 * (j + (mi >> 1)) + (lane & 7), pc = 2 * w + (mi & 1);
    stsm4t(rbx + line * 128 + ((pc ^ (line & 7)) << 4), o[2 * j], o[2 * j + 1], o[2 * j + 2], o[2 * j + 3]);
  }
#pragma unroll
  for (int o2 = 1; o2 <= 2; o2 <<= 1) {
    s0 += __shfl_xor_sync(~0u, s0, o2); q0 += __shfl_xor_sync(~0u, q0, o2);
    s1 += __shfl_xor_sync(~0u, s1, o2); q1 += __shfl_xor_sync(~0u, q1, o2);
  }
  const uint32_t stg = sb + SM_HALO + wg * 512;
  {
    const int row = 16 * w + (lane >> 2) + 8 * (t >> 1);
    const float v = (t == 0) ? s0 : (t == 1) ? q0 : (t == 2) ? s1 : q1;
    sts32f(stg + 4 * (((((row & 7) >> 1) * 8 + (row >> 3)) << 2) + (row & 1) * 2 + (t & 1)), v);
  }
  fence_async_smem();
  bar_sync(2 + wg, 128);
  if (w == 0 && elect_one()) {
    mbar_wait(bar + 8 * B_ZF, 0);
    tma_st(&p.mapXT, rb * 128 + wg * 64, (2 * layer) * DM + q * 64, rbx);
    bulk_red_add_f32(g_stats + layer * LSEQ * 2 + (rb * 2 + wg) * 128, stg, 512);
    bulk_commit();
    bulk_wait_all();
    red_relaxed(&g_cnt[(layer ? C_G2 : C_G0) * 32]);
    if (threadIdx.x == 0) TS(2 + layer * 20 + 10);
  }
}

__device__ __forceinline__ void conv_load(uint32_t* A, uint32_t pe) {
#pragma unroll
  for (int m = 0; m < 17; m++) {
    A[4 * m + 2] = lds32(pe + 4 * (64 * m - 8));
    A[4 * m + 0] = lds32(pe + 4 * (64 * m));
    A[4 * m + 1] = lds32(pe + 4 * (64 * m + 8));
  }
#pragma unroll
  for (int m = 0; m < 17; m++) asm volatile("mov.b32 %0, %1;" : "=r"(A[4 * m + 3]) : "r"(A[4 * m + 0]));
}
template <int M> __device__ __forceinline__ void conv_mma(float* acc, const uint32_t* A, uint64_t d) {
  wgmma_rs<128 - 8 * (M / 2), 0>(acc, A + 4 * M, d + (uint64_t)(4 * M), M != 0);
}
template <int M0, int M1> __device__ __forceinline__ void conv_mmas(float* acc, const uint32_t* A, uint64_t d) {
  if constexpr (M0 < M1) { conv_mma<M0>(acc, A, d); conv_mmas<M0 + 1, M1>(acc, A, d); }
}
__device__ __forceinline__ void conv_sums(uint32_t sb, int lc, int c, uint4 own) {
  const int m = c == 127 ? -1 : c;
  if (c == 127) own = make_uint4(0, 0, 0, 0);
  const uint32_t up = m >= 1 ? ((m - 1) & 1) * CV_UH + (127 - ((m - 1) >> 1)) * 16 + 8 : 128 * 16;
  const uint32_t un = ((m + 1) & 1) * CV_UH + (127 - ((m + 1) >> 1)) * 16;
  const bool odd = c & 1;
  const float2 v0 = lds64f(sb + cv_u(lc) + (odd ? un : up)), v1 = lds64f(sb + cv_u(lc) + (odd ? up : un));
  const uint32_t x[8] = {__float_as_uint(odd ? v1.x : v0.x), __float_as_uint(odd ? v1.y : v0.y), own.x, own.y, own.z, own.w,
                         __float_as_uint(odd ? v0.x : v1.x), __float_as_uint(odd ? v0.y : v1.y)};
  float pv[16];
#pragma unroll
  for (int k = 0; k < 8; k++) { pv[2 * k] = bf_lo(x[k]); pv[2 * k + 1] = bf_hi(x[k]); }
  float sf[8], pf[8], s9[8], s7[8];
  sf[7] = pv[7]; pf[0] = pv[8];
#pragma unroll
  for (int i = 6; i >= 0; i--) sf[i] = sf[i + 1] + pv[i];
#pragma unroll
  for (int i = 1; i < 8; i++) pf[i] = pf[i - 1] + pv[8 + i];
#pragma unroll
  for (int i = 0; i < 8; i++) {
    s9[i] = sf[i] + pf[i];
    s7[i] = i == 0 ? sf[1] : i == 7 ? pf[6] : sf[i + 1] + pf[i - 1];
  }
  const int ce = (m + 2) & 127, co = m + 1;
  uint4 e4 = make_uint4(packbf(s9[0], s9[1]), packbf(s9[2], s9[3]), packbf(s9[4], s9[5]), packbf(s9[6], s9[7]));
  if (ce == 0) e4 = make_uint4(0, 0, 0, 0);
  sts128(sb + cv_s(lc) + ((ce >> 3) & 1) * 1024 + (ce >> 4) * 128 + (((ce ^ (ce >> 4)) & 7) << 4), e4);
  sts128(sb + cv_s(lc) + 2048 + ((co >> 3) & 1) * 1024 + (co >> 4) * 128 + (((co ^ (co >> 4)) & 7) << 4),
         make_uint4(packbf(s7[0], s7[1]), packbf(s7[2], s7[3]), packbf(s7[4], s7[5]), packbf(s7[6], s7[7])));
}

__device__ __forceinline__ void conv_epi(uint32_t sb, int layer, int cta, int ch, int c0) {
  uint4 v[2][4], xr[2];
#pragma unroll
  for (int u = 0; u < 2; u++) xr[u] = ldcg128(g_xT + (size_t)(2 * layer * DM + cv_chan(cta, ch)) * LSEQ + (c0 + 128 * u) * 8);
  mbar_wait(sb + SM_BAR + 8 * (B_P + ch), layer);
#pragma unroll
  for (int u = 0; u < 2; u++) {
    const int c = c0 + 128 * u;
    const uint32_t pb = sb + cv_pb(ch) + (c ^ ((c >> 3) & 1)) * 16;
#pragma unroll
    for (int k = 0; k < 4; k++) v[u][k] = lds128(pb + k * CV_PBW);
  }
#pragma unroll
  for (int u = 0; u < 2; u++) {
    uint4 o;
    o.x = hadd2(xr[u].x, hadd2(hadd2(v[u][0].x, v[u][1].x), hadd2(v[u][2].x, v[u][3].x)));
    o.y = hadd2(xr[u].y, hadd2(hadd2(v[u][0].y, v[u][1].y), hadd2(v[u][2].y, v[u][3].y)));
    o.z = hadd2(xr[u].z, hadd2(hadd2(v[u][0].z, v[u][1].z), hadd2(v[u][2].z, v[u][3].z)));
    o.w = hadd2(xr[u].w, hadd2(hadd2(v[u][0].w, v[u][1].w), hadd2(v[u][2].w, v[u][3].w)));
    sts128(sb + cv_s(ch) + (c0 + 128 * u) * 16, o);
  }
}
__device__ __forceinline__ void warp_release(uint32_t b) {
  fence_async_smem();
  __syncwarp();
  if (elect_one()) mbar_arrive(b);
}

__device__ __forceinline__ void conv_prep(uint32_t sb, int layer, int cta, int c, uint4 (&un)[4]) {
  const uint32_t bar = sb + SM_BAR;
  const bf16* xin = g_xT + (size_t)(2 * layer) * DM * LSEQ;
  uint4 xr[4], st[4];
  mbar_wait(bar + 8 * B_GB, layer);
  if (threadIdx.x == 0) TS(2 + layer * 20 + 11);
#pragma unroll
  for (int i = 0; i < 4; i++) st[i] = ldcg128(g_stats + layer * LSEQ * 2 + ((c >> 3) * 4 + i) * 32 + (c & 7) * 4);
#pragma unroll
  for (int i = 0; i < 4; i++) xr[i] = ldcg128(xin + (size_t)cv_chan(cta, i) * LSEQ + c * 8);
  float nm[8], rstd[8];
#pragma unroll
  for (int i = 0; i < 4; i++) {
    const float m0 = __uint_as_float(st[i].x) * (1.f / DM), m1 = __uint_as_float(st[i].z) * (1.f / DM);
    rstd[2 * i] = rsqrt_approx(fmaxf(fmaf(__uint_as_float(st[i].y), 1.f / DM, -m0 * m0), 0.f) + 1e-5f);
    rstd[2 * i + 1] = rsqrt_approx(fmaxf(fmaf(__uint_as_float(st[i].w), 1.f / DM, -m1 * m1), 0.f) + 1e-5f);
    nm[2 * i] = -m0 * rstd[2 * i]; nm[2 * i + 1] = -m1 * rstd[2 * i + 1];
  }
  if (threadIdx.x == 0) TS(2 + layer * 20 + 12);
  const int a = c >> 1, h = c & 1;
#pragma unroll
  for (int i = 0; i < 4; i++) {
    const uint32_t x[4] = {xr[i].x, xr[i].y, xr[i].z, xr[i].w};
    uint32_t u[4];
#pragma unroll
    for (int k = 0; k < 4; k++)
      u[k] = packbf(fmaf(bf_lo(x[k]), rstd[2 * k], nm[2 * k]), fmaf(bf_hi(x[k]), rstd[2 * k + 1], nm[2 * k + 1]));
    un[i] = make_uint4(u[0], u[1], u[2], u[3]);
    sts128(sb + cv_u(i) + h * CV_UH + (127 - a) * 16, un[i]);
    warp_release(bar + 8 * (B_U + i));
  }
}
__device__ __forceinline__ void conv_zero(uint32_t sb, int ht) {
  if (ht < 96) {
    const int ch = ht / 24, h2 = (ht / 12) & 1, qq = ht % 12;
    sts128(sb + cv_u(ch) + h2 * CV_UH + (128 + qq) * 16, make_uint4(0, 0, 0, 0));
  }
  if (ht >= 80) {
    const int i = ht - 80, ch = i / 12, q2 = i % 12;
    const int w2 = q2 < 2 ? 1 : q2 < 6 ? 2 : 3, cc = q2 < 2 ? q2 : q2 < 6 ? q2 - 2 : q2 - 6;
    sts128(sb + cv_pb(ch) + w2 * CV_PBW + cc * 16, make_uint4(0, 0, 0, 0));
  }
}

#define HANDOVER 1
#define A_FIRST 0
__device__ __forceinline__ void conv_phase(const Params& p, uint32_t sb, int layer, int cta) {
  const int tid = opaque_tid();
  const int wg = __shfl_sync(~0u, tid >> 7, 0), w = __shfl_sync(~0u, (tid >> 5) & 3, 0);
  const uint32_t bar = sb + SM_BAR;
  uint32_t A[68];
  mbar_wait(bar + 8 * B_PE, layer);
  conv_load(A, sb + cv_pe(1 - wg) + 4 * (16 + 16 * w + ((tid & 31) >> 2) - 2 * (tid & 3)));
  if (wg == 0) {
    uint4 un[4];
    conv_prep(sb, layer, cta, opaque_tid() + 128, un);
  }
#pragma unroll 1
  for (int r = 0; r < 2; r++) {
    const int ch = 2 * r + 1 - wg;
    float acc[64];
    const uint64_t d = mkdesc(sb + cv_u(ch), CV_UH, 128, 0);
    const bool leader = (opaque_tid() & 127) == 0;
    FTS(39);
    mbar_wait(bar + 8 * (B_U + ch), layer);
    if (ch > 0) mbar_wait(bar + 8 * (B_T + ch - 1), layer);
    FTS(41);
    if (ch == 0 && threadIdx.x == 128) TS(2 + layer * 20 + 13);
    wg_fence();
    conv_mma<0>(acc, A, d);
    conv_mmas<2, 17>(acc, A, d);
    wg_commit();
    FTS(51);
    mbar_wait(bar + 8 * (B_S + ch), layer);
    if (HANDOVER == 0) mbar_arrive_if(bar + 8 * (B_T + ch), leader);
    wg_fence();
    conv_mma<1>(acc, A, d);
    if (HANDOVER == 1) mbar_arrive_if(bar + 8 * (B_T + ch), leader);
    wgmma_ss<64, 1, 1>(acc, mkdesc(sb + cv_s(ch), 1024, 1024, 1), mkdesc(sb + cv_ft(ch), 256, 16, 0), 1);
    if (HANDOVER == 2) mbar_arrive_if(bar + 8 * (B_T + ch), leader);
    wgmma_ss<64, 1, 1>(acc, mkdesc(sb + cv_s(ch) + 2048, 1024, 1024, 1), mkdesc(sb + cv_ft(ch) + 512, 256, 16, 0), 1);
    wg_commit();
    if (HANDOVER == 3) mbar_arrive_if(bar + 8 * (B_T + ch), leader);
    FTS(61);
    wg_wait<0>();
    const int l2 = opaque_tid() & 31;
    if (A_FIRST && r == 0) conv_load(A, sb + cv_pe(3 - wg) + 4 * (16 + 16 * w + (l2 >> 2) - 2 * (l2 & 3)));
    FTS(20);
    const uint32_t pb = sb + cv_pb(ch) + w * CV_PBW;
#pragma unroll
    for (int j = 0; j < 16; j += 2) {
      const int mt = l2 >> 3;
      const int a = 127 - (8 * (j + (mt >> 1)) + (l2 & 7));
      int c = 2 * (a + w) + (mt & 1);
      c ^= (c >> 3) & 1;
      stsm4t(pb + c * 16, packbf(acc[4 * j], acc[4 * j + 1]), packbf(acc[4 * j + 2], acc[4 * j + 3]),
             packbf(acc[4 * j + 4], acc[4 * j + 5]), packbf(acc[4 * j + 6], acc[4 * j + 7]));
    }
    __syncwarp();
    if (elect_one()) mbar_arrive(bar + 8 * (B_P + ch));
    if (threadIdx.x == 0) TS(2 + layer * 20 + 14 + r);
    FTS(57);
    if (!A_FIRST && r == 0) conv_load(A, sb + cv_pe(3 - wg) + 4 * (16 + 16 * w + (l2 >> 2) - 2 * (l2 & 3)));
  }
  if (wg == 1 && layer == 0) mbar_wait(bar + 8 * (B_T + 3), layer);
}

__device__ __forceinline__ void final_phase(const Params& p, uint32_t sb, int cta, int wg, int w) {
  if (wg == 1 && w == 3) return;
  const int lane = opaque_tid() & 31, g = lane >> 2, t = lane & 3;
  const int lc = wg ? w : 3;
  const int pos0 = (cta & 31) * 64, ch0 = 128 * lc + (cta >> 5) * 32;
  const bf16* src = g_xT + (size_t)(3 * DM + ch0 + 8 * (g >> 1) + (g & 1)) * LSEQ + pos0;
  bf16* dst = p.out + (size_t)pos0 * DM + ch0 + 8 * t;
  spin_until(&g_cnt[(C_F + (cta >> 5)) * 32 + lc], (lds32(sb + SM_EP) + 1) * 32);
  if (wg == 0) {
    if (threadIdx.x == 0) TS(42);
    uint2 v[4];
#pragma unroll
    for (int q = 0; q < 4; q++)
      asm volatile("ld.global.cg.v2.b32 {%0,%1}, [%2];" : "=r"(v[q].x), "=r"(v[q].y) : "l"(src + 2 * q * LSEQ + 16 * w + 4 * t) : "memory");
    dst += (16 * w + 4 * (g >> 1) + (g & 1)) * DM;
    *(uint4*)dst = make_uint4(movm_t(v[0].x), movm_t(v[1].x), movm_t(v[2].x), movm_t(v[3].x));
    *(uint4*)(dst + 2 * DM) = make_uint4(movm_t(v[0].y), movm_t(v[1].y), movm_t(v[2].y), movm_t(v[3].y));
  } else {
    uint4 v[2][4];
#pragma unroll
    for (int h = 0; h < 2; h++)
#pragma unroll
      for (int q = 0; q < 4; q++) v[h][q] = ldcg128(src + 2 * q * LSEQ + 32 * h + 8 * t);
    dst += (8 * (g >> 1) + (g & 1)) * DM;
#pragma unroll
    for (int h = 0; h < 2; h++) {
      *(uint4*)(dst + (32 * h + 0) * DM) = make_uint4(movm_t(v[h][0].x), movm_t(v[h][1].x), movm_t(v[h][2].x), movm_t(v[h][3].x));
      *(uint4*)(dst + (32 * h + 2) * DM) = make_uint4(movm_t(v[h][0].y), movm_t(v[h][1].y), movm_t(v[h][2].y), movm_t(v[h][3].y));
      *(uint4*)(dst + (32 * h + 4) * DM) = make_uint4(movm_t(v[h][0].z), movm_t(v[h][1].z), movm_t(v[h][2].z), movm_t(v[h][3].z));
      *(uint4*)(dst + (32 * h + 6) * DM) = make_uint4(movm_t(v[h][0].w), movm_t(v[h][1].w), movm_t(v[h][2].w), movm_t(v[h][3].w));
    }
  }
  if (threadIdx.x == 0) TS(43);
  if (threadIdx.x == 192) TS(63);
  if (threadIdx.x == 0) LTS(1);
}

struct cplx { float r, i; };
__device__ __forceinline__ cplx cmul(cplx a, cplx b) { return {fmaf(a.r, b.r, -a.i * b.i), fmaf(a.r, b.i, a.i * b.r)}; }
__device__ __forceinline__ cplx csqr(cplx a) { return {fmaf(a.r, a.r, -a.i * a.i), (a.r + a.r) * a.i}; }
__device__ __forceinline__ cplx cexp_l(float ar2, float ai, float l) {
  const float m = ex2(ar2 * l);
  const float x = ai * l;
  return {m * __cosf(x), m * __sinf(x)};
}

template <int N> __device__ __forceinline__ void halve(float* s, int lane) {
  const bool up = (lane & (2 * N)) != 0;
#pragma unroll
  for (int i = 0; i < N; i++) {
    const float keep = up ? s[i + N] : s[i], send = up ? s[i] : s[i + N];
    s[i] = keep + __shfl_xor_sync(~0u, send, 2 * N);
  }
}
__device__ __forceinline__ void colsum_part(const Params& p, uint32_t sb, int cta, int ht, uint32_t tag) {
  if (cta >= 96) return;
  uint4 v[4][2];
#pragma unroll
  for (int r = 0; r < 4; r++)
#pragma unroll
    for (int i = 0; i < 2; i++) v[r][i] = *(const uint4*)(p.wqkv + (size_t)(ht + 128 * r) * 1536 + cta * 16 + i * 8);
  float s[16];
#pragma unroll
  for (int i = 0; i < 16; i++) s[i] = 0.f;
#pragma unroll
  for (int r = 0; r < 4; r++)
#pragma unroll
    for (int i = 0; i < 2; i++) {
      const uint32_t x[4] = {v[r][i].x, v[r][i].y, v[r][i].z, v[r][i].w};
#pragma unroll
      for (int k = 0; k < 4; k++) { s[8 * i + 2 * k] += bf_lo(x[k]); s[8 * i + 2 * k + 1] += bf_hi(x[k]); }
    }
  const int lane = ht & 31, w = ht >> 5;
  halve<8>(s, lane); halve<4>(s, lane); halve<2>(s, lane); halve<1>(s, lane);
  s[0] += __shfl_xor_sync(~0u, s[0], 1);
  if ((lane & 1) == 0) sts32f(sb + SM_RED + (w * 16 + (lane >> 1)) * 4, s[0]);
  bar_sync(4, 128);
  if (ht < 16) {
    float tot = 0.f;
#pragma unroll
    for (int k = 0; k < 4; k++) tot += __uint_as_float(lds32(sb + SM_RED + (k * 16 + ht) * 4));
    asm volatile("st.relaxed.gpu.global.v2.u32 [%0], {%1,%2};" ::"l"(&g_colsum[cta * 16 + ht]), "r"(__float_as_uint(tot)), "r"(tag) : "memory");
  }
}

__device__ __forceinline__ uint32_t packh(float lo, float hi) { uint32_t r; asm("cvt.rn.f16x2.f32 %0, %1, %2;" : "=r"(r) : "f"(hi), "f"(lo)); return r; }
__device__ __forceinline__ void mma_f16(float* d, uint32_t a0, uint32_t a1, uint32_t a2, uint32_t a3, uint32_t b0, uint32_t b1) {
  asm volatile("mma.sync.aligned.m16n8k16.row.col.f32.f16.f16.f32 {%0,%1,%2,%3}, {%4,%5,%6,%7}, {%8,%9}, {%0,%1,%2,%3};"
      : "+f"(d[0]), "+f"(d[1]), "+f"(d[2]), "+f"(d[3]) : "r"(a0), "r"(a1), "r"(a2), "r"(a3), "r"(b0), "r"(b1));
}
struct HSeed { uint32_t r, i; };
__device__ __forceinline__ HSeed hseed(cplx s) { return {packh(s.r, s.r), packh(s.i, s.i)}; }
__device__ __forceinline__ void hcmul(uint32_t& o_r, uint32_t& o_i, uint32_t br, uint32_t bi, HSeed s) {
  asm("{\n.reg .b32 t, u;\nmul.rn.f16x2 t, %3, %5;\nneg.f16x2 t, t;\nmul.rn.f16x2 u, %3, %4;\nfma.rn.f16x2 %0, %2, %4, t;\nfma.rn.f16x2 %1, %2, %5, u;\n}"
      : "=&r"(o_r), "=&r"(o_i) : "r"(br), "r"(bi), "r"(s.r), "r"(s.i));
}
struct HTile { uint32_t r[4], i[4]; };
__device__ __forceinline__ void tile_set(HTile& t, int k, cplx a, cplx b) { t.r[k] = packh(a.r, b.r); t.i[k] = packh(a.i, b.i); }
__device__ __forceinline__ void tile_upper(HTile& t, HSeed s) { hcmul(t.r[2], t.i[2], t.r[0], t.i[0], s); hcmul(t.r[3], t.i[3], t.r[1], t.i[1], s); }
__device__ __forceinline__ HTile tile_shift(const HTile& t, HSeed s) {
  HTile o;
#pragma unroll
  for (int k = 0; k < 4; k++) hcmul(o.r[k], o.i[k], t.r[k], t.i[k], s);
  return o;
}
__device__ __forceinline__ void tile_put(const HTile& t, uint32_t a) {
  sts128(a, make_uint4(t.r[0], t.r[1], t.r[2], t.r[3]));
  sts128(a + 512, make_uint4(t.i[0], t.i[1], t.i[2], t.i[3]));
}
__device__ __forceinline__ HTile tile_get(uint32_t a) { HTile o; ldsm4t(o.r, a); ldsm4t(o.i, a + 512); return o; }
__device__ __forceinline__ void tile_mma(float* T, const HTile& a0, const HTile& a1, const HTile& b) {
  mma_f16(T, a0.r[0], a0.r[1], a0.r[2], a0.r[3], b.r[0], b.r[1]);
  mma_f16(T, a0.i[0], a0.i[1], a0.i[2], a0.i[3], b.i[0], b.i[1]);
  mma_f16(T, a1.r[0], a1.r[1], a1.r[2], a1.r[3], b.r[2], b.r[3]);
  mma_f16(T, a1.i[0], a1.i[1], a1.i[2], a1.i[3], b.i[2], b.i[3]);
}
__device__ __forceinline__ void tile_mma2(float* T, float* U, const HTile& a0, const HTile& a1, const HTile& b, const HTile& c) {
  mma_f16(T, a0.r[0], a0.r[1], a0.r[2], a0.r[3], b.r[0], b.r[1]);
  mma_f16(U, a0.r[0], a0.r[1], a0.r[2], a0.r[3], c.r[0], c.r[1]);
  mma_f16(T, a0.i[0], a0.i[1], a0.i[2], a0.i[3], b.i[0], b.i[1]);
  mma_f16(U, a0.i[0], a0.i[1], a0.i[2], a0.i[3], c.i[0], c.i[1]);
  mma_f16(T, a1.r[0], a1.r[1], a1.r[2], a1.r[3], b.r[2], b.r[3]);
  mma_f16(U, a1.r[0], a1.r[1], a1.r[2], a1.r[3], c.r[2], c.r[3]);
  mma_f16(T, a1.i[0], a1.i[1], a1.i[2], a1.i[3], b.i[2], b.i[3]);
  mma_f16(U, a1.i[0], a1.i[1], a1.i[2], a1.i[3], c.i[2], c.i[3]);
}
__device__ __forceinline__ void kgen_unit(uint32_t tab, uint32_t taba, float ar2, float ai, cplx c, float (&T)[5][4]) {
  const cplx z1 = cexp_l(ar2, ai, 1.f), z16 = cexp_l(ar2, ai, 16.f), z256 = cexp_l(ar2, ai, 256.f);
  HTile a0, a1, b0, b1;
  {
    const cplx y1 = {z16.r, -z16.i}, y2 = csqr(y1), y3 = cmul(y2, y1), y4 = csqr(y2), y5 = cmul(y4, y1), y6 = csqr(y3), y7 = cmul(y4, y3);
    HTile t;
    tile_set(t, 0, {1.f, 0.f}, y1); tile_set(t, 1, y2, y3); tile_set(t, 2, y4, y5); tile_set(t, 3, y6, y7);
    const HTile u = tile_shift(t, hseed(csqr(y4)));
    __syncwarp();
    tile_put(t, tab); tile_put(u, tab + 1024);
    __syncwarp();
    a0 = tile_get(taba); a1 = tile_get(taba + 256);
  }
  const cplx z2 = csqr(z1), z4 = csqr(z2), z8 = csqr(z4);
  const HSeed h8 = hseed(z8);
  const cplx d = cmul(c, z256), e = cmul(d, z256);
  {
    const cplx z512 = csqr(z256), f = cmul(e, z512), f8 = cmul(f, z8), f16 = cmul(f, z16), e4 = cmul(e, z4);
    HTile t, u;
    tile_set(t, 0, e4, cmul(e, z8)); tile_set(t, 1, cmul(e4, z8), cmul(e, z16));
    tile_upper(t, hseed(z256));
    tile_set(u, 0, f8, f16); tile_set(u, 1, cmul(f8, z256), cmul(f16, z256));
    tile_upper(u, hseed(z512));
    __syncwarp();
    tile_put(t, tab); tile_put(u, tab + 1024);
    __syncwarp();
    b0 = tile_get(tab); b1 = tile_get(tab + 1024);
  }
  {
    const cplx d2 = cmul(d, z2), d4 = cmul(d, z4);
    HTile t;
    tile_set(t, 0, d2, d4); tile_set(t, 1, cmul(d2, z4), cmul(d, z8));
    tile_upper(t, h8);
    __syncwarp();
    tile_put(t, tab);
    __syncwarp();
    tile_mma2(T[3], T[4], a0, a1, b0, b1);
    b0 = tile_get(tab);
  }
  {
    const cplx c1 = cmul(c, z1), c2 = cmul(c, z2), c3 = cmul(c1, z2), c4 = cmul(c, z4);
    HTile t;
    tile_set(t, 0, c1, c2); tile_set(t, 1, c3, c4); tile_set(t, 2, cmul(c1, z4), cmul(c2, z4)); tile_set(t, 3, cmul(c3, z4), cmul(c4, z4));
    const HTile u = tile_shift(t, h8);
    __syncwarp();
    tile_put(t, tab); tile_put(u, tab + 1024);
    __syncwarp();
    tile_mma(T[2], a0, a1, b0);
    b0 = tile_get(tab); b1 = tile_get(tab + 1024);
    tile_mma2(T[0], T[1], a0, a1, b0, b1);
  }
}
struct ModeIn { uint2 ar, ai, br, bi, cr, ci; };
__device__ __forceinline__ ModeIn load_modes(const Params& p, int idx) {
  return {*(const uint2*)(p.a_re + idx), *(const uint2*)(p.a_im + idx), *(const uint2*)(p.b_re + idx),
          *(const uint2*)(p.b_im + idx), *(const uint2*)(p.c_re + idx), *(const uint2*)(p.c_im + idx)};
}
__device__ __forceinline__ float bf_el(uint2 v, int k) { const uint32_t x = (k & 2) ? v.y : v.x; return (k & 1) ? bf_hi(x) : bf_lo(x); }
struct KGen { float4 cur; float T[5][4]; };
__device__ __forceinline__ uint32_t kgen_slot(uint32_t sb, int ht, int u) {
  return sb + (u < 3 ? SM_KC + (ht >> 5) * (KC_STRIDE * 2) + (u - 1) * 512 + (ht & 31) * 16 + 16 : SM_HALO + 1024 + ht * 16);
}
__device__ __forceinline__ void kgen_setup(KGen& s, uint32_t sb, int cta, int ht, const ModeIn& in, bf16 logdt, bf16 dskip) {
  const float dt = __bfloat162float(__float2bfloat16_rn(expf(__bfloat162float(logdt))));
  float mx = 0.f, k0 = 0.f, ar2[4];
  cplx c[4];
#pragma unroll
  for (int k = 0; k < 4; k++) {
    ar2[k] = (dt * bf_el(in.ar, k)) * 1.4426950408889634f;
    c[k] = cmul({bf_el(in.cr, k), bf_el(in.ci, k)}, {dt * bf_el(in.br, k), dt * bf_el(in.bi, k)});
    k0 += c[k].r;
    mx = fmaxf(mx, fmaxf(fabsf(c[k].r), fabsf(c[k].i)) * ex2(fmaxf(ar2[k] * 2048.f, 0.f)));
  }
  const int ex = min(max(267 - (int)(__reduce_max_sync(~0u, __float_as_uint(mx)) >> 23), 1), 253);
  const float sc = __uint_as_float(ex << 23);
#pragma unroll
  for (int o = 16; o > 0; o >>= 1) k0 += __shfl_xor_sync(~0u, k0, o);
  if ((ht & 31) == 0) {
    const uint32_t kc = sb + SM_KC + (ht >> 5) * (KC_STRIDE * 2);
    sts16(kc, __bfloat16_as_ushort(__float2bfloat16_rn(k0 + __bfloat162float(dskip))));
    sts16(kc + 641 * 2, 0);
    sts32f(kc + 644 * 2, __uint_as_float((254 - ex) << 23));
  }
  s.cur = make_float4(ar2[0], dt * bf_el(in.ai, 0), c[0].r * sc, c[0].i * sc);
#pragma unroll
  for (int k = 1; k < 4; k++) sts128f(kgen_slot(sb, ht, k), ar2[k], dt * bf_el(in.ai, k), c[k].r * sc, c[k].i * sc);
#pragma unroll
  for (int i = 0; i < 5; i++) s.T[i][0] = s.T[i][1] = s.T[i][2] = s.T[i][3] = 0.f;
}
__device__ __forceinline__ void kgen_finish(KGen& s, uint32_t sb, int cta, int ht) {
  const int w = ht >> 5, lane = ht & 31, g = lane >> 2, t = lane & 3;
  const uint32_t kc = sb + SM_KC + w * KC_STRIDE * 2;
  __syncwarp();
  const float inv = __uint_as_float(lds32(kc + 644 * 2));
  auto put = [&](int idx, float v) {
    sts16(kc + idx * 2, __bfloat16_as_ushort(__float2bfloat16_rn(v)));
  };
#pragma unroll
  for (int hi = 0; hi < 2; hi++)
#pragma unroll
    for (int lo = 0; lo < 2; lo++) {
      const int i = g + 8 * hi, j = 2 * t + lo, e = 2 * hi + lo;
      put(16 * i + 1 + j, s.T[0][e] * inv);
      put(16 * i + 9 + j, s.T[1][e] * inv);
      put(257 + 8 * i + j, s.T[2][e] * inv);
      put(385 + 4 * i + (j & 3) + 64 * (j >> 2), s.T[3][e] * inv);
      put(513 + 2 * i + lo + 32 * t, s.T[4][e] * inv);
    }
}

__device__ __forceinline__ void expand_taps(uint32_t sb, int ht) {
  const int ch = ht >> 5, lane = ht & 31;
  const uint32_t kc = sb + SM_KC + ch * KC_STRIDE * 2;
  const uint32_t dst0 = sb + cv_pe(ch);
  auto put = [&](int G, uint32_t v0, uint32_t v1, uint32_t v2, uint32_t v3, uint32_t v4, uint32_t v5, uint32_t v6, uint32_t v7, uint32_t v8) {
    const uint32_t dst = dst0 + G * 32;
    sts128(dst, make_uint4(v1 | (v0 << 16), v2 | (v1 << 16), v3 | (v2 << 16), v4 | (v3 << 16)));
    sts128(dst + 16, make_uint4(v5 | (v4 << 16), v6 | (v5 << 16), v7 | (v6 << 16), v8 | (v7 << 16)));
  };
  {
    const uint4 q = lds128(kc + lane * 16);
    const uint32_t pv = lane ? lds16(kc + lane * 16 - 2) : 0u;
    const uint32_t dst = dst0 + (lane + 2) * 32;
    sts128(dst, make_uint4(__byte_perm(q.x, pv, 0x5410), __byte_perm(q.x, q.x, 0x1032), __byte_perm(q.y, q.x, 0x7610), __byte_perm(q.y, q.y, 0x1032)));
    sts128(dst + 16, make_uint4(__byte_perm(q.z, q.y, 0x7610), __byte_perm(q.z, q.z, 0x1032), __byte_perm(q.w, q.z, 0x7610), __byte_perm(q.w, q.w, 0x1032)));
    if (lane < 4) sts128(dst0 + lane * 16, make_uint4(0, 0, 0, 0));
  }
  uint32_t a[5], b[2][3], fv[4];
  {
    const uint32_t s1 = kc + 2 * (256 + 4 * lane);
#pragma unroll
    for (int k = 0; k < 5; k++) a[k] = lds16(s1 + 2 * k);
#pragma unroll
    for (int u = 0; u < 2; u++) {
      const uint32_t s2 = kc + 2 * (384 + 2 * (lane + 32 * u));
#pragma unroll
      for (int k = 0; k < 3; k++) b[u][k] = lds16(s2 + 2 * k);
    }
#pragma unroll
    for (int k = 0; k < 4; k++) fv[k] = lds16(kc + 2 * (640 - 4 * lane - k));
  }
  const uint32_t k255 = lds16(kc + 2 * 255), k1024 = lds16(kc + 2 * 512);
  put(34 + lane, lane == 0 ? k255 : a[0], a[0], a[0], a[1], a[2], a[2], a[2], a[3], a[4]);
#pragma unroll
  for (int u = 0; u < 2; u++) put(66 + lane + 32 * u, b[u][0], b[u][0], b[u][0], b[u][0], b[u][1], b[u][1], b[u][1], b[u][2], b[u][2]);
  if (lane < 10) {
    const uint32_t v = lane == 0 ? k1024 : 0u;
    put(130 + lane, v, v, v, v, v, v, 0u, 0u, 0u);
  }
  const uint32_t ft = sb + cv_ft(ch) + 4 * lane;
#pragma unroll
  for (int ty = 0; ty < 2; ty++) {
    const uint32_t v = fv[ty] | (fv[ty + 2] << 16);
    sts32f(ft + ty * 512, __uint_as_float(v));
    sts32f(ft + ty * 512 + 128, 0.f);
    sts32f(ft + ty * 512 + 256 + (lane < 2 ? 120 : -8), __uint_as_float(lane < 2 ? 0u : v));
    sts32f(ft + ty * 512 + 384, 0.f);
  }
}

template <bool SMID> __device__ __forceinline__ int role_id() {
  uint32_t v;
  if (!SMID) { asm volatile("mov.u32 %0, %%ctaid.x;" : "=r"(v)); return v; }
  asm volatile("mov.u32 %0, %%smid;" : "=r"(v));
  const int tp = v >> 1;
  int gq, pos;
  if (tp < 32) { gq = tp & 7; pos = tp >> 3; }
  else if (tp < 60) { const int u = tp - 32, q = (u * 37) >> 8; gq = 1 + u - 7 * q; pos = 4 + q; }
  else if (tp < 62) { gq = 8; pos = tp - 60; }
  else { gq = 0; pos = tp - 58; }
  return __shfl_sync(~0u, gq * 16 + pos * 2 + (v & 1), 0);
}
__device__ __forceinline__ int role_rb(int cta) { return ((cta >> 4) & 3) * 4 + ((cta >> 2) & 3); }
__device__ __forceinline__ int role_hg(int cta) { return (cta >> 6) * 4 + (cta & 3); }
__device__ __forceinline__ int role_rb2(int cta) { return cta >> 3; }
__device__ __forceinline__ int role_q2(int cta) { return cta & 7; }

template <bool SMID> __global__ void __launch_bounds__(NTHREADS, 1) fused_kernel(const __grid_constant__ Params p) {
  extern __shared__ __align__(1024) uint8_t smem[];
  const uint32_t sb = s32(smem);
  const int tid = threadIdx.x, lane = tid & 31;
  const int warp = __shfl_sync(~0u, tid >> 5, 0);
  const int cta0 = role_id<SMID>();
  if (SMID && cta0 >= NCTA) {
    if (tid == 0) spin_until(&g_cnt[C_CS * 32], (ld_relaxed(&g_cnt[C_CS * 32]) / NCTA + 1) * NCTA);
    return;
  }
  const uint32_t bar = sb + SM_BAR;

  if (tid == 0) TS(0);
  if (warp < 4 && elect_one()) {
    const int rb = role_rb(cta0), hg = role_hg(cta0);
#pragma unroll
    for (int q = 0; q < 4; q++) {
      if (warp == q) {
#pragma unroll
        for (int i = 17 * q; i < 17 * q + 17; i++) {
          int cnt = 1;
          if ((i >= B_KVE && i < B_KVE + 5) || i == B_QDONE || i == B_PDONE || i == B_OST || i == B_AD) cnt = 2;
          if (i == B_Z0) cnt = 128;
          if (i >= B_U && i < B_U + 4) cnt = 8;
          if ((i >= B_S && i < B_S + 4) || (i >= B_E && i < B_E + 4) || i >= B_P || i == B_PE) cnt = 4;
          mbar_init(bar + 8 * i, cnt);
        }
      }
    }
    asm volatile("fence.mbarrier_init.release.cluster;" ::: "memory");
    if (warp == 0) {
      fence_async_smem();
      const int kc = 0;
      mbar_expect(bar + 8 * B_XF, 16384);
      tma_ld(sb + SM_X, &p.mapX128, kc, rb * 128, bar + 8 * B_XF);
      mbar_expect(bar + 8 * B_KVF, 24576);
      tma_ld3(sb + SM_W, &p.mapW3, hg * 64, kc, 0, bar + 8 * B_KVF);
      mbar_expect(bar + 8 * (B_XF + 1), 16384);
      tma_ld(sb + SM_X + 16384, &p.mapX128, 64, rb * 128, bar + 8 * (B_XF + 1));
      mbar_expect(bar + 8 * (B_KVF + 1), 24576);
      tma_ld3(sb + SM_W + 24576, &p.mapW3, hg * 64, 64, 0, bar + 8 * (B_KVF + 1));
      TS(56);
    }
  }

  if (warp < 8) {
    bar_sync(0, NTHREADS);
    if (tid == 0) TS(1);
    asm volatile("setmaxnreg.inc.sync.aligned.u32 %0;" ::"n"(R_CONS));
    const int cw = __shfl_sync(~0u, opaque_tid() >> 5, 0);
    const int wg = cw >> 2, w = cw & 3;
    const int cta = role_id<SMID>();
    if (tid == 0) TS(54);
#pragma unroll 1
    for (int layer = 0; layer < 2; layer++) {
      attn_phase(p, sb, layer, role_rb(cta), role_hg(cta), wg, w);
      if (p.stop == 1 + 3 * layer) return;
      proj_phase(p, sb, layer, role_rb2(cta), role_q2(cta), wg, w);
      if (p.stop == 2 + 3 * layer) return;
      conv_phase(p, sb, layer, cta);
      if (p.stop == 3 + 3 * layer) return;
    }
    final_phase(p, sb, cta, wg, w);
  } else if (warp < 12) {
    asm volatile("setmaxnreg.dec.sync.aligned.u32 %0;" ::"n"(R_HELP));
    const int ht = tid - 256;
    const int cta = role_id<SMID>(), rb = role_rb(cta), hg = role_hg(cta);
    unsigned ep0 = 0;
    if (ht == 0) ep0 = ld_relaxed(&g_cnt[C_CS * 32]);
    const ModeIn min0 = load_modes(p, cv_chan(cta, ht >> 5) * 128 + (ht & 31) * 4);
    const bf16 logdt0 = p.log_dt[cv_chan(cta, ht >> 5)], dskip0 = p.dskip[cv_chan(cta, ht >> 5)];
    bar_sync(0, NTHREADS);
    if (ht == 0) {
      asm volatile("st.shared.u32 [%0], %1;" ::"r"(sb + SM_EP), "r"(ep0 / NCTA) : "memory");
      mbar_arrive(bar + 8 * B_EP);
    }
    if (hg == 0) {
      *(float4*)(g_stats + (ht >> 6) * LSEQ * 2 + rb * 256 + (ht & 63) * 4) = make_float4(0.f, 0.f, 0.f, 0.f);
    }
    mbar_arrive(bar + 8 * B_Z0);
    mbar_wait(bar + 8 * B_EP, 0);
    colsum_part(p, sb, cta, ht, lds32(sb + SM_EP) + 1);
    if (ht == 0) TS(50);
    {
      KGen kg;
      const uint32_t tab0 = sb + ((ht >> 5) < 2 ? SM_T : SM_T2 - 4096) + (ht >> 5) * 2048;
      const uint32_t tab = tab0 + (ht & 31) * 16, taba = tab0 + ((ht >> 3) & 1) * 1024 + (((ht >> 1) & 8) + (ht & 7)) * 16;
      kgen_setup(kg, sb, cta, ht, min0, logdt0, dskip0);
#pragma unroll 1
      for (int u = 0; u < 4; u++) {
        if (u == KG_PRE) {
          if (ht == 0) TS(39);
          mbar_wait(bar + 8 * B_AD, 0);
          if (ht == 0) TS(41);
        }
        if (u == 3) mbar_wait(bar + 8 * B_PDONE, 0);
        kgen_unit(tab, taba, kg.cur.x, kg.cur.y, {kg.cur.z, kg.cur.w}, kg.T);
        kg.cur = lds128f(kgen_slot(sb, opaque_tid() - 256, u + 1));
      }
      kgen_finish(kg, sb, cta, opaque_tid() - 256);
    }
    if (ht == 0) TS(51);
    bar_sync(4, 128);
#pragma unroll 1
    for (int layer = 0; layer < 2; layer++) {
      if (p.stop <= 1 + 3 * layer) return;
      mbar_wait(bar + 8 * B_PDONE, layer);
      expand_taps(sb, opaque_tid() - 256);
      conv_zero(sb, opaque_tid() - 256);
      if (ht == 0) TS(52 + layer);
      warp_release(bar + 8 * B_PE);
      if (p.stop <= 2 + 3 * layer) return;
      {
        uint4 un[4];
        conv_prep(sb, layer, cta, opaque_tid() - 256, un);
        if (layer == 1 && ht == 0) TS(62);
        bar_sync(4, 128);
#pragma unroll
        for (int lc = 0; lc < 4; lc++) {
          conv_sums(sb, lc, opaque_tid() - 256, un[lc]);
          warp_release(bar + 8 * (B_S + lc));
          if (lc == 0 && layer == 1 && ht == 0) TS(46);
        }
      }
#pragma unroll 1
      for (int lc = 0; lc < 4; lc++) {
        conv_epi(sb, layer, cta, lc, opaque_tid() - 256);
        warp_release(bar + 8 * (B_E + lc));
      }
    }
  } else {
    asm volatile("setmaxnreg.dec.sync.aligned.u32 40;");
    const int cta = role_id<SMID>(), rb = role_rb(cta), hg = role_hg(cta), rb2 = role_rb2(cta), q2 = role_q2(cta);
    bar_sync(0, NTHREADS);
    if (warp == 12) {
      if (elect_one()) {
        unsigned epoch = 0;
#pragma unroll 1
        for (int layer = 0; layer < 2; layer++) {
          auto ld_x = [&](int c) {
            const uint32_t b = bar + 8 * (B_XF + c);
            const int kc = c;
            mbar_expect(b, 16384);
            tma_ld(sb + SM_X + c * 16384, &p.mapX128, kc * 64, rb * 128, b);
          };
          auto ld_w = [&](int c, int slot) {
            const uint32_t b = bar + 8 * (B_KVF + c);
            mbar_expect(b, 24576);
            tma_ld3(sb + SM_W + slot * 24576, &p.mapW3, hg * 64, c * 64, 0, b);
          };
          if (layer == 0) {
            TS(55);
            ld_x(2); ld_w(2, 2);
            ld_x(3);
            if (rb < 5) tma_prefetch3(&p.mapW3, hg * 64, (3 + rb) * 64, 0);
#pragma unroll 1
            for (int c = 4; c < 8; c++) ld_x(c);
            mbar_wait(bar + 8 * (B_KVF + 2), 0);
            if (rb2 < 4) tma_prefetch2(&p.mapWo128, q2 * 64, rb2 * 128);
            asm volatile("prefetch.tensormap [%0];" ::"l"(&p.mapO) : "memory");
            asm volatile("prefetch.tensormap [%0];" ::"l"(&p.mapO128) : "memory");
            asm volatile("prefetch.tensormap [%0];" ::"l"(&p.mapXT) : "memory");
            asm volatile("prefetch.tensormap [%0];" ::"l"(&p.mapXT3) : "memory");
            mbar_wait(bar + 8 * B_EP, 0);
            epoch = lds32(sb + SM_EP);
          } else {
            mbar_wait(bar + 8 * B_PDONE, 0);
            ld_w(0, 0); ld_w(1, 1);
          }
          {
            int slot = 0;
#pragma unroll 1
            for (int c = 3; c < 8; c++) {
              mbar_wait(bar + 8 * (B_KVE + c - 3), layer);
              ld_w(c, slot);
              slot = slot == 2 ? 0 : slot + 1;
            }
          }
          if (p.stop <= 1 + 3 * layer) return;
          mbar_wait(bar + 8 * B_QDONE, layer);
          if (rb > 0) mbar_wait(bar + 8 * B_HF, layer);
#pragma unroll 1
          for (int c = 0; c < 4; c++) {
            const uint32_t b = bar + 8 * (B_WOF + c);
            mbar_expect(b, 16384);
            tma_ld(sb + SM_X + c * 16384, &p.mapWo128, q2 * 64, c * 128, b);
          }
          {
            const uint32_t b = bar + 8 * B_RF;
            mbar_expect(b, 16384);
            if (layer == 0) tma_ld(sb + SM_R, &p.mapX128, q2 * 64, rb2 * 128, b);
            else tma_ld3(sb + SM_R, &p.mapXT3, 0, DM + q2 * 64, rb2 * 2, b);
          }
          spin_until(&g_cnt[(C_O + rb2) * 32], (2 * epoch + layer + 1) * 16);
          mbar_wait(bar + 8 * B_OST, layer);
          fence_async_global();
#pragma unroll 1
          for (int c = 0; c < 8; c++) {
            const uint32_t b = bar + 8 * (B_OF + c);
            mbar_expect(b, 16384);
            tma_ld(sb + (c < 4 ? SM_X + 65536 + c * 16384 : SM_W + (c - 4) * 16384), &p.mapO128, c * 64, rb2 * 128, b);
          }
          if (p.stop <= 3 + 3 * layer) return;
        }
      }
    } else if (warp == 13) {
      if (elect_one() && p.stop > 3) {
        mbar_wait(bar + 8 * B_GB, 0);
        const unsigned target = (lds32(sb + SM_EP) + 1) * NCTA;
#pragma unroll 1
        for (int lc = 0; lc < 4; lc++) {
          spin_until(&g_cnt[C_G1 * 32 + lc], target);
          if (lc == 3) TS(44);
          fence_async_global();
          fence_async_smem();
#pragma unroll
          for (int c = 2 * lc; c < 2 * lc + 2; c++) {
            mbar_expect(bar + 8 * (B_XF + c), 16384);
            tma_ld3(sb + SM_X + c * 16384, &p.mapXT3, 0, DM + c * 64, rb * 2, bar + 8 * (B_XF + c));
            if (c == 2) {
              mbar_expect(bar + 8 * (B_KVF + 2), 24576);
              tma_ld3(sb + SM_W + 2 * 24576, &p.mapW3, hg * 64, 128, 0, bar + 8 * (B_KVF + 2));
            }
          }
        }
      }
    } else if (warp == 15) {
      if (elect_one()) {
#pragma unroll 1
        for (int i = 0; i < 8; i++) {
          const int layer = i >> 2, lc = i & 3;
          if (p.stop <= 2 + 3 * layer) return;
          mbar_wait(bar + 8 * (B_E + lc), layer);
          bulk_st(g_xT + (size_t)((2 * layer + 1) * DM + cv_chan(cta, lc)) * LSEQ, sb + cv_s(lc), 4096);
          bulk_commit();
          bulk_wait_all();
          red_relaxed(&g_cnt[(layer ? C_F + (cta >> 5) : C_G1) * 32 + lc]);
          if (lc == 3) TS(2 + layer * 20 + 16);
        }
      }
    } else if (warp == 14) {
      mbar_wait(bar + 8 * B_EP, 0);
      const unsigned epoch = lds32(sb + SM_EP);
      {
        uint2 v[6];
        bool ok;
        int it = 0;
        do {
          ok = true;
#pragma unroll
          for (int i = 0; i < 6; i++) {
            const int k = lane + 32 * i;
            asm volatile("ld.relaxed.gpu.global.v2.u32 {%0,%1}, [%2];" : "=r"(v[i].x), "=r"(v[i].y) : "l"(&g_colsum[(k >> 6) * 512 + hg * 64 + (k & 63)]) : "memory");
            ok = ok && v[i].y == epoch + 1;
          }
          if (++it > (1 << 22)) __trap();
        } while (!__all_sync(~0u, ok));
#pragma unroll
        for (int i = 0; i < 6; i++) sts32f(sb + SM_CS + 4 * (lane + 32 * i), __uint_as_float(v[i].x));
      }
      __syncwarp();
      if (lane == 0) {
        mbar_arrive(bar + 8 * B_CSF);
        TS(40);
        mbar_wait(bar + 8 * B_Z0, 0);
        red_release(&g_cnt[C_CS * 32]);
        spin_until(&g_cnt[C_CS * 32], (epoch + 1) * NCTA);
        mbar_arrive(bar + 8 * B_ZF);
#pragma unroll 1
        for (int layer = 0; layer < 2; layer++) {
          if (p.stop <= 1 + 3 * layer) return;
          spin_until(&g_cnt[(layer ? C_G2 : C_G0) * 32], (epoch + 1) * 256);
          mbar_arrive(bar + 8 * B_GB);
        }
      }
    }
  }
}

typedef CUresult (*EncodeFn)(CUtensorMap*, CUtensorMapDataType, cuuint32_t, void*, const cuuint64_t*, const cuuint64_t*,
                             const cuuint32_t*, const cuuint32_t*, CUtensorMapInterleave, CUtensorMapSwizzle,
                             CUtensorMapL2promotion, CUtensorMapFloatOOBfill);

static void make_map(EncodeFn enc, CUtensorMap* m, void* ptr, uint64_t cols, uint64_t rows, uint32_t box_rows) {
  cuuint64_t dims[2] = {cols, rows};
  cuuint64_t strides[1] = {cols * 2};
  cuuint32_t box[2] = {64, box_rows};
  cuuint32_t es[2] = {1, 1};
  enc(m, CU_TENSOR_MAP_DATA_TYPE_BFLOAT16, 2, ptr, dims, strides, box, es, CU_TENSOR_MAP_INTERLEAVE_NONE,
      CU_TENSOR_MAP_SWIZZLE_128B, CU_TENSOR_MAP_L2_PROMOTION_L2_128B, CU_TENSOR_MAP_FLOAT_OOB_FILL_NONE);
}
static void make_map3(EncodeFn enc, CUtensorMap* m, void* ptr, uint64_t d0, uint64_t cols, uint64_t rows, uint64_t blk_stride,
                      uint64_t nblocks, uint32_t nblk) {
  cuuint64_t dims[3] = {d0, rows, nblocks};
  cuuint64_t strides[2] = {cols * 2, blk_stride * 2};
  cuuint32_t box[3] = {64, 64, nblk};
  cuuint32_t es[3] = {1, 1, 1};
  enc(m, CU_TENSOR_MAP_DATA_TYPE_BFLOAT16, 3, ptr, dims, strides, box, es, CU_TENSOR_MAP_INTERLEAVE_NONE,
      CU_TENSOR_MAP_SWIZZLE_128B, CU_TENSOR_MAP_L2_PROMOTION_L2_128B, CU_TENSOR_MAP_FLOAT_OOB_FILL_NONE);
}

extern "C" void kernel_launch(void* const* d_in, const int* in_sizes, int n_in, void* d_out, int out_size) {
  static Params prm;
  static void* cached[13] = {nullptr};
  static bool attr_done = false, by_smid = false;
  bool same = attr_done && cached[12] == d_out;
  for (int i = 0; i < 12 && same; i++) same = cached[i] == d_in[i];
  if (!same) {
    void* fn = nullptr;
    cudaDriverEntryPointQueryResult qr;
    cudaGetDriverEntryPoint("cuTensorMapEncodeTiled", &fn, cudaEnableDefault, &qr);
    EncodeFn enc = (EncodeFn)fn;
    void *pO, *pXT;
    cudaGetSymbolAddress(&pO, g_O);
    cudaGetSymbolAddress(&pXT, g_xT);
    make_map(enc, &prm.mapO, pO, DM, LSEQ, 64);
    make_map(enc, &prm.mapXT, pXT, LSEQ, 4 * DM, 64);
    prm.out = (bf16*)d_out;
    make_map(enc, &prm.mapX128, d_in[0], DM, LSEQ, 128);
    make_map(enc, &prm.mapWo128, d_in[2], DM, DM, 128);
    make_map(enc, &prm.mapO128, pO, DM, LSEQ, 128);
    make_map3(enc, &prm.mapW3, d_in[1], DM, 3 * DM, DM, DM, 3, 3);
    make_map3(enc, &prm.mapXT3, pXT, 64, LSEQ, 4 * DM, 64, 32, 2);
    prm.wqkv = (const bf16*)d_in[1];
    prm.a_re = (const bf16*)d_in[4]; prm.a_im = (const bf16*)d_in[5];
    prm.b_re = (const bf16*)d_in[6]; prm.b_im = (const bf16*)d_in[7];
    prm.c_re = (const bf16*)d_in[8]; prm.c_im = (const bf16*)d_in[9];
    prm.log_dt = (const bf16*)d_in[10]; prm.dskip = (const bf16*)d_in[11];
    int dev = 0, sms = 0;
    cudaGetDevice(&dev);
    cudaDeviceGetAttribute(&sms, cudaDevAttrMultiProcessorCount, dev);
    by_smid = sms == 132;
    cudaFuncSetAttribute(fused_kernel<true>, cudaFuncAttributeMaxDynamicSharedMemorySize, SM_TOTAL);
    cudaFuncSetAttribute(fused_kernel<false>, cudaFuncAttributeMaxDynamicSharedMemorySize, SM_TOTAL);
    for (int i = 0; i < 12; i++) cached[i] = d_in[i];
    cached[12] = d_out;
    attr_done = true;
  }
  prm.stop = 100;
    if (by_smid) fused_kernel<true><<<132, NTHREADS, SM_TOTAL>>>(prm);
  else fused_kernel<false><<<NCTA, NTHREADS, SM_TOTAL>>>(prm);
}
```

```cpp
#include <cuda_runtime.h>
#include <cuda_bf16.h>
#include <cuda.h>
#include <stdint.h>

typedef __nv_bfloat16 bf16;

constexpr int LSEQ = 2048;
constexpr int DM = 512;
constexpr int NCTA = 128;
constexpr int NTHREADS = 512;
#define RR 0
#define KG_PRE 0
#define CS_LATE 0
#define KG_LAST 1
#define X_JIT 0
#define PRE_MAP 1
#define KG_GATE 2
#define R_CONS 192
#define R_HELP 88

constexpr int SM_X = 0;
constexpr int SM_W = 131072;
constexpr int SM_KVX = SM_W;
constexpr int SM_OST = SM_W + 32768;
constexpr int SM_R = 196608;
constexpr int SM_T = 212992;
constexpr int SM_KC = 217088;
constexpr int KC_STRIDE = 648;
constexpr int SM_CS = SM_KC + 4 * KC_STRIDE * 2;
constexpr int SM_RED = SM_CS + 768;
constexpr int SM_EP = SM_RED + 256;
constexpr int SM_BAR = SM_RED + 272;
constexpr int SM_T2 = SM_BAR + 832;
constexpr int SM_HALO = SM_T2 + 4096;
constexpr int SM_TOTAL = SM_HALO + 4096;
static_assert(SM_TOTAL <= 232448, "shared memory");

constexpr int CV_UH = 140 * 16;
constexpr int CV_PECH = 1120 * 4;
constexpr int CV_PBW = 2112 * 2;
__host__ __device__ constexpr int cv_s(int lc) { return SM_X + lc * 32768; }
__host__ __device__ constexpr int cv_u(int lc) { return cv_s(lc) + 4096; }
__host__ __device__ constexpr int cv_pe(int lc) { return cv_u(lc) + 2 * CV_UH; }
__host__ __device__ constexpr int cv_pb(int lc) { return cv_pe(lc) + CV_PECH; }
__host__ __device__ constexpr int cv_ft(int lc) { return cv_pb(lc) + 4 * CV_PBW; }
static_assert(cv_ft(0) + 1024 <= 32768, "conv buffers");
__host__ __device__ constexpr int cv_chan(int cta, int lc) { return cta + 128 * lc; }

enum {
  B_XF = 0,
  B_KVF = 8,
  B_KVE = 16,
  B_AD = 21,
  B_OST = 22,
  B_RF = 23,
  B_U = 24,
  B_S = 28,
  B_T = 32,
  B_WOF = 36,
  B_E = 40,
  B_OF = 44,
  B_P = 64,
  B_HF = 54,
  B_CSF = 55,
  B_QDONE = 56,
  B_PDONE = 57,
  B_Z0 = 58,
  B_PE = 59,
  B_GB = 60,
  B_EP = 62,
  B_ZF = 63,
  B_COUNT = 68
};

enum {
  C_CS = 0,
  C_G0 = 1,
  C_G1 = 2,
  C_G2 = 3,
  C_O = 4,
  C_F = 20,
  C_COUNT = 24
};

__device__ unsigned g_cnt[C_COUNT * 32];
__device__ __align__(1024) bf16 g_O[LSEQ * DM];
__device__ __align__(1024) bf16 g_xT[4 * DM * LSEQ];
__device__ __align__(1024) float g_stats[2 * LSEQ * 2];
__device__ __align__(1024) uint2 g_colsum[3 * DM];
__device__ __align__(1024) uint4 g_halo[2 * 16 * 8 * 384];
__device__ __align__(1024) uint4 g_part[2 * 16 * 8 * 128];
#define TS(i) do { } while (0)

#define FTS(i) do { } while (0)
#define LTS(i) do { } while (0)

struct Params {
  CUtensorMap mapO, mapXT, mapX128, mapWo128, mapO128, mapW3, mapXT3;
  const bf16 *wqkv, *a_re, *a_im, *b_re, *b_im, *c_re, *c_im, *log_dt, *dskip;
  bf16* out;
  int stop;
};

__device__ __forceinline__ uint32_t s32(const void* p) { return (uint32_t)__cvta_generic_to_shared(p); }
__device__ __forceinline__ void mbar_init(uint32_t b, int c) { asm volatile("mbarrier.init.shared::cta.b64 [%0], %1;" ::"r"(b), "r"(c) : "memory"); }
__device__ __forceinline__ void mbar_expect(uint32_t b, int bytes) { asm volatile("mbarrier.arrive.expect_tx.shared::cta.b64 _, [%0], %1;" ::"r"(b), "r"(bytes) : "memory"); }
__device__ __forceinline__ void mbar_arrive(uint32_t b) { asm volatile("mbarrier.arrive.shared::cta.b64 _, [%0];" ::"r"(b) : "memory"); }
__device__ __forceinline__ void mbar_arrive_if(uint32_t b, bool c) {
  asm volatile("{\n.reg .pred p;\nsetp.ne.u32 p, %1, 0;\n@p mbarrier.arrive.shared::cta.b64 _, [%0];\n}" ::"r"(b), "r"((uint32_t)c) : "memory");
}
__device__ __forceinline__ void mbar_wait(uint32_t b, int parity) {
  asm volatile("{\n.reg .pred p;\nWAIT_LOOP:\nmbarrier.try_wait.parity.shared::cta.b64 p, [%0], %1;\n@p bra WAIT_DONE;\nbra WAIT_LOOP;\nWAIT_DONE:\n}" ::"r"(b), "r"(parity) : "memory");
}
__device__ __forceinline__ int opaque_tid() { int v; asm volatile("mov.u32 %0, %%tid.x;" : "=r"(v)); return v; }
__device__ __forceinline__ bool elect_one() {
  uint32_t r;
  asm volatile("{\n.reg .pred p;\nelect.sync _|p, 0xffffffff;\nselp.u32 %0, 1, 0, p;\n}" : "=r"(r));
  return r != 0;
}
__device__ __forceinline__ void tma_ld(uint32_t dst, const CUtensorMap* m, int c0, int c1, uint32_t bar) {
  asm volatile("cp.async.bulk.tensor.2d.shared::cluster.global.mbarrier::complete_tx::bytes [%0], [%1, {%3, %4}], [%2];"
               ::"r"(dst), "l"(m), "r"(bar), "r"(c0), "r"(c1) : "memory");
}
__device__ __forceinline__ void tma_ld3(uint32_t dst, const CUtensorMap* m, int c0, int c1, int c2, uint32_t bar) {
  asm volatile("cp.async.bulk.tensor.3d.shared::cluster.global.mbarrier::complete_tx::bytes [%0], [%1, {%3, %4, %5}], [%2];"
               ::"r"(dst), "l"(m), "r"(bar), "r"(c0), "r"(c1), "r"(c2) : "memory");
}
__device__ __forceinline__ void tma_prefetch2(const CUtensorMap* m, int c0, int c1) {
  asm volatile("cp.async.bulk.prefetch.tensor.2d.L2.global.tile [%0, {%1, %2}];" ::"l"(m), "r"(c0), "r"(c1) : "memory");
}
__device__ __forceinline__ void tma_prefetch3(const CUtensorMap* m, int c0, int c1, int c2) {
  asm volatile("cp.async.bulk.prefetch.tensor.3d.L2.global.tile [%0, {%1, %2, %3}];" ::"l"(m), "r"(c0), "r"(c1), "r"(c2) : "memory");
}
__device__ __forceinline__ void tma_st(const CUtensorMap* m, int c0, int c1, uint32_t src) {
  asm volatile("cp.async.bulk.tensor.2d.global.shared::cta.bulk_group [%0, {%2, %3}], [%1];" ::"l"(m), "r"(src), "r"(c0), "r"(c1) : "memory");
}
__device__ __forceinline__ void bulk_ld(uint32_t dst, const void* src, int bytes, uint32_t bar) {
  asm volatile("cp.async.bulk.shared::cluster.global.mbarrier::complete_tx::bytes [%0], [%1], %2, [%3];" ::"r"(dst), "l"(src), "r"(bytes), "r"(bar) : "memory");
}
__device__ __forceinline__ void bulk_st(void* dst, uint32_t src, int bytes) {
  asm volatile("cp.async.bulk.global.shared::cta.bulk_group [%0], [%1], %2;" ::"l"(dst), "r"(src), "r"(bytes) : "memory");
}
__device__ __forceinline__ void bulk_red_add_f32(void* dst, uint32_t src, int bytes) {
  asm volatile("cp.reduce.async.bulk.global.shared::cta.bulk_group.add.f32 [%0], [%1], %2;" ::"l"(dst), "r"(src), "r"(bytes) : "memory");
}
__device__ __forceinline__ void bulk_commit() { asm volatile("cp.async.bulk.commit_group;" ::: "memory"); }
__device__ __forceinline__ void bulk_wait_all() { asm volatile("cp.async.bulk.wait_group 0;" ::: "memory"); }
__device__ __forceinline__ void fence_async_smem() { asm volatile("fence.proxy.async.shared::cta;" ::: "memory"); }
__device__ __forceinline__ void fence_async_global() { asm volatile("fence.proxy.async.global;" ::: "memory"); }
__device__ __forceinline__ void bar_sync(int id, int n) { asm volatile("bar.sync %0, %1;" ::"r"(id), "r"(n) : "memory"); }
__device__ __forceinline__ void bar_arrive(int id, int n) { asm volatile("bar.arrive %0, %1;" ::"r"(id), "r"(n) : "memory"); }
__device__ __forceinline__ void wg_fence() { asm volatile("wgmma.fence.sync.aligned;" ::: "memory"); }
__device__ __forceinline__ void wg_commit() { asm volatile("wgmma.commit_group.sync.aligned;" ::: "memory"); }
template <int N> __device__ __forceinline__ void wg_wait() { asm volatile("wgmma.wait_group.sync.aligned %0;" ::"n"(N) : "memory"); }
__device__ __forceinline__ uint64_t mkdesc(uint32_t addr, uint32_t lbo, uint32_t sbo, int sw) {
  return (uint64_t)((addr & 0x3FFFF) >> 4) | ((uint64_t)(lbo >> 4) << 16) | ((uint64_t)(sbo >> 4) << 32) | ((uint64_t)sw << 62);
}
__device__ __forceinline__ void ldsm4(uint32_t* r, uint32_t a) {
  asm volatile("ldmatrix.sync.aligned.m8n8.x4.shared.b16 {%0,%1,%2,%3}, [%4];" : "=r"(r[0]), "=r"(r[1]), "=r"(r[2]), "=r"(r[3]) : "r"(a) : "memory");
}
__device__ __forceinline__ void ldsm4t(uint32_t* r, uint32_t a) {
  asm volatile("ldmatrix.sync.aligned.m8n8.x4.trans.shared.b16 {%0,%1,%2,%3}, [%4];" : "=r"(r[0]), "=r"(r[1]), "=r"(r[2]), "=r"(r[3]) : "r"(a) : "memory");
}
__device__ __forceinline__ void stsm4(uint32_t a, uint32_t r0, uint32_t r1, uint32_t r2, uint32_t r3) {
  asm volatile("stmatrix.sync.aligned.m8n8.x4.shared.b16 [%0], {%1,%2,%3,%4};" ::"r"(a), "r"(r0), "r"(r1), "r"(r2), "r"(r3) : "memory");
}
__device__ __forceinline__ void stsm4t(uint32_t a, uint32_t r0, uint32_t r1, uint32_t r2, uint32_t r3) {
  asm volatile("stmatrix.sync.aligned.m8n8.x4.trans.shared.b16 [%0], {%1,%2,%3,%4};" ::"r"(a), "r"(r0), "r"(r1), "r"(r2), "r"(r3) : "memory");
}
__device__ __forceinline__ uint32_t movm_t(uint32_t a) { uint32_t r; asm volatile("movmatrix.sync.aligned.m8n8.trans.b16 %0, %1;" : "=r"(r) : "r"(a)); return r; }
__device__ __forceinline__ uint32_t lds32(uint32_t a) { uint32_t v; asm volatile("ld.shared.b32 %0, [%1];" : "=r"(v) : "r"(a) : "memory"); return v; }
__device__ __forceinline__ float2 lds64f(uint32_t a) { float2 v; asm volatile("ld.shared.v2.f32 {%0,%1}, [%2];" : "=f"(v.x), "=f"(v.y) : "r"(a) : "memory"); return v; }
__device__ __forceinline__ float4 lds128f(uint32_t a) { float4 v; asm volatile("ld.shared.v4.f32 {%0,%1,%2,%3}, [%4];" : "=f"(v.x), "=f"(v.y), "=f"(v.z), "=f"(v.w) : "r"(a) : "memory"); return v; }
__device__ __forceinline__ uint4 lds128(uint32_t a) { uint4 v; asm volatile("ld.shared.v4.b32 {%0,%1,%2,%3}, [%4];" : "=r"(v.x), "=r"(v.y), "=r"(v.z), "=r"(v.w) : "r"(a) : "memory"); return v; }
__device__ __forceinline__ void sts128(uint32_t a, uint4 v) { asm volatile("st.shared.v4.b32 [%0], {%1,%2,%3,%4};" ::"r"(a), "r"(v.x), "r"(v.y), "r"(v.z), "r"(v.w) : "memory"); }
__device__ __forceinline__ void sts128f(uint32_t a, float x, float y, float z, float w) { asm volatile("st.shared.v4.f32 [%0], {%1,%2,%3,%4};" ::"r"(a), "f"(x), "f"(y), "f"(z), "f"(w) : "memory"); }
__device__ __forceinline__ void sts32f(uint32_t a, float v) { asm volatile("st.shared.f32 [%0], %1;" ::"r"(a), "f"(v) : "memory"); }
__device__ __forceinline__ void sts16(uint32_t a, uint16_t v) { asm volatile("st.shared.u16 [%0], %1;" ::"r"(a), "h"(v) : "memory"); }
__device__ __forceinline__ uint32_t lds16(uint32_t a) { uint16_t v; asm volatile("ld.shared.u16 %0, [%1];" : "=h"(v) : "r"(a) : "memory"); return v; }
__device__ __forceinline__ uint32_t packbf(float lo, float hi) { uint32_t r; asm("cvt.rn.bf16x2.f32 %0, %1, %2;" : "=r"(r) : "f"(hi), "f"(lo)); return r; }
__device__ __forceinline__ float bf_lo(uint32_t v) { return __uint_as_float(v << 16); }
__device__ __forceinline__ float bf_hi(uint32_t v) { return __uint_as_float(v & 0xffff0000u); }
__device__ __forceinline__ float ex2(float x) { float r; asm("ex2.approx.ftz.f32 %0, %1;" : "=f"(r) : "f"(x)); return r; }
__device__ __forceinline__ float rsqrt_approx(float x) { float r; asm("rsqrt.approx.ftz.f32 %0, %1;" : "=f"(r) : "f"(x)); return r; }
__device__ __forceinline__ float rcp_approx(float x) { float r; asm("rcp.approx.ftz.f32 %0, %1;" : "=f"(r) : "f"(x)); return r; }
__device__ __forceinline__ void mma_bf16(float* d, const uint32_t* a, uint32_t b0, uint32_t b1) {
  asm("mma.sync.aligned.m16n8k16.row.col.f32.bf16.bf16.f32 {%0,%1,%2,%3}, {%4,%5,%6,%7}, {%8,%9}, {%0,%1,%2,%3};"
               : "+f"(d[0]), "+f"(d[1]), "+f"(d[2]), "+f"(d[3]) : "r"(a[0]), "r"(a[1]), "r"(a[2]), "r"(a[3]), "r"(b0), "r"(b1));
}
__device__ __forceinline__ void red_release(unsigned* p) { asm volatile("red.release.gpu.global.add.u32 [%0], 1;" ::"l"(p) : "memory"); }
__device__ __forceinline__ void red_relaxed(unsigned* p) { asm volatile("red.relaxed.gpu.global.add.u32 [%0], 1;" ::"l"(p) : "memory"); }
__device__ __forceinline__ unsigned ld_relaxed(const unsigned* p) { unsigned v; asm volatile("ld.relaxed.gpu.global.u32 %0, [%1];" : "=r"(v) : "l"(p) : "memory"); return v; }
__device__ __forceinline__ void spin_until(const unsigned* p, unsigned target) {
  int it = 0;
  while ((int)(ld_relaxed(p) - target) < 0) {
    if (++it > (1 << 23)) __trap();
  }
}
__device__ __forceinline__ uint4 ldcg128(const void* p) { uint4 v; asm volatile("ld.global.cg.v4.b32 {%0,%1,%2,%3}, [%4];" : "=r"(v.x), "=r"(v.y), "=r"(v.z), "=r"(v.w) : "l"(p) : "memory"); return v; }
__device__ __forceinline__ uint4 ld_tagged(const uint4* p) { uint4 v; asm volatile("ld.relaxed.gpu.global.v4.u32 {%0,%1,%2,%3}, [%4];" : "=r"(v.x), "=r"(v.y), "=r"(v.z), "=r"(v.w) : "l"(p) : "memory"); return v; }
__device__ __forceinline__ void st_tagged(uint4* p, uint32_t a, uint32_t b, uint32_t tag) { asm volatile("st.relaxed.gpu.global.v4.u32 [%0], {%1,%2,%3,%2};" ::"l"(p), "r"(a), "r"(tag), "r"(b) : "memory"); }
__device__ __forceinline__ void st_tagged3(uint4* p, uint32_t a, uint32_t b, uint32_t c, uint32_t tag) { asm volatile("st.relaxed.gpu.global.v4.u32 [%0], {%1,%2,%3,%4};" ::"l"(p), "r"(a), "r"(b), "r"(c), "r"(tag) : "memory"); }
__device__ __forceinline__ uint4 poll_tagged(const uint4* p, uint32_t tag) {
  uint4 v = ld_tagged(p);
  int it = 0;
  while (v.y != tag || v.w != tag) {
    if (++it > (1 << 22)) __trap();
    v = ld_tagged(p);
  }
  return v;
}
__device__ __forceinline__ uint32_t hadd2(uint32_t a, uint32_t b) { uint32_t r; asm("add.rn.bf16x2 %0, %1, %2;" : "=r"(r) : "r"(a), "r"(b)); return r; }
__device__ __forceinline__ uint32_t hmul2(uint32_t a, uint32_t b) { uint32_t r; asm("mul.rn.bf16x2 %0, %1, %2;" : "=r"(r) : "r"(a), "r"(b)); return r; }

template<int N,int TB> __device__ __forceinline__ void wgmma_rs(float* d, const uint32_t* a, uint64_t db, int sd);
template<int N,int TA,int TB> __device__ __forceinline__ void wgmma_ss(float* d, uint64_t da, uint64_t db, int sd);
template<> __device__ __forceinline__ void wgmma_rs<128,0>(float* d, const uint32_t* a, uint64_t db, int sd) {
  asm volatile("{\n.reg .pred p;\nsetp.ne.b32 p, %69, 0;\nwgmma.mma_async.sync.aligned.m64n128k16.f32.bf16.bf16 {%0,%1,%2,%3,%4,%5,%6,%7,%8,%9,%10,%11,%12,%13,%14,%15,%16,%17,%18,%19,%20,%21,%22,%23,%24,%25,%26,%27,%28,%29,%30,%31,%32,%33,%34,%35,%36,%37,%38,%39,%40,%41,%42,%43,%44,%45,%46,%47,%48,%49,%50,%51,%52,%53,%54,%55,%56,%57,%58,%59,%60,%61,%62,%63}, {%64,%65,%66,%67}, %68, p, 1, 1, 0;\n}\n"
   : "+f"(d[0]),"+f"(d[1]),"+f"(d[2]),"+f"(d[3]),"+f"(d[4]),"+f"(d[5]),"+f"(d[6]),"+f"(d[7]),"+f"(d[8]),"+f"(d[9]),"+f"(d[10]),"+f"(d[11]),"+f"(d[12]),"+f"(d[13]),"+f"(d[14]),"+f"(d[15]),"+f"(d[16]),"+f"(d[17]),"+f"(d[18]),"+f"(d[19]),"+f"(d[20]),"+f"(d[21]),"+f"(d[22]),"+f"(d[23]),"+f"(d[24]),"+f"(d[25]),"+f"(d[26]),"+f"(d[27]),"+f"(d[28]),"+f"(d[29]),"+f"(d[30]),"+f"(d[31]),"+f"(d[32]),"+f"(d[33]),"+f"(d[34]),"+f"(d[35]),"+f"(d[36]),"+f"(d[37]),"+f"(d[38]),"+f"(d[39]),"+f"(d[40]),"+f"(d[41]),"+f"(d[42]),"+f"(d[43]),"+f"(d[44]),"+f"(d[45]),"+f"(d[46]),"+f"(d[47]),"+f"(d[48]),"+f"(d[49]),"+f"(d[50]),"+f"(d[51]),"+f"(d[52]),"+f"(d[53]),"+f"(d[54]),"+f"(d[55]),"+f"(d[56]),"+f"(d[57]),"+f"(d[58]),"+f"(d[59]),"+f"(d[60]),"+f"(d[61]),"+f"(d[62]),"+f"(d[63])
   : "r"(a[0]), "r"(a[1]), "r"(a[2]), "r"(a[3]), "l"(db), "r"(sd));
}
template<> __device__ __forceinline__ void wgmma_rs<120,0>(float* d, const uint32_t* a, uint64_t db, int sd) {
  asm volatile("{\n.reg .pred p;\nsetp.ne.b32 p, %65, 0;\nwgmma.mma_async.sync.aligned.m64n120k16.f32.bf16.bf16 {%0,%1,%2,%3,%4,%5,%6,%7,%8,%9,%10,%11,%12,%13,%14,%15,%16,%17,%18,%19,%20,%21,%22,%23,%24,%25,%26,%27,%28,%29,%30,%31,%32,%33,%34,%35,%36,%37,%38,%39,%40,%41,%42,%43,%44,%45,%46,%47,%48,%49,%50,%51,%52,%53,%54,%55,%56,%57,%58,%59}, {%60,%61,%62,%63}, %64, p, 1, 1, 0;\n}\n"
   : "+f"(d[0]),"+f"(d[1]),"+f"(d[2]),"+f"(d[3]),"+f"(d[4]),"+f"(d[5]),"+f"(d[6]),"+f"(d[7]),"+f"(d[8]),"+f"(d[9]),"+f"(d[10]),"+f"(d[11]),"+f"(d[12]),"+f"(d[13]),"+f"(d[14]),"+f"(d[15]),"+f"(d[16]),"+f"(d[17]),"+f"(d[18]),"+f"(d[19]),"+f"(d[20]),"+f"(d[21]),"+f"(d[22]),"+f"(d[23]),"+f"(d[24]),"+f"(d[25]),"+f"(d[26]),"+f"(d[27]),"+f"(d[28]),"+f"(d[29]),"+f"(d[30]),"+f"(d[31]),"+f"(d[32]),"+f"(d[33]),"+f"(d[34]),"+f"(d[35]),"+f"(d[36]),"+f"(d[37]),"+f"(d[38]),"+f"(d[39]),"+f"(d[40]),"+f"(d[41]),"+f"(d[42]),"+f"(d[43]),"+f"(d[44]),"+f"(d[45]),"+f"(d[46]),"+f"(d[47]),"+f"(d[48]),"+f"(d[49]),"+f"(d[50]),"+f"(d[51]),"+f"(d[52]),"+f"(d[53]),"+f"(d[54]),"+f"(d[55]),"+f"(d[56]),"+f"(d[57]),"+f"(d[58]),"+f"(d[59])
   : "r"(a[0]), "r"(a[1]), "r"(a[2]), "r"(a[3]), "l"(db), "r"(sd));
}
template<> __device__ __forceinline__ void wgmma_rs<112,0>(float* d, const uint32_t* a, uint64_t db, int sd) {
  asm volatile("{\n.reg .pred p;\nsetp.ne.b32 p, %61, 0;\nwgmma.mma_async.sync.aligned.m64n112k16.f32.bf16.bf16 {%0,%1,%2,%3,%4,%5,%6,%7,%8,%9,%10,%11,%12,%13,%14,%15,%16,%17,%18,%19,%20,%21,%22,%23,%24,%25,%26,%27,%28,%29,%30,%31,%32,%33,%34,%35,%36,%37,%38,%39,%40,%41,%42,%43,%44,%45,%46,%47,%48,%49,%50,%51,%52,%53,%54,%55}, {%56,%57,%58,%59}, %60, p, 1, 1, 0;\n}\n"
   : "+f"(d[0]),"+f"(d[1]),"+f"(d[2]),"+f"(d[3]),"+f"(d[4]),"+f"(d[5]),"+f"(d[6]),"+f"(d[7]),"+f"(d[8]),"+f"(d[9]),"+f"(d[10]),"+f"(d[11]),"+f"(d[12]),"+f"(d[13]),"+f"(d[14]),"+f"(d[15]),"+f"(d[16]),"+f"(d[17]),"+f"(d[18]),"+f"(d[19]),"+f"(d[20]),"+f"(d[21]),"+f"(d[22]),"+f"(d[23]),"+f"(d[24]),"+f"(d[25]),"+f"(d[26]),"+f"(d[27]),"+f"(d[28]),"+f"(d[29]),"+f"(d[30]),"+f"(d[31]),"+f"(d[32]),"+f"(d[33]),"+f"(d[34]),"+f"(d[35]),"+f"(d[36]),"+f"(d[37]),"+f"(d[38]),"+f"(d[39]),"+f"(d[40]),"+f"(d[41]),"+f"(d[42]),"+f"(d[43]),"+f"(d[44]),"+f"(d[45]),"+f"(d[46]),"+f"(d[47]),"+f"(d[48]),"+f"(d[49]),"+f"(d[50]),"+f"(d[51]),"+f"(d[52]),"+f"(d[53]),"+f"(d[54]),"+f"(d[55])
   : "r"(a[0]), "r"(a[1]), "r"(a[2]), "r"(a[3]), "l"(db), "r"(sd));
}
template<> __device__ __forceinline__ void wgmma_rs<104,0>(float* d, const uint32_t* a, uint64_t db, int sd) {
  asm volatile("{\n.reg .pred p;\nsetp.ne.b32 p, %57, 0;\nwgmma.mma_async.sync.aligned.m64n104k16.f32.bf16.bf16 {%0,%1,%2,%3,%4,%5,%6,%7,%8,%9,%10,%11,%12,%13,%14,%15,%16,%17,%18,%19,%20,%21,%22,%23,%24,%25,%26,%27,%28,%29,%30,%31,%32,%33,%34,%35,%36,%37,%38,%39,%40,%41,%42,%43,%44,%45,%46,%47,%48,%49,%50,%51}, {%52,%53,%54,%55}, %56, p, 1, 1, 0;\n}\n"
   : "+f"(d[0]),"+f"(d[1]),"+f"(d[2]),"+f"(d[3]),"+f"(d[4]),"+f"(d[5]),"+f"(d[6]),"+f"(d[7]),"+f"(d[8]),"+f"(d[9]),"+f"(d[10]),"+f"(d[11]),"+f"(d[12]),"+f"(d[13]),"+f"(d[14]),"+f"(d[15]),"+f"(d[16]),"+f"(d[17]),"+f"(d[18]),"+f"(d[19]),"+f"(d[20]),"+f"(d[21]),"+f"(d[22]),"+f"(d[23]),"+f"(d[24]),"+f"(d[25]),"+f"(d[26]),"+f"(d[27]),"+f"(d[28]),"+f"(d[29]),"+f"(d[30]),"+f"(d[31]),"+f"(d[32]),"+f"(d[33]),"+f"(d[34]),"+f"(d[35]),"+f"(d[36]),"+f"(d[37]),"+f"(d[38]),"+f"(d[39]),"+f"(d[40]),"+f"(d[41]),"+f"(d[42]),"+f"(d[43]),"+f"(d[44]),"+f"(d[45]),"+f"(d[46]),"+f"(d[47]),"+f"(d[48]),"+f"(d[49]),"+f"(d[50]),"+f"(d[51])
   : "r"(a[0]), "r"(a[1]), "r"(a[2]), "r"(a[3]), "l"(db), "r"(sd));
}
template<> __device__ __forceinline__ void wgmma_rs<96,0>(float* d, const uint32_t* a, uint64_t db, int sd) {
  asm volatile("{\n.reg .pred p;\nsetp.ne.b32 p, %53, 0;\nwgmma.mma_async.sync.aligned.m64n96k16.f32.bf16.bf16 {%0,%1,%2,%3,%4,%5,%6,%7,%8,%9,%10,%11,%12,%13,%14,%15,%16,%17,%18,%19,%20,%21,%22,%23,%24,%25,%26,%27,%28,%29,%30,%31,%32,%33,%34,%35,%36,%37,%38,%39,%40,%41,%42,%43,%44,%45,%46,%47}, {%48,%49,%50,%51}, %52, p, 1, 1, 0;\n}\n"
   : "+f"(d[0]),"+f"(d[1]),"+f"(d[2]),"+f"(d[3]),"+f"(d[4]),"+f"(d[5]),"+f"(d[6]),"+f"(d[7]),"+f"(d[8]),"+f"(d[9]),"+f"(d[10]),"+f"(d[11]),"+f"(d[12]),"+f"(d[13]),"+f"(d[14]),"+f"(d[15]),"+f"(d[16]),"+f"(d[17]),"+f"(d[18]),"+f"(d[19]),"+f"(d[20]),"+f"(d[21]),"+f"(d[22]),"+f"(d[23]),"+f"(d[24]),"+f"(d[25]),"+f"(d[26]),"+f"(d[27]),"+f"(d[28]),"+f"(d[29]),"+f"(d[30]),"+f"(d[31]),"+f"(d[32]),"+f"(d[33]),"+f"(d[34]),"+f"(d[35]),"+f"(d[36]),"+f"(d[37]),"+f"(d[38]),"+f"(d[39]),"+f"(d[40]),"+f"(d[41]),"+f"(d[42]),"+f"(d[43]),"+f"(d[44]),"+f"(d[45]),"+f"(d[46]),"+f"(d[47])
   : "r"(a[0]), "r"(a[1]), "r"(a[2]), "r"(a[3]), "l"(db), "r"(sd));
}
template<> __device__ __forceinline__ void wgmma_rs<88,0>(float* d, const uint32_t* a, uint64_t db, int sd) {
  asm volatile("{\n.reg .pred p;\nsetp.ne.b32 p, %49, 0;\nwgmma.mma_async.sync.aligned.m64n88k16.f32.bf16.bf16 {%0,%1,%2,%3,%4,%5,%6,%7,%8,%9,%10,%11,%12,%13,%14,%15,%16,%17,%18,%19,%20,%21,%22,%23,%24,%25,%26,%27,%28,%29,%30,%31,%32,%33,%34,%35,%36,%37,%38,%39,%40,%41,%42,%43}, {%44,%45,%46,%47}, %48, p, 1, 1, 0;\n}\n"
   : "+f"(d[0]),"+f"(d[1]),"+f"(d[2]),"+f"(d[3]),"+f"(d[4]),"+f"(d[5]),"+f"(d[6]),"+f"(d[7]),"+f"(d[8]),"+f"(d[9]),"+f"(d[10]),"+f"(d[11]),"+f"(d[12]),"+f"(d[13]),"+f"(d[14]),"+f"(d[15]),"+f"(d[16]),"+f"(d[17]),"+f"(d[18]),"+f"(d[19]),"+f"(d[20]),"+f"(d[21]),"+f"(d[22]),"+f"(d[23]),"+f"(d[24]),"+f"(d[25]),"+f"(d[26]),"+f"(d[27]),"+f"(d[28]),"+f"(d[29]),"+f"(d[30]),"+f"(d[31]),"+f"(d[32]),"+f"(d[33]),"+f"(d[34]),"+f"(d[35]),"+f"(d[36]),"+f"(d[37]),"+f"(d[38]),"+f"(d[39]),"+f"(d[40]),"+f"(d[41]),"+f"(d[42]),"+f"(d[43])
   : "r"(a[0]), "r"(a[1]), "r"(a[2]), "r"(a[3]), "l"(db), "r"(sd));
}
template<> __device__ __forceinline__ void wgmma_rs<80,0>(float* d, const uint32_t* a, uint64_t db, int sd) {
  asm volatile("{\n.reg .pred p;\nsetp.ne.b32 p, %45, 0;\nwgmma.mma_async.sync.aligned.m64n80k16.f32.bf16.bf16 {%0,%1,%2,%3,%4,%5,%6,%7,%8,%9,%10,%11,%12,%13,%14,%15,%16,%17,%18,%19,%20,%21,%22,%23,%24,%25,%26,%27,%28,%29,%30,%31,%32,%33,%34,%35,%36,%37,%38,%39}, {%40,%41,%42,%43}, %44, p, 1, 1, 0;\n}\n"
   : "+f"(d[0]),"+f"(d[1]),"+f"(d[2]),"+f"(d[3]),"+f"(d[4]),"+f"(d[5]),"+f"(d[6]),"+f"(d[7]),"+f"(d[8]),"+f"(d[9]),"+f"(d[10]),"+f"(d[11]),"+f"(d[12]),"+f"(d[13]),"+f"(d[14]),"+f"(d[15]),"+f"(d[16]),"+f"(d[17]),"+f"(d[18]),"+f"(d[19]),"+f"(d[20]),"+f"(d[21]),"+f"(d[22]),"+f"(d[23]),"+f"(d[24]),"+f"(d[25]),"+f"(d[26]),"+f"(d[27]),"+f"(d[28]),"+f"(d[29]),"+f"(d[30]),"+f"(d[31]),"+f"(d[32]),"+f"(d[33]),"+f"(d[34]),"+f"(d[35]),"+f"(d[36]),"+f"(d[37]),"+f"(d[38]),"+f"(d[39])
   : "r"(a[0]), "r"(a[1]), "r"(a[2]), "r"(a[3]), "l"(db), "r"(sd));
}
template<> __device__ __forceinline__ void wgmma_rs<72,0>(float* d, const uint32_t* a, uint64_t db, int sd) {
  asm volatile("{\n.reg .pred p;\nsetp.ne.b32 p, %41, 0;\nwgmma.mma_async.sync.aligned.m64n72k16.f32.bf16.bf16 {%0,%1,%2,%3,%4,%5,%6,%7,%8,%9,%10,%11,%12,%13,%14,%15,%16,%17,%18,%19,%20,%21,%22,%23,%24,%25,%26,%27,%28,%29,%30,%31,%32,%33,%34,%35}, {%36,%37,%38,%39}, %40, p, 1, 1, 0;\n}\n"
   : "+f"(d[0]),"+f"(d[1]),"+f"(d[2]),"+f"(d[3]),"+f"(d[4]),"+f"(d[5]),"+f"(d[6]),"+f"(d[7]),"+f"(d[8]),"+f"(d[9]),"+f"(d[10]),"+f"(d[11]),"+f"(d[12]),"+f"(d[13]),"+f"(d[14]),"+f"(d[15]),"+f"(d[16]),"+f"(d[17]),"+f"(d[18]),"+f"(d[19]),"+f"(d[20]),"+f"(d[21]),"+f"(d[22]),"+f"(d[23]),"+f"(d[24]),"+f"(d[25]),"+f"(d[26]),"+f"(d[27]),"+f"(d[28]),"+f"(d[29]),"+f"(d[30]),"+f"(d[31]),"+f"(d[32]),"+f"(d[33]),"+f"(d[34]),"+f"(d[35])
   : "r"(a[0]), "r"(a[1]), "r"(a[2]), "r"(a[3]), "l"(db), "r"(sd));
}
template<> __device__ __forceinline__ void wgmma_rs<64,0>(float* d, const uint32_t* a, uint64_t db, int sd) {
  asm volatile("{\n.reg .pred p;\nsetp.ne.b32 p, %37, 0;\nwgmma.mma_async.sync.aligned.m64n64k16.f32.bf16.bf16 {%0,%1,%2,%3,%4,%5,%6,%7,%8,%9,%10,%11,%12,%13,%14,%15,%16,%17,%18,%19,%20,%21,%22,%23,%24,%25,%26,%27,%28,%29,%30,%31}, {%32,%33,%34,%35}, %36, p, 1, 1, 0;\n}\n"
   : "+f"(d[0]),"+f"(d[1]),"+f"(d[2]),"+f"(d[3]),"+f"(d[4]),"+f"(d[5]),"+f"(d[6]),"+f"(d[7]),"+f"(d[8]),"+f"(d[9]),"+f"(d[10]),"+f"(d[11]),"+f"(d[12]),"+f"(d[13]),"+f"(d[14]),"+f"(d[15]),"+f"(d[16]),"+f"(d[17]),"+f"(d[18]),"+f"(d[19]),"+f"(d[20]),"+f"(d[21]),"+f"(d[22]),"+f"(d[23]),"+f"(d[24]),"+f"(d[25]),"+f"(d[26]),"+f"(d[27]),"+f"(d[28]),"+f"(d[29]),"+f"(d[30]),"+f"(d[31])
   : "r"(a[0]), "r"(a[1]), "r"(a[2]), "r"(a[3]), "l"(db), "r"(sd));
}
template<> __device__ __forceinline__ void wgmma_ss<64,0,1>(float* d, uint64_t da, uint64_t db, int sd) {
  asm volatile("{\n.reg .pred p;\nsetp.ne.b32 p, %34, 0;\nwgmma.mma_async.sync.aligned.m64n64k16.f32.bf16.bf16 {%0,%1,%2,%3,%4,%5,%6,%7,%8,%9,%10,%11,%12,%13,%14,%15,%16,%17,%18,%19,%20,%21,%22,%23,%24,%25,%26,%27,%28,%29,%30,%31}, %32, %33, p, 1, 1, 0, 1;\n}\n"
   : "+f"(d[0]),"+f"(d[1]),"+f"(d[2]),"+f"(d[3]),"+f"(d[4]),"+f"(d[5]),"+f"(d[6]),"+f"(d[7]),"+f"(d[8]),"+f"(d[9]),"+f"(d[10]),"+f"(d[11]),"+f"(d[12]),"+f"(d[13]),"+f"(d[14]),"+f"(d[15]),"+f"(d[16]),"+f"(d[17]),"+f"(d[18]),"+f"(d[19]),"+f"(d[20]),"+f"(d[21]),"+f"(d[22]),"+f"(d[23]),"+f"(d[24]),"+f"(d[25]),"+f"(d[26]),"+f"(d[27]),"+f"(d[28]),"+f"(d[29]),"+f"(d[30]),"+f"(d[31])
   : "l"(da), "l"(db), "r"(sd));
}
template<> __device__ __forceinline__ void wgmma_ss<64,1,1>(float* d, uint64_t da, uint64_t db, int sd) {
  asm volatile("{\n.reg .pred p;\nsetp.ne.b32 p, %34, 0;\nwgmma.mma_async.sync.aligned.m64n64k16.f32.bf16.bf16 {%0,%1,%2,%3,%4,%5,%6,%7,%8,%9,%10,%11,%12,%13,%14,%15,%16,%17,%18,%19,%20,%21,%22,%23,%24,%25,%26,%27,%28,%29,%30,%31}, %32, %33, p, 1, 1, 1, 1;\n}\n"
   : "+f"(d[0]),"+f"(d[1]),"+f"(d[2]),"+f"(d[3]),"+f"(d[4]),"+f"(d[5]),"+f"(d[6]),"+f"(d[7]),"+f"(d[8]),"+f"(d[9]),"+f"(d[10]),"+f"(d[11]),"+f"(d[12]),"+f"(d[13]),"+f"(d[14]),"+f"(d[15]),"+f"(d[16]),"+f"(d[17]),"+f"(d[18]),"+f"(d[19]),"+f"(d[20]),"+f"(d[21]),"+f"(d[22]),"+f"(d[23]),"+f"(d[24]),"+f"(d[25]),"+f"(d[26]),"+f"(d[27]),"+f"(d[28]),"+f"(d[29]),"+f"(d[30]),"+f"(d[31])
   : "l"(da), "l"(db), "r"(sd));
}
template<> __device__ __forceinline__ void wgmma_ss<192,0,1>(float* d, uint64_t da, uint64_t db, int sd) {
  asm volatile("{\n.reg .pred p;\nsetp.ne.b32 p, %98, 0;\nwgmma.mma_async.sync.aligned.m64n192k16.f32.bf16.bf16 {%0,%1,%2,%3,%4,%5,%6,%7,%8,%9,%10,%11,%12,%13,%14,%15,%16,%17,%18,%19,%20,%21,%22,%23,%24,%25,%26,%27,%28,%29,%30,%31,%32,%33,%34,%35,%36,%37,%38,%39,%40,%41,%42,%43,%44,%45,%46,%47,%48,%49,%50,%51,%52,%53,%54,%55,%56,%57,%58,%59,%60,%61,%62,%63,%64,%65,%66,%67,%68,%69,%70,%71,%72,%73,%74,%75,%76,%77,%78,%79,%80,%81,%82,%83,%84,%85,%86,%87,%88,%89,%90,%91,%92,%93,%94,%95}, %96, %97, p, 1, 1, 0, 1;\n}\n"
   : "+f"(d[0]),"+f"(d[1]),"+f"(d[2]),"+f"(d[3]),"+f"(d[4]),"+f"(d[5]),"+f"(d[6]),"+f"(d[7]),"+f"(d[8]),"+f"(d[9]),"+f"(d[10]),"+f"(d[11]),"+f"(d[12]),"+f"(d[13]),"+f"(d[14]),"+f"(d[15]),"+f"(d[16]),"+f"(d[17]),"+f"(d[18]),"+f"(d[19]),"+f"(d[20]),"+f"(d[21]),"+f"(d[22]),"+f"(d[23]),"+f"(d[24]),"+f"(d[25]),"+f"(d[26]),"+f"(d[27]),"+f"(d[28]),"+f"(d[29]),"+f"(d[30]),"+f"(d[31]),"+f"(d[32]),"+f"(d[33]),"+f"(d[34]),"+f"(d[35]),"+f"(d[36]),"+f"(d[37]),"+f"(d[38]),"+f"(d[39]),"+f"(d[40]),"+f"(d[41]),"+f"(d[42]),"+f"(d[43]),"+f"(d[44]),"+f"(d[45]),"+f"(d[46]),"+f"(d[47]),"+f"(d[48]),"+f"(d[49]),"+f"(d[50]),"+f"(d[51]),"+f"(d[52]),"+f"(d[53]),"+f"(d[54]),"+f"(d[55]),"+f"(d[56]),"+f"(d[57]),"+f"(d[58]),"+f"(d[59]),"+f"(d[60]),"+f"(d[61]),"+f"(d[62]),"+f"(d[63]),"+f"(d[64]),"+f"(d[65]),"+f"(d[66]),"+f"(d[67]),"+f"(d[68]),"+f"(d[69]),"+f"(d[70]),"+f"(d[71]),"+f"(d[72]),"+f"(d[73]),"+f"(d[74]),"+f"(d[75]),"+f"(d[76]),"+f"(d[77]),"+f"(d[78]),"+f"(d[79]),"+f"(d[80]),"+f"(d[81]),"+f"(d[82]),"+f"(d[83]),"+f"(d[84]),"+f"(d[85]),"+f"(d[86]),"+f"(d[87]),"+f"(d[88]),"+f"(d[89]),"+f"(d[90]),"+f"(d[91]),"+f"(d[92]),"+f"(d[93]),"+f"(d[94]),"+f"(d[95])
   : "l"(da), "l"(db), "r"(sd));
}
template<> __device__ __forceinline__ void wgmma_ss<192,1,1>(float* d, uint64_t da, uint64_t db, int sd) {
  asm volatile("{\n.reg .pred p;\nsetp.ne.b32 p, %98, 0;\nwgmma.mma_async.sync.aligned.m64n192k16.f32.bf16.bf16 {%0,%1,%2,%3,%4,%5,%6,%7,%8,%9,%10,%11,%12,%13,%14,%15,%16,%17,%18,%19,%20,%21,%22,%23,%24,%25,%26,%27,%28,%29,%30,%31,%32,%33,%34,%35,%36,%37,%38,%39,%40,%41,%42,%43,%44,%45,%46,%47,%48,%49,%50,%51,%52,%53,%54,%55,%56,%57,%58,%59,%60,%61,%62,%63,%64,%65,%66,%67,%68,%69,%70,%71,%72,%73,%74,%75,%76,%77,%78,%79,%80,%81,%82,%83,%84,%85,%86,%87,%88,%89,%90,%91,%92,%93,%94,%95}, %96, %97, p, 1, 1, 1, 1;\n}\n"
   : "+f"(d[0]),"+f"(d[1]),"+f"(d[2]),"+f"(d[3]),"+f"(d[4]),"+f"(d[5]),"+f"(d[6]),"+f"(d[7]),"+f"(d[8]),"+f"(d[9]),"+f"(d[10]),"+f"(d[11]),"+f"(d[12]),"+f"(d[13]),"+f"(d[14]),"+f"(d[15]),"+f"(d[16]),"+f"(d[17]),"+f"(d[18]),"+f"(d[19]),"+f"(d[20]),"+f"(d[21]),"+f"(d[22]),"+f"(d[23]),"+f"(d[24]),"+f"(d[25]),"+f"(d[26]),"+f"(d[27]),"+f"(d[28]),"+f"(d[29]),"+f"(d[30]),"+f"(d[31]),"+f"(d[32]),"+f"(d[33]),"+f"(d[34]),"+f"(d[35]),"+f"(d[36]),"+f"(d[37]),"+f"(d[38]),"+f"(d[39]),"+f"(d[40]),"+f"(d[41]),"+f"(d[42]),"+f"(d[43]),"+f"(d[44]),"+f"(d[45]),"+f"(d[46]),"+f"(d[47]),"+f"(d[48]),"+f"(d[49]),"+f"(d[50]),"+f"(d[51]),"+f"(d[52]),"+f"(d[53]),"+f"(d[54]),"+f"(d[55]),"+f"(d[56]),"+f"(d[57]),"+f"(d[58]),"+f"(d[59]),"+f"(d[60]),"+f"(d[61]),"+f"(d[62]),"+f"(d[63]),"+f"(d[64]),"+f"(d[65]),"+f"(d[66]),"+f"(d[67]),"+f"(d[68]),"+f"(d[69]),"+f"(d[70]),"+f"(d[71]),"+f"(d[72]),"+f"(d[73]),"+f"(d[74]),"+f"(d[75]),"+f"(d[76]),"+f"(d[77]),"+f"(d[78]),"+f"(d[79]),"+f"(d[80]),"+f"(d[81]),"+f"(d[82]),"+f"(d[83]),"+f"(d[84]),"+f"(d[85]),"+f"(d[86]),"+f"(d[87]),"+f"(d[88]),"+f"(d[89]),"+f"(d[90]),"+f"(d[91]),"+f"(d[92]),"+f"(d[93]),"+f"(d[94]),"+f"(d[95])
   : "l"(da), "l"(db), "r"(sd));
}

#define HOLD 0
template <bool TR>
__device__ __forceinline__ void gemm_section(float* acc, float& mean0, float& mean1, float& rstd0, float& rstd1,
                                             uint32_t sb, int layer, int rb, int hg, int wg, int w, int lane) {
  const uint32_t bar = sb + SM_BAR;
  const int g = lane >> 2, t = lane & 3;
  const bool leader = (w == 0) && (lane == 0);
  const int row0 = 64 * wg + 16 * w;
  auto issue = [&](int c, int slot) {
    mbar_wait(bar + 8 * (B_XF + c), layer);
    mbar_wait(bar + 8 * (B_KVF + c), layer);
    const uint64_t da = mkdesc(sb + SM_X + c * 16384 + wg * 8192, TR ? 8192 : 16, 1024, 1);
    const uint64_t db = mkdesc(sb + SM_W + slot * 24576, 8192, 1024, 1);
    wg_fence();
#pragma unroll
    for (int ks = 0; ks < 4; ks++) wgmma_ss<192, TR ? 1 : 0, 1>(acc, da + (TR ? ks * 128 : ks * 2), db + ks * 128, (c | ks) != 0);
    wg_commit();
  };
  auto step = [&](int c, int slot) {
    issue(c, slot);
    wg_wait<1>();
    if (leader) mbar_arrive(bar + 8 * (B_KVE + c - 1));
  };
  issue(0, 0);
  if (threadIdx.x == 0) TS(2 + layer * 20 + 0);
  if (threadIdx.x == 128 && layer == 1) TS(60);
  step(1, 1); step(2, 2); step(3, 0);
  issue(4, 1);
  mbar_wait(bar + 8 * B_EP, 0);
  const uint32_t tag = 2 * lds32(sb + SM_EP) + layer + 1;
  {
    mbar_wait(bar + 8 * (B_XF + hg), layer);
    uint32_t A[16];
    const uint32_t xb = sb + SM_X + hg * 16384 + wg * 8192;
#pragma unroll
    for (int ks = 0; ks < 4; ks++) {
      if (!TR) {
        const int row = 16 * w + (lane & 15), kc = 2 * ks + (lane >> 4);
        ldsm4(&A[4 * ks], xb + row * 128 + ((kc ^ (row & 7)) << 4));
      } else {
        const int k = 16 * ks + (lane & 7) + 8 * (lane >> 4), pc = 2 * w + ((lane >> 3) & 1);
        ldsm4t(&A[4 * ks], xb + k * 128 + ((pc ^ (k & 7)) << 4));
      }
    }
    float s0 = 0.f, q0 = 0.f, s1 = 0.f, q1 = 0.f;
#pragma unroll
    for (int i = 0; i < 16; i += 2) {
      const float a = bf_lo(A[i]), b = bf_hi(A[i]), c_ = bf_lo(A[i + 1]), d = bf_hi(A[i + 1]);
      s0 += a + b; q0 = fmaf(a, a, q0); q0 = fmaf(b, b, q0);
      s1 += c_ + d; q1 = fmaf(c_, c_, q1); q1 = fmaf(d, d, q1);
    }
#pragma unroll
    for (int o = 1; o <= 2; o <<= 1) {
      s0 += __shfl_xor_sync(~0u, s0, o); q0 += __shfl_xor_sync(~0u, q0, o);
      s1 += __shfl_xor_sync(~0u, s1, o); q1 += __shfl_xor_sync(~0u, q1, o);
    }
    if (t < 2)
      st_tagged(&g_part[(rb * 8 + hg) * 128 + row0 + g + 8 * t], __float_as_uint(t ? s1 : s0), __float_as_uint(t ? q1 : q0), tag);
  }
  wg_wait<1>();
  if (leader) mbar_arrive(bar + 8 * (B_KVE + 3));
  step(5, 2);
  issue(6, 0);
  wg_wait<1>();
  const uint4* psrc = &g_part[(rb * 8 + 2 * t) * 128 + row0 + g];
  uint4 a0 = ld_tagged(psrc), a1 = ld_tagged(psrc + 8), b0 = ld_tagged(psrc + 128), b1 = ld_tagged(psrc + 136);
  if (wg == 0) bar_sync(5, 256);
  issue(7, 1);
  if (wg == 1) bar_arrive(5, 256);
  int it = 0;
  while (!__all_sync(~0u, a0.y == tag && a0.w == tag && a1.y == tag && a1.w == tag && b0.y == tag && b0.w == tag && b1.y == tag && b1.w == tag) &&
         ++it < (1 << 20)) {
    a0 = ld_tagged(psrc); a1 = ld_tagged(psrc + 8); b0 = ld_tagged(psrc + 128); b1 = ld_tagged(psrc + 136);
  }
  float s0 = __uint_as_float(a0.x) + __uint_as_float(b0.x), q0 = __uint_as_float(a0.z) + __uint_as_float(b0.z);
  float s1 = __uint_as_float(a1.x) + __uint_as_float(b1.x), q1 = __uint_as_float(a1.z) + __uint_as_float(b1.z);
#pragma unroll
  for (int o = 1; o <= 2; o <<= 1) {
    s0 += __shfl_xor_sync(~0u, s0, o); q0 += __shfl_xor_sync(~0u, q0, o);
    s1 += __shfl_xor_sync(~0u, s1, o); q1 += __shfl_xor_sync(~0u, q1, o);
  }
  mean0 = s0 * (1.f / DM); mean1 = s1 * (1.f / DM);
  rstd0 = rsqrt_approx(fmaxf(q0 * (1.f / DM) - mean0 * mean0, 0.f) + 1e-5f);
  rstd1 = rsqrt_approx(fmaxf(q1 * (1.f / DM) - mean1 * mean1, 0.f) + 1e-5f);
  mbar_wait(bar + 8 * B_CSF, 0);
  wg_wait<0>();
}

__device__ __forceinline__ void attn_phase(const Params& p, uint32_t sb, int layer, int rb, int hg, int wg, int w) {
  const int lane = opaque_tid() & 31;
  const int g = lane >> 2, t = lane & 3;
  const uint32_t bar = sb + SM_BAR;
  const int row0 = 64 * wg + 16 * w;
  const bool leader = (w == 0) && (lane == 0);
  float acc[96];
  float2 cs[24];
  float mean0, mean1, rstd0, rstd1;
  if (layer) gemm_section<true>(acc, mean0, mean1, rstd0, rstd1, sb, layer, rb, hg, wg, w, lane);
  else gemm_section<false>(acc, mean0, mean1, rstd0, rstd1, sb, layer, rb, hg, wg, w, lane);
  const uint32_t tag = 2 * lds32(sb + SM_EP) + layer + 1;
  if (threadIdx.x == 0) TS(2 + layer * 20 + 1);
  if (leader) mbar_arrive(bar + 8 * B_QDONE);
#pragma unroll
  for (int j = 8; j < 24; j++) cs[j] = lds64f(sb + SM_CS + 4 * (8 * j + 2 * t));

  uint32_t kb[4][8], vb[4][8], qa[4][4];
  {
    const float nm0 = -mean0 * rstd0, nm1 = -mean1 * rstd1;
    const int st_row = row0 + (lane & 7) + 8 * ((lane >> 3) & 1);
    const uint32_t st_base = sb + SM_KVX + st_row * 256;
    const bool sender = (wg == 1 && w == 3 && rb < 15);
    uint4* halo = &g_halo[(rb * 8 + hg) * 384 + lane];
    if (wg == 0 && w == 3) bar_sync(6, 64);
    uint32_t r[4][2][4];
#pragma unroll
    for (int h = 0; h < 4; h++) {
#pragma unroll
      for (int kv = 0; kv < 2; kv++) {
#pragma unroll
        for (int dh = 0; dh < 2; dh++) {
          const int j = 8 + kv * 8 + 2 * h + dh;
          const float2 c2 = cs[j];
          const float v0 = fmaf(acc[4 * j + 0], rstd0, nm0 * c2.x), v1 = fmaf(acc[4 * j + 1], rstd0, nm0 * c2.y);
          const float v2 = fmaf(acc[4 * j + 2], rstd1, nm1 * c2.x), v3 = fmaf(acc[4 * j + 3], rstd1, nm1 * c2.y);
          r[h][kv][2 * dh] = packbf(v0, v1);
          r[h][kv][2 * dh + 1] = packbf(v2, v3);
        }
      }
      if (sender) {
        st_tagged3(halo + (3 * h) * 32, r[h][0][0], r[h][0][1], r[h][0][2], tag);
        st_tagged3(halo + (3 * h + 1) * 32, r[h][0][3], r[h][1][0], r[h][1][1], tag);
        st_tagged3(halo + (3 * h + 2) * 32, r[h][1][2], r[h][1][3], 0u, tag);
      }
    }
    if (wg == 1 && w == 3) bar_arrive(6, 64);
    if (layer == 1 && threadIdx.x == 224) TS(47);
#pragma unroll
    for (int j = 0; j < 8; j++) cs[j] = lds64f(sb + SM_CS + 4 * (8 * j + 2 * t));
    mbar_wait(bar + 8 * B_QDONE, layer);
#pragma unroll
    for (int h = 0; h < 4; h++) {
#pragma unroll
      for (int kv = 0; kv < 2; kv++) {
        const int chunk = 4 * h + 2 * kv + (lane >> 4);
        stsm4(st_base + (((chunk & 8) | ((chunk ^ st_row) & 7)) << 4), r[h][kv][0], r[h][kv][1], r[h][kv][2], r[h][kv][3]);
      }
      kb[h][4] = r[h][0][0]; kb[h][5] = r[h][0][2]; kb[h][6] = r[h][0][1]; kb[h][7] = r[h][0][3];
      vb[h][4] = movm_t(r[h][1][0]); vb[h][5] = movm_t(r[h][1][1]); vb[h][6] = movm_t(r[h][1][2]); vb[h][7] = movm_t(r[h][1][3]);
    }
    if (layer == 1 && threadIdx.x == 0) TS(45);
#pragma unroll
    for (int h = 0; h < 4; h++) {
#pragma unroll
      for (int dh = 0; dh < 2; dh++) {
        const int j = 2 * h + dh;
        const float2 c2 = cs[j];
        qa[h][2 * dh] = packbf(fmaf(-mean0, c2.x, acc[4 * j + 0]), fmaf(-mean0, c2.y, acc[4 * j + 1]));
        qa[h][2 * dh + 1] = packbf(fmaf(-mean1, c2.x, acc[4 * j + 2]), fmaf(-mean1, c2.y, acc[4 * j + 3]));
      }
    }
  }
  bar_sync(1, 256);
  if (threadIdx.x == 0) TS(2 + layer * 20 + 2);
  {
    const uint32_t own_base = sb + SM_KVX + row0 * 256;
    const int mi = lane >> 3;
    const int r = 8 * (mi >> 1) + (lane & 7), r2 = 8 * (mi & 1) + (lane & 7);
    if (row0 != 0) {
#pragma unroll
      for (int h = 0; h < 4; h++) {
        const int ch = 4 * h + (mi & 1), ch2 = 4 * h + 2 + (mi >> 1);
        ldsm4(&kb[h][0], own_base - 16 * 256 + r * 256 + (((ch & 8) | ((ch ^ r) & 7)) << 4));
        ldsm4t(&vb[h][0], own_base - 16 * 256 + r2 * 256 + (((ch2 & 8) | ((ch2 ^ r2) & 7)) << 4));
      }
    } else if (rb > 0) {
      const uint4* src = &g_halo[((rb - 1) * 8 + hg) * 384 + lane];
      uint4 hv[12];
      int it = 0;
      bool ok;
      do {
        ok = true;
#pragma unroll
        for (int i = 0; i < 12; i++) hv[i] = ld_tagged(src + i * 32);
#pragma unroll
        for (int i = 0; i < 12; i++) ok = ok && hv[i].w == tag;
      } while (!__all_sync(~0u, ok) && ++it < (1 << 20));
      if (lane == 0) mbar_arrive(bar + 8 * B_HF);
#pragma unroll
      for (int h = 0; h < 4; h++) {
        kb[h][0] = hv[3 * h].x; kb[h][1] = hv[3 * h].z; kb[h][2] = hv[3 * h].y; kb[h][3] = hv[3 * h + 1].x;
        vb[h][0] = movm_t(hv[3 * h + 1].y); vb[h][1] = movm_t(hv[3 * h + 1].z);
        vb[h][2] = movm_t(hv[3 * h + 2].x); vb[h][3] = movm_t(hv[3 * h + 2].y);
      }
    } else {
#pragma unroll
      for (int h = 0; h < 4; h++)
#pragma unroll
        for (int k = 0; k < 4; k++) kb[h][k] = vb[h][k] = 0u;
    }
    if (threadIdx.x == 0) TS(2 + layer * 20 + 4);
  }

  const bool first = (rb == 0 && wg == 0 && w == 0);
  const int e = t - (g >> 1);
  const bool par = g & 1, epos = e >= 1;
  const uint32_t pmask = par ? 0xffff0000u : 0x0000ffffu;
  const uint32_t mB0 = epos ? pmask : 0u, mB1 = epos ? 0u : pmask;
  const float cl2 = 0.25f * 1.4426950408889634f;
  const float sc0 = rstd0 * cl2, sc1 = rstd1 * cl2;
  const float NEG = -INFINITY;
  float vA0[4], vB0[4], vA1[4], vB1[4];
#pragma unroll
  for (int h = 0; h < 4; h++) {
    float S[4][4];
#pragma unroll
    for (int j = 0; j < 4; j++) {
      S[j][0] = S[j][1] = S[j][2] = S[j][3] = 0.f;
      mma_bf16(S[j], qa[h], kb[h][2 * j], kb[h][2 * j + 1]);
    }
    vA0[h] = par ? S[1][1] : S[1][0];
    vB0[h] = epos ? (par ? S[0][1] : S[0][0]) : (par ? S[2][1] : S[2][0]);
    vA1[h] = par ? S[2][3] : S[2][2];
    vB1[h] = epos ? (par ? S[1][3] : S[1][2]) : (par ? S[3][3] : S[3][2]);
    if (first) { vA0[h] = NEG; if (epos) { vB0[h] = NEG; vB1[h] = NEG; } }
  }
  float m0[4], m1[4];
#pragma unroll
  for (int h = 0; h < 4; h++) { m0[h] = fmaxf(vA0[h], vB0[h]); m1[h] = fmaxf(vA1[h], vB1[h]); }
#pragma unroll
  for (int o = 1; o <= 2; o <<= 1) {
#pragma unroll
    for (int h = 0; h < 4; h++) {
      m0[h] = fmaxf(m0[h], __shfl_xor_sync(~0u, m0[h], o));
      m1[h] = fmaxf(m1[h], __shfl_xor_sync(~0u, m1[h], o));
    }
  }
  float O0[4][4], O1[4][4], Z[4][4];
#pragma unroll
  for (int h = 0; h < 4; h++) {
    const float mm0 = -m0[h] * sc0, mm1 = -m1[h] * sc1;
    const float pA0 = ex2(fmaf(vA0[h], sc0, mm0)), pB0 = ex2(fmaf(vB0[h], sc0, mm0));
    const float pA1 = ex2(fmaf(vA1[h], sc1, mm1)), pB1 = ex2(fmaf(vB1[h], sc1, mm1));
    const uint32_t hA0 = packbf(pA0, pA0), hB0 = packbf(pB0, pB0), hA1 = packbf(pA1, pA1), hB1 = packbf(pB1, pB1);
    const uint32_t P0[4] = {hB0 & mB0, 0u, hA0 & pmask, hB1 & mB0};
    const uint32_t P1[4] = {hB0 & mB1, hA1 & pmask, 0u, hB1 & mB1};
#pragma unroll
    for (int k = 0; k < 4; k++) O0[h][k] = O1[h][k] = Z[h][k] = 0.f;
    mma_bf16(O0[h], P0, vb[h][0], vb[h][1]); mma_bf16(O1[h], P0, vb[h][2], vb[h][3]); mma_bf16(Z[h], P0, 0x3f803f80u, 0x3f803f80u);
    mma_bf16(O0[h], P1, vb[h][4], vb[h][5]); mma_bf16(O1[h], P1, vb[h][6], vb[h][7]); mma_bf16(Z[h], P1, 0x3f803f80u, 0x3f803f80u);
  }
  const uint32_t ob = sb + SM_OST + wg * 8192;
  const int o_row = 16 * w + (lane & 7) + 8 * ((lane >> 3) & 1);
#pragma unroll
  for (int h = 0; h < 4; h++) {
    const float i0 = rcp_approx(Z[h][0]), i1 = rcp_approx(Z[h][2]);
    const int ch = 2 * h + (lane >> 4);
    stsm4(ob + o_row * 128 + ((ch ^ (o_row & 7)) << 4), packbf(O0[h][0] * i0, O0[h][1] * i0), packbf(O0[h][2] * i1, O0[h][3] * i1),
          packbf(O1[h][0] * i0, O1[h][1] * i0), packbf(O1[h][2] * i1, O1[h][3] * i1));
  }
  if (threadIdx.x == 0) TS(2 + layer * 20 + 5);
  fence_async_smem();
  bar_sync(2 + wg, 128);
  if (w == 0 && elect_one()) {
    tma_st(&p.mapO, hg * 64, rb * 128 + wg * 64, ob);
    bulk_commit();
    mbar_arrive(bar + 8 * B_AD);
    bulk_wait_all();
    red_relaxed(&g_cnt[(C_O + rb) * 32]);
    mbar_arrive(bar + 8 * B_OST);
    if (threadIdx.x == 0) TS(2 + layer * 20 + 6);
  }
}

__device__ __forceinline__ void proj_phase(const Params& p, uint32_t sb, int layer, int rb, int q, int wg, int w) {
  const int lane = opaque_tid() & 31;
  const bool TR = layer != 0;
  const int t = lane & 3;
  const uint32_t bar = sb + SM_BAR;
  const uint32_t rbx = sb + SM_R + wg * 8192;
  uint32_t res[16];
  mbar_wait(bar + 8 * B_RF, layer);
  if (threadIdx.x == 0) TS(2 + layer * 20 + 7);
  if (!TR) {
#pragma unroll
    for (int j = 0; j < 8; j += 2) {
      const int mi = lane >> 3;
      const int row = 16 * w + (lane & 7) + 8 * (mi & 1), ch = j + (mi >> 1);
      ldsm4(&res[2 * j], rbx + row * 128 + ((ch ^ (row & 7)) << 4));
    }
  } else {
#pragma unroll
    for (int j = 0; j < 8; j += 2) {
      const int mi = lane >> 3;
      const int line = 8 * (j + (mi >> 1)) + (lane & 7), pc = 2 * w + (mi & 1);
      ldsm4t(&res[2 * j], rbx + line * 128 + ((pc ^ (line & 7)) << 4));
    }
  }
  bar_sync(2 + wg, 128);
  float acc[32];
#pragma unroll
  for (int i = 0; i < 32; i++) acc[i] = 0.f;
#pragma unroll 1
  for (int c = 0; c < 8; c++) {
    if ((c & 1) == 0) mbar_wait(bar + 8 * (B_WOF + (c >> 1)), layer);
    mbar_wait(bar + 8 * (B_OF + c), layer);
    if (c == 0 && threadIdx.x == 0) TS(2 + layer * 20 + 8);
    const uint64_t da = mkdesc(sb + (c < 4 ? SM_X + 65536 + c * 16384 : SM_W + (c - 4) * 16384) + wg * 8192, 16, 1024, 1);
    const uint64_t db = mkdesc(sb + SM_X + c * 8192, 8192, 1024, 1);
    wg_fence();
#pragma unroll
    for (int ks = 0; ks < 4; ks++) wgmma_ss<64, 0, 1>(acc, da + ks * 2, db + ks * 128, 1);
    wg_commit();
  }
  wg_wait<0>();
  if (threadIdx.x == 0) TS(2 + layer * 20 + 9);
  if (lane == 0 && w == 0) mbar_arrive(bar + 8 * B_PDONE);
  float s0 = 0.f, q0 = 0.f, s1 = 0.f, q1 = 0.f;
  uint32_t o[16];
#pragma unroll
  for (int j = 0; j < 8; j++) {
    const uint32_t r0 = res[2 * j], r1 = res[2 * j + 1];
    o[2 * j] = packbf(acc[4 * j] + bf_lo(r0), acc[4 * j + 1] + bf_hi(r0));
    o[2 * j + 1] = packbf(acc[4 * j + 2] + bf_lo(r1), acc[4 * j + 3] + bf_hi(r1));
    const float a = bf_lo(o[2 * j]), b = bf_hi(o[2 * j]), c = bf_lo(o[2 * j + 1]), d = bf_hi(o[2 * j + 1]);
    s0 += a + b; q0 = fmaf(a, a, q0); q0 = fmaf(b, b, q0);
    s1 += c + d; q1 = fmaf(c, c, q1); q1 = fmaf(d, d, q1);
  }
#pragma unroll
  for (int j = 0; j < 8; j += 2) {
    const int mi = lane >> 3;
    const int line = 8 * (j + (mi >> 1)) + (lane & 7), pc = 2 * w + (mi & 1);
    stsm4t(rbx + line * 128 + ((pc ^ (line & 7)) << 4), o[2 * j], o[2 * j + 1], o[2 * j + 2], o[2 * j + 3]);
  }
#pragma unroll
  for (int o2 = 1; o2 <= 2; o2 <<= 1) {
    s0 += __shfl_xor_sync(~0u, s0, o2); q0 += __shfl_xor_sync(~0u, q0, o2);
    s1 += __shfl_xor_sync(~0u, s1, o2); q1 += __shfl_xor_sync(~0u, q1, o2);
  }
  const uint32_t stg = sb + SM_HALO + wg * 512;
  {
    const int row = 16 * w + (lane >> 2) + 8 * (t >> 1);
    const float v = (t == 0) ? s0 : (t == 1) ? q0 : (t == 2) ? s1 : q1;
    sts32f(stg + 4 * (((((row & 7) >> 1) * 8 + (row >> 3)) << 2) + (row & 1) * 2 + (t & 1)), v);
  }
  fence_async_smem();
  bar_sync(2 + wg, 128);
  if (w == 0 && elect_one()) {
    mbar_wait(bar + 8 * B_ZF, 0);
    tma_st(&p.mapXT, rb * 128 + wg * 64, (2 * layer) * DM + q * 64, rbx);
    bulk_red_add_f32(g_stats + layer * LSEQ * 2 + (rb * 2 + wg) * 128, stg, 512);
    bulk_commit();
    bulk_wait_all();
    red_relaxed(&g_cnt[(layer ? C_G2 : C_G0) * 32]);
    if (threadIdx.x == 0) TS(2 + layer * 20 + 10);
  }
}

__device__ __forceinline__ void conv_load(uint32_t* A, uint32_t pe) {
#pragma unroll
  for (int m = 0; m < 17; m++) {
    A[4 * m + 2] = lds32(pe + 4 * (64 * m - 8));
    A[4 * m + 0] = lds32(pe + 4 * (64 * m));
    A[4 * m + 1] = lds32(pe + 4 * (64 * m + 8));
  }
#pragma unroll
  for (int m = 0; m < 17; m++) asm volatile("mov.b32 %0, %1;" : "=r"(A[4 * m + 3]) : "r"(A[4 * m + 0]));
}
template <int M> __device__ __forceinline__ void conv_mma(float* acc, const uint32_t* A, uint64_t d) {
  wgmma_rs<128 - 8 * (M / 2), 0>(acc, A + 4 * M, d + (uint64_t)(4 * M), M != 0);
}
template <int M0, int M1> __device__ __forceinline__ void conv_mmas(float* acc, const uint32_t* A, uint64_t d) {
  if constexpr (M0 < M1) { conv_mma<M0>(acc, A, d); conv_mmas<M0 + 1, M1>(acc, A, d); }
}
__device__ __forceinline__ void conv_sums(uint32_t sb, int lc, int c, uint4 own) {
  const int m = c == 127 ? -1 : c;
  if (c == 127) own = make_uint4(0, 0, 0, 0);
  const uint32_t up = m >= 1 ? ((m - 1) & 1) * CV_UH + (127 - ((m - 1) >> 1)) * 16 + 8 : 128 * 16;
  const uint32_t un = ((m + 1) & 1) * CV_UH + (127 - ((m + 1) >> 1)) * 16;
  const bool odd = c & 1;
  const float2 v0 = lds64f(sb + cv_u(lc) + (odd ? un : up)), v1 = lds64f(sb + cv_u(lc) + (odd ? up : un));
  const uint32_t x[8] = {__float_as_uint(odd ? v1.x : v0.x), __float_as_uint(odd ? v1.y : v0.y), own.x, own.y, own.z, own.w,
                         __float_as_uint(odd ? v0.x : v1.x), __float_as_uint(odd ? v0.y : v1.y)};
  float pv[16];
#pragma unroll
  for (int k = 0; k < 8; k++) { pv[2 * k] = bf_lo(x[k]); pv[2 * k + 1] = bf_hi(x[k]); }
  float sf[8], pf[8], s9[8], s7[8];
  sf[7] = pv[7]; pf[0] = pv[8];
#pragma unroll
  for (int i = 6; i >= 0; i--) sf[i] = sf[i + 1] + pv[i];
#pragma unroll
  for (int i = 1; i < 8; i++) pf[i] = pf[i - 1] + pv[8 + i];
#pragma unroll
  for (int i = 0; i < 8; i++) {
    s9[i] = sf[i] + pf[i];
    s7[i] = i == 0 ? sf[1] : i == 7 ? pf[6] : sf[i + 1] + pf[i - 1];
  }
  const int ce = (m + 2) & 127, co = m + 1;
  uint4 e4 = make_uint4(packbf(s9[0], s9[1]), packbf(s9[2], s9[3]), packbf(s9[4], s9[5]), packbf(s9[6], s9[7]));
  if (ce == 0) e4 = make_uint4(0, 0, 0, 0);
  sts128(sb + cv_s(lc) + ((ce >> 3) & 1) * 1024 + (ce >> 4) * 128 + (((ce ^ (ce >> 4)) & 7) << 4), e4);
  sts128(sb + cv_s(lc) + 2048 + ((co >> 3) & 1) * 1024 + (co >> 4) * 128 + (((co ^ (co >> 4)) & 7) << 4),
         make_uint4(packbf(s7[0], s7[1]), packbf(s7[2], s7[3]), packbf(s7[4], s7[5]), packbf(s7[6], s7[7])));
}

__device__ __forceinline__ void conv_epi(uint32_t sb, int layer, int cta, int ch, int c0) {
  uint4 v[2][4], xr[2];
#pragma unroll
  for (int u = 0; u < 2; u++) xr[u] = ldcg128(g_xT + (size_t)(2 * layer * DM + cv_chan(cta, ch)) * LSEQ + (c0 + 128 * u) * 8);
  mbar_wait(sb + SM_BAR + 8 * (B_P + ch), layer);
#pragma unroll
  for (int u = 0; u < 2; u++) {
    const int c = c0 + 128 * u;
    const uint32_t pb = sb + cv_pb(ch) + (c ^ ((c >> 3) & 1)) * 16;
#pragma unroll
    for (int k = 0; k < 4; k++) v[u][k] = lds128(pb + k * CV_PBW);
  }
#pragma unroll
  for (int u = 0; u < 2; u++) {
    uint4 o;
    o.x = hadd2(xr[u].x, hadd2(hadd2(v[u][0].x, v[u][1].x), hadd2(v[u][2].x, v[u][3].x)));
    o.y = hadd2(xr[u].y, hadd2(hadd2(v[u][0].y, v[u][1].y), hadd2(v[u][2].y, v[u][3].y)));
    o.z = hadd2(xr[u].z, hadd2(hadd2(v[u][0].z, v[u][1].z), hadd2(v[u][2].z, v[u][3].z)));
    o.w = hadd2(xr[u].w, hadd2(hadd2(v[u][0].w, v[u][1].w), hadd2(v[u][2].w, v[u][3].w)));
    sts128(sb + cv_s(ch) + (c0 + 128 * u) * 16, o);
  }
}
__device__ __forceinline__ void warp_release(uint32_t b) {
  fence_async_smem();
  __syncwarp();
  if (elect_one()) mbar_arrive(b);
}

__device__ __forceinline__ void conv_prep(uint32_t sb, int layer, int cta, int c, uint4 (&un)[4]) {
  const uint32_t bar = sb + SM_BAR;
  const bf16* xin = g_xT + (size_t)(2 * layer) * DM * LSEQ;
  uint4 xr[4], st[4];
  mbar_wait(bar + 8 * B_GB, layer);
  if (threadIdx.x == 0) TS(2 + layer * 20 + 11);
#pragma unroll
  for (int i = 0; i < 4; i++) st[i] = ldcg128(g_stats + layer * LSEQ * 2 + ((c >> 3) * 4 + i) * 32 + (c & 7) * 4);
#pragma unroll
  for (int i = 0; i < 4; i++) xr[i] = ldcg128(xin + (size_t)cv_chan(cta, i) * LSEQ + c * 8);
  float nm[8], rstd[8];
#pragma unroll
  for (int i = 0; i < 4; i++) {
    const float m0 = __uint_as_float(st[i].x) * (1.f / DM), m1 = __uint_as_float(st[i].z) * (1.f / DM);
    rstd[2 * i] = rsqrt_approx(fmaxf(fmaf(__uint_as_float(st[i].y), 1.f / DM, -m0 * m0), 0.f) + 1e-5f);
    rstd[2 * i + 1] = rsqrt_approx(fmaxf(fmaf(__uint_as_float(st[i].w), 1.f / DM, -m1 * m1), 0.f) + 1e-5f);
    nm[2 * i] = -m0 * rstd[2 * i]; nm[2 * i + 1] = -m1 * rstd[2 * i + 1];
  }
  if (threadIdx.x == 0) TS(2 + layer * 20 + 12);
  const int a = c >> 1, h = c & 1;
#pragma unroll
  for (int i = 0; i < 4; i++) {
    const uint32_t x[4] = {xr[i].x, xr[i].y, xr[i].z, xr[i].w};
    uint32_t u[4];
#pragma unroll
    for (int k = 0; k < 4; k++)
      u[k] = packbf(fmaf(bf_lo(x[k]), rstd[2 * k], nm[2 * k]), fmaf(bf_hi(x[k]), rstd[2 * k + 1], nm[2 * k + 1]));
    un[i] = make_uint4(u[0], u[1], u[2], u[3]);
    sts128(sb + cv_u(i) + h * CV_UH + (127 - a) * 16, un[i]);
    warp_release(bar + 8 * (B_U + i));
  }
}
__device__ __forceinline__ void conv_zero(uint32_t sb, int ht) {
  if (ht < 96) {
    const int ch = ht / 24, h2 = (ht / 12) & 1, qq = ht % 12;
    sts128(sb + cv_u(ch) + h2 * CV_UH + (128 + qq) * 16, make_uint4(0, 0, 0, 0));
  }
  if (ht >= 80) {
    const int i = ht - 80, ch = i / 12, q2 = i % 12;
    const int w2 = q2 < 2 ? 1 : q2 < 6 ? 2 : 3, cc = q2 < 2 ? q2 : q2 < 6 ? q2 - 2 : q2 - 6;
    sts128(sb + cv_pb(ch) + w2 * CV_PBW + cc * 16, make_uint4(0, 0, 0, 0));
  }
}

#define HANDOVER 1
#define A_FIRST 0
__device__ __forceinline__ void conv_phase(const Params& p, uint32_t sb, int layer, int cta) {
  const int tid = opaque_tid();
  const int wg = __shfl_sync(~0u, tid >> 7, 0), w = __shfl_sync(~0u, (tid >> 5) & 3, 0);
  const uint32_t bar = sb + SM_BAR;
  uint32_t A[68];
  mbar_wait(bar + 8 * B_PE, layer);
  conv_load(A, sb + cv_pe(1 - wg) + 4 * (16 + 16 * w + ((tid & 31) >> 2) - 2 * (tid & 3)));
  if (wg == 0) {
    uint4 un[4];
    conv_prep(sb, layer, cta, opaque_tid() + 128, un);
  }
#pragma unroll 1
  for (int r = 0; r < 2; r++) {
    const int ch = 2 * r + 1 - wg;
    float acc[64];
    const uint64_t d = mkdesc(sb + cv_u(ch), CV_UH, 128, 0);
    const bool leader = (opaque_tid() & 127) == 0;
    FTS(39);
    mbar_wait(bar + 8 * (B_U + ch), layer);
    if (ch > 0) mbar_wait(bar + 8 * (B_T + ch - 1), layer);
    FTS(41);
    if (ch == 0 && threadIdx.x == 128) TS(2 + layer * 20 + 13);
    wg_fence();
    conv_mma<0>(acc, A, d);
    conv_mmas<2, 17>(acc, A, d);
    wg_commit();
    FTS(51);
    mbar_wait(bar + 8 * (B_S + ch), layer);
    if (HANDOVER == 0) mbar_arrive_if(bar + 8 * (B_T + ch), leader);
    wg_fence();
    conv_mma<1>(acc, A, d);
    if (HANDOVER == 1) mbar_arrive_if(bar + 8 * (B_T + ch), leader);
    wgmma_ss<64, 1, 1>(acc, mkdesc(sb + cv_s(ch), 1024, 1024, 1), mkdesc(sb + cv_ft(ch), 256, 16, 0), 1);
    if (HANDOVER == 2) mbar_arrive_if(bar + 8 * (B_T + ch), leader);
    wgmma_ss<64, 1, 1>(acc, mkdesc(sb + cv_s(ch) + 2048, 1024, 1024, 1), mkdesc(sb + cv_ft(ch) + 512, 256, 16, 0), 1);
    wg_commit();
    if (HANDOVER == 3) mbar_arrive_if(bar + 8 * (B_T + ch), leader);
    FTS(61);
    wg_wait<0>();
    const int l2 = opaque_tid() & 31;
    if (A_FIRST && r == 0) conv_load(A, sb + cv_pe(3 - wg) + 4 * (16 + 16 * w + (l2 >> 2) - 2 * (l2 & 3)));
    FTS(20);
    const uint32_t pb = sb + cv_pb(ch) + w * CV_PBW;
#pragma unroll
    for (int j = 0; j < 16; j += 2) {
      const int mt = l2 >> 3;
      const int a = 127 - (8 * (j + (mt >> 1)) + (l2 & 7));
      int c = 2 * (a + w) + (mt & 1);
      c ^= (c >> 3) & 1;
      stsm4t(pb + c * 16, packbf(acc[4 * j], acc[4 * j + 1]), packbf(acc[4 * j + 2], acc[4 * j + 3]),
             packbf(acc[4 * j + 4], acc[4 * j + 5]), packbf(acc[4 * j + 6], acc[4 * j + 7]));
    }
    __syncwarp();
    if (elect_one()) mbar_arrive(bar + 8 * (B_P + ch));
    if (threadIdx.x == 0) TS(2 + layer * 20 + 14 + r);
    FTS(57);
    if (!A_FIRST && r == 0) conv_load(A, sb + cv_pe(3 - wg) + 4 * (16 + 16 * w + (l2 >> 2) - 2 * (l2 & 3)));
  }
  if (wg == 1 && layer == 0) mbar_wait(bar + 8 * (B_T + 3), layer);
}

__device__ __forceinline__ void final_phase(const Params& p, uint32_t sb, int cta, int wg, int w) {
  if (wg == 1 && w == 3) return;
  const int lane = opaque_tid() & 31, g = lane >> 2, t = lane & 3;
  const int lc = wg ? w : 3;
  const int pos0 = (cta & 31) * 64, ch0 = 128 * lc + (cta >> 5) * 32;
  const bf16* src = g_xT + (size_t)(3 * DM + ch0 + 8 * (g >> 1) + (g & 1)) * LSEQ + pos0;
  bf16* dst = p.out + (size_t)pos0 * DM + ch0 + 8 * t;
  spin_until(&g_cnt[(C_F + (cta >> 5)) * 32 + lc], (lds32(sb + SM_EP) + 1) * 32);
  if (wg == 0) {
    if (threadIdx.x == 0) TS(42);
    uint2 v[4];
#pragma unroll
    for (int q = 0; q < 4; q++)
      asm volatile("ld.global.cg.v2.b32 {%0,%1}, [%2];" : "=r"(v[q].x), "=r"(v[q].y) : "l"(src + 2 * q * LSEQ + 16 * w + 4 * t) : "memory");
    dst += (16 * w + 4 * (g >> 1) + (g & 1)) * DM;
    *(uint4*)dst = make_uint4(movm_t(v[0].x), movm_t(v[1].x), movm_t(v[2].x), movm_t(v[3].x));
    *(uint4*)(dst + 2 * DM) = make_uint4(movm_t(v[0].y), movm_t(v[1].y), movm_t(v[2].y), movm_t(v[3].y));
  } else {
    uint4 v[2][4];
#pragma unroll
    for (int h = 0; h < 2; h++)
#pragma unroll
      for (int q = 0; q < 4; q++) v[h][q] = ldcg128(src + 2 * q * LSEQ + 32 * h + 8 * t);
    dst += (8 * (g >> 1) + (g & 1)) * DM;
#pragma unroll
    for (int h = 0; h < 2; h++) {
      *(uint4*)(dst + (32 * h + 0) * DM) = make_uint4(movm_t(v[h][0].x), movm_t(v[h][1].x), movm_t(v[h][2].x), movm_t(v[h][3].x));
      *(uint4*)(dst + (32 * h + 2) * DM) = make_uint4(movm_t(v[h][0].y), movm_t(v[h][1].y), movm_t(v[h][2].y), movm_t(v[h][3].y));
      *(uint4*)(dst + (32 * h + 4) * DM) = make_uint4(movm_t(v[h][0].z), movm_t(v[h][1].z), movm_t(v[h][2].z), movm_t(v[h][3].z));
      *(uint4*)(dst + (32 * h + 6) * DM) = make_uint4(movm_t(v[h][0].w), movm_t(v[h][1].w), movm_t(v[h][2].w), movm_t(v[h][3].w));
    }
  }
  if (threadIdx.x == 0) TS(43);
  if (threadIdx.x == 192) TS(63);
  if (threadIdx.x == 0) LTS(1);
}

struct cplx { float r, i; };
__device__ __forceinline__ cplx cmul(cplx a, cplx b) { return {fmaf(a.r, b.r, -a.i * b.i), fmaf(a.r, b.i, a.i * b.r)}; }
__device__ __forceinline__ cplx csqr(cplx a) { return {fmaf(a.r, a.r, -a.i * a.i), (a.r + a.r) * a.i}; }
__device__ __forceinline__ cplx cexp_l(float ar2, float ai, float l) {
  const float m = ex2(ar2 * l);
  const float x = ai * l;
  return {m * __cosf(x), m * __sinf(x)};
}

template <int N> __device__ __forceinline__ void halve(float* s, int lane) {
  const bool up = (lane & (2 * N)) != 0;
#pragma unroll
  for (int i = 0; i < N; i++) {
    const float keep = up ? s[i + N] : s[i], send = up ? s[i] : s[i + N];
    s[i] = keep + __shfl_xor_sync(~0u, send, 2 * N);
  }
}
__device__ __forceinline__ void colsum_part(const Params& p, uint32_t sb, int cta, int ht, uint32_t tag) {
  if (cta >= 96) return;
  uint4 v[4][2];
#pragma unroll
  for (int r = 0; r < 4; r++)
#pragma unroll
    for (int i = 0; i < 2; i++) v[r][i] = *(const uint4*)(p.wqkv + (size_t)(ht + 128 * r) * 1536 + cta * 16 + i * 8);
  float s[16];
#pragma unroll
  for (int i = 0; i < 16; i++) s[i] = 0.f;
#pragma unroll
  for (int r = 0; r < 4; r++)
#pragma unroll
    for (int i = 0; i < 2; i++) {
      const uint32_t x[4] = {v[r][i].x, v[r][i].y, v[r][i].z, v[r][i].w};
#pragma unroll
      for (int k = 0; k < 4; k++) { s[8 * i + 2 * k] += bf_lo(x[k]); s[8 * i + 2 * k + 1] += bf_hi(x[k]); }
    }
  const int lane = ht & 31, w = ht >> 5;
  halve<8>(s, lane); halve<4>(s, lane); halve<2>(s, lane); halve<1>(s, lane);
  s[0] += __shfl_xor_sync(~0u, s[0], 1);
  if ((lane & 1) == 0) sts32f(sb + SM_RED + (w * 16 + (lane >> 1)) * 4, s[0]);
  bar_sync(4, 128);
  if (ht < 16) {
    float tot = 0.f;
#pragma unroll
    for (int k = 0; k < 4; k++) tot += __uint_as_float(lds32(sb + SM_RED + (k * 16 + ht) * 4));
    asm volatile("st.relaxed.gpu.global.v2.u32 [%0], {%1,%2};" ::"l"(&g_colsum[cta * 16 + ht]), "r"(__float_as_uint(tot)), "r"(tag) : "memory");
  }
}

__device__ __forceinline__ uint32_t packh(float lo, float hi) { uint32_t r; asm("cvt.rn.f16x2.f32 %0, %1, %2;" : "=r"(r) : "f"(hi), "f"(lo)); return r; }
__device__ __forceinline__ void mma_f16(float* d, uint32_t a0, uint32_t a1, uint32_t a2, uint32_t a3, uint32_t b0, uint32_t b1) {
  asm volatile("mma.sync.aligned.m16n8k16.row.col.f32.f16.f16.f32 {%0,%1,%2,%3}, {%4,%5,%6,%7}, {%8,%9}, {%0,%1,%2,%3};"
      : "+f"(d[0]), "+f"(d[1]), "+f"(d[2]), "+f"(d[3]) : "r"(a0), "r"(a1), "r"(a2), "r"(a3), "r"(b0), "r"(b1));
}
struct HSeed { uint32_t r, i; };
__device__ __forceinline__ HSeed hseed(cplx s) { return {packh(s.r, s.r), packh(s.i, s.i)}; }
__device__ __forceinline__ void hcmul(uint32_t& o_r, uint32_t& o_i, uint32_t br, uint32_t bi, HSeed s) {
  asm("{\n.reg .b32 t, u;\nmul.rn.f16x2 t, %3, %5;\nneg.f16x2 t, t;\nmul.rn.f16x2 u, %3, %4;\nfma.rn.f16x2 %0, %2, %4, t;\nfma.rn.f16x2 %1, %2, %5, u;\n}"
      : "=&r"(o_r), "=&r"(o_i) : "r"(br), "r"(bi), "r"(s.r), "r"(s.i));
}
struct HTile { uint32_t r[4], i[4]; };
__device__ __forceinline__ void tile_set(HTile& t, int k, cplx a, cplx b) { t.r[k] = packh(a.r, b.r); t.i[k] = packh(a.i, b.i); }
__device__ __forceinline__ void tile_upper(HTile& t, HSeed s) { hcmul(t.r[2], t.i[2], t.r[0], t.i[0], s); hcmul(t.r[3], t.i[3], t.r[1], t.i[1], s); }
__device__ __forceinline__ HTile tile_shift(const HTile& t, HSeed s) {
  HTile o;
#pragma unroll
  for (int k = 0; k < 4; k++) hcmul(o.r[k], o.i[k], t.r[k], t.i[k], s);
  return o;
}
__device__ __forceinline__ void tile_put(const HTile& t, uint32_t a) {
  sts128(a, make_uint4(t.r[0], t.r[1], t.r[2], t.r[3]));
  sts128(a + 512, make_uint4(t.i[0], t.i[1], t.i[2], t.i[3]));
}
__device__ __forceinline__ HTile tile_get(uint32_t a) { HTile o; ldsm4t(o.r, a); ldsm4t(o.i, a + 512); return o; }
__device__ __forceinline__ void tile_mma(float* T, const HTile& a0, const HTile& a1, const HTile& b) {
  mma_f16(T, a0.r[0], a0.r[1], a0.r[2], a0.r[3], b.r[0], b.r[1]);
  mma_f16(T, a0.i[0], a0.i[1], a0.i[2], a0.i[3], b.i[0], b.i[1]);
  mma_f16(T, a1.r[0], a1.r[1], a1.r[2], a1.r[3], b.r[2], b.r[3]);
  mma_f16(T, a1.i[0], a1.i[1], a1.i[2], a1.i[3], b.i[2], b.i[3]);
}
__device__ __forceinline__ void tile_mma2(float* T, float* U, const HTile& a0, const HTile& a1, const HTile& b, const HTile& c) {
  mma_f16(T, a0.r[0], a0.r[1], a0.r[2], a0.r[3], b.r[0], b.r[1]);
  mma_f16(U, a0.r[0], a0.r[1], a0.r[2], a0.r[3], c.r[0], c.r[1]);
  mma_f16(T, a0.i[0], a0.i[1], a0.i[2], a0.i[3], b.i[0], b.i[1]);
  mma_f16(U, a0.i[0], a0.i[1], a0.i[2], a0.i[3], c.i[0], c.i[1]);
  mma_f16(T, a1.r[0], a1.r[1], a1.r[2], a1.r[3], b.r[2], b.r[3]);
  mma_f16(U, a1.r[0], a1.r[1], a1.r[2], a1.r[3], c.r[2], c.r[3]);
  mma_f16(T, a1.i[0], a1.i[1], a1.i[2], a1.i[3], b.i[2], b.i[3]);
  mma_f16(U, a1.i[0], a1.i[1], a1.i[2], a1.i[3], c.i[2], c.i[3]);
}
__device__ __forceinline__ void kgen_unit(uint32_t tab, uint32_t taba, float ar2, float ai, cplx c, float (&T)[5][4]) {
  const cplx z1 = cexp_l(ar2, ai, 1.f), z16 = cexp_l(ar2, ai, 16.f), z256 = cexp_l(ar2, ai, 256.f);
  HTile a0, a1, b0, b1;
  {
    const cplx y1 = {z16.r, -z16.i}, y2 = csqr(y1), y3 = cmul(y2, y1), y4 = csqr(y2), y5 = cmul(y4, y1), y6 = csqr(y3), y7 = cmul(y4, y3);
    HTile t;
    tile_set(t, 0, {1.f, 0.f}, y1); tile_set(t, 1, y2, y3); tile_set(t, 2, y4, y5); tile_set(t, 3, y6, y7);
    const HTile u = tile_shift(t, hseed(csqr(y4)));
    __syncwarp();
    tile_put(t, tab); tile_put(u, tab + 1024);
    __syncwarp();
    a0 = tile_get(taba); a1 = tile_get(taba + 256);
  }
  const cplx z2 = csqr(z1), z4 = csqr(z2), z8 = csqr(z4);
  const HSeed h8 = hseed(z8);
  const cplx d = cmul(c, z256), e = cmul(d, z256);
  {
    const cplx z512 = csqr(z256), f = cmul(e, z512), f8 = cmul(f, z8), f16 = cmul(f, z16), e4 = cmul(e, z4);
    HTile t, u;
    tile_set(t, 0, e4, cmul(e, z8)); tile_set(t, 1, cmul(e4, z8), cmul(e, z16));
    tile_upper(t, hseed(z256));
    tile_set(u, 0, f8, f16); tile_set(u, 1, cmul(f8, z256), cmul(f16, z256));
    tile_upper(u, hseed(z512));
    __syncwarp();
    tile_put(t, tab); tile_put(u, tab + 1024);
    __syncwarp();
    b0 = tile_get(tab); b1 = tile_get(tab + 1024);
  }
  {
    const cplx d2 = cmul(d, z2), d4 = cmul(d, z4);
    HTile t;
    tile_set(t, 0, d2, d4); tile_set(t, 1, cmul(d2, z4), cmul(d, z8));
    tile_upper(t, h8);
    __syncwarp();
    tile_put(t, tab);
    __syncwarp();
    tile_mma2(T[3], T[4], a0, a1, b0, b1);
    b0 = tile_get(tab);
  }
  {
    const cplx c1 = cmul(c, z1), c2 = cmul(c, z2), c3 = cmul(c1, z2), c4 = cmul(c, z4);
    HTile t;
    tile_set(t, 0, c1, c2); tile_set(t, 1, c3, c4); tile_set(t, 2, cmul(c1, z4), cmul(c2, z4)); tile_set(t, 3, cmul(c3, z4), cmul(c4, z4));
    const HTile u = tile_shift(t, h8);
    __syncwarp();
    tile_put(t, tab); tile_put(u, tab + 1024);
    __syncwarp();
    tile_mma(T[2], a0, a1, b0);
    b0 = tile_get(tab); b1 = tile_get(tab + 1024);
    tile_mma2(T[0], T[1], a0, a1, b0, b1);
  }
}
struct ModeIn { uint2 ar, ai, br, bi, cr, ci; };
__device__ __forceinline__ ModeIn load_modes(const Params& p, int idx) {
  return {*(const uint2*)(p.a_re + idx), *(const uint2*)(p.a_im + idx), *(const uint2*)(p.b_re + idx),
          *(const uint2*)(p.b_im + idx), *(const uint2*)(p.c_re + idx), *(const uint2*)(p.c_im + idx)};
}
__device__ __forceinline__ float bf_el(uint2 v, int k) { const uint32_t x = (k & 2) ? v.y : v.x; return (k & 1) ? bf_hi(x) : bf_lo(x); }
struct KGen { float4 cur; float T[5][4]; };
__device__ __forceinline__ uint32_t kgen_slot(uint32_t sb, int ht, int u) {
  return sb + (u < 3 ? SM_KC + (ht >> 5) * (KC_STRIDE * 2) + (u - 1) * 512 + (ht & 31) * 16 + 16 : SM_HALO + 1024 + ht * 16);
}
__device__ __forceinline__ void kgen_setup(KGen& s, uint32_t sb, int cta, int ht, const ModeIn& in, bf16 logdt, bf16 dskip) {
  const float dt = __bfloat162float(__float2bfloat16_rn(expf(__bfloat162float(logdt))));
  float mx = 0.f, k0 = 0.f, ar2[4];
  cplx c[4];
#pragma unroll
  for (int k = 0; k < 4; k++) {
    ar2[k] = (dt * bf_el(in.ar, k)) * 1.4426950408889634f;
    c[k] = cmul({bf_el(in.cr, k), bf_el(in.ci, k)}, {dt * bf_el(in.br, k), dt * bf_el(in.bi, k)});
    k0 += c[k].r;
    mx = fmaxf(mx, fmaxf(fabsf(c[k].r), fabsf(c[k].i)) * ex2(fmaxf(ar2[k] * 2048.f, 0.f)));
  }
  const int ex = min(max(267 - (int)(__reduce_max_sync(~0u, __float_as_uint(mx)) >> 23), 1), 253);
  const float sc = __uint_as_float(ex << 23);
#pragma unroll
  for (int o = 16; o > 0; o >>= 1) k0 += __shfl_xor_sync(~0u, k0, o);
  if ((ht & 31) == 0) {
    const uint32_t kc = sb + SM_KC + (ht >> 5) * (KC_STRIDE * 2);
    sts16(kc, __bfloat16_as_ushort(__float2bfloat16_rn(k0 + __bfloat162float(dskip))));
    sts16(kc + 641 * 2, 0);
    sts32f(kc + 644 * 2, __uint_as_float((254 - ex) << 23));
  }
  s.cur = make_float4(ar2[0], dt * bf_el(in.ai, 0), c[0].r * sc, c[0].i * sc);
#pragma unroll
  for (int k = 1; k < 4; k++) sts128f(kgen_slot(sb, ht, k), ar2[k], dt * bf_el(in.ai, k), c[k].r * sc, c[k].i * sc);
#pragma unroll
  for (int i = 0; i < 5; i++) s.T[i][0] = s.T[i][1] = s.T[i][2] = s.T[i][3] = 0.f;
}
__device__ __forceinline__ void kgen_finish(KGen& s, uint32_t sb, int cta, int ht) {
  const int w = ht >> 5, lane = ht & 31, g = lane >> 2, t = lane & 3;
  const uint32_t kc = sb + SM_KC + w * KC_STRIDE * 2;
  __syncwarp();
  const float inv = __uint_as_float(lds32(kc + 644 * 2));
  auto put = [&](int idx, float v) {
    sts16(kc + idx * 2, __bfloat16_as_ushort(__float2bfloat16_rn(v)));
  };
#pragma unroll
  for (int hi = 0; hi < 2; hi++)
#pragma unroll
    for (int lo = 0; lo < 2; lo++) {
      const int i = g + 8 * hi, j = 2 * t + lo, e = 2 * hi + lo;
      put(16 * i + 1 + j, s.T[0][e] * inv);
      put(16 * i + 9 + j, s.T[1][e] * inv);
      put(257 + 8 * i + j, s.T[2][e] * inv);
      put(385 + 4 * i + (j & 3) + 64 * (j >> 2), s.T[3][e] * inv);
      put(513 + 2 * i + lo + 32 * t, s.T[4][e] * inv);
    }
}

__device__ __forceinline__ void expand_taps(uint32_t sb, int ht) {
  const int ch = ht >> 5, lane = ht & 31;
  const uint32_t kc = sb + SM_KC + ch * KC_STRIDE * 2;
  const uint32_t dst0 = sb + cv_pe(ch);
  auto put = [&](int G, uint32_t v0, uint32_t v1, uint32_t v2, uint32_t v3, uint32_t v4, uint32_t v5, uint32_t v6, uint32_t v7, uint32_t v8) {
    const uint32_t dst = dst0 + G * 32;
    sts128(dst, make_uint4(v1 | (v0 << 16), v2 | (v1 << 16), v3 | (v2 << 16), v4 | (v3 << 16)));
    sts128(dst + 16, make_uint4(v5 | (v4 << 16), v6 | (v5 << 16), v7 | (v6 << 16), v8 | (v7 << 16)));
  };
  {
    const uint4 q = lds128(kc + lane * 16);
    const uint32_t pv = lane ? lds16(kc + lane * 16 - 2) : 0u;
    const uint32_t dst = dst0 + (lane + 2) * 32;
    sts128(dst, make_uint4(__byte_perm(q.x, pv, 0x5410), __byte_perm(q.x, q.x, 0x1032), __byte_perm(q.y, q.x, 0x7610), __byte_perm(q.y, q.y, 0x1032)));
    sts128(dst + 16, make_uint4(__byte_perm(q.z, q.y, 0x7610), __byte_perm(q.z, q.z, 0x1032), __byte_perm(q.w, q.z, 0x7610), __byte_perm(q.w, q.w, 0x1032)));
    if (lane < 4) sts128(dst0 + lane * 16, make_uint4(0, 0, 0, 0));
  }
  uint32_t a[5], b[2][3], fv[4];
  {
    const uint32_t s1 = kc + 2 * (256 + 4 * lane);
#pragma unroll
    for (int k = 0; k < 5; k++) a[k] = lds16(s1 + 2 * k);
#pragma unroll
    for (int u = 0; u < 2; u++) {
      const uint32_t s2 = kc + 2 * (384 + 2 * (lane + 32 * u));
#pragma unroll
      for (int k = 0; k < 3; k++) b[u][k] = lds16(s2 + 2 * k);
    }
#pragma unroll
    for (int k = 0; k < 4; k++) fv[k] = lds16(kc + 2 * (640 - 4 * lane - k));
  }
  const uint32_t k255 = lds16(kc + 2 * 255), k1024 = lds16(kc + 2 * 512);
  put(34 + lane, lane == 0 ? k255 : a[0], a[0], a[0], a[1], a[2], a[2], a[2], a[3], a[4]);
#pragma unroll
  for (int u = 0; u < 2; u++) put(66 + lane + 32 * u, b[u][0], b[u][0], b[u][0], b[u][0], b[u][1], b[u][1], b[u][1], b[u][2], b[u][2]);
  if (lane < 10) {
    const uint32_t v = lane == 0 ? k1024 : 0u;
    put(130 + lane, v, v, v, v, v, v, 0u, 0u, 0u);
  }
  const uint32_t ft = sb + cv_ft(ch) + 4 * lane;
#pragma unroll
  for (int ty = 0; ty < 2; ty++) {
    const uint32_t v = fv[ty] | (fv[ty + 2] << 16);
    sts32f(ft + ty * 512, __uint_as_float(v));
    sts32f(ft + ty * 512 + 128, 0.f);
    sts32f(ft + ty * 512 + 256 + (lane < 2 ? 120 : -8), __uint_as_float(lane < 2 ? 0u : v));
    sts32f(ft + ty * 512 + 384, 0.f);
  }
}

template <bool SMID> __device__ __forceinline__ int role_id() {
  uint32_t v;
  if (!SMID) { asm volatile("mov.u32 %0, %%ctaid.x;" : "=r"(v)); return v; }
  asm volatile("mov.u32 %0, %%smid;" : "=r"(v));
  const int tp = v >> 1, q = ((tp - 32) * 37) >> 8;
  const int r = tp < 32 ? (tp & 7) * 8 + (tp >> 3) : tp < 60 ? (tp - 31 - 7 * q) * 8 + 4 + q : tp < 62 ? tp + 4 : tp - 58;
  return __shfl_sync(~0u, 2 * r + (v & 1), 0);
}
__device__ __forceinline__ int role_rb(int cta) { return ((cta >> 4) & 3) * 4 + ((cta >> 2) & 3); }
__device__ __forceinline__ int role_hg(int cta) { return (cta >> 6) * 4 + (cta & 3); }
__device__ __forceinline__ int role_rb2(int cta) { return cta >> 3; }
__device__ __forceinline__ int role_q2(int cta) { return cta & 7; }

template <bool SMID> __global__ void __launch_bounds__(NTHREADS, 1) fused_kernel(const __grid_constant__ Params p) {
  extern __shared__ __align__(1024) uint8_t smem[];
  const uint32_t sb = s32(smem);
  const int tid = threadIdx.x, lane = tid & 31;
  const int warp = __shfl_sync(~0u, tid >> 5, 0);
  const uint32_t bar = sb + SM_BAR;
  if (tid == 0) TS(0);
  const int cta0 = role_id<SMID>();
  if (warp == 0 && (!SMID || cta0 < NCTA) && elect_one()) {
    const int rb = role_rb(cta0), hg = role_hg(cta0);
    asm volatile("prefetch.tensormap [%0];" ::"l"(&p.mapW3) : "memory");
    mbar_init(bar + 8 * B_XF, 1); mbar_init(bar + 8 * B_KVF, 1); mbar_init(bar + 8 * (B_XF + 1), 1); mbar_init(bar + 8 * (B_KVF + 1), 1);
    fence_async_smem();
    mbar_expect(bar + 8 * B_XF, 16384);
    tma_ld(sb + SM_X, &p.mapX128, 0, rb * 128, bar + 8 * B_XF);
    mbar_expect(bar + 8 * B_KVF, 24576);
    tma_ld3(sb + SM_W, &p.mapW3, hg * 64, 0, 0, bar + 8 * B_KVF);
    mbar_expect(bar + 8 * (B_XF + 1), 16384);
    tma_ld(sb + SM_X + 16384, &p.mapX128, 64, rb * 128, bar + 8 * (B_XF + 1));
    mbar_expect(bar + 8 * (B_KVF + 1), 24576);
    tma_ld3(sb + SM_W + 24576, &p.mapW3, hg * 64, 64, 0, bar + 8 * (B_KVF + 1));
    TS(56);
  }
  if (SMID && cta0 >= NCTA) {
    if (tid == 0) spin_until(&g_cnt[C_CS * 32], (ld_relaxed(&g_cnt[C_CS * 32]) / NCTA + 1) * NCTA);
    return;
  }
  if (warp >= 1 && warp < 5 && elect_one()) {
#pragma unroll
    for (int q = 0; q < 4; q++) {
      if (warp == q + 1) {
#pragma unroll
        for (int i = 17 * q; i < 17 * q + 17; i++) {
          if (i == B_XF || i == B_XF + 1 || i == B_KVF || i == B_KVF + 1) continue;
          int cnt = 1;
          if ((i >= B_KVE && i < B_KVE + 5) || i == B_QDONE || i == B_PDONE || i == B_OST || i == B_AD) cnt = 2;
          if (i == B_Z0) cnt = 128;
          if (i >= B_U && i < B_U + 4) cnt = 8;
          if ((i >= B_S && i < B_S + 4) || (i >= B_E && i < B_E + 4) || i >= B_P || i == B_PE) cnt = 4;
          mbar_init(bar + 8 * i, cnt);
        }
      }
    }
    fence_async_smem();
  }

  if (warp < 8) {
    bar_sync(0, NTHREADS);
    if (tid == 0) TS(1);
    asm volatile("setmaxnreg.inc.sync.aligned.u32 %0;" ::"n"(R_CONS));
    const int cw = __shfl_sync(~0u, opaque_tid() >> 5, 0);
    const int wg = cw >> 2, w = cw & 3;
    const int cta = role_id<SMID>();
    if (tid == 0) TS(54);
#pragma unroll 1
    for (int layer = 0; layer < 2; layer++) {
      attn_phase(p, sb, layer, role_rb(cta), role_hg(cta), wg, w);
      if (p.stop == 1 + 3 * layer) return;
      proj_phase(p, sb, layer, role_rb2(cta), role_q2(cta), wg, w);
      if (p.stop == 2 + 3 * layer) return;
      conv_phase(p, sb, layer, cta);
      if (p.stop == 3 + 3 * layer) return;
    }
    final_phase(p, sb, cta, wg, w);
  } else if (warp < 12) {
    asm volatile("setmaxnreg.dec.sync.aligned.u32 %0;" ::"n"(R_HELP));
    const int ht = tid - 256;
    const int cta = role_id<SMID>(), rb = role_rb(cta), hg = role_hg(cta);
    unsigned ep0 = 0;
    if (ht == 0) ep0 = ld_relaxed(&g_cnt[C_CS * 32]);
    bar_sync(0, NTHREADS);
    if (ht == 0) {
      asm volatile("st.shared.u32 [%0], %1;" ::"r"(sb + SM_EP), "r"(ep0 / NCTA) : "memory");
      mbar_arrive(bar + 8 * B_EP);
    }
    if (hg == 0) {
      *(float4*)(g_stats + (ht >> 6) * LSEQ * 2 + rb * 256 + (ht & 63) * 4) = make_float4(0.f, 0.f, 0.f, 0.f);
    }
    mbar_arrive(bar + 8 * B_Z0);
    mbar_wait(bar + 8 * B_EP, 0);
    colsum_part(p, sb, cta, ht, lds32(sb + SM_EP) + 1);
    if (ht == 0) TS(50);
    {
      KGen kg;
      const uint32_t tab0 = sb + ((ht >> 5) < 2 ? SM_T : SM_T2 - 4096) + (ht >> 5) * 2048;
      const uint32_t tab = tab0 + (ht & 31) * 16, taba = tab0 + ((ht >> 3) & 1) * 1024 + (((ht >> 1) & 8) + (ht & 7)) * 16;
      const int chn = cv_chan(cta, ht >> 5);
      kgen_setup(kg, sb, cta, ht, load_modes(p, chn * 128 + (ht & 31) * 4), p.log_dt[chn], p.dskip[chn]);
#pragma unroll 1
      for (int u = 0; u < 4; u++) {
        if (u == KG_PRE) {
          if (ht == 0) TS(39);
          mbar_wait(bar + 8 * B_AD, 0);
          if (ht == 0) TS(41);
        }
        if (u == 3) mbar_wait(bar + 8 * B_PDONE, 0);
        kgen_unit(tab, taba, kg.cur.x, kg.cur.y, {kg.cur.z, kg.cur.w}, kg.T);
        kg.cur = lds128f(kgen_slot(sb, opaque_tid() - 256, u + 1));
      }
      kgen_finish(kg, sb, cta, opaque_tid() - 256);
    }
    if (ht == 0) TS(51);
    bar_sync(4, 128);
#pragma unroll 1
    for (int layer = 0; layer < 2; layer++) {
      if (p.stop <= 1 + 3 * layer) return;
      mbar_wait(bar + 8 * B_PDONE, layer);
      expand_taps(sb, opaque_tid() - 256);
      conv_zero(sb, opaque_tid() - 256);
      if (ht == 0) TS(52 + layer);
      warp_release(bar + 8 * B_PE);
      if (p.stop <= 2 + 3 * layer) return;
      {
        uint4 un[4];
        conv_prep(sb, layer, cta, opaque_tid() - 256, un);
        if (layer == 1 && ht == 0) TS(62);
        bar_sync(4, 128);
#pragma unroll
        for (int lc = 0; lc < 4; lc++) {
          conv_sums(sb, lc, opaque_tid() - 256, un[lc]);
          warp_release(bar + 8 * (B_S + lc));
          if (lc == 0 && layer == 1 && ht == 0) TS(46);
        }
      }
#pragma unroll 1
      for (int lc = 0; lc < 4; lc++) {
        conv_epi(sb, layer, cta, lc, opaque_tid() - 256);
        warp_release(bar + 8 * (B_E + lc));
      }
    }
  } else {
    asm volatile("setmaxnreg.dec.sync.aligned.u32 40;");
    const int cta = role_id<SMID>(), rb = role_rb(cta), hg = role_hg(cta), rb2 = role_rb2(cta), q2 = role_q2(cta);
    bar_sync(0, NTHREADS);
    if (warp == 12) {
      if (elect_one()) {
        unsigned epoch = 0;
#pragma unroll 1
        for (int layer = 0; layer < 2; layer++) {
          auto ld_x = [&](int c) {
            const uint32_t b = bar + 8 * (B_XF + c);
            const int kc = c;
            mbar_expect(b, 16384);
            tma_ld(sb + SM_X + c * 16384, &p.mapX128, kc * 64, rb * 128, b);
          };
          auto ld_w = [&](int c, int slot) {
            const uint32_t b = bar + 8 * (B_KVF + c);
            mbar_expect(b, 24576);
            tma_ld3(sb + SM_W + slot * 24576, &p.mapW3, hg * 64, c * 64, 0, b);
          };
          if (layer == 0) {
            TS(55);
            ld_x(2); ld_w(2, 2);
            ld_x(3);
            if (rb < 5) tma_prefetch3(&p.mapW3, hg * 64, (3 + rb) * 64, 0);
#pragma unroll 1
            for (int c = 4; c < 8; c++) ld_x(c);
            mbar_wait(bar + 8 * (B_KVF + 2), 0);
            if (rb2 < 4) tma_prefetch2(&p.mapWo128, q2 * 64, rb2 * 128);
            asm volatile("prefetch.tensormap [%0];" ::"l"(&p.mapO) : "memory");
            asm volatile("prefetch.tensormap [%0];" ::"l"(&p.mapO128) : "memory");
            asm volatile("prefetch.tensormap [%0];" ::"l"(&p.mapXT) : "memory");
            asm volatile("prefetch.tensormap [%0];" ::"l"(&p.mapXT3) : "memory");
            mbar_wait(bar + 8 * B_EP, 0);
            epoch = lds32(sb + SM_EP);
          } else {
            mbar_wait(bar + 8 * B_PDONE, 0);
            ld_w(0, 0); ld_w(1, 1);
          }
          {
            int slot = 0;
#pragma unroll 1
            for (int c = 3; c < 8; c++) {
              mbar_wait(bar + 8 * (B_KVE + c - 3), layer);
              ld_w(c, slot);
              slot = slot == 2 ? 0 : slot + 1;
            }
          }
          if (p.stop <= 1 + 3 * layer) return;
          mbar_wait(bar + 8 * B_QDONE, layer);
          if (rb > 0) mbar_wait(bar + 8 * B_HF, layer);
#pragma unroll 1
          for (int c = 0; c < 4; c++) {
            const uint32_t b = bar + 8 * (B_WOF + c);
            mbar_expect(b, 16384);
            tma_ld(sb + SM_X + c * 16384, &p.mapWo128, q2 * 64, c * 128, b);
          }
          {
            const uint32_t b = bar + 8 * B_RF;
            mbar_expect(b, 16384);
            if (layer == 0) tma_ld(sb + SM_R, &p.mapX128, q2 * 64, rb2 * 128, b);
            else tma_ld3(sb + SM_R, &p.mapXT3, 0, DM + q2 * 64, rb2 * 2, b);
          }
          spin_until(&g_cnt[(C_O + rb2) * 32], (2 * epoch + layer + 1) * 16);
          mbar_wait(bar + 8 * B_OST, layer);
          fence_async_global();
#pragma unroll 1
          for (int c = 0; c < 8; c++) {
            const uint32_t b = bar + 8 * (B_OF + c);
            mbar_expect(b, 16384);
            tma_ld(sb + (c < 4 ? SM_X + 65536 + c * 16384 : SM_W + (c - 4) * 16384), &p.mapO128, c * 64, rb2 * 128, b);
          }
          if (p.stop <= 3 + 3 * layer) return;
        }
      }
    } else if (warp == 13) {
      if (elect_one() && p.stop > 3) {
        mbar_wait(bar + 8 * B_GB, 0);
        const unsigned target = (lds32(sb + SM_EP) + 1) * NCTA;
#pragma unroll 1
        for (int lc = 0; lc < 4; lc++) {
          spin_until(&g_cnt[C_G1 * 32 + lc], target);
          if (lc == 3) TS(44);
          fence_async_global();
          fence_async_smem();
#pragma unroll
          for (int c = 2 * lc; c < 2 * lc + 2; c++) {
            mbar_expect(bar + 8 * (B_XF + c), 16384);
            tma_ld3(sb + SM_X + c * 16384, &p.mapXT3, 0, DM + c * 64, rb * 2, bar + 8 * (B_XF + c));
            if (c == 2) {
              mbar_expect(bar + 8 * (B_KVF + 2), 24576);
              tma_ld3(sb + SM_W + 2 * 24576, &p.mapW3, hg * 64, 128, 0, bar + 8 * (B_KVF + 2));
            }
          }
        }
      }
    } else if (warp == 15) {
      if (elect_one()) {
#pragma unroll 1
        for (int i = 0; i < 8; i++) {
          const int layer = i >> 2, lc = i & 3;
          if (p.stop <= 2 + 3 * layer) return;
          mbar_wait(bar + 8 * (B_E + lc), layer);
          bulk_st(g_xT + (size_t)((2 * layer + 1) * DM + cv_chan(cta, lc)) * LSEQ, sb + cv_s(lc), 4096);
          bulk_commit();
          bulk_wait_all();
          red_relaxed(&g_cnt[(layer ? C_F + (cta >> 5) : C_G1) * 32 + lc]);
          if (lc == 3) TS(2 + layer * 20 + 16);
        }
      }
    } else if (warp == 14) {
      mbar_wait(bar + 8 * B_EP, 0);
      const unsigned epoch = lds32(sb + SM_EP);
      {
        uint2 v[6];
        bool ok;
        int it = 0;
        do {
          ok = true;
#pragma unroll
          for (int i = 0; i < 6; i++) {
            const int k = lane + 32 * i;
            asm volatile("ld.relaxed.gpu.global.v2.u32 {%0,%1}, [%2];" : "=r"(v[i].x), "=r"(v[i].y) : "l"(&g_colsum[(k >> 6) * 512 + hg * 64 + (k & 63)]) : "memory");
            ok = ok && v[i].y == epoch + 1;
          }
          if (++it > (1 << 22)) __trap();
        } while (!__all_sync(~0u, ok));
#pragma unroll
        for (int i = 0; i < 6; i++) sts32f(sb + SM_CS + 4 * (lane + 32 * i), __uint_as_float(v[i].x));
      }
      __syncwarp();
      if (lane == 0) {
        mbar_arrive(bar + 8 * B_CSF);
        TS(40);
        mbar_wait(bar + 8 * B_Z0, 0);
        red_release(&g_cnt[C_CS * 32]);
        spin_until(&g_cnt[C_CS * 32], (epoch + 1) * NCTA);
        mbar_arrive(bar + 8 * B_ZF);
#pragma unroll 1
        for (int layer = 0; layer < 2; layer++) {
          if (p.stop <= 1 + 3 * layer) return;
          spin_until(&g_cnt[(layer ? C_G2 : C_G0) * 32], (epoch + 1) * 256);
          mbar_arrive(bar + 8 * B_GB);
        }
      }
    }
  }
}

typedef CUresult (*EncodeFn)(CUtensorMap*, CUtensorMapDataType, cuuint32_t, void*, const cuuint64_t*, const cuuint64_t*,
                             const cuuint32_t*, const cuuint32_t*, CUtensorMapInterleave, CUtensorMapSwizzle,
                             CUtensorMapL2promotion, CUtensorMapFloatOOBfill);

static void make_map(EncodeFn enc, CUtensorMap* m, void* ptr, uint64_t cols, uint64_t rows, uint32_t box_rows) {
  cuuint64_t dims[2] = {cols, rows};
  cuuint64_t strides[1] = {cols * 2};
  cuuint32_t box[2] = {64, box_rows};
  cuuint32_t es[2] = {1, 1};
  enc(m, CU_TENSOR_MAP_DATA_TYPE_BFLOAT16, 2, ptr, dims, strides, box, es, CU_TENSOR_MAP_INTERLEAVE_NONE,
      CU_TENSOR_MAP_SWIZZLE_128B, CU_TENSOR_MAP_L2_PROMOTION_L2_128B, CU_TENSOR_MAP_FLOAT_OOB_FILL_NONE);
}
static void make_map3(EncodeFn enc, CUtensorMap* m, void* ptr, uint64_t d0, uint64_t cols, uint64_t rows, uint64_t blk_stride,
                      uint64_t nblocks, uint32_t nblk) {
  cuuint64_t dims[3] = {d0, rows, nblocks};
  cuuint64_t strides[2] = {cols * 2, blk_stride * 2};
  cuuint32_t box[3] = {64, 64, nblk};
  cuuint32_t es[3] = {1, 1, 1};
  enc(m, CU_TENSOR_MAP_DATA_TYPE_BFLOAT16, 3, ptr, dims, strides, box, es, CU_TENSOR_MAP_INTERLEAVE_NONE,
      CU_TENSOR_MAP_SWIZZLE_128B, CU_TENSOR_MAP_L2_PROMOTION_L2_128B, CU_TENSOR_MAP_FLOAT_OOB_FILL_NONE);
}

extern "C" void kernel_launch(void* const* d_in, const int* in_sizes, int n_in, void* d_out, int out_size) {
  static Params prm;
  static void* cached[13] = {nullptr};
  static bool attr_done = false, by_smid = false;
  bool same = attr_done && cached[12] == d_out;
  for (int i = 0; i < 12 && same; i++) same = cached[i] == d_in[i];
  if (!same) {
    void* fn = nullptr;
    cudaDriverEntryPointQueryResult qr;
    cudaGetDriverEntryPoint("cuTensorMapEncodeTiled", &fn, cudaEnableDefault, &qr);
    EncodeFn enc = (EncodeFn)fn;
    void *pO, *pXT;
    cudaGetSymbolAddress(&pO, g_O);
    cudaGetSymbolAddress(&pXT, g_xT);
    make_map(enc, &prm.mapO, pO, DM, LSEQ, 64);
    make_map(enc, &prm.mapXT, pXT, LSEQ, 4 * DM, 64);
    prm.out = (bf16*)d_out;
    make_map(enc, &prm.mapX128, d_in[0], DM, LSEQ, 128);
    make_map(enc, &prm.mapWo128, d_in[2], DM, DM, 128);
    make_map(enc, &prm.mapO128, pO, DM, LSEQ, 128);
    make_map3(enc, &prm.mapW3, d_in[1], DM, 3 * DM, DM, DM, 3, 3);
    make_map3(enc, &prm.mapXT3, pXT, 64, LSEQ, 4 * DM, 64, 32, 2);
    prm.wqkv = (const bf16*)d_in[1];
    prm.a_re = (const bf16*)d_in[4]; prm.a_im = (const bf16*)d_in[5];
    prm.b_re = (const bf16*)d_in[6]; prm.b_im = (const bf16*)d_in[7];
    prm.c_re = (const bf16*)d_in[8]; prm.c_im = (const bf16*)d_in[9];
    prm.log_dt = (const bf16*)d_in[10]; prm.dskip = (const bf16*)d_in[11];
    int dev = 0, sms = 0;
    cudaGetDevice(&dev);
    cudaDeviceGetAttribute(&sms, cudaDevAttrMultiProcessorCount, dev);
    by_smid = sms == 132;
    cudaFuncSetAttribute(fused_kernel<true>, cudaFuncAttributeMaxDynamicSharedMemorySize, SM_TOTAL);
    cudaFuncSetAttribute(fused_kernel<false>, cudaFuncAttributeMaxDynamicSharedMemorySize, SM_TOTAL);
    for (int i = 0; i < 12; i++) cached[i] = d_in[i];
    cached[12] = d_out;
    attr_done = true;
  }
  prm.stop = 100;
    if (by_smid) fused_kernel<true><<<132, NTHREADS, SM_TOTAL>>>(prm);
  else fused_kernel<false><<<NCTA, NTHREADS, SM_TOTAL>>>(prm);
}
```

```cpp
#include <cuda_runtime.h>
#include <cuda_bf16.h>
#include <cuda.h>
#include <stdint.h>

typedef __nv_bfloat16 bf16;

constexpr int LSEQ = 2048;
constexpr int DM = 512;
constexpr int NCTA = 128;
constexpr int NTHREADS = 512;
#define RR 0
#define KG_PRE 0
#define CS_AT 5
#define KG_LAST 1
#define X_JIT 0
#define PF_AT 2
#define KG_GATE 2
#define R_CONS 192
#define R_HELP 88

constexpr int SM_X = 0;
constexpr int SM_W = 131072;
constexpr int SM_KVX = SM_W;
constexpr int SM_OST = SM_W + 32768;
constexpr int SM_R = 196608;
constexpr int SM_T = 212992;
constexpr int SM_KC = 217088;
constexpr int KC_STRIDE = 648;
constexpr int SM_CS = SM_KC + 4 * KC_STRIDE * 2;
constexpr int SM_CW = SM_R + 8192;
constexpr int SM_EP = SM_CS + 768;
constexpr int SM_BAR = SM_EP + 16;
constexpr int SM_T2 = SM_BAR + 832;
constexpr int SM_HALO = SM_T2 + 4096;
constexpr int SM_TOTAL = SM_HALO + 4096;
static_assert(SM_TOTAL <= 232448, "shared memory");

constexpr int CV_UH = 140 * 16;
constexpr int CV_PECH = 1120 * 4;
constexpr int CV_PBW = 2112 * 2;
__host__ __device__ constexpr int cv_s(int lc) { return SM_X + lc * 32768; }
__host__ __device__ constexpr int cv_u(int lc) { return cv_s(lc) + 4096; }
__host__ __device__ constexpr int cv_pe(int lc) { return cv_u(lc) + 2 * CV_UH; }
__host__ __device__ constexpr int cv_pb(int lc) { return cv_pe(lc) + CV_PECH; }
__host__ __device__ constexpr int cv_ft(int lc) { return cv_pb(lc) + 4 * CV_PBW; }
static_assert(cv_ft(0) + 1024 <= 32768, "conv buffers");
__host__ __device__ constexpr int cv_chan(int cta, int lc) { return cta + 128 * lc; }

enum {
  B_XF = 0,
  B_KVF = 8,
  B_KVE = 16,
  B_AD = 21,
  B_OST = 22,
  B_RF = 23,
  B_U = 24,
  B_S = 28,
  B_T = 32,
  B_WOF = 36,
  B_E = 40,
  B_OF = 44,
  B_P = 64,
  B_CW = 53,
  B_HF = 54,
  B_CSF = 55,
  B_QDONE = 56,
  B_PDONE = 57,
  B_Z0 = 58,
  B_PE = 59,
  B_GB = 60,
  B_EP = 62,
  B_ZF = 63,
  B_COUNT = 68
};

enum {
  C_CS = 0,
  C_G0 = 1,
  C_G1 = 2,
  C_G2 = 3,
  C_O = 4,
  C_F = 20,
  C_COUNT = 24
};

__device__ unsigned g_cnt[C_COUNT * 32];
__device__ __align__(1024) bf16 g_O[LSEQ * DM];
__device__ __align__(1024) bf16 g_xT[4 * DM * LSEQ];
__device__ __align__(1024) float g_stats[2 * LSEQ * 2];
__device__ __align__(1024) uint4 g_colsum[8 * 16 * 48];
__device__ __align__(1024) uint4 g_halo[2 * 16 * 8 * 384];
__device__ __align__(1024) uint4 g_part[2 * 16 * 8 * 128];
#define TS(i) do { } while (0)

#define KTS(i) do { if (ht == 0) TS(i); } while (0)
#define FTS(i) do { } while (0)
#define LTS(i) do { } while (0)

struct Params {
  CUtensorMap mapO, mapXT, mapX128, mapWo128, mapO128, mapW3, mapW3h, mapXT3;
  const bf16 *a_re, *a_im, *b_re, *b_im, *c_re, *c_im, *log_dt, *dskip;
  bf16* out;
  int stop;
};

__device__ __forceinline__ uint32_t s32(const void* p) { return (uint32_t)__cvta_generic_to_shared(p); }
__device__ __forceinline__ void mbar_init(uint32_t b, int c) { asm volatile("mbarrier.init.shared::cta.b64 [%0], %1;" ::"r"(b), "r"(c) : "memory"); }
__device__ __forceinline__ void mbar_expect(uint32_t b, int bytes) { asm volatile("mbarrier.arrive.expect_tx.shared::cta.b64 _, [%0], %1;" ::"r"(b), "r"(bytes) : "memory"); }
__device__ __forceinline__ void mbar_arrive(uint32_t b) { asm volatile("mbarrier.arrive.shared::cta.b64 _, [%0];" ::"r"(b) : "memory"); }
__device__ __forceinline__ void mbar_arrive_if(uint32_t b, bool c) {
  asm volatile("{\n.reg .pred p;\nsetp.ne.u32 p, %1, 0;\n@p mbarrier.arrive.shared::cta.b64 _, [%0];\n}" ::"r"(b), "r"((uint32_t)c) : "memory");
}
__device__ __forceinline__ void mbar_wait(uint32_t b, int parity) {
  asm volatile("{\n.reg .pred p;\nWAIT_LOOP:\nmbarrier.try_wait.parity.shared::cta.b64 p, [%0], %1;\n@p bra WAIT_DONE;\nbra WAIT_LOOP;\nWAIT_DONE:\n}" ::"r"(b), "r"(parity) : "memory");
}
__device__ __forceinline__ int opaque_tid() { int v; asm volatile("mov.u32 %0, %%tid.x;" : "=r"(v)); return v; }
__device__ __forceinline__ bool elect_one() {
  uint32_t r;
  asm volatile("{\n.reg .pred p;\nelect.sync _|p, 0xffffffff;\nselp.u32 %0, 1, 0, p;\n}" : "=r"(r));
  return r != 0;
}
__device__ __forceinline__ void tma_ld(uint32_t dst, const CUtensorMap* m, int c0, int c1, uint32_t bar) {
  asm volatile("cp.async.bulk.tensor.2d.shared::cluster.global.mbarrier::complete_tx::bytes [%0], [%1, {%3, %4}], [%2];"
               ::"r"(dst), "l"(m), "r"(bar), "r"(c0), "r"(c1) : "memory");
}
__device__ __forceinline__ void tma_ld3(uint32_t dst, const CUtensorMap* m, int c0, int c1, int c2, uint32_t bar) {
  asm volatile("cp.async.bulk.tensor.3d.shared::cluster.global.mbarrier::complete_tx::bytes [%0], [%1, {%3, %4, %5}], [%2];"
               ::"r"(dst), "l"(m), "r"(bar), "r"(c0), "r"(c1), "r"(c2) : "memory");
}
__device__ __forceinline__ void tma_prefetch2(const CUtensorMap* m, int c0, int c1) {
  asm volatile("cp.async.bulk.prefetch.tensor.2d.L2.global.tile [%0, {%1, %2}];" ::"l"(m), "r"(c0), "r"(c1) : "memory");
}
__device__ __forceinline__ void tma_prefetch3(const CUtensorMap* m, int c0, int c1, int c2) {
  asm volatile("cp.async.bulk.prefetch.tensor.3d.L2.global.tile [%0, {%1, %2, %3}];" ::"l"(m), "r"(c0), "r"(c1), "r"(c2) : "memory");
}
__device__ __forceinline__ void tma_st(const CUtensorMap* m, int c0, int c1, uint32_t src) {
  asm volatile("cp.async.bulk.tensor.2d.global.shared::cta.bulk_group [%0, {%2, %3}], [%1];" ::"l"(m), "r"(src), "r"(c0), "r"(c1) : "memory");
}
__device__ __forceinline__ void bulk_ld(uint32_t dst, const void* src, int bytes, uint32_t bar) {
  asm volatile("cp.async.bulk.shared::cluster.global.mbarrier::complete_tx::bytes [%0], [%1], %2, [%3];" ::"r"(dst), "l"(src), "r"(bytes), "r"(bar) : "memory");
}
__device__ __forceinline__ void bulk_st(void* dst, uint32_t src, int bytes) {
  asm volatile("cp.async.bulk.global.shared::cta.bulk_group [%0], [%1], %2;" ::"l"(dst), "r"(src), "r"(bytes) : "memory");
}
__device__ __forceinline__ void bulk_red_add_f32(void* dst, uint32_t src, int bytes) {
  asm volatile("cp.reduce.async.bulk.global.shared::cta.bulk_group.add.f32 [%0], [%1], %2;" ::"l"(dst), "r"(src), "r"(bytes) : "memory");
}
__device__ __forceinline__ void bulk_commit() { asm volatile("cp.async.bulk.commit_group;" ::: "memory"); }
__device__ __forceinline__ void bulk_wait_all() { asm volatile("cp.async.bulk.wait_group 0;" ::: "memory"); }
__device__ __forceinline__ void fence_async_smem() { asm volatile("fence.proxy.async.shared::cta;" ::: "memory"); }
__device__ __forceinline__ void fence_async_global() { asm volatile("fence.proxy.async.global;" ::: "memory"); }
__device__ __forceinline__ void bar_sync(int id, int n) { asm volatile("bar.sync %0, %1;" ::"r"(id), "r"(n) : "memory"); }
__device__ __forceinline__ void bar_arrive(int id, int n) { asm volatile("bar.arrive %0, %1;" ::"r"(id), "r"(n) : "memory"); }
__device__ __forceinline__ void wg_fence() { asm volatile("wgmma.fence.sync.aligned;" ::: "memory"); }
__device__ __forceinline__ void wg_commit() { asm volatile("wgmma.commit_group.sync.aligned;" ::: "memory"); }
template <int N> __device__ __forceinline__ void wg_wait() { asm volatile("wgmma.wait_group.sync.aligned %0;" ::"n"(N) : "memory"); }
__device__ __forceinline__ uint64_t mkdesc(uint32_t addr, uint32_t lbo, uint32_t sbo, int sw) {
  return (uint64_t)((addr & 0x3FFFF) >> 4) | ((uint64_t)(lbo >> 4) << 16) | ((uint64_t)(sbo >> 4) << 32) | ((uint64_t)sw << 62);
}
__device__ __forceinline__ void ldsm4(uint32_t* r, uint32_t a) {
  asm volatile("ldmatrix.sync.aligned.m8n8.x4.shared.b16 {%0,%1,%2,%3}, [%4];" : "=r"(r[0]), "=r"(r[1]), "=r"(r[2]), "=r"(r[3]) : "r"(a) : "memory");
}
__device__ __forceinline__ void ldsm4t(uint32_t* r, uint32_t a) {
  asm volatile("ldmatrix.sync.aligned.m8n8.x4.trans.shared.b16 {%0,%1,%2,%3}, [%4];" : "=r"(r[0]), "=r"(r[1]), "=r"(r[2]), "=r"(r[3]) : "r"(a) : "memory");
}
__device__ __forceinline__ void stsm4(uint32_t a, uint32_t r0, uint32_t r1, uint32_t r2, uint32_t r3) {
  asm volatile("stmatrix.sync.aligned.m8n8.x4.shared.b16 [%0], {%1,%2,%3,%4};" ::"r"(a), "r"(r0), "r"(r1), "r"(r2), "r"(r3) : "memory");
}
__device__ __forceinline__ void stsm4t(uint32_t a, uint32_t r0, uint32_t r1, uint32_t r2, uint32_t r3) {
  asm volatile("stmatrix.sync.aligned.m8n8.x4.trans.shared.b16 [%0], {%1,%2,%3,%4};" ::"r"(a), "r"(r0), "r"(r1), "r"(r2), "r"(r3) : "memory");
}
__device__ __forceinline__ uint32_t movm_t(uint32_t a) { uint32_t r; asm volatile("movmatrix.sync.aligned.m8n8.trans.b16 %0, %1;" : "=r"(r) : "r"(a)); return r; }
__device__ __forceinline__ uint32_t lds32(uint32_t a) { uint32_t v; asm volatile("ld.shared.b32 %0, [%1];" : "=r"(v) : "r"(a) : "memory"); return v; }
__device__ __forceinline__ float2 lds64f(uint32_t a) { float2 v; asm volatile("ld.shared.v2.f32 {%0,%1}, [%2];" : "=f"(v.x), "=f"(v.y) : "r"(a) : "memory"); return v; }
__device__ __forceinline__ float4 lds128f(uint32_t a) { float4 v; asm volatile("ld.shared.v4.f32 {%0,%1,%2,%3}, [%4];" : "=f"(v.x), "=f"(v.y), "=f"(v.z), "=f"(v.w) : "r"(a) : "memory"); return v; }
__device__ __forceinline__ uint4 lds128(uint32_t a) { uint4 v; asm volatile("ld.shared.v4.b32 {%0,%1,%2,%3}, [%4];" : "=r"(v.x), "=r"(v.y), "=r"(v.z), "=r"(v.w) : "r"(a) : "memory"); return v; }
__device__ __forceinline__ void sts128(uint32_t a, uint4 v) { asm volatile("st.shared.v4.b32 [%0], {%1,%2,%3,%4};" ::"r"(a), "r"(v.x), "r"(v.y), "r"(v.z), "r"(v.w) : "memory"); }
__device__ __forceinline__ void sts128f(uint32_t a, float x, float y, float z, float w) { asm volatile("st.shared.v4.f32 [%0], {%1,%2,%3,%4};" ::"r"(a), "f"(x), "f"(y), "f"(z), "f"(w) : "memory"); }
__device__ __forceinline__ void sts32f(uint32_t a, float v) { asm volatile("st.shared.f32 [%0], %1;" ::"r"(a), "f"(v) : "memory"); }
__device__ __forceinline__ void sts16(uint32_t a, uint16_t v) { asm volatile("st.shared.u16 [%0], %1;" ::"r"(a), "h"(v) : "memory"); }
__device__ __forceinline__ uint32_t lds16(uint32_t a) { uint16_t v; asm volatile("ld.shared.u16 %0, [%1];" : "=h"(v) : "r"(a) : "memory"); return v; }
__device__ __forceinline__ uint32_t packbf(float lo, float hi) { uint32_t r; asm("cvt.rn.bf16x2.f32 %0, %1, %2;" : "=r"(r) : "f"(hi), "f"(lo)); return r; }
__device__ __forceinline__ float bf_lo(uint32_t v) { return __uint_as_float(v << 16); }
__device__ __forceinline__ float bf_hi(uint32_t v) { return __uint_as_float(v & 0xffff0000u); }
__device__ __forceinline__ float ex2(float x) { float r; asm("ex2.approx.ftz.f32 %0, %1;" : "=f"(r) : "f"(x)); return r; }
__device__ __forceinline__ float rsqrt_approx(float x) { float r; asm("rsqrt.approx.ftz.f32 %0, %1;" : "=f"(r) : "f"(x)); return r; }
__device__ __forceinline__ float rcp_approx(float x) { float r; asm("rcp.approx.ftz.f32 %0, %1;" : "=f"(r) : "f"(x)); return r; }
__device__ __forceinline__ void mma_bf16(float* d, const uint32_t* a, uint32_t b0, uint32_t b1) {
  asm("mma.sync.aligned.m16n8k16.row.col.f32.bf16.bf16.f32 {%0,%1,%2,%3}, {%4,%5,%6,%7}, {%8,%9}, {%0,%1,%2,%3};"
               : "+f"(d[0]), "+f"(d[1]), "+f"(d[2]), "+f"(d[3]) : "r"(a[0]), "r"(a[1]), "r"(a[2]), "r"(a[3]), "r"(b0), "r"(b1));
}
__device__ __forceinline__ void red_release(unsigned* p) { asm volatile("red.release.gpu.global.add.u32 [%0], 1;" ::"l"(p) : "memory"); }
__device__ __forceinline__ void red_relaxed(unsigned* p) { asm volatile("red.relaxed.gpu.global.add.u32 [%0], 1;" ::"l"(p) : "memory"); }
__device__ __forceinline__ unsigned ld_relaxed(const unsigned* p) { unsigned v; asm volatile("ld.relaxed.gpu.global.u32 %0, [%1];" : "=r"(v) : "l"(p) : "memory"); return v; }
__device__ __forceinline__ void spin_until(const unsigned* p, unsigned target) {
  int it = 0;
  while ((int)(ld_relaxed(p) - target) < 0) {
    if (++it > (1 << 23)) __trap();
  }
}
__device__ __forceinline__ uint4 ldcg128(const void* p) { uint4 v; asm volatile("ld.global.cg.v4.b32 {%0,%1,%2,%3}, [%4];" : "=r"(v.x), "=r"(v.y), "=r"(v.z), "=r"(v.w) : "l"(p) : "memory"); return v; }
__device__ __forceinline__ uint4 ld_tagged(const uint4* p) { uint4 v; asm volatile("ld.relaxed.gpu.global.v4.u32 {%0,%1,%2,%3}, [%4];" : "=r"(v.x), "=r"(v.y), "=r"(v.z), "=r"(v.w) : "l"(p) : "memory"); return v; }
__device__ __forceinline__ void st_tagged(uint4* p, uint32_t a, uint32_t b, uint32_t tag) { asm volatile("st.relaxed.gpu.global.v4.u32 [%0], {%1,%2,%3,%2};" ::"l"(p), "r"(a), "r"(tag), "r"(b) : "memory"); }
__device__ __forceinline__ void st_tagged3(uint4* p, uint32_t a, uint32_t b, uint32_t c, uint32_t tag) { asm volatile("st.relaxed.gpu.global.v4.u32 [%0], {%1,%2,%3,%4};" ::"l"(p), "r"(a), "r"(b), "r"(c), "r"(tag) : "memory"); }
__device__ __forceinline__ uint4 poll_tagged(const uint4* p, uint32_t tag) {
  uint4 v = ld_tagged(p);
  int it = 0;
  while (v.y != tag || v.w != tag) {
    if (++it > (1 << 22)) __trap();
    v = ld_tagged(p);
  }
  return v;
}
__device__ __forceinline__ uint32_t hadd2(uint32_t a, uint32_t b) { uint32_t r; asm("add.rn.bf16x2 %0, %1, %2;" : "=r"(r) : "r"(a), "r"(b)); return r; }
__device__ __forceinline__ uint32_t hmul2(uint32_t a, uint32_t b) { uint32_t r; asm("mul.rn.bf16x2 %0, %1, %2;" : "=r"(r) : "r"(a), "r"(b)); return r; }

template<int N,int TB> __device__ __forceinline__ void wgmma_rs(float* d, const uint32_t* a, uint64_t db, int sd);
template<int N,int TA,int TB> __device__ __forceinline__ void wgmma_ss(float* d, uint64_t da, uint64_t db, int sd);
template<> __device__ __forceinline__ void wgmma_rs<128,0>(float* d, const uint32_t* a, uint64_t db, int sd) {
  asm volatile("{\n.reg .pred p;\nsetp.ne.b32 p, %69, 0;\nwgmma.mma_async.sync.aligned.m64n128k16.f32.bf16.bf16 {%0,%1,%2,%3,%4,%5,%6,%7,%8,%9,%10,%11,%12,%13,%14,%15,%16,%17,%18,%19,%20,%21,%22,%23,%24,%25,%26,%27,%28,%29,%30,%31,%32,%33,%34,%35,%36,%37,%38,%39,%40,%41,%42,%43,%44,%45,%46,%47,%48,%49,%50,%51,%52,%53,%54,%55,%56,%57,%58,%59,%60,%61,%62,%63}, {%64,%65,%66,%67}, %68, p, 1, 1, 0;\n}\n"
   : "+f"(d[0]),"+f"(d[1]),"+f"(d[2]),"+f"(d[3]),"+f"(d[4]),"+f"(d[5]),"+f"(d[6]),"+f"(d[7]),"+f"(d[8]),"+f"(d[9]),"+f"(d[10]),"+f"(d[11]),"+f"(d[12]),"+f"(d[13]),"+f"(d[14]),"+f"(d[15]),"+f"(d[16]),"+f"(d[17]),"+f"(d[18]),"+f"(d[19]),"+f"(d[20]),"+f"(d[21]),"+f"(d[22]),"+f"(d[23]),"+f"(d[24]),"+f"(d[25]),"+f"(d[26]),"+f"(d[27]),"+f"(d[28]),"+f"(d[29]),"+f"(d[30]),"+f"(d[31]),"+f"(d[32]),"+f"(d[33]),"+f"(d[34]),"+f"(d[35]),"+f"(d[36]),"+f"(d[37]),"+f"(d[38]),"+f"(d[39]),"+f"(d[40]),"+f"(d[41]),"+f"(d[42]),"+f"(d[43]),"+f"(d[44]),"+f"(d[45]),"+f"(d[46]),"+f"(d[47]),"+f"(d[48]),"+f"(d[49]),"+f"(d[50]),"+f"(d[51]),"+f"(d[52]),"+f"(d[53]),"+f"(d[54]),"+f"(d[55]),"+f"(d[56]),"+f"(d[57]),"+f"(d[58]),"+f"(d[59]),"+f"(d[60]),"+f"(d[61]),"+f"(d[62]),"+f"(d[63])
   : "r"(a[0]), "r"(a[1]), "r"(a[2]), "r"(a[3]), "l"(db), "r"(sd));
}
template<> __device__ __forceinline__ void wgmma_rs<120,0>(float* d, const uint32_t* a, uint64_t db, int sd) {
  asm volatile("{\n.reg .pred p;\nsetp.ne.b32 p, %65, 0;\nwgmma.mma_async.sync.aligned.m64n120k16.f32.bf16.bf16 {%0,%1,%2,%3,%4,%5,%6,%7,%8,%9,%10,%11,%12,%13,%14,%15,%16,%17,%18,%19,%20,%21,%22,%23,%24,%25,%26,%27,%28,%29,%30,%31,%32,%33,%34,%35,%36,%37,%38,%39,%40,%41,%42,%43,%44,%45,%46,%47,%48,%49,%50,%51,%52,%53,%54,%55,%56,%57,%58,%59}, {%60,%61,%62,%63}, %64, p, 1, 1, 0;\n}\n"
   : "+f"(d[0]),"+f"(d[1]),"+f"(d[2]),"+f"(d[3]),"+f"(d[4]),"+f"(d[5]),"+f"(d[6]),"+f"(d[7]),"+f"(d[8]),"+f"(d[9]),"+f"(d[10]),"+f"(d[11]),"+f"(d[12]),"+f"(d[13]),"+f"(d[14]),"+f"(d[15]),"+f"(d[16]),"+f"(d[17]),"+f"(d[18]),"+f"(d[19]),"+f"(d[20]),"+f"(d[21]),"+f"(d[22]),"+f"(d[23]),"+f"(d[24]),"+f"(d[25]),"+f"(d[26]),"+f"(d[27]),"+f"(d[28]),"+f"(d[29]),"+f"(d[30]),"+f"(d[31]),"+f"(d[32]),"+f"(d[33]),"+f"(d[34]),"+f"(d[35]),"+f"(d[36]),"+f"(d[37]),"+f"(d[38]),"+f"(d[39]),"+f"(d[40]),"+f"(d[41]),"+f"(d[42]),"+f"(d[43]),"+f"(d[44]),"+f"(d[45]),"+f"(d[46]),"+f"(d[47]),"+f"(d[48]),"+f"(d[49]),"+f"(d[50]),"+f"(d[51]),"+f"(d[52]),"+f"(d[53]),"+f"(d[54]),"+f"(d[55]),"+f"(d[56]),"+f"(d[57]),"+f"(d[58]),"+f"(d[59])
   : "r"(a[0]), "r"(a[1]), "r"(a[2]), "r"(a[3]), "l"(db), "r"(sd));
}
template<> __device__ __forceinline__ void wgmma_rs<112,0>(float* d, const uint32_t* a, uint64_t db, int sd) {
  asm volatile("{\n.reg .pred p;\nsetp.ne.b32 p, %61, 0;\nwgmma.mma_async.sync.aligned.m64n112k16.f32.bf16.bf16 {%0,%1,%2,%3,%4,%5,%6,%7,%8,%9,%10,%11,%12,%13,%14,%15,%16,%17,%18,%19,%20,%21,%22,%23,%24,%25,%26,%27,%28,%29,%30,%31,%32,%33,%34,%35,%36,%37,%38,%39,%40,%41,%42,%43,%44,%45,%46,%47,%48,%49,%50,%51,%52,%53,%54,%55}, {%56,%57,%58,%59}, %60, p, 1, 1, 0;\n}\n"
   : "+f"(d[0]),"+f"(d[1]),"+f"(d[2]),"+f"(d[3]),"+f"(d[4]),"+f"(d[5]),"+f"(d[6]),"+f"(d[7]),"+f"(d[8]),"+f"(d[9]),"+f"(d[10]),"+f"(d[11]),"+f"(d[12]),"+f"(d[13]),"+f"(d[14]),"+f"(d[15]),"+f"(d[16]),"+f"(d[17]),"+f"(d[18]),"+f"(d[19]),"+f"(d[20]),"+f"(d[21]),"+f"(d[22]),"+f"(d[23]),"+f"(d[24]),"+f"(d[25]),"+f"(d[26]),"+f"(d[27]),"+f"(d[28]),"+f"(d[29]),"+f"(d[30]),"+f"(d[31]),"+f"(d[32]),"+f"(d[33]),"+f"(d[34]),"+f"(d[35]),"+f"(d[36]),"+f"(d[37]),"+f"(d[38]),"+f"(d[39]),"+f"(d[40]),"+f"(d[41]),"+f"(d[42]),"+f"(d[43]),"+f"(d[44]),"+f"(d[45]),"+f"(d[46]),"+f"(d[47]),"+f"(d[48]),"+f"(d[49]),"+f"(d[50]),"+f"(d[51]),"+f"(d[52]),"+f"(d[53]),"+f"(d[54]),"+f"(d[55])
   : "r"(a[0]), "r"(a[1]), "r"(a[2]), "r"(a[3]), "l"(db), "r"(sd));
}
template<> __device__ __forceinline__ void wgmma_rs<104,0>(float* d, const uint32_t* a, uint64_t db, int sd) {
  asm volatile("{\n.reg .pred p;\nsetp.ne.b32 p, %57, 0;\nwgmma.mma_async.sync.aligned.m64n104k16.f32.bf16.bf16 {%0,%1,%2,%3,%4,%5,%6,%7,%8,%9,%10,%11,%12,%13,%14,%15,%16,%17,%18,%19,%20,%21,%22,%23,%24,%25,%26,%27,%28,%29,%30,%31,%32,%33,%34,%35,%36,%37,%38,%39,%40,%41,%42,%43,%44,%45,%46,%47,%48,%49,%50,%51}, {%52,%53,%54,%55}, %56, p, 1, 1, 0;\n}\n"
   : "+f"(d[0]),"+f"(d[1]),"+f"(d[2]),"+f"(d[3]),"+f"(d[4]),"+f"(d[5]),"+f"(d[6]),"+f"(d[7]),"+f"(d[8]),"+f"(d[9]),"+f"(d[10]),"+f"(d[11]),"+f"(d[12]),"+f"(d[13]),"+f"(d[14]),"+f"(d[15]),"+f"(d[16]),"+f"(d[17]),"+f"(d[18]),"+f"(d[19]),"+f"(d[20]),"+f"(d[21]),"+f"(d[22]),"+f"(d[23]),"+f"(d[24]),"+f"(d[25]),"+f"(d[26]),"+f"(d[27]),"+f"(d[28]),"+f"(d[29]),"+f"(d[30]),"+f"(d[31]),"+f"(d[32]),"+f"(d[33]),"+f"(d[34]),"+f"(d[35]),"+f"(d[36]),"+f"(d[37]),"+f"(d[38]),"+f"(d[39]),"+f"(d[40]),"+f"(d[41]),"+f"(d[42]),"+f"(d[43]),"+f"(d[44]),"+f"(d[45]),"+f"(d[46]),"+f"(d[47]),"+f"(d[48]),"+f"(d[49]),"+f"(d[50]),"+f"(d[51])
   : "r"(a[0]), "r"(a[1]), "r"(a[2]), "r"(a[3]), "l"(db), "r"(sd));
}
template<> __device__ __forceinline__ void wgmma_rs<96,0>(float* d, const uint32_t* a, uint64_t db, int sd) {
  asm volatile("{\n.reg .pred p;\nsetp.ne.b32 p, %53, 0;\nwgmma.mma_async.sync.aligned.m64n96k16.f32.bf16.bf16 {%0,%1,%2,%3,%4,%5,%6,%7,%8,%9,%10,%11,%12,%13,%14,%15,%16,%17,%18,%19,%20,%21,%22,%23,%24,%25,%26,%27,%28,%29,%30,%31,%32,%33,%34,%35,%36,%37,%38,%39,%40,%41,%42,%43,%44,%45,%46,%47}, {%48,%49,%50,%51}, %52, p, 1, 1, 0;\n}\n"
   : "+f"(d[0]),"+f"(d[1]),"+f"(d[2]),"+f"(d[3]),"+f"(d[4]),"+f"(d[5]),"+f"(d[6]),"+f"(d[7]),"+f"(d[8]),"+f"(d[9]),"+f"(d[10]),"+f"(d[11]),"+f"(d[12]),"+f"(d[13]),"+f"(d[14]),"+f"(d[15]),"+f"(d[16]),"+f"(d[17]),"+f"(d[18]),"+f"(d[19]),"+f"(d[20]),"+f"(d[21]),"+f"(d[22]),"+f"(d[23]),"+f"(d[24]),"+f"(d[25]),"+f"(d[26]),"+f"(d[27]),"+f"(d[28]),"+f"(d[29]),"+f"(d[30]),"+f"(d[31]),"+f"(d[32]),"+f"(d[33]),"+f"(d[34]),"+f"(d[35]),"+f"(d[36]),"+f"(d[37]),"+f"(d[38]),"+f"(d[39]),"+f"(d[40]),"+f"(d[41]),"+f"(d[42]),"+f"(d[43]),"+f"(d[44]),"+f"(d[45]),"+f"(d[46]),"+f"(d[47])
   : "r"(a[0]), "r"(a[1]), "r"(a[2]), "r"(a[3]), "l"(db), "r"(sd));
}
template<> __device__ __forceinline__ void wgmma_rs<88,0>(float* d, const uint32_t* a, uint64_t db, int sd) {
  asm volatile("{\n.reg .pred p;\nsetp.ne.b32 p, %49, 0;\nwgmma.mma_async.sync.aligned.m64n88k16.f32.bf16.bf16 {%0,%1,%2,%3,%4,%5,%6,%7,%8,%9,%10,%11,%12,%13,%14,%15,%16,%17,%18,%19,%20,%21,%22,%23,%24,%25,%26,%27,%28,%29,%30,%31,%32,%33,%34,%35,%36,%37,%38,%39,%40,%41,%42,%43}, {%44,%45,%46,%47}, %48, p, 1, 1, 0;\n}\n"
   : "+f"(d[0]),"+f"(d[1]),"+f"(d[2]),"+f"(d[3]),"+f"(d[4]),"+f"(d[5]),"+f"(d[6]),"+f"(d[7]),"+f"(d[8]),"+f"(d[9]),"+f"(d[10]),"+f"(d[11]),"+f"(d[12]),"+f"(d[13]),"+f"(d[14]),"+f"(d[15]),"+f"(d[16]),"+f"(d[17]),"+f"(d[18]),"+f"(d[19]),"+f"(d[20]),"+f"(d[21]),"+f"(d[22]),"+f"(d[23]),"+f"(d[24]),"+f"(d[25]),"+f"(d[26]),"+f"(d[27]),"+f"(d[28]),"+f"(d[29]),"+f"(d[30]),"+f"(d[31]),"+f"(d[32]),"+f"(d[33]),"+f"(d[34]),"+f"(d[35]),"+f"(d[36]),"+f"(d[37]),"+f"(d[38]),"+f"(d[39]),"+f"(d[40]),"+f"(d[41]),"+f"(d[42]),"+f"(d[43])
   : "r"(a[0]), "r"(a[1]), "r"(a[2]), "r"(a[3]), "l"(db), "r"(sd));
}
template<> __device__ __forceinline__ void wgmma_rs<80,0>(float* d, const uint32_t* a, uint64_t db, int sd) {
  asm volatile("{\n.reg .pred p;\nsetp.ne.b32 p, %45, 0;\nwgmma.mma_async.sync.aligned.m64n80k16.f32.bf16.bf16 {%0,%1,%2,%3,%4,%5,%6,%7,%8,%9,%10,%11,%12,%13,%14,%15,%16,%17,%18,%19,%20,%21,%22,%23,%24,%25,%26,%27,%28,%29,%30,%31,%32,%33,%34,%35,%36,%37,%38,%39}, {%40,%41,%42,%43}, %44, p, 1, 1, 0;\n}\n"
   : "+f"(d[0]),"+f"(d[1]),"+f"(d[2]),"+f"(d[3]),"+f"(d[4]),"+f"(d[5]),"+f"(d[6]),"+f"(d[7]),"+f"(d[8]),"+f"(d[9]),"+f"(d[10]),"+f"(d[11]),"+f"(d[12]),"+f"(d[13]),"+f"(d[14]),"+f"(d[15]),"+f"(d[16]),"+f"(d[17]),"+f"(d[18]),"+f"(d[19]),"+f"(d[20]),"+f"(d[21]),"+f"(d[22]),"+f"(d[23]),"+f"(d[24]),"+f"(d[25]),"+f"(d[26]),"+f"(d[27]),"+f"(d[28]),"+f"(d[29]),"+f"(d[30]),"+f"(d[31]),"+f"(d[32]),"+f"(d[33]),"+f"(d[34]),"+f"(d[35]),"+f"(d[36]),"+f"(d[37]),"+f"(d[38]),"+f"(d[39])
   : "r"(a[0]), "r"(a[1]), "r"(a[2]), "r"(a[3]), "l"(db), "r"(sd));
}
template<> __device__ __forceinline__ void wgmma_rs<72,0>(float* d, const uint32_t* a, uint64_t db, int sd) {
  asm volatile("{\n.reg .pred p;\nsetp.ne.b32 p, %41, 0;\nwgmma.mma_async.sync.aligned.m64n72k16.f32.bf16.bf16 {%0,%1,%2,%3,%4,%5,%6,%7,%8,%9,%10,%11,%12,%13,%14,%15,%16,%17,%18,%19,%20,%21,%22,%23,%24,%25,%26,%27,%28,%29,%30,%31,%32,%33,%34,%35}, {%36,%37,%38,%39}, %40, p, 1, 1, 0;\n}\n"
   : "+f"(d[0]),"+f"(d[1]),"+f"(d[2]),"+f"(d[3]),"+f"(d[4]),"+f"(d[5]),"+f"(d[6]),"+f"(d[7]),"+f"(d[8]),"+f"(d[9]),"+f"(d[10]),"+f"(d[11]),"+f"(d[12]),"+f"(d[13]),"+f"(d[14]),"+f"(d[15]),"+f"(d[16]),"+f"(d[17]),"+f"(d[18]),"+f"(d[19]),"+f"(d[20]),"+f"(d[21]),"+f"(d[22]),"+f"(d[23]),"+f"(d[24]),"+f"(d[25]),"+f"(d[26]),"+f"(d[27]),"+f"(d[28]),"+f"(d[29]),"+f"(d[30]),"+f"(d[31]),"+f"(d[32]),"+f"(d[33]),"+f"(d[34]),"+f"(d[35])
   : "r"(a[0]), "r"(a[1]), "r"(a[2]), "r"(a[3]), "l"(db), "r"(sd));
}
template<> __device__ __forceinline__ void wgmma_rs<64,0>(float* d, const uint32_t* a, uint64_t db, int sd) {
  asm volatile("{\n.reg .pred p;\nsetp.ne.b32 p, %37, 0;\nwgmma.mma_async.sync.aligned.m64n64k16.f32.bf16.bf16 {%0,%1,%2,%3,%4,%5,%6,%7,%8,%9,%10,%11,%12,%13,%14,%15,%16,%17,%18,%19,%20,%21,%22,%23,%24,%25,%26,%27,%28,%29,%30,%31}, {%32,%33,%34,%35}, %36, p, 1, 1, 0;\n}\n"
   : "+f"(d[0]),"+f"(d[1]),"+f"(d[2]),"+f"(d[3]),"+f"(d[4]),"+f"(d[5]),"+f"(d[6]),"+f"(d[7]),"+f"(d[8]),"+f"(d[9]),"+f"(d[10]),"+f"(d[11]),"+f"(d[12]),"+f"(d[13]),"+f"(d[14]),"+f"(d[15]),"+f"(d[16]),"+f"(d[17]),"+f"(d[18]),"+f"(d[19]),"+f"(d[20]),"+f"(d[21]),"+f"(d[22]),"+f"(d[23]),"+f"(d[24]),"+f"(d[25]),"+f"(d[26]),"+f"(d[27]),"+f"(d[28]),"+f"(d[29]),"+f"(d[30]),"+f"(d[31])
   : "r"(a[0]), "r"(a[1]), "r"(a[2]), "r"(a[3]), "l"(db), "r"(sd));
}
template<> __device__ __forceinline__ void wgmma_ss<64,0,1>(float* d, uint64_t da, uint64_t db, int sd) {
  asm volatile("{\n.reg .pred p;\nsetp.ne.b32 p, %34, 0;\nwgmma.mma_async.sync.aligned.m64n64k16.f32.bf16.bf16 {%0,%1,%2,%3,%4,%5,%6,%7,%8,%9,%10,%11,%12,%13,%14,%15,%16,%17,%18,%19,%20,%21,%22,%23,%24,%25,%26,%27,%28,%29,%30,%31}, %32, %33, p, 1, 1, 0, 1;\n}\n"
   : "+f"(d[0]),"+f"(d[1]),"+f"(d[2]),"+f"(d[3]),"+f"(d[4]),"+f"(d[5]),"+f"(d[6]),"+f"(d[7]),"+f"(d[8]),"+f"(d[9]),"+f"(d[10]),"+f"(d[11]),"+f"(d[12]),"+f"(d[13]),"+f"(d[14]),"+f"(d[15]),"+f"(d[16]),"+f"(d[17]),"+f"(d[18]),"+f"(d[19]),"+f"(d[20]),"+f"(d[21]),"+f"(d[22]),"+f"(d[23]),"+f"(d[24]),"+f"(d[25]),"+f"(d[26]),"+f"(d[27]),"+f"(d[28]),"+f"(d[29]),"+f"(d[30]),"+f"(d[31])
   : "l"(da), "l"(db), "r"(sd));
}
template<> __device__ __forceinline__ void wgmma_ss<64,1,1>(float* d, uint64_t da, uint64_t db, int sd) {
  asm volatile("{\n.reg .pred p;\nsetp.ne.b32 p, %34, 0;\nwgmma.mma_async.sync.aligned.m64n64k16.f32.bf16.bf16 {%0,%1,%2,%3,%4,%5,%6,%7,%8,%9,%10,%11,%12,%13,%14,%15,%16,%17,%18,%19,%20,%21,%22,%23,%24,%25,%26,%27,%28,%29,%30,%31}, %32, %33, p, 1, 1, 1, 1;\n}\n"
   : "+f"(d[0]),"+f"(d[1]),"+f"(d[2]),"+f"(d[3]),"+f"(d[4]),"+f"(d[5]),"+f"(d[6]),"+f"(d[7]),"+f"(d[8]),"+f"(d[9]),"+f"(d[10]),"+f"(d[11]),"+f"(d[12]),"+f"(d[13]),"+f"(d[14]),"+f"(d[15]),"+f"(d[16]),"+f"(d[17]),"+f"(d[18]),"+f"(d[19]),"+f"(d[20]),"+f"(d[21]),"+f"(d[22]),"+f"(d[23]),"+f"(d[24]),"+f"(d[25]),"+f"(d[26]),"+f"(d[27]),"+f"(d[28]),"+f"(d[29]),"+f"(d[30]),"+f"(d[31])
   : "l"(da), "l"(db), "r"(sd));
}
template<> __device__ __forceinline__ void wgmma_ss<192,0,1>(float* d, uint64_t da, uint64_t db, int sd) {
  asm volatile("{\n.reg .pred p;\nsetp.ne.b32 p, %98, 0;\nwgmma.mma_async.sync.aligned.m64n192k16.f32.bf16.bf16 {%0,%1,%2,%3,%4,%5,%6,%7,%8,%9,%10,%11,%12,%13,%14,%15,%16,%17,%18,%19,%20,%21,%22,%23,%24,%25,%26,%27,%28,%29,%30,%31,%32,%33,%34,%35,%36,%37,%38,%39,%40,%41,%42,%43,%44,%45,%46,%47,%48,%49,%50,%51,%52,%53,%54,%55,%56,%57,%58,%59,%60,%61,%62,%63,%64,%65,%66,%67,%68,%69,%70,%71,%72,%73,%74,%75,%76,%77,%78,%79,%80,%81,%82,%83,%84,%85,%86,%87,%88,%89,%90,%91,%92,%93,%94,%95}, %96, %97, p, 1, 1, 0, 1;\n}\n"
   : "+f"(d[0]),"+f"(d[1]),"+f"(d[2]),"+f"(d[3]),"+f"(d[4]),"+f"(d[5]),"+f"(d[6]),"+f"(d[7]),"+f"(d[8]),"+f"(d[9]),"+f"(d[10]),"+f"(d[11]),"+f"(d[12]),"+f"(d[13]),"+f"(d[14]),"+f"(d[15]),"+f"(d[16]),"+f"(d[17]),"+f"(d[18]),"+f"(d[19]),"+f"(d[20]),"+f"(d[21]),"+f"(d[22]),"+f"(d[23]),"+f"(d[24]),"+f"(d[25]),"+f"(d[26]),"+f"(d[27]),"+f"(d[28]),"+f"(d[29]),"+f"(d[30]),"+f"(d[31]),"+f"(d[32]),"+f"(d[33]),"+f"(d[34]),"+f"(d[35]),"+f"(d[36]),"+f"(d[37]),"+f"(d[38]),"+f"(d[39]),"+f"(d[40]),"+f"(d[41]),"+f"(d[42]),"+f"(d[43]),"+f"(d[44]),"+f"(d[45]),"+f"(d[46]),"+f"(d[47]),"+f"(d[48]),"+f"(d[49]),"+f"(d[50]),"+f"(d[51]),"+f"(d[52]),"+f"(d[53]),"+f"(d[54]),"+f"(d[55]),"+f"(d[56]),"+f"(d[57]),"+f"(d[58]),"+f"(d[59]),"+f"(d[60]),"+f"(d[61]),"+f"(d[62]),"+f"(d[63]),"+f"(d[64]),"+f"(d[65]),"+f"(d[66]),"+f"(d[67]),"+f"(d[68]),"+f"(d[69]),"+f"(d[70]),"+f"(d[71]),"+f"(d[72]),"+f"(d[73]),"+f"(d[74]),"+f"(d[75]),"+f"(d[76]),"+f"(d[77]),"+f"(d[78]),"+f"(d[79]),"+f"(d[80]),"+f"(d[81]),"+f"(d[82]),"+f"(d[83]),"+f"(d[84]),"+f"(d[85]),"+f"(d[86]),"+f"(d[87]),"+f"(d[88]),"+f"(d[89]),"+f"(d[90]),"+f"(d[91]),"+f"(d[92]),"+f"(d[93]),"+f"(d[94]),"+f"(d[95])
   : "l"(da), "l"(db), "r"(sd));
}
template<> __device__ __forceinline__ void wgmma_ss<192,1,1>(float* d, uint64_t da, uint64_t db, int sd) {
  asm volatile("{\n.reg .pred p;\nsetp.ne.b32 p, %98, 0;\nwgmma.mma_async.sync.aligned.m64n192k16.f32.bf16.bf16 {%0,%1,%2,%3,%4,%5,%6,%7,%8,%9,%10,%11,%12,%13,%14,%15,%16,%17,%18,%19,%20,%21,%22,%23,%24,%25,%26,%27,%28,%29,%30,%31,%32,%33,%34,%35,%36,%37,%38,%39,%40,%41,%42,%43,%44,%45,%46,%47,%48,%49,%50,%51,%52,%53,%54,%55,%56,%57,%58,%59,%60,%61,%62,%63,%64,%65,%66,%67,%68,%69,%70,%71,%72,%73,%74,%75,%76,%77,%78,%79,%80,%81,%82,%83,%84,%85,%86,%87,%88,%89,%90,%91,%92,%93,%94,%95}, %96, %97, p, 1, 1, 1, 1;\n}\n"
   : "+f"(d[0]),"+f"(d[1]),"+f"(d[2]),"+f"(d[3]),"+f"(d[4]),"+f"(d[5]),"+f"(d[6]),"+f"(d[7]),"+f"(d[8]),"+f"(d[9]),"+f"(d[10]),"+f"(d[11]),"+f"(d[12]),"+f"(d[13]),"+f"(d[14]),"+f"(d[15]),"+f"(d[16]),"+f"(d[17]),"+f"(d[18]),"+f"(d[19]),"+f"(d[20]),"+f"(d[21]),"+f"(d[22]),"+f"(d[23]),"+f"(d[24]),"+f"(d[25]),"+f"(d[26]),"+f"(d[27]),"+f"(d[28]),"+f"(d[29]),"+f"(d[30]),"+f"(d[31]),"+f"(d[32]),"+f"(d[33]),"+f"(d[34]),"+f"(d[35]),"+f"(d[36]),"+f"(d[37]),"+f"(d[38]),"+f"(d[39]),"+f"(d[40]),"+f"(d[41]),"+f"(d[42]),"+f"(d[43]),"+f"(d[44]),"+f"(d[45]),"+f"(d[46]),"+f"(d[47]),"+f"(d[48]),"+f"(d[49]),"+f"(d[50]),"+f"(d[51]),"+f"(d[52]),"+f"(d[53]),"+f"(d[54]),"+f"(d[55]),"+f"(d[56]),"+f"(d[57]),"+f"(d[58]),"+f"(d[59]),"+f"(d[60]),"+f"(d[61]),"+f"(d[62]),"+f"(d[63]),"+f"(d[64]),"+f"(d[65]),"+f"(d[66]),"+f"(d[67]),"+f"(d[68]),"+f"(d[69]),"+f"(d[70]),"+f"(d[71]),"+f"(d[72]),"+f"(d[73]),"+f"(d[74]),"+f"(d[75]),"+f"(d[76]),"+f"(d[77]),"+f"(d[78]),"+f"(d[79]),"+f"(d[80]),"+f"(d[81]),"+f"(d[82]),"+f"(d[83]),"+f"(d[84]),"+f"(d[85]),"+f"(d[86]),"+f"(d[87]),"+f"(d[88]),"+f"(d[89]),"+f"(d[90]),"+f"(d[91]),"+f"(d[92]),"+f"(d[93]),"+f"(d[94]),"+f"(d[95])
   : "l"(da), "l"(db), "r"(sd));
}

template <bool TR>
__device__ __forceinline__ void gemm_section(float* acc, float& mean0, float& mean1, float& rstd0, float& rstd1,
                                             uint32_t sb, int layer, int rb, int hg, int wg, int w, int lane) {
  const uint32_t bar = sb + SM_BAR;
  const int g = lane >> 2, t = lane & 3;
  const bool leader = (w == 0) && (lane == 0);
  const int row0 = 64 * wg + 16 * w;
  auto issue = [&](int c, int slot) {
    mbar_wait(bar + 8 * (B_XF + c), layer);
    mbar_wait(bar + 8 * (B_KVF + c), layer);
    const uint64_t da = mkdesc(sb + SM_X + c * 16384 + wg * 8192, TR ? 8192 : 16, 1024, 1);
    const uint64_t db = mkdesc(sb + SM_W + slot * 24576, 8192, 1024, 1);
    wg_fence();
#pragma unroll
    for (int ks = 0; ks < 4; ks++) wgmma_ss<192, TR ? 1 : 0, 1>(acc, da + (TR ? ks * 128 : ks * 2), db + ks * 128, (c | ks) != 0);
    wg_commit();
  };
  auto step = [&](int c, int slot) {
    issue(c, slot);
    wg_wait<1>();
    if (leader) mbar_arrive(bar + 8 * (B_KVE + c - 1));
  };
  issue(0, 0);
  if (threadIdx.x == 0) TS(2 + layer * 20 + 0);
  if (threadIdx.x == 128 && layer == 1) TS(60);
  step(1, 1); step(2, 2); step(3, 0);
  issue(4, 1);
  mbar_wait(bar + 8 * B_EP, 0);
  const uint32_t tag = 2 * lds32(sb + SM_EP) + layer + 1;
  {
    mbar_wait(bar + 8 * (B_XF + hg), layer);
    uint32_t A[16];
    const uint32_t xb = sb + SM_X + hg * 16384 + wg * 8192;
#pragma unroll
    for (int ks = 0; ks < 4; ks++) {
      if (!TR) {
        const int row = 16 * w + (lane & 15), kc = 2 * ks + (lane >> 4);
        ldsm4(&A[4 * ks], xb + row * 128 + ((kc ^ (row & 7)) << 4));
      } else {
        const int k = 16 * ks + (lane & 7) + 8 * (lane >> 4), pc = 2 * w + ((lane >> 3) & 1);
        ldsm4t(&A[4 * ks], xb + k * 128 + ((pc ^ (k & 7)) << 4));
      }
    }
    float s0 = 0.f, q0 = 0.f, s1 = 0.f, q1 = 0.f;
#pragma unroll
    for (int i = 0; i < 16; i += 2) {
      const float a = bf_lo(A[i]), b = bf_hi(A[i]), c_ = bf_lo(A[i + 1]), d = bf_hi(A[i + 1]);
      s0 += a + b; q0 = fmaf(a, a, q0); q0 = fmaf(b, b, q0);
      s1 += c_ + d; q1 = fmaf(c_, c_, q1); q1 = fmaf(d, d, q1);
    }
#pragma unroll
    for (int o = 1; o <= 2; o <<= 1) {
      s0 += __shfl_xor_sync(~0u, s0, o); q0 += __shfl_xor_sync(~0u, q0, o);
      s1 += __shfl_xor_sync(~0u, s1, o); q1 += __shfl_xor_sync(~0u, q1, o);
    }
    if (t < 2)
      st_tagged(&g_part[(rb * 8 + hg) * 128 + row0 + g + 8 * t], __float_as_uint(t ? s1 : s0), __float_as_uint(t ? q1 : q0), tag);
  }
  wg_wait<1>();
  if (leader) mbar_arrive(bar + 8 * (B_KVE + 3));
  step(5, 2);
  issue(6, 0);
  wg_wait<1>();
  const uint4* psrc = &g_part[(rb * 8 + 2 * t) * 128 + row0 + g];
  uint4 a0 = ld_tagged(psrc), a1 = ld_tagged(psrc + 8), b0 = ld_tagged(psrc + 128), b1 = ld_tagged(psrc + 136);
  if (wg == 0) bar_sync(5, 256);
  issue(7, 1);
  if (wg == 1) bar_arrive(5, 256);
  int it = 0;
  while (!__all_sync(~0u, a0.y == tag && a0.w == tag && a1.y == tag && a1.w == tag && b0.y == tag && b0.w == tag && b1.y == tag && b1.w == tag) &&
         ++it < (1 << 20)) {
    a0 = ld_tagged(psrc); a1 = ld_tagged(psrc + 8); b0 = ld_tagged(psrc + 128); b1 = ld_tagged(psrc + 136);
  }
  float s0 = __uint_as_float(a0.x) + __uint_as_float(b0.x), q0 = __uint_as_float(a0.z) + __uint_as_float(b0.z);
  float s1 = __uint_as_float(a1.x) + __uint_as_float(b1.x), q1 = __uint_as_float(a1.z) + __uint_as_float(b1.z);
#pragma unroll
  for (int o = 1; o <= 2; o <<= 1) {
    s0 += __shfl_xor_sync(~0u, s0, o); q0 += __shfl_xor_sync(~0u, q0, o);
    s1 += __shfl_xor_sync(~0u, s1, o); q1 += __shfl_xor_sync(~0u, q1, o);
  }
  mean0 = s0 * (1.f / DM); mean1 = s1 * (1.f / DM);
  rstd0 = rsqrt_approx(fmaxf(q0 * (1.f / DM) - mean0 * mean0, 0.f) + 1e-5f);
  rstd1 = rsqrt_approx(fmaxf(q1 * (1.f / DM) - mean1 * mean1, 0.f) + 1e-5f);
  mbar_wait(bar + 8 * B_CSF, 0);
  wg_wait<0>();
}

__device__ __forceinline__ void attn_phase(const Params& p, uint32_t sb, int layer, int rb, int hg, int wg, int w) {
  const int lane = opaque_tid() & 31;
  const int g = lane >> 2, t = lane & 3;
  const uint32_t bar = sb + SM_BAR;
  const int row0 = 64 * wg + 16 * w;
  const bool leader = (w == 0) && (lane == 0);
  float acc[96];
  float2 cs[24];
  float mean0, mean1, rstd0, rstd1;
  if (layer) gemm_section<true>(acc, mean0, mean1, rstd0, rstd1, sb, layer, rb, hg, wg, w, lane);
  else gemm_section<false>(acc, mean0, mean1, rstd0, rstd1, sb, layer, rb, hg, wg, w, lane);
  const uint32_t tag = 2 * lds32(sb + SM_EP) + layer + 1;
  if (threadIdx.x == 0) TS(2 + layer * 20 + 1);
  if (leader) mbar_arrive(bar + 8 * B_QDONE);
#pragma unroll
  for (int j = 8; j < 24; j++) cs[j] = lds64f(sb + SM_CS + 4 * (8 * j + 2 * t));

  uint32_t kb[4][8], vb[4][8], qa[4][4];
  {
    const float nm0 = -mean0 * rstd0, nm1 = -mean1 * rstd1;
    const int st_row = row0 + (lane & 7) + 8 * ((lane >> 3) & 1);
    const uint32_t st_base = sb + SM_KVX + st_row * 256;
    const bool sender = (wg == 1 && w == 3 && rb < 15);
    uint4* halo = &g_halo[(rb * 8 + hg) * 384 + lane];
    if (wg == 0 && w == 3) bar_sync(6, 64);
    uint32_t r[4][2][4];
#pragma unroll
    for (int h = 0; h < 4; h++) {
#pragma unroll
      for (int kv = 0; kv < 2; kv++) {
#pragma unroll
        for (int dh = 0; dh < 2; dh++) {
          const int j = 8 + kv * 8 + 2 * h + dh;
          const float2 c2 = cs[j];
          const float v0 = fmaf(acc[4 * j + 0], rstd0, nm0 * c2.x), v1 = fmaf(acc[4 * j + 1], rstd0, nm0 * c2.y);
          const float v2 = fmaf(acc[4 * j + 2], rstd1, nm1 * c2.x), v3 = fmaf(acc[4 * j + 3], rstd1, nm1 * c2.y);
          r[h][kv][2 * dh] = packbf(v0, v1);
          r[h][kv][2 * dh + 1] = packbf(v2, v3);
        }
      }
      if (sender) {
        st_tagged3(halo + (3 * h) * 32, r[h][0][0], r[h][0][1], r[h][0][2], tag);
        st_tagged3(halo + (3 * h + 1) * 32, r[h][0][3], r[h][1][0], r[h][1][1], tag);
        st_tagged3(halo + (3 * h + 2) * 32, r[h][1][2], r[h][1][3], 0u, tag);
      }
    }
    if (wg == 1 && w == 3) bar_arrive(6, 64);
    if (layer == 1 && threadIdx.x == 224) TS(47);
#pragma unroll
    for (int j = 0; j < 8; j++) cs[j] = lds64f(sb + SM_CS + 4 * (8 * j + 2 * t));
    mbar_wait(bar + 8 * B_QDONE, layer);
#pragma unroll
    for (int h = 0; h < 4; h++) {
#pragma unroll
      for (int kv = 0; kv < 2; kv++) {
        const int chunk = 4 * h + 2 * kv + (lane >> 4);
        stsm4(st_base + (((chunk & 8) | ((chunk ^ st_row) & 7)) << 4), r[h][kv][0], r[h][kv][1], r[h][kv][2], r[h][kv][3]);
      }
      kb[h][4] = r[h][0][0]; kb[h][5] = r[h][0][2]; kb[h][6] = r[h][0][1]; kb[h][7] = r[h][0][3];
      vb[h][4] = movm_t(r[h][1][0]); vb[h][5] = movm_t(r[h][1][1]); vb[h][6] = movm_t(r[h][1][2]); vb[h][7] = movm_t(r[h][1][3]);
    }
    if (layer == 1 && threadIdx.x == 0) TS(45);
#pragma unroll
    for (int h = 0; h < 4; h++) {
#pragma unroll
      for (int dh = 0; dh < 2; dh++) {
        const int j = 2 * h + dh;
        const float2 c2 = cs[j];
        qa[h][2 * dh] = packbf(fmaf(-mean0, c2.x, acc[4 * j + 0]), fmaf(-mean0, c2.y, acc[4 * j + 1]));
        qa[h][2 * dh + 1] = packbf(fmaf(-mean1, c2.x, acc[4 * j + 2]), fmaf(-mean1, c2.y, acc[4 * j + 3]));
      }
    }
  }
  bar_sync(1, 256);
  if (threadIdx.x == 0) TS(2 + layer * 20 + 2);
  {
    const uint32_t own_base = sb + SM_KVX + row0 * 256;
    const int mi = lane >> 3;
    const int r = 8 * (mi >> 1) + (lane & 7), r2 = 8 * (mi & 1) + (lane & 7);
    if (row0 != 0) {
#pragma unroll
      for (int h = 0; h < 4; h++) {
        const int ch = 4 * h + (mi & 1), ch2 = 4 * h + 2 + (mi >> 1);
        ldsm4(&kb[h][0], own_base - 16 * 256 + r * 256 + (((ch & 8) | ((ch ^ r) & 7)) << 4));
        ldsm4t(&vb[h][0], own_base - 16 * 256 + r2 * 256 + (((ch2 & 8) | ((ch2 ^ r2) & 7)) << 4));
      }
    } else if (rb > 0) {
      const uint4* src = &g_halo[((rb - 1) * 8 + hg) * 384 + lane];
      uint4 hv[12];
      int it = 0;
      bool ok;
      do {
        ok = true;
#pragma unroll
        for (int i = 0; i < 12; i++) hv[i] = ld_tagged(src + i * 32);
#pragma unroll
        for (int i = 0; i < 12; i++) ok = ok && hv[i].w == tag;
      } while (!__all_sync(~0u, ok) && ++it < (1 << 20));
      if (lane == 0) mbar_arrive(bar + 8 * B_HF);
#pragma unroll
      for (int h = 0; h < 4; h++) {
        kb[h][0] = hv[3 * h].x; kb[h][1] = hv[3 * h].z; kb[h][2] = hv[3 * h].y; kb[h][3] = hv[3 * h + 1].x;
        vb[h][0] = movm_t(hv[3 * h + 1].y); vb[h][1] = movm_t(hv[3 * h + 1].z);
        vb[h][2] = movm_t(hv[3 * h + 2].x); vb[h][3] = movm_t(hv[3 * h + 2].y);
      }
    } else {
#pragma unroll
      for (int h = 0; h < 4; h++)
#pragma unroll
        for (int k = 0; k < 4; k++) kb[h][k] = vb[h][k] = 0u;
    }
    if (threadIdx.x == 0) TS(2 + layer * 20 + 4);
  }

  const bool first = (rb == 0 && wg == 0 && w == 0);
  const int e = t - (g >> 1);
  const bool par = g & 1, epos = e >= 1;
  const uint32_t pmask = par ? 0xffff0000u : 0x0000ffffu;
  const uint32_t mB0 = epos ? pmask : 0u, mB1 = epos ? 0u : pmask;
  const float cl2 = 0.25f * 1.4426950408889634f;
  const float sc0 = rstd0 * cl2, sc1 = rstd1 * cl2;
  const float NEG = -INFINITY;
  float vA0[4], vB0[4], vA1[4], vB1[4];
#pragma unroll
  for (int h = 0; h < 4; h++) {
    float S[4][4];
#pragma unroll
    for (int j = 0; j < 4; j++) {
      S[j][0] = S[j][1] = S[j][2] = S[j][3] = 0.f;
      mma_bf16(S[j], qa[h], kb[h][2 * j], kb[h][2 * j + 1]);
    }
    vA0[h] = par ? S[1][1] : S[1][0];
    vB0[h] = epos ? (par ? S[0][1] : S[0][0]) : (par ? S[2][1] : S[2][0]);
    vA1[h] = par ? S[2][3] : S[2][2];
    vB1[h] = epos ? (par ? S[1][3] : S[1][2]) : (par ? S[3][3] : S[3][2]);
    if (first) { vA0[h] = NEG; if (epos) { vB0[h] = NEG; vB1[h] = NEG; } }
  }
  float m0[4], m1[4];
#pragma unroll
  for (int h = 0; h < 4; h++) { m0[h] = fmaxf(vA0[h], vB0[h]); m1[h] = fmaxf(vA1[h], vB1[h]); }
#pragma unroll
  for (int o = 1; o <= 2; o <<= 1) {
#pragma unroll
    for (int h = 0; h < 4; h++) {
      m0[h] = fmaxf(m0[h], __shfl_xor_sync(~0u, m0[h], o));
      m1[h] = fmaxf(m1[h], __shfl_xor_sync(~0u, m1[h], o));
    }
  }
  float O0[4][4], O1[4][4], Z[4][4];
#pragma unroll
  for (int h = 0; h < 4; h++) {
    const float mm0 = -m0[h] * sc0, mm1 = -m1[h] * sc1;
    const float pA0 = ex2(fmaf(vA0[h], sc0, mm0)), pB0 = ex2(fmaf(vB0[h], sc0, mm0));
    const float pA1 = ex2(fmaf(vA1[h], sc1, mm1)), pB1 = ex2(fmaf(vB1[h], sc1, mm1));
    const uint32_t hA0 = packbf(pA0, pA0), hB0 = packbf(pB0, pB0), hA1 = packbf(pA1, pA1), hB1 = packbf(pB1, pB1);
    const uint32_t P0[4] = {hB0 & mB0, 0u, hA0 & pmask, hB1 & mB0};
    const uint32_t P1[4] = {hB0 & mB1, hA1 & pmask, 0u, hB1 & mB1};
#pragma unroll
    for (int k = 0; k < 4; k++) O0[h][k] = O1[h][k] = Z[h][k] = 0.f;
    mma_bf16(O0[h], P0, vb[h][0], vb[h][1]); mma_bf16(O1[h], P0, vb[h][2], vb[h][3]); mma_bf16(Z[h], P0, 0x3f803f80u, 0x3f803f80u);
    mma_bf16(O0[h], P1, vb[h][4], vb[h][5]); mma_bf16(O1[h], P1, vb[h][6], vb[h][7]); mma_bf16(Z[h], P1, 0x3f803f80u, 0x3f803f80u);
  }
  const uint32_t ob = sb + SM_OST + wg * 8192;
  const int o_row = 16 * w + (lane & 7) + 8 * ((lane >> 3) & 1);
#pragma unroll
  for (int h = 0; h < 4; h++) {
    const float i0 = rcp_approx(Z[h][0]), i1 = rcp_approx(Z[h][2]);
    const int ch = 2 * h + (lane >> 4);
    stsm4(ob + o_row * 128 + ((ch ^ (o_row & 7)) << 4), packbf(O0[h][0] * i0, O0[h][1] * i0), packbf(O0[h][2] * i1, O0[h][3] * i1),
          packbf(O1[h][0] * i0, O1[h][1] * i0), packbf(O1[h][2] * i1, O1[h][3] * i1));
  }
  if (threadIdx.x == 0) TS(2 + layer * 20 + 5);
  fence_async_smem();
  bar_sync(2 + wg, 128);
  if (w == 0 && elect_one()) {
    tma_st(&p.mapO, hg * 64, rb * 128 + wg * 64, ob);
    bulk_commit();
    mbar_arrive(bar + 8 * B_AD);
    bulk_wait_all();
    red_relaxed(&g_cnt[(C_O + rb) * 32]);
    mbar_arrive(bar + 8 * B_OST);
    if (threadIdx.x == 0) TS(2 + layer * 20 + 6);
  }
}

__device__ __forceinline__ void proj_phase(const Params& p, uint32_t sb, int layer, int rb, int q, int wg, int w) {
  const int lane = opaque_tid() & 31;
  const bool TR = layer != 0;
  const int t = lane & 3;
  const uint32_t bar = sb + SM_BAR;
  const uint32_t rbx = sb + SM_R + wg * 8192;
  uint32_t res[16];
  mbar_wait(bar + 8 * B_RF, layer);
  if (threadIdx.x == 0) TS(2 + layer * 20 + 7);
  if (!TR) {
#pragma unroll
    for (int j = 0; j < 8; j += 2) {
      const int mi = lane >> 3;
      const int row = 16 * w + (lane & 7) + 8 * (mi & 1), ch = j + (mi >> 1);
      ldsm4(&res[2 * j], rbx + row * 128 + ((ch ^ (row & 7)) << 4));
    }
  } else {
#pragma unroll
    for (int j = 0; j < 8; j += 2) {
      const int mi = lane >> 3;
      const int line = 8 * (j + (mi >> 1)) + (lane & 7), pc = 2 * w + (mi & 1);
      ldsm4t(&res[2 * j], rbx + line * 128 + ((pc ^ (line & 7)) << 4));
    }
  }
  bar_sync(2 + wg, 128);
  float acc[32];
#pragma unroll
  for (int i = 0; i < 32; i++) acc[i] = 0.f;
#pragma unroll 1
  for (int c = 0; c < 8; c++) {
    if ((c & 1) == 0) mbar_wait(bar + 8 * (B_WOF + (c >> 1)), layer);
    mbar_wait(bar + 8 * (B_OF + c), layer);
    if (c == 0 && threadIdx.x == 0) TS(2 + layer * 20 + 8);
    const uint64_t da = mkdesc(sb + (c < 4 ? SM_X + 65536 + c * 16384 : SM_W + (c - 4) * 16384) + wg * 8192, 16, 1024, 1);
    const uint64_t db = mkdesc(sb + SM_X + c * 8192, 8192, 1024, 1);
    wg_fence();
#pragma unroll
    for (int ks = 0; ks < 4; ks++) wgmma_ss<64, 0, 1>(acc, da + ks * 2, db + ks * 128, 1);
    wg_commit();
  }
  wg_wait<0>();
  if (threadIdx.x == 0) TS(2 + layer * 20 + 9);
  if (lane == 0 && w == 0) mbar_arrive(bar + 8 * B_PDONE);
  float s0 = 0.f, q0 = 0.f, s1 = 0.f, q1 = 0.f;
  uint32_t o[16];
#pragma unroll
  for (int j = 0; j < 8; j++) {
    const uint32_t r0 = res[2 * j], r1 = res[2 * j + 1];
    o[2 * j] = packbf(acc[4 * j] + bf_lo(r0), acc[4 * j + 1] + bf_hi(r0));
    o[2 * j + 1] = packbf(acc[4 * j + 2] + bf_lo(r1), acc[4 * j + 3] + bf_hi(r1));
    const float a = bf_lo(o[2 * j]), b = bf_hi(o[2 * j]), c = bf_lo(o[2 * j + 1]), d = bf_hi(o[2 * j + 1]);
    s0 += a + b; q0 = fmaf(a, a, q0); q0 = fmaf(b, b, q0);
    s1 += c + d; q1 = fmaf(c, c, q1); q1 = fmaf(d, d, q1);
  }
#pragma unroll
  for (int j = 0; j < 8; j += 2) {
    const int mi = lane >> 3;
    const int line = 8 * (j + (mi >> 1)) + (lane & 7), pc = 2 * w + (mi & 1);
    stsm4t(rbx + line * 128 + ((pc ^ (line & 7)) << 4), o[2 * j], o[2 * j + 1], o[2 * j + 2], o[2 * j + 3]);
  }
#pragma unroll
  for (int o2 = 1; o2 <= 2; o2 <<= 1) {
    s0 += __shfl_xor_sync(~0u, s0, o2); q0 += __shfl_xor_sync(~0u, q0, o2);
    s1 += __shfl_xor_sync(~0u, s1, o2); q1 += __shfl_xor_sync(~0u, q1, o2);
  }
  const uint32_t stg = sb + SM_HALO + wg * 512;
  {
    const int row = 16 * w + (lane >> 2) + 8 * (t >> 1);
    const float v = (t == 0) ? s0 : (t == 1) ? q0 : (t == 2) ? s1 : q1;
    sts32f(stg + 4 * (((((row & 7) >> 1) * 8 + (row >> 3)) << 2) + (row & 1) * 2 + (t & 1)), v);
  }
  fence_async_smem();
  bar_sync(2 + wg, 128);
  if (w == 0 && elect_one()) {
    mbar_wait(bar + 8 * B_ZF, 0);
    tma_st(&p.mapXT, rb * 128 + wg * 64, (2 * layer) * DM + q * 64, rbx);
    bulk_red_add_f32(g_stats + layer * LSEQ * 2 + (rb * 2 + wg) * 128, stg, 512);
    bulk_commit();
    bulk_wait_all();
    red_relaxed(&g_cnt[(layer ? C_G2 : C_G0) * 32]);
    if (threadIdx.x == 0) TS(2 + layer * 20 + 10);
  }
}

__device__ __forceinline__ void conv_load(uint32_t* A, uint32_t pe) {
#pragma unroll
  for (int m = 0; m < 17; m++) {
    A[4 * m + 2] = lds32(pe + 4 * (64 * m - 8));
    A[4 * m + 0] = lds32(pe + 4 * (64 * m));
    A[4 * m + 1] = lds32(pe + 4 * (64 * m + 8));
  }
#pragma unroll
  for (int m = 0; m < 17; m++) asm volatile("mov.b32 %0, %1;" : "=r"(A[4 * m + 3]) : "r"(A[4 * m + 0]));
}
template <int M> __device__ __forceinline__ void conv_mma(float* acc, const uint32_t* A, uint64_t d) {
  wgmma_rs<128 - 8 * (M / 2), 0>(acc, A + 4 * M, d + (uint64_t)(4 * M), M != 0);
}
template <int M0, int M1> __device__ __forceinline__ void conv_mmas(float* acc, const uint32_t* A, uint64_t d) {
  if constexpr (M0 < M1) { conv_mma<M0>(acc, A, d); conv_mmas<M0 + 1, M1>(acc, A, d); }
}
__device__ __forceinline__ void conv_sums(uint32_t sb, int lc, int c, uint4 own) {
  const int m = c == 127 ? -1 : c;
  if (c == 127) own = make_uint4(0, 0, 0, 0);
  const uint32_t up = m >= 1 ? ((m - 1) & 1) * CV_UH + (127 - ((m - 1) >> 1)) * 16 + 8 : 128 * 16;
  const uint32_t un = ((m + 1) & 1) * CV_UH + (127 - ((m + 1) >> 1)) * 16;
  const bool odd = c & 1;
  const float2 v0 = lds64f(sb + cv_u(lc) + (odd ? un : up)), v1 = lds64f(sb + cv_u(lc) + (odd ? up : un));
  const uint32_t x[8] = {__float_as_uint(odd ? v1.x : v0.x), __float_as_uint(odd ? v1.y : v0.y), own.x, own.y, own.z, own.w,
                         __float_as_uint(odd ? v0.x : v1.x), __float_as_uint(odd ? v0.y : v1.y)};
  float pv[16];
#pragma unroll
  for (int k = 0; k < 8; k++) { pv[2 * k] = bf_lo(x[k]); pv[2 * k + 1] = bf_hi(x[k]); }
  float sf[8], pf[8], s9[8], s7[8];
  sf[7] = pv[7]; pf[0] = pv[8];
#pragma unroll
  for (int i = 6; i >= 0; i--) sf[i] = sf[i + 1] + pv[i];
#pragma unroll
  for (int i = 1; i < 8; i++) pf[i] = pf[i - 1] + pv[8 + i];
#pragma unroll
  for (int i = 0; i < 8; i++) {
    s9[i] = sf[i] + pf[i];
    s7[i] = i == 0 ? sf[1] : i == 7 ? pf[6] : sf[i + 1] + pf[i - 1];
  }
  const int ce = (m + 2) & 127, co = m + 1;
  uint4 e4 = make_uint4(packbf(s9[0], s9[1]), packbf(s9[2], s9[3]), packbf(s9[4], s9[5]), packbf(s9[6], s9[7]));
  if (ce == 0) e4 = make_uint4(0, 0, 0, 0);
  sts128(sb + cv_s(lc) + ((ce >> 3) & 1) * 1024 + (ce >> 4) * 128 + (((ce ^ (ce >> 4)) & 7) << 4), e4);
  sts128(sb + cv_s(lc) + 2048 + ((co >> 3) & 1) * 1024 + (co >> 4) * 128 + (((co ^ (co >> 4)) & 7) << 4),
         make_uint4(packbf(s7[0], s7[1]), packbf(s7[2], s7[3]), packbf(s7[4], s7[5]), packbf(s7[6], s7[7])));
}

__device__ __forceinline__ void conv_epi(uint32_t sb, int layer, int cta, int ch, int c0) {
  uint4 v[2][4], xr[2];
#pragma unroll
  for (int u = 0; u < 2; u++) xr[u] = ldcg128(g_xT + (size_t)(2 * layer * DM + cv_chan(cta, ch)) * LSEQ + (c0 + 128 * u) * 8);
  mbar_wait(sb + SM_BAR + 8 * (B_P + ch), layer);
#pragma unroll
  for (int u = 0; u < 2; u++) {
    const int c = c0 + 128 * u;
    const uint32_t pb = sb + cv_pb(ch) + (c ^ ((c >> 3) & 1)) * 16;
#pragma unroll
    for (int k = 0; k < 4; k++) v[u][k] = lds128(pb + k * CV_PBW);
  }
#pragma unroll
  for (int u = 0; u < 2; u++) {
    uint4 o;
    o.x = hadd2(xr[u].x, hadd2(hadd2(v[u][0].x, v[u][1].x), hadd2(v[u][2].x, v[u][3].x)));
    o.y = hadd2(xr[u].y, hadd2(hadd2(v[u][0].y, v[u][1].y), hadd2(v[u][2].y, v[u][3].y)));
    o.z = hadd2(xr[u].z, hadd2(hadd2(v[u][0].z, v[u][1].z), hadd2(v[u][2].z, v[u][3].z)));
    o.w = hadd2(xr[u].w, hadd2(hadd2(v[u][0].w, v[u][1].w), hadd2(v[u][2].w, v[u][3].w)));
    sts128(sb + cv_s(ch) + (c0 + 128 * u) * 16, o);
  }
}
__device__ __forceinline__ void warp_release(uint32_t b) {
  fence_async_smem();
  __syncwarp();
  if (elect_one()) mbar_arrive(b);
}

__device__ __forceinline__ void conv_prep(uint32_t sb, int layer, int cta, int c, uint4 (&un)[4]) {
  const uint32_t bar = sb + SM_BAR;
  const bf16* xin = g_xT + (size_t)(2 * layer) * DM * LSEQ;
  uint4 xr[4], st[4];
  mbar_wait(bar + 8 * B_GB, layer);
  if (threadIdx.x == 0) TS(2 + layer * 20 + 11);
#pragma unroll
  for (int i = 0; i < 4; i++) st[i] = ldcg128(g_stats + layer * LSEQ * 2 + ((c >> 3) * 4 + i) * 32 + (c & 7) * 4);
#pragma unroll
  for (int i = 0; i < 4; i++) xr[i] = ldcg128(xin + (size_t)cv_chan(cta, i) * LSEQ + c * 8);
  float nm[8], rstd[8];
#pragma unroll
  for (int i = 0; i < 4; i++) {
    const float m0 = __uint_as_float(st[i].x) * (1.f / DM), m1 = __uint_as_float(st[i].z) * (1.f / DM);
    rstd[2 * i] = rsqrt_approx(fmaxf(fmaf(__uint_as_float(st[i].y), 1.f / DM, -m0 * m0), 0.f) + 1e-5f);
    rstd[2 * i + 1] = rsqrt_approx(fmaxf(fmaf(__uint_as_float(st[i].w), 1.f / DM, -m1 * m1), 0.f) + 1e-5f);
    nm[2 * i] = -m0 * rstd[2 * i]; nm[2 * i + 1] = -m1 * rstd[2 * i + 1];
  }
  if (threadIdx.x == 0) TS(2 + layer * 20 + 12);
  const int a = c >> 1, h = c & 1;
#pragma unroll
  for (int i = 0; i < 4; i++) {
    const uint32_t x[4] = {xr[i].x, xr[i].y, xr[i].z, xr[i].w};
    uint32_t u[4];
#pragma unroll
    for (int k = 0; k < 4; k++)
      u[k] = packbf(fmaf(bf_lo(x[k]), rstd[2 * k], nm[2 * k]), fmaf(bf_hi(x[k]), rstd[2 * k + 1], nm[2 * k + 1]));
    un[i] = make_uint4(u[0], u[1], u[2], u[3]);
    sts128(sb + cv_u(i) + h * CV_UH + (127 - a) * 16, un[i]);
    warp_release(bar + 8 * (B_U + i));
  }
}
__device__ __forceinline__ void conv_zero(uint32_t sb, int ht) {
  if (ht < 96) {
    const int ch = ht / 24, h2 = (ht / 12) & 1, qq = ht % 12;
    sts128(sb + cv_u(ch) + h2 * CV_UH + (128 + qq) * 16, make_uint4(0, 0, 0, 0));
  }
  if (ht >= 80) {
    const int i = ht - 80, ch = i / 12, q2 = i % 12;
    const int w2 = q2 < 2 ? 1 : q2 < 6 ? 2 : 3, cc = q2 < 2 ? q2 : q2 < 6 ? q2 - 2 : q2 - 6;
    sts128(sb + cv_pb(ch) + w2 * CV_PBW + cc * 16, make_uint4(0, 0, 0, 0));
  }
}

#define HANDOVER 1
#define A_FIRST 0
__device__ __forceinline__ void conv_phase(const Params& p, uint32_t sb, int layer, int cta) {
  const int tid = opaque_tid();
  const int wg = __shfl_sync(~0u, tid >> 7, 0), w = __shfl_sync(~0u, (tid >> 5) & 3, 0);
  const uint32_t bar = sb + SM_BAR;
  uint32_t A[68];
  mbar_wait(bar + 8 * B_PE, layer);
  conv_load(A, sb + cv_pe(1 - wg) + 4 * (16 + 16 * w + ((tid & 31) >> 2) - 2 * (tid & 3)));
  if (wg == 0) {
    uint4 un[4];
    conv_prep(sb, layer, cta, opaque_tid() + 128, un);
  }
#pragma unroll 1
  for (int r = 0; r < 2; r++) {
    const int ch = 2 * r + 1 - wg;
    float acc[64];
    const uint64_t d = mkdesc(sb + cv_u(ch), CV_UH, 128, 0);
    const bool leader = (opaque_tid() & 127) == 0;
    FTS(39);
    mbar_wait(bar + 8 * (B_U + ch), layer);
    if (ch > 0) mbar_wait(bar + 8 * (B_T + ch - 1), layer);
    FTS(41);
    if (ch == 0 && threadIdx.x == 128) TS(2 + layer * 20 + 13);
    wg_fence();
    conv_mma<0>(acc, A, d);
    conv_mmas<2, 17>(acc, A, d);
    wg_commit();
    FTS(51);
    mbar_wait(bar + 8 * (B_S + ch), layer);
    if (HANDOVER == 0) mbar_arrive_if(bar + 8 * (B_T + ch), leader);
    wg_fence();
    conv_mma<1>(acc, A, d);
    if (HANDOVER == 1) mbar_arrive_if(bar + 8 * (B_T + ch), leader);
    wgmma_ss<64, 1, 1>(acc, mkdesc(sb + cv_s(ch), 1024, 1024, 1), mkdesc(sb + cv_ft(ch), 256, 16, 0), 1);
    if (HANDOVER == 2) mbar_arrive_if(bar + 8 * (B_T + ch), leader);
    wgmma_ss<64, 1, 1>(acc, mkdesc(sb + cv_s(ch) + 2048, 1024, 1024, 1), mkdesc(sb + cv_ft(ch) + 512, 256, 16, 0), 1);
    wg_commit();
    if (HANDOVER == 3) mbar_arrive_if(bar + 8 * (B_T + ch), leader);
    FTS(61);
    wg_wait<0>();
    const int l2 = opaque_tid() & 31;
    if (A_FIRST && r == 0) conv_load(A, sb + cv_pe(3 - wg) + 4 * (16 + 16 * w + (l2 >> 2) - 2 * (l2 & 3)));
    FTS(20);
    const uint32_t pb = sb + cv_pb(ch) + w * CV_PBW;
#pragma unroll
    for (int j = 0; j < 16; j += 2) {
      const int mt = l2 >> 3;
      const int a = 127 - (8 * (j + (mt >> 1)) + (l2 & 7));
      int c = 2 * (a + w) + (mt & 1);
      c ^= (c >> 3) & 1;
      stsm4t(pb + c * 16, packbf(acc[4 * j], acc[4 * j + 1]), packbf(acc[4 * j + 2], acc[4 * j + 3]),
             packbf(acc[4 * j + 4], acc[4 * j + 5]), packbf(acc[4 * j + 6], acc[4 * j + 7]));
    }
    __syncwarp();
    if (elect_one()) mbar_arrive(bar + 8 * (B_P + ch));
    if (threadIdx.x == 0) TS(2 + layer * 20 + 14 + r);
    FTS(57);
    if (!A_FIRST && r == 0) conv_load(A, sb + cv_pe(3 - wg) + 4 * (16 + 16 * w + (l2 >> 2) - 2 * (l2 & 3)));
  }
  if (wg == 1 && layer == 0) mbar_wait(bar + 8 * (B_T + 3), layer);
}

__device__ __forceinline__ void final_phase(const Params& p, uint32_t sb, int cta, int wg, int w) {
  if (wg == 1 && w == 3) return;
  const int lane = opaque_tid() & 31, g = lane >> 2, t = lane & 3;
  const int lc = wg ? w : 3;
  const int pos0 = (cta & 31) * 64, ch0 = 128 * lc + (cta >> 5) * 32;
  const bf16* src = g_xT + (size_t)(3 * DM + ch0 + 8 * (g >> 1) + (g & 1)) * LSEQ + pos0;
  bf16* dst = p.out + (size_t)pos0 * DM + ch0 + 8 * t;
  spin_until(&g_cnt[(C_F + (cta >> 5)) * 32 + lc], (lds32(sb + SM_EP) + 1) * 32);
  if (wg == 0) {
    if (threadIdx.x == 0) TS(42);
    uint2 v[4];
#pragma unroll
    for (int q = 0; q < 4; q++)
      asm volatile("ld.global.cg.v2.b32 {%0,%1}, [%2];" : "=r"(v[q].x), "=r"(v[q].y) : "l"(src + 2 * q * LSEQ + 16 * w + 4 * t) : "memory");
    dst += (16 * w + 4 * (g >> 1) + (g & 1)) * DM;
    *(uint4*)dst = make_uint4(movm_t(v[0].x), movm_t(v[1].x), movm_t(v[2].x), movm_t(v[3].x));
    *(uint4*)(dst + 2 * DM) = make_uint4(movm_t(v[0].y), movm_t(v[1].y), movm_t(v[2].y), movm_t(v[3].y));
  } else {
    uint4 v[2][4];
#pragma unroll
    for (int h = 0; h < 2; h++)
#pragma unroll
      for (int q = 0; q < 4; q++) v[h][q] = ldcg128(src + 2 * q * LSEQ + 32 * h + 8 * t);
    dst += (8 * (g >> 1) + (g & 1)) * DM;
#pragma unroll
    for (int h = 0; h < 2; h++) {
      *(uint4*)(dst + (32 * h + 0) * DM) = make_uint4(movm_t(v[h][0].x), movm_t(v[h][1].x), movm_t(v[h][2].x), movm_t(v[h][3].x));
      *(uint4*)(dst + (32 * h + 2) * DM) = make_uint4(movm_t(v[h][0].y), movm_t(v[h][1].y), movm_t(v[h][2].y), movm_t(v[h][3].y));
      *(uint4*)(dst + (32 * h + 4) * DM) = make_uint4(movm_t(v[h][0].z), movm_t(v[h][1].z), movm_t(v[h][2].z), movm_t(v[h][3].z));
      *(uint4*)(dst + (32 * h + 6) * DM) = make_uint4(movm_t(v[h][0].w), movm_t(v[h][1].w), movm_t(v[h][2].w), movm_t(v[h][3].w));
    }
  }
  if (threadIdx.x == 0) TS(43);
  if (threadIdx.x == 192) TS(63);
  if (threadIdx.x == 0) LTS(1);
}

struct cplx { float r, i; };
__device__ __forceinline__ cplx cmul(cplx a, cplx b) { return {fmaf(a.r, b.r, -a.i * b.i), fmaf(a.r, b.i, a.i * b.r)}; }
__device__ __forceinline__ cplx csqr(cplx a) { return {fmaf(a.r, a.r, -a.i * a.i), (a.r + a.r) * a.i}; }
__device__ __forceinline__ cplx cexp_l(float ar2, float ai, float l) {
  const float m = ex2(ar2 * l);
  const float x = ai * l;
  return {m * __cosf(x), m * __sinf(x)};
}

__device__ __forceinline__ void colsum_publish(uint32_t sb, int rb, int hg, int ht, uint32_t tag) {
  const int lane = ht & 31, q = lane & 15, h = lane >> 4;
  const uint32_t src = sb + SM_CW + (ht >> 5) * 4096 + h * 128 + (q & 1) * 8;
  float s[4] = {0.f, 0.f, 0.f, 0.f};
#pragma unroll
  for (int r = 0; r < 16; r++) {
    const float2 v = lds64f(src + r * 256 + (((q >> 1) ^ ((2 * r + h) & 7)) << 4));
    s[0] += bf_lo(__float_as_uint(v.x)); s[1] += bf_hi(__float_as_uint(v.x));
    s[2] += bf_lo(__float_as_uint(v.y)); s[3] += bf_hi(__float_as_uint(v.y));
  }
#pragma unroll
  for (int k = 0; k < 4; k++) s[k] += __shfl_xor_sync(~0u, s[k], 16);
  if (h == 0)
    st_tagged3(&g_colsum[(hg * 16 + rb) * 48 + (ht >> 5) * 16 + q], (__float_as_uint(s[0]) & ~7u) | tag, __float_as_uint(s[1]),
               __float_as_uint(s[2]), __float_as_uint(s[3]));
}
__device__ __forceinline__ void colsum_gather(uint32_t sb, int hg, int ht, uint32_t tag) {
  const int lane = ht & 31, rec = (ht >> 5) * 16 + (lane & 15);
  const uint4* src = &g_colsum[(hg * 16 + (lane >> 4) * 8) * 48 + rec];
  uint4 v[8];
  bool ok;
  int it = 0;
  do {
    ok = true;
#pragma unroll
    for (int i = 0; i < 8; i++) v[i] = ld_tagged(src + i * 48);
#pragma unroll
    for (int i = 0; i < 8; i++) ok = ok && (v[i].x & 7u) == tag;
    if (++it > (1 << 22)) __trap();
  } while (!__all_sync(~0u, ok));
  float s[4] = {0.f, 0.f, 0.f, 0.f};
#pragma unroll
  for (int i = 0; i < 8; i++) {
    s[0] += __uint_as_float(v[i].x & ~7u); s[1] += __uint_as_float(v[i].y); s[2] += __uint_as_float(v[i].z); s[3] += __uint_as_float(v[i].w);
  }
#pragma unroll
  for (int k = 0; k < 4; k++) s[k] += __shfl_xor_sync(~0u, s[k], 16);
  if (lane < 16) sts128f(sb + SM_CS + rec * 16, s[0], s[1], s[2], s[3]);
}

__device__ __forceinline__ uint32_t packh(float lo, float hi) { uint32_t r; asm("cvt.rn.f16x2.f32 %0, %1, %2;" : "=r"(r) : "f"(hi), "f"(lo)); return r; }
__device__ __forceinline__ void mma_f16(float* d, uint32_t a0, uint32_t a1, uint32_t a2, uint32_t a3, uint32_t b0, uint32_t b1) {
  asm volatile("mma.sync.aligned.m16n8k16.row.col.f32.f16.f16.f32 {%0,%1,%2,%3}, {%4,%5,%6,%7}, {%8,%9}, {%0,%1,%2,%3};"
      : "+f"(d[0]), "+f"(d[1]), "+f"(d[2]), "+f"(d[3]) : "r"(a0), "r"(a1), "r"(a2), "r"(a3), "r"(b0), "r"(b1));
}
struct HSeed { uint32_t r, i; };
__device__ __forceinline__ HSeed hseed(cplx s) { return {packh(s.r, s.r), packh(s.i, s.i)}; }
__device__ __forceinline__ void hcmul(uint32_t& o_r, uint32_t& o_i, uint32_t br, uint32_t bi, HSeed s) {
  asm("{\n.reg .b32 t, u;\nmul.rn.f16x2 t, %3, %5;\nneg.f16x2 t, t;\nmul.rn.f16x2 u, %3, %4;\nfma.rn.f16x2 %0, %2, %4, t;\nfma.rn.f16x2 %1, %2, %5, u;\n}"
      : "=&r"(o_r), "=&r"(o_i) : "r"(br), "r"(bi), "r"(s.r), "r"(s.i));
}
struct HTile { uint32_t r[4], i[4]; };
__device__ __forceinline__ void tile_set(HTile& t, int k, cplx a, cplx b) { t.r[k] = packh(a.r, b.r); t.i[k] = packh(a.i, b.i); }
__device__ __forceinline__ void tile_upper(HTile& t, HSeed s) { hcmul(t.r[2], t.i[2], t.r[0], t.i[0], s); hcmul(t.r[3], t.i[3], t.r[1], t.i[1], s); }
__device__ __forceinline__ HTile tile_shift(const HTile& t, HSeed s) {
  HTile o;
#pragma unroll
  for (int k = 0; k < 4; k++) hcmul(o.r[k], o.i[k], t.r[k], t.i[k], s);
  return o;
}
__device__ __forceinline__ void tile_put(const HTile& t, uint32_t a) {
  sts128(a, make_uint4(t.r[0], t.r[1], t.r[2], t.r[3]));
  sts128(a + 512, make_uint4(t.i[0], t.i[1], t.i[2], t.i[3]));
}
__device__ __forceinline__ HTile tile_get(uint32_t a) { HTile o; ldsm4t(o.r, a); ldsm4t(o.i, a + 512); return o; }
__device__ __forceinline__ void tile_mma(float* T, const HTile& a0, const HTile& a1, const HTile& b) {
  mma_f16(T, a0.r[0], a0.r[1], a0.r[2], a0.r[3], b.r[0], b.r[1]);
  mma_f16(T, a0.i[0], a0.i[1], a0.i[2], a0.i[3], b.i[0], b.i[1]);
  mma_f16(T, a1.r[0], a1.r[1], a1.r[2], a1.r[3], b.r[2], b.r[3]);
  mma_f16(T, a1.i[0], a1.i[1], a1.i[2], a1.i[3], b.i[2], b.i[3]);
}
__device__ __forceinline__ void tile_mma2(float* T, float* U, const HTile& a0, const HTile& a1, const HTile& b, const HTile& c) {
  mma_f16(T, a0.r[0], a0.r[1], a0.r[2], a0.r[3], b.r[0], b.r[1]);
  mma_f16(U, a0.r[0], a0.r[1], a0.r[2], a0.r[3], c.r[0], c.r[1]);
  mma_f16(T, a0.i[0], a0.i[1], a0.i[2], a0.i[3], b.i[0], b.i[1]);
  mma_f16(U, a0.i[0], a0.i[1], a0.i[2], a0.i[3], c.i[0], c.i[1]);
  mma_f16(T, a1.r[0], a1.r[1], a1.r[2], a1.r[3], b.r[2], b.r[3]);
  mma_f16(U, a1.r[0], a1.r[1], a1.r[2], a1.r[3], c.r[2], c.r[3]);
  mma_f16(T, a1.i[0], a1.i[1], a1.i[2], a1.i[3], b.i[2], b.i[3]);
  mma_f16(U, a1.i[0], a1.i[1], a1.i[2], a1.i[3], c.i[2], c.i[3]);
}
__device__ __forceinline__ void kgen_unit(uint32_t tab, uint32_t taba, float ar2, float ai, cplx c, float (&T)[5][4]) {
  const cplx z1 = cexp_l(ar2, ai, 1.f), z16 = cexp_l(ar2, ai, 16.f), z256 = cexp_l(ar2, ai, 256.f);
  HTile a0, a1, b0, b1;
  {
    const cplx y1 = {z16.r, -z16.i}, y2 = csqr(y1), y3 = cmul(y2, y1), y4 = csqr(y2), y5 = cmul(y4, y1), y6 = csqr(y3), y7 = cmul(y4, y3);
    HTile t;
    tile_set(t, 0, {1.f, 0.f}, y1); tile_set(t, 1, y2, y3); tile_set(t, 2, y4, y5); tile_set(t, 3, y6, y7);
    const HTile u = tile_shift(t, hseed(csqr(y4)));
    __syncwarp();
    tile_put(t, tab); tile_put(u, tab + 1024);
    __syncwarp();
    a0 = tile_get(taba); a1 = tile_get(taba + 256);
  }
  const cplx z2 = csqr(z1), z4 = csqr(z2), z8 = csqr(z4);
  const HSeed h8 = hseed(z8);
  const cplx d = cmul(c, z256), e = cmul(d, z256);
  {
    const cplx z512 = csqr(z256), f = cmul(e, z512), f8 = cmul(f, z8), f16 = cmul(f, z16), e4 = cmul(e, z4);
    HTile t, u;
    tile_set(t, 0, e4, cmul(e, z8)); tile_set(t, 1, cmul(e4, z8), cmul(e, z16));
    tile_upper(t, hseed(z256));
    tile_set(u, 0, f8, f16); tile_set(u, 1, cmul(f8, z256), cmul(f16, z256));
    tile_upper(u, hseed(z512));
    __syncwarp();
    tile_put(t, tab); tile_put(u, tab + 1024);
    __syncwarp();
    b0 = tile_get(tab); b1 = tile_get(tab + 1024);
  }
  {
    const cplx d2 = cmul(d, z2), d4 = cmul(d, z4);
    HTile t;
    tile_set(t, 0, d2, d4); tile_set(t, 1, cmul(d2, z4), cmul(d, z8));
    tile_upper(t, h8);
    __syncwarp();
    tile_put(t, tab);
    __syncwarp();
    tile_mma2(T[3], T[4], a0, a1, b0, b1);
    b0 = tile_get(tab);
  }
  {
    const cplx c1 = cmul(c, z1), c2 = cmul(c, z2), c3 = cmul(c1, z2), c4 = cmul(c, z4);
    HTile t;
    tile_set(t, 0, c1, c2); tile_set(t, 1, c3, c4); tile_set(t, 2, cmul(c1, z4), cmul(c2, z4)); tile_set(t, 3, cmul(c3, z4), cmul(c4, z4));
    const HTile u = tile_shift(t, h8);
    __syncwarp();
    tile_put(t, tab); tile_put(u, tab + 1024);
    __syncwarp();
    tile_mma(T[2], a0, a1, b0);
    b0 = tile_get(tab); b1 = tile_get(tab + 1024);
    tile_mma2(T[0], T[1], a0, a1, b0, b1);
  }
}
struct ModeIn { uint2 ar, ai, br, bi, cr, ci; };
__device__ __forceinline__ ModeIn load_modes(const Params& p, int idx) {
  return {*(const uint2*)(p.a_re + idx), *(const uint2*)(p.a_im + idx), *(const uint2*)(p.b_re + idx),
          *(const uint2*)(p.b_im + idx), *(const uint2*)(p.c_re + idx), *(const uint2*)(p.c_im + idx)};
}
__device__ __forceinline__ float bf_el(uint2 v, int k) { const uint32_t x = (k & 2) ? v.y : v.x; return (k & 1) ? bf_hi(x) : bf_lo(x); }
struct KGen { float4 cur; float T[5][4]; };
__device__ __forceinline__ uint32_t kgen_slot(uint32_t sb, int ht, int u) {
  return sb + (u < 3 ? SM_KC + (ht >> 5) * (KC_STRIDE * 2) + (u - 1) * 512 + (ht & 31) * 16 + 16 : SM_HALO + 1024 + ht * 16);
}
__device__ __forceinline__ void kgen_setup(KGen& s, uint32_t sb, int cta, int ht, const ModeIn& in, bf16 logdt, bf16 dskip) {
  const float dt = __bfloat162float(__float2bfloat16_rn(expf(__bfloat162float(logdt))));
  float mx = 0.f, k0 = 0.f, ar2[4];
  cplx c[4];
#pragma unroll
  for (int k = 0; k < 4; k++) {
    ar2[k] = (dt * bf_el(in.ar, k)) * 1.4426950408889634f;
    c[k] = cmul({bf_el(in.cr, k), bf_el(in.ci, k)}, {dt * bf_el(in.br, k), dt * bf_el(in.bi, k)});
    k0 += c[k].r;
    mx = fmaxf(mx, fmaxf(fabsf(c[k].r), fabsf(c[k].i)) * ex2(fmaxf(ar2[k] * 2048.f, 0.f)));
  }
  const int ex = min(max(267 - (int)(__reduce_max_sync(~0u, __float_as_uint(mx)) >> 23), 1), 253);
  const float sc = __uint_as_float(ex << 23);
#pragma unroll
  for (int o = 16; o > 0; o >>= 1) k0 += __shfl_xor_sync(~0u, k0, o);
  if ((ht & 31) == 0) {
    const uint32_t kc = sb + SM_KC + (ht >> 5) * (KC_STRIDE * 2);
    sts16(kc, __bfloat16_as_ushort(__float2bfloat16_rn(k0 + __bfloat162float(dskip))));
    sts16(kc + 641 * 2, 0);
    sts32f(kc + 644 * 2, __uint_as_float((254 - ex) << 23));
  }
  s.cur = make_float4(ar2[0], dt * bf_el(in.ai, 0), c[0].r * sc, c[0].i * sc);
#pragma unroll
  for (int k = 1; k < 4; k++) sts128f(kgen_slot(sb, ht, k), ar2[k], dt * bf_el(in.ai, k), c[k].r * sc, c[k].i * sc);
#pragma unroll
  for (int i = 0; i < 5; i++) s.T[i][0] = s.T[i][1] = s.T[i][2] = s.T[i][3] = 0.f;
}
__device__ __forceinline__ void kgen_finish(KGen& s, uint32_t sb, int cta, int ht) {
  const int w = ht >> 5, lane = ht & 31, g = lane >> 2, t = lane & 3;
  const uint32_t kc = sb + SM_KC + w * KC_STRIDE * 2;
  __syncwarp();
  const float inv = __uint_as_float(lds32(kc + 644 * 2));
  auto put = [&](int idx, float v) {
    sts16(kc + idx * 2, __bfloat16_as_ushort(__float2bfloat16_rn(v)));
  };
#pragma unroll
  for (int hi = 0; hi < 2; hi++)
#pragma unroll
    for (int lo = 0; lo < 2; lo++) {
      const int i = g + 8 * hi, j = 2 * t + lo, e = 2 * hi + lo;
      put(16 * i + 1 + j, s.T[0][e] * inv);
      put(16 * i + 9 + j, s.T[1][e] * inv);
      put(257 + 8 * i + j, s.T[2][e] * inv);
      put(385 + 4 * i + (j & 3) + 64 * (j >> 2), s.T[3][e] * inv);
      put(513 + 2 * i + lo + 32 * t, s.T[4][e] * inv);
    }
}

__device__ __forceinline__ void expand_taps(uint32_t sb, int ht) {
  const int ch = ht >> 5, lane = ht & 31;
  const uint32_t kc = sb + SM_KC + ch * KC_STRIDE * 2;
  const uint32_t dst0 = sb + cv_pe(ch);
  auto put = [&](int G, uint32_t v0, uint32_t v1, uint32_t v2, uint32_t v3, uint32_t v4, uint32_t v5, uint32_t v6, uint32_t v7, uint32_t v8) {
    const uint32_t dst = dst0 + G * 32;
    sts128(dst, make_uint4(v1 | (v0 << 16), v2 | (v1 << 16), v3 | (v2 << 16), v4 | (v3 << 16)));
    sts128(dst + 16, make_uint4(v5 | (v4 << 16), v6 | (v5 << 16), v7 | (v6 << 16), v8 | (v7 << 16)));
  };
  {
    const uint4 q = lds128(kc + lane * 16);
    const uint32_t pv = lane ? lds16(kc + lane * 16 - 2) : 0u;
    const uint32_t dst = dst0 + (lane + 2) * 32;
    sts128(dst, make_uint4(__byte_perm(q.x, pv, 0x5410), __byte_perm(q.x, q.x, 0x1032), __byte_perm(q.y, q.x, 0x7610), __byte_perm(q.y, q.y, 0x1032)));
    sts128(dst + 16, make_uint4(__byte_perm(q.z, q.y, 0x7610), __byte_perm(q.z, q.z, 0x1032), __byte_perm(q.w, q.z, 0x7610), __byte_perm(q.w, q.w, 0x1032)));
    if (lane < 4) sts128(dst0 + lane * 16, make_uint4(0, 0, 0, 0));
  }
  uint32_t a[5], b[2][3], fv[4];
  {
    const uint32_t s1 = kc + 2 * (256 + 4 * lane);
#pragma unroll
    for (int k = 0; k < 5; k++) a[k] = lds16(s1 + 2 * k);
#pragma unroll
    for (int u = 0; u < 2; u++) {
      const uint32_t s2 = kc + 2 * (384 + 2 * (lane + 32 * u));
#pragma unroll
      for (int k = 0; k < 3; k++) b[u][k] = lds16(s2 + 2 * k);
    }
#pragma unroll
    for (int k = 0; k < 4; k++) fv[k] = lds16(kc + 2 * (640 - 4 * lane - k));
  }
  const uint32_t k255 = lds16(kc + 2 * 255), k1024 = lds16(kc + 2 * 512);
  put(34 + lane, lane == 0 ? k255 : a[0], a[0], a[0], a[1], a[2], a[2], a[2], a[3], a[4]);
#pragma unroll
  for (int u = 0; u < 2; u++) put(66 + lane + 32 * u, b[u][0], b[u][0], b[u][0], b[u][0], b[u][1], b[u][1], b[u][1], b[u][2], b[u][2]);
  if (lane < 10) {
    const uint32_t v = lane == 0 ? k1024 : 0u;
    put(130 + lane, v, v, v, v, v, v, 0u, 0u, 0u);
  }
  const uint32_t ft = sb + cv_ft(ch) + 4 * lane;
#pragma unroll
  for (int ty = 0; ty < 2; ty++) {
    const uint32_t v = fv[ty] | (fv[ty + 2] << 16);
    sts32f(ft + ty * 512, __uint_as_float(v));
    sts32f(ft + ty * 512 + 128, 0.f);
    sts32f(ft + ty * 512 + 256 + (lane < 2 ? 120 : -8), __uint_as_float(lane < 2 ? 0u : v));
    sts32f(ft + ty * 512 + 384, 0.f);
  }
}

template <bool SMID> __device__ __forceinline__ int role_id() {
  uint32_t v;
  if (!SMID) { asm volatile("mov.u32 %0, %%ctaid.x;" : "=r"(v)); return v; }
  asm volatile("mov.u32 %0, %%smid;" : "=r"(v));
  const int tp = v >> 1, q = ((tp - 32) * 37) >> 8;
  const int r = tp < 32 ? (tp & 7) * 8 + (tp >> 3) : tp < 60 ? (tp - 31 - 7 * q) * 8 + 4 + q : tp < 62 ? tp + 4 : tp - 58;
  return __shfl_sync(~0u, 2 * r + (v & 1), 0);
}
__device__ __forceinline__ int role_rb(int cta) { return ((cta >> 4) & 3) * 4 + ((cta >> 2) & 3); }
__device__ __forceinline__ int role_hg(int cta) { return (cta >> 6) * 4 + (cta & 3); }
__device__ __forceinline__ int role_rb2(int cta) { return cta >> 3; }
__device__ __forceinline__ int role_q2(int cta) { return cta & 7; }

template <bool SMID> __global__ void __launch_bounds__(NTHREADS, 1) fused_kernel(const __grid_constant__ Params p) {
  extern __shared__ __align__(1024) uint8_t smem[];
  const uint32_t sb = s32(smem);
  const int tid = threadIdx.x, lane = tid & 31;
  const int warp = __shfl_sync(~0u, tid >> 5, 0);
  constexpr unsigned NARR = SMID ? 132 : NCTA;
  const uint32_t bar = sb + SM_BAR;
  if (tid == 0) TS(0);
  const int cta0 = role_id<SMID>();
  if (warp == 0 && (!SMID || cta0 < NCTA) && elect_one()) {
    const int rb = role_rb(cta0), hg = role_hg(cta0);
    mbar_init(bar + 8 * B_XF, 1); mbar_init(bar + 8 * B_KVF, 1);
    fence_async_smem();
#pragma unroll
    for (int c = 0; c < 8; c++) {
      mbar_expect(bar + 8 * (B_XF + c), 16384);
      tma_ld(sb + SM_X + c * 16384, &p.mapX128, c * 64, rb * 128, bar + 8 * (B_XF + c));
      if (c < 3) {
        mbar_expect(bar + 8 * (B_KVF + c), 24576);
        tma_ld3(sb + SM_W + c * 24576, &p.mapW3, hg * 64, c * 64, 0, bar + 8 * (B_KVF + c));
      }
      if (c == 0) {
#pragma unroll
        for (int i = 1; i < 8; i++) mbar_init(bar + 8 * (B_XF + i), 1);
        mbar_init(bar + 8 * (B_KVF + 1), 1); mbar_init(bar + 8 * (B_KVF + 2), 1); mbar_init(bar + 8 * B_CW, 1);
        fence_async_smem();
      }
      if (c == PF_AT) {
        mbar_expect(bar + 8 * B_CW, 12288);
        tma_ld3(sb + SM_CW, &p.mapW3h, hg * 64, rb * 32, 0, bar + 8 * B_CW);
      }
    }
    TS(56);
  }
  if (SMID && cta0 >= NCTA) {
    if (tid == 0) spin_until(&g_cnt[C_CS * 32], (atomicAdd(&g_cnt[C_CS * 32], 1u) / NARR + 1) * NARR);
    return;
  }
  if (warp >= 1 && warp < 5 && elect_one()) {
#pragma unroll
    for (int q = 0; q < 4; q++) {
      if (warp == q + 1) {
#pragma unroll
        for (int i = 17 * q; i < 17 * q + 17; i++) {
          if (i < B_KVF + 3 || i == B_CW) continue;
          int cnt = 1;
          if ((i >= B_KVE && i < B_KVE + 5) || i == B_QDONE || i == B_PDONE || i == B_OST || i == B_AD) cnt = 2;
          if (i == B_Z0) cnt = 128;
          if (i == B_CSF) cnt = 3;
          if (i >= B_U && i < B_U + 4) cnt = 8;
          if ((i >= B_S && i < B_S + 4) || (i >= B_E && i < B_E + 4) || i >= B_P || i == B_PE) cnt = 4;
          mbar_init(bar + 8 * i, cnt);
        }
      }
    }
    fence_async_smem();
  }

  if (warp < 8) {
    bar_sync(0, NTHREADS);
    if (tid == 0) TS(1);
    asm volatile("setmaxnreg.inc.sync.aligned.u32 %0;" ::"n"(R_CONS));
    const int cw = __shfl_sync(~0u, opaque_tid() >> 5, 0);
    const int wg = cw >> 2, w = cw & 3;
    const int cta = role_id<SMID>();
    if (tid == 0) TS(54);
#pragma unroll 1
    for (int layer = 0; layer < 2; layer++) {
      attn_phase(p, sb, layer, role_rb(cta), role_hg(cta), wg, w);
      if (p.stop == 1 + 3 * layer) return;
      proj_phase(p, sb, layer, role_rb2(cta), role_q2(cta), wg, w);
      if (p.stop == 2 + 3 * layer) return;
      conv_phase(p, sb, layer, cta);
      if (p.stop == 3 + 3 * layer) return;
    }
    final_phase(p, sb, cta, wg, w);
  } else if (warp < 12) {
    asm volatile("setmaxnreg.dec.sync.aligned.u32 %0;" ::"n"(R_HELP));
    const int ht = tid - 256;
    const int cta = role_id<SMID>(), rb = role_rb(cta), hg = role_hg(cta);
    unsigned ep0 = 0;
    if (ht == 0) ep0 = ld_relaxed(&g_cnt[C_CS * 32]);
    bar_sync(0, NTHREADS);
    if (ht == 0) {
      asm volatile("st.shared.u32 [%0], %1;" ::"r"(sb + SM_EP), "r"(ep0 / NARR) : "memory");
      mbar_arrive(bar + 8 * B_EP);
    }
    if (hg == 0) {
      *(float4*)(g_stats + (ht >> 6) * LSEQ * 2 + rb * 256 + (ht & 63) * 4) = make_float4(0.f, 0.f, 0.f, 0.f);
    }
    mbar_arrive(bar + 8 * B_Z0);
    mbar_wait(bar + 8 * B_EP, 0);
    const uint32_t cs_tag = lds32(sb + SM_EP) % 7 + 1;
    if (ht < 96) {
      mbar_wait(bar + 8 * B_CW, 0);
      colsum_publish(sb, rb, hg, ht, cs_tag);
    }
    if (ht == 0) TS(50);
    {
      KGen kg;
      const uint32_t tab0 = sb + ((ht >> 5) < 2 ? SM_T : SM_T2 - 4096) + (ht >> 5) * 2048;
      const uint32_t tab = tab0 + (ht & 31) * 16, taba = tab0 + ((ht >> 3) & 1) * 1024 + (((ht >> 1) & 8) + (ht & 7)) * 16;
      const int chn = cv_chan(cta, ht >> 5);
      kgen_setup(kg, sb, cta, ht, load_modes(p, chn * 128 + (ht & 31) * 4), p.log_dt[chn], p.dskip[chn]);
      if (ht < 96) {
        mbar_wait(bar + 8 * (B_KVF + CS_AT), 0);
        colsum_gather(sb, hg, ht, cs_tag);
        __syncwarp();
        if (elect_one()) mbar_arrive(bar + 8 * B_CSF);
        if (ht == 0) TS(40);
      }
#pragma unroll 1
      for (int u = 0; u < 4; u++) {
        if (u == KG_PRE) {
          KTS(39);
          mbar_wait(bar + 8 * B_AD, 0);
          KTS(41);
        }
        if (u == 3) mbar_wait(bar + 8 * B_PDONE, 0);
        kgen_unit(tab, taba, kg.cur.x, kg.cur.y, {kg.cur.z, kg.cur.w}, kg.T);
        kg.cur = lds128f(kgen_slot(sb, opaque_tid() - 256, u + 1));
      }
      kgen_finish(kg, sb, cta, opaque_tid() - 256);
    }
    KTS(51);
    bar_sync(4, 128);
#pragma unroll 1
    for (int layer = 0; layer < 2; layer++) {
      if (p.stop <= 1 + 3 * layer) return;
      mbar_wait(bar + 8 * B_PDONE, layer);
      expand_taps(sb, opaque_tid() - 256);
      conv_zero(sb, opaque_tid() - 256);
      if (ht == 0) TS(52 + layer);
      warp_release(bar + 8 * B_PE);
      if (p.stop <= 2 + 3 * layer) return;
      {
        uint4 un[4];
        conv_prep(sb, layer, cta, opaque_tid() - 256, un);
        if (layer == 1 && ht == 0) TS(62);
        bar_sync(4, 128);
#pragma unroll
        for (int lc = 0; lc < 4; lc++) {
          conv_sums(sb, lc, opaque_tid() - 256, un[lc]);
          warp_release(bar + 8 * (B_S + lc));
          if (lc == 0 && layer == 1 && ht == 0) TS(46);
        }
      }
#pragma unroll 1
      for (int lc = 0; lc < 4; lc++) {
        conv_epi(sb, layer, cta, lc, opaque_tid() - 256);
        warp_release(bar + 8 * (B_E + lc));
      }
    }
  } else {
    asm volatile("setmaxnreg.dec.sync.aligned.u32 40;");
    const int cta = role_id<SMID>(), rb = role_rb(cta), hg = role_hg(cta), rb2 = role_rb2(cta), q2 = role_q2(cta);
    bar_sync(0, NTHREADS);
    if (warp == 12) {
      if (elect_one()) {
        unsigned epoch = 0;
#pragma unroll 1
        for (int layer = 0; layer < 2; layer++) {
          auto ld_w = [&](int c, int slot) {
            const uint32_t b = bar + 8 * (B_KVF + c);
            mbar_expect(b, 24576);
            tma_ld3(sb + SM_W + slot * 24576, &p.mapW3, hg * 64, c * 64, 0, b);
          };
          if (layer == 0) {
            TS(55);
            mbar_wait(bar + 8 * (B_KVF + 2), 0);
            if (rb2 < 4) tma_prefetch2(&p.mapWo128, q2 * 64, rb2 * 128);
            asm volatile("prefetch.tensormap [%0];" ::"l"(&p.mapO) : "memory");
            asm volatile("prefetch.tensormap [%0];" ::"l"(&p.mapO128) : "memory");
            asm volatile("prefetch.tensormap [%0];" ::"l"(&p.mapXT) : "memory");
            asm volatile("prefetch.tensormap [%0];" ::"l"(&p.mapXT3) : "memory");
            mbar_wait(bar + 8 * B_EP, 0);
            epoch = lds32(sb + SM_EP);
          } else {
            mbar_wait(bar + 8 * B_PDONE, 0);
            ld_w(0, 0); ld_w(1, 1);
          }
          {
            int slot = 0;
#pragma unroll 1
            for (int c = 3; c < 8; c++) {
              mbar_wait(bar + 8 * (B_KVE + c - 3), layer);
              ld_w(c, slot);
              slot = slot == 2 ? 0 : slot + 1;
            }
          }
          if (p.stop <= 1 + 3 * layer) return;
          mbar_wait(bar + 8 * B_QDONE, layer);
          if (rb > 0) mbar_wait(bar + 8 * B_HF, layer);
#pragma unroll 1
          for (int c = 0; c < 4; c++) {
            const uint32_t b = bar + 8 * (B_WOF + c);
            mbar_expect(b, 16384);
            tma_ld(sb + SM_X + c * 16384, &p.mapWo128, q2 * 64, c * 128, b);
          }
          {
            const uint32_t b = bar + 8 * B_RF;
            mbar_expect(b, 16384);
            if (layer == 0) tma_ld(sb + SM_R, &p.mapX128, q2 * 64, rb2 * 128, b);
            else tma_ld3(sb + SM_R, &p.mapXT3, 0, DM + q2 * 64, rb2 * 2, b);
          }
          spin_until(&g_cnt[(C_O + rb2) * 32], (2 * epoch + layer + 1) * 16);
          mbar_wait(bar + 8 * B_OST, layer);
          fence_async_global();
#pragma unroll 1
          for (int c = 0; c < 8; c++) {
            const uint32_t b = bar + 8 * (B_OF + c);
            mbar_expect(b, 16384);
            tma_ld(sb + (c < 4 ? SM_X + 65536 + c * 16384 : SM_W + (c - 4) * 16384), &p.mapO128, c * 64, rb2 * 128, b);
          }
          if (p.stop <= 3 + 3 * layer) return;
        }
      }
    } else if (warp == 13) {
      if (elect_one() && p.stop > 3) {
        mbar_wait(bar + 8 * B_GB, 0);
        const unsigned target = (lds32(sb + SM_EP) + 1) * NCTA;
#pragma unroll 1
        for (int lc = 0; lc < 4; lc++) {
          spin_until(&g_cnt[C_G1 * 32 + lc], target);
          if (lc == 3) TS(44);
          fence_async_global();
          fence_async_smem();
#pragma unroll
          for (int c = 2 * lc; c < 2 * lc + 2; c++) {
            mbar_expect(bar + 8 * (B_XF + c), 16384);
            tma_ld3(sb + SM_X + c * 16384, &p.mapXT3, 0, DM + c * 64, rb * 2, bar + 8 * (B_XF + c));
            if (c == 2) {
              mbar_expect(bar + 8 * (B_KVF + 2), 24576);
              tma_ld3(sb + SM_W + 2 * 24576, &p.mapW3, hg * 64, 128, 0, bar + 8 * (B_KVF + 2));
            }
          }
        }
      }
    } else if (warp == 15) {
      if (elect_one()) {
#pragma unroll 1
        for (int i = 0; i < 8; i++) {
          const int layer = i >> 2, lc = i & 3;
          if (p.stop <= 2 + 3 * layer) return;
          mbar_wait(bar + 8 * (B_E + lc), layer);
          bulk_st(g_xT + (size_t)((2 * layer + 1) * DM + cv_chan(cta, lc)) * LSEQ, sb + cv_s(lc), 4096);
          bulk_commit();
          bulk_wait_all();
          red_relaxed(&g_cnt[(layer ? C_F + (cta >> 5) : C_G1) * 32 + lc]);
          if (lc == 3) TS(2 + layer * 20 + 16);
        }
      }
    } else if (warp == 14) {
      mbar_wait(bar + 8 * B_EP, 0);
      const unsigned epoch = lds32(sb + SM_EP);
      if (lane == 0) {
        mbar_wait(bar + 8 * B_Z0, 0);
        red_release(&g_cnt[C_CS * 32]);
        spin_until(&g_cnt[C_CS * 32], (epoch + 1) * NARR);
        mbar_arrive(bar + 8 * B_ZF);
#pragma unroll 1
        for (int layer = 0; layer < 2; layer++) {
          if (p.stop <= 1 + 3 * layer) return;
          spin_until(&g_cnt[(layer ? C_G2 : C_G0) * 32], (epoch + 1) * 256);
          mbar_arrive(bar + 8 * B_GB);
        }
      }
    }
  }
}

typedef CUresult (*EncodeFn)(CUtensorMap*, CUtensorMapDataType, cuuint32_t, void*, const cuuint64_t*, const cuuint64_t*,
                             const cuuint32_t*, const cuuint32_t*, CUtensorMapInterleave, CUtensorMapSwizzle,
                             CUtensorMapL2promotion, CUtensorMapFloatOOBfill);

static void make_map(EncodeFn enc, CUtensorMap* m, void* ptr, uint64_t cols, uint64_t rows, uint32_t box_rows) {
  cuuint64_t dims[2] = {cols, rows};
  cuuint64_t strides[1] = {cols * 2};
  cuuint32_t box[2] = {64, box_rows};
  cuuint32_t es[2] = {1, 1};
  enc(m, CU_TENSOR_MAP_DATA_TYPE_BFLOAT16, 2, ptr, dims, strides, box, es, CU_TENSOR_MAP_INTERLEAVE_NONE,
      CU_TENSOR_MAP_SWIZZLE_128B, CU_TENSOR_MAP_L2_PROMOTION_L2_128B, CU_TENSOR_MAP_FLOAT_OOB_FILL_NONE);
}
static void make_map3(EncodeFn enc, CUtensorMap* m, void* ptr, uint64_t d0, uint64_t cols, uint64_t rows, uint64_t blk_stride,
                      uint64_t nblocks, uint32_t nblk, uint32_t box_rows = 64) {
  cuuint64_t dims[3] = {d0, rows, nblocks};
  cuuint64_t strides[2] = {cols * 2, blk_stride * 2};
  cuuint32_t box[3] = {64, box_rows, nblk};
  cuuint32_t es[3] = {1, 1, 1};
  enc(m, CU_TENSOR_MAP_DATA_TYPE_BFLOAT16, 3, ptr, dims, strides, box, es, CU_TENSOR_MAP_INTERLEAVE_NONE,
      CU_TENSOR_MAP_SWIZZLE_128B, CU_TENSOR_MAP_L2_PROMOTION_L2_128B, CU_TENSOR_MAP_FLOAT_OOB_FILL_NONE);
}

extern "C" void kernel_launch(void* const* d_in, const int* in_sizes, int n_in, void* d_out, int out_size) {
  static Params prm;
  static void* cached[13] = {nullptr};
  static bool attr_done = false, by_smid = false;
  bool same = attr_done && cached[12] == d_out;
  for (int i = 0; i < 12 && same; i++) same = cached[i] == d_in[i];
  if (!same) {
    void* fn = nullptr;
    cudaDriverEntryPointQueryResult qr;
    cudaGetDriverEntryPoint("cuTensorMapEncodeTiled", &fn, cudaEnableDefault, &qr);
    EncodeFn enc = (EncodeFn)fn;
    void *pO, *pXT;
    cudaGetSymbolAddress(&pO, g_O);
    cudaGetSymbolAddress(&pXT, g_xT);
    make_map(enc, &prm.mapO, pO, DM, LSEQ, 64);
    make_map(enc, &prm.mapXT, pXT, LSEQ, 4 * DM, 64);
    prm.out = (bf16*)d_out;
    make_map(enc, &prm.mapX128, d_in[0], DM, LSEQ, 128);
    make_map(enc, &prm.mapWo128, d_in[2], DM, DM, 128);
    make_map(enc, &prm.mapO128, pO, DM, LSEQ, 128);
    make_map3(enc, &prm.mapW3, d_in[1], DM, 3 * DM, DM, DM, 3, 3);
    make_map3(enc, &prm.mapW3h, d_in[1], DM, 3 * DM, DM, DM, 3, 3, 32);
    make_map3(enc, &prm.mapXT3, pXT, 64, LSEQ, 4 * DM, 64, 32, 2);
    prm.a_re = (const bf16*)d_in[4]; prm.a_im = (const bf16*)d_in[5];
    prm.b_re = (const bf16*)d_in[6]; prm.b_im = (const bf16*)d_in[7];
    prm.c_re = (const bf16*)d_in[8]; prm.c_im = (const bf16*)d_in[9];
    prm.log_dt = (const bf16*)d_in[10]; prm.dskip = (const bf16*)d_in[11];
    int dev = 0, sms = 0;
    cudaGetDevice(&dev);
    cudaDeviceGetAttribute(&sms, cudaDevAttrMultiProcessorCount, dev);
    by_smid = sms == 132;
    cudaFuncSetAttribute(fused_kernel<true>, cudaFuncAttributeMaxDynamicSharedMemorySize, SM_TOTAL);
    cudaFuncSetAttribute(fused_kernel<false>, cudaFuncAttributeMaxDynamicSharedMemorySize, SM_TOTAL);
    for (int i = 0; i < 12; i++) cached[i] = d_in[i];
    cached[12] = d_out;
    attr_done = true;
  }
  prm.stop = 100;
    if (by_smid) fused_kernel<true><<<132, NTHREADS, SM_TOTAL>>>(prm);
  else fused_kernel<false><<<NCTA, NTHREADS, SM_TOTAL>>>(prm);
}
```

```cpp
#include <cuda_runtime.h>
#include <cuda_bf16.h>
#include <cuda.h>
#include <stdint.h>

typedef __nv_bfloat16 bf16;

constexpr int LSEQ = 2048;
constexpr int DM = 512;
constexpr int NCTA = 128;
constexpr int NTHREADS = 512;
#define RR 0
#define KG_PRE 0
#define ST_AT 6
#define CS_AT 4
#define KG_LAST 1
#define X_JIT 0
#define PF_AT 2
#define KG_GATE 2
#define R_CONS 192
#define R_HELP 88

constexpr int SM_X = 0;
constexpr int SM_W = 131072;
constexpr int SM_KVX = SM_W;
constexpr int SM_OST = SM_W + 32768;
constexpr int SM_R = 196608;
constexpr int SM_T = 212992;
constexpr int SM_KC = 217088;
constexpr int KC_STRIDE = 648;
constexpr int SM_CS = SM_KC + 4 * KC_STRIDE * 2;
constexpr int SM_CW = SM_R + 8192;
constexpr int SM_EP = SM_CS + 768;
constexpr int SM_BAR = SM_EP + 16;
constexpr int SM_T2 = SM_BAR + 832;
constexpr int SM_HALO = SM_T2 + 4096;
constexpr int SM_ST = SM_HALO + 3072;
constexpr int SM_TOTAL = SM_HALO + 4096;
static_assert(SM_TOTAL <= 232448, "shared memory");

constexpr int CV_UH = 140 * 16;
constexpr int CV_PECH = 1120 * 4;
constexpr int CV_PBW = 2112 * 2;
__host__ __device__ constexpr int cv_s(int lc) { return SM_X + lc * 32768; }
__host__ __device__ constexpr int cv_u(int lc) { return cv_s(lc) + 4096; }
__host__ __device__ constexpr int cv_pe(int lc) { return cv_u(lc) + 2 * CV_UH; }
__host__ __device__ constexpr int cv_pb(int lc) { return cv_pe(lc) + CV_PECH; }
__host__ __device__ constexpr int cv_ft(int lc) { return cv_pb(lc) + 4 * CV_PBW; }
static_assert(cv_ft(0) + 1024 <= 32768, "conv buffers");
__host__ __device__ constexpr int cv_chan(int cta, int lc) { return cta + 128 * lc; }

enum {
  B_XF = 0,
  B_KVF = 8,
  B_KVE = 16,
  B_AD = 21,
  B_OST = 22,
  B_RF = 23,
  B_U = 24,
  B_S = 28,
  B_T = 32,
  B_WOF = 36,
  B_E = 40,
  B_OF = 44,
  B_P = 64,
  B_CW = 53,
  B_HF = 54,
  B_STF = 55,
  B_QDONE = 56,
  B_PDONE = 57,
  B_Z0 = 58,
  B_PE = 59,
  B_GB = 60,
  B_EP = 62,
  B_ZF = 63,
  B_COUNT = 68
};

enum {
  C_CS = 0,
  C_G0 = 1,
  C_G1 = 2,
  C_G2 = 3,
  C_O = 4,
  C_F = 20,
  C_COUNT = 24
};

__device__ unsigned g_cnt[C_COUNT * 32];
__device__ __align__(1024) bf16 g_O[LSEQ * DM];
__device__ __align__(1024) bf16 g_xT[4 * DM * LSEQ];
__device__ __align__(1024) float g_stats[2 * LSEQ * 2];
__device__ __align__(1024) uint4 g_colsum[8 * 16 * 48];
__device__ __align__(1024) uint4 g_halo[2 * 16 * 8 * 384];
__device__ __align__(1024) uint4 g_part[2 * 16 * 8 * 128];
#define TS(i) do { } while (0)

#define KTS(i) do { if (ht == 0) TS(i); } while (0)
#define FTS(i) do { } while (0)
#define LTS(i) do { } while (0)

struct Params {
  CUtensorMap mapO, mapXT, mapX128, mapWo128, mapO128, mapW3, mapW3h, mapXT3;
  const bf16 *a_re, *a_im, *b_re, *b_im, *c_re, *c_im, *log_dt, *dskip;
  bf16* out;
  int stop;
};

__device__ __forceinline__ uint32_t s32(const void* p) { return (uint32_t)__cvta_generic_to_shared(p); }
__device__ __forceinline__ void mbar_init(uint32_t b, int c) { asm volatile("mbarrier.init.shared::cta.b64 [%0], %1;" ::"r"(b), "r"(c) : "memory"); }
__device__ __forceinline__ void mbar_expect(uint32_t b, int bytes) { asm volatile("mbarrier.arrive.expect_tx.shared::cta.b64 _, [%0], %1;" ::"r"(b), "r"(bytes) : "memory"); }
__device__ __forceinline__ void mbar_arrive(uint32_t b) { asm volatile("mbarrier.arrive.shared::cta.b64 _, [%0];" ::"r"(b) : "memory"); }
__device__ __forceinline__ void mbar_arrive_if(uint32_t b, bool c) {
  asm volatile("{\n.reg .pred p;\nsetp.ne.u32 p, %1, 0;\n@p mbarrier.arrive.shared::cta.b64 _, [%0];\n}" ::"r"(b), "r"((uint32_t)c) : "memory");
}
__device__ __forceinline__ void mbar_wait(uint32_t b, int parity) {
  asm volatile("{\n.reg .pred p;\nWAIT_LOOP:\nmbarrier.try_wait.parity.shared::cta.b64 p, [%0], %1;\n@p bra WAIT_DONE;\nbra WAIT_LOOP;\nWAIT_DONE:\n}" ::"r"(b), "r"(parity) : "memory");
}
__device__ __forceinline__ int opaque_tid() { int v; asm volatile("mov.u32 %0, %%tid.x;" : "=r"(v)); return v; }
__device__ __forceinline__ bool elect_one() {
  uint32_t r;
  asm volatile("{\n.reg .pred p;\nelect.sync _|p, 0xffffffff;\nselp.u32 %0, 1, 0, p;\n}" : "=r"(r));
  return r != 0;
}
__device__ __forceinline__ void tma_ld(uint32_t dst, const CUtensorMap* m, int c0, int c1, uint32_t bar) {
  asm volatile("cp.async.bulk.tensor.2d.shared::cluster.global.mbarrier::complete_tx::bytes [%0], [%1, {%3, %4}], [%2];"
               ::"r"(dst), "l"(m), "r"(bar), "r"(c0), "r"(c1) : "memory");
}
__device__ __forceinline__ void tma_ld3(uint32_t dst, const CUtensorMap* m, int c0, int c1, int c2, uint32_t bar) {
  asm volatile("cp.async.bulk.tensor.3d.shared::cluster.global.mbarrier::complete_tx::bytes [%0], [%1, {%3, %4, %5}], [%2];"
               ::"r"(dst), "l"(m), "r"(bar), "r"(c0), "r"(c1), "r"(c2) : "memory");
}
__device__ __forceinline__ void tma_prefetch2(const CUtensorMap* m, int c0, int c1) {
  asm volatile("cp.async.bulk.prefetch.tensor.2d.L2.global.tile [%0, {%1, %2}];" ::"l"(m), "r"(c0), "r"(c1) : "memory");
}
__device__ __forceinline__ void tma_prefetch3(const CUtensorMap* m, int c0, int c1, int c2) {
  asm volatile("cp.async.bulk.prefetch.tensor.3d.L2.global.tile [%0, {%1, %2, %3}];" ::"l"(m), "r"(c0), "r"(c1), "r"(c2) : "memory");
}
__device__ __forceinline__ void tma_st(const CUtensorMap* m, int c0, int c1, uint32_t src) {
  asm volatile("cp.async.bulk.tensor.2d.global.shared::cta.bulk_group [%0, {%2, %3}], [%1];" ::"l"(m), "r"(src), "r"(c0), "r"(c1) : "memory");
}
__device__ __forceinline__ void bulk_ld(uint32_t dst, const void* src, int bytes, uint32_t bar) {
  asm volatile("cp.async.bulk.shared::cluster.global.mbarrier::complete_tx::bytes [%0], [%1], %2, [%3];" ::"r"(dst), "l"(src), "r"(bytes), "r"(bar) : "memory");
}
__device__ __forceinline__ void bulk_st(void* dst, uint32_t src, int bytes) {
  asm volatile("cp.async.bulk.global.shared::cta.bulk_group [%0], [%1], %2;" ::"l"(dst), "r"(src), "r"(bytes) : "memory");
}
__device__ __forceinline__ void bulk_red_add_f32(void* dst, uint32_t src, int bytes) {
  asm volatile("cp.reduce.async.bulk.global.shared::cta.bulk_group.add.f32 [%0], [%1], %2;" ::"l"(dst), "r"(src), "r"(bytes) : "memory");
}
__device__ __forceinline__ void bulk_commit() { asm volatile("cp.async.bulk.commit_group;" ::: "memory"); }
__device__ __forceinline__ void bulk_wait_all() { asm volatile("cp.async.bulk.wait_group 0;" ::: "memory"); }
__device__ __forceinline__ void fence_async_smem() { asm volatile("fence.proxy.async.shared::cta;" ::: "memory"); }
__device__ __forceinline__ void fence_async_global() { asm volatile("fence.proxy.async.global;" ::: "memory"); }
__device__ __forceinline__ void bar_sync(int id, int n) { asm volatile("bar.sync %0, %1;" ::"r"(id), "r"(n) : "memory"); }
__device__ __forceinline__ void bar_arrive(int id, int n) { asm volatile("bar.arrive %0, %1;" ::"r"(id), "r"(n) : "memory"); }
__device__ __forceinline__ void wg_fence() { asm volatile("wgmma.fence.sync.aligned;" ::: "memory"); }
__device__ __forceinline__ void wg_commit() { asm volatile("wgmma.commit_group.sync.aligned;" ::: "memory"); }
template <int N> __device__ __forceinline__ void wg_wait() { asm volatile("wgmma.wait_group.sync.aligned %0;" ::"n"(N) : "memory"); }
__device__ __forceinline__ uint64_t mkdesc(uint32_t addr, uint32_t lbo, uint32_t sbo, int sw) {
  return (uint64_t)((addr & 0x3FFFF) >> 4) | ((uint64_t)(lbo >> 4) << 16) | ((uint64_t)(sbo >> 4) << 32) | ((uint64_t)sw << 62);
}
__device__ __forceinline__ void ldsm4(uint32_t* r, uint32_t a) {
  asm volatile("ldmatrix.sync.aligned.m8n8.x4.shared.b16 {%0,%1,%2,%3}, [%4];" : "=r"(r[0]), "=r"(r[1]), "=r"(r[2]), "=r"(r[3]) : "r"(a) : "memory");
}
__device__ __forceinline__ void ldsm4t(uint32_t* r, uint32_t a) {
  asm volatile("ldmatrix.sync.aligned.m8n8.x4.trans.shared.b16 {%0,%1,%2,%3}, [%4];" : "=r"(r[0]), "=r"(r[1]), "=r"(r[2]), "=r"(r[3]) : "r"(a) : "memory");
}
__device__ __forceinline__ void stsm4(uint32_t a, uint32_t r0, uint32_t r1, uint32_t r2, uint32_t r3) {
  asm volatile("stmatrix.sync.aligned.m8n8.x4.shared.b16 [%0], {%1,%2,%3,%4};" ::"r"(a), "r"(r0), "r"(r1), "r"(r2), "r"(r3) : "memory");
}
__device__ __forceinline__ void stsm4t(uint32_t a, uint32_t r0, uint32_t r1, uint32_t r2, uint32_t r3) {
  asm volatile("stmatrix.sync.aligned.m8n8.x4.trans.shared.b16 [%0], {%1,%2,%3,%4};" ::"r"(a), "r"(r0), "r"(r1), "r"(r2), "r"(r3) : "memory");
}
__device__ __forceinline__ uint32_t movm_t(uint32_t a) { uint32_t r; asm volatile("movmatrix.sync.aligned.m8n8.trans.b16 %0, %1;" : "=r"(r) : "r"(a)); return r; }
__device__ __forceinline__ uint32_t lds32(uint32_t a) { uint32_t v; asm volatile("ld.shared.b32 %0, [%1];" : "=r"(v) : "r"(a) : "memory"); return v; }
__device__ __forceinline__ float2 lds64f(uint32_t a) { float2 v; asm volatile("ld.shared.v2.f32 {%0,%1}, [%2];" : "=f"(v.x), "=f"(v.y) : "r"(a) : "memory"); return v; }
__device__ __forceinline__ float4 lds128f(uint32_t a) { float4 v; asm volatile("ld.shared.v4.f32 {%0,%1,%2,%3}, [%4];" : "=f"(v.x), "=f"(v.y), "=f"(v.z), "=f"(v.w) : "r"(a) : "memory"); return v; }
__device__ __forceinline__ uint4 lds128(uint32_t a) { uint4 v; asm volatile("ld.shared.v4.b32 {%0,%1,%2,%3}, [%4];" : "=r"(v.x), "=r"(v.y), "=r"(v.z), "=r"(v.w) : "r"(a) : "memory"); return v; }
__device__ __forceinline__ void sts128(uint32_t a, uint4 v) { asm volatile("st.shared.v4.b32 [%0], {%1,%2,%3,%4};" ::"r"(a), "r"(v.x), "r"(v.y), "r"(v.z), "r"(v.w) : "memory"); }
__device__ __forceinline__ void sts128f(uint32_t a, float x, float y, float z, float w) { asm volatile("st.shared.v4.f32 [%0], {%1,%2,%3,%4};" ::"r"(a), "f"(x), "f"(y), "f"(z), "f"(w) : "memory"); }
__device__ __forceinline__ void sts32f(uint32_t a, float v) { asm volatile("st.shared.f32 [%0], %1;" ::"r"(a), "f"(v) : "memory"); }
__device__ __forceinline__ void sts16(uint32_t a, uint16_t v) { asm volatile("st.shared.u16 [%0], %1;" ::"r"(a), "h"(v) : "memory"); }
__device__ __forceinline__ uint32_t lds16(uint32_t a) { uint16_t v; asm volatile("ld.shared.u16 %0, [%1];" : "=h"(v) : "r"(a) : "memory"); return v; }
__device__ __forceinline__ uint32_t packbf(float lo, float hi) { uint32_t r; asm("cvt.rn.bf16x2.f32 %0, %1, %2;" : "=r"(r) : "f"(hi), "f"(lo)); return r; }
__device__ __forceinline__ float bf_lo(uint32_t v) { return __uint_as_float(v << 16); }
__device__ __forceinline__ float bf_hi(uint32_t v) { return __uint_as_float(v & 0xffff0000u); }
__device__ __forceinline__ float ex2(float x) { float r; asm("ex2.approx.ftz.f32 %0, %1;" : "=f"(r) : "f"(x)); return r; }
__device__ __forceinline__ float rsqrt_approx(float x) { float r; asm("rsqrt.approx.ftz.f32 %0, %1;" : "=f"(r) : "f"(x)); return r; }
__device__ __forceinline__ float rcp_approx(float x) { float r; asm("rcp.approx.ftz.f32 %0, %1;" : "=f"(r) : "f"(x)); return r; }
__device__ __forceinline__ void mma_bf16(float* d, const uint32_t* a, uint32_t b0, uint32_t b1) {
  asm("mma.sync.aligned.m16n8k16.row.col.f32.bf16.bf16.f32 {%0,%1,%2,%3}, {%4,%5,%6,%7}, {%8,%9}, {%0,%1,%2,%3};"
               : "+f"(d[0]), "+f"(d[1]), "+f"(d[2]), "+f"(d[3]) : "r"(a[0]), "r"(a[1]), "r"(a[2]), "r"(a[3]), "r"(b0), "r"(b1));
}
__device__ __forceinline__ void red_release(unsigned* p) { asm volatile("red.release.gpu.global.add.u32 [%0], 1;" ::"l"(p) : "memory"); }
__device__ __forceinline__ void red_relaxed(unsigned* p) { asm volatile("red.relaxed.gpu.global.add.u32 [%0], 1;" ::"l"(p) : "memory"); }
__device__ __forceinline__ unsigned ld_relaxed(const unsigned* p) { unsigned v; asm volatile("ld.relaxed.gpu.global.u32 %0, [%1];" : "=r"(v) : "l"(p) : "memory"); return v; }
__device__ __forceinline__ void spin_until(const unsigned* p, unsigned target) {
  int it = 0;
  while ((int)(ld_relaxed(p) - target) < 0) {
    if (++it > (1 << 23)) __trap();
  }
}
__device__ __forceinline__ uint4 ldcg128(const void* p) { uint4 v; asm volatile("ld.global.cg.v4.b32 {%0,%1,%2,%3}, [%4];" : "=r"(v.x), "=r"(v.y), "=r"(v.z), "=r"(v.w) : "l"(p) : "memory"); return v; }
__device__ __forceinline__ uint4 ld_tagged(const uint4* p) { uint4 v; asm volatile("ld.relaxed.gpu.global.v4.u32 {%0,%1,%2,%3}, [%4];" : "=r"(v.x), "=r"(v.y), "=r"(v.z), "=r"(v.w) : "l"(p) : "memory"); return v; }
__device__ __forceinline__ void st_tagged(uint4* p, uint32_t a, uint32_t b, uint32_t tag) { asm volatile("st.relaxed.gpu.global.v4.u32 [%0], {%1,%2,%3,%2};" ::"l"(p), "r"(a), "r"(tag), "r"(b) : "memory"); }
__device__ __forceinline__ void st_tagged3(uint4* p, uint32_t a, uint32_t b, uint32_t c, uint32_t tag) { asm volatile("st.relaxed.gpu.global.v4.u32 [%0], {%1,%2,%3,%4};" ::"l"(p), "r"(a), "r"(b), "r"(c), "r"(tag) : "memory"); }
__device__ __forceinline__ uint4 poll_tagged(const uint4* p, uint32_t tag) {
  uint4 v = ld_tagged(p);
  int it = 0;
  while (v.y != tag || v.w != tag) {
    if (++it > (1 << 22)) __trap();
    v = ld_tagged(p);
  }
  return v;
}
__device__ __forceinline__ uint32_t hadd2(uint32_t a, uint32_t b) { uint32_t r; asm("add.rn.bf16x2 %0, %1, %2;" : "=r"(r) : "r"(a), "r"(b)); return r; }
__device__ __forceinline__ uint32_t hmul2(uint32_t a, uint32_t b) { uint32_t r; asm("mul.rn.bf16x2 %0, %1, %2;" : "=r"(r) : "r"(a), "r"(b)); return r; }

template<int N,int TB> __device__ __forceinline__ void wgmma_rs(float* d, const uint32_t* a, uint64_t db, int sd);
template<int N,int TA,int TB> __device__ __forceinline__ void wgmma_ss(float* d, uint64_t da, uint64_t db, int sd);
template<> __device__ __forceinline__ void wgmma_rs<128,0>(float* d, const uint32_t* a, uint64_t db, int sd) {
  asm volatile("{\n.reg .pred p;\nsetp.ne.b32 p, %69, 0;\nwgmma.mma_async.sync.aligned.m64n128k16.f32.bf16.bf16 {%0,%1,%2,%3,%4,%5,%6,%7,%8,%9,%10,%11,%12,%13,%14,%15,%16,%17,%18,%19,%20,%21,%22,%23,%24,%25,%26,%27,%28,%29,%30,%31,%32,%33,%34,%35,%36,%37,%38,%39,%40,%41,%42,%43,%44,%45,%46,%47,%48,%49,%50,%51,%52,%53,%54,%55,%56,%57,%58,%59,%60,%61,%62,%63}, {%64,%65,%66,%67}, %68, p, 1, 1, 0;\n}\n"
   : "+f"(d[0]),"+f"(d[1]),"+f"(d[2]),"+f"(d[3]),"+f"(d[4]),"+f"(d[5]),"+f"(d[6]),"+f"(d[7]),"+f"(d[8]),"+f"(d[9]),"+f"(d[10]),"+f"(d[11]),"+f"(d[12]),"+f"(d[13]),"+f"(d[14]),"+f"(d[15]),"+f"(d[16]),"+f"(d[17]),"+f"(d[18]),"+f"(d[19]),"+f"(d[20]),"+f"(d[21]),"+f"(d[22]),"+f"(d[23]),"+f"(d[24]),"+f"(d[25]),"+f"(d[26]),"+f"(d[27]),"+f"(d[28]),"+f"(d[29]),"+f"(d[30]),"+f"(d[31]),"+f"(d[32]),"+f"(d[33]),"+f"(d[34]),"+f"(d[35]),"+f"(d[36]),"+f"(d[37]),"+f"(d[38]),"+f"(d[39]),"+f"(d[40]),"+f"(d[41]),"+f"(d[42]),"+f"(d[43]),"+f"(d[44]),"+f"(d[45]),"+f"(d[46]),"+f"(d[47]),"+f"(d[48]),"+f"(d[49]),"+f"(d[50]),"+f"(d[51]),"+f"(d[52]),"+f"(d[53]),"+f"(d[54]),"+f"(d[55]),"+f"(d[56]),"+f"(d[57]),"+f"(d[58]),"+f"(d[59]),"+f"(d[60]),"+f"(d[61]),"+f"(d[62]),"+f"(d[63])
   : "r"(a[0]), "r"(a[1]), "r"(a[2]), "r"(a[3]), "l"(db), "r"(sd));
}
template<> __device__ __forceinline__ void wgmma_rs<120,0>(float* d, const uint32_t* a, uint64_t db, int sd) {
  asm volatile("{\n.reg .pred p;\nsetp.ne.b32 p, %65, 0;\nwgmma.mma_async.sync.aligned.m64n120k16.f32.bf16.bf16 {%0,%1,%2,%3,%4,%5,%6,%7,%8,%9,%10,%11,%12,%13,%14,%15,%16,%17,%18,%19,%20,%21,%22,%23,%24,%25,%26,%27,%28,%29,%30,%31,%32,%33,%34,%35,%36,%37,%38,%39,%40,%41,%42,%43,%44,%45,%46,%47,%48,%49,%50,%51,%52,%53,%54,%55,%56,%57,%58,%59}, {%60,%61,%62,%63}, %64, p, 1, 1, 0;\n}\n"
   : "+f"(d[0]),"+f"(d[1]),"+f"(d[2]),"+f"(d[3]),"+f"(d[4]),"+f"(d[5]),"+f"(d[6]),"+f"(d[7]),"+f"(d[8]),"+f"(d[9]),"+f"(d[10]),"+f"(d[11]),"+f"(d[12]),"+f"(d[13]),"+f"(d[14]),"+f"(d[15]),"+f"(d[16]),"+f"(d[17]),"+f"(d[18]),"+f"(d[19]),"+f"(d[20]),"+f"(d[21]),"+f"(d[22]),"+f"(d[23]),"+f"(d[24]),"+f"(d[25]),"+f"(d[26]),"+f"(d[27]),"+f"(d[28]),"+f"(d[29]),"+f"(d[30]),"+f"(d[31]),"+f"(d[32]),"+f"(d[33]),"+f"(d[34]),"+f"(d[35]),"+f"(d[36]),"+f"(d[37]),"+f"(d[38]),"+f"(d[39]),"+f"(d[40]),"+f"(d[41]),"+f"(d[42]),"+f"(d[43]),"+f"(d[44]),"+f"(d[45]),"+f"(d[46]),"+f"(d[47]),"+f"(d[48]),"+f"(d[49]),"+f"(d[50]),"+f"(d[51]),"+f"(d[52]),"+f"(d[53]),"+f"(d[54]),"+f"(d[55]),"+f"(d[56]),"+f"(d[57]),"+f"(d[58]),"+f"(d[59])
   : "r"(a[0]), "r"(a[1]), "r"(a[2]), "r"(a[3]), "l"(db), "r"(sd));
}
template<> __device__ __forceinline__ void wgmma_rs<112,0>(float* d, const uint32_t* a, uint64_t db, int sd) {
  asm volatile("{\n.reg .pred p;\nsetp.ne.b32 p, %61, 0;\nwgmma.mma_async.sync.aligned.m64n112k16.f32.bf16.bf16 {%0,%1,%2,%3,%4,%5,%6,%7,%8,%9,%10,%11,%12,%13,%14,%15,%16,%17,%18,%19,%20,%21,%22,%23,%24,%25,%26,%27,%28,%29,%30,%31,%32,%33,%34,%35,%36,%37,%38,%39,%40,%41,%42,%43,%44,%45,%46,%47,%48,%49,%50,%51,%52,%53,%54,%55}, {%56,%57,%58,%59}, %60, p, 1, 1, 0;\n}\n"
   : "+f"(d[0]),"+f"(d[1]),"+f"(d[2]),"+f"(d[3]),"+f"(d[4]),"+f"(d[5]),"+f"(d[6]),"+f"(d[7]),"+f"(d[8]),"+f"(d[9]),"+f"(d[10]),"+f"(d[11]),"+f"(d[12]),"+f"(d[13]),"+f"(d[14]),"+f"(d[15]),"+f"(d[16]),"+f"(d[17]),"+f"(d[18]),"+f"(d[19]),"+f"(d[20]),"+f"(d[21]),"+f"(d[22]),"+f"(d[23]),"+f"(d[24]),"+f"(d[25]),"+f"(d[26]),"+f"(d[27]),"+f"(d[28]),"+f"(d[29]),"+f"(d[30]),"+f"(d[31]),"+f"(d[32]),"+f"(d[33]),"+f"(d[34]),"+f"(d[35]),"+f"(d[36]),"+f"(d[37]),"+f"(d[38]),"+f"(d[39]),"+f"(d[40]),"+f"(d[41]),"+f"(d[42]),"+f"(d[43]),"+f"(d[44]),"+f"(d[45]),"+f"(d[46]),"+f"(d[47]),"+f"(d[48]),"+f"(d[49]),"+f"(d[50]),"+f"(d[51]),"+f"(d[52]),"+f"(d[53]),"+f"(d[54]),"+f"(d[55])
   : "r"(a[0]), "r"(a[1]), "r"(a[2]), "r"(a[3]), "l"(db), "r"(sd));
}
template<> __device__ __forceinline__ void wgmma_rs<104,0>(float* d, const uint32_t* a, uint64_t db, int sd) {
  asm volatile("{\n.reg .pred p;\nsetp.ne.b32 p, %57, 0;\nwgmma.mma_async.sync.aligned.m64n104k16.f32.bf16.bf16 {%0,%1,%2,%3,%4,%5,%6,%7,%8,%9,%10,%11,%12,%13,%14,%15,%16,%17,%18,%19,%20,%21,%22,%23,%24,%25,%26,%27,%28,%29,%30,%31,%32,%33,%34,%35,%36,%37,%38,%39,%40,%41,%42,%43,%44,%45,%46,%47,%48,%49,%50,%51}, {%52,%53,%54,%55}, %56, p, 1, 1, 0;\n}\n"
   : "+f"(d[0]),"+f"(d[1]),"+f"(d[2]),"+f"(d[3]),"+f"(d[4]),"+f"(d[5]),"+f"(d[6]),"+f"(d[7]),"+f"(d[8]),"+f"(d[9]),"+f"(d[10]),"+f"(d[11]),"+f"(d[12]),"+f"(d[13]),"+f"(d[14]),"+f"(d[15]),"+f"(d[16]),"+f"(d[17]),"+f"(d[18]),"+f"(d[19]),"+f"(d[20]),"+f"(d[21]),"+f"(d[22]),"+f"(d[23]),"+f"(d[24]),"+f"(d[25]),"+f"(d[26]),"+f"(d[27]),"+f"(d[28]),"+f"(d[29]),"+f"(d[30]),"+f"(d[31]),"+f"(d[32]),"+f"(d[33]),"+f"(d[34]),"+f"(d[35]),"+f"(d[36]),"+f"(d[37]),"+f"(d[38]),"+f"(d[39]),"+f"(d[40]),"+f"(d[41]),"+f"(d[42]),"+f"(d[43]),"+f"(d[44]),"+f"(d[45]),"+f"(d[46]),"+f"(d[47]),"+f"(d[48]),"+f"(d[49]),"+f"(d[50]),"+f"(d[51])
   : "r"(a[0]), "r"(a[1]), "r"(a[2]), "r"(a[3]), "l"(db), "r"(sd));
}
template<> __device__ __forceinline__ void wgmma_rs<96,0>(float* d, const uint32_t* a, uint64_t db, int sd) {
  asm volatile("{\n.reg .pred p;\nsetp.ne.b32 p, %53, 0;\nwgmma.mma_async.sync.aligned.m64n96k16.f32.bf16.bf16 {%0,%1,%2,%3,%4,%5,%6,%7,%8,%9,%10,%11,%12,%13,%14,%15,%16,%17,%18,%19,%20,%21,%22,%23,%24,%25,%26,%27,%28,%29,%30,%31,%32,%33,%34,%35,%36,%37,%38,%39,%40,%41,%42,%43,%44,%45,%46,%47}, {%48,%49,%50,%51}, %52, p, 1, 1, 0;\n}\n"
   : "+f"(d[0]),"+f"(d[1]),"+f"(d[2]),"+f"(d[3]),"+f"(d[4]),"+f"(d[5]),"+f"(d[6]),"+f"(d[7]),"+f"(d[8]),"+f"(d[9]),"+f"(d[10]),"+f"(d[11]),"+f"(d[12]),"+f"(d[13]),"+f"(d[14]),"+f"(d[15]),"+f"(d[16]),"+f"(d[17]),"+f"(d[18]),"+f"(d[19]),"+f"(d[20]),"+f"(d[21]),"+f"(d[22]),"+f"(d[23]),"+f"(d[24]),"+f"(d[25]),"+f"(d[26]),"+f"(d[27]),"+f"(d[28]),"+f"(d[29]),"+f"(d[30]),"+f"(d[31]),"+f"(d[32]),"+f"(d[33]),"+f"(d[34]),"+f"(d[35]),"+f"(d[36]),"+f"(d[37]),"+f"(d[38]),"+f"(d[39]),"+f"(d[40]),"+f"(d[41]),"+f"(d[42]),"+f"(d[43]),"+f"(d[44]),"+f"(d[45]),"+f"(d[46]),"+f"(d[47])
   : "r"(a[0]), "r"(a[1]), "r"(a[2]), "r"(a[3]), "l"(db), "r"(sd));
}
template<> __device__ __forceinline__ void wgmma_rs<88,0>(float* d, const uint32_t* a, uint64_t db, int sd) {
  asm volatile("{\n.reg .pred p;\nsetp.ne.b32 p, %49, 0;\nwgmma.mma_async.sync.aligned.m64n88k16.f32.bf16.bf16 {%0,%1,%2,%3,%4,%5,%6,%7,%8,%9,%10,%11,%12,%13,%14,%15,%16,%17,%18,%19,%20,%21,%22,%23,%24,%25,%26,%27,%28,%29,%30,%31,%32,%33,%34,%35,%36,%37,%38,%39,%40,%41,%42,%43}, {%44,%45,%46,%47}, %48, p, 1, 1, 0;\n}\n"
   : "+f"(d[0]),"+f"(d[1]),"+f"(d[2]),"+f"(d[3]),"+f"(d[4]),"+f"(d[5]),"+f"(d[6]),"+f"(d[7]),"+f"(d[8]),"+f"(d[9]),"+f"(d[10]),"+f"(d[11]),"+f"(d[12]),"+f"(d[13]),"+f"(d[14]),"+f"(d[15]),"+f"(d[16]),"+f"(d[17]),"+f"(d[18]),"+f"(d[19]),"+f"(d[20]),"+f"(d[21]),"+f"(d[22]),"+f"(d[23]),"+f"(d[24]),"+f"(d[25]),"+f"(d[26]),"+f"(d[27]),"+f"(d[28]),"+f"(d[29]),"+f"(d[30]),"+f"(d[31]),"+f"(d[32]),"+f"(d[33]),"+f"(d[34]),"+f"(d[35]),"+f"(d[36]),"+f"(d[37]),"+f"(d[38]),"+f"(d[39]),"+f"(d[40]),"+f"(d[41]),"+f"(d[42]),"+f"(d[43])
   : "r"(a[0]), "r"(a[1]), "r"(a[2]), "r"(a[3]), "l"(db), "r"(sd));
}
template<> __device__ __forceinline__ void wgmma_rs<80,0>(float* d, const uint32_t* a, uint64_t db, int sd) {
  asm volatile("{\n.reg .pred p;\nsetp.ne.b32 p, %45, 0;\nwgmma.mma_async.sync.aligned.m64n80k16.f32.bf16.bf16 {%0,%1,%2,%3,%4,%5,%6,%7,%8,%9,%10,%11,%12,%13,%14,%15,%16,%17,%18,%19,%20,%21,%22,%23,%24,%25,%26,%27,%28,%29,%30,%31,%32,%33,%34,%35,%36,%37,%38,%39}, {%40,%41,%42,%43}, %44, p, 1, 1, 0;\n}\n"
   : "+f"(d[0]),"+f"(d[1]),"+f"(d[2]),"+f"(d[3]),"+f"(d[4]),"+f"(d[5]),"+f"(d[6]),"+f"(d[7]),"+f"(d[8]),"+f"(d[9]),"+f"(d[10]),"+f"(d[11]),"+f"(d[12]),"+f"(d[13]),"+f"(d[14]),"+f"(d[15]),"+f"(d[16]),"+f"(d[17]),"+f"(d[18]),"+f"(d[19]),"+f"(d[20]),"+f"(d[21]),"+f"(d[22]),"+f"(d[23]),"+f"(d[24]),"+f"(d[25]),"+f"(d[26]),"+f"(d[27]),"+f"(d[28]),"+f"(d[29]),"+f"(d[30]),"+f"(d[31]),"+f"(d[32]),"+f"(d[33]),"+f"(d[34]),"+f"(d[35]),"+f"(d[36]),"+f"(d[37]),"+f"(d[38]),"+f"(d[39])
   : "r"(a[0]), "r"(a[1]), "r"(a[2]), "r"(a[3]), "l"(db), "r"(sd));
}
template<> __device__ __forceinline__ void wgmma_rs<72,0>(float* d, const uint32_t* a, uint64_t db, int sd) {
  asm volatile("{\n.reg .pred p;\nsetp.ne.b32 p, %41, 0;\nwgmma.mma_async.sync.aligned.m64n72k16.f32.bf16.bf16 {%0,%1,%2,%3,%4,%5,%6,%7,%8,%9,%10,%11,%12,%13,%14,%15,%16,%17,%18,%19,%20,%21,%22,%23,%24,%25,%26,%27,%28,%29,%30,%31,%32,%33,%34,%35}, {%36,%37,%38,%39}, %40, p, 1, 1, 0;\n}\n"
   : "+f"(d[0]),"+f"(d[1]),"+f"(d[2]),"+f"(d[3]),"+f"(d[4]),"+f"(d[5]),"+f"(d[6]),"+f"(d[7]),"+f"(d[8]),"+f"(d[9]),"+f"(d[10]),"+f"(d[11]),"+f"(d[12]),"+f"(d[13]),"+f"(d[14]),"+f"(d[15]),"+f"(d[16]),"+f"(d[17]),"+f"(d[18]),"+f"(d[19]),"+f"(d[20]),"+f"(d[21]),"+f"(d[22]),"+f"(d[23]),"+f"(d[24]),"+f"(d[25]),"+f"(d[26]),"+f"(d[27]),"+f"(d[28]),"+f"(d[29]),"+f"(d[30]),"+f"(d[31]),"+f"(d[32]),"+f"(d[33]),"+f"(d[34]),"+f"(d[35])
   : "r"(a[0]), "r"(a[1]), "r"(a[2]), "r"(a[3]), "l"(db), "r"(sd));
}
template<> __device__ __forceinline__ void wgmma_rs<64,0>(float* d, const uint32_t* a, uint64_t db, int sd) {
  asm volatile("{\n.reg .pred p;\nsetp.ne.b32 p, %37, 0;\nwgmma.mma_async.sync.aligned.m64n64k16.f32.bf16.bf16 {%0,%1,%2,%3,%4,%5,%6,%7,%8,%9,%10,%11,%12,%13,%14,%15,%16,%17,%18,%19,%20,%21,%22,%23,%24,%25,%26,%27,%28,%29,%30,%31}, {%32,%33,%34,%35}, %36, p, 1, 1, 0;\n}\n"
   : "+f"(d[0]),"+f"(d[1]),"+f"(d[2]),"+f"(d[3]),"+f"(d[4]),"+f"(d[5]),"+f"(d[6]),"+f"(d[7]),"+f"(d[8]),"+f"(d[9]),"+f"(d[10]),"+f"(d[11]),"+f"(d[12]),"+f"(d[13]),"+f"(d[14]),"+f"(d[15]),"+f"(d[16]),"+f"(d[17]),"+f"(d[18]),"+f"(d[19]),"+f"(d[20]),"+f"(d[21]),"+f"(d[22]),"+f"(d[23]),"+f"(d[24]),"+f"(d[25]),"+f"(d[26]),"+f"(d[27]),"+f"(d[28]),"+f"(d[29]),"+f"(d[30]),"+f"(d[31])
   : "r"(a[0]), "r"(a[1]), "r"(a[2]), "r"(a[3]), "l"(db), "r"(sd));
}
template<> __device__ __forceinline__ void wgmma_ss<64,0,1>(float* d, uint64_t da, uint64_t db, int sd) {
  asm volatile("{\n.reg .pred p;\nsetp.ne.b32 p, %34, 0;\nwgmma.mma_async.sync.aligned.m64n64k16.f32.bf16.bf16 {%0,%1,%2,%3,%4,%5,%6,%7,%8,%9,%10,%11,%12,%13,%14,%15,%16,%17,%18,%19,%20,%21,%22,%23,%24,%25,%26,%27,%28,%29,%30,%31}, %32, %33, p, 1, 1, 0, 1;\n}\n"
   : "+f"(d[0]),"+f"(d[1]),"+f"(d[2]),"+f"(d[3]),"+f"(d[4]),"+f"(d[5]),"+f"(d[6]),"+f"(d[7]),"+f"(d[8]),"+f"(d[9]),"+f"(d[10]),"+f"(d[11]),"+f"(d[12]),"+f"(d[13]),"+f"(d[14]),"+f"(d[15]),"+f"(d[16]),"+f"(d[17]),"+f"(d[18]),"+f"(d[19]),"+f"(d[20]),"+f"(d[21]),"+f"(d[22]),"+f"(d[23]),"+f"(d[24]),"+f"(d[25]),"+f"(d[26]),"+f"(d[27]),"+f"(d[28]),"+f"(d[29]),"+f"(d[30]),"+f"(d[31])
   : "l"(da), "l"(db), "r"(sd));
}
template<> __device__ __forceinline__ void wgmma_ss<64,1,1>(float* d, uint64_t da, uint64_t db, int sd) {
  asm volatile("{\n.reg .pred p;\nsetp.ne.b32 p, %34, 0;\nwgmma.mma_async.sync.aligned.m64n64k16.f32.bf16.bf16 {%0,%1,%2,%3,%4,%5,%6,%7,%8,%9,%10,%11,%12,%13,%14,%15,%16,%17,%18,%19,%20,%21,%22,%23,%24,%25,%26,%27,%28,%29,%30,%31}, %32, %33, p, 1, 1, 1, 1;\n}\n"
   : "+f"(d[0]),"+f"(d[1]),"+f"(d[2]),"+f"(d[3]),"+f"(d[4]),"+f"(d[5]),"+f"(d[6]),"+f"(d[7]),"+f"(d[8]),"+f"(d[9]),"+f"(d[10]),"+f"(d[11]),"+f"(d[12]),"+f"(d[13]),"+f"(d[14]),"+f"(d[15]),"+f"(d[16]),"+f"(d[17]),"+f"(d[18]),"+f"(d[19]),"+f"(d[20]),"+f"(d[21]),"+f"(d[22]),"+f"(d[23]),"+f"(d[24]),"+f"(d[25]),"+f"(d[26]),"+f"(d[27]),"+f"(d[28]),"+f"(d[29]),"+f"(d[30]),"+f"(d[31])
   : "l"(da), "l"(db), "r"(sd));
}
template<> __device__ __forceinline__ void wgmma_ss<192,0,1>(float* d, uint64_t da, uint64_t db, int sd) {
  asm volatile("{\n.reg .pred p;\nsetp.ne.b32 p, %98, 0;\nwgmma.mma_async.sync.aligned.m64n192k16.f32.bf16.bf16 {%0,%1,%2,%3,%4,%5,%6,%7,%8,%9,%10,%11,%12,%13,%14,%15,%16,%17,%18,%19,%20,%21,%22,%23,%24,%25,%26,%27,%28,%29,%30,%31,%32,%33,%34,%35,%36,%37,%38,%39,%40,%41,%42,%43,%44,%45,%46,%47,%48,%49,%50,%51,%52,%53,%54,%55,%56,%57,%58,%59,%60,%61,%62,%63,%64,%65,%66,%67,%68,%69,%70,%71,%72,%73,%74,%75,%76,%77,%78,%79,%80,%81,%82,%83,%84,%85,%86,%87,%88,%89,%90,%91,%92,%93,%94,%95}, %96, %97, p, 1, 1, 0, 1;\n}\n"
   : "+f"(d[0]),"+f"(d[1]),"+f"(d[2]),"+f"(d[3]),"+f"(d[4]),"+f"(d[5]),"+f"(d[6]),"+f"(d[7]),"+f"(d[8]),"+f"(d[9]),"+f"(d[10]),"+f"(d[11]),"+f"(d[12]),"+f"(d[13]),"+f"(d[14]),"+f"(d[15]),"+f"(d[16]),"+f"(d[17]),"+f"(d[18]),"+f"(d[19]),"+f"(d[20]),"+f"(d[21]),"+f"(d[22]),"+f"(d[23]),"+f"(d[24]),"+f"(d[25]),"+f"(d[26]),"+f"(d[27]),"+f"(d[28]),"+f"(d[29]),"+f"(d[30]),"+f"(d[31]),"+f"(d[32]),"+f"(d[33]),"+f"(d[34]),"+f"(d[35]),"+f"(d[36]),"+f"(d[37]),"+f"(d[38]),"+f"(d[39]),"+f"(d[40]),"+f"(d[41]),"+f"(d[42]),"+f"(d[43]),"+f"(d[44]),"+f"(d[45]),"+f"(d[46]),"+f"(d[47]),"+f"(d[48]),"+f"(d[49]),"+f"(d[50]),"+f"(d[51]),"+f"(d[52]),"+f"(d[53]),"+f"(d[54]),"+f"(d[55]),"+f"(d[56]),"+f"(d[57]),"+f"(d[58]),"+f"(d[59]),"+f"(d[60]),"+f"(d[61]),"+f"(d[62]),"+f"(d[63]),"+f"(d[64]),"+f"(d[65]),"+f"(d[66]),"+f"(d[67]),"+f"(d[68]),"+f"(d[69]),"+f"(d[70]),"+f"(d[71]),"+f"(d[72]),"+f"(d[73]),"+f"(d[74]),"+f"(d[75]),"+f"(d[76]),"+f"(d[77]),"+f"(d[78]),"+f"(d[79]),"+f"(d[80]),"+f"(d[81]),"+f"(d[82]),"+f"(d[83]),"+f"(d[84]),"+f"(d[85]),"+f"(d[86]),"+f"(d[87]),"+f"(d[88]),"+f"(d[89]),"+f"(d[90]),"+f"(d[91]),"+f"(d[92]),"+f"(d[93]),"+f"(d[94]),"+f"(d[95])
   : "l"(da), "l"(db), "r"(sd));
}
template<> __device__ __forceinline__ void wgmma_ss<192,1,1>(float* d, uint64_t da, uint64_t db, int sd) {
  asm volatile("{\n.reg .pred p;\nsetp.ne.b32 p, %98, 0;\nwgmma.mma_async.sync.aligned.m64n192k16.f32.bf16.bf16 {%0,%1,%2,%3,%4,%5,%6,%7,%8,%9,%10,%11,%12,%13,%14,%15,%16,%17,%18,%19,%20,%21,%22,%23,%24,%25,%26,%27,%28,%29,%30,%31,%32,%33,%34,%35,%36,%37,%38,%39,%40,%41,%42,%43,%44,%45,%46,%47,%48,%49,%50,%51,%52,%53,%54,%55,%56,%57,%58,%59,%60,%61,%62,%63,%64,%65,%66,%67,%68,%69,%70,%71,%72,%73,%74,%75,%76,%77,%78,%79,%80,%81,%82,%83,%84,%85,%86,%87,%88,%89,%90,%91,%92,%93,%94,%95}, %96, %97, p, 1, 1, 1, 1;\n}\n"
   : "+f"(d[0]),"+f"(d[1]),"+f"(d[2]),"+f"(d[3]),"+f"(d[4]),"+f"(d[5]),"+f"(d[6]),"+f"(d[7]),"+f"(d[8]),"+f"(d[9]),"+f"(d[10]),"+f"(d[11]),"+f"(d[12]),"+f"(d[13]),"+f"(d[14]),"+f"(d[15]),"+f"(d[16]),"+f"(d[17]),"+f"(d[18]),"+f"(d[19]),"+f"(d[20]),"+f"(d[21]),"+f"(d[22]),"+f"(d[23]),"+f"(d[24]),"+f"(d[25]),"+f"(d[26]),"+f"(d[27]),"+f"(d[28]),"+f"(d[29]),"+f"(d[30]),"+f"(d[31]),"+f"(d[32]),"+f"(d[33]),"+f"(d[34]),"+f"(d[35]),"+f"(d[36]),"+f"(d[37]),"+f"(d[38]),"+f"(d[39]),"+f"(d[40]),"+f"(d[41]),"+f"(d[42]),"+f"(d[43]),"+f"(d[44]),"+f"(d[45]),"+f"(d[46]),"+f"(d[47]),"+f"(d[48]),"+f"(d[49]),"+f"(d[50]),"+f"(d[51]),"+f"(d[52]),"+f"(d[53]),"+f"(d[54]),"+f"(d[55]),"+f"(d[56]),"+f"(d[57]),"+f"(d[58]),"+f"(d[59]),"+f"(d[60]),"+f"(d[61]),"+f"(d[62]),"+f"(d[63]),"+f"(d[64]),"+f"(d[65]),"+f"(d[66]),"+f"(d[67]),"+f"(d[68]),"+f"(d[69]),"+f"(d[70]),"+f"(d[71]),"+f"(d[72]),"+f"(d[73]),"+f"(d[74]),"+f"(d[75]),"+f"(d[76]),"+f"(d[77]),"+f"(d[78]),"+f"(d[79]),"+f"(d[80]),"+f"(d[81]),"+f"(d[82]),"+f"(d[83]),"+f"(d[84]),"+f"(d[85]),"+f"(d[86]),"+f"(d[87]),"+f"(d[88]),"+f"(d[89]),"+f"(d[90]),"+f"(d[91]),"+f"(d[92]),"+f"(d[93]),"+f"(d[94]),"+f"(d[95])
   : "l"(da), "l"(db), "r"(sd));
}

__device__ __forceinline__ void stats_publish(uint32_t sb, int layer, int rb, int hg, int ht, uint32_t tag) {
  const int lane = ht & 31, w = ht >> 5, g = lane >> 2, t = lane & 3;
  mbar_wait(sb + SM_BAR + 8 * (B_XF + hg), layer);
  uint32_t A[2][16];
#pragma unroll
  for (int h = 0; h < 2; h++) {
    const uint32_t xb = sb + SM_X + hg * 16384 + h * 8192;
#pragma unroll
    for (int ks = 0; ks < 4; ks++) {
      if (layer == 0) {
        const int row = 16 * w + (lane & 15), kc = 2 * ks + (lane >> 4);
        ldsm4(&A[h][4 * ks], xb + row * 128 + ((kc ^ (row & 7)) << 4));
      } else {
        const int k = 16 * ks + (lane & 7) + 8 * (lane >> 4), pc = 2 * w + ((lane >> 3) & 1);
        ldsm4t(&A[h][4 * ks], xb + k * 128 + ((pc ^ (k & 7)) << 4));
      }
    }
  }
  float s[4], q[4];
#pragma unroll
  for (int r = 0; r < 4; r++) {
    s[r] = q[r] = 0.f;
#pragma unroll
    for (int i = 0; i < 8; i++) {
      const uint32_t v = A[r >> 1][2 * i + (r & 1)];
      const float a = bf_lo(v), b = bf_hi(v);
      s[r] += a + b; q[r] = fmaf(a, a, q[r]); q[r] = fmaf(b, b, q[r]);
    }
  }
#pragma unroll
  for (int r = 0; r < 2; r++) {
    s[r] = ((t & 2) ? s[r + 2] : s[r]) + __shfl_xor_sync(~0u, (t & 2) ? s[r] : s[r + 2], 2);
    q[r] = ((t & 2) ? q[r + 2] : q[r]) + __shfl_xor_sync(~0u, (t & 2) ? q[r] : q[r + 2], 2);
  }
  s[0] = ((t & 1) ? s[1] : s[0]) + __shfl_xor_sync(~0u, (t & 1) ? s[0] : s[1], 1);
  q[0] = ((t & 1) ? q[1] : q[0]) + __shfl_xor_sync(~0u, (t & 1) ? q[0] : q[1], 1);
  st_tagged(&g_part[(rb * 8 + hg) * 128 + 64 * (t >> 1) + 16 * w + 8 * (t & 1) + g], __float_as_uint(s[0]), __float_as_uint(q[0]), tag);
}
__device__ __forceinline__ void stats_gather(uint32_t sb, int rb, int ht, uint32_t tag) {
  const uint4* src = &g_part[rb * 8 * 128 + ht];
  uint4 v[8];
  bool ok;
  int it = 0;
  do {
    ok = true;
#pragma unroll
    for (int i = 0; i < 8; i++) v[i] = ld_tagged(src + i * 128);
#pragma unroll
    for (int i = 0; i < 8; i++) ok = ok && v[i].y == tag && v[i].w == tag;
    if (++it > (1 << 22)) __trap();
  } while (!__all_sync(~0u, ok));
  float s = 0.f, q = 0.f;
#pragma unroll
  for (int i = 0; i < 8; i++) { s += __uint_as_float(v[i].x); q += __uint_as_float(v[i].z); }
  const float mean = s * (1.f / DM);
  const float rstd = rsqrt_approx(fmaxf(q * (1.f / DM) - mean * mean, 0.f) + 1e-5f);
  asm volatile("st.shared.v2.f32 [%0], {%1,%2};" ::"r"(sb + SM_ST + ht * 8), "f"(mean), "f"(rstd) : "memory");
  __syncwarp();
  if (elect_one()) mbar_arrive(sb + SM_BAR + 8 * B_STF);
}

template <bool TR>
__device__ __forceinline__ void gemm_section(float* acc, uint32_t sb, int layer, int wg, int w, int lane) {
  const uint32_t bar = sb + SM_BAR;
  const bool leader = (w == 0) && (lane == 0);
  auto issue = [&](int c, int slot) {
    mbar_wait(bar + 8 * (B_XF + c), layer);
    mbar_wait(bar + 8 * (B_KVF + c), layer);
    const uint64_t da = mkdesc(sb + SM_X + c * 16384 + wg * 8192, TR ? 8192 : 16, 1024, 1);
    const uint64_t db = mkdesc(sb + SM_W + slot * 24576, 8192, 1024, 1);
    wg_fence();
#pragma unroll
    for (int ks = 0; ks < 4; ks++) wgmma_ss<192, TR ? 1 : 0, 1>(acc, da + (TR ? ks * 128 : ks * 2), db + ks * 128, (c | ks) != 0);
    wg_commit();
  };
  auto step = [&](int c, int slot) {
    issue(c, slot);
    wg_wait<1>();
    if (leader) mbar_arrive(bar + 8 * (B_KVE + c - 1));
  };
  issue(0, 0);
  if (threadIdx.x == 0) TS(2 + layer * 20 + 0);
  if (threadIdx.x == 128 && layer == 1) TS(60);
  step(1, 1); step(2, 2); step(3, 0); step(4, 1); step(5, 2);
  issue(6, 0);
  wg_wait<1>();
  if (wg == 0) bar_sync(5, 256);
  issue(7, 1);
  if (wg == 1) bar_arrive(5, 256);
}

__device__ __forceinline__ void attn_phase(const Params& p, uint32_t sb, int layer, int rb, int hg, int wg, int w) {
  const int lane = opaque_tid() & 31;
  const int g = lane >> 2, t = lane & 3;
  const uint32_t bar = sb + SM_BAR;
  const int row0 = 64 * wg + 16 * w;
  const bool leader = (w == 0) && (lane == 0);
  float acc[96];
  float2 cs[24];
  if (layer) gemm_section<true>(acc, sb, layer, wg, w, lane);
  else gemm_section<false>(acc, sb, layer, wg, w, lane);
  mbar_wait(bar + 8 * B_STF, layer);
  const uint32_t tag = 2 * lds32(sb + SM_EP) + layer + 1;
  const float2 st0 = lds64f(sb + SM_ST + (row0 + g) * 8), st1 = lds64f(sb + SM_ST + (row0 + g + 8) * 8);
  const float mean0 = st0.x, rstd0 = st0.y, mean1 = st1.x, rstd1 = st1.y;
#pragma unroll
  for (int j = 8; j < 24; j++) cs[j] = lds64f(sb + SM_CS + 4 * (8 * j + 2 * t));
  wg_wait<0>();
  if (threadIdx.x == 0) TS(2 + layer * 20 + 1);
  if (leader) mbar_arrive(bar + 8 * B_QDONE);

  uint32_t kb[4][8], vb[4][8], qa[4][4];
  {
    const float nm0 = -mean0 * rstd0, nm1 = -mean1 * rstd1;
    const int st_row = row0 + (lane & 7) + 8 * ((lane >> 3) & 1);
    const uint32_t st_base = sb + SM_KVX + st_row * 256;
    const bool sender = (wg == 1 && w == 3 && rb < 15);
    uint4* halo = &g_halo[(rb * 8 + hg) * 384 + lane];
    if (wg == 0 && w == 3) bar_sync(6, 64);
    uint32_t r[4][2][4];
#pragma unroll
    for (int h = 0; h < 4; h++) {
#pragma unroll
      for (int kv = 0; kv < 2; kv++) {
#pragma unroll
        for (int dh = 0; dh < 2; dh++) {
          const int j = 8 + kv * 8 + 2 * h + dh;
          const float2 c2 = cs[j];
          const float v0 = fmaf(acc[4 * j + 0], rstd0, nm0 * c2.x), v1 = fmaf(acc[4 * j + 1], rstd0, nm0 * c2.y);
          const float v2 = fmaf(acc[4 * j + 2], rstd1, nm1 * c2.x), v3 = fmaf(acc[4 * j + 3], rstd1, nm1 * c2.y);
          r[h][kv][2 * dh] = packbf(v0, v1);
          r[h][kv][2 * dh + 1] = packbf(v2, v3);
        }
      }
      if (sender) {
        st_tagged3(halo + (3 * h) * 32, r[h][0][0], r[h][0][1], r[h][0][2], tag);
        st_tagged3(halo + (3 * h + 1) * 32, r[h][0][3], r[h][1][0], r[h][1][1], tag);
        st_tagged3(halo + (3 * h + 2) * 32, r[h][1][2], r[h][1][3], 0u, tag);
      }
    }
    if (wg == 1 && w == 3) bar_arrive(6, 64);
    if (layer == 1 && threadIdx.x == 224) TS(47);
#pragma unroll
    for (int j = 0; j < 8; j++) cs[j] = lds64f(sb + SM_CS + 4 * (8 * j + 2 * t));
    mbar_wait(bar + 8 * B_QDONE, layer);
#pragma unroll
    for (int h = 0; h < 4; h++) {
#pragma unroll
      for (int kv = 0; kv < 2; kv++) {
        const int chunk = 4 * h + 2 * kv + (lane >> 4);
        stsm4(st_base + (((chunk & 8) | ((chunk ^ st_row) & 7)) << 4), r[h][kv][0], r[h][kv][1], r[h][kv][2], r[h][kv][3]);
      }
      kb[h][4] = r[h][0][0]; kb[h][5] = r[h][0][2]; kb[h][6] = r[h][0][1]; kb[h][7] = r[h][0][3];
      vb[h][4] = movm_t(r[h][1][0]); vb[h][5] = movm_t(r[h][1][1]); vb[h][6] = movm_t(r[h][1][2]); vb[h][7] = movm_t(r[h][1][3]);
    }
    if (layer == 1 && threadIdx.x == 0) TS(45);
#pragma unroll
    for (int h = 0; h < 4; h++) {
#pragma unroll
      for (int dh = 0; dh < 2; dh++) {
        const int j = 2 * h + dh;
        const float2 c2 = cs[j];
        qa[h][2 * dh] = packbf(fmaf(-mean0, c2.x, acc[4 * j + 0]), fmaf(-mean0, c2.y, acc[4 * j + 1]));
        qa[h][2 * dh + 1] = packbf(fmaf(-mean1, c2.x, acc[4 * j + 2]), fmaf(-mean1, c2.y, acc[4 * j + 3]));
      }
    }
  }
  bar_sync(1, 256);
  if (threadIdx.x == 0) TS(2 + layer * 20 + 2);
  {
    const uint32_t own_base = sb + SM_KVX + row0 * 256;
    const int mi = lane >> 3;
    const int r = 8 * (mi >> 1) + (lane & 7), r2 = 8 * (mi & 1) + (lane & 7);
    if (row0 != 0) {
#pragma unroll
      for (int h = 0; h < 4; h++) {
        const int ch = 4 * h + (mi & 1), ch2 = 4 * h + 2 + (mi >> 1);
        ldsm4(&kb[h][0], own_base - 16 * 256 + r * 256 + (((ch & 8) | ((ch ^ r) & 7)) << 4));
        ldsm4t(&vb[h][0], own_base - 16 * 256 + r2 * 256 + (((ch2 & 8) | ((ch2 ^ r2) & 7)) << 4));
      }
    } else if (rb > 0) {
      const uint4* src = &g_halo[((rb - 1) * 8 + hg) * 384 + lane];
      uint4 hv[12];
      int it = 0;
      bool ok;
      do {
        ok = true;
#pragma unroll
        for (int i = 0; i < 12; i++) hv[i] = ld_tagged(src + i * 32);
#pragma unroll
        for (int i = 0; i < 12; i++) ok = ok && hv[i].w == tag;
      } while (!__all_sync(~0u, ok) && ++it < (1 << 20));
      if (lane == 0) mbar_arrive(bar + 8 * B_HF);
#pragma unroll
      for (int h = 0; h < 4; h++) {
        kb[h][0] = hv[3 * h].x; kb[h][1] = hv[3 * h].z; kb[h][2] = hv[3 * h].y; kb[h][3] = hv[3 * h + 1].x;
        vb[h][0] = movm_t(hv[3 * h + 1].y); vb[h][1] = movm_t(hv[3 * h + 1].z);
        vb[h][2] = movm_t(hv[3 * h + 2].x); vb[h][3] = movm_t(hv[3 * h + 2].y);
      }
    } else {
#pragma unroll
      for (int h = 0; h < 4; h++)
#pragma unroll
        for (int k = 0; k < 4; k++) kb[h][k] = vb[h][k] = 0u;
    }
    if (threadIdx.x == 0) TS(2 + layer * 20 + 4);
  }

  const bool first = (rb == 0 && wg == 0 && w == 0);
  const int e = t - (g >> 1);
  const bool par = g & 1, epos = e >= 1;
  const uint32_t pmask = par ? 0xffff0000u : 0x0000ffffu;
  const uint32_t mB0 = epos ? pmask : 0u, mB1 = epos ? 0u : pmask;
  const float cl2 = 0.25f * 1.4426950408889634f;
  const float sc0 = rstd0 * cl2, sc1 = rstd1 * cl2;
  const float NEG = -INFINITY;
  float vA0[4], vB0[4], vA1[4], vB1[4];
#pragma unroll
  for (int h = 0; h < 4; h++) {
    float S[4][4];
#pragma unroll
    for (int j = 0; j < 4; j++) {
      S[j][0] = S[j][1] = S[j][2] = S[j][3] = 0.f;
      mma_bf16(S[j], qa[h], kb[h][2 * j], kb[h][2 * j + 1]);
    }
    vA0[h] = par ? S[1][1] : S[1][0];
    vB0[h] = epos ? (par ? S[0][1] : S[0][0]) : (par ? S[2][1] : S[2][0]);
    vA1[h] = par ? S[2][3] : S[2][2];
    vB1[h] = epos ? (par ? S[1][3] : S[1][2]) : (par ? S[3][3] : S[3][2]);
    if (first) { vA0[h] = NEG; if (epos) { vB0[h] = NEG; vB1[h] = NEG; } }
  }
  float m0[4], m1[4];
#pragma unroll
  for (int h = 0; h < 4; h++) { m0[h] = fmaxf(vA0[h], vB0[h]); m1[h] = fmaxf(vA1[h], vB1[h]); }
#pragma unroll
  for (int o = 1; o <= 2; o <<= 1) {
#pragma unroll
    for (int h = 0; h < 4; h++) {
      m0[h] = fmaxf(m0[h], __shfl_xor_sync(~0u, m0[h], o));
      m1[h] = fmaxf(m1[h], __shfl_xor_sync(~0u, m1[h], o));
    }
  }
  float O0[4][4], O1[4][4], Z[4][4];
#pragma unroll
  for (int h = 0; h < 4; h++) {
    const float mm0 = -m0[h] * sc0, mm1 = -m1[h] * sc1;
    const float pA0 = ex2(fmaf(vA0[h], sc0, mm0)), pB0 = ex2(fmaf(vB0[h], sc0, mm0));
    const float pA1 = ex2(fmaf(vA1[h], sc1, mm1)), pB1 = ex2(fmaf(vB1[h], sc1, mm1));
    const uint32_t hA0 = packbf(pA0, pA0), hB0 = packbf(pB0, pB0), hA1 = packbf(pA1, pA1), hB1 = packbf(pB1, pB1);
    const uint32_t P0[4] = {hB0 & mB0, 0u, hA0 & pmask, hB1 & mB0};
    const uint32_t P1[4] = {hB0 & mB1, hA1 & pmask, 0u, hB1 & mB1};
#pragma unroll
    for (int k = 0; k < 4; k++) O0[h][k] = O1[h][k] = Z[h][k] = 0.f;
    mma_bf16(O0[h], P0, vb[h][0], vb[h][1]); mma_bf16(O1[h], P0, vb[h][2], vb[h][3]); mma_bf16(Z[h], P0, 0x3f803f80u, 0x3f803f80u);
    mma_bf16(O0[h], P1, vb[h][4], vb[h][5]); mma_bf16(O1[h], P1, vb[h][6], vb[h][7]); mma_bf16(Z[h], P1, 0x3f803f80u, 0x3f803f80u);
  }
  const uint32_t ob = sb + SM_OST + wg * 8192;
  const int o_row = 16 * w + (lane & 7) + 8 * ((lane >> 3) & 1);
#pragma unroll
  for (int h = 0; h < 4; h++) {
    const float i0 = rcp_approx(Z[h][0]), i1 = rcp_approx(Z[h][2]);
    const int ch = 2 * h + (lane >> 4);
    stsm4(ob + o_row * 128 + ((ch ^ (o_row & 7)) << 4), packbf(O0[h][0] * i0, O0[h][1] * i0), packbf(O0[h][2] * i1, O0[h][3] * i1),
          packbf(O1[h][0] * i0, O1[h][1] * i0), packbf(O1[h][2] * i1, O1[h][3] * i1));
  }
  if (threadIdx.x == 0) TS(2 + layer * 20 + 5);
  fence_async_smem();
  bar_sync(2 + wg, 128);
  if (w == 0 && elect_one()) {
    tma_st(&p.mapO, hg * 64, rb * 128 + wg * 64, ob);
    bulk_commit();
    mbar_arrive(bar + 8 * B_AD);
    bulk_wait_all();
    red_relaxed(&g_cnt[(C_O + rb) * 32]);
    mbar_arrive(bar + 8 * B_OST);
    if (threadIdx.x == 0) TS(2 + layer * 20 + 6);
  }
}

__device__ __forceinline__ void proj_phase(const Params& p, uint32_t sb, int layer, int rb, int q, int wg, int w) {
  const int lane = opaque_tid() & 31;
  const bool TR = layer != 0;
  const int t = lane & 3;
  const uint32_t bar = sb + SM_BAR;
  const uint32_t rbx = sb + SM_R + wg * 8192;
  uint32_t res[16];
  mbar_wait(bar + 8 * B_RF, layer);
  if (threadIdx.x == 0) TS(2 + layer * 20 + 7);
  if (!TR) {
#pragma unroll
    for (int j = 0; j < 8; j += 2) {
      const int mi = lane >> 3;
      const int row = 16 * w + (lane & 7) + 8 * (mi & 1), ch = j + (mi >> 1);
      ldsm4(&res[2 * j], rbx + row * 128 + ((ch ^ (row & 7)) << 4));
    }
  } else {
#pragma unroll
    for (int j = 0; j < 8; j += 2) {
      const int mi = lane >> 3;
      const int line = 8 * (j + (mi >> 1)) + (lane & 7), pc = 2 * w + (mi & 1);
      ldsm4t(&res[2 * j], rbx + line * 128 + ((pc ^ (line & 7)) << 4));
    }
  }
  bar_sync(2 + wg, 128);
  float acc[32];
#pragma unroll
  for (int i = 0; i < 32; i++) acc[i] = 0.f;
#pragma unroll 1
  for (int c = 0; c < 8; c++) {
    if ((c & 1) == 0) mbar_wait(bar + 8 * (B_WOF + (c >> 1)), layer);
    mbar_wait(bar + 8 * (B_OF + c), layer);
    if (c == 0 && threadIdx.x == 0) TS(2 + layer * 20 + 8);
    const uint64_t da = mkdesc(sb + (c < 4 ? SM_X + 65536 + c * 16384 : SM_W + (c - 4) * 16384) + wg * 8192, 16, 1024, 1);
    const uint64_t db = mkdesc(sb + SM_X + c * 8192, 8192, 1024, 1);
    wg_fence();
#pragma unroll
    for (int ks = 0; ks < 4; ks++) wgmma_ss<64, 0, 1>(acc, da + ks * 2, db + ks * 128, 1);
    wg_commit();
  }
  wg_wait<0>();
  if (threadIdx.x == 0) TS(2 + layer * 20 + 9);
  if (lane == 0 && w == 0) mbar_arrive(bar + 8 * B_PDONE);
  float s0 = 0.f, q0 = 0.f, s1 = 0.f, q1 = 0.f;
  uint32_t o[16];
#pragma unroll
  for (int j = 0; j < 8; j++) {
    const uint32_t r0 = res[2 * j], r1 = res[2 * j + 1];
    o[2 * j] = packbf(acc[4 * j] + bf_lo(r0), acc[4 * j + 1] + bf_hi(r0));
    o[2 * j + 1] = packbf(acc[4 * j + 2] + bf_lo(r1), acc[4 * j + 3] + bf_hi(r1));
    const float a = bf_lo(o[2 * j]), b = bf_hi(o[2 * j]), c = bf_lo(o[2 * j + 1]), d = bf_hi(o[2 * j + 1]);
    s0 += a + b; q0 = fmaf(a, a, q0); q0 = fmaf(b, b, q0);
    s1 += c + d; q1 = fmaf(c, c, q1); q1 = fmaf(d, d, q1);
  }
#pragma unroll
  for (int j = 0; j < 8; j += 2) {
    const int mi = lane >> 3;
    const int line = 8 * (j + (mi >> 1)) + (lane & 7), pc = 2 * w + (mi & 1);
    stsm4t(rbx + line * 128 + ((pc ^ (line & 7)) << 4), o[2 * j], o[2 * j + 1], o[2 * j + 2], o[2 * j + 3]);
  }
#pragma unroll
  for (int o2 = 1; o2 <= 2; o2 <<= 1) {
    s0 += __shfl_xor_sync(~0u, s0, o2); q0 += __shfl_xor_sync(~0u, q0, o2);
    s1 += __shfl_xor_sync(~0u, s1, o2); q1 += __shfl_xor_sync(~0u, q1, o2);
  }
  const uint32_t stg = sb + SM_HALO + wg * 512;
  {
    const int row = 16 * w + (lane >> 2) + 8 * (t >> 1);
    const float v = (t == 0) ? s0 : (t == 1) ? q0 : (t == 2) ? s1 : q1;
    sts32f(stg + 4 * (((((row & 7) >> 1) * 8 + (row >> 3)) << 2) + (row & 1) * 2 + (t & 1)), v);
  }
  fence_async_smem();
  bar_sync(2 + wg, 128);
  if (w == 0 && elect_one()) {
    mbar_wait(bar + 8 * B_ZF, 0);
    tma_st(&p.mapXT, rb * 128 + wg * 64, (2 * layer) * DM + q * 64, rbx);
    bulk_red_add_f32(g_stats + layer * LSEQ * 2 + (rb * 2 + wg) * 128, stg, 512);
    bulk_commit();
    bulk_wait_all();
    red_relaxed(&g_cnt[(layer ? C_G2 : C_G0) * 32]);
    if (threadIdx.x == 0) TS(2 + layer * 20 + 10);
  }
}

template <int M0, int M1> __device__ __forceinline__ void conv_load(uint32_t* A, uint32_t pe) {
#pragma unroll
  for (int m = M0; m < M1; m++) {
    A[4 * m + 2] = lds32(pe + 4 * (64 * m - 8));
    A[4 * m + 0] = lds32(pe + 4 * (64 * m));
    A[4 * m + 1] = lds32(pe + 4 * (64 * m + 8));
  }
#pragma unroll
  for (int m = M0; m < M1; m++) asm volatile("mov.b32 %0, %1;" : "=r"(A[4 * m + 3]) : "r"(A[4 * m + 0]));
}
#define NPRE 12
__device__ __forceinline__ void conv_park(uint32_t* P, uint32_t pe) {
#pragma unroll
  for (int m = 0; m < NPRE; m++)
#pragma unroll
    for (int k = 0; k < 3; k++) P[3 * m + k] = lds32(pe + 4 * (64 * m - 8 + 8 * k));
}
__device__ __forceinline__ void conv_unpark(uint32_t* A, const uint32_t* P) {
#pragma unroll
  for (int m = 0; m < NPRE; m++) {
    asm volatile("mov.b32 %0, %1;" : "=r"(A[4 * m + 2]) : "r"(P[3 * m]));
    asm volatile("mov.b32 %0, %1;" : "=r"(A[4 * m + 0]) : "r"(P[3 * m + 1]));
    asm volatile("mov.b32 %0, %1;" : "=r"(A[4 * m + 3]) : "r"(P[3 * m + 1]));
    asm volatile("mov.b32 %0, %1;" : "=r"(A[4 * m + 1]) : "r"(P[3 * m + 2]));
  }
}
template <int M> __device__ __forceinline__ void conv_mma(float* acc, const uint32_t* A, uint64_t d) {
  wgmma_rs<128 - 8 * (M / 2), 0>(acc, A + 4 * M, d + (uint64_t)(4 * M), M != 0);
}
template <int M0, int M1> __device__ __forceinline__ void conv_mmas(float* acc, const uint32_t* A, uint64_t d) {
  if constexpr (M0 < M1) { conv_mma<M0>(acc, A, d); conv_mmas<M0 + 1, M1>(acc, A, d); }
}
__device__ __forceinline__ void conv_sums(uint32_t sb, int lc, int c, uint4 own) {
  const int m = c == 127 ? -1 : c;
  if (c == 127) own = make_uint4(0, 0, 0, 0);
  const uint32_t up = m >= 1 ? ((m - 1) & 1) * CV_UH + (127 - ((m - 1) >> 1)) * 16 + 8 : 128 * 16;
  const uint32_t un = ((m + 1) & 1) * CV_UH + (127 - ((m + 1) >> 1)) * 16;
  const bool odd = c & 1;
  const float2 v0 = lds64f(sb + cv_u(lc) + (odd ? un : up)), v1 = lds64f(sb + cv_u(lc) + (odd ? up : un));
  const uint32_t x[8] = {__float_as_uint(odd ? v1.x : v0.x), __float_as_uint(odd ? v1.y : v0.y), own.x, own.y, own.z, own.w,
                         __float_as_uint(odd ? v0.x : v1.x), __float_as_uint(odd ? v0.y : v1.y)};
  float pv[16];
#pragma unroll
  for (int k = 0; k < 8; k++) { pv[2 * k] = bf_lo(x[k]); pv[2 * k + 1] = bf_hi(x[k]); }
  float sf[8], pf[8], s9[8], s7[8];
  sf[7] = pv[7]; pf[0] = pv[8];
#pragma unroll
  for (int i = 6; i >= 0; i--) sf[i] = sf[i + 1] + pv[i];
#pragma unroll
  for (int i = 1; i < 8; i++) pf[i] = pf[i - 1] + pv[8 + i];
#pragma unroll
  for (int i = 0; i < 8; i++) {
    s9[i] = sf[i] + pf[i];
    s7[i] = i == 0 ? sf[1] : i == 7 ? pf[6] : sf[i + 1] + pf[i - 1];
  }
  const int ce = (m + 2) & 127, co = m + 1;
  uint4 e4 = make_uint4(packbf(s9[0], s9[1]), packbf(s9[2], s9[3]), packbf(s9[4], s9[5]), packbf(s9[6], s9[7]));
  if (ce == 0) e4 = make_uint4(0, 0, 0, 0);
  sts128(sb + cv_s(lc) + ((ce >> 3) & 1) * 1024 + (ce >> 4) * 128 + (((ce ^ (ce >> 4)) & 7) << 4), e4);
  sts128(sb + cv_s(lc) + 2048 + ((co >> 3) & 1) * 1024 + (co >> 4) * 128 + (((co ^ (co >> 4)) & 7) << 4),
         make_uint4(packbf(s7[0], s7[1]), packbf(s7[2], s7[3]), packbf(s7[4], s7[5]), packbf(s7[6], s7[7])));
}

__device__ __forceinline__ void conv_epi(uint32_t sb, int layer, int ch, int c0, uint4 x0, uint4 x1) {
  uint4 v[2][4];
  const uint4 xr[2] = {x0, x1};
  mbar_wait(sb + SM_BAR + 8 * (B_P + ch), layer);
#pragma unroll
  for (int u = 0; u < 2; u++) {
    const int c = c0 + 128 * u;
    const uint32_t pb = sb + cv_pb(ch) + (c ^ ((c >> 3) & 1)) * 16;
#pragma unroll
    for (int k = 0; k < 4; k++) v[u][k] = lds128(pb + k * CV_PBW);
  }
#pragma unroll
  for (int u = 0; u < 2; u++) {
    uint4 o;
    o.x = hadd2(xr[u].x, hadd2(hadd2(v[u][0].x, v[u][1].x), hadd2(v[u][2].x, v[u][3].x)));
    o.y = hadd2(xr[u].y, hadd2(hadd2(v[u][0].y, v[u][1].y), hadd2(v[u][2].y, v[u][3].y)));
    o.z = hadd2(xr[u].z, hadd2(hadd2(v[u][0].z, v[u][1].z), hadd2(v[u][2].z, v[u][3].z)));
    o.w = hadd2(xr[u].w, hadd2(hadd2(v[u][0].w, v[u][1].w), hadd2(v[u][2].w, v[u][3].w)));
    sts128(sb + cv_s(ch) + (c0 + 128 * u) * 16, o);
  }
}
__device__ __forceinline__ void warp_release(uint32_t b) {
  fence_async_smem();
  __syncwarp();
  if (elect_one()) mbar_arrive(b);
}

__device__ __forceinline__ void conv_prep_load(uint32_t sb, int layer, int cta, int c, uint4 (&xr)[4], uint4 (&st)[4]) {
  const bf16* xin = g_xT + (size_t)(2 * layer) * DM * LSEQ;
  mbar_wait(sb + SM_BAR + 8 * B_GB, layer);
  if (threadIdx.x == 0) TS(2 + layer * 20 + 11);
#pragma unroll
  for (int i = 0; i < 4; i++) st[i] = ldcg128(g_stats + layer * LSEQ * 2 + ((c >> 3) * 4 + i) * 32 + (c & 7) * 4);
#pragma unroll
  for (int i = 0; i < 4; i++) xr[i] = ldcg128(xin + (size_t)cv_chan(cta, i) * LSEQ + c * 8);
}
__device__ __forceinline__ void conv_prep(uint32_t sb, int layer, int c, const uint4 (&xr)[4], const uint4 (&st)[4], uint4 (&un)[4]) {
  const uint32_t bar = sb + SM_BAR;
  float nm[8], rstd[8];
#pragma unroll
  for (int i = 0; i < 4; i++) {
    const float m0 = __uint_as_float(st[i].x) * (1.f / DM), m1 = __uint_as_float(st[i].z) * (1.f / DM);
    rstd[2 * i] = rsqrt_approx(fmaxf(fmaf(__uint_as_float(st[i].y), 1.f / DM, -m0 * m0), 0.f) + 1e-5f);
    rstd[2 * i + 1] = rsqrt_approx(fmaxf(fmaf(__uint_as_float(st[i].w), 1.f / DM, -m1 * m1), 0.f) + 1e-5f);
    nm[2 * i] = -m0 * rstd[2 * i]; nm[2 * i + 1] = -m1 * rstd[2 * i + 1];
  }
  if (threadIdx.x == 0) TS(2 + layer * 20 + 12);
  const int a = c >> 1, h = c & 1;
#pragma unroll
  for (int i = 0; i < 4; i++) {
    const uint32_t x[4] = {xr[i].x, xr[i].y, xr[i].z, xr[i].w};
    uint32_t u[4];
#pragma unroll
    for (int k = 0; k < 4; k++)
      u[k] = packbf(fmaf(bf_lo(x[k]), rstd[2 * k], nm[2 * k]), fmaf(bf_hi(x[k]), rstd[2 * k + 1], nm[2 * k + 1]));
    un[i] = make_uint4(u[0], u[1], u[2], u[3]);
    sts128(sb + cv_u(i) + h * CV_UH + (127 - a) * 16, un[i]);
    warp_release(bar + 8 * (B_U + i));
  }
}
__device__ __forceinline__ void conv_zero(uint32_t sb, int ht) {
  if (ht < 96) {
    const int ch = ht / 24, h2 = (ht / 12) & 1, qq = ht % 12;
    sts128(sb + cv_u(ch) + h2 * CV_UH + (128 + qq) * 16, make_uint4(0, 0, 0, 0));
  }
  if (ht >= 80) {
    const int i = ht - 80, ch = i / 12, q2 = i % 12;
    const int w2 = q2 < 2 ? 1 : q2 < 6 ? 2 : 3, cc = q2 < 2 ? q2 : q2 < 6 ? q2 - 2 : q2 - 6;
    sts128(sb + cv_pb(ch) + w2 * CV_PBW + cc * 16, make_uint4(0, 0, 0, 0));
  }
}

#define HANDOVER 1
__device__ __forceinline__ void conv_phase(const Params& p, uint32_t sb, int layer, int cta) {
  const int tid = opaque_tid();
  const int wg = __shfl_sync(~0u, tid >> 7, 0), w = __shfl_sync(~0u, (tid >> 5) & 3, 0);
  const uint32_t bar = sb + SM_BAR;
  uint32_t A[68], P[3 * NPRE + 1];
  {
    const uint32_t pe = sb + cv_pe(1 - wg) + 4 * (16 + 16 * w + ((tid & 31) >> 2) - 2 * (tid & 3));
    if (wg == 0) {
      uint4 xr[4], st[4], un[4];
      conv_prep_load(sb, layer, cta, tid + 128, xr, st);
      mbar_wait(bar + 8 * B_PE, layer);
      conv_load<0, 17>(A, pe);
      conv_park(P, pe + 65536);
      conv_prep(sb, layer, opaque_tid() + 128, xr, st, un);
    } else {
      mbar_wait(bar + 8 * B_PE, layer);
      conv_load<0, 17>(A, pe);
      conv_park(P, pe + 65536);
    }
  }
#pragma unroll 1
  for (int r = 0; r < 2; r++) {
    const int ch = 2 * r + 1 - wg;
    float acc[64];
    const uint64_t d = mkdesc(sb + cv_u(ch), CV_UH, 128, 0);
    const bool leader = (opaque_tid() & 127) == 0;
    FTS(39);
    mbar_wait(bar + 8 * (B_U + ch), layer);
    if (ch > 0) mbar_wait(bar + 8 * (B_T + ch - 1), layer);
    FTS(41);
    if (ch == 0 && threadIdx.x == 128) TS(2 + layer * 20 + 13);
    wg_fence();
    conv_mma<0>(acc, A, d);
    conv_mmas<2, 17>(acc, A, d);
    wg_commit();
    FTS(51);
    mbar_wait(bar + 8 * (B_S + ch), layer);
    if (HANDOVER == 0) mbar_arrive_if(bar + 8 * (B_T + ch), leader);
    wg_fence();
    conv_mma<1>(acc, A, d);
    if (HANDOVER == 1) mbar_arrive_if(bar + 8 * (B_T + ch), leader);
    wgmma_ss<64, 1, 1>(acc, mkdesc(sb + cv_s(ch), 1024, 1024, 1), mkdesc(sb + cv_ft(ch), 256, 16, 0), 1);
    if (HANDOVER == 2) mbar_arrive_if(bar + 8 * (B_T + ch), leader);
    wgmma_ss<64, 1, 1>(acc, mkdesc(sb + cv_s(ch) + 2048, 1024, 1024, 1), mkdesc(sb + cv_ft(ch) + 512, 256, 16, 0), 1);
    wg_commit();
    if (HANDOVER == 3) mbar_arrive_if(bar + 8 * (B_T + ch), leader);
    FTS(61);
    wg_wait<0>();
    const int l2 = opaque_tid() & 31;
    FTS(20);
    const uint32_t pb = sb + cv_pb(ch) + w * CV_PBW;
#pragma unroll
    for (int j = 0; j < 16; j += 2) {
      const int mt = l2 >> 3;
      const int a = 127 - (8 * (j + (mt >> 1)) + (l2 & 7));
      int c = 2 * (a + w) + (mt & 1);
      c ^= (c >> 3) & 1;
      stsm4t(pb + c * 16, packbf(acc[4 * j], acc[4 * j + 1]), packbf(acc[4 * j + 2], acc[4 * j + 3]),
             packbf(acc[4 * j + 4], acc[4 * j + 5]), packbf(acc[4 * j + 6], acc[4 * j + 7]));
    }
    __syncwarp();
    if (elect_one()) mbar_arrive(bar + 8 * (B_P + ch));
    if (threadIdx.x == 0) TS(2 + layer * 20 + 14 + r);
    FTS(57);
    if (r == 0) {
      conv_unpark(A, P);
      conv_load<NPRE, 17>(A, sb + cv_pe(3 - wg) + 4 * (16 + 16 * w + (l2 >> 2) - 2 * (l2 & 3)));
    }
  }
  if (wg == 1 && layer == 0) mbar_wait(bar + 8 * (B_T + 3), layer);
}

__device__ __forceinline__ void final_phase(const Params& p, uint32_t sb, int cta, int wg, int w) {
  if (wg == 1 && w == 3) return;
  const int lane = opaque_tid() & 31, g = lane >> 2, t = lane & 3;
  const int lc = wg ? w : 3;
  const int pos0 = (cta & 31) * 64, ch0 = 128 * lc + (cta >> 5) * 32;
  const bf16* src = g_xT + (size_t)(3 * DM + ch0 + 8 * (g >> 1) + (g & 1)) * LSEQ + pos0;
  bf16* dst = p.out + (size_t)pos0 * DM + ch0 + 8 * t;
  spin_until(&g_cnt[(C_F + (cta >> 5)) * 32 + lc], (lds32(sb + SM_EP) + 1) * 32);
  if (wg == 0) {
    if (threadIdx.x == 0) TS(42);
    uint2 v[4];
#pragma unroll
    for (int q = 0; q < 4; q++)
      asm volatile("ld.global.cg.v2.b32 {%0,%1}, [%2];" : "=r"(v[q].x), "=r"(v[q].y) : "l"(src + 2 * q * LSEQ + 16 * w + 4 * t) : "memory");
    dst += (16 * w + 4 * (g >> 1) + (g & 1)) * DM;
    *(uint4*)dst = make_uint4(movm_t(v[0].x), movm_t(v[1].x), movm_t(v[2].x), movm_t(v[3].x));
    *(uint4*)(dst + 2 * DM) = make_uint4(movm_t(v[0].y), movm_t(v[1].y), movm_t(v[2].y), movm_t(v[3].y));
  } else {
    uint4 v[2][4];
#pragma unroll
    for (int h = 0; h < 2; h++)
#pragma unroll
      for (int q = 0; q < 4; q++) v[h][q] = ldcg128(src + 2 * q * LSEQ + 32 * h + 8 * t);
    dst += (8 * (g >> 1) + (g & 1)) * DM;
#pragma unroll
    for (int h = 0; h < 2; h++) {
      *(uint4*)(dst + (32 * h + 0) * DM) = make_uint4(movm_t(v[h][0].x), movm_t(v[h][1].x), movm_t(v[h][2].x), movm_t(v[h][3].x));
      *(uint4*)(dst + (32 * h + 2) * DM) = make_uint4(movm_t(v[h][0].y), movm_t(v[h][1].y), movm_t(v[h][2].y), movm_t(v[h][3].y));
      *(uint4*)(dst + (32 * h + 4) * DM) = make_uint4(movm_t(v[h][0].z), movm_t(v[h][1].z), movm_t(v[h][2].z), movm_t(v[h][3].z));
      *(uint4*)(dst + (32 * h + 6) * DM) = make_uint4(movm_t(v[h][0].w), movm_t(v[h][1].w), movm_t(v[h][2].w), movm_t(v[h][3].w));
    }
  }
  if (threadIdx.x == 0) TS(43);
  if (threadIdx.x == 192) TS(63);
  if (threadIdx.x == 0) LTS(1);
}

struct cplx { float r, i; };
__device__ __forceinline__ cplx cmul(cplx a, cplx b) { return {fmaf(a.r, b.r, -a.i * b.i), fmaf(a.r, b.i, a.i * b.r)}; }
__device__ __forceinline__ cplx csqr(cplx a) { return {fmaf(a.r, a.r, -a.i * a.i), (a.r + a.r) * a.i}; }
__device__ __forceinline__ cplx cexp_l(float ar2, float ai, float l) {
  const float m = ex2(ar2 * l);
  const float x = ai * l;
  return {m * __cosf(x), m * __sinf(x)};
}

__device__ __forceinline__ void colsum_publish(uint32_t sb, int rb, int hg, int ht, uint32_t tag) {
  const int lane = ht & 31, q = lane & 15, h = lane >> 4;
  const uint32_t src = sb + SM_CW + (ht >> 5) * 4096 + h * 128 + (q & 1) * 8;
  float s[4] = {0.f, 0.f, 0.f, 0.f};
#pragma unroll
  for (int r = 0; r < 16; r++) {
    const float2 v = lds64f(src + r * 256 + (((q >> 1) ^ ((2 * r + h) & 7)) << 4));
    s[0] += bf_lo(__float_as_uint(v.x)); s[1] += bf_hi(__float_as_uint(v.x));
    s[2] += bf_lo(__float_as_uint(v.y)); s[3] += bf_hi(__float_as_uint(v.y));
  }
#pragma unroll
  for (int k = 0; k < 4; k++) s[k] += __shfl_xor_sync(~0u, s[k], 16);
  if (h == 0)
    st_tagged3(&g_colsum[(hg * 16 + rb) * 48 + (ht >> 5) * 16 + q], (__float_as_uint(s[0]) & ~7u) | tag, __float_as_uint(s[1]),
               __float_as_uint(s[2]), __float_as_uint(s[3]));
}
__device__ __forceinline__ void colsum_gather(uint32_t sb, int hg, int ht, uint32_t tag) {
  const int lane = ht & 31, rec = (ht >> 5) * 16 + (lane & 15);
  const uint4* src = &g_colsum[(hg * 16 + (lane >> 4) * 8) * 48 + rec];
  uint4 v[8];
  bool ok;
  int it = 0;
  do {
    ok = true;
#pragma unroll
    for (int i = 0; i < 8; i++) v[i] = ld_tagged(src + i * 48);
#pragma unroll
    for (int i = 0; i < 8; i++) ok = ok && (v[i].x & 7u) == tag;
    if (++it > (1 << 22)) __trap();
  } while (!__all_sync(~0u, ok));
  float s[4] = {0.f, 0.f, 0.f, 0.f};
#pragma unroll
  for (int i = 0; i < 8; i++) {
    s[0] += __uint_as_float(v[i].x & ~7u); s[1] += __uint_as_float(v[i].y); s[2] += __uint_as_float(v[i].z); s[3] += __uint_as_float(v[i].w);
  }
#pragma unroll
  for (int k = 0; k < 4; k++) s[k] += __shfl_xor_sync(~0u, s[k], 16);
  if (lane < 16) sts128f(sb + SM_CS + rec * 16, s[0], s[1], s[2], s[3]);
}

__device__ __forceinline__ uint32_t packh(float lo, float hi) { uint32_t r; asm("cvt.rn.f16x2.f32 %0, %1, %2;" : "=r"(r) : "f"(hi), "f"(lo)); return r; }
__device__ __forceinline__ void mma_f16(float* d, uint32_t a0, uint32_t a1, uint32_t a2, uint32_t a3, uint32_t b0, uint32_t b1) {
  asm volatile("mma.sync.aligned.m16n8k16.row.col.f32.f16.f16.f32 {%0,%1,%2,%3}, {%4,%5,%6,%7}, {%8,%9}, {%0,%1,%2,%3};"
      : "+f"(d[0]), "+f"(d[1]), "+f"(d[2]), "+f"(d[3]) : "r"(a0), "r"(a1), "r"(a2), "r"(a3), "r"(b0), "r"(b1));
}
struct HSeed { uint32_t r, i; };
__device__ __forceinline__ HSeed hseed(cplx s) { return {packh(s.r, s.r), packh(s.i, s.i)}; }
__device__ __forceinline__ void hcmul(uint32_t& o_r, uint32_t& o_i, uint32_t br, uint32_t bi, HSeed s) {
  asm("{\n.reg .b32 t, u;\nmul.rn.f16x2 t, %3, %5;\nneg.f16x2 t, t;\nmul.rn.f16x2 u, %3, %4;\nfma.rn.f16x2 %0, %2, %4, t;\nfma.rn.f16x2 %1, %2, %5, u;\n}"
      : "=&r"(o_r), "=&r"(o_i) : "r"(br), "r"(bi), "r"(s.r), "r"(s.i));
}
struct HTile { uint32_t r[4], i[4]; };
__device__ __forceinline__ void tile_set(HTile& t, int k, cplx a, cplx b) { t.r[k] = packh(a.r, b.r); t.i[k] = packh(a.i, b.i); }
__device__ __forceinline__ void tile_upper(HTile& t, HSeed s) { hcmul(t.r[2], t.i[2], t.r[0], t.i[0], s); hcmul(t.r[3], t.i[3], t.r[1], t.i[1], s); }
__device__ __forceinline__ HTile tile_shift(const HTile& t, HSeed s) {
  HTile o;
#pragma unroll
  for (int k = 0; k < 4; k++) hcmul(o.r[k], o.i[k], t.r[k], t.i[k], s);
  return o;
}
__device__ __forceinline__ void tile_put(const HTile& t, uint32_t a) {
  sts128(a, make_uint4(t.r[0], t.r[1], t.r[2], t.r[3]));
  sts128(a + 512, make_uint4(t.i[0], t.i[1], t.i[2], t.i[3]));
}
__device__ __forceinline__ HTile tile_get(uint32_t a) { HTile o; ldsm4t(o.r, a); ldsm4t(o.i, a + 512); return o; }
__device__ __forceinline__ void tile_mma(float* T, const HTile& a0, const HTile& a1, const HTile& b) {
  mma_f16(T, a0.r[0], a0.r[1], a0.r[2], a0.r[3], b.r[0], b.r[1]);
  mma_f16(T, a0.i[0], a0.i[1], a0.i[2], a0.i[3], b.i[0], b.i[1]);
  mma_f16(T, a1.r[0], a1.r[1], a1.r[2], a1.r[3], b.r[2], b.r[3]);
  mma_f16(T, a1.i[0], a1.i[1], a1.i[2], a1.i[3], b.i[2], b.i[3]);
}
__device__ __forceinline__ void tile_mma2(float* T, float* U, const HTile& a0, const HTile& a1, const HTile& b, const HTile& c) {
  mma_f16(T, a0.r[0], a0.r[1], a0.r[2], a0.r[3], b.r[0], b.r[1]);
  mma_f16(U, a0.r[0], a0.r[1], a0.r[2], a0.r[3], c.r[0], c.r[1]);
  mma_f16(T, a0.i[0], a0.i[1], a0.i[2], a0.i[3], b.i[0], b.i[1]);
  mma_f16(U, a0.i[0], a0.i[1], a0.i[2], a0.i[3], c.i[0], c.i[1]);
  mma_f16(T, a1.r[0], a1.r[1], a1.r[2], a1.r[3], b.r[2], b.r[3]);
  mma_f16(U, a1.r[0], a1.r[1], a1.r[2], a1.r[3], c.r[2], c.r[3]);
  mma_f16(T, a1.i[0], a1.i[1], a1.i[2], a1.i[3], b.i[2], b.i[3]);
  mma_f16(U, a1.i[0], a1.i[1], a1.i[2], a1.i[3], c.i[2], c.i[3]);
}
__device__ __forceinline__ void kgen_unit(uint32_t tab, uint32_t taba, float ar2, float ai, cplx c, float (&T)[5][4]) {
  const cplx z1 = cexp_l(ar2, ai, 1.f), z16 = cexp_l(ar2, ai, 16.f), z256 = cexp_l(ar2, ai, 256.f);
  HTile a0, a1, b0, b1;
  {
    const cplx y1 = {z16.r, -z16.i}, y2 = csqr(y1), y3 = cmul(y2, y1), y4 = csqr(y2), y5 = cmul(y4, y1), y6 = csqr(y3), y7 = cmul(y4, y3);
    HTile t;
    tile_set(t, 0, {1.f, 0.f}, y1); tile_set(t, 1, y2, y3); tile_set(t, 2, y4, y5); tile_set(t, 3, y6, y7);
    const HTile u = tile_shift(t, hseed(csqr(y4)));
    __syncwarp();
    tile_put(t, tab); tile_put(u, tab + 1024);
    __syncwarp();
    a0 = tile_get(taba); a1 = tile_get(taba + 256);
  }
  const cplx z2 = csqr(z1), z4 = csqr(z2), z8 = csqr(z4);
  const HSeed h8 = hseed(z8);
  const cplx d = cmul(c, z256), e = cmul(d, z256);
  {
    const cplx z512 = csqr(z256), f = cmul(e, z512), f8 = cmul(f, z8), f16 = cmul(f, z16), e4 = cmul(e, z4);
    HTile t, u;
    tile_set(t, 0, e4, cmul(e, z8)); tile_set(t, 1, cmul(e4, z8), cmul(e, z16));
    tile_upper(t, hseed(z256));
    tile_set(u, 0, f8, f16); tile_set(u, 1, cmul(f8, z256), cmul(f16, z256));
    tile_upper(u, hseed(z512));
    __syncwarp();
    tile_put(t, tab); tile_put(u, tab + 1024);
    __syncwarp();
    b0 = tile_get(tab); b1 = tile_get(tab + 1024);
  }
  {
    const cplx d2 = cmul(d, z2), d4 = cmul(d, z4);
    HTile t;
    tile_set(t, 0, d2, d4); tile_set(t, 1, cmul(d2, z4), cmul(d, z8));
    tile_upper(t, h8);
    __syncwarp();
    tile_put(t, tab);
    __syncwarp();
    tile_mma2(T[3], T[4], a0, a1, b0, b1);
    b0 = tile_get(tab);
  }
  {
    const cplx c1 = cmul(c, z1), c2 = cmul(c, z2), c3 = cmul(c1, z2), c4 = cmul(c, z4);
    HTile t;
    tile_set(t, 0, c1, c2); tile_set(t, 1, c3, c4); tile_set(t, 2, cmul(c1, z4), cmul(c2, z4)); tile_set(t, 3, cmul(c3, z4), cmul(c4, z4));
    const HTile u = tile_shift(t, h8);
    __syncwarp();
    tile_put(t, tab); tile_put(u, tab + 1024);
    __syncwarp();
    tile_mma(T[2], a0, a1, b0);
    b0 = tile_get(tab); b1 = tile_get(tab + 1024);
    tile_mma2(T[0], T[1], a0, a1, b0, b1);
  }
}
struct ModeIn { uint2 ar, ai, br, bi, cr, ci; };
__device__ __forceinline__ ModeIn load_modes(const Params& p, int idx) {
  return {*(const uint2*)(p.a_re + idx), *(const uint2*)(p.a_im + idx), *(const uint2*)(p.b_re + idx),
          *(const uint2*)(p.b_im + idx), *(const uint2*)(p.c_re + idx), *(const uint2*)(p.c_im + idx)};
}
__device__ __forceinline__ float bf_el(uint2 v, int k) { const uint32_t x = (k & 2) ? v.y : v.x; return (k & 1) ? bf_hi(x) : bf_lo(x); }
struct KGen { float4 cur; float T[5][4]; };
__device__ __forceinline__ uint32_t kgen_slot(uint32_t sb, int ht, int u) {
  return sb + (u < 3 ? SM_KC + (ht >> 5) * (KC_STRIDE * 2) + (u - 1) * 512 + (ht & 31) * 16 + 16 : SM_HALO + 1024 + ht * 16);
}
__device__ __forceinline__ void kgen_setup(KGen& s, uint32_t sb, int cta, int ht, const ModeIn& in, bf16 logdt, bf16 dskip) {
  const float dt = __bfloat162float(__float2bfloat16_rn(expf(__bfloat162float(logdt))));
  float mx = 0.f, k0 = 0.f, ar2[4];
  cplx c[4];
#pragma unroll
  for (int k = 0; k < 4; k++) {
    ar2[k] = (dt * bf_el(in.ar, k)) * 1.4426950408889634f;
    c[k] = cmul({bf_el(in.cr, k), bf_el(in.ci, k)}, {dt * bf_el(in.br, k), dt * bf_el(in.bi, k)});
    k0 += c[k].r;
    mx = fmaxf(mx, fmaxf(fabsf(c[k].r), fabsf(c[k].i)) * ex2(fmaxf(ar2[k] * 2048.f, 0.f)));
  }
  const int ex = min(max(267 - (int)(__reduce_max_sync(~0u, __float_as_uint(mx)) >> 23), 1), 253);
  const float sc = __uint_as_float(ex << 23);
#pragma unroll
  for (int o = 16; o > 0; o >>= 1) k0 += __shfl_xor_sync(~0u, k0, o);
  if ((ht & 31) == 0) {
    const uint32_t kc = sb + SM_KC + (ht >> 5) * (KC_STRIDE * 2);
    sts16(kc, __bfloat16_as_ushort(__float2bfloat16_rn(k0 + __bfloat162float(dskip))));
    sts16(kc + 641 * 2, 0);
    sts32f(kc + 644 * 2, __uint_as_float((254 - ex) << 23));
  }
  s.cur = make_float4(ar2[0], dt * bf_el(in.ai, 0), c[0].r * sc, c[0].i * sc);
#pragma unroll
  for (int k = 1; k < 4; k++) sts128f(kgen_slot(sb, ht, k), ar2[k], dt * bf_el(in.ai, k), c[k].r * sc, c[k].i * sc);
#pragma unroll
  for (int i = 0; i < 5; i++) s.T[i][0] = s.T[i][1] = s.T[i][2] = s.T[i][3] = 0.f;
}
__device__ __forceinline__ void kgen_finish(KGen& s, uint32_t sb, int cta, int ht) {
  const int w = ht >> 5, lane = ht & 31, g = lane >> 2, t = lane & 3;
  const uint32_t kc = sb + SM_KC + w * KC_STRIDE * 2;
  __syncwarp();
  const float inv = __uint_as_float(lds32(kc + 644 * 2));
  auto put = [&](int idx, float v) {
    sts16(kc + idx * 2, __bfloat16_as_ushort(__float2bfloat16_rn(v)));
  };
#pragma unroll
  for (int hi = 0; hi < 2; hi++)
#pragma unroll
    for (int lo = 0; lo < 2; lo++) {
      const int i = g + 8 * hi, j = 2 * t + lo, e = 2 * hi + lo;
      put(16 * i + 1 + j, s.T[0][e] * inv);
      put(16 * i + 9 + j, s.T[1][e] * inv);
      put(257 + 8 * i + j, s.T[2][e] * inv);
      put(385 + 4 * i + (j & 3) + 64 * (j >> 2), s.T[3][e] * inv);
      put(513 + 2 * i + lo + 32 * t, s.T[4][e] * inv);
    }
}

__device__ __forceinline__ void expand_taps(uint32_t sb, int ht) {
  const int ch = ht >> 5, lane = ht & 31;
  const uint32_t kc = sb + SM_KC + ch * KC_STRIDE * 2;
  const uint32_t dst0 = sb + cv_pe(ch);
  auto put = [&](int G, uint32_t v0, uint32_t v1, uint32_t v2, uint32_t v3, uint32_t v4, uint32_t v5, uint32_t v6, uint32_t v7, uint32_t v8) {
    const uint32_t dst = dst0 + G * 32;
    sts128(dst, make_uint4(v1 | (v0 << 16), v2 | (v1 << 16), v3 | (v2 << 16), v4 | (v3 << 16)));
    sts128(dst + 16, make_uint4(v5 | (v4 << 16), v6 | (v5 << 16), v7 | (v6 << 16), v8 | (v7 << 16)));
  };
  {
    const uint4 q = lds128(kc + lane * 16);
    const uint32_t pv = lane ? lds16(kc + lane * 16 - 2) : 0u;
    const uint32_t dst = dst0 + (lane + 2) * 32;
    sts128(dst, make_uint4(__byte_perm(q.x, pv, 0x5410), __byte_perm(q.x, q.x, 0x1032), __byte_perm(q.y, q.x, 0x7610), __byte_perm(q.y, q.y, 0x1032)));
    sts128(dst + 16, make_uint4(__byte_perm(q.z, q.y, 0x7610), __byte_perm(q.z, q.z, 0x1032), __byte_perm(q.w, q.z, 0x7610), __byte_perm(q.w, q.w, 0x1032)));
    if (lane < 4) sts128(dst0 + lane * 16, make_uint4(0, 0, 0, 0));
  }
  uint32_t a[5], b[2][3], fv[4];
  {
    const uint32_t s1 = kc + 2 * (256 + 4 * lane);
#pragma unroll
    for (int k = 0; k < 5; k++) a[k] = lds16(s1 + 2 * k);
#pragma unroll
    for (int u = 0; u < 2; u++) {
      const uint32_t s2 = kc + 2 * (384 + 2 * (lane + 32 * u));
#pragma unroll
      for (int k = 0; k < 3; k++) b[u][k] = lds16(s2 + 2 * k);
    }
#pragma unroll
    for (int k = 0; k < 4; k++) fv[k] = lds16(kc + 2 * (640 - 4 * lane - k));
  }
  const uint32_t k255 = lds16(kc + 2 * 255), k1024 = lds16(kc + 2 * 512);
  put(34 + lane, lane == 0 ? k255 : a[0], a[0], a[0], a[1], a[2], a[2], a[2], a[3], a[4]);
#pragma unroll
  for (int u = 0; u < 2; u++) put(66 + lane + 32 * u, b[u][0], b[u][0], b[u][0], b[u][0], b[u][1], b[u][1], b[u][1], b[u][2], b[u][2]);
  if (lane < 10) {
    const uint32_t v = lane == 0 ? k1024 : 0u;
    put(130 + lane, v, v, v, v, v, v, 0u, 0u, 0u);
  }
  const uint32_t ft = sb + cv_ft(ch) + 4 * lane;
#pragma unroll
  for (int ty = 0; ty < 2; ty++) {
    const uint32_t v = fv[ty] | (fv[ty + 2] << 16);
    sts32f(ft + ty * 512, __uint_as_float(v));
    sts32f(ft + ty * 512 + 128, 0.f);
    sts32f(ft + ty * 512 + 256 + (lane < 2 ? 120 : -8), __uint_as_float(lane < 2 ? 0u : v));
    sts32f(ft + ty * 512 + 384, 0.f);
  }
}

template <bool SMID> __device__ __forceinline__ int role_id() {
  uint32_t v;
  if (!SMID) { asm volatile("mov.u32 %0, %%ctaid.x;" : "=r"(v)); return v; }
  asm volatile("mov.u32 %0, %%smid;" : "=r"(v));
  const int tp = v >> 1, q = ((tp - 32) * 37) >> 8;
  const int r = tp < 32 ? (tp & 7) * 8 + (tp >> 3) : tp < 60 ? (tp - 31 - 7 * q) * 8 + 4 + q : tp < 62 ? tp + 4 : tp - 58;
  return __shfl_sync(~0u, 2 * r + (v & 1), 0);
}
__device__ __forceinline__ int role_rb(int cta) { return ((cta >> 4) & 3) * 4 + ((cta >> 2) & 3); }
__device__ __forceinline__ int role_hg(int cta) { return (cta >> 6) * 4 + (cta & 3); }
__device__ __forceinline__ int role_rb2(int cta) { return cta >> 3; }
__device__ __forceinline__ int role_q2(int cta) { return cta & 7; }

template <bool SMID> __global__ void __launch_bounds__(NTHREADS, 1) fused_kernel(const __grid_constant__ Params p) {
  extern __shared__ __align__(1024) uint8_t smem[];
  const uint32_t sb = s32(smem);
  const int tid = threadIdx.x, lane = tid & 31;
  const int warp = __shfl_sync(~0u, tid >> 5, 0);
  constexpr unsigned NARR = SMID ? 132 : NCTA;
  const uint32_t bar = sb + SM_BAR;
  if (tid == 0) TS(0);
  const int cta0 = role_id<SMID>();
  if (warp == 0 && (!SMID || cta0 < NCTA) && elect_one()) {
    const int rb = role_rb(cta0), hg = role_hg(cta0);
    mbar_init(bar + 8 * B_XF, 1); mbar_init(bar + 8 * B_KVF, 1);
    fence_async_smem();
#pragma unroll
    for (int c = 0; c < 8; c++) {
      mbar_expect(bar + 8 * (B_XF + c), 16384);
      tma_ld(sb + SM_X + c * 16384, &p.mapX128, c * 64, rb * 128, bar + 8 * (B_XF + c));
      if (c < 3) {
        mbar_expect(bar + 8 * (B_KVF + c), 24576);
        tma_ld3(sb + SM_W + c * 24576, &p.mapW3, hg * 64, c * 64, 0, bar + 8 * (B_KVF + c));
      }
      if (c == 0) {
#pragma unroll
        for (int i = 1; i < 8; i++) mbar_init(bar + 8 * (B_XF + i), 1);
        mbar_init(bar + 8 * (B_KVF + 1), 1); mbar_init(bar + 8 * (B_KVF + 2), 1); mbar_init(bar + 8 * B_CW, 1);
        fence_async_smem();
      }
      if (c == PF_AT) {
        mbar_expect(bar + 8 * B_CW, 12288);
        tma_ld3(sb + SM_CW, &p.mapW3h, hg * 64, rb * 32, 0, bar + 8 * B_CW);
      }
    }
    TS(56);
  }
  if (SMID && cta0 >= NCTA) {
    if (tid == 0) spin_until(&g_cnt[C_CS * 32], (atomicAdd(&g_cnt[C_CS * 32], 1u) / NARR + 1) * NARR);
    return;
  }
  if (warp >= 1 && warp < 5 && elect_one()) {
#pragma unroll
    for (int q = 0; q < 4; q++) {
      if (warp == q + 1) {
#pragma unroll
        for (int i = 17 * q; i < 17 * q + 17; i++) {
          if (i < B_KVF + 3 || i == B_CW) continue;
          int cnt = 1;
          if ((i >= B_KVE && i < B_KVE + 5) || i == B_QDONE || i == B_PDONE || i == B_OST || i == B_AD) cnt = 2;
          if (i == B_Z0) cnt = 128;
          if (i >= B_U && i < B_U + 4) cnt = 8;
          if ((i >= B_S && i < B_S + 4) || (i >= B_E && i < B_E + 4) || i >= B_P || i == B_PE || i == B_STF) cnt = 4;
          mbar_init(bar + 8 * i, cnt);
        }
      }
    }
    fence_async_smem();
  }

  if (warp < 8) {
    bar_sync(0, NTHREADS);
    if (tid == 0) TS(1);
    asm volatile("setmaxnreg.inc.sync.aligned.u32 %0;" ::"n"(R_CONS));
    const int cw = __shfl_sync(~0u, opaque_tid() >> 5, 0);
    const int wg = cw >> 2, w = cw & 3;
    const int cta = role_id<SMID>();
    if (tid == 0) TS(54);
#pragma unroll 1
    for (int layer = 0; layer < 2; layer++) {
      attn_phase(p, sb, layer, role_rb(cta), role_hg(cta), wg, w);
      if (p.stop == 1 + 3 * layer) return;
      proj_phase(p, sb, layer, role_rb2(cta), role_q2(cta), wg, w);
      if (p.stop == 2 + 3 * layer) return;
      conv_phase(p, sb, layer, cta);
      if (p.stop == 3 + 3 * layer) return;
    }
    final_phase(p, sb, cta, wg, w);
  } else if (warp < 12) {
    asm volatile("setmaxnreg.dec.sync.aligned.u32 %0;" ::"n"(R_HELP));
    const int ht = tid - 256;
    const int cta = role_id<SMID>(), rb = role_rb(cta), hg = role_hg(cta);
    unsigned ep0 = 0;
    if (ht == 0) ep0 = ld_relaxed(&g_cnt[C_CS * 32]);
    bar_sync(0, NTHREADS);
    if (ht == 0) {
      asm volatile("st.shared.u32 [%0], %1;" ::"r"(sb + SM_EP), "r"(ep0 / NARR) : "memory");
      mbar_arrive(bar + 8 * B_EP);
    }
    if (hg == 0) {
      *(float4*)(g_stats + (ht >> 6) * LSEQ * 2 + rb * 256 + (ht & 63) * 4) = make_float4(0.f, 0.f, 0.f, 0.f);
    }
    mbar_arrive(bar + 8 * B_Z0);
    mbar_wait(bar + 8 * B_EP, 0);
    const uint32_t cs_tag = lds32(sb + SM_EP) % 7 + 1;
    if (ht < 96) {
      mbar_wait(bar + 8 * B_CW, 0);
      colsum_publish(sb, rb, hg, ht, cs_tag);
    }
    if (ht == 0) TS(50);
    stats_publish(sb, 0, rb, hg, opaque_tid() - 256, 2 * lds32(sb + SM_EP) + 1);
    {
      KGen kg;
      const uint32_t tab0 = sb + ((ht >> 5) < 2 ? SM_T : SM_T2 - 4096) + (ht >> 5) * 2048;
      const uint32_t tab = tab0 + (ht & 31) * 16, taba = tab0 + ((ht >> 3) & 1) * 1024 + (((ht >> 1) & 8) + (ht & 7)) * 16;
      mbar_wait(bar + 8 * (B_KVF + CS_AT), 0);
      if (ht < 96) colsum_gather(sb, hg, ht, cs_tag);
      stats_gather(sb, rb, opaque_tid() - 256, 2 * lds32(sb + SM_EP) + 1);
      if (ht == 0) TS(40);
      const int chn = cv_chan(cta, ht >> 5);
      kgen_setup(kg, sb, cta, ht, load_modes(p, chn * 128 + (ht & 31) * 4), p.log_dt[chn], p.dskip[chn]);
#pragma unroll 1
      for (int u = 0; u < 4; u++) {
        if (u == KG_PRE) {
          KTS(39);
          mbar_wait(bar + 8 * B_AD, 0);
          KTS(41);
        }
        if (u == 3) mbar_wait(bar + 8 * B_PDONE, 0);
        kgen_unit(tab, taba, kg.cur.x, kg.cur.y, {kg.cur.z, kg.cur.w}, kg.T);
        kg.cur = lds128f(kgen_slot(sb, opaque_tid() - 256, u + 1));
      }
      kgen_finish(kg, sb, cta, opaque_tid() - 256);
    }
    KTS(51);
    bar_sync(4, 128);
#pragma unroll 1
    for (int layer = 0; layer < 2; layer++) {
      if (p.stop <= 1 + 3 * layer) return;
      mbar_wait(bar + 8 * B_PDONE, layer);
      expand_taps(sb, opaque_tid() - 256);
      conv_zero(sb, opaque_tid() - 256);
      if (ht == 0) TS(52 + layer);
      warp_release(bar + 8 * B_PE);
      if (p.stop <= 2 + 3 * layer) return;
      {
        uint4 xr[4], st[4], un[4];
        conv_prep_load(sb, layer, cta, opaque_tid() - 256, xr, st);
        conv_prep(sb, layer, opaque_tid() - 256, xr, st, un);
        if (layer == 1 && ht == 0) TS(62);
        bar_sync(4, 128);
#pragma unroll
        for (int lc = 0; lc < 4; lc++) {
          conv_sums(sb, lc, opaque_tid() - 256, un[lc]);
          warp_release(bar + 8 * (B_S + lc));
          if (lc == 0 && layer == 1 && ht == 0) TS(46);
          st[lc] = ldcg128(g_xT + (size_t)(2 * layer * DM + cv_chan(cta, lc)) * LSEQ + (opaque_tid() - 128) * 8);
        }
#pragma unroll
        for (int lc = 0; lc < 4; lc++) {
          conv_epi(sb, layer, lc, opaque_tid() - 256, xr[lc], st[lc]);
          warp_release(bar + 8 * (B_E + lc));
        }
      }
      if (layer == 0 && p.stop > 3) {
        const int c1 = role_id<SMID>();
        stats_publish(sb, 1, role_rb(c1), role_hg(c1), opaque_tid() - 256, 2 * lds32(sb + SM_EP) + 2);
        mbar_wait(bar + 8 * (B_XF + 7), 1);
        mbar_wait(bar + 8 * (B_KVF + ST_AT), 1);
        stats_gather(sb, role_rb(c1), opaque_tid() - 256, 2 * lds32(sb + SM_EP) + 2);
        if (ht == 0) TS(25);
      }
    }
  } else {
    asm volatile("setmaxnreg.dec.sync.aligned.u32 %0;" ::"n"(512 - 2 * R_CONS - R_HELP));
    const int cta = role_id<SMID>(), rb = role_rb(cta), hg = role_hg(cta), rb2 = role_rb2(cta), q2 = role_q2(cta);
    bar_sync(0, NTHREADS);
    if (warp == 12) {
      if (elect_one()) {
        unsigned epoch = 0;
#pragma unroll 1
        for (int layer = 0; layer < 2; layer++) {
          auto ld_w = [&](int c, int slot) {
            const uint32_t b = bar + 8 * (B_KVF + c);
            mbar_expect(b, 24576);
            tma_ld3(sb + SM_W + slot * 24576, &p.mapW3, hg * 64, c * 64, 0, b);
          };
          if (layer == 0) {
            TS(55);
            mbar_wait(bar + 8 * (B_KVF + 2), 0);
            if (rb2 < 4) tma_prefetch2(&p.mapWo128, q2 * 64, rb2 * 128);
            asm volatile("prefetch.tensormap [%0];" ::"l"(&p.mapO) : "memory");
            asm volatile("prefetch.tensormap [%0];" ::"l"(&p.mapO128) : "memory");
            asm volatile("prefetch.tensormap [%0];" ::"l"(&p.mapXT) : "memory");
            asm volatile("prefetch.tensormap [%0];" ::"l"(&p.mapXT3) : "memory");
            mbar_wait(bar + 8 * B_EP, 0);
            epoch = lds32(sb + SM_EP);
          } else {
            mbar_wait(bar + 8 * B_PDONE, 0);
            ld_w(0, 0); ld_w(1, 1);
          }
          {
            int slot = 0;
#pragma unroll 1
            for (int c = 3; c < 8; c++) {
              mbar_wait(bar + 8 * (B_KVE + c - 3), layer);
              ld_w(c, slot);
              slot = slot == 2 ? 0 : slot + 1;
            }
          }
          if (p.stop <= 1 + 3 * layer) return;
          mbar_wait(bar + 8 * B_QDONE, layer);
          if (rb > 0) mbar_wait(bar + 8 * B_HF, layer);
#pragma unroll 1
          for (int c = 0; c < 4; c++) {
            const uint32_t b = bar + 8 * (B_WOF + c);
            mbar_expect(b, 16384);
            tma_ld(sb + SM_X + c * 16384, &p.mapWo128, q2 * 64, c * 128, b);
          }
          {
            const uint32_t b = bar + 8 * B_RF;
            mbar_expect(b, 16384);
            if (layer == 0) tma_ld(sb + SM_R, &p.mapX128, q2 * 64, rb2 * 128, b);
            else tma_ld3(sb + SM_R, &p.mapXT3, 0, DM + q2 * 64, rb2 * 2, b);
          }
          spin_until(&g_cnt[(C_O + rb2) * 32], (2 * epoch + layer + 1) * 16);
          mbar_wait(bar + 8 * B_OST, layer);
          fence_async_global();
#pragma unroll 1
          for (int c = 0; c < 8; c++) {
            const uint32_t b = bar + 8 * (B_OF + c);
            mbar_expect(b, 16384);
            tma_ld(sb + (c < 4 ? SM_X + 65536 + c * 16384 : SM_W + (c - 4) * 16384), &p.mapO128, c * 64, rb2 * 128, b);
          }
          if (p.stop <= 3 + 3 * layer) return;
        }
      }
    } else if (warp == 13) {
      if (elect_one() && p.stop > 3) {
        mbar_wait(bar + 8 * B_GB, 0);
        const unsigned target = (lds32(sb + SM_EP) + 1) * NCTA;
#pragma unroll 1
        for (int lc = 0; lc < 4; lc++) {
          spin_until(&g_cnt[C_G1 * 32 + lc], target);
          if (lc == 3) TS(44);
          fence_async_global();
          fence_async_smem();
#pragma unroll
          for (int c = 2 * lc; c < 2 * lc + 2; c++) {
            mbar_expect(bar + 8 * (B_XF + c), 16384);
            tma_ld3(sb + SM_X + c * 16384, &p.mapXT3, 0, DM + c * 64, rb * 2, bar + 8 * (B_XF + c));
            if (c == 2) {
              mbar_expect(bar + 8 * (B_KVF + 2), 24576);
              tma_ld3(sb + SM_W + 2 * 24576, &p.mapW3, hg * 64, 128, 0, bar + 8 * (B_KVF + 2));
            }
          }
        }
      }
    } else if (warp == 15) {
      if (elect_one()) {
#pragma unroll 1
        for (int i = 0; i < 8; i++) {
          const int layer = i >> 2, lc = i & 3;
          if (p.stop <= 2 + 3 * layer) return;
          mbar_wait(bar + 8 * (B_E + lc), layer);
          bulk_st(g_xT + (size_t)((2 * layer + 1) * DM + cv_chan(cta, lc)) * LSEQ, sb + cv_s(lc), 4096);
          bulk_commit();
          bulk_wait_all();
          red_relaxed(&g_cnt[(layer ? C_F + (cta >> 5) : C_G1) * 32 + lc]);
          if (lc == 3) TS(2 + layer * 20 + 16);
        }
      }
    } else if (warp == 14) {
      mbar_wait(bar + 8 * B_EP, 0);
      const unsigned epoch = lds32(sb + SM_EP);
      if (lane == 0) {
        mbar_wait(bar + 8 * B_Z0, 0);
        red_release(&g_cnt[C_CS * 32]);
        spin_until(&g_cnt[C_CS * 32], (epoch + 1) * NARR);
        mbar_arrive(bar + 8 * B_ZF);
#pragma unroll 1
        for (int layer = 0; layer < 2; layer++) {
          if (p.stop <= 1 + 3 * layer) return;
          spin_until(&g_cnt[(layer ? C_G2 : C_G0) * 32], (epoch + 1) * 256);
          mbar_arrive(bar + 8 * B_GB);
        }
      }
    }
  }
}

typedef CUresult (*EncodeFn)(CUtensorMap*, CUtensorMapDataType, cuuint32_t, void*, const cuuint64_t*, const cuuint64_t*,
                             const cuuint32_t*, const cuuint32_t*, CUtensorMapInterleave, CUtensorMapSwizzle,
                             CUtensorMapL2promotion, CUtensorMapFloatOOBfill);

static void make_map(EncodeFn enc, CUtensorMap* m, void* ptr, uint64_t cols, uint64_t rows, uint32_t box_rows) {
  cuuint64_t dims[2] = {cols, rows};
  cuuint64_t strides[1] = {cols * 2};
  cuuint32_t box[2] = {64, box_rows};
  cuuint32_t es[2] = {1, 1};
  enc(m, CU_TENSOR_MAP_DATA_TYPE_BFLOAT16, 2, ptr, dims, strides, box, es, CU_TENSOR_MAP_INTERLEAVE_NONE,
      CU_TENSOR_MAP_SWIZZLE_128B, CU_TENSOR_MAP_L2_PROMOTION_L2_128B, CU_TENSOR_MAP_FLOAT_OOB_FILL_NONE);
}
static void make_map3(EncodeFn enc, CUtensorMap* m, void* ptr, uint64_t d0, uint64_t cols, uint64_t rows, uint64_t blk_stride,
                      uint64_t nblocks, uint32_t nblk, uint32_t box_rows = 64) {
  cuuint64_t dims[3] = {d0, rows, nblocks};
  cuuint64_t strides[2] = {cols * 2, blk_stride * 2};
  cuuint32_t box[3] = {64, box_rows, nblk};
  cuuint32_t es[3] = {1, 1, 1};
  enc(m, CU_TENSOR_MAP_DATA_TYPE_BFLOAT16, 3, ptr, dims, strides, box, es, CU_TENSOR_MAP_INTERLEAVE_NONE,
      CU_TENSOR_MAP_SWIZZLE_128B, CU_TENSOR_MAP_L2_PROMOTION_L2_128B, CU_TENSOR_MAP_FLOAT_OOB_FILL_NONE);
}

extern "C" void kernel_launch(void* const* d_in, const int* in_sizes, int n_in, void* d_out, int out_size) {
  static Params prm;
  static void* cached[13] = {nullptr};
  static bool attr_done = false, by_smid = false;
  bool same = attr_done && cached[12] == d_out;
  for (int i = 0; i < 12 && same; i++) same = cached[i] == d_in[i];
  if (!same) {
    void* fn = nullptr;
    cudaDriverEntryPointQueryResult qr;
    cudaGetDriverEntryPoint("cuTensorMapEncodeTiled", &fn, cudaEnableDefault, &qr);
    EncodeFn enc = (EncodeFn)fn;
    void *pO, *pXT;
    cudaGetSymbolAddress(&pO, g_O);
    cudaGetSymbolAddress(&pXT, g_xT);
    make_map(enc, &prm.mapO, pO, DM, LSEQ, 64);
    make_map(enc, &prm.mapXT, pXT, LSEQ, 4 * DM, 64);
    prm.out = (bf16*)d_out;
    make_map(enc, &prm.mapX128, d_in[0], DM, LSEQ, 128);
    make_map(enc, &prm.mapWo128, d_in[2], DM, DM, 128);
    make_map(enc, &prm.mapO128, pO, DM, LSEQ, 128);
    make_map3(enc, &prm.mapW3, d_in[1], DM, 3 * DM, DM, DM, 3, 3);
    make_map3(enc, &prm.mapW3h, d_in[1], DM, 3 * DM, DM, DM, 3, 3, 32);
    make_map3(enc, &prm.mapXT3, pXT, 64, LSEQ, 4 * DM, 64, 32, 2);
    prm.a_re = (const bf16*)d_in[4]; prm.a_im = (const bf16*)d_in[5];
    prm.b_re = (const bf16*)d_in[6]; prm.b_im = (const bf16*)d_in[7];
    prm.c_re = (const bf16*)d_in[8]; prm.c_im = (const bf16*)d_in[9];
    prm.log_dt = (const bf16*)d_in[10]; prm.dskip = (const bf16*)d_in[11];
    int dev = 0, sms = 0;
    cudaGetDevice(&dev);
    cudaDeviceGetAttribute(&sms, cudaDevAttrMultiProcessorCount, dev);
    by_smid = sms == 132;
    cudaFuncSetAttribute(fused_kernel<true>, cudaFuncAttributeMaxDynamicSharedMemorySize, SM_TOTAL);
    cudaFuncSetAttribute(fused_kernel<false>, cudaFuncAttributeMaxDynamicSharedMemorySize, SM_TOTAL);
    for (int i = 0; i < 12; i++) cached[i] = d_in[i];
    cached[12] = d_out;
    attr_done = true;
  }
  prm.stop = 100;
    if (by_smid) fused_kernel<true><<<132, NTHREADS, SM_TOTAL>>>(prm);
  else fused_kernel<false><<<NCTA, NTHREADS, SM_TOTAL>>>(prm);
}
```

```cpp
#include <cuda_runtime.h>
#include <cuda_bf16.h>
#include <cuda.h>
#include <stdint.h>

typedef __nv_bfloat16 bf16;

constexpr int LSEQ = 2048;
constexpr int DM = 512;
constexpr int NCTA = 128;
constexpr int NTHREADS = 512;
#define RR 0
#define KG_PRE 0
#define ST_AT 6
#define W2_LATE 0
#define FILL_AT 2
#define EXP_LATE 1
#define RFENCE 1
#define CS_AT 4
#define KG_LAST 1
#define X_JIT 0
#define PF_AT 2
#define KG_GATE 2
#define R_CONS 192
#define R_HELP 88

constexpr int SM_X = 0;
constexpr int SM_W = 131072;
constexpr int SM_KVX = SM_W;
constexpr int SM_OST = SM_W + 32768;
constexpr int SM_R = 196608;
constexpr int SM_T = 212992;
constexpr int SM_KC = 217088;
constexpr int KC_STRIDE = 648;
constexpr int SM_CS = SM_KC + 4 * KC_STRIDE * 2;
constexpr int SM_CW = SM_R + 8192;
constexpr int SM_EP = SM_CS + 768;
constexpr int SM_BAR = SM_EP + 16;
constexpr int SM_T2 = SM_BAR + 832;
constexpr int SM_HALO = SM_T2 + 4096;
constexpr int SM_ST = SM_HALO + 3072;
constexpr int SM_TOTAL = SM_HALO + 4096;
static_assert(SM_TOTAL <= 232448, "shared memory");

constexpr int CV_UH = 140 * 16;
constexpr int CV_PECH = 1120 * 4;
constexpr int CV_PBW = 2112 * 2;
__host__ __device__ constexpr int cv_s(int lc) { return SM_X + lc * 32768; }
__host__ __device__ constexpr int cv_u(int lc) { return cv_s(lc) + 4096; }
__host__ __device__ constexpr int cv_pe(int lc) { return cv_u(lc) + 2 * CV_UH; }
__host__ __device__ constexpr int cv_pb(int lc) { return cv_pe(lc) + CV_PECH; }
__host__ __device__ constexpr int cv_ft(int lc) { return cv_pb(lc) + 4 * CV_PBW; }
static_assert(cv_ft(0) + 1024 <= 32768, "conv buffers");
__host__ __device__ constexpr int cv_chan(int cta, int lc) { return cta + 128 * lc; }

enum {
  B_XF = 0,
  B_KVF = 8,
  B_KVE = 16,
  B_AD = 21,
  B_OST = 22,
  B_RF = 23,
  B_U = 24,
  B_S = 28,
  B_T = 32,
  B_WOF = 36,
  B_E = 40,
  B_OF = 44,
  B_P = 64,
  B_RE = 52,
  B_CW = 53,
  B_HF = 54,
  B_STF = 55,
  B_QDONE = 56,
  B_PDONE = 57,
  B_PS = 58,
  B_PE = 59,
  B_GB = 60,
  B_EP = 62,
  B_ZF = 63,
  B_COUNT = 68
};

enum {
  C_CS = 0,
  C_G1 = 2,
  C_O = 4,
  C_COUNT = 20
};

__device__ __align__(128) unsigned g_cnt[C_COUNT * 32];
__device__ __align__(1024) bf16 g_O[LSEQ * DM];
__device__ __align__(1024) bf16 g_xT[4 * DM * LSEQ];
__device__ __align__(1024) float g_stats[2 * LSEQ * 2];
__device__ __align__(1024) uint4 g_colsum[8 * 16 * 48];
__device__ __align__(1024) uint4 g_halo[2 * 16 * 8 * 384];
__device__ __align__(1024) uint4 g_part[2 * 16 * 8 * 128];
#define TS(i) do { } while (0)

#define KTS(i) do { if (ht == 0) TS(i); } while (0)
#define FTS(i) do { } while (0)
#define LTS(i) do { } while (0)

struct Params {
  CUtensorMap mapO, mapXT, mapX128, mapWo128, mapO128, mapW3, mapW3h, mapXT3;
  const bf16 *a_re, *a_im, *b_re, *b_im, *c_re, *c_im, *log_dt, *dskip;
  bf16* out;
  int stop;
};

__device__ __forceinline__ uint32_t s32(const void* p) { return (uint32_t)__cvta_generic_to_shared(p); }
__device__ __forceinline__ void mbar_init(uint32_t b, int c) { asm volatile("mbarrier.init.shared::cta.b64 [%0], %1;" ::"r"(b), "r"(c) : "memory"); }
__device__ __forceinline__ void mbar_expect(uint32_t b, int bytes) { asm volatile("mbarrier.arrive.expect_tx.shared::cta.b64 _, [%0], %1;" ::"r"(b), "r"(bytes) : "memory"); }
__device__ __forceinline__ void mbar_arrive(uint32_t b) { asm volatile("mbarrier.arrive.shared::cta.b64 _, [%0];" ::"r"(b) : "memory"); }
__device__ __forceinline__ void mbar_arrive_if(uint32_t b, bool c) {
  asm volatile("{\n.reg .pred p;\nsetp.ne.u32 p, %1, 0;\n@p mbarrier.arrive.shared::cta.b64 _, [%0];\n}" ::"r"(b), "r"((uint32_t)c) : "memory");
}
__device__ __forceinline__ void mbar_wait(uint32_t b, int parity) {
  asm volatile("{\n.reg .pred p;\nWAIT_LOOP:\nmbarrier.try_wait.parity.shared::cta.b64 p, [%0], %1;\n@p bra WAIT_DONE;\nbra WAIT_LOOP;\nWAIT_DONE:\n}" ::"r"(b), "r"(parity) : "memory");
}
__device__ __forceinline__ int opaque_tid() { int v; asm volatile("mov.u32 %0, %%tid.x;" : "=r"(v)); return v; }
__device__ __forceinline__ bool elect_one() {
  uint32_t r;
  asm volatile("{\n.reg .pred p;\nelect.sync _|p, 0xffffffff;\nselp.u32 %0, 1, 0, p;\n}" : "=r"(r));
  return r != 0;
}
__device__ __forceinline__ void tma_ld(uint32_t dst, const CUtensorMap* m, int c0, int c1, uint32_t bar) {
  asm volatile("cp.async.bulk.tensor.2d.shared::cluster.global.mbarrier::complete_tx::bytes [%0], [%1, {%3, %4}], [%2];"
               ::"r"(dst), "l"(m), "r"(bar), "r"(c0), "r"(c1) : "memory");
}
__device__ __forceinline__ void tma_ld3(uint32_t dst, const CUtensorMap* m, int c0, int c1, int c2, uint32_t bar) {
  asm volatile("cp.async.bulk.tensor.3d.shared::cluster.global.mbarrier::complete_tx::bytes [%0], [%1, {%3, %4, %5}], [%2];"
               ::"r"(dst), "l"(m), "r"(bar), "r"(c0), "r"(c1), "r"(c2) : "memory");
}
__device__ __forceinline__ void tma_prefetch2(const CUtensorMap* m, int c0, int c1) {
  asm volatile("cp.async.bulk.prefetch.tensor.2d.L2.global.tile [%0, {%1, %2}];" ::"l"(m), "r"(c0), "r"(c1) : "memory");
}
__device__ __forceinline__ void tma_prefetch3(const CUtensorMap* m, int c0, int c1, int c2) {
  asm volatile("cp.async.bulk.prefetch.tensor.3d.L2.global.tile [%0, {%1, %2, %3}];" ::"l"(m), "r"(c0), "r"(c1), "r"(c2) : "memory");
}
__device__ __forceinline__ void tma_st(const CUtensorMap* m, int c0, int c1, uint32_t src) {
  asm volatile("cp.async.bulk.tensor.2d.global.shared::cta.bulk_group [%0, {%2, %3}], [%1];" ::"l"(m), "r"(src), "r"(c0), "r"(c1) : "memory");
}
__device__ __forceinline__ void bulk_ld(uint32_t dst, const void* src, int bytes, uint32_t bar) {
  asm volatile("cp.async.bulk.shared::cluster.global.mbarrier::complete_tx::bytes [%0], [%1], %2, [%3];" ::"r"(dst), "l"(src), "r"(bytes), "r"(bar) : "memory");
}
__device__ __forceinline__ void bulk_st(void* dst, uint32_t src, int bytes) {
  asm volatile("cp.async.bulk.global.shared::cta.bulk_group [%0], [%1], %2;" ::"l"(dst), "r"(src), "r"(bytes) : "memory");
}
__device__ __forceinline__ void bulk_red_add_f32(void* dst, uint32_t src, int bytes) {
  asm volatile("cp.reduce.async.bulk.global.shared::cta.bulk_group.add.f32 [%0], [%1], %2;" ::"l"(dst), "r"(src), "r"(bytes) : "memory");
}
__device__ __forceinline__ void bulk_commit() { asm volatile("cp.async.bulk.commit_group;" ::: "memory"); }
__device__ __forceinline__ void bulk_wait_all() { asm volatile("cp.async.bulk.wait_group 0;" ::: "memory"); }
__device__ __forceinline__ void fence_async_smem() { asm volatile("fence.proxy.async.shared::cta;" ::: "memory"); }
__device__ __forceinline__ void fence_writer() { if (!RFENCE) fence_async_smem(); }
__device__ __forceinline__ void fence_reader() { if (RFENCE) fence_async_smem(); }
__device__ __forceinline__ void fence_async_global() { asm volatile("fence.proxy.async.global;" ::: "memory"); }
__device__ __forceinline__ void bar_sync(int id, int n) { asm volatile("bar.sync %0, %1;" ::"r"(id), "r"(n) : "memory"); }
__device__ __forceinline__ void bar_arrive(int id, int n) { asm volatile("bar.arrive %0, %1;" ::"r"(id), "r"(n) : "memory"); }
__device__ __forceinline__ void wg_fence() { asm volatile("wgmma.fence.sync.aligned;" ::: "memory"); }
__device__ __forceinline__ void wg_commit() { asm volatile("wgmma.commit_group.sync.aligned;" ::: "memory"); }
template <int N> __device__ __forceinline__ void wg_wait() { asm volatile("wgmma.wait_group.sync.aligned %0;" ::"n"(N) : "memory"); }
__device__ __forceinline__ uint64_t mkdesc(uint32_t addr, uint32_t lbo, uint32_t sbo, int sw) {
  return (uint64_t)((addr & 0x3FFFF) >> 4) | ((uint64_t)(lbo >> 4) << 16) | ((uint64_t)(sbo >> 4) << 32) | ((uint64_t)sw << 62);
}
__device__ __forceinline__ void ldsm4(uint32_t* r, uint32_t a) {
  asm volatile("ldmatrix.sync.aligned.m8n8.x4.shared.b16 {%0,%1,%2,%3}, [%4];" : "=r"(r[0]), "=r"(r[1]), "=r"(r[2]), "=r"(r[3]) : "r"(a) : "memory");
}
__device__ __forceinline__ void ldsm4t(uint32_t* r, uint32_t a) {
  asm volatile("ldmatrix.sync.aligned.m8n8.x4.trans.shared.b16 {%0,%1,%2,%3}, [%4];" : "=r"(r[0]), "=r"(r[1]), "=r"(r[2]), "=r"(r[3]) : "r"(a) : "memory");
}
__device__ __forceinline__ void stsm4(uint32_t a, uint32_t r0, uint32_t r1, uint32_t r2, uint32_t r3) {
  asm volatile("stmatrix.sync.aligned.m8n8.x4.shared.b16 [%0], {%1,%2,%3,%4};" ::"r"(a), "r"(r0), "r"(r1), "r"(r2), "r"(r3) : "memory");
}
__device__ __forceinline__ void stsm4t(uint32_t a, uint32_t r0, uint32_t r1, uint32_t r2, uint32_t r3) {
  asm volatile("stmatrix.sync.aligned.m8n8.x4.trans.shared.b16 [%0], {%1,%2,%3,%4};" ::"r"(a), "r"(r0), "r"(r1), "r"(r2), "r"(r3) : "memory");
}
__device__ __forceinline__ uint32_t movm_t(uint32_t a) { uint32_t r; asm volatile("movmatrix.sync.aligned.m8n8.trans.b16 %0, %1;" : "=r"(r) : "r"(a)); return r; }
__device__ __forceinline__ uint32_t lds32(uint32_t a) { uint32_t v; asm volatile("ld.shared.b32 %0, [%1];" : "=r"(v) : "r"(a) : "memory"); return v; }
__device__ __forceinline__ float2 lds64f(uint32_t a) { float2 v; asm volatile("ld.shared.v2.f32 {%0,%1}, [%2];" : "=f"(v.x), "=f"(v.y) : "r"(a) : "memory"); return v; }
__device__ __forceinline__ float4 lds128f(uint32_t a) { float4 v; asm volatile("ld.shared.v4.f32 {%0,%1,%2,%3}, [%4];" : "=f"(v.x), "=f"(v.y), "=f"(v.z), "=f"(v.w) : "r"(a) : "memory"); return v; }
__device__ __forceinline__ uint4 lds128(uint32_t a) { uint4 v; asm volatile("ld.shared.v4.b32 {%0,%1,%2,%3}, [%4];" : "=r"(v.x), "=r"(v.y), "=r"(v.z), "=r"(v.w) : "r"(a) : "memory"); return v; }
__device__ __forceinline__ void sts128(uint32_t a, uint4 v) { asm volatile("st.shared.v4.b32 [%0], {%1,%2,%3,%4};" ::"r"(a), "r"(v.x), "r"(v.y), "r"(v.z), "r"(v.w) : "memory"); }
__device__ __forceinline__ void sts128f(uint32_t a, float x, float y, float z, float w) { asm volatile("st.shared.v4.f32 [%0], {%1,%2,%3,%4};" ::"r"(a), "f"(x), "f"(y), "f"(z), "f"(w) : "memory"); }
__device__ __forceinline__ void sts32f(uint32_t a, float v) { asm volatile("st.shared.f32 [%0], %1;" ::"r"(a), "f"(v) : "memory"); }
__device__ __forceinline__ void sts16(uint32_t a, uint16_t v) { asm volatile("st.shared.u16 [%0], %1;" ::"r"(a), "h"(v) : "memory"); }
__device__ __forceinline__ uint32_t lds16(uint32_t a) { uint16_t v; asm volatile("ld.shared.u16 %0, [%1];" : "=h"(v) : "r"(a) : "memory"); return v; }
__device__ __forceinline__ uint32_t packbf(float lo, float hi) { uint32_t r; asm("cvt.rn.bf16x2.f32 %0, %1, %2;" : "=r"(r) : "f"(hi), "f"(lo)); return r; }
__device__ __forceinline__ float bf_lo(uint32_t v) { return __uint_as_float(v << 16); }
__device__ __forceinline__ float bf_hi(uint32_t v) { return __uint_as_float(v & 0xffff0000u); }
__device__ __forceinline__ float ex2(float x) { float r; asm("ex2.approx.ftz.f32 %0, %1;" : "=f"(r) : "f"(x)); return r; }
__device__ __forceinline__ float rsqrt_approx(float x) { float r; asm("rsqrt.approx.ftz.f32 %0, %1;" : "=f"(r) : "f"(x)); return r; }
__device__ __forceinline__ float rcp_approx(float x) { float r; asm("rcp.approx.ftz.f32 %0, %1;" : "=f"(r) : "f"(x)); return r; }
__device__ __forceinline__ void mma_bf16(float* d, const uint32_t* a, uint32_t b0, uint32_t b1) {
  asm("mma.sync.aligned.m16n8k16.row.col.f32.bf16.bf16.f32 {%0,%1,%2,%3}, {%4,%5,%6,%7}, {%8,%9}, {%0,%1,%2,%3};"
               : "+f"(d[0]), "+f"(d[1]), "+f"(d[2]), "+f"(d[3]) : "r"(a[0]), "r"(a[1]), "r"(a[2]), "r"(a[3]), "r"(b0), "r"(b1));
}
__device__ __forceinline__ void red_release(unsigned* p) { asm volatile("red.release.gpu.global.add.u32 [%0], 1;" ::"l"(p) : "memory"); }
__device__ __forceinline__ void red_relaxed(unsigned* p) { asm volatile("red.relaxed.gpu.global.add.u32 [%0], 1;" ::"l"(p) : "memory"); }
__device__ __forceinline__ unsigned ld_relaxed(const unsigned* p) { unsigned v; asm volatile("ld.relaxed.gpu.global.u32 %0, [%1];" : "=r"(v) : "l"(p) : "memory"); return v; }
__device__ __forceinline__ void spin_until(const unsigned* p, unsigned target) {
  int it = 0;
  while ((int)(ld_relaxed(p) - target) < 0) {
    if (++it > (1 << 23)) __trap();
  }
}
__device__ __forceinline__ uint4 ldcg128(const void* p) { uint4 v; asm volatile("ld.global.cg.v4.b32 {%0,%1,%2,%3}, [%4];" : "=r"(v.x), "=r"(v.y), "=r"(v.z), "=r"(v.w) : "l"(p) : "memory"); return v; }
__device__ __forceinline__ uint4 ld_tagged(const uint4* p) { uint4 v; asm volatile("ld.relaxed.gpu.global.v4.u32 {%0,%1,%2,%3}, [%4];" : "=r"(v.x), "=r"(v.y), "=r"(v.z), "=r"(v.w) : "l"(p) : "memory"); return v; }
__device__ __forceinline__ void st_tagged(uint4* p, uint32_t a, uint32_t b, uint32_t tag) { asm volatile("st.relaxed.gpu.global.v4.u32 [%0], {%1,%2,%3,%2};" ::"l"(p), "r"(a), "r"(tag), "r"(b) : "memory"); }
__device__ __forceinline__ void st_tagged3(uint4* p, uint32_t a, uint32_t b, uint32_t c, uint32_t tag) { asm volatile("st.relaxed.gpu.global.v4.u32 [%0], {%1,%2,%3,%4};" ::"l"(p), "r"(a), "r"(b), "r"(c), "r"(tag) : "memory"); }
__device__ __forceinline__ uint4 poll_tagged(const uint4* p, uint32_t tag) {
  uint4 v = ld_tagged(p);
  int it = 0;
  while (v.y != tag || v.w != tag) {
    if (++it > (1 << 22)) __trap();
    v = ld_tagged(p);
  }
  return v;
}
__device__ __forceinline__ uint32_t hadd2(uint32_t a, uint32_t b) { uint32_t r; asm("add.rn.bf16x2 %0, %1, %2;" : "=r"(r) : "r"(a), "r"(b)); return r; }
__device__ __forceinline__ uint32_t hmul2(uint32_t a, uint32_t b) { uint32_t r; asm("mul.rn.bf16x2 %0, %1, %2;" : "=r"(r) : "r"(a), "r"(b)); return r; }

template<int N,int TB> __device__ __forceinline__ void wgmma_rs(float* d, const uint32_t* a, uint64_t db, int sd);
template<int N,int TA,int TB> __device__ __forceinline__ void wgmma_ss(float* d, uint64_t da, uint64_t db, int sd);
template<> __device__ __forceinline__ void wgmma_rs<128,0>(float* d, const uint32_t* a, uint64_t db, int sd) {
  asm volatile("{\n.reg .pred p;\nsetp.ne.b32 p, %69, 0;\nwgmma.mma_async.sync.aligned.m64n128k16.f32.bf16.bf16 {%0,%1,%2,%3,%4,%5,%6,%7,%8,%9,%10,%11,%12,%13,%14,%15,%16,%17,%18,%19,%20,%21,%22,%23,%24,%25,%26,%27,%28,%29,%30,%31,%32,%33,%34,%35,%36,%37,%38,%39,%40,%41,%42,%43,%44,%45,%46,%47,%48,%49,%50,%51,%52,%53,%54,%55,%56,%57,%58,%59,%60,%61,%62,%63}, {%64,%65,%66,%67}, %68, p, 1, 1, 0;\n}\n"
   : "+f"(d[0]),"+f"(d[1]),"+f"(d[2]),"+f"(d[3]),"+f"(d[4]),"+f"(d[5]),"+f"(d[6]),"+f"(d[7]),"+f"(d[8]),"+f"(d[9]),"+f"(d[10]),"+f"(d[11]),"+f"(d[12]),"+f"(d[13]),"+f"(d[14]),"+f"(d[15]),"+f"(d[16]),"+f"(d[17]),"+f"(d[18]),"+f"(d[19]),"+f"(d[20]),"+f"(d[21]),"+f"(d[22]),"+f"(d[23]),"+f"(d[24]),"+f"(d[25]),"+f"(d[26]),"+f"(d[27]),"+f"(d[28]),"+f"(d[29]),"+f"(d[30]),"+f"(d[31]),"+f"(d[32]),"+f"(d[33]),"+f"(d[34]),"+f"(d[35]),"+f"(d[36]),"+f"(d[37]),"+f"(d[38]),"+f"(d[39]),"+f"(d[40]),"+f"(d[41]),"+f"(d[42]),"+f"(d[43]),"+f"(d[44]),"+f"(d[45]),"+f"(d[46]),"+f"(d[47]),"+f"(d[48]),"+f"(d[49]),"+f"(d[50]),"+f"(d[51]),"+f"(d[52]),"+f"(d[53]),"+f"(d[54]),"+f"(d[55]),"+f"(d[56]),"+f"(d[57]),"+f"(d[58]),"+f"(d[59]),"+f"(d[60]),"+f"(d[61]),"+f"(d[62]),"+f"(d[63])
   : "r"(a[0]), "r"(a[1]), "r"(a[2]), "r"(a[3]), "l"(db), "r"(sd));
}
template<> __device__ __forceinline__ void wgmma_rs<120,0>(float* d, const uint32_t* a, uint64_t db, int sd) {
  asm volatile("{\n.reg .pred p;\nsetp.ne.b32 p, %65, 0;\nwgmma.mma_async.sync.aligned.m64n120k16.f32.bf16.bf16 {%0,%1,%2,%3,%4,%5,%6,%7,%8,%9,%10,%11,%12,%13,%14,%15,%16,%17,%18,%19,%20,%21,%22,%23,%24,%25,%26,%27,%28,%29,%30,%31,%32,%33,%34,%35,%36,%37,%38,%39,%40,%41,%42,%43,%44,%45,%46,%47,%48,%49,%50,%51,%52,%53,%54,%55,%56,%57,%58,%59}, {%60,%61,%62,%63}, %64, p, 1, 1, 0;\n}\n"
   : "+f"(d[0]),"+f"(d[1]),"+f"(d[2]),"+f"(d[3]),"+f"(d[4]),"+f"(d[5]),"+f"(d[6]),"+f"(d[7]),"+f"(d[8]),"+f"(d[9]),"+f"(d[10]),"+f"(d[11]),"+f"(d[12]),"+f"(d[13]),"+f"(d[14]),"+f"(d[15]),"+f"(d[16]),"+f"(d[17]),"+f"(d[18]),"+f"(d[19]),"+f"(d[20]),"+f"(d[21]),"+f"(d[22]),"+f"(d[23]),"+f"(d[24]),"+f"(d[25]),"+f"(d[26]),"+f"(d[27]),"+f"(d[28]),"+f"(d[29]),"+f"(d[30]),"+f"(d[31]),"+f"(d[32]),"+f"(d[33]),"+f"(d[34]),"+f"(d[35]),"+f"(d[36]),"+f"(d[37]),"+f"(d[38]),"+f"(d[39]),"+f"(d[40]),"+f"(d[41]),"+f"(d[42]),"+f"(d[43]),"+f"(d[44]),"+f"(d[45]),"+f"(d[46]),"+f"(d[47]),"+f"(d[48]),"+f"(d[49]),"+f"(d[50]),"+f"(d[51]),"+f"(d[52]),"+f"(d[53]),"+f"(d[54]),"+f"(d[55]),"+f"(d[56]),"+f"(d[57]),"+f"(d[58]),"+f"(d[59])
   : "r"(a[0]), "r"(a[1]), "r"(a[2]), "r"(a[3]), "l"(db), "r"(sd));
}
template<> __device__ __forceinline__ void wgmma_rs<112,0>(float* d, const uint32_t* a, uint64_t db, int sd) {
  asm volatile("{\n.reg .pred p;\nsetp.ne.b32 p, %61, 0;\nwgmma.mma_async.sync.aligned.m64n112k16.f32.bf16.bf16 {%0,%1,%2,%3,%4,%5,%6,%7,%8,%9,%10,%11,%12,%13,%14,%15,%16,%17,%18,%19,%20,%21,%22,%23,%24,%25,%26,%27,%28,%29,%30,%31,%32,%33,%34,%35,%36,%37,%38,%39,%40,%41,%42,%43,%44,%45,%46,%47,%48,%49,%50,%51,%52,%53,%54,%55}, {%56,%57,%58,%59}, %60, p, 1, 1, 0;\n}\n"
   : "+f"(d[0]),"+f"(d[1]),"+f"(d[2]),"+f"(d[3]),"+f"(d[4]),"+f"(d[5]),"+f"(d[6]),"+f"(d[7]),"+f"(d[8]),"+f"(d[9]),"+f"(d[10]),"+f"(d[11]),"+f"(d[12]),"+f"(d[13]),"+f"(d[14]),"+f"(d[15]),"+f"(d[16]),"+f"(d[17]),"+f"(d[18]),"+f"(d[19]),"+f"(d[20]),"+f"(d[21]),"+f"(d[22]),"+f"(d[23]),"+f"(d[24]),"+f"(d[25]),"+f"(d[26]),"+f"(d[27]),"+f"(d[28]),"+f"(d[29]),"+f"(d[30]),"+f"(d[31]),"+f"(d[32]),"+f"(d[33]),"+f"(d[34]),"+f"(d[35]),"+f"(d[36]),"+f"(d[37]),"+f"(d[38]),"+f"(d[39]),"+f"(d[40]),"+f"(d[41]),"+f"(d[42]),"+f"(d[43]),"+f"(d[44]),"+f"(d[45]),"+f"(d[46]),"+f"(d[47]),"+f"(d[48]),"+f"(d[49]),"+f"(d[50]),"+f"(d[51]),"+f"(d[52]),"+f"(d[53]),"+f"(d[54]),"+f"(d[55])
   : "r"(a[0]), "r"(a[1]), "r"(a[2]), "r"(a[3]), "l"(db), "r"(sd));
}
template<> __device__ __forceinline__ void wgmma_rs<104,0>(float* d, const uint32_t* a, uint64_t db, int sd) {
  asm volatile("{\n.reg .pred p;\nsetp.ne.b32 p, %57, 0;\nwgmma.mma_async.sync.aligned.m64n104k16.f32.bf16.bf16 {%0,%1,%2,%3,%4,%5,%6,%7,%8,%9,%10,%11,%12,%13,%14,%15,%16,%17,%18,%19,%20,%21,%22,%23,%24,%25,%26,%27,%28,%29,%30,%31,%32,%33,%34,%35,%36,%37,%38,%39,%40,%41,%42,%43,%44,%45,%46,%47,%48,%49,%50,%51}, {%52,%53,%54,%55}, %56, p, 1, 1, 0;\n}\n"
   : "+f"(d[0]),"+f"(d[1]),"+f"(d[2]),"+f"(d[3]),"+f"(d[4]),"+f"(d[5]),"+f"(d[6]),"+f"(d[7]),"+f"(d[8]),"+f"(d[9]),"+f"(d[10]),"+f"(d[11]),"+f"(d[12]),"+f"(d[13]),"+f"(d[14]),"+f"(d[15]),"+f"(d[16]),"+f"(d[17]),"+f"(d[18]),"+f"(d[19]),"+f"(d[20]),"+f"(d[21]),"+f"(d[22]),"+f"(d[23]),"+f"(d[24]),"+f"(d[25]),"+f"(d[26]),"+f"(d[27]),"+f"(d[28]),"+f"(d[29]),"+f"(d[30]),"+f"(d[31]),"+f"(d[32]),"+f"(d[33]),"+f"(d[34]),"+f"(d[35]),"+f"(d[36]),"+f"(d[37]),"+f"(d[38]),"+f"(d[39]),"+f"(d[40]),"+f"(d[41]),"+f"(d[42]),"+f"(d[43]),"+f"(d[44]),"+f"(d[45]),"+f"(d[46]),"+f"(d[47]),"+f"(d[48]),"+f"(d[49]),"+f"(d[50]),"+f"(d[51])
   : "r"(a[0]), "r"(a[1]), "r"(a[2]), "r"(a[3]), "l"(db), "r"(sd));
}
template<> __device__ __forceinline__ void wgmma_rs<96,0>(float* d, const uint32_t* a, uint64_t db, int sd) {
  asm volatile("{\n.reg .pred p;\nsetp.ne.b32 p, %53, 0;\nwgmma.mma_async.sync.aligned.m64n96k16.f32.bf16.bf16 {%0,%1,%2,%3,%4,%5,%6,%7,%8,%9,%10,%11,%12,%13,%14,%15,%16,%17,%18,%19,%20,%21,%22,%23,%24,%25,%26,%27,%28,%29,%30,%31,%32,%33,%34,%35,%36,%37,%38,%39,%40,%41,%42,%43,%44,%45,%46,%47}, {%48,%49,%50,%51}, %52, p, 1, 1, 0;\n}\n"
   : "+f"(d[0]),"+f"(d[1]),"+f"(d[2]),"+f"(d[3]),"+f"(d[4]),"+f"(d[5]),"+f"(d[6]),"+f"(d[7]),"+f"(d[8]),"+f"(d[9]),"+f"(d[10]),"+f"(d[11]),"+f"(d[12]),"+f"(d[13]),"+f"(d[14]),"+f"(d[15]),"+f"(d[16]),"+f"(d[17]),"+f"(d[18]),"+f"(d[19]),"+f"(d[20]),"+f"(d[21]),"+f"(d[22]),"+f"(d[23]),"+f"(d[24]),"+f"(d[25]),"+f"(d[26]),"+f"(d[27]),"+f"(d[28]),"+f"(d[29]),"+f"(d[30]),"+f"(d[31]),"+f"(d[32]),"+f"(d[33]),"+f"(d[34]),"+f"(d[35]),"+f"(d[36]),"+f"(d[37]),"+f"(d[38]),"+f"(d[39]),"+f"(d[40]),"+f"(d[41]),"+f"(d[42]),"+f"(d[43]),"+f"(d[44]),"+f"(d[45]),"+f"(d[46]),"+f"(d[47])
   : "r"(a[0]), "r"(a[1]), "r"(a[2]), "r"(a[3]), "l"(db), "r"(sd));
}
template<> __device__ __forceinline__ void wgmma_rs<88,0>(float* d, const uint32_t* a, uint64_t db, int sd) {
  asm volatile("{\n.reg .pred p;\nsetp.ne.b32 p, %49, 0;\nwgmma.mma_async.sync.aligned.m64n88k16.f32.bf16.bf16 {%0,%1,%2,%3,%4,%5,%6,%7,%8,%9,%10,%11,%12,%13,%14,%15,%16,%17,%18,%19,%20,%21,%22,%23,%24,%25,%26,%27,%28,%29,%30,%31,%32,%33,%34,%35,%36,%37,%38,%39,%40,%41,%42,%43}, {%44,%45,%46,%47}, %48, p, 1, 1, 0;\n}\n"
   : "+f"(d[0]),"+f"(d[1]),"+f"(d[2]),"+f"(d[3]),"+f"(d[4]),"+f"(d[5]),"+f"(d[6]),"+f"(d[7]),"+f"(d[8]),"+f"(d[9]),"+f"(d[10]),"+f"(d[11]),"+f"(d[12]),"+f"(d[13]),"+f"(d[14]),"+f"(d[15]),"+f"(d[16]),"+f"(d[17]),"+f"(d[18]),"+f"(d[19]),"+f"(d[20]),"+f"(d[21]),"+f"(d[22]),"+f"(d[23]),"+f"(d[24]),"+f"(d[25]),"+f"(d[26]),"+f"(d[27]),"+f"(d[28]),"+f"(d[29]),"+f"(d[30]),"+f"(d[31]),"+f"(d[32]),"+f"(d[33]),"+f"(d[34]),"+f"(d[35]),"+f"(d[36]),"+f"(d[37]),"+f"(d[38]),"+f"(d[39]),"+f"(d[40]),"+f"(d[41]),"+f"(d[42]),"+f"(d[43])
   : "r"(a[0]), "r"(a[1]), "r"(a[2]), "r"(a[3]), "l"(db), "r"(sd));
}
template<> __device__ __forceinline__ void wgmma_rs<80,0>(float* d, const uint32_t* a, uint64_t db, int sd) {
  asm volatile("{\n.reg .pred p;\nsetp.ne.b32 p, %45, 0;\nwgmma.mma_async.sync.aligned.m64n80k16.f32.bf16.bf16 {%0,%1,%2,%3,%4,%5,%6,%7,%8,%9,%10,%11,%12,%13,%14,%15,%16,%17,%18,%19,%20,%21,%22,%23,%24,%25,%26,%27,%28,%29,%30,%31,%32,%33,%34,%35,%36,%37,%38,%39}, {%40,%41,%42,%43}, %44, p, 1, 1, 0;\n}\n"
   : "+f"(d[0]),"+f"(d[1]),"+f"(d[2]),"+f"(d[3]),"+f"(d[4]),"+f"(d[5]),"+f"(d[6]),"+f"(d[7]),"+f"(d[8]),"+f"(d[9]),"+f"(d[10]),"+f"(d[11]),"+f"(d[12]),"+f"(d[13]),"+f"(d[14]),"+f"(d[15]),"+f"(d[16]),"+f"(d[17]),"+f"(d[18]),"+f"(d[19]),"+f"(d[20]),"+f"(d[21]),"+f"(d[22]),"+f"(d[23]),"+f"(d[24]),"+f"(d[25]),"+f"(d[26]),"+f"(d[27]),"+f"(d[28]),"+f"(d[29]),"+f"(d[30]),"+f"(d[31]),"+f"(d[32]),"+f"(d[33]),"+f"(d[34]),"+f"(d[35]),"+f"(d[36]),"+f"(d[37]),"+f"(d[38]),"+f"(d[39])
   : "r"(a[0]), "r"(a[1]), "r"(a[2]), "r"(a[3]), "l"(db), "r"(sd));
}
template<> __device__ __forceinline__ void wgmma_rs<72,0>(float* d, const uint32_t* a, uint64_t db, int sd) {
  asm volatile("{\n.reg .pred p;\nsetp.ne.b32 p, %41, 0;\nwgmma.mma_async.sync.aligned.m64n72k16.f32.bf16.bf16 {%0,%1,%2,%3,%4,%5,%6,%7,%8,%9,%10,%11,%12,%13,%14,%15,%16,%17,%18,%19,%20,%21,%22,%23,%24,%25,%26,%27,%28,%29,%30,%31,%32,%33,%34,%35}, {%36,%37,%38,%39}, %40, p, 1, 1, 0;\n}\n"
   : "+f"(d[0]),"+f"(d[1]),"+f"(d[2]),"+f"(d[3]),"+f"(d[4]),"+f"(d[5]),"+f"(d[6]),"+f"(d[7]),"+f"(d[8]),"+f"(d[9]),"+f"(d[10]),"+f"(d[11]),"+f"(d[12]),"+f"(d[13]),"+f"(d[14]),"+f"(d[15]),"+f"(d[16]),"+f"(d[17]),"+f"(d[18]),"+f"(d[19]),"+f"(d[20]),"+f"(d[21]),"+f"(d[22]),"+f"(d[23]),"+f"(d[24]),"+f"(d[25]),"+f"(d[26]),"+f"(d[27]),"+f"(d[28]),"+f"(d[29]),"+f"(d[30]),"+f"(d[31]),"+f"(d[32]),"+f"(d[33]),"+f"(d[34]),"+f"(d[35])
   : "r"(a[0]), "r"(a[1]), "r"(a[2]), "r"(a[3]), "l"(db), "r"(sd));
}
template<> __device__ __forceinline__ void wgmma_rs<64,0>(float* d, const uint32_t* a, uint64_t db, int sd) {
  asm volatile("{\n.reg .pred p;\nsetp.ne.b32 p, %37, 0;\nwgmma.mma_async.sync.aligned.m64n64k16.f32.bf16.bf16 {%0,%1,%2,%3,%4,%5,%6,%7,%8,%9,%10,%11,%12,%13,%14,%15,%16,%17,%18,%19,%20,%21,%22,%23,%24,%25,%26,%27,%28,%29,%30,%31}, {%32,%33,%34,%35}, %36, p, 1, 1, 0;\n}\n"
   : "+f"(d[0]),"+f"(d[1]),"+f"(d[2]),"+f"(d[3]),"+f"(d[4]),"+f"(d[5]),"+f"(d[6]),"+f"(d[7]),"+f"(d[8]),"+f"(d[9]),"+f"(d[10]),"+f"(d[11]),"+f"(d[12]),"+f"(d[13]),"+f"(d[14]),"+f"(d[15]),"+f"(d[16]),"+f"(d[17]),"+f"(d[18]),"+f"(d[19]),"+f"(d[20]),"+f"(d[21]),"+f"(d[22]),"+f"(d[23]),"+f"(d[24]),"+f"(d[25]),"+f"(d[26]),"+f"(d[27]),"+f"(d[28]),"+f"(d[29]),"+f"(d[30]),"+f"(d[31])
   : "r"(a[0]), "r"(a[1]), "r"(a[2]), "r"(a[3]), "l"(db), "r"(sd));
}
template<> __device__ __forceinline__ void wgmma_ss<64,0,1>(float* d, uint64_t da, uint64_t db, int sd) {
  asm volatile("{\n.reg .pred p;\nsetp.ne.b32 p, %34, 0;\nwgmma.mma_async.sync.aligned.m64n64k16.f32.bf16.bf16 {%0,%1,%2,%3,%4,%5,%6,%7,%8,%9,%10,%11,%12,%13,%14,%15,%16,%17,%18,%19,%20,%21,%22,%23,%24,%25,%26,%27,%28,%29,%30,%31}, %32, %33, p, 1, 1, 0, 1;\n}\n"
   : "+f"(d[0]),"+f"(d[1]),"+f"(d[2]),"+f"(d[3]),"+f"(d[4]),"+f"(d[5]),"+f"(d[6]),"+f"(d[7]),"+f"(d[8]),"+f"(d[9]),"+f"(d[10]),"+f"(d[11]),"+f"(d[12]),"+f"(d[13]),"+f"(d[14]),"+f"(d[15]),"+f"(d[16]),"+f"(d[17]),"+f"(d[18]),"+f"(d[19]),"+f"(d[20]),"+f"(d[21]),"+f"(d[22]),"+f"(d[23]),"+f"(d[24]),"+f"(d[25]),"+f"(d[26]),"+f"(d[27]),"+f"(d[28]),"+f"(d[29]),"+f"(d[30]),"+f"(d[31])
   : "l"(da), "l"(db), "r"(sd));
}
template<> __device__ __forceinline__ void wgmma_ss<64,1,1>(float* d, uint64_t da, uint64_t db, int sd) {
  asm volatile("{\n.reg .pred p;\nsetp.ne.b32 p, %34, 0;\nwgmma.mma_async.sync.aligned.m64n64k16.f32.bf16.bf16 {%0,%1,%2,%3,%4,%5,%6,%7,%8,%9,%10,%11,%12,%13,%14,%15,%16,%17,%18,%19,%20,%21,%22,%23,%24,%25,%26,%27,%28,%29,%30,%31}, %32, %33, p, 1, 1, 1, 1;\n}\n"
   : "+f"(d[0]),"+f"(d[1]),"+f"(d[2]),"+f"(d[3]),"+f"(d[4]),"+f"(d[5]),"+f"(d[6]),"+f"(d[7]),"+f"(d[8]),"+f"(d[9]),"+f"(d[10]),"+f"(d[11]),"+f"(d[12]),"+f"(d[13]),"+f"(d[14]),"+f"(d[15]),"+f"(d[16]),"+f"(d[17]),"+f"(d[18]),"+f"(d[19]),"+f"(d[20]),"+f"(d[21]),"+f"(d[22]),"+f"(d[23]),"+f"(d[24]),"+f"(d[25]),"+f"(d[26]),"+f"(d[27]),"+f"(d[28]),"+f"(d[29]),"+f"(d[30]),"+f"(d[31])
   : "l"(da), "l"(db), "r"(sd));
}
template<> __device__ __forceinline__ void wgmma_ss<192,0,1>(float* d, uint64_t da, uint64_t db, int sd) {
  asm volatile("{\n.reg .pred p;\nsetp.ne.b32 p, %98, 0;\nwgmma.mma_async.sync.aligned.m64n192k16.f32.bf16.bf16 {%0,%1,%2,%3,%4,%5,%6,%7,%8,%9,%10,%11,%12,%13,%14,%15,%16,%17,%18,%19,%20,%21,%22,%23,%24,%25,%26,%27,%28,%29,%30,%31,%32,%33,%34,%35,%36,%37,%38,%39,%40,%41,%42,%43,%44,%45,%46,%47,%48,%49,%50,%51,%52,%53,%54,%55,%56,%57,%58,%59,%60,%61,%62,%63,%64,%65,%66,%67,%68,%69,%70,%71,%72,%73,%74,%75,%76,%77,%78,%79,%80,%81,%82,%83,%84,%85,%86,%87,%88,%89,%90,%91,%92,%93,%94,%95}, %96, %97, p, 1, 1, 0, 1;\n}\n"
   : "+f"(d[0]),"+f"(d[1]),"+f"(d[2]),"+f"(d[3]),"+f"(d[4]),"+f"(d[5]),"+f"(d[6]),"+f"(d[7]),"+f"(d[8]),"+f"(d[9]),"+f"(d[10]),"+f"(d[11]),"+f"(d[12]),"+f"(d[13]),"+f"(d[14]),"+f"(d[15]),"+f"(d[16]),"+f"(d[17]),"+f"(d[18]),"+f"(d[19]),"+f"(d[20]),"+f"(d[21]),"+f"(d[22]),"+f"(d[23]),"+f"(d[24]),"+f"(d[25]),"+f"(d[26]),"+f"(d[27]),"+f"(d[28]),"+f"(d[29]),"+f"(d[30]),"+f"(d[31]),"+f"(d[32]),"+f"(d[33]),"+f"(d[34]),"+f"(d[35]),"+f"(d[36]),"+f"(d[37]),"+f"(d[38]),"+f"(d[39]),"+f"(d[40]),"+f"(d[41]),"+f"(d[42]),"+f"(d[43]),"+f"(d[44]),"+f"(d[45]),"+f"(d[46]),"+f"(d[47]),"+f"(d[48]),"+f"(d[49]),"+f"(d[50]),"+f"(d[51]),"+f"(d[52]),"+f"(d[53]),"+f"(d[54]),"+f"(d[55]),"+f"(d[56]),"+f"(d[57]),"+f"(d[58]),"+f"(d[59]),"+f"(d[60]),"+f"(d[61]),"+f"(d[62]),"+f"(d[63]),"+f"(d[64]),"+f"(d[65]),"+f"(d[66]),"+f"(d[67]),"+f"(d[68]),"+f"(d[69]),"+f"(d[70]),"+f"(d[71]),"+f"(d[72]),"+f"(d[73]),"+f"(d[74]),"+f"(d[75]),"+f"(d[76]),"+f"(d[77]),"+f"(d[78]),"+f"(d[79]),"+f"(d[80]),"+f"(d[81]),"+f"(d[82]),"+f"(d[83]),"+f"(d[84]),"+f"(d[85]),"+f"(d[86]),"+f"(d[87]),"+f"(d[88]),"+f"(d[89]),"+f"(d[90]),"+f"(d[91]),"+f"(d[92]),"+f"(d[93]),"+f"(d[94]),"+f"(d[95])
   : "l"(da), "l"(db), "r"(sd));
}
template<> __device__ __forceinline__ void wgmma_ss<192,1,1>(float* d, uint64_t da, uint64_t db, int sd) {
  asm volatile("{\n.reg .pred p;\nsetp.ne.b32 p, %98, 0;\nwgmma.mma_async.sync.aligned.m64n192k16.f32.bf16.bf16 {%0,%1,%2,%3,%4,%5,%6,%7,%8,%9,%10,%11,%12,%13,%14,%15,%16,%17,%18,%19,%20,%21,%22,%23,%24,%25,%26,%27,%28,%29,%30,%31,%32,%33,%34,%35,%36,%37,%38,%39,%40,%41,%42,%43,%44,%45,%46,%47,%48,%49,%50,%51,%52,%53,%54,%55,%56,%57,%58,%59,%60,%61,%62,%63,%64,%65,%66,%67,%68,%69,%70,%71,%72,%73,%74,%75,%76,%77,%78,%79,%80,%81,%82,%83,%84,%85,%86,%87,%88,%89,%90,%91,%92,%93,%94,%95}, %96, %97, p, 1, 1, 1, 1;\n}\n"
   : "+f"(d[0]),"+f"(d[1]),"+f"(d[2]),"+f"(d[3]),"+f"(d[4]),"+f"(d[5]),"+f"(d[6]),"+f"(d[7]),"+f"(d[8]),"+f"(d[9]),"+f"(d[10]),"+f"(d[11]),"+f"(d[12]),"+f"(d[13]),"+f"(d[14]),"+f"(d[15]),"+f"(d[16]),"+f"(d[17]),"+f"(d[18]),"+f"(d[19]),"+f"(d[20]),"+f"(d[21]),"+f"(d[22]),"+f"(d[23]),"+f"(d[24]),"+f"(d[25]),"+f"(d[26]),"+f"(d[27]),"+f"(d[28]),"+f"(d[29]),"+f"(d[30]),"+f"(d[31]),"+f"(d[32]),"+f"(d[33]),"+f"(d[34]),"+f"(d[35]),"+f"(d[36]),"+f"(d[37]),"+f"(d[38]),"+f"(d[39]),"+f"(d[40]),"+f"(d[41]),"+f"(d[42]),"+f"(d[43]),"+f"(d[44]),"+f"(d[45]),"+f"(d[46]),"+f"(d[47]),"+f"(d[48]),"+f"(d[49]),"+f"(d[50]),"+f"(d[51]),"+f"(d[52]),"+f"(d[53]),"+f"(d[54]),"+f"(d[55]),"+f"(d[56]),"+f"(d[57]),"+f"(d[58]),"+f"(d[59]),"+f"(d[60]),"+f"(d[61]),"+f"(d[62]),"+f"(d[63]),"+f"(d[64]),"+f"(d[65]),"+f"(d[66]),"+f"(d[67]),"+f"(d[68]),"+f"(d[69]),"+f"(d[70]),"+f"(d[71]),"+f"(d[72]),"+f"(d[73]),"+f"(d[74]),"+f"(d[75]),"+f"(d[76]),"+f"(d[77]),"+f"(d[78]),"+f"(d[79]),"+f"(d[80]),"+f"(d[81]),"+f"(d[82]),"+f"(d[83]),"+f"(d[84]),"+f"(d[85]),"+f"(d[86]),"+f"(d[87]),"+f"(d[88]),"+f"(d[89]),"+f"(d[90]),"+f"(d[91]),"+f"(d[92]),"+f"(d[93]),"+f"(d[94]),"+f"(d[95])
   : "l"(da), "l"(db), "r"(sd));
}

__device__ __forceinline__ void stats_publish(uint32_t sb, int layer, int rb, int hg, int ht, uint32_t tag) {
  const int lane = ht & 31, w = ht >> 5, g = lane >> 2, t = lane & 3;
  mbar_wait(sb + SM_BAR + 8 * (B_XF + hg), layer);
  uint32_t A[2][16];
#pragma unroll
  for (int h = 0; h < 2; h++) {
    const uint32_t xb = sb + SM_X + hg * 16384 + h * 8192;
#pragma unroll
    for (int ks = 0; ks < 4; ks++) {
      if (layer == 0) {
        const int row = 16 * w + (lane & 15), kc = 2 * ks + (lane >> 4);
        ldsm4(&A[h][4 * ks], xb + row * 128 + ((kc ^ (row & 7)) << 4));
      } else {
        const int k = 16 * ks + (lane & 7) + 8 * (lane >> 4), pc = 2 * w + ((lane >> 3) & 1);
        ldsm4t(&A[h][4 * ks], xb + k * 128 + ((pc ^ (k & 7)) << 4));
      }
    }
  }
  float s[4], q[4];
#pragma unroll
  for (int r = 0; r < 4; r++) {
    s[r] = q[r] = 0.f;
#pragma unroll
    for (int i = 0; i < 8; i++) {
      const uint32_t v = A[r >> 1][2 * i + (r & 1)];
      const float a = bf_lo(v), b = bf_hi(v);
      s[r] += a + b; q[r] = fmaf(a, a, q[r]); q[r] = fmaf(b, b, q[r]);
    }
  }
#pragma unroll
  for (int r = 0; r < 2; r++) {
    s[r] = ((t & 2) ? s[r + 2] : s[r]) + __shfl_xor_sync(~0u, (t & 2) ? s[r] : s[r + 2], 2);
    q[r] = ((t & 2) ? q[r + 2] : q[r]) + __shfl_xor_sync(~0u, (t & 2) ? q[r] : q[r + 2], 2);
  }
  s[0] = ((t & 1) ? s[1] : s[0]) + __shfl_xor_sync(~0u, (t & 1) ? s[0] : s[1], 1);
  q[0] = ((t & 1) ? q[1] : q[0]) + __shfl_xor_sync(~0u, (t & 1) ? q[0] : q[1], 1);
  st_tagged(&g_part[(rb * 8 + hg) * 128 + 64 * (t >> 1) + 16 * w + 8 * (t & 1) + g], __float_as_uint(s[0]), __float_as_uint(q[0]), tag);
}
__device__ __forceinline__ void stats_gather(uint32_t sb, int rb, int ht, uint32_t tag) {
  const uint4* src = &g_part[rb * 8 * 128 + ht];
  uint4 v[8];
  bool ok;
  int it = 0;
  do {
    ok = true;
#pragma unroll
    for (int i = 0; i < 8; i++) v[i] = ld_tagged(src + i * 128);
#pragma unroll
    for (int i = 0; i < 8; i++) ok = ok && v[i].y == tag && v[i].w == tag;
    if (++it > (1 << 22)) __trap();
  } while (!__all_sync(~0u, ok));
  float s = 0.f, q = 0.f;
#pragma unroll
  for (int i = 0; i < 8; i++) { s += __uint_as_float(v[i].x); q += __uint_as_float(v[i].z); }
  const float mean = s * (1.f / DM);
  const float rstd = rsqrt_approx(fmaxf(q * (1.f / DM) - mean * mean, 0.f) + 1e-5f);
  asm volatile("st.shared.v2.f32 [%0], {%1,%2};" ::"r"(sb + SM_ST + ht * 8), "f"(mean), "f"(rstd) : "memory");
  __syncwarp();
  if (elect_one()) mbar_arrive(sb + SM_BAR + 8 * B_STF);
}

template <bool TR>
__device__ __forceinline__ void gemm_section(float* acc, uint32_t sb, int layer, int wg, int w, int lane) {
  const uint32_t bar = sb + SM_BAR;
  const bool leader = (w == 0) && (lane == 0);
  auto issue = [&](int c, int slot) {
    mbar_wait(bar + 8 * (B_XF + c), layer);
    mbar_wait(bar + 8 * (B_KVF + c), layer);
    const uint64_t da = mkdesc(sb + SM_X + c * 16384 + wg * 8192, TR ? 8192 : 16, 1024, 1);
    const uint64_t db = mkdesc(sb + SM_W + slot * 24576, 8192, 1024, 1);
    wg_fence();
#pragma unroll
    for (int ks = 0; ks < 4; ks++) wgmma_ss<192, TR ? 1 : 0, 1>(acc, da + (TR ? ks * 128 : ks * 2), db + ks * 128, (c | ks) != 0);
    wg_commit();
  };
  auto step = [&](int c, int slot) {
    issue(c, slot);
    wg_wait<1>();
    if (leader) mbar_arrive(bar + 8 * (B_KVE + c - 1));
  };
  issue(0, 0);
  if (threadIdx.x == 0) TS(2 + layer * 20 + 0);
  if (threadIdx.x == 128 && layer == 1) TS(60);
  step(1, 1); step(2, 2); step(3, 0); step(4, 1); step(5, 2);
  issue(6, 0);
  wg_wait<1>();
  if (wg == 0) bar_sync(5, 256);
  issue(7, 1);
  if (wg == 1) bar_arrive(5, 256);
}

__device__ __forceinline__ void attn_phase(const Params& p, uint32_t sb, int layer, int rb, int hg, int wg, int w) {
  const int lane = opaque_tid() & 31;
  const int g = lane >> 2, t = lane & 3;
  const uint32_t bar = sb + SM_BAR;
  const int row0 = 64 * wg + 16 * w;
  const bool leader = (w == 0) && (lane == 0);
  float acc[96];
  float2 cs[24];
  if (layer) gemm_section<true>(acc, sb, layer, wg, w, lane);
  else gemm_section<false>(acc, sb, layer, wg, w, lane);
  mbar_wait(bar + 8 * B_STF, layer);
  const uint32_t tag = 2 * lds32(sb + SM_EP) + layer + 1;
  const float2 st0 = lds64f(sb + SM_ST + (row0 + g) * 8), st1 = lds64f(sb + SM_ST + (row0 + g + 8) * 8);
  const float mean0 = st0.x, rstd0 = st0.y, mean1 = st1.x, rstd1 = st1.y;
#pragma unroll
  for (int j = 8; j < 24; j++) cs[j] = lds64f(sb + SM_CS + 4 * (8 * j + 2 * t));
  wg_wait<0>();
  if (threadIdx.x == 0) TS(2 + layer * 20 + 1);
  if (leader) mbar_arrive(bar + 8 * B_QDONE);

  uint32_t kb[4][8], vb[4][8], qa[4][4];
  {
    const float nm0 = -mean0 * rstd0, nm1 = -mean1 * rstd1;
    const int st_row = row0 + (lane & 7) + 8 * ((lane >> 3) & 1);
    const uint32_t st_base = sb + SM_KVX + st_row * 256;
    const bool sender = (wg == 1 && w == 3 && rb < 15);
    uint4* halo = &g_halo[(rb * 8 + hg) * 384 + lane];
    if (wg == 0 && w == 3) bar_sync(6, 64);
    uint32_t r[4][2][4];
#pragma unroll
    for (int h = 0; h < 4; h++) {
#pragma unroll
      for (int kv = 0; kv < 2; kv++) {
#pragma unroll
        for (int dh = 0; dh < 2; dh++) {
          const int j = 8 + kv * 8 + 2 * h + dh;
          const float2 c2 = cs[j];
          const float v0 = fmaf(acc[4 * j + 0], rstd0, nm0 * c2.x), v1 = fmaf(acc[4 * j + 1], rstd0, nm0 * c2.y);
          const float v2 = fmaf(acc[4 * j + 2], rstd1, nm1 * c2.x), v3 = fmaf(acc[4 * j + 3], rstd1, nm1 * c2.y);
          r[h][kv][2 * dh] = packbf(v0, v1);
          r[h][kv][2 * dh + 1] = packbf(v2, v3);
        }
      }
      if (sender) {
        st_tagged3(halo + (3 * h) * 32, r[h][0][0], r[h][0][1], r[h][0][2], tag);
        st_tagged3(halo + (3 * h + 1) * 32, r[h][0][3], r[h][1][0], r[h][1][1], tag);
        st_tagged3(halo + (3 * h + 2) * 32, r[h][1][2], r[h][1][3], 0u, tag);
      }
    }
    if (wg == 1 && w == 3) bar_arrive(6, 64);
    if (layer == 1 && threadIdx.x == 224) TS(47);
#pragma unroll
    for (int j = 0; j < 8; j++) cs[j] = lds64f(sb + SM_CS + 4 * (8 * j + 2 * t));
    mbar_wait(bar + 8 * B_QDONE, layer);
#pragma unroll
    for (int h = 0; h < 4; h++) {
#pragma unroll
      for (int kv = 0; kv < 2; kv++) {
        const int chunk = 4 * h + 2 * kv + (lane >> 4);
        stsm4(st_base + (((chunk & 8) | ((chunk ^ st_row) & 7)) << 4), r[h][kv][0], r[h][kv][1], r[h][kv][2], r[h][kv][3]);
      }
      kb[h][4] = r[h][0][0]; kb[h][5] = r[h][0][2]; kb[h][6] = r[h][0][1]; kb[h][7] = r[h][0][3];
      vb[h][4] = movm_t(r[h][1][0]); vb[h][5] = movm_t(r[h][1][1]); vb[h][6] = movm_t(r[h][1][2]); vb[h][7] = movm_t(r[h][1][3]);
    }
    if (layer == 1 && threadIdx.x == 0) TS(45);
#pragma unroll
    for (int h = 0; h < 4; h++) {
#pragma unroll
      for (int dh = 0; dh < 2; dh++) {
        const int j = 2 * h + dh;
        const float2 c2 = cs[j];
        qa[h][2 * dh] = packbf(fmaf(-mean0, c2.x, acc[4 * j + 0]), fmaf(-mean0, c2.y, acc[4 * j + 1]));
        qa[h][2 * dh + 1] = packbf(fmaf(-mean1, c2.x, acc[4 * j + 2]), fmaf(-mean1, c2.y, acc[4 * j + 3]));
      }
    }
  }
  bar_sync(1, 256);
  if (threadIdx.x == 0) TS(2 + layer * 20 + 2);
  {
    const uint32_t own_base = sb + SM_KVX + row0 * 256;
    const int mi = lane >> 3;
    const int r = 8 * (mi >> 1) + (lane & 7), r2 = 8 * (mi & 1) + (lane & 7);
    if (row0 != 0) {
#pragma unroll
      for (int h = 0; h < 4; h++) {
        const int ch = 4 * h + (mi & 1), ch2 = 4 * h + 2 + (mi >> 1);
        ldsm4(&kb[h][0], own_base - 16 * 256 + r * 256 + (((ch & 8) | ((ch ^ r) & 7)) << 4));
        ldsm4t(&vb[h][0], own_base - 16 * 256 + r2 * 256 + (((ch2 & 8) | ((ch2 ^ r2) & 7)) << 4));
      }
    } else if (rb > 0) {
      const uint4* src = &g_halo[((rb - 1) * 8 + hg) * 384 + lane];
      uint4 hv[12];
      int it = 0;
      bool ok;
      do {
        ok = true;
#pragma unroll
        for (int i = 0; i < 12; i++) hv[i] = ld_tagged(src + i * 32);
#pragma unroll
        for (int i = 0; i < 12; i++) ok = ok && hv[i].w == tag;
      } while (!__all_sync(~0u, ok) && ++it < (1 << 20));
      if (lane == 0) mbar_arrive(bar + 8 * B_HF);
#pragma unroll
      for (int h = 0; h < 4; h++) {
        kb[h][0] = hv[3 * h].x; kb[h][1] = hv[3 * h].z; kb[h][2] = hv[3 * h].y; kb[h][3] = hv[3 * h + 1].x;
        vb[h][0] = movm_t(hv[3 * h + 1].y); vb[h][1] = movm_t(hv[3 * h + 1].z);
        vb[h][2] = movm_t(hv[3 * h + 2].x); vb[h][3] = movm_t(hv[3 * h + 2].y);
      }
    } else {
#pragma unroll
      for (int h = 0; h < 4; h++)
#pragma unroll
        for (int k = 0; k < 4; k++) kb[h][k] = vb[h][k] = 0u;
    }
    if (threadIdx.x == 0) TS(2 + layer * 20 + 4);
  }

  const bool first = (rb == 0 && wg == 0 && w == 0);
  const int e = t - (g >> 1);
  const bool par = g & 1, epos = e >= 1;
  const uint32_t pmask = par ? 0xffff0000u : 0x0000ffffu;
  const uint32_t mB0 = epos ? pmask : 0u, mB1 = epos ? 0u : pmask;
  const float cl2 = 0.25f * 1.4426950408889634f;
  const float sc0 = rstd0 * cl2, sc1 = rstd1 * cl2;
  const float NEG = -INFINITY;
  float vA0[4], vB0[4], vA1[4], vB1[4];
#pragma unroll
  for (int h = 0; h < 4; h++) {
    float S[4][4];
#pragma unroll
    for (int j = 0; j < 4; j++) {
      S[j][0] = S[j][1] = S[j][2] = S[j][3] = 0.f;
      mma_bf16(S[j], qa[h], kb[h][2 * j], kb[h][2 * j + 1]);
    }
    vA0[h] = par ? S[1][1] : S[1][0];
    vB0[h] = epos ? (par ? S[0][1] : S[0][0]) : (par ? S[2][1] : S[2][0]);
    vA1[h] = par ? S[2][3] : S[2][2];
    vB1[h] = epos ? (par ? S[1][3] : S[1][2]) : (par ? S[3][3] : S[3][2]);
    if (first) { vA0[h] = NEG; if (epos) { vB0[h] = NEG; vB1[h] = NEG; } }
  }
  float m0[4], m1[4];
#pragma unroll
  for (int h = 0; h < 4; h++) { m0[h] = fmaxf(vA0[h], vB0[h]); m1[h] = fmaxf(vA1[h], vB1[h]); }
#pragma unroll
  for (int o = 1; o <= 2; o <<= 1) {
#pragma unroll
    for (int h = 0; h < 4; h++) {
      m0[h] = fmaxf(m0[h], __shfl_xor_sync(~0u, m0[h], o));
      m1[h] = fmaxf(m1[h], __shfl_xor_sync(~0u, m1[h], o));
    }
  }
  float O0[4][4], O1[4][4], Z[4][4];
#pragma unroll
  for (int h = 0; h < 4; h++) {
    const float mm0 = -m0[h] * sc0, mm1 = -m1[h] * sc1;
    const float pA0 = ex2(fmaf(vA0[h], sc0, mm0)), pB0 = ex2(fmaf(vB0[h], sc0, mm0));
    const float pA1 = ex2(fmaf(vA1[h], sc1, mm1)), pB1 = ex2(fmaf(vB1[h], sc1, mm1));
    const uint32_t hA0 = packbf(pA0, pA0), hB0 = packbf(pB0, pB0), hA1 = packbf(pA1, pA1), hB1 = packbf(pB1, pB1);
    const uint32_t P0[4] = {hB0 & mB0, 0u, hA0 & pmask, hB1 & mB0};
    const uint32_t P1[4] = {hB0 & mB1, hA1 & pmask, 0u, hB1 & mB1};
#pragma unroll
    for (int k = 0; k < 4; k++) O0[h][k] = O1[h][k] = Z[h][k] = 0.f;
    mma_bf16(O0[h], P0, vb[h][0], vb[h][1]); mma_bf16(O1[h], P0, vb[h][2], vb[h][3]); mma_bf16(Z[h], P0, 0x3f803f80u, 0x3f803f80u);
    mma_bf16(O0[h], P1, vb[h][4], vb[h][5]); mma_bf16(O1[h], P1, vb[h][6], vb[h][7]); mma_bf16(Z[h], P1, 0x3f803f80u, 0x3f803f80u);
  }
  const uint32_t ob = sb + SM_OST + wg * 8192;
  const int o_row = 16 * w + (lane & 7) + 8 * ((lane >> 3) & 1);
#pragma unroll
  for (int h = 0; h < 4; h++) {
    const float i0 = rcp_approx(Z[h][0]), i1 = rcp_approx(Z[h][2]);
    const int ch = 2 * h + (lane >> 4);
    stsm4(ob + o_row * 128 + ((ch ^ (o_row & 7)) << 4), packbf(O0[h][0] * i0, O0[h][1] * i0), packbf(O0[h][2] * i1, O0[h][3] * i1),
          packbf(O1[h][0] * i0, O1[h][1] * i0), packbf(O1[h][2] * i1, O1[h][3] * i1));
  }
  if (threadIdx.x == 0) TS(2 + layer * 20 + 5);
  fence_writer();
  bar_sync(2 + wg, 128);
  if (w == 0 && elect_one()) {
    fence_reader();
    tma_st(&p.mapO, hg * 64, rb * 128 + wg * 64, ob);
    bulk_commit();
    mbar_arrive(bar + 8 * B_AD);
    bulk_wait_all();
    red_relaxed(&g_cnt[(C_O + rb) * 32]);
    mbar_arrive(bar + 8 * B_OST);
    if (threadIdx.x == 0) TS(2 + layer * 20 + 6);
  }
}

__device__ __forceinline__ void proj_phase(const Params& p, uint32_t sb, int layer, int rb, int q, int wg, int w) {
  const int lane = opaque_tid() & 31;
  const bool TR = layer != 0;
  const int t = lane & 3;
  const uint32_t bar = sb + SM_BAR;
  const uint32_t rbx = sb + SM_R + wg * 8192;
  uint32_t res[16];
  mbar_wait(bar + 8 * B_RF, layer);
  if (threadIdx.x == 0) TS(2 + layer * 20 + 7);
  if (!TR) {
#pragma unroll
    for (int j = 0; j < 8; j += 2) {
      const int mi = lane >> 3;
      const int row = 16 * w + (lane & 7) + 8 * (mi & 1), ch = j + (mi >> 1);
      ldsm4(&res[2 * j], rbx + row * 128 + ((ch ^ (row & 7)) << 4));
    }
  } else {
#pragma unroll
    for (int j = 0; j < 8; j += 2) {
      const int mi = lane >> 3;
      const int line = 8 * (j + (mi >> 1)) + (lane & 7), pc = 2 * w + (mi & 1);
      ldsm4t(&res[2 * j], rbx + line * 128 + ((pc ^ (line & 7)) << 4));
    }
  }
  bar_sync(2 + wg, 128);
  float acc[32];
#pragma unroll
  for (int i = 0; i < 16; i++) {
    asm volatile("shl.b32 %0, %1, 16;" : "=f"(acc[2 * i]) : "r"(res[i]));
    asm volatile("and.b32 %0, %1, 0xffff0000;" : "=f"(acc[2 * i + 1]) : "r"(res[i]));
  }
  const uint32_t tag = 4 * lds32(sb + SM_EP) + 2 * layer + 2;
#pragma unroll 1
  for (int c = 0; c < 8; c++) {
    if ((c & 1) == 0) mbar_wait(bar + 8 * (B_WOF + (c >> 1)), layer);
    mbar_wait(bar + 8 * (B_OF + c), layer);
    if (c == 0 && threadIdx.x == 0) TS(2 + layer * 20 + 8);
    const uint64_t da = mkdesc(sb + (c < 4 ? SM_X + 65536 + c * 16384 : SM_W + (c - 4) * 16384) + wg * 8192, 16, 1024, 1);
    const uint64_t db = mkdesc(sb + SM_X + c * 8192, 8192, 1024, 1);
    wg_fence();
#pragma unroll
    for (int ks = 0; ks < 4; ks++) wgmma_ss<64, 0, 1>(acc, da + ks * 2, db + ks * 128, 1);
    wg_commit();
  }
  wg_wait<0>();
#pragma unroll
  for (int i = 0; i < 32; i++) asm volatile("" : "+f"(acc[i]) :: "memory");
  if (threadIdx.x == 0) TS(2 + layer * 20 + 9);
  if (lane == 0 && w == 0) mbar_arrive(bar + 8 * B_PDONE);
  {
    float s[4], qq[4];
#pragma unroll
    for (int k = 0; k < 4; k++) { s[k] = acc[k]; qq[k] = acc[k] * acc[k]; }
#pragma unroll
    for (int j = 1; j < 8; j++)
#pragma unroll
      for (int k = 0; k < 4; k++) { s[k] += acc[4 * j + k]; qq[k] = fmaf(acc[4 * j + k], acc[4 * j + k], qq[k]); }
    const float s0 = s[0] + s[1], s1 = s[2] + s[3], q0 = qq[0] + qq[1], q1 = qq[2] + qq[3];
    float sr = ((t & 1) ? s1 : s0) + __shfl_xor_sync(~0u, (t & 1) ? s0 : s1, 1);
    float qr = ((t & 1) ? q1 : q0) + __shfl_xor_sync(~0u, (t & 1) ? q0 : q1, 1);
    sr += __shfl_xor_sync(~0u, sr, 2);
    qr += __shfl_xor_sync(~0u, qr, 2);
    if (t < 2) st_tagged(&g_part[(rb * 8 + q) * 128 + 64 * wg + 16 * w + (lane >> 2) + 8 * t], __float_as_uint(sr), __float_as_uint(qr), tag);
    __syncwarp();
    if (elect_one()) mbar_arrive(bar + 8 * B_PS);
  }
#pragma unroll
  for (int j = 0; j < 8; j += 2) {
    const int mi = lane >> 3;
    const int line = 8 * (j + (mi >> 1)) + (lane & 7), pc = 2 * w + (mi & 1);
    stsm4t(rbx + line * 128 + ((pc ^ (line & 7)) << 4), packbf(acc[4 * j], acc[4 * j + 1]), packbf(acc[4 * j + 2], acc[4 * j + 3]),
           packbf(acc[4 * j + 4], acc[4 * j + 5]), packbf(acc[4 * j + 6], acc[4 * j + 7]));
  }
  fence_writer();
  bar_sync(2 + wg, 128);
  if (w == 0 && elect_one()) {
    fence_reader();
    mbar_wait(bar + 8 * B_ZF, layer);
    fence_async_global();
    tma_st(&p.mapXT, rb * 128 + wg * 64, (2 * layer) * DM + q * 64, rbx);
    bulk_commit();
    if (threadIdx.x == 0) TS(2 + layer * 20 + 10);
    asm volatile("cp.async.bulk.wait_group.read 0;" ::: "memory");
    if (wg == 0) mbar_arrive(bar + 8 * B_RE);
  }
}
__device__ __forceinline__ void proj_stats(int layer, int rb, int q, int lane, uint32_t tag) {
  const int r = 16 * q + (lane & 15);
  const uint4* src = &g_part[(rb * 8 + (lane >> 4) * 4) * 128 + r];
  uint4 v[4];
  bool ok;
  int it = 0;
  do {
    ok = true;
#pragma unroll
    for (int i = 0; i < 4; i++) v[i] = ld_tagged(src + i * 128);
#pragma unroll
    for (int i = 0; i < 4; i++) ok = ok && v[i].y == tag && v[i].w == tag;
    if (++it > (1 << 22)) __trap();
  } while (!__all_sync(~0u, ok));
  float s = (__uint_as_float(v[0].x) + __uint_as_float(v[1].x)) + (__uint_as_float(v[2].x) + __uint_as_float(v[3].x));
  float qq = (__uint_as_float(v[0].z) + __uint_as_float(v[1].z)) + (__uint_as_float(v[2].z) + __uint_as_float(v[3].z));
  s += __shfl_xor_sync(~0u, s, 16);
  qq += __shfl_xor_sync(~0u, qq, 16);
  const float mean = s * (1.f / DM);
  const float rstd = rsqrt_approx(fmaxf(fmaf(qq, 1.f / DM, -mean * mean), 0.f) + 1e-5f), nm = -mean * rstd;
  const float nm1 = __shfl_xor_sync(~0u, nm, 1), rstd1 = __shfl_xor_sync(~0u, rstd, 1);
  if ((lane & 17) == 0)
    st_tagged3((uint4*)g_stats + (layer * 32 + rb * 2 + (r >> 6)) * 32 + ((r & 7) >> 1) * 8 + ((r >> 3) & 7),
               __float_as_uint(nm), __float_as_uint(rstd) | 1u, __float_as_uint(nm1), __float_as_uint(rstd1));
}

#define NA 8
template <bool GB> __host__ __device__ constexpr int grp_n() { return GB ? 17 - NA : NA; }
template <bool GB> __host__ __device__ constexpr int grp_m(int i) { return i == 0 ? (GB ? 1 : 0) : (GB ? NA + i : 1 + i); }
template <bool GB> __device__ __forceinline__ void conv_load(uint32_t* A, uint32_t pe) {
#pragma unroll
  for (int i = 0; i < grp_n<GB>(); i++) {
    A[4 * i + 2] = lds32(pe + 4 * (64 * grp_m<GB>(i) - 8));
    A[4 * i + 0] = lds32(pe + 4 * (64 * grp_m<GB>(i)));
    A[4 * i + 1] = lds32(pe + 4 * (64 * grp_m<GB>(i) + 8));
  }
}
template <bool GB> __device__ __forceinline__ void conv_dup_early(uint32_t* A, uint32_t zero) {
#pragma unroll
  for (int i = 0; i < grp_n<GB>(); i++) asm volatile("or.b32 %0, %1, %2;" : "=r"(A[4 * i + 3]) : "r"(A[4 * i + 0]), "r"(zero));
}
template <bool GB> __device__ __forceinline__ void conv_dup(uint32_t* A) {
#pragma unroll
  for (int i = 0; i < grp_n<GB>(); i++) asm volatile("mov.b32 %0, %1;" : "=r"(A[4 * i + 3]) : "r"(A[4 * i + 0]));
}
template <bool GB, int I0, int I1> __device__ __forceinline__ void conv_mmas(float* acc, const uint32_t* A, uint64_t d) {
  if constexpr (I0 < I1) {
    constexpr int M = grp_m<GB>(I0);
    wgmma_rs<128 - 8 * (M / 2), 0>(acc, A + 4 * I0, d + (uint64_t)(4 * M), M != 0);
    conv_mmas<GB, I0 + 1, I1>(acc, A, d);
  }
}
struct SumAddr { uint32_t l0, l1, se, so; };
__device__ __forceinline__ SumAddr conv_sum_addr(uint32_t sb, int c) {
  const int m = c == 127 ? -1 : c;
  const uint32_t up = m >= 1 ? ((m - 1) & 1) * CV_UH + (127 - ((m - 1) >> 1)) * 16 + 8 : 128 * 16;
  const uint32_t un = ((m + 1) & 1) * CV_UH + (127 - ((m + 1) >> 1)) * 16;
  const int ce = (m + 2) & 127, co = m + 1;
  return {sb + cv_u(0) + ((c & 1) ? un : up), sb + cv_u(0) + ((c & 1) ? up : un),
          sb + cv_s(0) + ((ce >> 3) & 1) * 1024 + (ce >> 4) * 128 + (((ce ^ (ce >> 4)) & 7) << 4),
          sb + cv_s(0) + 2048 + ((co >> 3) & 1) * 1024 + (co >> 4) * 128 + (((co ^ (co >> 4)) & 7) << 4)};
}
__device__ __forceinline__ void conv_sums(const SumAddr& sa, int lc, int c, uint4 own) {
  if (c == 127) own = make_uint4(0, 0, 0, 0);
  const bool odd = c & 1;
  const float2 v0 = lds64f(sa.l0 + lc * 32768), v1 = lds64f(sa.l1 + lc * 32768);
  const uint32_t x[8] = {__float_as_uint(odd ? v1.x : v0.x), __float_as_uint(odd ? v1.y : v0.y), own.x, own.y, own.z, own.w,
                         __float_as_uint(odd ? v0.x : v1.x), __float_as_uint(odd ? v0.y : v1.y)};
  float pv[16];
#pragma unroll
  for (int k = 0; k < 8; k++) { pv[2 * k] = bf_lo(x[k]); pv[2 * k + 1] = bf_hi(x[k]); }
  float sf[8], pf[8], s9[8], s7[8];
  sf[7] = pv[7]; pf[0] = pv[8];
#pragma unroll
  for (int i = 6; i >= 0; i--) sf[i] = sf[i + 1] + pv[i];
#pragma unroll
  for (int i = 1; i < 8; i++) pf[i] = pf[i - 1] + pv[8 + i];
#pragma unroll
  for (int i = 0; i < 8; i++) {
    s9[i] = sf[i] + pf[i];
    s7[i] = i == 0 ? sf[1] : i == 7 ? pf[6] : sf[i + 1] + pf[i - 1];
  }
  uint4 e4 = make_uint4(packbf(s9[0], s9[1]), packbf(s9[2], s9[3]), packbf(s9[4], s9[5]), packbf(s9[6], s9[7]));
  if (c == 126) e4 = make_uint4(0, 0, 0, 0);
  sts128(sa.se + lc * 32768, e4);
  sts128(sa.so + lc * 32768, make_uint4(packbf(s7[0], s7[1]), packbf(s7[2], s7[3]), packbf(s7[4], s7[5]), packbf(s7[6], s7[7])));
}

__device__ __forceinline__ void conv_epi(uint32_t sb, int layer, int cta, int ch, int c0, uint4 x0, uint4 x1) {
  uint4 v[2][4];
  const uint4 xr[2] = {x0, x1};
  mbar_wait(sb + SM_BAR + 8 * (B_P + ch), layer);
#pragma unroll
  for (int u = 0; u < 2; u++) {
    const int c = c0 + 128 * u;
    const uint32_t pb = sb + cv_pb(ch) + (c ^ ((c >> 3) & 1)) * 16;
#pragma unroll
    for (int k = 0; k < 4; k++) v[u][k] = lds128(pb + k * CV_PBW);
  }
#pragma unroll
  for (int u = 0; u < 2; u++) {
    uint4 o;
    o.x = hadd2(xr[u].x, hadd2(hadd2(v[u][0].x, v[u][1].x), hadd2(v[u][2].x, v[u][3].x)));
    o.y = hadd2(xr[u].y, hadd2(hadd2(v[u][0].y, v[u][1].y), hadd2(v[u][2].y, v[u][3].y)));
    o.z = hadd2(xr[u].z, hadd2(hadd2(v[u][0].z, v[u][1].z), hadd2(v[u][2].z, v[u][3].z)));
    o.w = hadd2(xr[u].w, hadd2(hadd2(v[u][0].w, v[u][1].w), hadd2(v[u][2].w, v[u][3].w)));
    if (layer == 0) sts128(sb + cv_s(ch) + (c0 + 128 * u) * 16, o);
    else st_tagged3((uint4*)(g_xT + (size_t)(3 * DM + cv_chan(cta, ch)) * LSEQ) + c0 + 128 * u, o.x, o.y, o.z, o.w);
  }
}
__device__ __forceinline__ void warp_release(uint32_t b) {
  fence_writer();
  __syncwarp();
  if (elect_one()) mbar_arrive(b);
}

__device__ __forceinline__ void conv_prep_load(uint32_t sb, int layer, int cta, int c, uint4 (&xr)[4], uint4 (&st)[4]) {
  mbar_wait(sb + SM_BAR + 8 * B_GB, layer);
  if (threadIdx.x == 0) TS(2 + layer * 20 + 11);
  xr[0] = ld_tagged((const uint4*)(g_xT + (size_t)(2 * layer * DM + cta) * LSEQ) + c);
#pragma unroll
  for (int i = 0; i < 4; i++) st[i] = ld_tagged((const uint4*)g_stats + (layer * 32 + (c >> 3)) * 32 + i * 8 + (c & 7));
}
template <bool HELPER>
__device__ __forceinline__ void conv_prep(uint32_t sb, int layer, int cta, int c, uint4 (&xr)[4], uint4 (&st)[4], uint4 (&un)[4], const SumAddr& sa) {
  const uint32_t bar = sb + SM_BAR;
  const uint4* xin = (const uint4*)(g_xT + (size_t)(2 * layer * DM + cta) * LSEQ) + c;
  for (int it = 0;; it++) {
    const bool okx = __all_sync(~0u, xr[0].x != ~0u);
    const bool oks = __all_sync(~0u, (st[0].y & st[1].y & st[2].y & st[3].y & 1u) != 0);
    if (okx && oks) break;
    if (it > (1 << 22)) __trap();
    if (!okx) xr[0] = ld_tagged(xin);
    if (!oks) {
#pragma unroll
      for (int i = 0; i < 4; i++) st[i] = ld_tagged((const uint4*)g_stats + (layer * 32 + (c >> 3)) * 32 + i * 8 + (c & 7));
    }
  }
  if (threadIdx.x == 0) TS(2 + layer * 20 + 12);
  const int a = c >> 1, h = c & 1;
#pragma unroll
  for (int i = 0; i < 4; i++) {
    if (i == 1) {
#pragma unroll
      for (int j = 1; j < 4; j++) xr[j] = ld_tagged(xin + j * (128 * LSEQ / 8));
      if (HELPER) {
        bar_sync(4, 128);
        conv_sums(sa, 0, c, un[0]);
        fence_async_smem();
        warp_release(bar + 8 * B_S);
        if (layer == 1 && c == 0) TS(46);
        mbar_wait(bar + 8 * B_GB, layer);
      }
      for (int it = 0; !__all_sync(~0u, xr[1].x != ~0u && xr[2].x != ~0u && xr[3].x != ~0u); it++) {
        if (it > (1 << 22)) __trap();
#pragma unroll
        for (int j = 1; j < 4; j++) xr[j] = ld_tagged(xin + j * (128 * LSEQ / 8));
      }
    }
    const uint32_t x[4] = {xr[i].x, xr[i].y, xr[i].z, xr[i].w};
    uint32_t u[4];
#pragma unroll
    for (int k = 0; k < 4; k++)
      u[k] = packbf(fmaf(bf_lo(x[k]), __uint_as_float(st[k].y), __uint_as_float(st[k].x)), fmaf(bf_hi(x[k]), __uint_as_float(st[k].w), __uint_as_float(st[k].z)));
    un[i] = make_uint4(u[0], u[1], u[2], u[3]);
    sts128(sb + cv_u(i) + h * CV_UH + (127 - a) * 16, un[i]);
    warp_release(bar + 8 * (B_U + i));
  }
}
__device__ __forceinline__ void conv_zero(uint32_t sb, int ht) {
  if (ht < 96) {
    const int ch = ht / 24, h2 = (ht / 12) & 1, qq = ht % 12;
    sts128(sb + cv_u(ch) + h2 * CV_UH + (128 + qq) * 16, make_uint4(0, 0, 0, 0));
  }
  if (ht >= 80) {
    const int i = ht - 80, ch = i / 12, q2 = i % 12;
    const int w2 = q2 < 2 ? 1 : q2 < 6 ? 2 : 3, cc = q2 < 2 ? q2 : q2 < 6 ? q2 - 2 : q2 - 6;
    sts128(sb + cv_pb(ch) + w2 * CV_PBW + cc * 16, make_uint4(0, 0, 0, 0));
  }
}

#define LD_AT 2
#define HANDOVER 12
template <int R>
__device__ __forceinline__ void conv_round(uint32_t sb, int layer, int wg, uint32_t* FA, uint32_t* FB, uint32_t pb, uint32_t pe2) {
  const uint32_t bar = sb + SM_BAR;
  const int ch = 2 * R + 1 - wg;
  float acc[64];
  const uint64_t d = mkdesc(sb + cv_u(ch), CV_UH, 128, 0);
  const bool leader = (opaque_tid() & 127) == 0;
  FTS(39);
  if (R == 0) {
    mbar_wait(bar + 8 * (B_U + ch), layer);
    fence_reader();
  }
  if (ch > 0) mbar_wait(bar + 8 * (B_T + ch - 1), layer);
  FTS(41);
  if (ch == 0 && threadIdx.x == 128) TS(2 + layer * 20 + 13);
  wg_fence();
  conv_mmas<false, 0, LD_AT>(acc, FA, d);
  if (R == 1) conv_load<true>(FB, pe2);
  conv_mmas<false, LD_AT, (HANDOVER < NA ? HANDOVER : NA)>(acc, FA, d);
  if (HANDOVER <= NA) mbar_arrive_if(bar + 8 * (B_T + ch), leader);
  conv_mmas<false, (HANDOVER < NA ? HANDOVER : NA), NA>(acc, FA, d);
  wg_commit();
  FTS(51);
  mbar_wait(bar + 8 * (B_S + ch), layer);
  if (R == 1) conv_dup<true>(FB);
  wg_fence();
  conv_mmas<true, 0, (HANDOVER > NA ? HANDOVER - NA : 0)>(acc, FB, d);
  if (HANDOVER > NA) mbar_arrive_if(bar + 8 * (B_T + ch), leader);
  conv_mmas<true, (HANDOVER > NA ? HANDOVER - NA : 0), 17 - NA>(acc, FB, d);
  wgmma_ss<64, 1, 1>(acc, mkdesc(sb + cv_s(ch), 1024, 1024, 1), mkdesc(sb + cv_ft(ch), 256, 16, 0), 1);
  wgmma_ss<64, 1, 1>(acc, mkdesc(sb + cv_s(ch) + 2048, 1024, 1024, 1), mkdesc(sb + cv_ft(ch) + 512, 256, 16, 0), 1);
  wg_commit();
  FTS(61);
  wg_wait<0>();
#pragma unroll
  for (int j = 0; j < 16; j += 2)
    stsm4t(pb + R * 65536 - j * 256, packbf(acc[4 * j], acc[4 * j + 1]), packbf(acc[4 * j + 2], acc[4 * j + 3]),
           packbf(acc[4 * j + 4], acc[4 * j + 5]), packbf(acc[4 * j + 6], acc[4 * j + 7]));
  __syncwarp();
  if (elect_one()) mbar_arrive(bar + 8 * (B_P + ch));
  if (threadIdx.x == 0) TS(2 + layer * 20 + 14 + R);
  FTS(57);
  if (R == 0) {
    mbar_wait(bar + 8 * (B_S + ch + 2), layer);
    fence_reader();
  }
}
__device__ __forceinline__ void conv_phase(const Params& p, uint32_t sb, int layer, int cta) {
  const int tid = opaque_tid();
  const int wg = __shfl_sync(~0u, tid >> 7, 0), w = __shfl_sync(~0u, (tid >> 5) & 3, 0);
  const uint32_t bar = sb + SM_BAR;
  uint32_t FA0[4 * NA], FA1[4 * NA], FB[4 * (17 - NA)];
  const uint32_t pe = sb + cv_pe(1 - wg) + 4 * (16 + 16 * w + ((tid & 31) >> 2) - 2 * (tid & 3));
  mbar_wait(bar + 8 * B_PE, layer);
  conv_load<false>(FA0, pe); conv_load<true>(FB, pe);
  const uint32_t zero = tid >> 10;
  conv_dup_early<false>(FA0, zero); conv_dup_early<true>(FB, zero);
  if (wg == 0) {
    uint4 xr[4], st[4], un[4];
    conv_prep_load(sb, layer, cta, tid + 128, xr, st);
    conv_load<false>(FA1, pe + 65536);
    conv_dup_early<false>(FA1, zero);
    conv_prep<false>(sb, layer, cta, opaque_tid() + 128, xr, st, un, SumAddr());
  } else {
    conv_load<false>(FA1, pe + 65536);
    conv_dup_early<false>(FA1, zero);
  }
  uint32_t pb;
  {
    const int l2 = opaque_tid() & 31, mt = l2 >> 3;
    const int c = 2 * (127 - 8 * (mt >> 1) - (l2 & 7) + w) + (mt & 1);
    pb = sb + cv_pb(1 - wg) + w * CV_PBW + (c ^ ((c >> 3) & 1)) * 16;
  }
  conv_round<0>(sb, layer, wg, FA0, FB, pb, 0);
  conv_round<1>(sb, layer, wg, FA1, FB, pb, pe + 65536);
  if (wg == 1 && layer == 0) mbar_wait(bar + 8 * (B_T + 3), layer);
}

__device__ __forceinline__ void final_phase(const Params& p, uint32_t sb, int cta, int wg, int w) {
  if (wg == 1 && w == 3) return;
  const int lane = opaque_tid() & 31, g = lane >> 2, t = lane & 3;
  const int lc = wg ? w : 3;
  const int pos0 = (cta & 31) * 64, ch0 = 128 * lc + (cta >> 5) * 32;
  const bf16* src = g_xT + (size_t)(3 * DM + ch0 + 8 * (g >> 1) + (g & 1)) * LSEQ + pos0;
  bf16* dst = p.out + (size_t)pos0 * DM + ch0 + 8 * t;
  int it = 0;
  if (wg == 0) {
    uint2 v[4];
    do {
#pragma unroll
      for (int q = 0; q < 4; q++)
        asm volatile("ld.relaxed.gpu.global.v2.u32 {%0,%1}, [%2];" : "=r"(v[q].x), "=r"(v[q].y) : "l"(src + 2 * q * LSEQ + 16 * w + 4 * t) : "memory");
      if (++it > (1 << 22)) __trap();
    } while (!__all_sync(~0u, v[0].x != ~0u && v[1].x != ~0u && v[2].x != ~0u && v[3].x != ~0u));
    if (threadIdx.x == 0) TS(42);
    dst += (16 * w + 4 * (g >> 1) + (g & 1)) * DM;
    *(uint4*)dst = make_uint4(movm_t(v[0].x), movm_t(v[1].x), movm_t(v[2].x), movm_t(v[3].x));
    *(uint4*)(dst + 2 * DM) = make_uint4(movm_t(v[0].y), movm_t(v[1].y), movm_t(v[2].y), movm_t(v[3].y));
  } else {
    uint4 v[2][4];
    bool ok;
    do {
      ok = true;
#pragma unroll
      for (int h = 0; h < 2; h++)
#pragma unroll
        for (int q = 0; q < 4; q++) v[h][q] = ld_tagged((const uint4*)(src + 2 * q * LSEQ + 32 * h + 8 * t));
#pragma unroll
      for (int h = 0; h < 2; h++)
#pragma unroll
        for (int q = 0; q < 4; q++) ok = ok && v[h][q].x != ~0u;
      if (++it > (1 << 22)) __trap();
    } while (!__all_sync(~0u, ok));
    dst += (8 * (g >> 1) + (g & 1)) * DM;
#pragma unroll
    for (int h = 0; h < 2; h++) {
      *(uint4*)(dst + (32 * h + 0) * DM) = make_uint4(movm_t(v[h][0].x), movm_t(v[h][1].x), movm_t(v[h][2].x), movm_t(v[h][3].x));
      *(uint4*)(dst + (32 * h + 2) * DM) = make_uint4(movm_t(v[h][0].y), movm_t(v[h][1].y), movm_t(v[h][2].y), movm_t(v[h][3].y));
      *(uint4*)(dst + (32 * h + 4) * DM) = make_uint4(movm_t(v[h][0].z), movm_t(v[h][1].z), movm_t(v[h][2].z), movm_t(v[h][3].z));
      *(uint4*)(dst + (32 * h + 6) * DM) = make_uint4(movm_t(v[h][0].w), movm_t(v[h][1].w), movm_t(v[h][2].w), movm_t(v[h][3].w));
    }
  }
  if (threadIdx.x == 0) TS(43);
  if (threadIdx.x == 192) TS(63);
  if (threadIdx.x == 0) LTS(1);
}

struct cplx { float r, i; };
__device__ __forceinline__ cplx cmul(cplx a, cplx b) { return {fmaf(a.r, b.r, -a.i * b.i), fmaf(a.r, b.i, a.i * b.r)}; }
__device__ __forceinline__ cplx csqr(cplx a) { return {fmaf(a.r, a.r, -a.i * a.i), (a.r + a.r) * a.i}; }
__device__ __forceinline__ cplx cexp_l(float ar2, float ai, float l) {
  const float m = ex2(ar2 * l);
  const float x = ai * l;
  return {m * __cosf(x), m * __sinf(x)};
}

__device__ __forceinline__ void colsum_publish(uint32_t sb, int rb, int hg, int ht, uint32_t tag) {
  const int lane = ht & 31, q = lane & 15, h = lane >> 4;
  const uint32_t src = sb + SM_CW + (ht >> 5) * 4096 + h * 128 + (q & 1) * 8;
  float s[4] = {0.f, 0.f, 0.f, 0.f};
#pragma unroll
  for (int r = 0; r < 16; r++) {
    const float2 v = lds64f(src + r * 256 + (((q >> 1) ^ ((2 * r + h) & 7)) << 4));
    s[0] += bf_lo(__float_as_uint(v.x)); s[1] += bf_hi(__float_as_uint(v.x));
    s[2] += bf_lo(__float_as_uint(v.y)); s[3] += bf_hi(__float_as_uint(v.y));
  }
#pragma unroll
  for (int k = 0; k < 4; k++) s[k] += __shfl_xor_sync(~0u, s[k], 16);
  if (h == 0)
    st_tagged3(&g_colsum[(hg * 16 + rb) * 48 + (ht >> 5) * 16 + q], (__float_as_uint(s[0]) & ~7u) | tag, __float_as_uint(s[1]),
               __float_as_uint(s[2]), __float_as_uint(s[3]));
}
__device__ __forceinline__ void colsum_gather(uint32_t sb, int hg, int ht, uint32_t tag) {
  const int lane = ht & 31, rec = (ht >> 5) * 16 + (lane & 15);
  const uint4* src = &g_colsum[(hg * 16 + (lane >> 4) * 8) * 48 + rec];
  uint4 v[8];
  bool ok;
  int it = 0;
  do {
    ok = true;
#pragma unroll
    for (int i = 0; i < 8; i++) v[i] = ld_tagged(src + i * 48);
#pragma unroll
    for (int i = 0; i < 8; i++) ok = ok && (v[i].x & 7u) == tag;
    if (++it > (1 << 22)) __trap();
  } while (!__all_sync(~0u, ok));
  float s[4] = {0.f, 0.f, 0.f, 0.f};
#pragma unroll
  for (int i = 0; i < 8; i++) {
    s[0] += __uint_as_float(v[i].x & ~7u); s[1] += __uint_as_float(v[i].y); s[2] += __uint_as_float(v[i].z); s[3] += __uint_as_float(v[i].w);
  }
#pragma unroll
  for (int k = 0; k < 4; k++) s[k] += __shfl_xor_sync(~0u, s[k], 16);
  if (lane < 16) sts128f(sb + SM_CS + rec * 16, s[0], s[1], s[2], s[3]);
}

__device__ __forceinline__ uint32_t packh(float lo, float hi) { uint32_t r; asm("cvt.rn.f16x2.f32 %0, %1, %2;" : "=r"(r) : "f"(hi), "f"(lo)); return r; }
__device__ __forceinline__ void mma_f16(float* d, uint32_t a0, uint32_t a1, uint32_t a2, uint32_t a3, uint32_t b0, uint32_t b1) {
  asm volatile("mma.sync.aligned.m16n8k16.row.col.f32.f16.f16.f32 {%0,%1,%2,%3}, {%4,%5,%6,%7}, {%8,%9}, {%0,%1,%2,%3};"
      : "+f"(d[0]), "+f"(d[1]), "+f"(d[2]), "+f"(d[3]) : "r"(a0), "r"(a1), "r"(a2), "r"(a3), "r"(b0), "r"(b1));
}
struct HSeed { uint32_t r, i; };
__device__ __forceinline__ HSeed hseed(cplx s) { return {packh(s.r, s.r), packh(s.i, s.i)}; }
__device__ __forceinline__ void hcmul(uint32_t& o_r, uint32_t& o_i, uint32_t br, uint32_t bi, HSeed s) {
  asm("{\n.reg .b32 t, u;\nmul.rn.f16x2 t, %3, %5;\nneg.f16x2 t, t;\nmul.rn.f16x2 u, %3, %4;\nfma.rn.f16x2 %0, %2, %4, t;\nfma.rn.f16x2 %1, %2, %5, u;\n}"
      : "=&r"(o_r), "=&r"(o_i) : "r"(br), "r"(bi), "r"(s.r), "r"(s.i));
}
struct HTile { uint32_t r[4], i[4]; };
__device__ __forceinline__ void tile_set(HTile& t, int k, cplx a, cplx b) { t.r[k] = packh(a.r, b.r); t.i[k] = packh(a.i, b.i); }
__device__ __forceinline__ void tile_upper(HTile& t, HSeed s) { hcmul(t.r[2], t.i[2], t.r[0], t.i[0], s); hcmul(t.r[3], t.i[3], t.r[1], t.i[1], s); }
__device__ __forceinline__ HTile tile_shift(const HTile& t, HSeed s) {
  HTile o;
#pragma unroll
  for (int k = 0; k < 4; k++) hcmul(o.r[k], o.i[k], t.r[k], t.i[k], s);
  return o;
}
__device__ __forceinline__ void tile_put(const HTile& t, uint32_t a) {
  sts128(a, make_uint4(t.r[0], t.r[1], t.r[2], t.r[3]));
  sts128(a + 512, make_uint4(t.i[0], t.i[1], t.i[2], t.i[3]));
}
__device__ __forceinline__ HTile tile_get(uint32_t a) { HTile o; ldsm4t(o.r, a); ldsm4t(o.i, a + 512); return o; }
__device__ __forceinline__ void tile_mma(float* T, const HTile& a0, const HTile& a1, const HTile& b) {
  mma_f16(T, a0.r[0], a0.r[1], a0.r[2], a0.r[3], b.r[0], b.r[1]);
  mma_f16(T, a0.i[0], a0.i[1], a0.i[2], a0.i[3], b.i[0], b.i[1]);
  mma_f16(T, a1.r[0], a1.r[1], a1.r[2], a1.r[3], b.r[2], b.r[3]);
  mma_f16(T, a1.i[0], a1.i[1], a1.i[2], a1.i[3], b.i[2], b.i[3]);
}
__device__ __forceinline__ void tile_mma2(float* T, float* U, const HTile& a0, const HTile& a1, const HTile& b, const HTile& c) {
  mma_f16(T, a0.r[0], a0.r[1], a0.r[2], a0.r[3], b.r[0], b.r[1]);
  mma_f16(U, a0.r[0], a0.r[1], a0.r[2], a0.r[3], c.r[0], c.r[1]);
  mma_f16(T, a0.i[0], a0.i[1], a0.i[2], a0.i[3], b.i[0], b.i[1]);
  mma_f16(U, a0.i[0], a0.i[1], a0.i[2], a0.i[3], c.i[0], c.i[1]);
  mma_f16(T, a1.r[0], a1.r[1], a1.r[2], a1.r[3], b.r[2], b.r[3]);
  mma_f16(U, a1.r[0], a1.r[1], a1.r[2], a1.r[3], c.r[2], c.r[3]);
  mma_f16(T, a1.i[0], a1.i[1], a1.i[2], a1.i[3], b.i[2], b.i[3]);
  mma_f16(U, a1.i[0], a1.i[1], a1.i[2], a1.i[3], c.i[2], c.i[3]);
}
__device__ __forceinline__ void kgen_unit(uint32_t tab, uint32_t taba, float ar2, float ai, cplx c, float (&T)[5][4]) {
  const cplx z1 = cexp_l(ar2, ai, 1.f), z16 = cexp_l(ar2, ai, 16.f), z256 = cexp_l(ar2, ai, 256.f);
  HTile a0, a1, b0, b1;
  {
    const cplx y1 = {z16.r, -z16.i}, y2 = csqr(y1), y3 = cmul(y2, y1), y4 = csqr(y2), y5 = cmul(y4, y1), y6 = csqr(y3), y7 = cmul(y4, y3);
    HTile t;
    tile_set(t, 0, {1.f, 0.f}, y1); tile_set(t, 1, y2, y3); tile_set(t, 2, y4, y5); tile_set(t, 3, y6, y7);
    const HTile u = tile_shift(t, hseed(csqr(y4)));
    __syncwarp();
    tile_put(t, tab); tile_put(u, tab + 1024);
    __syncwarp();
    a0 = tile_get(taba); a1 = tile_get(taba + 256);
  }
  const cplx z2 = csqr(z1), z4 = csqr(z2), z8 = csqr(z4);
  const HSeed h8 = hseed(z8);
  const cplx d = cmul(c, z256), e = cmul(d, z256);
  {
    const cplx z512 = csqr(z256), f = cmul(e, z512), f8 = cmul(f, z8), f16 = cmul(f, z16), e4 = cmul(e, z4);
    HTile t, u;
    tile_set(t, 0, e4, cmul(e, z8)); tile_set(t, 1, cmul(e4, z8), cmul(e, z16));
    tile_upper(t, hseed(z256));
    tile_set(u, 0, f8, f16); tile_set(u, 1, cmul(f8, z256), cmul(f16, z256));
    tile_upper(u, hseed(z512));
    __syncwarp();
    tile_put(t, tab); tile_put(u, tab + 1024);
    __syncwarp();
    b0 = tile_get(tab); b1 = tile_get(tab + 1024);
  }
  {
    const cplx d2 = cmul(d, z2), d4 = cmul(d, z4);
    HTile t;
    tile_set(t, 0, d2, d4); tile_set(t, 1, cmul(d2, z4), cmul(d, z8));
    tile_upper(t, h8);
    __syncwarp();
    tile_put(t, tab);
    __syncwarp();
    tile_mma2(T[3], T[4], a0, a1, b0, b1);
    b0 = tile_get(tab);
  }
  {
    const cplx c1 = cmul(c, z1), c2 = cmul(c, z2), c3 = cmul(c1, z2), c4 = cmul(c, z4);
    HTile t;
    tile_set(t, 0, c1, c2); tile_set(t, 1, c3, c4); tile_set(t, 2, cmul(c1, z4), cmul(c2, z4)); tile_set(t, 3, cmul(c3, z4), cmul(c4, z4));
    const HTile u = tile_shift(t, h8);
    __syncwarp();
    tile_put(t, tab); tile_put(u, tab + 1024);
    __syncwarp();
    tile_mma(T[2], a0, a1, b0);
    b0 = tile_get(tab); b1 = tile_get(tab + 1024);
    tile_mma2(T[0], T[1], a0, a1, b0, b1);
  }
}
struct ModeIn { uint2 ar, ai, br, bi, cr, ci; };
__device__ __forceinline__ ModeIn load_modes(const Params& p, int idx) {
  return {*(const uint2*)(p.a_re + idx), *(const uint2*)(p.a_im + idx), *(const uint2*)(p.b_re + idx),
          *(const uint2*)(p.b_im + idx), *(const uint2*)(p.c_re + idx), *(const uint2*)(p.c_im + idx)};
}
__device__ __forceinline__ float bf_el(uint2 v, int k) { const uint32_t x = (k & 2) ? v.y : v.x; return (k & 1) ? bf_hi(x) : bf_lo(x); }
struct KGen { float4 cur; float T[5][4]; };
__device__ __forceinline__ uint32_t kgen_slot(uint32_t sb, int ht, int u) {
  return sb + (u < 3 ? SM_KC + (ht >> 5) * (KC_STRIDE * 2) + (u - 1) * 512 + (ht & 31) * 16 + 16 : SM_HALO + 1024 + ht * 16);
}
__device__ __forceinline__ void kgen_setup(KGen& s, uint32_t sb, int cta, int ht, const ModeIn& in, bf16 logdt, bf16 dskip) {
  const float dt = __bfloat162float(__float2bfloat16_rn(expf(__bfloat162float(logdt))));
  float mx = 0.f, k0 = 0.f, ar2[4];
  cplx c[4];
#pragma unroll
  for (int k = 0; k < 4; k++) {
    ar2[k] = (dt * bf_el(in.ar, k)) * 1.4426950408889634f;
    c[k] = cmul({bf_el(in.cr, k), bf_el(in.ci, k)}, {dt * bf_el(in.br, k), dt * bf_el(in.bi, k)});
    k0 += c[k].r;
    mx = fmaxf(mx, fmaxf(fabsf(c[k].r), fabsf(c[k].i)) * ex2(fmaxf(ar2[k] * 2048.f, 0.f)));
  }
  const int ex = min(max(267 - (int)(__reduce_max_sync(~0u, __float_as_uint(mx)) >> 23), 1), 253);
  const float sc = __uint_as_float(ex << 23);
#pragma unroll
  for (int o = 16; o > 0; o >>= 1) k0 += __shfl_xor_sync(~0u, k0, o);
  if ((ht & 31) == 0) {
    const uint32_t kc = sb + SM_KC + (ht >> 5) * (KC_STRIDE * 2);
    sts16(kc, __bfloat16_as_ushort(__float2bfloat16_rn(k0 + __bfloat162float(dskip))));
    sts16(kc + 641 * 2, 0);
    sts32f(kc + 644 * 2, __uint_as_float((254 - ex) << 23));
  }
  s.cur = make_float4(ar2[0], dt * bf_el(in.ai, 0), c[0].r * sc, c[0].i * sc);
#pragma unroll
  for (int k = 1; k < 4; k++) sts128f(kgen_slot(sb, ht, k), ar2[k], dt * bf_el(in.ai, k), c[k].r * sc, c[k].i * sc);
#pragma unroll
  for (int i = 0; i < 5; i++) s.T[i][0] = s.T[i][1] = s.T[i][2] = s.T[i][3] = 0.f;
}
__device__ __forceinline__ void kgen_finish(KGen& s, uint32_t sb, int cta, int ht) {
  const int w = ht >> 5, lane = ht & 31, g = lane >> 2, t = lane & 3;
  const uint32_t kc = sb + SM_KC + w * KC_STRIDE * 2;
  __syncwarp();
  const float inv = __uint_as_float(lds32(kc + 644 * 2));
  auto put = [&](int idx, float v) {
    sts16(kc + idx * 2, __bfloat16_as_ushort(__float2bfloat16_rn(v)));
  };
#pragma unroll
  for (int hi = 0; hi < 2; hi++)
#pragma unroll
    for (int lo = 0; lo < 2; lo++) {
      const int i = g + 8 * hi, j = 2 * t + lo, e = 2 * hi + lo;
      put(16 * i + 1 + j, s.T[0][e] * inv);
      put(16 * i + 9 + j, s.T[1][e] * inv);
      put(257 + 8 * i + j, s.T[2][e] * inv);
      put(385 + 4 * i + (j & 3) + 64 * (j >> 2), s.T[3][e] * inv);
      put(513 + 2 * i + lo + 32 * t, s.T[4][e] * inv);
    }
}

__device__ __forceinline__ void expand_taps(uint32_t sb, int ht) {
  const int ch = ht >> 5, lane = ht & 31;
  const uint32_t kc = sb + SM_KC + ch * KC_STRIDE * 2;
  const uint32_t dst0 = sb + cv_pe(ch);
  auto put = [&](int G, uint32_t v0, uint32_t v1, uint32_t v2, uint32_t v3, uint32_t v4, uint32_t v5, uint32_t v6, uint32_t v7, uint32_t v8) {
    const uint32_t dst = dst0 + G * 32;
    sts128(dst, make_uint4(v1 | (v0 << 16), v2 | (v1 << 16), v3 | (v2 << 16), v4 | (v3 << 16)));
    sts128(dst + 16, make_uint4(v5 | (v4 << 16), v6 | (v5 << 16), v7 | (v6 << 16), v8 | (v7 << 16)));
  };
  {
    const uint4 q = lds128(kc + lane * 16);
    const uint32_t pv = lane ? lds16(kc + lane * 16 - 2) : 0u;
    const uint32_t dst = dst0 + (lane + 2) * 32;
    sts128(dst, make_uint4(__byte_perm(q.x, pv, 0x5410), __byte_perm(q.x, q.x, 0x1032), __byte_perm(q.y, q.x, 0x7610), __byte_perm(q.y, q.y, 0x1032)));
    sts128(dst + 16, make_uint4(__byte_perm(q.z, q.y, 0x7610), __byte_perm(q.z, q.z, 0x1032), __byte_perm(q.w, q.z, 0x7610), __byte_perm(q.w, q.w, 0x1032)));
    if (lane < 4) sts128(dst0 + lane * 16, make_uint4(0, 0, 0, 0));
  }
  uint32_t a[5], b[2][3], fv[4];
  {
    const uint32_t s1 = kc + 2 * (256 + 4 * lane);
#pragma unroll
    for (int k = 0; k < 5; k++) a[k] = lds16(s1 + 2 * k);
#pragma unroll
    for (int u = 0; u < 2; u++) {
      const uint32_t s2 = kc + 2 * (384 + 2 * (lane + 32 * u));
#pragma unroll
      for (int k = 0; k < 3; k++) b[u][k] = lds16(s2 + 2 * k);
    }
#pragma unroll
    for (int k = 0; k < 4; k++) fv[k] = lds16(kc + 2 * (640 - 4 * lane - k));
  }
  const uint32_t k255 = lds16(kc + 2 * 255), k1024 = lds16(kc + 2 * 512);
  put(34 + lane, lane == 0 ? k255 : a[0], a[0], a[0], a[1], a[2], a[2], a[2], a[3], a[4]);
#pragma unroll
  for (int u = 0; u < 2; u++) put(66 + lane + 32 * u, b[u][0], b[u][0], b[u][0], b[u][0], b[u][1], b[u][1], b[u][1], b[u][2], b[u][2]);
  if (lane < 10) {
    const uint32_t v = lane == 0 ? k1024 : 0u;
    put(130 + lane, v, v, v, v, v, v, 0u, 0u, 0u);
  }
  const uint32_t ft = sb + cv_ft(ch) + 4 * lane;
#pragma unroll
  for (int ty = 0; ty < 2; ty++) {
    const uint32_t v = fv[ty] | (fv[ty + 2] << 16);
    sts32f(ft + ty * 512, __uint_as_float(v));
    sts32f(ft + ty * 512 + 128, 0.f);
    sts32f(ft + ty * 512 + 256 + (lane < 2 ? 120 : -8), __uint_as_float(lane < 2 ? 0u : v));
    sts32f(ft + ty * 512 + 384, 0.f);
  }
}

template <bool SMID> __device__ __forceinline__ int role_id() {
  uint32_t v;
  if (!SMID) { asm volatile("mov.u32 %0, %%ctaid.x;" : "=r"(v)); return v; }
  asm volatile("mov.u32 %0, %%smid;" : "=r"(v));
  const int tp = v >> 1, q = ((tp - 32) * 37) >> 8;
  const int r = tp < 32 ? (tp & 7) * 8 + (tp >> 3) : tp < 60 ? (tp - 31 - 7 * q) * 8 + 4 + q : tp < 62 ? tp + 4 : tp - 58;
  return __shfl_sync(~0u, 2 * r + (v & 1), 0);
}
__device__ __forceinline__ int role_rb(int cta) { return ((cta >> 4) & 3) * 4 + ((cta >> 2) & 3); }
__device__ __forceinline__ int role_hg(int cta) { return (cta >> 6) * 4 + (cta & 3); }
__device__ __forceinline__ int role_rb2(int cta) { return cta >> 3; }
__device__ __forceinline__ int role_q2(int cta) { return cta & 7; }

template <bool SMID> __global__ void __launch_bounds__(NTHREADS, 1) fused_kernel(const __grid_constant__ Params p) {
  extern __shared__ __align__(1024) uint8_t smem[];
  const uint32_t sb = s32(smem);
  const int tid = threadIdx.x, lane = tid & 31;
  const int warp = __shfl_sync(~0u, tid >> 5, 0);
  constexpr unsigned NARR = SMID ? 132 : NCTA;
  const uint32_t bar = sb + SM_BAR;
  if (tid == 0) TS(0);
  const int cta0 = role_id<SMID>();
  if (warp == 0 && (!SMID || cta0 < NCTA) && elect_one()) {
    const int rb = role_rb(cta0), hg = role_hg(cta0);
    mbar_init(bar + 8 * B_XF, 1); mbar_init(bar + 8 * B_KVF, 1);
    fence_async_smem();
#pragma unroll
    for (int c = 0; c < 8; c++) {
      mbar_expect(bar + 8 * (B_XF + c), 16384);
      tma_ld(sb + SM_X + c * 16384, &p.mapX128, c * 64, rb * 128, bar + 8 * (B_XF + c));
      if (c < 3) {
        mbar_expect(bar + 8 * (B_KVF + c), 24576);
        tma_ld3(sb + SM_W + c * 24576, &p.mapW3, hg * 64, c * 64, 0, bar + 8 * (B_KVF + c));
      }
      if (c == 0) {
#pragma unroll
        for (int i = 1; i < 8; i++) mbar_init(bar + 8 * (B_XF + i), 1);
        mbar_init(bar + 8 * (B_KVF + 1), 1); mbar_init(bar + 8 * (B_KVF + 2), 1); mbar_init(bar + 8 * B_CW, 1);
        fence_async_smem();
      }
      if (c == PF_AT) {
        mbar_expect(bar + 8 * B_CW, 12288);
        tma_ld3(sb + SM_CW, &p.mapW3h, hg * 64, rb * 32, 0, bar + 8 * B_CW);
      }
    }
    TS(56);
  }
  if (SMID && cta0 >= NCTA) {
    if (tid == 0) spin_until(&g_cnt[C_CS * 32], (atomicAdd(&g_cnt[C_CS * 32], 1u) / NARR + 1) * NARR);
    return;
  }
  if (warp >= 1 && warp < 5 && elect_one()) {
#pragma unroll
    for (int q = 0; q < 4; q++) {
      if (warp == q + 1) {
#pragma unroll
        for (int i = 17 * q; i < 17 * q + 17; i++) {
          if (i < B_KVF + 3 || i == B_CW) continue;
          int cnt = 1;
          if ((i >= B_KVE && i < B_KVE + 5) || i == B_QDONE || i == B_PDONE || i == B_OST || i == B_AD) cnt = 2;
          if ((i >= B_U && i < B_U + 4) || i == B_PS) cnt = 8;
          if ((i >= B_S && i < B_S + 4) || (i >= B_E && i < B_E + 4) || i >= B_P || i == B_PE || i == B_STF) cnt = 4;
          mbar_init(bar + 8 * i, cnt);
        }
      }
    }
    fence_async_smem();
  }

  if (warp < 8) {
    bar_sync(0, NTHREADS);
    if (tid == 0) TS(1);
    asm volatile("setmaxnreg.inc.sync.aligned.u32 %0;" ::"n"(R_CONS));
    const int cw = __shfl_sync(~0u, opaque_tid() >> 5, 0);
    const int wg = cw >> 2, w = cw & 3;
    const int cta = role_id<SMID>();
    if (tid == 0) TS(54);
#pragma unroll 1
    for (int layer = 0; layer < 2; layer++) {
      attn_phase(p, sb, layer, role_rb(cta), role_hg(cta), wg, w);
      if (p.stop == 1 + 3 * layer) return;
      proj_phase(p, sb, layer, role_rb2(cta), role_q2(cta), wg, w);
      if (p.stop == 2 + 3 * layer) return;
      conv_phase(p, sb, layer, cta);
      if (p.stop == 3 + 3 * layer) return;
    }
    final_phase(p, sb, cta, wg, w);
  } else if (warp < 12) {
    asm volatile("setmaxnreg.dec.sync.aligned.u32 %0;" ::"n"(R_HELP));
    const int ht = tid - 256;
    const int cta = role_id<SMID>(), rb = role_rb(cta), hg = role_hg(cta);
    unsigned ep0 = 0;
    if (ht == 0) ep0 = ld_relaxed(&g_cnt[C_CS * 32]);
    bar_sync(0, NTHREADS);
    if (ht == 0) {
      asm volatile("st.shared.u32 [%0], %1;" ::"r"(sb + SM_EP), "r"(ep0 / NARR) : "memory");
      mbar_arrive(bar + 8 * B_EP);
    }
    mbar_wait(bar + 8 * B_EP, 0);
    const uint32_t cs_tag = lds32(sb + SM_EP) % 7 + 1;
    if (ht < 96) {
      mbar_wait(bar + 8 * B_CW, 0);
      colsum_publish(sb, rb, hg, ht, cs_tag);
    }
    if (ht == 0) TS(50);
    stats_publish(sb, 0, rb, hg, opaque_tid() - 256, 4 * lds32(sb + SM_EP) + 1);
    {
      KGen kg;
      const uint32_t tab0 = sb + ((ht >> 5) < 2 ? SM_T : SM_T2 - 4096) + (ht >> 5) * 2048;
      const uint32_t tab = tab0 + (ht & 31) * 16, taba = tab0 + ((ht >> 3) & 1) * 1024 + (((ht >> 1) & 8) + (ht & 7)) * 16;
      mbar_wait(bar + 8 * (B_KVF + CS_AT), 0);
      if (ht < 96) colsum_gather(sb, hg, ht, cs_tag);
      stats_gather(sb, rb, opaque_tid() - 256, 4 * lds32(sb + SM_EP) + 1);
      if (ht == 0) TS(40);
      const int chn = cv_chan(cta, ht >> 5);
      kgen_setup(kg, sb, cta, ht, load_modes(p, chn * 128 + (ht & 31) * 4), p.log_dt[chn], p.dskip[chn]);
#pragma unroll 1
      for (int u = 0; u < 4; u++) {
        if (u == KG_PRE) {
          KTS(39);
          mbar_wait(bar + 8 * B_AD, 0);
          KTS(41);
        }
        if (u == 3) mbar_wait(bar + 8 * (EXP_LATE ? B_PS : B_PDONE), 0);
        kgen_unit(tab, taba, kg.cur.x, kg.cur.y, {kg.cur.z, kg.cur.w}, kg.T);
        kg.cur = lds128f(kgen_slot(sb, opaque_tid() - 256, u + 1));
      }
      kgen_finish(kg, sb, cta, opaque_tid() - 256);
    }
    KTS(51);
    bar_sync(4, 128);
#pragma unroll 1
    for (int layer = 0; layer < 2; layer++) {
      if (p.stop <= 1 + 3 * layer) return;
      mbar_wait(bar + 8 * (EXP_LATE ? B_PS : B_PDONE), layer);
      expand_taps(sb, opaque_tid() - 256);
      conv_zero(sb, opaque_tid() - 256);
      if (ht == 0) TS(52 + layer);
      warp_release(bar + 8 * B_PE);
      if (p.stop <= 2 + 3 * layer) return;
      {
        uint4 xr[4], st[4], un[4];
        const int c = opaque_tid() - 256;
        const SumAddr sa = conv_sum_addr(sb, c);
        conv_prep_load(sb, layer, cta, c, xr, st);
        conv_prep<true>(sb, layer, cta, c, xr, st, un, sa);
        if (layer == 1 && ht == 0) TS(62);
        bar_sync(4, 128);
        conv_sums(sa, 1, c, un[1]);
        fence_async_smem();
        warp_release(bar + 8 * (B_S + 1));
        conv_sums(sa, 2, c, un[2]);
        mbar_wait(bar + 8 * (B_U + 3), layer);
        warp_release(bar + 8 * (B_S + 2));
        const bf16* xup = g_xT + (size_t)(2 * layer * DM + cta) * LSEQ + (c + 128) * 8;
        st[0] = ldcg128(xup);
        conv_sums(sa, 3, c, un[3]);
        warp_release(bar + 8 * (B_S + 3));
#pragma unroll
        for (int lc = 0; lc < 4; lc++) {
          if (lc < 3) st[lc + 1] = ldcg128(xup + (lc + 1) * 128 * LSEQ);
          conv_epi(sb, layer, cta, lc, c, xr[lc], st[lc]);
          if (layer == 0) warp_release(bar + 8 * (B_E + lc));
          if (layer == 1 && lc == 3 && ht == 0) TS(38);
        }
      }
      if (layer == 0 && p.stop > 3) {
        const int c1 = role_id<SMID>();
        stats_publish(sb, 1, role_rb(c1), role_hg(c1), opaque_tid() - 256, 4 * lds32(sb + SM_EP) + 3);
        mbar_wait(bar + 8 * (B_XF + 7), 1);
        mbar_wait(bar + 8 * (B_KVF + ST_AT), 1);
        stats_gather(sb, role_rb(c1), opaque_tid() - 256, 4 * lds32(sb + SM_EP) + 3);
        if (ht == 0) TS(25);
      }
    }
  } else {
    asm volatile("setmaxnreg.dec.sync.aligned.u32 %0;" ::"n"(512 - 2 * R_CONS - R_HELP));
    const int cta = role_id<SMID>(), rb = role_rb(cta), hg = role_hg(cta), rb2 = role_rb2(cta), q2 = role_q2(cta);
    bar_sync(0, NTHREADS);
    if (warp == 12) {
      if (elect_one()) {
        unsigned epoch = 0;
#pragma unroll 1
        for (int layer = 0; layer < 2; layer++) {
          auto ld_w = [&](int c, int slot) {
            const uint32_t b = bar + 8 * (B_KVF + c);
            mbar_expect(b, 24576);
            tma_ld3(sb + SM_W + slot * 24576, &p.mapW3, hg * 64, c * 64, 0, b);
          };
          if (layer == 0) {
            TS(55);
            mbar_wait(bar + 8 * (B_KVF + 2), 0);
            if (rb2 < 4) tma_prefetch2(&p.mapWo128, q2 * 64, rb2 * 128);
            asm volatile("prefetch.tensormap [%0];" ::"l"(&p.mapO) : "memory");
            asm volatile("prefetch.tensormap [%0];" ::"l"(&p.mapO128) : "memory");
            asm volatile("prefetch.tensormap [%0];" ::"l"(&p.mapXT) : "memory");
            asm volatile("prefetch.tensormap [%0];" ::"l"(&p.mapXT3) : "memory");
            mbar_wait(bar + 8 * B_EP, 0);
            epoch = lds32(sb + SM_EP);
          } else {
            mbar_wait(bar + 8 * B_PDONE, 0);
            ld_w(0, 0); ld_w(1, 1);
            mbar_wait(bar + 8 * (W2_LATE ? B_U : B_RE), 0);
            ld_w(2, 2);
          }
          {
            int slot = 0;
#pragma unroll 1
            for (int c = 3; c < 8; c++) {
              mbar_wait(bar + 8 * (B_KVE + c - 3), layer);
              ld_w(c, slot);
              slot = slot == 2 ? 0 : slot + 1;
            }
          }
          if (p.stop <= 1 + 3 * layer) return;
          mbar_wait(bar + 8 * B_QDONE, layer);
          if (rb > 0) mbar_wait(bar + 8 * B_HF, layer);
#pragma unroll 1
          for (int c = 0; c < 4; c++) {
            const uint32_t b = bar + 8 * (B_WOF + c);
            mbar_expect(b, 16384);
            tma_ld(sb + SM_X + c * 16384, &p.mapWo128, q2 * 64, c * 128, b);
          }
          {
            const uint32_t b = bar + 8 * B_RF;
            mbar_expect(b, 16384);
            if (layer == 0) tma_ld(sb + SM_R, &p.mapX128, q2 * 64, rb2 * 128, b);
            else tma_ld3(sb + SM_R, &p.mapXT3, 0, DM + q2 * 64, rb2 * 2, b);
          }
          spin_until(&g_cnt[(C_O + rb2) * 32], (2 * epoch + layer + 1) * 16);
          mbar_wait(bar + 8 * B_OST, layer);
          fence_async_global();
#pragma unroll 1
          for (int c = 0; c < 8; c++) {
            const uint32_t b = bar + 8 * (B_OF + c);
            mbar_expect(b, 16384);
            tma_ld(sb + (c < 4 ? SM_X + 65536 + c * 16384 : SM_W + (c - 4) * 16384), &p.mapO128, c * 64, rb2 * 128, b);
          }
          if (p.stop <= 3 + 3 * layer) return;
        }
      }
    } else if (warp == 13) {
      if (elect_one() && p.stop > 3) {
        mbar_wait(bar + 8 * B_GB, 0);
        const unsigned target = (lds32(sb + SM_EP) + 1) * NCTA;
        auto ld_x = [&](int c) {
          mbar_expect(bar + 8 * (B_XF + c), 16384);
          tma_ld3(sb + SM_X + c * 16384, &p.mapXT3, 0, DM + c * 64, rb * 2, bar + 8 * (B_XF + c));
        };
        int done = 0, it = 0;
        while (done < 4) {
          const uint4 v = ld_tagged((const uint4*)&g_cnt[C_G1 * 32]);
          const int n = (int)(v.x - target) < 0 ? 0 : (int)(v.y - target) < 0 ? 1 : (int)(v.z - target) < 0 ? 2 : (int)(v.w - target) < 0 ? 3 : 4;
          if (++it > (1 << 23)) __trap();
          if (n == done) continue;
          if (n == 4) TS(44);
          fence_async_global();
          fence_async_smem();
          const bool own_first = done > 0 && hg >= 2 * done && hg < 2 * n;
          if (own_first) ld_x(hg);
#pragma unroll 1
          for (int c = 2 * done; c < 2 * n; c++)
            if (!own_first || c != hg) ld_x(c);
          done = n;
        }
      }
    } else if (warp == 15) {
      mbar_wait(bar + 8 * B_EP, 0);
      const unsigned epoch = lds32(sb + SM_EP);
#pragma unroll 1
      for (int layer = 0; layer < 2; layer++) {
#pragma unroll 1
        for (int i = 0; i < 6; i++) {
          mbar_wait(bar + 8 * (B_KVF + (FILL_AT + i < 7 ? FILL_AT + i : 7)), layer);
          uint4* dst = (uint4*)(g_xT + (size_t)(i < 4 ? 2 * layer * DM + cv_chan(cta, i) : 3 * DM + cv_chan(cta, 2 * layer + i - 4)) * LSEQ) + lane;
#pragma unroll
          for (int k = 0; k < 8; k++) dst[32 * k] = make_uint4(~0u, ~0u, ~0u, ~0u);
        }
        if (lane < 8) ((uint4*)g_stats)[layer * 1024 + cta * 8 + lane] = make_uint4(0, 0, 0, 0);
        __syncwarp();
        if (elect_one()) {
          red_release(&g_cnt[C_CS * 32 + layer]);
          spin_until(&g_cnt[C_CS * 32 + layer], (epoch + 1) * (layer ? NCTA : NARR));
          mbar_arrive(bar + 8 * B_ZF);
          if (layer == 0 && p.stop > 2) {
#pragma unroll 1
            for (int lc = 0; lc < 4; lc++) {
              mbar_wait(bar + 8 * (B_E + lc), 0);
              fence_reader();
              bulk_st(g_xT + (size_t)(DM + cv_chan(cta, lc)) * LSEQ, sb + cv_s(lc), 4096);
              bulk_commit();
              bulk_wait_all();
              red_relaxed(&g_cnt[C_G1 * 32 + lc]);
              if (lc == 3) TS(18);
            }
          }
        }
        __syncwarp();
        if (p.stop <= 3) return;
      }
    } else if (warp == 14) {
      mbar_wait(bar + 8 * B_EP, 0);
      const unsigned epoch = lds32(sb + SM_EP);
#pragma unroll 1
      for (int layer = 0; layer < 2; layer++) {
        if (p.stop <= 1 + 3 * layer) return;
        mbar_wait(bar + 8 * B_ZF, layer);
        mbar_wait(bar + 8 * (EXP_LATE ? B_PS : B_PDONE), layer);
        proj_stats(layer, rb2, q2, lane, 4 * epoch + 2 * layer + 2);
        if (layer == 1 && lane == 0) TS(5);
        if (lane == 0) mbar_arrive(bar + 8 * B_GB);
      }
    }
  }
}

typedef CUresult (*EncodeFn)(CUtensorMap*, CUtensorMapDataType, cuuint32_t, void*, const cuuint64_t*, const cuuint64_t*,
                             const cuuint32_t*, const cuuint32_t*, CUtensorMapInterleave, CUtensorMapSwizzle,
                             CUtensorMapL2promotion, CUtensorMapFloatOOBfill);

static void make_map(EncodeFn enc, CUtensorMap* m, void* ptr, uint64_t cols, uint64_t rows, uint32_t box_rows) {
  cuuint64_t dims[2] = {cols, rows};
  cuuint64_t strides[1] = {cols * 2};
  cuuint32_t box[2] = {64, box_rows};
  cuuint32_t es[2] = {1, 1};
  enc(m, CU_TENSOR_MAP_DATA_TYPE_BFLOAT16, 2, ptr, dims, strides, box, es, CU_TENSOR_MAP_INTERLEAVE_NONE,
      CU_TENSOR_MAP_SWIZZLE_128B, CU_TENSOR_MAP_L2_PROMOTION_L2_128B, CU_TENSOR_MAP_FLOAT_OOB_FILL_NONE);
}
static void make_map3(EncodeFn enc, CUtensorMap* m, void* ptr, uint64_t d0, uint64_t cols, uint64_t rows, uint64_t blk_stride,
                      uint64_t nblocks, uint32_t nblk, uint32_t box_rows = 64) {
  cuuint64_t dims[3] = {d0, rows, nblocks};
  cuuint64_t strides[2] = {cols * 2, blk_stride * 2};
  cuuint32_t box[3] = {64, box_rows, nblk};
  cuuint32_t es[3] = {1, 1, 1};
  enc(m, CU_TENSOR_MAP_DATA_TYPE_BFLOAT16, 3, ptr, dims, strides, box, es, CU_TENSOR_MAP_INTERLEAVE_NONE,
      CU_TENSOR_MAP_SWIZZLE_128B, CU_TENSOR_MAP_L2_PROMOTION_L2_128B, CU_TENSOR_MAP_FLOAT_OOB_FILL_NONE);
}

extern "C" void kernel_launch(void* const* d_in, const int* in_sizes, int n_in, void* d_out, int out_size) {
  static Params prm;
  static void* cached[13] = {nullptr};
  static bool attr_done = false, by_smid = false;
  bool same = attr_done && cached[12] == d_out;
  for (int i = 0; i < 12 && same; i++) same = cached[i] == d_in[i];
  if (!same) {
    void* fn = nullptr;
    cudaDriverEntryPointQueryResult qr;
    cudaGetDriverEntryPoint("cuTensorMapEncodeTiled", &fn, cudaEnableDefault, &qr);
    EncodeFn enc = (EncodeFn)fn;
    void *pO, *pXT;
    cudaGetSymbolAddress(&pO, g_O);
    cudaGetSymbolAddress(&pXT, g_xT);
    make_map(enc, &prm.mapO, pO, DM, LSEQ, 64);
    make_map(enc, &prm.mapXT, pXT, LSEQ, 4 * DM, 64);
    prm.out = (bf16*)d_out;
    make_map(enc, &prm.mapX128, d_in[0], DM, LSEQ, 128);
    make_map(enc, &prm.mapWo128, d_in[2], DM, DM, 128);
    make_map(enc, &prm.mapO128, pO, DM, LSEQ, 128);
    make_map3(enc, &prm.mapW3, d_in[1], DM, 3 * DM, DM, DM, 3, 3);
    make_map3(enc, &prm.mapW3h, d_in[1], DM, 3 * DM, DM, DM, 3, 3, 32);
    make_map3(enc, &prm.mapXT3, pXT, 64, LSEQ, 4 * DM, 64, 32, 2);
    prm.a_re = (const bf16*)d_in[4]; prm.a_im = (const bf16*)d_in[5];
    prm.b_re = (const bf16*)d_in[6]; prm.b_im = (const bf16*)d_in[7];
    prm.c_re = (const bf16*)d_in[8]; prm.c_im = (const bf16*)d_in[9];
    prm.log_dt = (const bf16*)d_in[10]; prm.dskip = (const bf16*)d_in[11];
    int dev = 0, sms = 0;
    cudaGetDevice(&dev);
    cudaDeviceGetAttribute(&sms, cudaDevAttrMultiProcessorCount, dev);
    by_smid = sms == 132;
    cudaFuncSetAttribute(fused_kernel<true>, cudaFuncAttributeMaxDynamicSharedMemorySize, SM_TOTAL);
    cudaFuncSetAttribute(fused_kernel<false>, cudaFuncAttributeMaxDynamicSharedMemorySize, SM_TOTAL);
    for (int i = 0; i < 12; i++) cached[i] = d_in[i];
    cached[12] = d_out;
    attr_done = true;
  }
  prm.stop = 100;
    if (by_smid) fused_kernel<true><<<132, NTHREADS, SM_TOTAL>>>(prm);
  else fused_kernel<false><<<NCTA, NTHREADS, SM_TOTAL>>>(prm);
}
```

```cpp
#include <cuda_runtime.h>
#include <cuda_bf16.h>
#include <cuda.h>
#include <stdint.h>

typedef __nv_bfloat16 bf16;

constexpr int LSEQ = 2048;
constexpr int DM = 512;
constexpr int NCTA = 128;
constexpr int NTHREADS = 512;
#define RR 0
#define KG_PRE 0
#define ST_AT 6
#define W2_LATE 0
#define FILL_AT 2
#define EXP_LATE 1
#define RFENCE 1
#define D_FIN 550
#define D_PREP 500
#define D_PST 0
#define D_HALO 0
#define CS_AT 4
#define KG_LAST 1
#define X_JIT 0
#define PF_AT 2
#define KG_GATE 2
#define R_CONS 192
#define R_HELP 88

constexpr int SM_X = 0;
constexpr int SM_W = 131072;
constexpr int SM_KVX = SM_W;
constexpr int SM_OST = SM_W + 32768;
constexpr int SM_R = 196608;
constexpr int SM_T = 212992;
constexpr int SM_KC = 217088;
constexpr int KC_STRIDE = 648;
constexpr int SM_CS = SM_KC + 4 * KC_STRIDE * 2;
constexpr int SM_CW = SM_R + 8192;
constexpr int SM_EP = SM_CS + 768;
constexpr int SM_BAR = SM_EP + 16;
constexpr int SM_T2 = SM_BAR + 832;
constexpr int SM_HALO = SM_T2 + 4096;
constexpr int SM_ST = SM_HALO + 3072;
constexpr int SM_TOTAL = SM_HALO + 4096;
static_assert(SM_TOTAL <= 232448, "shared memory");

constexpr int CV_UH = 140 * 16;
constexpr int CV_PECH = 1120 * 4;
constexpr int CV_PBW = 2112 * 2;
__host__ __device__ constexpr int cv_s(int lc) { return SM_X + lc * 32768; }
__host__ __device__ constexpr int cv_u(int lc) { return cv_s(lc) + 4096; }
__host__ __device__ constexpr int cv_pe(int lc) { return cv_u(lc) + 2 * CV_UH; }
__host__ __device__ constexpr int cv_pb(int lc) { return cv_pe(lc) + CV_PECH; }
__host__ __device__ constexpr int cv_ft(int lc) { return cv_pb(lc) + 4 * CV_PBW; }
static_assert(cv_ft(0) + 1024 <= 32768, "conv buffers");
__host__ __device__ constexpr int cv_chan(int cta, int lc) { return cta + 128 * lc; }

enum {
  B_XF = 0,
  B_KVF = 8,
  B_KVE = 16,
  B_AD = 21,
  B_OST = 22,
  B_RF = 23,
  B_U = 24,
  B_S = 28,
  B_T = 32,
  B_WOF = 36,
  B_E = 40,
  B_OF = 44,
  B_P = 64,
  B_RE = 52,
  B_CW = 53,
  B_HF = 54,
  B_STF = 55,
  B_QDONE = 56,
  B_PDONE = 57,
  B_PS = 58,
  B_PE = 59,
  B_GB = 60,
  B_EP = 62,
  B_ZF = 63,
  B_COUNT = 68
};

enum {
  C_CS = 0,
  C_G1 = 2,
  C_O = 4,
  C_COUNT = 20
};

__device__ __align__(128) unsigned g_cnt[C_COUNT * 32];
__device__ __align__(1024) bf16 g_O[LSEQ * DM];
__device__ __align__(1024) bf16 g_xT[4 * DM * LSEQ];
__device__ __align__(1024) float g_stats[2 * LSEQ * 2];
__device__ __align__(1024) uint4 g_colsum[8 * 16 * 48];
__device__ __align__(1024) uint4 g_halo[2 * 16 * 8 * 384];
__device__ __align__(1024) uint4 g_part[2 * 16 * 8 * 128];
#define TS(i) do { } while (0)

#define KTS(i) do { if (ht == 0) TS(i); } while (0)
#define FTS(i) do { } while (0)
#define LTS(i) do { } while (0)

struct Params {
  CUtensorMap mapO, mapXT, mapX128, mapWo128, mapO128, mapW3, mapW3h, mapXT3;
  const bf16 *a_re, *a_im, *b_re, *b_im, *c_re, *c_im, *log_dt, *dskip;
  bf16* out;
  int stop;
};

__device__ __forceinline__ uint32_t s32(const void* p) { return (uint32_t)__cvta_generic_to_shared(p); }
__device__ __forceinline__ void mbar_init(uint32_t b, int c) { asm volatile("mbarrier.init.shared::cta.b64 [%0], %1;" ::"r"(b), "r"(c) : "memory"); }
__device__ __forceinline__ void mbar_expect(uint32_t b, int bytes) { asm volatile("mbarrier.arrive.expect_tx.shared::cta.b64 _, [%0], %1;" ::"r"(b), "r"(bytes) : "memory"); }
__device__ __forceinline__ void mbar_arrive(uint32_t b) { asm volatile("mbarrier.arrive.shared::cta.b64 _, [%0];" ::"r"(b) : "memory"); }
__device__ __forceinline__ void mbar_arrive_if(uint32_t b, bool c) {
  asm volatile("{\n.reg .pred p;\nsetp.ne.u32 p, %1, 0;\n@p mbarrier.arrive.shared::cta.b64 _, [%0];\n}" ::"r"(b), "r"((uint32_t)c) : "memory");
}
__device__ __forceinline__ void mbar_wait(uint32_t b, int parity) {
  asm volatile("{\n.reg .pred p;\nWAIT_LOOP:\nmbarrier.try_wait.parity.shared::cta.b64 p, [%0], %1;\n@p bra WAIT_DONE;\nbra WAIT_LOOP;\nWAIT_DONE:\n}" ::"r"(b), "r"(parity) : "memory");
}
template <int N> __device__ __forceinline__ void delay() {
  if (N > 0) {
    uint32_t t0, t;
    asm volatile("mov.u32 %0, %%clock;" : "=r"(t0));
    do { asm volatile("mov.u32 %0, %%clock;" : "=r"(t)); } while (t - t0 < N);
  }
}
__device__ __forceinline__ int opaque_tid() { int v; asm volatile("mov.u32 %0, %%tid.x;" : "=r"(v)); return v; }
__device__ __forceinline__ bool elect_one() {
  uint32_t r;
  asm volatile("{\n.reg .pred p;\nelect.sync _|p, 0xffffffff;\nselp.u32 %0, 1, 0, p;\n}" : "=r"(r));
  return r != 0;
}
__device__ __forceinline__ void tma_ld(uint32_t dst, const CUtensorMap* m, int c0, int c1, uint32_t bar) {
  asm volatile("cp.async.bulk.tensor.2d.shared::cluster.global.mbarrier::complete_tx::bytes [%0], [%1, {%3, %4}], [%2];"
               ::"r"(dst), "l"(m), "r"(bar), "r"(c0), "r"(c1) : "memory");
}
__device__ __forceinline__ void tma_ld3(uint32_t dst, const CUtensorMap* m, int c0, int c1, int c2, uint32_t bar) {
  asm volatile("cp.async.bulk.tensor.3d.shared::cluster.global.mbarrier::complete_tx::bytes [%0], [%1, {%3, %4, %5}], [%2];"
               ::"r"(dst), "l"(m), "r"(bar), "r"(c0), "r"(c1), "r"(c2) : "memory");
}
__device__ __forceinline__ void tma_prefetch2(const CUtensorMap* m, int c0, int c1) {
  asm volatile("cp.async.bulk.prefetch.tensor.2d.L2.global.tile [%0, {%1, %2}];" ::"l"(m), "r"(c0), "r"(c1) : "memory");
}
__device__ __forceinline__ void tma_prefetch3(const CUtensorMap* m, int c0, int c1, int c2) {
  asm volatile("cp.async.bulk.prefetch.tensor.3d.L2.global.tile [%0, {%1, %2, %3}];" ::"l"(m), "r"(c0), "r"(c1), "r"(c2) : "memory");
}
__device__ __forceinline__ void tma_st(const CUtensorMap* m, int c0, int c1, uint32_t src) {
  asm volatile("cp.async.bulk.tensor.2d.global.shared::cta.bulk_group [%0, {%2, %3}], [%1];" ::"l"(m), "r"(src), "r"(c0), "r"(c1) : "memory");
}
__device__ __forceinline__ void bulk_ld(uint32_t dst, const void* src, int bytes, uint32_t bar) {
  asm volatile("cp.async.bulk.shared::cluster.global.mbarrier::complete_tx::bytes [%0], [%1], %2, [%3];" ::"r"(dst), "l"(src), "r"(bytes), "r"(bar) : "memory");
}
__device__ __forceinline__ void bulk_st(void* dst, uint32_t src, int bytes) {
  asm volatile("cp.async.bulk.global.shared::cta.bulk_group [%0], [%1], %2;" ::"l"(dst), "r"(src), "r"(bytes) : "memory");
}
__device__ __forceinline__ void bulk_red_add_f32(void* dst, uint32_t src, int bytes) {
  asm volatile("cp.reduce.async.bulk.global.shared::cta.bulk_group.add.f32 [%0], [%1], %2;" ::"l"(dst), "r"(src), "r"(bytes) : "memory");
}
__device__ __forceinline__ void bulk_commit() { asm volatile("cp.async.bulk.commit_group;" ::: "memory"); }
__device__ __forceinline__ void bulk_wait_all() { asm volatile("cp.async.bulk.wait_group 0;" ::: "memory"); }
__device__ __forceinline__ void fence_async_smem() { asm volatile("fence.proxy.async.shared::cta;" ::: "memory"); }
__device__ __forceinline__ void fence_writer() { if (!RFENCE) fence_async_smem(); }
__device__ __forceinline__ void fence_reader() { if (RFENCE) fence_async_smem(); }
__device__ __forceinline__ void fence_async_global() { asm volatile("fence.proxy.async.global;" ::: "memory"); }
__device__ __forceinline__ void bar_sync(int id, int n) { asm volatile("bar.sync %0, %1;" ::"r"(id), "r"(n) : "memory"); }
__device__ __forceinline__ void bar_arrive(int id, int n) { asm volatile("bar.arrive %0, %1;" ::"r"(id), "r"(n) : "memory"); }
__device__ __forceinline__ void wg_fence() { asm volatile("wgmma.fence.sync.aligned;" ::: "memory"); }
__device__ __forceinline__ void wg_commit() { asm volatile("wgmma.commit_group.sync.aligned;" ::: "memory"); }
template <int N> __device__ __forceinline__ void wg_wait() { asm volatile("wgmma.wait_group.sync.aligned %0;" ::"n"(N) : "memory"); }
__device__ __forceinline__ uint64_t mkdesc(uint32_t addr, uint32_t lbo, uint32_t sbo, int sw) {
  return (uint64_t)((addr & 0x3FFFF) >> 4) | ((uint64_t)(lbo >> 4) << 16) | ((uint64_t)(sbo >> 4) << 32) | ((uint64_t)sw << 62);
}
__device__ __forceinline__ void ldsm4(uint32_t* r, uint32_t a) {
  asm volatile("ldmatrix.sync.aligned.m8n8.x4.shared.b16 {%0,%1,%2,%3}, [%4];" : "=r"(r[0]), "=r"(r[1]), "=r"(r[2]), "=r"(r[3]) : "r"(a) : "memory");
}
__device__ __forceinline__ void ldsm4t(uint32_t* r, uint32_t a) {
  asm volatile("ldmatrix.sync.aligned.m8n8.x4.trans.shared.b16 {%0,%1,%2,%3}, [%4];" : "=r"(r[0]), "=r"(r[1]), "=r"(r[2]), "=r"(r[3]) : "r"(a) : "memory");
}
__device__ __forceinline__ void stsm4(uint32_t a, uint32_t r0, uint32_t r1, uint32_t r2, uint32_t r3) {
  asm volatile("stmatrix.sync.aligned.m8n8.x4.shared.b16 [%0], {%1,%2,%3,%4};" ::"r"(a), "r"(r0), "r"(r1), "r"(r2), "r"(r3) : "memory");
}
__device__ __forceinline__ void stsm4t(uint32_t a, uint32_t r0, uint32_t r1, uint32_t r2, uint32_t r3) {
  asm volatile("stmatrix.sync.aligned.m8n8.x4.trans.shared.b16 [%0], {%1,%2,%3,%4};" ::"r"(a), "r"(r0), "r"(r1), "r"(r2), "r"(r3) : "memory");
}
__device__ __forceinline__ uint32_t movm_t(uint32_t a) { uint32_t r; asm volatile("movmatrix.sync.aligned.m8n8.trans.b16 %0, %1;" : "=r"(r) : "r"(a)); return r; }
__device__ __forceinline__ uint32_t lds32(uint32_t a) { uint32_t v; asm volatile("ld.shared.b32 %0, [%1];" : "=r"(v) : "r"(a) : "memory"); return v; }
__device__ __forceinline__ float2 lds64f(uint32_t a) { float2 v; asm volatile("ld.shared.v2.f32 {%0,%1}, [%2];" : "=f"(v.x), "=f"(v.y) : "r"(a) : "memory"); return v; }
__device__ __forceinline__ float4 lds128f(uint32_t a) { float4 v; asm volatile("ld.shared.v4.f32 {%0,%1,%2,%3}, [%4];" : "=f"(v.x), "=f"(v.y), "=f"(v.z), "=f"(v.w) : "r"(a) : "memory"); return v; }
__device__ __forceinline__ uint4 lds128(uint32_t a) { uint4 v; asm volatile("ld.shared.v4.b32 {%0,%1,%2,%3}, [%4];" : "=r"(v.x), "=r"(v.y), "=r"(v.z), "=r"(v.w) : "r"(a) : "memory"); return v; }
__device__ __forceinline__ void sts128(uint32_t a, uint4 v) { asm volatile("st.shared.v4.b32 [%0], {%1,%2,%3,%4};" ::"r"(a), "r"(v.x), "r"(v.y), "r"(v.z), "r"(v.w) : "memory"); }
__device__ __forceinline__ void sts128f(uint32_t a, float x, float y, float z, float w) { asm volatile("st.shared.v4.f32 [%0], {%1,%2,%3,%4};" ::"r"(a), "f"(x), "f"(y), "f"(z), "f"(w) : "memory"); }
__device__ __forceinline__ void sts32f(uint32_t a, float v) { asm volatile("st.shared.f32 [%0], %1;" ::"r"(a), "f"(v) : "memory"); }
__device__ __forceinline__ void sts16(uint32_t a, uint16_t v) { asm volatile("st.shared.u16 [%0], %1;" ::"r"(a), "h"(v) : "memory"); }
__device__ __forceinline__ uint32_t lds16(uint32_t a) { uint16_t v; asm volatile("ld.shared.u16 %0, [%1];" : "=h"(v) : "r"(a) : "memory"); return v; }
__device__ __forceinline__ uint32_t packbf(float lo, float hi) { uint32_t r; asm("cvt.rn.bf16x2.f32 %0, %1, %2;" : "=r"(r) : "f"(hi), "f"(lo)); return r; }
__device__ __forceinline__ float bf_lo(uint32_t v) { return __uint_as_float(v << 16); }
__device__ __forceinline__ float bf_hi(uint32_t v) { return __uint_as_float(v & 0xffff0000u); }
__device__ __forceinline__ float ex2(float x) { float r; asm("ex2.approx.ftz.f32 %0, %1;" : "=f"(r) : "f"(x)); return r; }
__device__ __forceinline__ float rsqrt_approx(float x) { float r; asm("rsqrt.approx.ftz.f32 %0, %1;" : "=f"(r) : "f"(x)); return r; }
__device__ __forceinline__ float rcp_approx(float x) { float r; asm("rcp.approx.ftz.f32 %0, %1;" : "=f"(r) : "f"(x)); return r; }
__device__ __forceinline__ void mma_bf16(float* d, const uint32_t* a, uint32_t b0, uint32_t b1) {
  asm("mma.sync.aligned.m16n8k16.row.col.f32.bf16.bf16.f32 {%0,%1,%2,%3}, {%4,%5,%6,%7}, {%8,%9}, {%0,%1,%2,%3};"
               : "+f"(d[0]), "+f"(d[1]), "+f"(d[2]), "+f"(d[3]) : "r"(a[0]), "r"(a[1]), "r"(a[2]), "r"(a[3]), "r"(b0), "r"(b1));
}
__device__ __forceinline__ void red_release(unsigned* p) { asm volatile("red.release.gpu.global.add.u32 [%0], 1;" ::"l"(p) : "memory"); }
__device__ __forceinline__ void red_relaxed(unsigned* p) { asm volatile("red.relaxed.gpu.global.add.u32 [%0], 1;" ::"l"(p) : "memory"); }
__device__ __forceinline__ unsigned ld_relaxed(const unsigned* p) { unsigned v; asm volatile("ld.relaxed.gpu.global.u32 %0, [%1];" : "=r"(v) : "l"(p) : "memory"); return v; }
__device__ __forceinline__ void spin_until(const unsigned* p, unsigned target) {
  int it = 0;
  while ((int)(ld_relaxed(p) - target) < 0) {
    if (++it > (1 << 23)) __trap();
  }
}
__device__ __forceinline__ uint4 ldcg128(const void* p) { uint4 v; asm volatile("ld.global.cg.v4.b32 {%0,%1,%2,%3}, [%4];" : "=r"(v.x), "=r"(v.y), "=r"(v.z), "=r"(v.w) : "l"(p) : "memory"); return v; }
__device__ __forceinline__ uint4 ld_tagged(const uint4* p) { uint4 v; asm volatile("ld.relaxed.gpu.global.v4.u32 {%0,%1,%2,%3}, [%4];" : "=r"(v.x), "=r"(v.y), "=r"(v.z), "=r"(v.w) : "l"(p) : "memory"); return v; }
__device__ __forceinline__ void st_tagged(uint4* p, uint32_t a, uint32_t b, uint32_t tag) { asm volatile("st.relaxed.gpu.global.v4.u32 [%0], {%1,%2,%3,%2};" ::"l"(p), "r"(a), "r"(tag), "r"(b) : "memory"); }
__device__ __forceinline__ void st_tagged3(uint4* p, uint32_t a, uint32_t b, uint32_t c, uint32_t tag) { asm volatile("st.relaxed.gpu.global.v4.u32 [%0], {%1,%2,%3,%4};" ::"l"(p), "r"(a), "r"(b), "r"(c), "r"(tag) : "memory"); }
__device__ __forceinline__ uint4 poll_tagged(const uint4* p, uint32_t tag) {
  uint4 v = ld_tagged(p);
  int it = 0;
  while (v.y != tag || v.w != tag) {
    if (++it > (1 << 22)) __trap();
    v = ld_tagged(p);
  }
  return v;
}
__device__ __forceinline__ uint32_t hadd2(uint32_t a, uint32_t b) { uint32_t r; asm("add.rn.bf16x2 %0, %1, %2;" : "=r"(r) : "r"(a), "r"(b)); return r; }
__device__ __forceinline__ uint32_t hmul2(uint32_t a, uint32_t b) { uint32_t r; asm("mul.rn.bf16x2 %0, %1, %2;" : "=r"(r) : "r"(a), "r"(b)); return r; }

template<int N,int TB> __device__ __forceinline__ void wgmma_rs(float* d, const uint32_t* a, uint64_t db, int sd);
template<int N,int TA,int TB> __device__ __forceinline__ void wgmma_ss(float* d, uint64_t da, uint64_t db, int sd);
template<> __device__ __forceinline__ void wgmma_rs<128,0>(float* d, const uint32_t* a, uint64_t db, int sd) {
  asm volatile("{\n.reg .pred p;\nsetp.ne.b32 p, %69, 0;\nwgmma.mma_async.sync.aligned.m64n128k16.f32.bf16.bf16 {%0,%1,%2,%3,%4,%5,%6,%7,%8,%9,%10,%11,%12,%13,%14,%15,%16,%17,%18,%19,%20,%21,%22,%23,%24,%25,%26,%27,%28,%29,%30,%31,%32,%33,%34,%35,%36,%37,%38,%39,%40,%41,%42,%43,%44,%45,%46,%47,%48,%49,%50,%51,%52,%53,%54,%55,%56,%57,%58,%59,%60,%61,%62,%63}, {%64,%65,%66,%67}, %68, p, 1, 1, 0;\n}\n"
   : "+f"(d[0]),"+f"(d[1]),"+f"(d[2]),"+f"(d[3]),"+f"(d[4]),"+f"(d[5]),"+f"(d[6]),"+f"(d[7]),"+f"(d[8]),"+f"(d[9]),"+f"(d[10]),"+f"(d[11]),"+f"(d[12]),"+f"(d[13]),"+f"(d[14]),"+f"(d[15]),"+f"(d[16]),"+f"(d[17]),"+f"(d[18]),"+f"(d[19]),"+f"(d[20]),"+f"(d[21]),"+f"(d[22]),"+f"(d[23]),"+f"(d[24]),"+f"(d[25]),"+f"(d[26]),"+f"(d[27]),"+f"(d[28]),"+f"(d[29]),"+f"(d[30]),"+f"(d[31]),"+f"(d[32]),"+f"(d[33]),"+f"(d[34]),"+f"(d[35]),"+f"(d[36]),"+f"(d[37]),"+f"(d[38]),"+f"(d[39]),"+f"(d[40]),"+f"(d[41]),"+f"(d[42]),"+f"(d[43]),"+f"(d[44]),"+f"(d[45]),"+f"(d[46]),"+f"(d[47]),"+f"(d[48]),"+f"(d[49]),"+f"(d[50]),"+f"(d[51]),"+f"(d[52]),"+f"(d[53]),"+f"(d[54]),"+f"(d[55]),"+f"(d[56]),"+f"(d[57]),"+f"(d[58]),"+f"(d[59]),"+f"(d[60]),"+f"(d[61]),"+f"(d[62]),"+f"(d[63])
   : "r"(a[0]), "r"(a[1]), "r"(a[2]), "r"(a[3]), "l"(db), "r"(sd));
}
template<> __device__ __forceinline__ void wgmma_rs<120,0>(float* d, const uint32_t* a, uint64_t db, int sd) {
  asm volatile("{\n.reg .pred p;\nsetp.ne.b32 p, %65, 0;\nwgmma.mma_async.sync.aligned.m64n120k16.f32.bf16.bf16 {%0,%1,%2,%3,%4,%5,%6,%7,%8,%9,%10,%11,%12,%13,%14,%15,%16,%17,%18,%19,%20,%21,%22,%23,%24,%25,%26,%27,%28,%29,%30,%31,%32,%33,%34,%35,%36,%37,%38,%39,%40,%41,%42,%43,%44,%45,%46,%47,%48,%49,%50,%51,%52,%53,%54,%55,%56,%57,%58,%59}, {%60,%61,%62,%63}, %64, p, 1, 1, 0;\n}\n"
   : "+f"(d[0]),"+f"(d[1]),"+f"(d[2]),"+f"(d[3]),"+f"(d[4]),"+f"(d[5]),"+f"(d[6]),"+f"(d[7]),"+f"(d[8]),"+f"(d[9]),"+f"(d[10]),"+f"(d[11]),"+f"(d[12]),"+f"(d[13]),"+f"(d[14]),"+f"(d[15]),"+f"(d[16]),"+f"(d[17]),"+f"(d[18]),"+f"(d[19]),"+f"(d[20]),"+f"(d[21]),"+f"(d[22]),"+f"(d[23]),"+f"(d[24]),"+f"(d[25]),"+f"(d[26]),"+f"(d[27]),"+f"(d[28]),"+f"(d[29]),"+f"(d[30]),"+f"(d[31]),"+f"(d[32]),"+f"(d[33]),"+f"(d[34]),"+f"(d[35]),"+f"(d[36]),"+f"(d[37]),"+f"(d[38]),"+f"(d[39]),"+f"(d[40]),"+f"(d[41]),"+f"(d[42]),"+f"(d[43]),"+f"(d[44]),"+f"(d[45]),"+f"(d[46]),"+f"(d[47]),"+f"(d[48]),"+f"(d[49]),"+f"(d[50]),"+f"(d[51]),"+f"(d[52]),"+f"(d[53]),"+f"(d[54]),"+f"(d[55]),"+f"(d[56]),"+f"(d[57]),"+f"(d[58]),"+f"(d[59])
   : "r"(a[0]), "r"(a[1]), "r"(a[2]), "r"(a[3]), "l"(db), "r"(sd));
}
template<> __device__ __forceinline__ void wgmma_rs<112,0>(float* d, const uint32_t* a, uint64_t db, int sd) {
  asm volatile("{\n.reg .pred p;\nsetp.ne.b32 p, %61, 0;\nwgmma.mma_async.sync.aligned.m64n112k16.f32.bf16.bf16 {%0,%1,%2,%3,%4,%5,%6,%7,%8,%9,%10,%11,%12,%13,%14,%15,%16,%17,%18,%19,%20,%21,%22,%23,%24,%25,%26,%27,%28,%29,%30,%31,%32,%33,%34,%35,%36,%37,%38,%39,%40,%41,%42,%43,%44,%45,%46,%47,%48,%49,%50,%51,%52,%53,%54,%55}, {%56,%57,%58,%59}, %60, p, 1, 1, 0;\n}\n"
   : "+f"(d[0]),"+f"(d[1]),"+f"(d[2]),"+f"(d[3]),"+f"(d[4]),"+f"(d[5]),"+f"(d[6]),"+f"(d[7]),"+f"(d[8]),"+f"(d[9]),"+f"(d[10]),"+f"(d[11]),"+f"(d[12]),"+f"(d[13]),"+f"(d[14]),"+f"(d[15]),"+f"(d[16]),"+f"(d[17]),"+f"(d[18]),"+f"(d[19]),"+f"(d[20]),"+f"(d[21]),"+f"(d[22]),"+f"(d[23]),"+f"(d[24]),"+f"(d[25]),"+f"(d[26]),"+f"(d[27]),"+f"(d[28]),"+f"(d[29]),"+f"(d[30]),"+f"(d[31]),"+f"(d[32]),"+f"(d[33]),"+f"(d[34]),"+f"(d[35]),"+f"(d[36]),"+f"(d[37]),"+f"(d[38]),"+f"(d[39]),"+f"(d[40]),"+f"(d[41]),"+f"(d[42]),"+f"(d[43]),"+f"(d[44]),"+f"(d[45]),"+f"(d[46]),"+f"(d[47]),"+f"(d[48]),"+f"(d[49]),"+f"(d[50]),"+f"(d[51]),"+f"(d[52]),"+f"(d[53]),"+f"(d[54]),"+f"(d[55])
   : "r"(a[0]), "r"(a[1]), "r"(a[2]), "r"(a[3]), "l"(db), "r"(sd));
}
template<> __device__ __forceinline__ void wgmma_rs<104,0>(float* d, const uint32_t* a, uint64_t db, int sd) {
  asm volatile("{\n.reg .pred p;\nsetp.ne.b32 p, %57, 0;\nwgmma.mma_async.sync.aligned.m64n104k16.f32.bf16.bf16 {%0,%1,%2,%3,%4,%5,%6,%7,%8,%9,%10,%11,%12,%13,%14,%15,%16,%17,%18,%19,%20,%21,%22,%23,%24,%25,%26,%27,%28,%29,%30,%31,%32,%33,%34,%35,%36,%37,%38,%39,%40,%41,%42,%43,%44,%45,%46,%47,%48,%49,%50,%51}, {%52,%53,%54,%55}, %56, p, 1, 1, 0;\n}\n"
   : "+f"(d[0]),"+f"(d[1]),"+f"(d[2]),"+f"(d[3]),"+f"(d[4]),"+f"(d[5]),"+f"(d[6]),"+f"(d[7]),"+f"(d[8]),"+f"(d[9]),"+f"(d[10]),"+f"(d[11]),"+f"(d[12]),"+f"(d[13]),"+f"(d[14]),"+f"(d[15]),"+f"(d[16]),"+f"(d[17]),"+f"(d[18]),"+f"(d[19]),"+f"(d[20]),"+f"(d[21]),"+f"(d[22]),"+f"(d[23]),"+f"(d[24]),"+f"(d[25]),"+f"(d[26]),"+f"(d[27]),"+f"(d[28]),"+f"(d[29]),"+f"(d[30]),"+f"(d[31]),"+f"(d[32]),"+f"(d[33]),"+f"(d[34]),"+f"(d[35]),"+f"(d[36]),"+f"(d[37]),"+f"(d[38]),"+f"(d[39]),"+f"(d[40]),"+f"(d[41]),"+f"(d[42]),"+f"(d[43]),"+f"(d[44]),"+f"(d[45]),"+f"(d[46]),"+f"(d[47]),"+f"(d[48]),"+f"(d[49]),"+f"(d[50]),"+f"(d[51])
   : "r"(a[0]), "r"(a[1]), "r"(a[2]), "r"(a[3]), "l"(db), "r"(sd));
}
template<> __device__ __forceinline__ void wgmma_rs<96,0>(float* d, const uint32_t* a, uint64_t db, int sd) {
  asm volatile("{\n.reg .pred p;\nsetp.ne.b32 p, %53, 0;\nwgmma.mma_async.sync.aligned.m64n96k16.f32.bf16.bf16 {%0,%1,%2,%3,%4,%5,%6,%7,%8,%9,%10,%11,%12,%13,%14,%15,%16,%17,%18,%19,%20,%21,%22,%23,%24,%25,%26,%27,%28,%29,%30,%31,%32,%33,%34,%35,%36,%37,%38,%39,%40,%41,%42,%43,%44,%45,%46,%47}, {%48,%49,%50,%51}, %52, p, 1, 1, 0;\n}\n"
   : "+f"(d[0]),"+f"(d[1]),"+f"(d[2]),"+f"(d[3]),"+f"(d[4]),"+f"(d[5]),"+f"(d[6]),"+f"(d[7]),"+f"(d[8]),"+f"(d[9]),"+f"(d[10]),"+f"(d[11]),"+f"(d[12]),"+f"(d[13]),"+f"(d[14]),"+f"(d[15]),"+f"(d[16]),"+f"(d[17]),"+f"(d[18]),"+f"(d[19]),"+f"(d[20]),"+f"(d[21]),"+f"(d[22]),"+f"(d[23]),"+f"(d[24]),"+f"(d[25]),"+f"(d[26]),"+f"(d[27]),"+f"(d[28]),"+f"(d[29]),"+f"(d[30]),"+f"(d[31]),"+f"(d[32]),"+f"(d[33]),"+f"(d[34]),"+f"(d[35]),"+f"(d[36]),"+f"(d[37]),"+f"(d[38]),"+f"(d[39]),"+f"(d[40]),"+f"(d[41]),"+f"(d[42]),"+f"(d[43]),"+f"(d[44]),"+f"(d[45]),"+f"(d[46]),"+f"(d[47])
   : "r"(a[0]), "r"(a[1]), "r"(a[2]), "r"(a[3]), "l"(db), "r"(sd));
}
template<> __device__ __forceinline__ void wgmma_rs<88,0>(float* d, const uint32_t* a, uint64_t db, int sd) {
  asm volatile("{\n.reg .pred p;\nsetp.ne.b32 p, %49, 0;\nwgmma.mma_async.sync.aligned.m64n88k16.f32.bf16.bf16 {%0,%1,%2,%3,%4,%5,%6,%7,%8,%9,%10,%11,%12,%13,%14,%15,%16,%17,%18,%19,%20,%21,%22,%23,%24,%25,%26,%27,%28,%29,%30,%31,%32,%33,%34,%35,%36,%37,%38,%39,%40,%41,%42,%43}, {%44,%45,%46,%47}, %48, p, 1, 1, 0;\n}\n"
   : "+f"(d[0]),"+f"(d[1]),"+f"(d[2]),"+f"(d[3]),"+f"(d[4]),"+f"(d[5]),"+f"(d[6]),"+f"(d[7]),"+f"(d[8]),"+f"(d[9]),"+f"(d[10]),"+f"(d[11]),"+f"(d[12]),"+f"(d[13]),"+f"(d[14]),"+f"(d[15]),"+f"(d[16]),"+f"(d[17]),"+f"(d[18]),"+f"(d[19]),"+f"(d[20]),"+f"(d[21]),"+f"(d[22]),"+f"(d[23]),"+f"(d[24]),"+f"(d[25]),"+f"(d[26]),"+f"(d[27]),"+f"(d[28]),"+f"(d[29]),"+f"(d[30]),"+f"(d[31]),"+f"(d[32]),"+f"(d[33]),"+f"(d[34]),"+f"(d[35]),"+f"(d[36]),"+f"(d[37]),"+f"(d[38]),"+f"(d[39]),"+f"(d[40]),"+f"(d[41]),"+f"(d[42]),"+f"(d[43])
   : "r"(a[0]), "r"(a[1]), "r"(a[2]), "r"(a[3]), "l"(db), "r"(sd));
}
template<> __device__ __forceinline__ void wgmma_rs<80,0>(float* d, const uint32_t* a, uint64_t db, int sd) {
  asm volatile("{\n.reg .pred p;\nsetp.ne.b32 p, %45, 0;\nwgmma.mma_async.sync.aligned.m64n80k16.f32.bf16.bf16 {%0,%1,%2,%3,%4,%5,%6,%7,%8,%9,%10,%11,%12,%13,%14,%15,%16,%17,%18,%19,%20,%21,%22,%23,%24,%25,%26,%27,%28,%29,%30,%31,%32,%33,%34,%35,%36,%37,%38,%39}, {%40,%41,%42,%43}, %44, p, 1, 1, 0;\n}\n"
   : "+f"(d[0]),"+f"(d[1]),"+f"(d[2]),"+f"(d[3]),"+f"(d[4]),"+f"(d[5]),"+f"(d[6]),"+f"(d[7]),"+f"(d[8]),"+f"(d[9]),"+f"(d[10]),"+f"(d[11]),"+f"(d[12]),"+f"(d[13]),"+f"(d[14]),"+f"(d[15]),"+f"(d[16]),"+f"(d[17]),"+f"(d[18]),"+f"(d[19]),"+f"(d[20]),"+f"(d[21]),"+f"(d[22]),"+f"(d[23]),"+f"(d[24]),"+f"(d[25]),"+f"(d[26]),"+f"(d[27]),"+f"(d[28]),"+f"(d[29]),"+f"(d[30]),"+f"(d[31]),"+f"(d[32]),"+f"(d[33]),"+f"(d[34]),"+f"(d[35]),"+f"(d[36]),"+f"(d[37]),"+f"(d[38]),"+f"(d[39])
   : "r"(a[0]), "r"(a[1]), "r"(a[2]), "r"(a[3]), "l"(db), "r"(sd));
}
template<> __device__ __forceinline__ void wgmma_rs<72,0>(float* d, const uint32_t* a, uint64_t db, int sd) {
  asm volatile("{\n.reg .pred p;\nsetp.ne.b32 p, %41, 0;\nwgmma.mma_async.sync.aligned.m64n72k16.f32.bf16.bf16 {%0,%1,%2,%3,%4,%5,%6,%7,%8,%9,%10,%11,%12,%13,%14,%15,%16,%17,%18,%19,%20,%21,%22,%23,%24,%25,%26,%27,%28,%29,%30,%31,%32,%33,%34,%35}, {%36,%37,%38,%39}, %40, p, 1, 1, 0;\n}\n"
   : "+f"(d[0]),"+f"(d[1]),"+f"(d[2]),"+f"(d[3]),"+f"(d[4]),"+f"(d[5]),"+f"(d[6]),"+f"(d[7]),"+f"(d[8]),"+f"(d[9]),"+f"(d[10]),"+f"(d[11]),"+f"(d[12]),"+f"(d[13]),"+f"(d[14]),"+f"(d[15]),"+f"(d[16]),"+f"(d[17]),"+f"(d[18]),"+f"(d[19]),"+f"(d[20]),"+f"(d[21]),"+f"(d[22]),"+f"(d[23]),"+f"(d[24]),"+f"(d[25]),"+f"(d[26]),"+f"(d[27]),"+f"(d[28]),"+f"(d[29]),"+f"(d[30]),"+f"(d[31]),"+f"(d[32]),"+f"(d[33]),"+f"(d[34]),"+f"(d[35])
   : "r"(a[0]), "r"(a[1]), "r"(a[2]), "r"(a[3]), "l"(db), "r"(sd));
}
template<> __device__ __forceinline__ void wgmma_rs<64,0>(float* d, const uint32_t* a, uint64_t db, int sd) {
  asm volatile("{\n.reg .pred p;\nsetp.ne.b32 p, %37, 0;\nwgmma.mma_async.sync.aligned.m64n64k16.f32.bf16.bf16 {%0,%1,%2,%3,%4,%5,%6,%7,%8,%9,%10,%11,%12,%13,%14,%15,%16,%17,%18,%19,%20,%21,%22,%23,%24,%25,%26,%27,%28,%29,%30,%31}, {%32,%33,%34,%35}, %36, p, 1, 1, 0;\n}\n"
   : "+f"(d[0]),"+f"(d[1]),"+f"(d[2]),"+f"(d[3]),"+f"(d[4]),"+f"(d[5]),"+f"(d[6]),"+f"(d[7]),"+f"(d[8]),"+f"(d[9]),"+f"(d[10]),"+f"(d[11]),"+f"(d[12]),"+f"(d[13]),"+f"(d[14]),"+f"(d[15]),"+f"(d[16]),"+f"(d[17]),"+f"(d[18]),"+f"(d[19]),"+f"(d[20]),"+f"(d[21]),"+f"(d[22]),"+f"(d[23]),"+f"(d[24]),"+f"(d[25]),"+f"(d[26]),"+f"(d[27]),"+f"(d[28]),"+f"(d[29]),"+f"(d[30]),"+f"(d[31])
   : "r"(a[0]), "r"(a[1]), "r"(a[2]), "r"(a[3]), "l"(db), "r"(sd));
}
template<> __device__ __forceinline__ void wgmma_ss<64,0,1>(float* d, uint64_t da, uint64_t db, int sd) {
  asm volatile("{\n.reg .pred p;\nsetp.ne.b32 p, %34, 0;\nwgmma.mma_async.sync.aligned.m64n64k16.f32.bf16.bf16 {%0,%1,%2,%3,%4,%5,%6,%7,%8,%9,%10,%11,%12,%13,%14,%15,%16,%17,%18,%19,%20,%21,%22,%23,%24,%25,%26,%27,%28,%29,%30,%31}, %32, %33, p, 1, 1, 0, 1;\n}\n"
   : "+f"(d[0]),"+f"(d[1]),"+f"(d[2]),"+f"(d[3]),"+f"(d[4]),"+f"(d[5]),"+f"(d[6]),"+f"(d[7]),"+f"(d[8]),"+f"(d[9]),"+f"(d[10]),"+f"(d[11]),"+f"(d[12]),"+f"(d[13]),"+f"(d[14]),"+f"(d[15]),"+f"(d[16]),"+f"(d[17]),"+f"(d[18]),"+f"(d[19]),"+f"(d[20]),"+f"(d[21]),"+f"(d[22]),"+f"(d[23]),"+f"(d[24]),"+f"(d[25]),"+f"(d[26]),"+f"(d[27]),"+f"(d[28]),"+f"(d[29]),"+f"(d[30]),"+f"(d[31])
   : "l"(da), "l"(db), "r"(sd));
}
template<> __device__ __forceinline__ void wgmma_ss<64,1,1>(float* d, uint64_t da, uint64_t db, int sd) {
  asm volatile("{\n.reg .pred p;\nsetp.ne.b32 p, %34, 0;\nwgmma.mma_async.sync.aligned.m64n64k16.f32.bf16.bf16 {%0,%1,%2,%3,%4,%5,%6,%7,%8,%9,%10,%11,%12,%13,%14,%15,%16,%17,%18,%19,%20,%21,%22,%23,%24,%25,%26,%27,%28,%29,%30,%31}, %32, %33, p, 1, 1, 1, 1;\n}\n"
   : "+f"(d[0]),"+f"(d[1]),"+f"(d[2]),"+f"(d[3]),"+f"(d[4]),"+f"(d[5]),"+f"(d[6]),"+f"(d[7]),"+f"(d[8]),"+f"(d[9]),"+f"(d[10]),"+f"(d[11]),"+f"(d[12]),"+f"(d[13]),"+f"(d[14]),"+f"(d[15]),"+f"(d[16]),"+f"(d[17]),"+f"(d[18]),"+f"(d[19]),"+f"(d[20]),"+f"(d[21]),"+f"(d[22]),"+f"(d[23]),"+f"(d[24]),"+f"(d[25]),"+f"(d[26]),"+f"(d[27]),"+f"(d[28]),"+f"(d[29]),"+f"(d[30]),"+f"(d[31])
   : "l"(da), "l"(db), "r"(sd));
}
template<> __device__ __forceinline__ void wgmma_ss<192,0,1>(float* d, uint64_t da, uint64_t db, int sd) {
  asm volatile("{\n.reg .pred p;\nsetp.ne.b32 p, %98, 0;\nwgmma.mma_async.sync.aligned.m64n192k16.f32.bf16.bf16 {%0,%1,%2,%3,%4,%5,%6,%7,%8,%9,%10,%11,%12,%13,%14,%15,%16,%17,%18,%19,%20,%21,%22,%23,%24,%25,%26,%27,%28,%29,%30,%31,%32,%33,%34,%35,%36,%37,%38,%39,%40,%41,%42,%43,%44,%45,%46,%47,%48,%49,%50,%51,%52,%53,%54,%55,%56,%57,%58,%59,%60,%61,%62,%63,%64,%65,%66,%67,%68,%69,%70,%71,%72,%73,%74,%75,%76,%77,%78,%79,%80,%81,%82,%83,%84,%85,%86,%87,%88,%89,%90,%91,%92,%93,%94,%95}, %96, %97, p, 1, 1, 0, 1;\n}\n"
   : "+f"(d[0]),"+f"(d[1]),"+f"(d[2]),"+f"(d[3]),"+f"(d[4]),"+f"(d[5]),"+f"(d[6]),"+f"(d[7]),"+f"(d[8]),"+f"(d[9]),"+f"(d[10]),"+f"(d[11]),"+f"(d[12]),"+f"(d[13]),"+f"(d[14]),"+f"(d[15]),"+f"(d[16]),"+f"(d[17]),"+f"(d[18]),"+f"(d[19]),"+f"(d[20]),"+f"(d[21]),"+f"(d[22]),"+f"(d[23]),"+f"(d[24]),"+f"(d[25]),"+f"(d[26]),"+f"(d[27]),"+f"(d[28]),"+f"(d[29]),"+f"(d[30]),"+f"(d[31]),"+f"(d[32]),"+f"(d[33]),"+f"(d[34]),"+f"(d[35]),"+f"(d[36]),"+f"(d[37]),"+f"(d[38]),"+f"(d[39]),"+f"(d[40]),"+f"(d[41]),"+f"(d[42]),"+f"(d[43]),"+f"(d[44]),"+f"(d[45]),"+f"(d[46]),"+f"(d[47]),"+f"(d[48]),"+f"(d[49]),"+f"(d[50]),"+f"(d[51]),"+f"(d[52]),"+f"(d[53]),"+f"(d[54]),"+f"(d[55]),"+f"(d[56]),"+f"(d[57]),"+f"(d[58]),"+f"(d[59]),"+f"(d[60]),"+f"(d[61]),"+f"(d[62]),"+f"(d[63]),"+f"(d[64]),"+f"(d[65]),"+f"(d[66]),"+f"(d[67]),"+f"(d[68]),"+f"(d[69]),"+f"(d[70]),"+f"(d[71]),"+f"(d[72]),"+f"(d[73]),"+f"(d[74]),"+f"(d[75]),"+f"(d[76]),"+f"(d[77]),"+f"(d[78]),"+f"(d[79]),"+f"(d[80]),"+f"(d[81]),"+f"(d[82]),"+f"(d[83]),"+f"(d[84]),"+f"(d[85]),"+f"(d[86]),"+f"(d[87]),"+f"(d[88]),"+f"(d[89]),"+f"(d[90]),"+f"(d[91]),"+f"(d[92]),"+f"(d[93]),"+f"(d[94]),"+f"(d[95])
   : "l"(da), "l"(db), "r"(sd));
}
template<> __device__ __forceinline__ void wgmma_ss<192,1,1>(float* d, uint64_t da, uint64_t db, int sd) {
  asm volatile("{\n.reg .pred p;\nsetp.ne.b32 p, %98, 0;\nwgmma.mma_async.sync.aligned.m64n192k16.f32.bf16.bf16 {%0,%1,%2,%3,%4,%5,%6,%7,%8,%9,%10,%11,%12,%13,%14,%15,%16,%17,%18,%19,%20,%21,%22,%23,%24,%25,%26,%27,%28,%29,%30,%31,%32,%33,%34,%35,%36,%37,%38,%39,%40,%41,%42,%43,%44,%45,%46,%47,%48,%49,%50,%51,%52,%53,%54,%55,%56,%57,%58,%59,%60,%61,%62,%63,%64,%65,%66,%67,%68,%69,%70,%71,%72,%73,%74,%75,%76,%77,%78,%79,%80,%81,%82,%83,%84,%85,%86,%87,%88,%89,%90,%91,%92,%93,%94,%95}, %96, %97, p, 1, 1, 1, 1;\n}\n"
   : "+f"(d[0]),"+f"(d[1]),"+f"(d[2]),"+f"(d[3]),"+f"(d[4]),"+f"(d[5]),"+f"(d[6]),"+f"(d[7]),"+f"(d[8]),"+f"(d[9]),"+f"(d[10]),"+f"(d[11]),"+f"(d[12]),"+f"(d[13]),"+f"(d[14]),"+f"(d[15]),"+f"(d[16]),"+f"(d[17]),"+f"(d[18]),"+f"(d[19]),"+f"(d[20]),"+f"(d[21]),"+f"(d[22]),"+f"(d[23]),"+f"(d[24]),"+f"(d[25]),"+f"(d[26]),"+f"(d[27]),"+f"(d[28]),"+f"(d[29]),"+f"(d[30]),"+f"(d[31]),"+f"(d[32]),"+f"(d[33]),"+f"(d[34]),"+f"(d[35]),"+f"(d[36]),"+f"(d[37]),"+f"(d[38]),"+f"(d[39]),"+f"(d[40]),"+f"(d[41]),"+f"(d[42]),"+f"(d[43]),"+f"(d[44]),"+f"(d[45]),"+f"(d[46]),"+f"(d[47]),"+f"(d[48]),"+f"(d[49]),"+f"(d[50]),"+f"(d[51]),"+f"(d[52]),"+f"(d[53]),"+f"(d[54]),"+f"(d[55]),"+f"(d[56]),"+f"(d[57]),"+f"(d[58]),"+f"(d[59]),"+f"(d[60]),"+f"(d[61]),"+f"(d[62]),"+f"(d[63]),"+f"(d[64]),"+f"(d[65]),"+f"(d[66]),"+f"(d[67]),"+f"(d[68]),"+f"(d[69]),"+f"(d[70]),"+f"(d[71]),"+f"(d[72]),"+f"(d[73]),"+f"(d[74]),"+f"(d[75]),"+f"(d[76]),"+f"(d[77]),"+f"(d[78]),"+f"(d[79]),"+f"(d[80]),"+f"(d[81]),"+f"(d[82]),"+f"(d[83]),"+f"(d[84]),"+f"(d[85]),"+f"(d[86]),"+f"(d[87]),"+f"(d[88]),"+f"(d[89]),"+f"(d[90]),"+f"(d[91]),"+f"(d[92]),"+f"(d[93]),"+f"(d[94]),"+f"(d[95])
   : "l"(da), "l"(db), "r"(sd));
}

__device__ __forceinline__ void stats_publish(uint32_t sb, int layer, int rb, int hg, int ht, uint32_t tag) {
  const int lane = ht & 31, w = ht >> 5, g = lane >> 2, t = lane & 3;
  mbar_wait(sb + SM_BAR + 8 * (B_XF + hg), layer);
  uint32_t A[2][16];
#pragma unroll
  for (int h = 0; h < 2; h++) {
    const uint32_t xb = sb + SM_X + hg * 16384 + h * 8192;
#pragma unroll
    for (int ks = 0; ks < 4; ks++) {
      if (layer == 0) {
        const int row = 16 * w + (lane & 15), kc = 2 * ks + (lane >> 4);
        ldsm4(&A[h][4 * ks], xb + row * 128 + ((kc ^ (row & 7)) << 4));
      } else {
        const int k = 16 * ks + (lane & 7) + 8 * (lane >> 4), pc = 2 * w + ((lane >> 3) & 1);
        ldsm4t(&A[h][4 * ks], xb + k * 128 + ((pc ^ (k & 7)) << 4));
      }
    }
  }
  float s[4], q[4];
#pragma unroll
  for (int r = 0; r < 4; r++) {
    s[r] = q[r] = 0.f;
#pragma unroll
    for (int i = 0; i < 8; i++) {
      const uint32_t v = A[r >> 1][2 * i + (r & 1)];
      const float a = bf_lo(v), b = bf_hi(v);
      s[r] += a + b; q[r] = fmaf(a, a, q[r]); q[r] = fmaf(b, b, q[r]);
    }
  }
#pragma unroll
  for (int r = 0; r < 2; r++) {
    s[r] = ((t & 2) ? s[r + 2] : s[r]) + __shfl_xor_sync(~0u, (t & 2) ? s[r] : s[r + 2], 2);
    q[r] = ((t & 2) ? q[r + 2] : q[r]) + __shfl_xor_sync(~0u, (t & 2) ? q[r] : q[r + 2], 2);
  }
  s[0] = ((t & 1) ? s[1] : s[0]) + __shfl_xor_sync(~0u, (t & 1) ? s[0] : s[1], 1);
  q[0] = ((t & 1) ? q[1] : q[0]) + __shfl_xor_sync(~0u, (t & 1) ? q[0] : q[1], 1);
  st_tagged(&g_part[(rb * 8 + hg) * 128 + 64 * (t >> 1) + 16 * w + 8 * (t & 1) + g], __float_as_uint(s[0]), __float_as_uint(q[0]), tag);
}
__device__ __forceinline__ void stats_gather(uint32_t sb, int rb, int ht, uint32_t tag) {
  const uint4* src = &g_part[rb * 8 * 128 + ht];
  uint4 v[8];
  bool ok;
  int it = 0;
  do {
    ok = true;
#pragma unroll
    for (int i = 0; i < 8; i++) v[i] = ld_tagged(src + i * 128);
#pragma unroll
    for (int i = 0; i < 8; i++) ok = ok && v[i].y == tag && v[i].w == tag;
    if (++it > (1 << 22)) __trap();
  } while (!__all_sync(~0u, ok));
  float s = 0.f, q = 0.f;
#pragma unroll
  for (int i = 0; i < 8; i++) { s += __uint_as_float(v[i].x); q += __uint_as_float(v[i].z); }
  const float mean = s * (1.f / DM);
  const float rstd = rsqrt_approx(fmaxf(q * (1.f / DM) - mean * mean, 0.f) + 1e-5f);
  asm volatile("st.shared.v2.f32 [%0], {%1,%2};" ::"r"(sb + SM_ST + ht * 8), "f"(mean), "f"(rstd) : "memory");
  __syncwarp();
  if (elect_one()) mbar_arrive(sb + SM_BAR + 8 * B_STF);
}

template <bool TR>
__device__ __forceinline__ void gemm_section(float* acc, uint32_t sb, int layer, int wg, int w, int lane) {
  const uint32_t bar = sb + SM_BAR;
  const bool leader = (w == 0) && (lane == 0);
  auto issue = [&](int c, int slot) {
    mbar_wait(bar + 8 * (B_XF + c), layer);
    mbar_wait(bar + 8 * (B_KVF + c), layer);
    const uint64_t da = mkdesc(sb + SM_X + c * 16384 + wg * 8192, TR ? 8192 : 16, 1024, 1);
    const uint64_t db = mkdesc(sb + SM_W + slot * 24576, 8192, 1024, 1);
    wg_fence();
#pragma unroll
    for (int ks = 0; ks < 4; ks++) wgmma_ss<192, TR ? 1 : 0, 1>(acc, da + (TR ? ks * 128 : ks * 2), db + ks * 128, (c | ks) != 0);
    wg_commit();
  };
  auto step = [&](int c, int slot) {
    issue(c, slot);
    wg_wait<1>();
    if (leader) mbar_arrive(bar + 8 * (B_KVE + c - 1));
  };
  issue(0, 0);
  if (threadIdx.x == 0) TS(2 + layer * 20 + 0);
  if (threadIdx.x == 128 && layer == 1) TS(60);
  step(1, 1); step(2, 2); step(3, 0); step(4, 1); step(5, 2);
  issue(6, 0);
  wg_wait<1>();
  if (wg == 0) bar_sync(5, 256);
  issue(7, 1);
  if (wg == 1) bar_arrive(5, 256);
}

__device__ __forceinline__ void attn_phase(const Params& p, uint32_t sb, int layer, int rb, int hg, int wg, int w) {
  const int lane = opaque_tid() & 31;
  const int g = lane >> 2, t = lane & 3;
  const uint32_t bar = sb + SM_BAR;
  const int row0 = 64 * wg + 16 * w;
  const bool leader = (w == 0) && (lane == 0);
  float acc[96];
  float2 cs[24];
  if (layer) gemm_section<true>(acc, sb, layer, wg, w, lane);
  else gemm_section<false>(acc, sb, layer, wg, w, lane);
  mbar_wait(bar + 8 * B_STF, layer);
  const uint32_t tag = 2 * lds32(sb + SM_EP) + layer + 1;
  const float2 st0 = lds64f(sb + SM_ST + (row0 + g) * 8), st1 = lds64f(sb + SM_ST + (row0 + g + 8) * 8);
  const float mean0 = st0.x, rstd0 = st0.y, mean1 = st1.x, rstd1 = st1.y;
#pragma unroll
  for (int j = 8; j < 24; j++) cs[j] = lds64f(sb + SM_CS + 4 * (8 * j + 2 * t));
  wg_wait<0>();
  if (threadIdx.x == 0) TS(2 + layer * 20 + 1);
  if (leader) mbar_arrive(bar + 8 * B_QDONE);

  uint32_t kb[4][8], vb[4][8], qa[4][4];
  {
    const float nm0 = -mean0 * rstd0, nm1 = -mean1 * rstd1;
    const int st_row = row0 + (lane & 7) + 8 * ((lane >> 3) & 1);
    const uint32_t st_base = sb + SM_KVX + st_row * 256;
    const bool sender = (wg == 1 && w == 3 && rb < 15);
    uint4* halo = &g_halo[(rb * 8 + hg) * 384 + lane];
    if (wg == 0 && w == 3) bar_sync(6, 64);
    uint32_t r[4][2][4];
#pragma unroll
    for (int h = 0; h < 4; h++) {
#pragma unroll
      for (int kv = 0; kv < 2; kv++) {
#pragma unroll
        for (int dh = 0; dh < 2; dh++) {
          const int j = 8 + kv * 8 + 2 * h + dh;
          const float2 c2 = cs[j];
          const float v0 = fmaf(acc[4 * j + 0], rstd0, nm0 * c2.x), v1 = fmaf(acc[4 * j + 1], rstd0, nm0 * c2.y);
          const float v2 = fmaf(acc[4 * j + 2], rstd1, nm1 * c2.x), v3 = fmaf(acc[4 * j + 3], rstd1, nm1 * c2.y);
          r[h][kv][2 * dh] = packbf(v0, v1);
          r[h][kv][2 * dh + 1] = packbf(v2, v3);
        }
      }
      if (sender) {
        st_tagged3(halo + (3 * h) * 32, r[h][0][0], r[h][0][1], r[h][0][2], tag);
        st_tagged3(halo + (3 * h + 1) * 32, r[h][0][3], r[h][1][0], r[h][1][1], tag);
        st_tagged3(halo + (3 * h + 2) * 32, r[h][1][2], r[h][1][3], 0u, tag);
      }
    }
    if (wg == 1 && w == 3) bar_arrive(6, 64);
    if (layer == 1 && threadIdx.x == 224) TS(47);
#pragma unroll
    for (int j = 0; j < 8; j++) cs[j] = lds64f(sb + SM_CS + 4 * (8 * j + 2 * t));
    mbar_wait(bar + 8 * B_QDONE, layer);
#pragma unroll
    for (int h = 0; h < 4; h++) {
#pragma unroll
      for (int kv = 0; kv < 2; kv++) {
        const int chunk = 4 * h + 2 * kv + (lane >> 4);
        stsm4(st_base + (((chunk & 8) | ((chunk ^ st_row) & 7)) << 4), r[h][kv][0], r[h][kv][1], r[h][kv][2], r[h][kv][3]);
      }
      kb[h][4] = r[h][0][0]; kb[h][5] = r[h][0][2]; kb[h][6] = r[h][0][1]; kb[h][7] = r[h][0][3];
      vb[h][4] = movm_t(r[h][1][0]); vb[h][5] = movm_t(r[h][1][1]); vb[h][6] = movm_t(r[h][1][2]); vb[h][7] = movm_t(r[h][1][3]);
    }
    if (layer == 1 && threadIdx.x == 0) TS(45);
#pragma unroll
    for (int h = 0; h < 4; h++) {
#pragma unroll
      for (int dh = 0; dh < 2; dh++) {
        const int j = 2 * h + dh;
        const float2 c2 = cs[j];
        qa[h][2 * dh] = packbf(fmaf(-mean0, c2.x, acc[4 * j + 0]), fmaf(-mean0, c2.y, acc[4 * j + 1]));
        qa[h][2 * dh + 1] = packbf(fmaf(-mean1, c2.x, acc[4 * j + 2]), fmaf(-mean1, c2.y, acc[4 * j + 3]));
      }
    }
  }
  bar_sync(1, 256);
  if (threadIdx.x == 0) TS(2 + layer * 20 + 2);
  {
    const uint32_t own_base = sb + SM_KVX + row0 * 256;
    const int mi = lane >> 3;
    const int r = 8 * (mi >> 1) + (lane & 7), r2 = 8 * (mi & 1) + (lane & 7);
    if (row0 != 0) {
#pragma unroll
      for (int h = 0; h < 4; h++) {
        const int ch = 4 * h + (mi & 1), ch2 = 4 * h + 2 + (mi >> 1);
        ldsm4(&kb[h][0], own_base - 16 * 256 + r * 256 + (((ch & 8) | ((ch ^ r) & 7)) << 4));
        ldsm4t(&vb[h][0], own_base - 16 * 256 + r2 * 256 + (((ch2 & 8) | ((ch2 ^ r2) & 7)) << 4));
      }
    } else if (rb > 0) {
      const uint4* src = &g_halo[((rb - 1) * 8 + hg) * 384 + lane];
      delay<D_HALO>();
      uint4 hv[12];
      int it = 0;
      bool ok;
      do {
        ok = true;
#pragma unroll
        for (int i = 0; i < 12; i++) hv[i] = ld_tagged(src + i * 32);
#pragma unroll
        for (int i = 0; i < 12; i++) ok = ok && hv[i].w == tag;
      } while (!__all_sync(~0u, ok) && ++it < (1 << 20));
      if (lane == 0) mbar_arrive(bar + 8 * B_HF);
#pragma unroll
      for (int h = 0; h < 4; h++) {
        kb[h][0] = hv[3 * h].x; kb[h][1] = hv[3 * h].z; kb[h][2] = hv[3 * h].y; kb[h][3] = hv[3 * h + 1].x;
        vb[h][0] = movm_t(hv[3 * h + 1].y); vb[h][1] = movm_t(hv[3 * h + 1].z);
        vb[h][2] = movm_t(hv[3 * h + 2].x); vb[h][3] = movm_t(hv[3 * h + 2].y);
      }
    } else {
#pragma unroll
      for (int h = 0; h < 4; h++)
#pragma unroll
        for (int k = 0; k < 4; k++) kb[h][k] = vb[h][k] = 0u;
    }
    if (threadIdx.x == 0) TS(2 + layer * 20 + 4);
  }

  const bool first = (rb == 0 && wg == 0 && w == 0);
  const int e = t - (g >> 1);
  const bool par = g & 1, epos = e >= 1;
  const uint32_t pmask = par ? 0xffff0000u : 0x0000ffffu;
  const uint32_t mB0 = epos ? pmask : 0u, mB1 = epos ? 0u : pmask;
  const float cl2 = 0.25f * 1.4426950408889634f;
  const float sc0 = rstd0 * cl2, sc1 = rstd1 * cl2;
  const float NEG = -INFINITY;
  float vA0[4], vB0[4], vA1[4], vB1[4];
#pragma unroll
  for (int h = 0; h < 4; h++) {
    float S[4][4];
#pragma unroll
    for (int j = 0; j < 4; j++) {
      S[j][0] = S[j][1] = S[j][2] = S[j][3] = 0.f;
      mma_bf16(S[j], qa[h], kb[h][2 * j], kb[h][2 * j + 1]);
    }
    vA0[h] = par ? S[1][1] : S[1][0];
    vB0[h] = epos ? (par ? S[0][1] : S[0][0]) : (par ? S[2][1] : S[2][0]);
    vA1[h] = par ? S[2][3] : S[2][2];
    vB1[h] = epos ? (par ? S[1][3] : S[1][2]) : (par ? S[3][3] : S[3][2]);
    if (first) { vA0[h] = NEG; if (epos) { vB0[h] = NEG; vB1[h] = NEG; } }
  }
  float m0[4], m1[4];
#pragma unroll
  for (int h = 0; h < 4; h++) { m0[h] = fmaxf(vA0[h], vB0[h]); m1[h] = fmaxf(vA1[h], vB1[h]); }
#pragma unroll
  for (int o = 1; o <= 2; o <<= 1) {
#pragma unroll
    for (int h = 0; h < 4; h++) {
      m0[h] = fmaxf(m0[h], __shfl_xor_sync(~0u, m0[h], o));
      m1[h] = fmaxf(m1[h], __shfl_xor_sync(~0u, m1[h], o));
    }
  }
  float O0[4][4], O1[4][4], Z[4][4];
#pragma unroll
  for (int h = 0; h < 4; h++) {
    const float mm0 = -m0[h] * sc0, mm1 = -m1[h] * sc1;
    const float pA0 = ex2(fmaf(vA0[h], sc0, mm0)), pB0 = ex2(fmaf(vB0[h], sc0, mm0));
    const float pA1 = ex2(fmaf(vA1[h], sc1, mm1)), pB1 = ex2(fmaf(vB1[h], sc1, mm1));
    const uint32_t hA0 = packbf(pA0, pA0), hB0 = packbf(pB0, pB0), hA1 = packbf(pA1, pA1), hB1 = packbf(pB1, pB1);
    const uint32_t P0[4] = {hB0 & mB0, 0u, hA0 & pmask, hB1 & mB0};
    const uint32_t P1[4] = {hB0 & mB1, hA1 & pmask, 0u, hB1 & mB1};
#pragma unroll
    for (int k = 0; k < 4; k++) O0[h][k] = O1[h][k] = Z[h][k] = 0.f;
    mma_bf16(O0[h], P0, vb[h][0], vb[h][1]); mma_bf16(O1[h], P0, vb[h][2], vb[h][3]); mma_bf16(Z[h], P0, 0x3f803f80u, 0x3f803f80u);
    mma_bf16(O0[h], P1, vb[h][4], vb[h][5]); mma_bf16(O1[h], P1, vb[h][6], vb[h][7]); mma_bf16(Z[h], P1, 0x3f803f80u, 0x3f803f80u);
  }
  const uint32_t ob = sb + SM_OST + wg * 8192;
  const int o_row = 16 * w + (lane & 7) + 8 * ((lane >> 3) & 1);
#pragma unroll
  for (int h = 0; h < 4; h++) {
    const float i0 = rcp_approx(Z[h][0]), i1 = rcp_approx(Z[h][2]);
    const int ch = 2 * h + (lane >> 4);
    stsm4(ob + o_row * 128 + ((ch ^ (o_row & 7)) << 4), packbf(O0[h][0] * i0, O0[h][1] * i0), packbf(O0[h][2] * i1, O0[h][3] * i1),
          packbf(O1[h][0] * i0, O1[h][1] * i0), packbf(O1[h][2] * i1, O1[h][3] * i1));
  }
  if (threadIdx.x == 0) TS(2 + layer * 20 + 5);
  fence_writer();
  bar_sync(2 + wg, 128);
  if (w == 0 && elect_one()) {
    fence_reader();
    tma_st(&p.mapO, hg * 64, rb * 128 + wg * 64, ob);
    bulk_commit();
    mbar_arrive(bar + 8 * B_AD);
    bulk_wait_all();
    red_relaxed(&g_cnt[(C_O + rb) * 32]);
    mbar_arrive(bar + 8 * B_OST);
    if (threadIdx.x == 0) TS(2 + layer * 20 + 6);
  }
}

__device__ __forceinline__ void proj_phase(const Params& p, uint32_t sb, int layer, int rb, int q, int wg, int w) {
  const int lane = opaque_tid() & 31;
  const bool TR = layer != 0;
  const int t = lane & 3;
  const uint32_t bar = sb + SM_BAR;
  const uint32_t rbx = sb + SM_R + wg * 8192;
  uint32_t res[16];
  mbar_wait(bar + 8 * B_RF, layer);
  if (threadIdx.x == 0) TS(2 + layer * 20 + 7);
  if (!TR) {
#pragma unroll
    for (int j = 0; j < 8; j += 2) {
      const int mi = lane >> 3;
      const int row = 16 * w + (lane & 7) + 8 * (mi & 1), ch = j + (mi >> 1);
      ldsm4(&res[2 * j], rbx + row * 128 + ((ch ^ (row & 7)) << 4));
    }
  } else {
#pragma unroll
    for (int j = 0; j < 8; j += 2) {
      const int mi = lane >> 3;
      const int line = 8 * (j + (mi >> 1)) + (lane & 7), pc = 2 * w + (mi & 1);
      ldsm4t(&res[2 * j], rbx + line * 128 + ((pc ^ (line & 7)) << 4));
    }
  }
  bar_sync(2 + wg, 128);
  float acc[32];
#pragma unroll
  for (int i = 0; i < 16; i++) {
    asm volatile("shl.b32 %0, %1, 16;" : "=f"(acc[2 * i]) : "r"(res[i]));
    asm volatile("and.b32 %0, %1, 0xffff0000;" : "=f"(acc[2 * i + 1]) : "r"(res[i]));
  }
  const uint32_t tag = 4 * lds32(sb + SM_EP) + 2 * layer + 2;
#pragma unroll 1
  for (int c = 0; c < 8; c++) {
    if ((c & 1) == 0) mbar_wait(bar + 8 * (B_WOF + (c >> 1)), layer);
    mbar_wait(bar + 8 * (B_OF + c), layer);
    if (c == 0 && threadIdx.x == 0) TS(2 + layer * 20 + 8);
    const uint64_t da = mkdesc(sb + (c < 4 ? SM_X + 65536 + c * 16384 : SM_W + (c - 4) * 16384) + wg * 8192, 16, 1024, 1);
    const uint64_t db = mkdesc(sb + SM_X + c * 8192, 8192, 1024, 1);
    wg_fence();
#pragma unroll
    for (int ks = 0; ks < 4; ks++) wgmma_ss<64, 0, 1>(acc, da + ks * 2, db + ks * 128, 1);
    wg_commit();
  }
  wg_wait<0>();
#pragma unroll
  for (int i = 0; i < 32; i++) asm volatile("" : "+f"(acc[i]) :: "memory");
  if (threadIdx.x == 0) TS(2 + layer * 20 + 9);
  if (lane == 0 && w == 0) mbar_arrive(bar + 8 * B_PDONE);
  {
    float s[4], qq[4];
#pragma unroll
    for (int k = 0; k < 4; k++) { s[k] = acc[k]; qq[k] = acc[k] * acc[k]; }
#pragma unroll
    for (int j = 1; j < 8; j++)
#pragma unroll
      for (int k = 0; k < 4; k++) { s[k] += acc[4 * j + k]; qq[k] = fmaf(acc[4 * j + k], acc[4 * j + k], qq[k]); }
    const float s0 = s[0] + s[1], s1 = s[2] + s[3], q0 = qq[0] + qq[1], q1 = qq[2] + qq[3];
    float sr = ((t & 1) ? s1 : s0) + __shfl_xor_sync(~0u, (t & 1) ? s0 : s1, 1);
    float qr = ((t & 1) ? q1 : q0) + __shfl_xor_sync(~0u, (t & 1) ? q0 : q1, 1);
    sr += __shfl_xor_sync(~0u, sr, 2);
    qr += __shfl_xor_sync(~0u, qr, 2);
    if (t < 2) st_tagged(&g_part[(rb * 8 + q) * 128 + 64 * wg + 16 * w + (lane >> 2) + 8 * t], __float_as_uint(sr), __float_as_uint(qr), tag);
    __syncwarp();
    if (elect_one()) mbar_arrive(bar + 8 * B_PS);
  }
#pragma unroll
  for (int j = 0; j < 8; j += 2) {
    const int mi = lane >> 3;
    const int line = 8 * (j + (mi >> 1)) + (lane & 7), pc = 2 * w + (mi & 1);
    stsm4t(rbx + line * 128 + ((pc ^ (line & 7)) << 4), packbf(acc[4 * j], acc[4 * j + 1]), packbf(acc[4 * j + 2], acc[4 * j + 3]),
           packbf(acc[4 * j + 4], acc[4 * j + 5]), packbf(acc[4 * j + 6], acc[4 * j + 7]));
  }
  fence_writer();
  bar_sync(2 + wg, 128);
  if (w == 0 && elect_one()) {
    fence_reader();
    mbar_wait(bar + 8 * B_ZF, layer);
    fence_async_global();
    tma_st(&p.mapXT, rb * 128 + wg * 64, (2 * layer) * DM + q * 64, rbx);
    bulk_commit();
    if (threadIdx.x == 0) TS(2 + layer * 20 + 10);
    asm volatile("cp.async.bulk.wait_group.read 0;" ::: "memory");
    if (wg == 0) mbar_arrive(bar + 8 * B_RE);
  }
}
__device__ __forceinline__ void proj_stats(int layer, int rb, int q, int lane, uint32_t tag) {
  const int r = 16 * q + (lane & 15);
  const uint4* src = &g_part[(rb * 8 + (lane >> 4) * 4) * 128 + r];
  uint4 v[4];
  bool ok;
  int it = 0;
  do {
    ok = true;
#pragma unroll
    for (int i = 0; i < 4; i++) v[i] = ld_tagged(src + i * 128);
#pragma unroll
    for (int i = 0; i < 4; i++) ok = ok && v[i].y == tag && v[i].w == tag;
    if (++it > (1 << 22)) __trap();
  } while (!__all_sync(~0u, ok));
  float s = (__uint_as_float(v[0].x) + __uint_as_float(v[1].x)) + (__uint_as_float(v[2].x) + __uint_as_float(v[3].x));
  float qq = (__uint_as_float(v[0].z) + __uint_as_float(v[1].z)) + (__uint_as_float(v[2].z) + __uint_as_float(v[3].z));
  s += __shfl_xor_sync(~0u, s, 16);
  qq += __shfl_xor_sync(~0u, qq, 16);
  const float mean = s * (1.f / DM);
  const float rstd = rsqrt_approx(fmaxf(fmaf(qq, 1.f / DM, -mean * mean), 0.f) + 1e-5f), nm = -mean * rstd;
  const float nm1 = __shfl_xor_sync(~0u, nm, 1), rstd1 = __shfl_xor_sync(~0u, rstd, 1);
  if ((lane & 17) == 0)
    st_tagged3((uint4*)g_stats + (layer * 32 + rb * 2 + (r >> 6)) * 32 + ((r & 7) >> 1) * 8 + ((r >> 3) & 7),
               __float_as_uint(nm), __float_as_uint(rstd) | 1u, __float_as_uint(nm1), __float_as_uint(rstd1));
}

#define NA 8
template <bool GB> __host__ __device__ constexpr int grp_n() { return GB ? 17 - NA : NA; }
template <bool GB> __host__ __device__ constexpr int grp_m(int i) { return i == 0 ? (GB ? 1 : 0) : (GB ? NA + i : 1 + i); }
template <bool GB> __device__ __forceinline__ void conv_load(uint32_t* A, uint32_t pe) {
#pragma unroll
  for (int i = 0; i < grp_n<GB>(); i++) {
    A[4 * i + 2] = lds32(pe + 4 * (64 * grp_m<GB>(i) - 8));
    A[4 * i + 0] = lds32(pe + 4 * (64 * grp_m<GB>(i)));
    A[4 * i + 1] = lds32(pe + 4 * (64 * grp_m<GB>(i) + 8));
  }
}
template <bool GB> __device__ __forceinline__ void conv_dup_early(uint32_t* A, uint32_t zero) {
#pragma unroll
  for (int i = 0; i < grp_n<GB>(); i++) asm volatile("or.b32 %0, %1, %2;" : "=r"(A[4 * i + 3]) : "r"(A[4 * i + 0]), "r"(zero));
}
template <bool GB> __device__ __forceinline__ void conv_dup(uint32_t* A) {
#pragma unroll
  for (int i = 0; i < grp_n<GB>(); i++) asm volatile("mov.b32 %0, %1;" : "=r"(A[4 * i + 3]) : "r"(A[4 * i + 0]));
}
template <bool GB, int I0, int I1> __device__ __forceinline__ void conv_mmas(float* acc, const uint32_t* A, uint64_t d) {
  if constexpr (I0 < I1) {
    constexpr int M = grp_m<GB>(I0);
    wgmma_rs<128 - 8 * (M / 2), 0>(acc, A + 4 * I0, d + (uint64_t)(4 * M), M != 0);
    conv_mmas<GB, I0 + 1, I1>(acc, A, d);
  }
}
struct SumAddr { uint32_t l0, l1, se, so; };
__device__ __forceinline__ SumAddr conv_sum_addr(uint32_t sb, int c) {
  const int m = c == 127 ? -1 : c;
  const uint32_t up = m >= 1 ? ((m - 1) & 1) * CV_UH + (127 - ((m - 1) >> 1)) * 16 + 8 : 128 * 16;
  const uint32_t un = ((m + 1) & 1) * CV_UH + (127 - ((m + 1) >> 1)) * 16;
  const int ce = (m + 2) & 127, co = m + 1;
  return {sb + cv_u(0) + ((c & 1) ? un : up), sb + cv_u(0) + ((c & 1) ? up : un),
          sb + cv_s(0) + ((ce >> 3) & 1) * 1024 + (ce >> 4) * 128 + (((ce ^ (ce >> 4)) & 7) << 4),
          sb + cv_s(0) + 2048 + ((co >> 3) & 1) * 1024 + (co >> 4) * 128 + (((co ^ (co >> 4)) & 7) << 4)};
}
__device__ __forceinline__ void conv_sums(const SumAddr& sa, int lc, int c, uint4 own) {
  if (c == 127) own = make_uint4(0, 0, 0, 0);
  const bool odd = c & 1;
  const float2 v0 = lds64f(sa.l0 + lc * 32768), v1 = lds64f(sa.l1 + lc * 32768);
  const uint32_t x[8] = {__float_as_uint(odd ? v1.x : v0.x), __float_as_uint(odd ? v1.y : v0.y), own.x, own.y, own.z, own.w,
                         __float_as_uint(odd ? v0.x : v1.x), __float_as_uint(odd ? v0.y : v1.y)};
  float pv[16];
#pragma unroll
  for (int k = 0; k < 8; k++) { pv[2 * k] = bf_lo(x[k]); pv[2 * k + 1] = bf_hi(x[k]); }
  float sf[8], pf[8], s9[8], s7[8];
  sf[7] = pv[7]; pf[0] = pv[8];
#pragma unroll
  for (int i = 6; i >= 0; i--) sf[i] = sf[i + 1] + pv[i];
#pragma unroll
  for (int i = 1; i < 8; i++) pf[i] = pf[i - 1] + pv[8 + i];
#pragma unroll
  for (int i = 0; i < 8; i++) {
    s9[i] = sf[i] + pf[i];
    s7[i] = i == 0 ? sf[1] : i == 7 ? pf[6] : sf[i + 1] + pf[i - 1];
  }
  uint4 e4 = make_uint4(packbf(s9[0], s9[1]), packbf(s9[2], s9[3]), packbf(s9[4], s9[5]), packbf(s9[6], s9[7]));
  if (c == 126) e4 = make_uint4(0, 0, 0, 0);
  sts128(sa.se + lc * 32768, e4);
  sts128(sa.so + lc * 32768, make_uint4(packbf(s7[0], s7[1]), packbf(s7[2], s7[3]), packbf(s7[4], s7[5]), packbf(s7[6], s7[7])));
}

__device__ __forceinline__ void conv_epi(uint32_t sb, int layer, int cta, int ch, int c0, uint4 x0, uint4 x1) {
  uint4 v[2][4];
  const uint4 xr[2] = {x0, x1};
  mbar_wait(sb + SM_BAR + 8 * (B_P + ch), layer);
#pragma unroll
  for (int u = 0; u < 2; u++) {
    const int c = c0 + 128 * u;
    const uint32_t pb = sb + cv_pb(ch) + (c ^ ((c >> 3) & 1)) * 16;
#pragma unroll
    for (int k = 0; k < 4; k++) v[u][k] = lds128(pb + k * CV_PBW);
  }
#pragma unroll
  for (int u = 0; u < 2; u++) {
    uint4 o;
    o.x = hadd2(xr[u].x, hadd2(hadd2(v[u][0].x, v[u][1].x), hadd2(v[u][2].x, v[u][3].x)));
    o.y = hadd2(xr[u].y, hadd2(hadd2(v[u][0].y, v[u][1].y), hadd2(v[u][2].y, v[u][3].y)));
    o.z = hadd2(xr[u].z, hadd2(hadd2(v[u][0].z, v[u][1].z), hadd2(v[u][2].z, v[u][3].z)));
    o.w = hadd2(xr[u].w, hadd2(hadd2(v[u][0].w, v[u][1].w), hadd2(v[u][2].w, v[u][3].w)));
    if (layer == 0) sts128(sb + cv_s(ch) + (c0 + 128 * u) * 16, o);
    else st_tagged3((uint4*)(g_xT + (size_t)(3 * DM + cv_chan(cta, ch)) * LSEQ) + c0 + 128 * u, o.x, o.y, o.z, o.w);
  }
}
__device__ __forceinline__ void warp_release(uint32_t b) {
  fence_writer();
  __syncwarp();
  if (elect_one()) mbar_arrive(b);
}

__device__ __forceinline__ void conv_prep_load(uint32_t sb, int layer, int cta, int c, uint4 (&xr)[4], uint4 (&st)[4]) {
  mbar_wait(sb + SM_BAR + 8 * B_GB, layer);
  if (threadIdx.x == 0) TS(2 + layer * 20 + 11);
  xr[0] = ld_tagged((const uint4*)(g_xT + (size_t)(2 * layer * DM + cta) * LSEQ) + c);
#pragma unroll
  for (int i = 0; i < 4; i++) st[i] = ld_tagged((const uint4*)g_stats + (layer * 32 + (c >> 3)) * 32 + i * 8 + (c & 7));
}
template <bool HELPER>
__device__ __forceinline__ void conv_prep(uint32_t sb, int layer, int cta, int c, uint4 (&xr)[4], uint4 (&st)[4], uint4 (&un)[4], const SumAddr& sa) {
  const uint32_t bar = sb + SM_BAR;
  const uint4* xin = (const uint4*)(g_xT + (size_t)(2 * layer * DM + cta) * LSEQ) + c;
  for (int it = 0;; it++) {
    const bool okx = __all_sync(~0u, xr[0].x != ~0u);
    const bool oks = __all_sync(~0u, (st[0].y & st[1].y & st[2].y & st[3].y & 1u) != 0);
    if (okx && oks) break;
    if (it > (1 << 22)) __trap();
    if (!okx) xr[0] = ld_tagged(xin);
    if (!oks) {
#pragma unroll
      for (int i = 0; i < 4; i++) st[i] = ld_tagged((const uint4*)g_stats + (layer * 32 + (c >> 3)) * 32 + i * 8 + (c & 7));
    }
  }
  if (threadIdx.x == 0) TS(2 + layer * 20 + 12);
  const int a = c >> 1, h = c & 1;
#pragma unroll
  for (int i = 0; i < 4; i++) {
    if (i == 1) {
#pragma unroll
      for (int j = 1; j < 4; j++) xr[j] = ld_tagged(xin + j * (128 * LSEQ / 8));
      if (HELPER) {
        bar_sync(4, 128);
        conv_sums(sa, 0, c, un[0]);
        fence_async_smem();
        warp_release(bar + 8 * B_S);
        if (layer == 1 && c == 0) TS(46);
        mbar_wait(bar + 8 * B_GB, layer);
      }
      for (int it = 0; !__all_sync(~0u, xr[1].x != ~0u && xr[2].x != ~0u && xr[3].x != ~0u); it++) {
        if (it > (1 << 22)) __trap();
#pragma unroll
        for (int j = 1; j < 4; j++) xr[j] = ld_tagged(xin + j * (128 * LSEQ / 8));
      }
    }
    const uint32_t x[4] = {xr[i].x, xr[i].y, xr[i].z, xr[i].w};
    uint32_t u[4];
#pragma unroll
    for (int k = 0; k < 4; k++)
      u[k] = packbf(fmaf(bf_lo(x[k]), __uint_as_float(st[k].y), __uint_as_float(st[k].x)), fmaf(bf_hi(x[k]), __uint_as_float(st[k].w), __uint_as_float(st[k].z)));
    un[i] = make_uint4(u[0], u[1], u[2], u[3]);
    sts128(sb + cv_u(i) + h * CV_UH + (127 - a) * 16, un[i]);
    warp_release(bar + 8 * (B_U + i));
  }
}
__device__ __forceinline__ void conv_zero(uint32_t sb, int ht) {
  if (ht < 96) {
    const int ch = ht / 24, h2 = (ht / 12) & 1, qq = ht % 12;
    sts128(sb + cv_u(ch) + h2 * CV_UH + (128 + qq) * 16, make_uint4(0, 0, 0, 0));
  }
  if (ht >= 80) {
    const int i = ht - 80, ch = i / 12, q2 = i % 12;
    const int w2 = q2 < 2 ? 1 : q2 < 6 ? 2 : 3, cc = q2 < 2 ? q2 : q2 < 6 ? q2 - 2 : q2 - 6;
    sts128(sb + cv_pb(ch) + w2 * CV_PBW + cc * 16, make_uint4(0, 0, 0, 0));
  }
}

#define LD_AT 2
#define HANDOVER 12
template <int R>
__device__ __forceinline__ void conv_round(uint32_t sb, int layer, int wg, uint32_t* FA, uint32_t* FB, uint32_t pb, uint32_t pe2) {
  const uint32_t bar = sb + SM_BAR;
  const int ch = 2 * R + 1 - wg;
  float acc[64];
  const uint64_t d = mkdesc(sb + cv_u(ch), CV_UH, 128, 0);
  const bool leader = (opaque_tid() & 127) == 0;
  FTS(39);
  if (R == 0) {
    mbar_wait(bar + 8 * (B_U + ch), layer);
    fence_reader();
  }
  if (ch > 0) mbar_wait(bar + 8 * (B_T + ch - 1), layer);
  FTS(41);
  if (ch == 0 && threadIdx.x == 128) TS(2 + layer * 20 + 13);
  wg_fence();
  conv_mmas<false, 0, LD_AT>(acc, FA, d);
  if (R == 1) conv_load<true>(FB, pe2);
  conv_mmas<false, LD_AT, (HANDOVER < NA ? HANDOVER : NA)>(acc, FA, d);
  if (HANDOVER <= NA) mbar_arrive_if(bar + 8 * (B_T + ch), leader);
  conv_mmas<false, (HANDOVER < NA ? HANDOVER : NA), NA>(acc, FA, d);
  wg_commit();
  FTS(51);
  mbar_wait(bar + 8 * (B_S + ch), layer);
  if (R == 1) conv_dup<true>(FB);
  wg_fence();
  conv_mmas<true, 0, (HANDOVER > NA ? HANDOVER - NA : 0)>(acc, FB, d);
  if (HANDOVER > NA) mbar_arrive_if(bar + 8 * (B_T + ch), leader);
  conv_mmas<true, (HANDOVER > NA ? HANDOVER - NA : 0), 17 - NA>(acc, FB, d);
  wgmma_ss<64, 1, 1>(acc, mkdesc(sb + cv_s(ch), 1024, 1024, 1), mkdesc(sb + cv_ft(ch), 256, 16, 0), 1);
  wgmma_ss<64, 1, 1>(acc, mkdesc(sb + cv_s(ch) + 2048, 1024, 1024, 1), mkdesc(sb + cv_ft(ch) + 512, 256, 16, 0), 1);
  wg_commit();
  FTS(61);
  wg_wait<0>();
#pragma unroll
  for (int j = 0; j < 16; j += 2)
    stsm4t(pb + R * 65536 - j * 256, packbf(acc[4 * j], acc[4 * j + 1]), packbf(acc[4 * j + 2], acc[4 * j + 3]),
           packbf(acc[4 * j + 4], acc[4 * j + 5]), packbf(acc[4 * j + 6], acc[4 * j + 7]));
  __syncwarp();
  if (elect_one()) mbar_arrive(bar + 8 * (B_P + ch));
  if (threadIdx.x == 0) TS(2 + layer * 20 + 14 + R);
  FTS(57);
  if (R == 0) {
    mbar_wait(bar + 8 * (B_S + ch + 2), layer);
    fence_reader();
  }
}
__device__ __forceinline__ void conv_phase(const Params& p, uint32_t sb, int layer, int cta) {
  const int tid = opaque_tid();
  const int wg = __shfl_sync(~0u, tid >> 7, 0), w = __shfl_sync(~0u, (tid >> 5) & 3, 0);
  const uint32_t bar = sb + SM_BAR;
  uint32_t FA0[4 * NA], FA1[4 * NA], FB[4 * (17 - NA)];
  const uint32_t pe = sb + cv_pe(1 - wg) + 4 * (16 + 16 * w + ((tid & 31) >> 2) - 2 * (tid & 3));
  mbar_wait(bar + 8 * B_PE, layer);
  conv_load<false>(FA0, pe); conv_load<true>(FB, pe);
  const uint32_t zero = tid >> 10;
  conv_dup_early<false>(FA0, zero); conv_dup_early<true>(FB, zero);
  if (wg == 0) {
    uint4 xr[4], st[4], un[4];
    conv_prep_load(sb, layer, cta, tid + 128, xr, st);
    conv_load<false>(FA1, pe + 65536);
    conv_dup_early<false>(FA1, zero);
    conv_prep<false>(sb, layer, cta, opaque_tid() + 128, xr, st, un, SumAddr());
  } else {
    conv_load<false>(FA1, pe + 65536);
    conv_dup_early<false>(FA1, zero);
  }
  uint32_t pb;
  {
    const int l2 = opaque_tid() & 31, mt = l2 >> 3;
    const int c = 2 * (127 - 8 * (mt >> 1) - (l2 & 7) + w) + (mt & 1);
    pb = sb + cv_pb(1 - wg) + w * CV_PBW + (c ^ ((c >> 3) & 1)) * 16;
  }
  conv_round<0>(sb, layer, wg, FA0, FB, pb, 0);
  conv_round<1>(sb, layer, wg, FA1, FB, pb, pe + 65536);
  if (wg == 1 && layer == 0) mbar_wait(bar + 8 * (B_T + 3), layer);
}

__device__ __forceinline__ void final_phase(const Params& p, uint32_t sb, int cta, int wg, int w) {
  if (wg == 1 && w == 3) return;
  const int lane = opaque_tid() & 31, g = lane >> 2, t = lane & 3;
  const int lc = wg ? w : 3;
  const int pos0 = (cta & 31) * 64, ch0 = 128 * lc + (cta >> 5) * 32;
  const bf16* src = g_xT + (size_t)(3 * DM + ch0 + 8 * (g >> 1) + (g & 1)) * LSEQ + pos0;
  bf16* dst = p.out + (size_t)pos0 * DM + ch0 + 8 * t;
  int it = 0;
  mbar_wait(sb + SM_BAR + 8 * (B_E + lc), 1);
  delay<D_FIN>();
  if (wg == 0) {
    uint2 v[4];
    do {
#pragma unroll
      for (int q = 0; q < 4; q++)
        asm volatile("ld.relaxed.gpu.global.v2.u32 {%0,%1}, [%2];" : "=r"(v[q].x), "=r"(v[q].y) : "l"(src + 2 * q * LSEQ + 16 * w + 4 * t) : "memory");
      if (++it > (1 << 22)) __trap();
    } while (!__all_sync(~0u, v[0].x != ~0u && v[1].x != ~0u && v[2].x != ~0u && v[3].x != ~0u));
    if (threadIdx.x == 0) TS(42);
    dst += (16 * w + 4 * (g >> 1) + (g & 1)) * DM;
    *(uint4*)dst = make_uint4(movm_t(v[0].x), movm_t(v[1].x), movm_t(v[2].x), movm_t(v[3].x));
    *(uint4*)(dst + 2 * DM) = make_uint4(movm_t(v[0].y), movm_t(v[1].y), movm_t(v[2].y), movm_t(v[3].y));
  } else {
    uint4 v[2][4];
    bool ok;
    do {
      ok = true;
#pragma unroll
      for (int h = 0; h < 2; h++)
#pragma unroll
        for (int q = 0; q < 4; q++) v[h][q] = ld_tagged((const uint4*)(src + 2 * q * LSEQ + 32 * h + 8 * t));
#pragma unroll
      for (int h = 0; h < 2; h++)
#pragma unroll
        for (int q = 0; q < 4; q++) ok = ok && v[h][q].x != ~0u;
      if (++it > (1 << 22)) __trap();
    } while (!__all_sync(~0u, ok));
    dst += (8 * (g >> 1) + (g & 1)) * DM;
#pragma unroll
    for (int h = 0; h < 2; h++) {
      *(uint4*)(dst + (32 * h + 0) * DM) = make_uint4(movm_t(v[h][0].x), movm_t(v[h][1].x), movm_t(v[h][2].x), movm_t(v[h][3].x));
      *(uint4*)(dst + (32 * h + 2) * DM) = make_uint4(movm_t(v[h][0].y), movm_t(v[h][1].y), movm_t(v[h][2].y), movm_t(v[h][3].y));
      *(uint4*)(dst + (32 * h + 4) * DM) = make_uint4(movm_t(v[h][0].z), movm_t(v[h][1].z), movm_t(v[h][2].z), movm_t(v[h][3].z));
      *(uint4*)(dst + (32 * h + 6) * DM) = make_uint4(movm_t(v[h][0].w), movm_t(v[h][1].w), movm_t(v[h][2].w), movm_t(v[h][3].w));
    }
  }
  if (threadIdx.x == 0) TS(43);
  if (threadIdx.x == 192) TS(63);
  if (threadIdx.x == 0) LTS(1);
}

struct cplx { float r, i; };
__device__ __forceinline__ cplx cmul(cplx a, cplx b) { return {fmaf(a.r, b.r, -a.i * b.i), fmaf(a.r, b.i, a.i * b.r)}; }
__device__ __forceinline__ cplx csqr(cplx a) { return {fmaf(a.r, a.r, -a.i * a.i), (a.r + a.r) * a.i}; }
__device__ __forceinline__ cplx cexp_l(float ar2, float ai, float l) {
  const float m = ex2(ar2 * l);
  const float x = ai * l;
  return {m * __cosf(x), m * __sinf(x)};
}

__device__ __forceinline__ void colsum_publish(uint32_t sb, int rb, int hg, int ht, uint32_t tag) {
  const int lane = ht & 31, q = lane & 15, h = lane >> 4;
  const uint32_t src = sb + SM_CW + (ht >> 5) * 4096 + h * 128 + (q & 1) * 8;
  float s[4] = {0.f, 0.f, 0.f, 0.f};
#pragma unroll
  for (int r = 0; r < 16; r++) {
    const float2 v = lds64f(src + r * 256 + (((q >> 1) ^ ((2 * r + h) & 7)) << 4));
    s[0] += bf_lo(__float_as_uint(v.x)); s[1] += bf_hi(__float_as_uint(v.x));
    s[2] += bf_lo(__float_as_uint(v.y)); s[3] += bf_hi(__float_as_uint(v.y));
  }
#pragma unroll
  for (int k = 0; k < 4; k++) s[k] += __shfl_xor_sync(~0u, s[k], 16);
  if (h == 0)
    st_tagged3(&g_colsum[(hg * 16 + rb) * 48 + (ht >> 5) * 16 + q], (__float_as_uint(s[0]) & ~7u) | tag, __float_as_uint(s[1]),
               __float_as_uint(s[2]), __float_as_uint(s[3]));
}
__device__ __forceinline__ void colsum_gather(uint32_t sb, int hg, int ht, uint32_t tag) {
  const int lane = ht & 31, rec = (ht >> 5) * 16 + (lane & 15);
  const uint4* src = &g_colsum[(hg * 16 + (lane >> 4) * 8) * 48 + rec];
  uint4 v[8];
  bool ok;
  int it = 0;
  do {
    ok = true;
#pragma unroll
    for (int i = 0; i < 8; i++) v[i] = ld_tagged(src + i * 48);
#pragma unroll
    for (int i = 0; i < 8; i++) ok = ok && (v[i].x & 7u) == tag;
    if (++it > (1 << 22)) __trap();
  } while (!__all_sync(~0u, ok));
  float s[4] = {0.f, 0.f, 0.f, 0.f};
#pragma unroll
  for (int i = 0; i < 8; i++) {
    s[0] += __uint_as_float(v[i].x & ~7u); s[1] += __uint_as_float(v[i].y); s[2] += __uint_as_float(v[i].z); s[3] += __uint_as_float(v[i].w);
  }
#pragma unroll
  for (int k = 0; k < 4; k++) s[k] += __shfl_xor_sync(~0u, s[k], 16);
  if (lane < 16) sts128f(sb + SM_CS + rec * 16, s[0], s[1], s[2], s[3]);
}

__device__ __forceinline__ uint32_t packh(float lo, float hi) { uint32_t r; asm("cvt.rn.f16x2.f32 %0, %1, %2;" : "=r"(r) : "f"(hi), "f"(lo)); return r; }
__device__ __forceinline__ void mma_f16(float* d, uint32_t a0, uint32_t a1, uint32_t a2, uint32_t a3, uint32_t b0, uint32_t b1) {
  asm volatile("mma.sync.aligned.m16n8k16.row.col.f32.f16.f16.f32 {%0,%1,%2,%3}, {%4,%5,%6,%7}, {%8,%9}, {%0,%1,%2,%3};"
      : "+f"(d[0]), "+f"(d[1]), "+f"(d[2]), "+f"(d[3]) : "r"(a0), "r"(a1), "r"(a2), "r"(a3), "r"(b0), "r"(b1));
}
struct HSeed { uint32_t r, i; };
__device__ __forceinline__ HSeed hseed(cplx s) { return {packh(s.r, s.r), packh(s.i, s.i)}; }
__device__ __forceinline__ void hcmul(uint32_t& o_r, uint32_t& o_i, uint32_t br, uint32_t bi, HSeed s) {
  asm("{\n.reg .b32 t, u;\nmul.rn.f16x2 t, %3, %5;\nneg.f16x2 t, t;\nmul.rn.f16x2 u, %3, %4;\nfma.rn.f16x2 %0, %2, %4, t;\nfma.rn.f16x2 %1, %2, %5, u;\n}"
      : "=&r"(o_r), "=&r"(o_i) : "r"(br), "r"(bi), "r"(s.r), "r"(s.i));
}
struct HTile { uint32_t r[4], i[4]; };
__device__ __forceinline__ void tile_set(HTile& t, int k, cplx a, cplx b) { t.r[k] = packh(a.r, b.r); t.i[k] = packh(a.i, b.i); }
__device__ __forceinline__ void tile_upper(HTile& t, HSeed s) { hcmul(t.r[2], t.i[2], t.r[0], t.i[0], s); hcmul(t.r[3], t.i[3], t.r[1], t.i[1], s); }
__device__ __forceinline__ HTile tile_shift(const HTile& t, HSeed s) {
  HTile o;
#pragma unroll
  for (int k = 0; k < 4; k++) hcmul(o.r[k], o.i[k], t.r[k], t.i[k], s);
  return o;
}
__device__ __forceinline__ void tile_put(const HTile& t, uint32_t a) {
  sts128(a, make_uint4(t.r[0], t.r[1], t.r[2], t.r[3]));
  sts128(a + 512, make_uint4(t.i[0], t.i[1], t.i[2], t.i[3]));
}
__device__ __forceinline__ HTile tile_get(uint32_t a) { HTile o; ldsm4t(o.r, a); ldsm4t(o.i, a + 512); return o; }
__device__ __forceinline__ void tile_mma(float* T, const HTile& a0, const HTile& a1, const HTile& b) {
  mma_f16(T, a0.r[0], a0.r[1], a0.r[2], a0.r[3], b.r[0], b.r[1]);
  mma_f16(T, a0.i[0], a0.i[1], a0.i[2], a0.i[3], b.i[0], b.i[1]);
  mma_f16(T, a1.r[0], a1.r[1], a1.r[2], a1.r[3], b.r[2], b.r[3]);
  mma_f16(T, a1.i[0], a1.i[1], a1.i[2], a1.i[3], b.i[2], b.i[3]);
}
__device__ __forceinline__ void tile_mma2(float* T, float* U, const HTile& a0, const HTile& a1, const HTile& b, const HTile& c) {
  mma_f16(T, a0.r[0], a0.r[1], a0.r[2], a0.r[3], b.r[0], b.r[1]);
  mma_f16(U, a0.r[0], a0.r[1], a0.r[2], a0.r[3], c.r[0], c.r[1]);
  mma_f16(T, a0.i[0], a0.i[1], a0.i[2], a0.i[3], b.i[0], b.i[1]);
  mma_f16(U, a0.i[0], a0.i[1], a0.i[2], a0.i[3], c.i[0], c.i[1]);
  mma_f16(T, a1.r[0], a1.r[1], a1.r[2], a1.r[3], b.r[2], b.r[3]);
  mma_f16(U, a1.r[0], a1.r[1], a1.r[2], a1.r[3], c.r[2], c.r[3]);
  mma_f16(T, a1.i[0], a1.i[1], a1.i[2], a1.i[3], b.i[2], b.i[3]);
  mma_f16(U, a1.i[0], a1.i[1], a1.i[2], a1.i[3], c.i[2], c.i[3]);
}
__device__ __forceinline__ void kgen_unit(uint32_t tab, uint32_t taba, float ar2, float ai, cplx c, float (&T)[5][4]) {
  const cplx z1 = cexp_l(ar2, ai, 1.f), z16 = cexp_l(ar2, ai, 16.f), z256 = cexp_l(ar2, ai, 256.f);
  HTile a0, a1, b0, b1;
  {
    const cplx y1 = {z16.r, -z16.i}, y2 = csqr(y1), y3 = cmul(y2, y1), y4 = csqr(y2), y5 = cmul(y4, y1), y6 = csqr(y3), y7 = cmul(y4, y3);
    HTile t;
    tile_set(t, 0, {1.f, 0.f}, y1); tile_set(t, 1, y2, y3); tile_set(t, 2, y4, y5); tile_set(t, 3, y6, y7);
    const HTile u = tile_shift(t, hseed(csqr(y4)));
    __syncwarp();
    tile_put(t, tab); tile_put(u, tab + 1024);
    __syncwarp();
    a0 = tile_get(taba); a1 = tile_get(taba + 256);
  }
  const cplx z2 = csqr(z1), z4 = csqr(z2), z8 = csqr(z4);
  const HSeed h8 = hseed(z8);
  const cplx d = cmul(c, z256), e = cmul(d, z256);
  {
    const cplx z512 = csqr(z256), f = cmul(e, z512), f8 = cmul(f, z8), f16 = cmul(f, z16), e4 = cmul(e, z4);
    HTile t, u;
    tile_set(t, 0, e4, cmul(e, z8)); tile_set(t, 1, cmul(e4, z8), cmul(e, z16));
    tile_upper(t, hseed(z256));
    tile_set(u, 0, f8, f16); tile_set(u, 1, cmul(f8, z256), cmul(f16, z256));
    tile_upper(u, hseed(z512));
    __syncwarp();
    tile_put(t, tab); tile_put(u, tab + 1024);
    __syncwarp();
    b0 = tile_get(tab); b1 = tile_get(tab + 1024);
  }
  {
    const cplx d2 = cmul(d, z2), d4 = cmul(d, z4);
    HTile t;
    tile_set(t, 0, d2, d4); tile_set(t, 1, cmul(d2, z4), cmul(d, z8));
    tile_upper(t, h8);
    __syncwarp();
    tile_put(t, tab);
    __syncwarp();
    tile_mma2(T[3], T[4], a0, a1, b0, b1);
    b0 = tile_get(tab);
  }
  {
    const cplx c1 = cmul(c, z1), c2 = cmul(c, z2), c3 = cmul(c1, z2), c4 = cmul(c, z4);
    HTile t;
    tile_set(t, 0, c1, c2); tile_set(t, 1, c3, c4); tile_set(t, 2, cmul(c1, z4), cmul(c2, z4)); tile_set(t, 3, cmul(c3, z4), cmul(c4, z4));
    const HTile u = tile_shift(t, h8);
    __syncwarp();
    tile_put(t, tab); tile_put(u, tab + 1024);
    __syncwarp();
    tile_mma(T[2], a0, a1, b0);
    b0 = tile_get(tab); b1 = tile_get(tab + 1024);
    tile_mma2(T[0], T[1], a0, a1, b0, b1);
  }
}
struct ModeIn { uint2 ar, ai, br, bi, cr, ci; };
__device__ __forceinline__ ModeIn load_modes(const Params& p, int idx) {
  return {*(const uint2*)(p.a_re + idx), *(const uint2*)(p.a_im + idx), *(const uint2*)(p.b_re + idx),
          *(const uint2*)(p.b_im + idx), *(const uint2*)(p.c_re + idx), *(const uint2*)(p.c_im + idx)};
}
__device__ __forceinline__ float bf_el(uint2 v, int k) { const uint32_t x = (k & 2) ? v.y : v.x; return (k & 1) ? bf_hi(x) : bf_lo(x); }
struct KGen { float4 cur; float T[5][4]; };
__device__ __forceinline__ uint32_t kgen_slot(uint32_t sb, int ht, int u) {
  return sb + (u < 3 ? SM_KC + (ht >> 5) * (KC_STRIDE * 2) + (u - 1) * 512 + (ht & 31) * 16 + 16 : SM_HALO + 1024 + ht * 16);
}
__device__ __forceinline__ void kgen_setup(KGen& s, uint32_t sb, int cta, int ht, const ModeIn& in, bf16 logdt, bf16 dskip) {
  const float dt = __bfloat162float(__float2bfloat16_rn(expf(__bfloat162float(logdt))));
  float mx = 0.f, k0 = 0.f, ar2[4];
  cplx c[4];
#pragma unroll
  for (int k = 0; k < 4; k++) {
    ar2[k] = (dt * bf_el(in.ar, k)) * 1.4426950408889634f;
    c[k] = cmul({bf_el(in.cr, k), bf_el(in.ci, k)}, {dt * bf_el(in.br, k), dt * bf_el(in.bi, k)});
    k0 += c[k].r;
    mx = fmaxf(mx, fmaxf(fabsf(c[k].r), fabsf(c[k].i)) * ex2(fmaxf(ar2[k] * 2048.f, 0.f)));
  }
  const int ex = min(max(267 - (int)(__reduce_max_sync(~0u, __float_as_uint(mx)) >> 23), 1), 253);
  const float sc = __uint_as_float(ex << 23);
#pragma unroll
  for (int o = 16; o > 0; o >>= 1) k0 += __shfl_xor_sync(~0u, k0, o);
  if ((ht & 31) == 0) {
    const uint32_t kc = sb + SM_KC + (ht >> 5) * (KC_STRIDE * 2);
    sts16(kc, __bfloat16_as_ushort(__float2bfloat16_rn(k0 + __bfloat162float(dskip))));
    sts16(kc + 641 * 2, 0);
    sts32f(kc + 644 * 2, __uint_as_float((254 - ex) << 23));
  }
  s.cur = make_float4(ar2[0], dt * bf_el(in.ai, 0), c[0].r * sc, c[0].i * sc);
#pragma unroll
  for (int k = 1; k < 4; k++) sts128f(kgen_slot(sb, ht, k), ar2[k], dt * bf_el(in.ai, k), c[k].r * sc, c[k].i * sc);
#pragma unroll
  for (int i = 0; i < 5; i++) s.T[i][0] = s.T[i][1] = s.T[i][2] = s.T[i][3] = 0.f;
}
__device__ __forceinline__ void kgen_finish(KGen& s, uint32_t sb, int cta, int ht) {
  const int w = ht >> 5, lane = ht & 31, g = lane >> 2, t = lane & 3;
  const uint32_t kc = sb + SM_KC + w * KC_STRIDE * 2;
  __syncwarp();
  const float inv = __uint_as_float(lds32(kc + 644 * 2));
  auto put = [&](int idx, float v) {
    sts16(kc + idx * 2, __bfloat16_as_ushort(__float2bfloat16_rn(v)));
  };
#pragma unroll
  for (int hi = 0; hi < 2; hi++)
#pragma unroll
    for (int lo = 0; lo < 2; lo++) {
      const int i = g + 8 * hi, j = 2 * t + lo, e = 2 * hi + lo;
      put(16 * i + 1 + j, s.T[0][e] * inv);
      put(16 * i + 9 + j, s.T[1][e] * inv);
      put(257 + 8 * i + j, s.T[2][e] * inv);
      put(385 + 4 * i + (j & 3) + 64 * (j >> 2), s.T[3][e] * inv);
      put(513 + 2 * i + lo + 32 * t, s.T[4][e] * inv);
    }
}

__device__ __forceinline__ void expand_taps(uint32_t sb, int ht) {
  const int ch = ht >> 5, lane = ht & 31;
  const uint32_t kc = sb + SM_KC + ch * KC_STRIDE * 2;
  const uint32_t dst0 = sb + cv_pe(ch);
  auto put = [&](int G, uint32_t v0, uint32_t v1, uint32_t v2, uint32_t v3, uint32_t v4, uint32_t v5, uint32_t v6, uint32_t v7, uint32_t v8) {
    const uint32_t dst = dst0 + G * 32;
    sts128(dst, make_uint4(v1 | (v0 << 16), v2 | (v1 << 16), v3 | (v2 << 16), v4 | (v3 << 16)));
    sts128(dst + 16, make_uint4(v5 | (v4 << 16), v6 | (v5 << 16), v7 | (v6 << 16), v8 | (v7 << 16)));
  };
  {
    const uint4 q = lds128(kc + lane * 16);
    const uint32_t pv = lane ? lds16(kc + lane * 16 - 2) : 0u;
    const uint32_t dst = dst0 + (lane + 2) * 32;
    sts128(dst, make_uint4(__byte_perm(q.x, pv, 0x5410), __byte_perm(q.x, q.x, 0x1032), __byte_perm(q.y, q.x, 0x7610), __byte_perm(q.y, q.y, 0x1032)));
    sts128(dst + 16, make_uint4(__byte_perm(q.z, q.y, 0x7610), __byte_perm(q.z, q.z, 0x1032), __byte_perm(q.w, q.z, 0x7610), __byte_perm(q.w, q.w, 0x1032)));
    if (lane < 4) sts128(dst0 + lane * 16, make_uint4(0, 0, 0, 0));
  }
  uint32_t a[5], b[2][3], fv[4];
  {
    const uint32_t s1 = kc + 2 * (256 + 4 * lane);
#pragma unroll
    for (int k = 0; k < 5; k++) a[k] = lds16(s1 + 2 * k);
#pragma unroll
    for (int u = 0; u < 2; u++) {
      const uint32_t s2 = kc + 2 * (384 + 2 * (lane + 32 * u));
#pragma unroll
      for (int k = 0; k < 3; k++) b[u][k] = lds16(s2 + 2 * k);
    }
#pragma unroll
    for (int k = 0; k < 4; k++) fv[k] = lds16(kc + 2 * (640 - 4 * lane - k));
  }
  const uint32_t k255 = lds16(kc + 2 * 255), k1024 = lds16(kc + 2 * 512);
  put(34 + lane, lane == 0 ? k255 : a[0], a[0], a[0], a[1], a[2], a[2], a[2], a[3], a[4]);
#pragma unroll
  for (int u = 0; u < 2; u++) put(66 + lane + 32 * u, b[u][0], b[u][0], b[u][0], b[u][0], b[u][1], b[u][1], b[u][1], b[u][2], b[u][2]);
  if (lane < 10) {
    const uint32_t v = lane == 0 ? k1024 : 0u;
    put(130 + lane, v, v, v, v, v, v, 0u, 0u, 0u);
  }
  const uint32_t ft = sb + cv_ft(ch) + 4 * lane;
#pragma unroll
  for (int ty = 0; ty < 2; ty++) {
    const uint32_t v = fv[ty] | (fv[ty + 2] << 16);
    sts32f(ft + ty * 512, __uint_as_float(v));
    sts32f(ft + ty * 512 + 128, 0.f);
    sts32f(ft + ty * 512 + 256 + (lane < 2 ? 120 : -8), __uint_as_float(lane < 2 ? 0u : v));
    sts32f(ft + ty * 512 + 384, 0.f);
  }
}

template <bool SMID> __device__ __forceinline__ int role_id() {
  uint32_t v;
  if (!SMID) { asm volatile("mov.u32 %0, %%ctaid.x;" : "=r"(v)); return v; }
  asm volatile("mov.u32 %0, %%smid;" : "=r"(v));
  const int tp = v >> 1, q = ((tp - 32) * 37) >> 8;
  const int r = tp < 32 ? (tp & 7) * 8 + (tp >> 3) : tp < 60 ? (tp - 31 - 7 * q) * 8 + 4 + q : tp < 62 ? tp + 4 : tp - 58;
  return __shfl_sync(~0u, 2 * r + (v & 1), 0);
}
__device__ __forceinline__ int role_rb(int cta) { return ((cta >> 4) & 3) * 4 + ((cta >> 2) & 3); }
__device__ __forceinline__ int role_hg(int cta) { return (cta >> 6) * 4 + (cta & 3); }
__device__ __forceinline__ int role_rb2(int cta) { return cta >> 3; }
__device__ __forceinline__ int role_q2(int cta) { return cta & 7; }

template <bool SMID> __global__ void __launch_bounds__(NTHREADS, 1) fused_kernel(const __grid_constant__ Params p) {
  extern __shared__ __align__(1024) uint8_t smem[];
  const uint32_t sb = s32(smem);
  const int tid = threadIdx.x, lane = tid & 31;
  const int warp = __shfl_sync(~0u, tid >> 5, 0);
  constexpr unsigned NARR = SMID ? 132 : NCTA;
  const uint32_t bar = sb + SM_BAR;
  if (tid == 0) TS(0);
  const int cta0 = role_id<SMID>();
  if (warp == 0 && (!SMID || cta0 < NCTA) && elect_one()) {
    const int rb = role_rb(cta0), hg = role_hg(cta0);
    mbar_init(bar + 8 * B_XF, 1); mbar_init(bar + 8 * B_KVF, 1);
    fence_async_smem();
#pragma unroll
    for (int c = 0; c < 8; c++) {
      mbar_expect(bar + 8 * (B_XF + c), 16384);
      tma_ld(sb + SM_X + c * 16384, &p.mapX128, c * 64, rb * 128, bar + 8 * (B_XF + c));
      if (c < 3) {
        mbar_expect(bar + 8 * (B_KVF + c), 24576);
        tma_ld3(sb + SM_W + c * 24576, &p.mapW3, hg * 64, c * 64, 0, bar + 8 * (B_KVF + c));
      }
      if (c == 0) {
#pragma unroll
        for (int i = 1; i < 8; i++) mbar_init(bar + 8 * (B_XF + i), 1);
        mbar_init(bar + 8 * (B_KVF + 1), 1); mbar_init(bar + 8 * (B_KVF + 2), 1); mbar_init(bar + 8 * B_CW, 1);
        fence_async_smem();
      }
      if (c == PF_AT) {
        mbar_expect(bar + 8 * B_CW, 12288);
        tma_ld3(sb + SM_CW, &p.mapW3h, hg * 64, rb * 32, 0, bar + 8 * B_CW);
      }
    }
    TS(56);
  }
  if (SMID && cta0 >= NCTA) {
    if (tid == 0) spin_until(&g_cnt[C_CS * 32], (atomicAdd(&g_cnt[C_CS * 32], 1u) / NARR + 1) * NARR);
    return;
  }
  if (warp >= 1 && warp < 5 && elect_one()) {
#pragma unroll
    for (int q = 0; q < 4; q++) {
      if (warp == q + 1) {
#pragma unroll
        for (int i = 17 * q; i < 17 * q + 17; i++) {
          if (i < B_KVF + 3 || i == B_CW) continue;
          int cnt = 1;
          if ((i >= B_KVE && i < B_KVE + 5) || i == B_QDONE || i == B_PDONE || i == B_OST || i == B_AD) cnt = 2;
          if ((i >= B_U && i < B_U + 4) || i == B_PS) cnt = 8;
          if ((i >= B_S && i < B_S + 4) || (i >= B_E && i < B_E + 4) || i >= B_P || i == B_PE || i == B_STF) cnt = 4;
          mbar_init(bar + 8 * i, cnt);
        }
      }
    }
    fence_async_smem();
  }

  if (warp < 8) {
    bar_sync(0, NTHREADS);
    if (tid == 0) TS(1);
    asm volatile("setmaxnreg.inc.sync.aligned.u32 %0;" ::"n"(R_CONS));
    const int cw = __shfl_sync(~0u, opaque_tid() >> 5, 0);
    const int wg = cw >> 2, w = cw & 3;
    const int cta = role_id<SMID>();
    if (tid == 0) TS(54);
#pragma unroll 1
    for (int layer = 0; layer < 2; layer++) {
      attn_phase(p, sb, layer, role_rb(cta), role_hg(cta), wg, w);
      if (p.stop == 1 + 3 * layer) return;
      proj_phase(p, sb, layer, role_rb2(cta), role_q2(cta), wg, w);
      if (p.stop == 2 + 3 * layer) return;
      conv_phase(p, sb, layer, cta);
      if (p.stop == 3 + 3 * layer) return;
    }
    final_phase(p, sb, cta, wg, w);
  } else if (warp < 12) {
    asm volatile("setmaxnreg.dec.sync.aligned.u32 %0;" ::"n"(R_HELP));
    const int ht = tid - 256;
    const int cta = role_id<SMID>(), rb = role_rb(cta), hg = role_hg(cta);
    unsigned ep0 = 0;
    if (ht == 0) ep0 = ld_relaxed(&g_cnt[C_CS * 32]);
    bar_sync(0, NTHREADS);
    if (ht == 0) {
      asm volatile("st.shared.u32 [%0], %1;" ::"r"(sb + SM_EP), "r"(ep0 / NARR) : "memory");
      mbar_arrive(bar + 8 * B_EP);
    }
    mbar_wait(bar + 8 * B_EP, 0);
    const uint32_t cs_tag = lds32(sb + SM_EP) % 7 + 1;
    if (ht < 96) {
      mbar_wait(bar + 8 * B_CW, 0);
      colsum_publish(sb, rb, hg, ht, cs_tag);
    }
    if (ht == 0) TS(50);
    stats_publish(sb, 0, rb, hg, opaque_tid() - 256, 4 * lds32(sb + SM_EP) + 1);
    {
      KGen kg;
      const uint32_t tab0 = sb + ((ht >> 5) < 2 ? SM_T : SM_T2 - 4096) + (ht >> 5) * 2048;
      const uint32_t tab = tab0 + (ht & 31) * 16, taba = tab0 + ((ht >> 3) & 1) * 1024 + (((ht >> 1) & 8) + (ht & 7)) * 16;
      mbar_wait(bar + 8 * (B_KVF + CS_AT), 0);
      if (ht < 96) colsum_gather(sb, hg, ht, cs_tag);
      stats_gather(sb, rb, opaque_tid() - 256, 4 * lds32(sb + SM_EP) + 1);
      if (ht == 0) TS(40);
      const int chn = cv_chan(cta, ht >> 5);
      kgen_setup(kg, sb, cta, ht, load_modes(p, chn * 128 + (ht & 31) * 4), p.log_dt[chn], p.dskip[chn]);
#pragma unroll 1
      for (int u = 0; u < 4; u++) {
        if (u == KG_PRE) {
          KTS(39);
          mbar_wait(bar + 8 * B_AD, 0);
          KTS(41);
        }
        if (u == 3) mbar_wait(bar + 8 * (EXP_LATE ? B_PS : B_PDONE), 0);
        kgen_unit(tab, taba, kg.cur.x, kg.cur.y, {kg.cur.z, kg.cur.w}, kg.T);
        kg.cur = lds128f(kgen_slot(sb, opaque_tid() - 256, u + 1));
      }
      kgen_finish(kg, sb, cta, opaque_tid() - 256);
    }
    KTS(51);
    bar_sync(4, 128);
#pragma unroll 1
    for (int layer = 0; layer < 2; layer++) {
      if (p.stop <= 1 + 3 * layer) return;
      mbar_wait(bar + 8 * (EXP_LATE ? B_PS : B_PDONE), layer);
      expand_taps(sb, opaque_tid() - 256);
      conv_zero(sb, opaque_tid() - 256);
      if (ht == 0) TS(52 + layer);
      warp_release(bar + 8 * B_PE);
      if (p.stop <= 2 + 3 * layer) return;
      {
        uint4 xr[4], st[4], un[4];
        const int c = opaque_tid() - 256;
        const SumAddr sa = conv_sum_addr(sb, c);
        conv_prep_load(sb, layer, cta, c, xr, st);
        conv_prep<true>(sb, layer, cta, c, xr, st, un, sa);
        if (layer == 1 && ht == 0) TS(62);
        bar_sync(4, 128);
        conv_sums(sa, 1, c, un[1]);
        fence_async_smem();
        warp_release(bar + 8 * (B_S + 1));
        conv_sums(sa, 2, c, un[2]);
        mbar_wait(bar + 8 * (B_U + 3), layer);
        warp_release(bar + 8 * (B_S + 2));
        const bf16* xup = g_xT + (size_t)(2 * layer * DM + cta) * LSEQ + (c + 128) * 8;
        st[0] = ldcg128(xup);
        conv_sums(sa, 3, c, un[3]);
        warp_release(bar + 8 * (B_S + 3));
#pragma unroll
        for (int lc = 0; lc < 4; lc++) {
          if (lc < 3) st[lc + 1] = ldcg128(xup + (lc + 1) * 128 * LSEQ);
          conv_epi(sb, layer, cta, lc, c, xr[lc], st[lc]);
          warp_release(bar + 8 * (B_E + lc));
          if (layer == 1 && lc == 3 && ht == 0) TS(38);
        }
      }
      if (layer == 0 && p.stop > 3) {
        const int c1 = role_id<SMID>();
        stats_publish(sb, 1, role_rb(c1), role_hg(c1), opaque_tid() - 256, 4 * lds32(sb + SM_EP) + 3);
        mbar_wait(bar + 8 * (B_XF + 7), 1);
        mbar_wait(bar + 8 * (B_KVF + ST_AT), 1);
        stats_gather(sb, role_rb(c1), opaque_tid() - 256, 4 * lds32(sb + SM_EP) + 3);
        if (ht == 0) TS(25);
      }
    }
  } else {
    asm volatile("setmaxnreg.dec.sync.aligned.u32 %0;" ::"n"(512 - 2 * R_CONS - R_HELP));
    const int cta = role_id<SMID>(), rb = role_rb(cta), hg = role_hg(cta), rb2 = role_rb2(cta), q2 = role_q2(cta);
    bar_sync(0, NTHREADS);
    if (warp == 12) {
      if (elect_one()) {
        unsigned epoch = 0;
#pragma unroll 1
        for (int layer = 0; layer < 2; layer++) {
          auto ld_w = [&](int c, int slot) {
            const uint32_t b = bar + 8 * (B_KVF + c);
            mbar_expect(b, 24576);
            tma_ld3(sb + SM_W + slot * 24576, &p.mapW3, hg * 64, c * 64, 0, b);
          };
          if (layer == 0) {
            TS(55);
            mbar_wait(bar + 8 * (B_KVF + 2), 0);
            if (rb2 < 4) tma_prefetch2(&p.mapWo128, q2 * 64, rb2 * 128);
            asm volatile("prefetch.tensormap [%0];" ::"l"(&p.mapO) : "memory");
            asm volatile("prefetch.tensormap [%0];" ::"l"(&p.mapO128) : "memory");
            asm volatile("prefetch.tensormap [%0];" ::"l"(&p.mapXT) : "memory");
            asm volatile("prefetch.tensormap [%0];" ::"l"(&p.mapXT3) : "memory");
            mbar_wait(bar + 8 * B_EP, 0);
            epoch = lds32(sb + SM_EP);
          } else {
            mbar_wait(bar + 8 * B_PDONE, 0);
            ld_w(0, 0); ld_w(1, 1);
            mbar_wait(bar + 8 * (W2_LATE ? B_U : B_RE), 0);
            ld_w(2, 2);
          }
          {
            int slot = 0;
#pragma unroll 1
            for (int c = 3; c < 8; c++) {
              mbar_wait(bar + 8 * (B_KVE + c - 3), layer);
              ld_w(c, slot);
              slot = slot == 2 ? 0 : slot + 1;
            }
          }
          if (p.stop <= 1 + 3 * layer) return;
          mbar_wait(bar + 8 * B_QDONE, layer);
          if (rb > 0) mbar_wait(bar + 8 * B_HF, layer);
#pragma unroll 1
          for (int c = 0; c < 4; c++) {
            const uint32_t b = bar + 8 * (B_WOF + c);
            mbar_expect(b, 16384);
            tma_ld(sb + SM_X + c * 16384, &p.mapWo128, q2 * 64, c * 128, b);
          }
          {
            const uint32_t b = bar + 8 * B_RF;
            mbar_expect(b, 16384);
            if (layer == 0) tma_ld(sb + SM_R, &p.mapX128, q2 * 64, rb2 * 128, b);
            else tma_ld3(sb + SM_R, &p.mapXT3, 0, DM + q2 * 64, rb2 * 2, b);
          }
          spin_until(&g_cnt[(C_O + rb2) * 32], (2 * epoch + layer + 1) * 16);
          mbar_wait(bar + 8 * B_OST, layer);
          fence_async_global();
#pragma unroll 1
          for (int c = 0; c < 8; c++) {
            const uint32_t b = bar + 8 * (B_OF + c);
            mbar_expect(b, 16384);
            tma_ld(sb + (c < 4 ? SM_X + 65536 + c * 16384 : SM_W + (c - 4) * 16384), &p.mapO128, c * 64, rb2 * 128, b);
          }
          if (p.stop <= 3 + 3 * layer) return;
        }
      }
    } else if (warp == 13) {
      if (elect_one() && p.stop > 3) {
        mbar_wait(bar + 8 * B_GB, 0);
        const unsigned target = (lds32(sb + SM_EP) + 1) * NCTA;
        auto ld_x = [&](int c) {
          mbar_expect(bar + 8 * (B_XF + c), 16384);
          tma_ld3(sb + SM_X + c * 16384, &p.mapXT3, 0, DM + c * 64, rb * 2, bar + 8 * (B_XF + c));
        };
        int done = 0, it = 0;
        while (done < 4) {
          const uint4 v = ld_tagged((const uint4*)&g_cnt[C_G1 * 32]);
          const int n = (int)(v.x - target) < 0 ? 0 : (int)(v.y - target) < 0 ? 1 : (int)(v.z - target) < 0 ? 2 : (int)(v.w - target) < 0 ? 3 : 4;
          if (++it > (1 << 23)) __trap();
          if (n == done) continue;
          if (n == 4) TS(44);
          fence_async_global();
          fence_async_smem();
          const bool own_first = done > 0 && hg >= 2 * done && hg < 2 * n;
          if (own_first) ld_x(hg);
#pragma unroll 1
          for (int c = 2 * done; c < 2 * n; c++)
            if (!own_first || c != hg) ld_x(c);
          done = n;
        }
      }
    } else if (warp == 15) {
      mbar_wait(bar + 8 * B_EP, 0);
      const unsigned epoch = lds32(sb + SM_EP);
#pragma unroll 1
      for (int layer = 0; layer < 2; layer++) {
#pragma unroll 1
        for (int i = 0; i < 6; i++) {
          mbar_wait(bar + 8 * (B_KVF + (FILL_AT + i < 7 ? FILL_AT + i : 7)), layer);
          uint4* dst = (uint4*)(g_xT + (size_t)(i < 4 ? 2 * layer * DM + cv_chan(cta, i) : 3 * DM + cv_chan(cta, 2 * layer + i - 4)) * LSEQ) + lane;
#pragma unroll
          for (int k = 0; k < 8; k++) dst[32 * k] = make_uint4(~0u, ~0u, ~0u, ~0u);
        }
        if (lane < 8) ((uint4*)g_stats)[layer * 1024 + cta * 8 + lane] = make_uint4(0, 0, 0, 0);
        __syncwarp();
        if (elect_one()) {
          red_release(&g_cnt[C_CS * 32 + layer]);
          spin_until(&g_cnt[C_CS * 32 + layer], (epoch + 1) * (layer ? NCTA : NARR));
          mbar_arrive(bar + 8 * B_ZF);
          if (layer == 0 && p.stop > 2) {
#pragma unroll 1
            for (int lc = 0; lc < 4; lc++) {
              mbar_wait(bar + 8 * (B_E + lc), 0);
              fence_reader();
              bulk_st(g_xT + (size_t)(DM + cv_chan(cta, lc)) * LSEQ, sb + cv_s(lc), 4096);
              bulk_commit();
              bulk_wait_all();
              red_relaxed(&g_cnt[C_G1 * 32 + lc]);
              if (lc == 3) TS(18);
            }
          }
        }
        __syncwarp();
        if (p.stop <= 3) return;
      }
    } else if (warp == 14) {
      mbar_wait(bar + 8 * B_EP, 0);
      const unsigned epoch = lds32(sb + SM_EP);
#pragma unroll 1
      for (int layer = 0; layer < 2; layer++) {
        if (p.stop <= 1 + 3 * layer) return;
        mbar_wait(bar + 8 * B_ZF, layer);
        mbar_wait(bar + 8 * (EXP_LATE ? B_PS : B_PDONE), layer);
        delay<D_PST>();
        proj_stats(layer, rb2, q2, lane, 4 * epoch + 2 * layer + 2);
        if (layer == 1 && lane == 0) TS(5);
        delay<D_PREP>();
        if (lane == 0) mbar_arrive(bar + 8 * B_GB);
      }
    }
  }
}

typedef CUresult (*EncodeFn)(CUtensorMap*, CUtensorMapDataType, cuuint32_t, void*, const cuuint64_t*, const cuuint64_t*,
                             const cuuint32_t*, const cuuint32_t*, CUtensorMapInterleave, CUtensorMapSwizzle,
                             CUtensorMapL2promotion, CUtensorMapFloatOOBfill);

static void make_map(EncodeFn enc, CUtensorMap* m, void* ptr, uint64_t cols, uint64_t rows, uint32_t box_rows) {
  cuuint64_t dims[2] = {cols, rows};
  cuuint64_t strides[1] = {cols * 2};
  cuuint32_t box[2] = {64, box_rows};
  cuuint32_t es[2] = {1, 1};
  enc(m, CU_TENSOR_MAP_DATA_TYPE_BFLOAT16, 2, ptr, dims, strides, box, es, CU_TENSOR_MAP_INTERLEAVE_NONE,
      CU_TENSOR_MAP_SWIZZLE_128B, CU_TENSOR_MAP_L2_PROMOTION_L2_128B, CU_TENSOR_MAP_FLOAT_OOB_FILL_NONE);
}
static void make_map3(EncodeFn enc, CUtensorMap* m, void* ptr, uint64_t d0, uint64_t cols, uint64_t rows, uint64_t blk_stride,
                      uint64_t nblocks, uint32_t nblk, uint32_t box_rows = 64) {
  cuuint64_t dims[3] = {d0, rows, nblocks};
  cuuint64_t strides[2] = {cols * 2, blk_stride * 2};
  cuuint32_t box[3] = {64, box_rows, nblk};
  cuuint32_t es[3] = {1, 1, 1};
  enc(m, CU_TENSOR_MAP_DATA_TYPE_BFLOAT16, 3, ptr, dims, strides, box, es, CU_TENSOR_MAP_INTERLEAVE_NONE,
      CU_TENSOR_MAP_SWIZZLE_128B, CU_TENSOR_MAP_L2_PROMOTION_L2_128B, CU_TENSOR_MAP_FLOAT_OOB_FILL_NONE);
}

extern "C" void kernel_launch(void* const* d_in, const int* in_sizes, int n_in, void* d_out, int out_size) {
  static Params prm;
  static void* cached[13] = {nullptr};
  static bool attr_done = false, by_smid = false;
  bool same = attr_done && cached[12] == d_out;
  for (int i = 0; i < 12 && same; i++) same = cached[i] == d_in[i];
  if (!same) {
    void* fn = nullptr;
    cudaDriverEntryPointQueryResult qr;
    cudaGetDriverEntryPoint("cuTensorMapEncodeTiled", &fn, cudaEnableDefault, &qr);
    EncodeFn enc = (EncodeFn)fn;
    void *pO, *pXT;
    cudaGetSymbolAddress(&pO, g_O);
    cudaGetSymbolAddress(&pXT, g_xT);
    make_map(enc, &prm.mapO, pO, DM, LSEQ, 64);
    make_map(enc, &prm.mapXT, pXT, LSEQ, 4 * DM, 64);
    prm.out = (bf16*)d_out;
    make_map(enc, &prm.mapX128, d_in[0], DM, LSEQ, 128);
    make_map(enc, &prm.mapWo128, d_in[2], DM, DM, 128);
    make_map(enc, &prm.mapO128, pO, DM, LSEQ, 128);
    make_map3(enc, &prm.mapW3, d_in[1], DM, 3 * DM, DM, DM, 3, 3);
    make_map3(enc, &prm.mapW3h, d_in[1], DM, 3 * DM, DM, DM, 3, 3, 32);
    make_map3(enc, &prm.mapXT3, pXT, 64, LSEQ, 4 * DM, 64, 32, 2);
    prm.a_re = (const bf16*)d_in[4]; prm.a_im = (const bf16*)d_in[5];
    prm.b_re = (const bf16*)d_in[6]; prm.b_im = (const bf16*)d_in[7];
    prm.c_re = (const bf16*)d_in[8]; prm.c_im = (const bf16*)d_in[9];
    prm.log_dt = (const bf16*)d_in[10]; prm.dskip = (const bf16*)d_in[11];
    int dev = 0, sms = 0;
    cudaGetDevice(&dev);
    cudaDeviceGetAttribute(&sms, cudaDevAttrMultiProcessorCount, dev);
    by_smid = sms == 132;
    cudaFuncSetAttribute(fused_kernel<true>, cudaFuncAttributeMaxDynamicSharedMemorySize, SM_TOTAL);
    cudaFuncSetAttribute(fused_kernel<false>, cudaFuncAttributeMaxDynamicSharedMemorySize, SM_TOTAL);
    for (int i = 0; i < 12; i++) cached[i] = d_in[i];
    cached[12] = d_out;
    attr_done = true;
  }
  prm.stop = 100;
    if (by_smid) fused_kernel<true><<<132, NTHREADS, SM_TOTAL>>>(prm);
  else fused_kernel<false><<<NCTA, NTHREADS, SM_TOTAL>>>(prm);
}
```

```cpp
#include <cuda_runtime.h>
#include <cuda_bf16.h>
#include <cuda.h>
#include <stdint.h>

typedef __nv_bfloat16 bf16;

constexpr int LSEQ = 2048;
constexpr int DM = 512;
constexpr int NCTA = 128;
constexpr int NTHREADS = 512;
#define RR 0
#define KG_PRE 2
#define W2_LATE 0
#define FILL_AT 2
#define EXP_LATE 1
#define RFENCE 1
#define D_FIN 550
#define D_PREP 500
#define D_PST 0
#define D_HALO 300
#define STAG 2
#define D_ST 0
#define TLAYER 1
#define KG_PD 0
#define CS_AT 4
#define KG_LAST 1
#define X_JIT 0
#define PF_AT 2
#define KG_GATE 2
#define R_CONS 192
#define R_HELP 88

constexpr int SM_X = 0;
constexpr int SM_W = 131072;
constexpr int SM_KVX = SM_X;
constexpr int SM_OST = SM_X + 32768;
constexpr int SM_WO = SM_X + 65536;
__host__ __device__ constexpr int sm_o(int c) { return c < 4 ? SM_W + c * 16384 : SM_X + (c - 4) * 16384; }
constexpr int SM_R = 196608;
constexpr int SM_T = 212992;
constexpr int SM_KC = 217088;
constexpr int KC_STRIDE = 648;
constexpr int SM_CS = SM_KC + 4 * KC_STRIDE * 2;
constexpr int SM_CW = SM_R + 8192;
constexpr int SM_EP = SM_CS + 768;
constexpr int SM_BAR = SM_EP + 16;
constexpr int SM_T2 = SM_BAR + 832;
constexpr int SM_HALO = SM_T2 + 4096;
constexpr int SM_ST = SM_HALO + 3072;
constexpr int SM_TOTAL = SM_HALO + 4096;
static_assert(SM_TOTAL <= 232448, "shared memory");

constexpr int CV_UH = 140 * 16;
constexpr int CV_PECH = 1120 * 4;
constexpr int CV_PBW = 2112 * 2;
__host__ __device__ constexpr int cv_s(int lc) { return SM_X + lc * 32768; }
__host__ __device__ constexpr int cv_u(int lc) { return cv_s(lc) + 4096; }
__host__ __device__ constexpr int cv_pe(int lc) { return cv_u(lc) + 2 * CV_UH; }
__host__ __device__ constexpr int cv_pb(int lc) { return cv_pe(lc) + CV_PECH; }
__host__ __device__ constexpr int cv_ft(int lc) { return cv_pb(lc) + 4 * CV_PBW; }
static_assert(cv_ft(0) + 1024 <= 32768, "conv buffers");
__host__ __device__ constexpr int cv_chan(int cta, int lc) { return cta + 128 * lc; }

enum {
  B_XF = 0,
  B_KVF = 8,
  B_KVE = 16,
  B_AD = 21,
  B_OST = 22,
  B_RF = 23,
  B_U = 24,
  B_S = 28,
  B_T = 32,
  B_WOF = 36,
  B_E = 40,
  B_OF = 44,
  B_P = 64,
  B_RE = 52,
  B_CW = 53,
  B_HF = 54,
  B_STF = 55,
  B_CSF = 61,
  B_SD = 68,
  B_QDONE = 56,
  B_PDONE = 57,
  B_PS = 58,
  B_PE = 59,
  B_GB = 60,
  B_EP = 62,
  B_ZF = 63,
  B_COUNT = 69
};

enum {
  C_CS = 0,
  C_G1 = 2,
  C_O = 4,
  C_COUNT = 20
};

__device__ __align__(128) unsigned g_cnt[C_COUNT * 32];
__device__ __align__(1024) bf16 g_O[LSEQ * DM];
__device__ __align__(1024) bf16 g_xT[4 * DM * LSEQ];
__device__ __align__(1024) float g_stats[2 * LSEQ * 2];
__device__ __align__(1024) uint4 g_colsum[8 * 16 * 48];
__device__ __align__(1024) uint4 g_halo[16 * 8 * 384];
__device__ __align__(1024) uint2 g_part[16 * 8 * 128];
#define TS(i) do { } while (0)

#define ATS(i, th) do { } while (0)
#define KTS(i) do { if (ht == 0) TS(i); } while (0)
#define FTS(i) do { } while (0)
#define LTS(i) do { } while (0)

struct Params {
  CUtensorMap mapO, mapXT, mapX128, mapWo128, mapO128, mapW3, mapW3h, mapXT3;
  const bf16 *a_re, *a_im, *b_re, *b_im, *c_re, *c_im, *log_dt, *dskip;
  bf16* out;
  int stop;
};

__device__ __forceinline__ uint32_t s32(const void* p) { return (uint32_t)__cvta_generic_to_shared(p); }
__device__ __forceinline__ void mbar_init(uint32_t b, int c) { asm volatile("mbarrier.init.shared::cta.b64 [%0], %1;" ::"r"(b), "r"(c) : "memory"); }
__device__ __forceinline__ void mbar_expect(uint32_t b, int bytes) { asm volatile("mbarrier.arrive.expect_tx.shared::cta.b64 _, [%0], %1;" ::"r"(b), "r"(bytes) : "memory"); }
__device__ __forceinline__ void mbar_arrive(uint32_t b) { asm volatile("mbarrier.arrive.shared::cta.b64 _, [%0];" ::"r"(b) : "memory"); }
__device__ __forceinline__ void mbar_arrive_if(uint32_t b, bool c) {
  asm volatile("{\n.reg .pred p;\nsetp.ne.u32 p, %1, 0;\n@p mbarrier.arrive.shared::cta.b64 _, [%0];\n}" ::"r"(b), "r"((uint32_t)c) : "memory");
}
__device__ __forceinline__ void mbar_wait(uint32_t b, int parity) {
  asm volatile("{\n.reg .pred p;\nWAIT_LOOP:\nmbarrier.try_wait.parity.shared::cta.b64 p, [%0], %1;\n@p bra WAIT_DONE;\nbra WAIT_LOOP;\nWAIT_DONE:\n}" ::"r"(b), "r"(parity) : "memory");
}
template <int N> __device__ __forceinline__ void delay() {
  if constexpr (N > 0) {
    uint32_t t0, t;
    asm volatile("mov.u32 %0, %%clock;" : "=r"(t0));
    do { asm volatile("mov.u32 %0, %%clock;" : "=r"(t)); } while (t - t0 < N);
  }
}
__device__ __forceinline__ int opaque_tid() { int v; asm volatile("mov.u32 %0, %%tid.x;" : "=r"(v)); return v; }
__device__ __forceinline__ bool elect_one() {
  uint32_t r;
  asm volatile("{\n.reg .pred p;\nelect.sync _|p, 0xffffffff;\nselp.u32 %0, 1, 0, p;\n}" : "=r"(r));
  return r != 0;
}
__device__ __forceinline__ void tma_ld(uint32_t dst, const CUtensorMap* m, int c0, int c1, uint32_t bar) {
  asm volatile("cp.async.bulk.tensor.2d.shared::cluster.global.mbarrier::complete_tx::bytes [%0], [%1, {%3, %4}], [%2];"
               ::"r"(dst), "l"(m), "r"(bar), "r"(c0), "r"(c1) : "memory");
}
__device__ __forceinline__ void tma_ld3(uint32_t dst, const CUtensorMap* m, int c0, int c1, int c2, uint32_t bar) {
  asm volatile("cp.async.bulk.tensor.3d.shared::cluster.global.mbarrier::complete_tx::bytes [%0], [%1, {%3, %4, %5}], [%2];"
               ::"r"(dst), "l"(m), "r"(bar), "r"(c0), "r"(c1), "r"(c2) : "memory");
}
__device__ __forceinline__ void tma_prefetch2(const CUtensorMap* m, int c0, int c1) {
  asm volatile("cp.async.bulk.prefetch.tensor.2d.L2.global.tile [%0, {%1, %2}];" ::"l"(m), "r"(c0), "r"(c1) : "memory");
}
__device__ __forceinline__ void tma_prefetch3(const CUtensorMap* m, int c0, int c1, int c2) {
  asm volatile("cp.async.bulk.prefetch.tensor.3d.L2.global.tile [%0, {%1, %2, %3}];" ::"l"(m), "r"(c0), "r"(c1), "r"(c2) : "memory");
}
__device__ __forceinline__ void tma_st(const CUtensorMap* m, int c0, int c1, uint32_t src) {
  asm volatile("cp.async.bulk.tensor.2d.global.shared::cta.bulk_group [%0, {%2, %3}], [%1];" ::"l"(m), "r"(src), "r"(c0), "r"(c1) : "memory");
}
__device__ __forceinline__ void bulk_ld(uint32_t dst, const void* src, int bytes, uint32_t bar) {
  asm volatile("cp.async.bulk.shared::cluster.global.mbarrier::complete_tx::bytes [%0], [%1], %2, [%3];" ::"r"(dst), "l"(src), "r"(bytes), "r"(bar) : "memory");
}
__device__ __forceinline__ void bulk_st(void* dst, uint32_t src, int bytes) {
  asm volatile("cp.async.bulk.global.shared::cta.bulk_group [%0], [%1], %2;" ::"l"(dst), "r"(src), "r"(bytes) : "memory");
}
__device__ __forceinline__ void bulk_red_add_f32(void* dst, uint32_t src, int bytes) {
  asm volatile("cp.reduce.async.bulk.global.shared::cta.bulk_group.add.f32 [%0], [%1], %2;" ::"l"(dst), "r"(src), "r"(bytes) : "memory");
}
__device__ __forceinline__ void bulk_commit() { asm volatile("cp.async.bulk.commit_group;" ::: "memory"); }
__device__ __forceinline__ void bulk_wait_all() { asm volatile("cp.async.bulk.wait_group 0;" ::: "memory"); }
__device__ __forceinline__ void fence_async_smem() { asm volatile("fence.proxy.async.shared::cta;" ::: "memory"); }
__device__ __forceinline__ void fence_writer() { if (!RFENCE) fence_async_smem(); }
__device__ __forceinline__ void fence_reader() { if (RFENCE) fence_async_smem(); }
__device__ __forceinline__ void fence_async_global() { asm volatile("fence.proxy.async.global;" ::: "memory"); }
__device__ __forceinline__ void bar_sync(int id, int n) { asm volatile("bar.sync %0, %1;" ::"r"(id), "r"(n) : "memory"); }
__device__ __forceinline__ void bar_arrive(int id, int n) { asm volatile("bar.arrive %0, %1;" ::"r"(id), "r"(n) : "memory"); }
__device__ __forceinline__ void wg_fence() { asm volatile("wgmma.fence.sync.aligned;" ::: "memory"); }
__device__ __forceinline__ void wg_commit() { asm volatile("wgmma.commit_group.sync.aligned;" ::: "memory"); }
template <int N> __device__ __forceinline__ void wg_wait() { asm volatile("wgmma.wait_group.sync.aligned %0;" ::"n"(N) : "memory"); }
__device__ __forceinline__ uint64_t mkdesc(uint32_t addr, uint32_t lbo, uint32_t sbo, int sw) {
  return (uint64_t)((addr & 0x3FFFF) >> 4) | ((uint64_t)(lbo >> 4) << 16) | ((uint64_t)(sbo >> 4) << 32) | ((uint64_t)sw << 62);
}
__device__ __forceinline__ void ldsm4(uint32_t* r, uint32_t a) {
  asm volatile("ldmatrix.sync.aligned.m8n8.x4.shared.b16 {%0,%1,%2,%3}, [%4];" : "=r"(r[0]), "=r"(r[1]), "=r"(r[2]), "=r"(r[3]) : "r"(a) : "memory");
}
__device__ __forceinline__ void ldsm4t(uint32_t* r, uint32_t a) {
  asm volatile("ldmatrix.sync.aligned.m8n8.x4.trans.shared.b16 {%0,%1,%2,%3}, [%4];" : "=r"(r[0]), "=r"(r[1]), "=r"(r[2]), "=r"(r[3]) : "r"(a) : "memory");
}
__device__ __forceinline__ void stsm4(uint32_t a, uint32_t r0, uint32_t r1, uint32_t r2, uint32_t r3) {
  asm volatile("stmatrix.sync.aligned.m8n8.x4.shared.b16 [%0], {%1,%2,%3,%4};" ::"r"(a), "r"(r0), "r"(r1), "r"(r2), "r"(r3) : "memory");
}
__device__ __forceinline__ void stsm4t(uint32_t a, uint32_t r0, uint32_t r1, uint32_t r2, uint32_t r3) {
  asm volatile("stmatrix.sync.aligned.m8n8.x4.trans.shared.b16 [%0], {%1,%2,%3,%4};" ::"r"(a), "r"(r0), "r"(r1), "r"(r2), "r"(r3) : "memory");
}
__device__ __forceinline__ uint32_t movm_t(uint32_t a) { uint32_t r; asm volatile("movmatrix.sync.aligned.m8n8.trans.b16 %0, %1;" : "=r"(r) : "r"(a)); return r; }
__device__ __forceinline__ uint32_t lds32(uint32_t a) { uint32_t v; asm volatile("ld.shared.b32 %0, [%1];" : "=r"(v) : "r"(a) : "memory"); return v; }
__device__ __forceinline__ float2 lds64f(uint32_t a) { float2 v; asm volatile("ld.shared.v2.f32 {%0,%1}, [%2];" : "=f"(v.x), "=f"(v.y) : "r"(a) : "memory"); return v; }
__device__ __forceinline__ float4 lds128f(uint32_t a) { float4 v; asm volatile("ld.shared.v4.f32 {%0,%1,%2,%3}, [%4];" : "=f"(v.x), "=f"(v.y), "=f"(v.z), "=f"(v.w) : "r"(a) : "memory"); return v; }
__device__ __forceinline__ uint4 lds128(uint32_t a) { uint4 v; asm volatile("ld.shared.v4.b32 {%0,%1,%2,%3}, [%4];" : "=r"(v.x), "=r"(v.y), "=r"(v.z), "=r"(v.w) : "r"(a) : "memory"); return v; }
__device__ __forceinline__ void sts128(uint32_t a, uint4 v) { asm volatile("st.shared.v4.b32 [%0], {%1,%2,%3,%4};" ::"r"(a), "r"(v.x), "r"(v.y), "r"(v.z), "r"(v.w) : "memory"); }
__device__ __forceinline__ void sts128f(uint32_t a, float x, float y, float z, float w) { asm volatile("st.shared.v4.f32 [%0], {%1,%2,%3,%4};" ::"r"(a), "f"(x), "f"(y), "f"(z), "f"(w) : "memory"); }
__device__ __forceinline__ void sts32f(uint32_t a, float v) { asm volatile("st.shared.f32 [%0], %1;" ::"r"(a), "f"(v) : "memory"); }
__device__ __forceinline__ void sts16(uint32_t a, uint16_t v) { asm volatile("st.shared.u16 [%0], %1;" ::"r"(a), "h"(v) : "memory"); }
__device__ __forceinline__ uint32_t lds16(uint32_t a) { uint16_t v; asm volatile("ld.shared.u16 %0, [%1];" : "=h"(v) : "r"(a) : "memory"); return v; }
__device__ __forceinline__ uint32_t packbf(float lo, float hi) { uint32_t r; asm("cvt.rn.bf16x2.f32 %0, %1, %2;" : "=r"(r) : "f"(hi), "f"(lo)); return r; }
__device__ __forceinline__ float bf_lo(uint32_t v) { return __uint_as_float(v << 16); }
__device__ __forceinline__ float bf_hi(uint32_t v) { return __uint_as_float(v & 0xffff0000u); }
__device__ __forceinline__ float ex2(float x) { float r; asm("ex2.approx.ftz.f32 %0, %1;" : "=f"(r) : "f"(x)); return r; }
__device__ __forceinline__ float rsqrt_approx(float x) { float r; asm("rsqrt.approx.ftz.f32 %0, %1;" : "=f"(r) : "f"(x)); return r; }
__device__ __forceinline__ float rcp_approx(float x) { float r; asm("rcp.approx.ftz.f32 %0, %1;" : "=f"(r) : "f"(x)); return r; }
__device__ __forceinline__ void mma_bf16(float* d, const uint32_t* a, uint32_t b0, uint32_t b1) {
  asm("mma.sync.aligned.m16n8k16.row.col.f32.bf16.bf16.f32 {%0,%1,%2,%3}, {%4,%5,%6,%7}, {%8,%9}, {%0,%1,%2,%3};"
               : "+f"(d[0]), "+f"(d[1]), "+f"(d[2]), "+f"(d[3]) : "r"(a[0]), "r"(a[1]), "r"(a[2]), "r"(a[3]), "r"(b0), "r"(b1));
}
__device__ __forceinline__ void red_release(unsigned* p) { asm volatile("red.release.gpu.global.add.u32 [%0], 1;" ::"l"(p) : "memory"); }
__device__ __forceinline__ void red_relaxed(unsigned* p) { asm volatile("red.relaxed.gpu.global.add.u32 [%0], 1;" ::"l"(p) : "memory"); }
__device__ __forceinline__ unsigned ld_relaxed(const unsigned* p) { unsigned v; asm volatile("ld.relaxed.gpu.global.u32 %0, [%1];" : "=r"(v) : "l"(p) : "memory"); return v; }
__device__ __forceinline__ void spin_until(const unsigned* p, unsigned target) {
  int it = 0;
  while ((int)(ld_relaxed(p) - target) < 0) {
    if (++it > (1 << 23)) __trap();
  }
}
__device__ __forceinline__ uint4 ldcg128(const void* p) { uint4 v; asm volatile("ld.global.cg.v4.b32 {%0,%1,%2,%3}, [%4];" : "=r"(v.x), "=r"(v.y), "=r"(v.z), "=r"(v.w) : "l"(p) : "memory"); return v; }
__device__ __forceinline__ uint4 ld_tagged(const uint4* p) { uint4 v; asm volatile("ld.relaxed.gpu.global.v4.u32 {%0,%1,%2,%3}, [%4];" : "=r"(v.x), "=r"(v.y), "=r"(v.z), "=r"(v.w) : "l"(p) : "memory"); return v; }
__device__ __forceinline__ uint2 ld_part(const uint2* p) { uint2 v; asm volatile("ld.relaxed.gpu.global.v2.u32 {%0,%1}, [%2];" : "=r"(v.x), "=r"(v.y) : "l"(p) : "memory"); return v; }
__device__ __forceinline__ void st_part(uint2* p, float s, float q, uint32_t tag) {
  asm volatile("st.relaxed.gpu.global.v2.u32 [%0], {%1,%2};" ::"l"(p), "r"(__float_as_uint(s)), "r"((__float_as_uint(q) & ~7u) | tag) : "memory");
}
__device__ __forceinline__ uint32_t part_tag(uint32_t epoch, int k) { return (4 * (epoch % 7) + k) % 7 + 1; }
__device__ __forceinline__ void st_tagged3(uint4* p, uint32_t a, uint32_t b, uint32_t c, uint32_t tag) { asm volatile("st.relaxed.gpu.global.v4.u32 [%0], {%1,%2,%3,%4};" ::"l"(p), "r"(a), "r"(b), "r"(c), "r"(tag) : "memory"); }
__device__ __forceinline__ uint32_t hadd2(uint32_t a, uint32_t b) { uint32_t r; asm("add.rn.bf16x2 %0, %1, %2;" : "=r"(r) : "r"(a), "r"(b)); return r; }
__device__ __forceinline__ uint32_t hmul2(uint32_t a, uint32_t b) { uint32_t r; asm("mul.rn.bf16x2 %0, %1, %2;" : "=r"(r) : "r"(a), "r"(b)); return r; }

template<int N,int TB> __device__ __forceinline__ void wgmma_rs(float* d, const uint32_t* a, uint64_t db, int sd);
template<int N,int TA,int TB> __device__ __forceinline__ void wgmma_ss(float* d, uint64_t da, uint64_t db, int sd);
template<> __device__ __forceinline__ void wgmma_rs<128,0>(float* d, const uint32_t* a, uint64_t db, int sd) {
  asm volatile("{\n.reg .pred p;\nsetp.ne.b32 p, %69, 0;\nwgmma.mma_async.sync.aligned.m64n128k16.f32.bf16.bf16 {%0,%1,%2,%3,%4,%5,%6,%7,%8,%9,%10,%11,%12,%13,%14,%15,%16,%17,%18,%19,%20,%21,%22,%23,%24,%25,%26,%27,%28,%29,%30,%31,%32,%33,%34,%35,%36,%37,%38,%39,%40,%41,%42,%43,%44,%45,%46,%47,%48,%49,%50,%51,%52,%53,%54,%55,%56,%57,%58,%59,%60,%61,%62,%63}, {%64,%65,%66,%67}, %68, p, 1, 1, 0;\n}\n"
   : "+f"(d[0]),"+f"(d[1]),"+f"(d[2]),"+f"(d[3]),"+f"(d[4]),"+f"(d[5]),"+f"(d[6]),"+f"(d[7]),"+f"(d[8]),"+f"(d[9]),"+f"(d[10]),"+f"(d[11]),"+f"(d[12]),"+f"(d[13]),"+f"(d[14]),"+f"(d[15]),"+f"(d[16]),"+f"(d[17]),"+f"(d[18]),"+f"(d[19]),"+f"(d[20]),"+f"(d[21]),"+f"(d[22]),"+f"(d[23]),"+f"(d[24]),"+f"(d[25]),"+f"(d[26]),"+f"(d[27]),"+f"(d[28]),"+f"(d[29]),"+f"(d[30]),"+f"(d[31]),"+f"(d[32]),"+f"(d[33]),"+f"(d[34]),"+f"(d[35]),"+f"(d[36]),"+f"(d[37]),"+f"(d[38]),"+f"(d[39]),"+f"(d[40]),"+f"(d[41]),"+f"(d[42]),"+f"(d[43]),"+f"(d[44]),"+f"(d[45]),"+f"(d[46]),"+f"(d[47]),"+f"(d[48]),"+f"(d[49]),"+f"(d[50]),"+f"(d[51]),"+f"(d[52]),"+f"(d[53]),"+f"(d[54]),"+f"(d[55]),"+f"(d[56]),"+f"(d[57]),"+f"(d[58]),"+f"(d[59]),"+f"(d[60]),"+f"(d[61]),"+f"(d[62]),"+f"(d[63])
   : "r"(a[0]), "r"(a[1]), "r"(a[2]), "r"(a[3]), "l"(db), "r"(sd));
}
template<> __device__ __forceinline__ void wgmma_rs<120,0>(float* d, const uint32_t* a, uint64_t db, int sd) {
  asm volatile("{\n.reg .pred p;\nsetp.ne.b32 p, %65, 0;\nwgmma.mma_async.sync.aligned.m64n120k16.f32.bf16.bf16 {%0,%1,%2,%3,%4,%5,%6,%7,%8,%9,%10,%11,%12,%13,%14,%15,%16,%17,%18,%19,%20,%21,%22,%23,%24,%25,%26,%27,%28,%29,%30,%31,%32,%33,%34,%35,%36,%37,%38,%39,%40,%41,%42,%43,%44,%45,%46,%47,%48,%49,%50,%51,%52,%53,%54,%55,%56,%57,%58,%59}, {%60,%61,%62,%63}, %64, p, 1, 1, 0;\n}\n"
   : "+f"(d[0]),"+f"(d[1]),"+f"(d[2]),"+f"(d[3]),"+f"(d[4]),"+f"(d[5]),"+f"(d[6]),"+f"(d[7]),"+f"(d[8]),"+f"(d[9]),"+f"(d[10]),"+f"(d[11]),"+f"(d[12]),"+f"(d[13]),"+f"(d[14]),"+f"(d[15]),"+f"(d[16]),"+f"(d[17]),"+f"(d[18]),"+f"(d[19]),"+f"(d[20]),"+f"(d[21]),"+f"(d[22]),"+f"(d[23]),"+f"(d[24]),"+f"(d[25]),"+f"(d[26]),"+f"(d[27]),"+f"(d[28]),"+f"(d[29]),"+f"(d[30]),"+f"(d[31]),"+f"(d[32]),"+f"(d[33]),"+f"(d[34]),"+f"(d[35]),"+f"(d[36]),"+f"(d[37]),"+f"(d[38]),"+f"(d[39]),"+f"(d[40]),"+f"(d[41]),"+f"(d[42]),"+f"(d[43]),"+f"(d[44]),"+f"(d[45]),"+f"(d[46]),"+f"(d[47]),"+f"(d[48]),"+f"(d[49]),"+f"(d[50]),"+f"(d[51]),"+f"(d[52]),"+f"(d[53]),"+f"(d[54]),"+f"(d[55]),"+f"(d[56]),"+f"(d[57]),"+f"(d[58]),"+f"(d[59])
   : "r"(a[0]), "r"(a[1]), "r"(a[2]), "r"(a[3]), "l"(db), "r"(sd));
}
template<> __device__ __forceinline__ void wgmma_rs<112,0>(float* d, const uint32_t* a, uint64_t db, int sd) {
  asm volatile("{\n.reg .pred p;\nsetp.ne.b32 p, %61, 0;\nwgmma.mma_async.sync.aligned.m64n112k16.f32.bf16.bf16 {%0,%1,%2,%3,%4,%5,%6,%7,%8,%9,%10,%11,%12,%13,%14,%15,%16,%17,%18,%19,%20,%21,%22,%23,%24,%25,%26,%27,%28,%29,%30,%31,%32,%33,%34,%35,%36,%37,%38,%39,%40,%41,%42,%43,%44,%45,%46,%47,%48,%49,%50,%51,%52,%53,%54,%55}, {%56,%57,%58,%59}, %60, p, 1, 1, 0;\n}\n"
   : "+f"(d[0]),"+f"(d[1]),"+f"(d[2]),"+f"(d[3]),"+f"(d[4]),"+f"(d[5]),"+f"(d[6]),"+f"(d[7]),"+f"(d[8]),"+f"(d[9]),"+f"(d[10]),"+f"(d[11]),"+f"(d[12]),"+f"(d[13]),"+f"(d[14]),"+f"(d[15]),"+f"(d[16]),"+f"(d[17]),"+f"(d[18]),"+f"(d[19]),"+f"(d[20]),"+f"(d[21]),"+f"(d[22]),"+f"(d[23]),"+f"(d[24]),"+f"(d[25]),"+f"(d[26]),"+f"(d[27]),"+f"(d[28]),"+f"(d[29]),"+f"(d[30]),"+f"(d[31]),"+f"(d[32]),"+f"(d[33]),"+f"(d[34]),"+f"(d[35]),"+f"(d[36]),"+f"(d[37]),"+f"(d[38]),"+f"(d[39]),"+f"(d[40]),"+f"(d[41]),"+f"(d[42]),"+f"(d[43]),"+f"(d[44]),"+f"(d[45]),"+f"(d[46]),"+f"(d[47]),"+f"(d[48]),"+f"(d[49]),"+f"(d[50]),"+f"(d[51]),"+f"(d[52]),"+f"(d[53]),"+f"(d[54]),"+f"(d[55])
   : "r"(a[0]), "r"(a[1]), "r"(a[2]), "r"(a[3]), "l"(db), "r"(sd));
}
template<> __device__ __forceinline__ void wgmma_rs<104,0>(float* d, const uint32_t* a, uint64_t db, int sd) {
  asm volatile("{\n.reg .pred p;\nsetp.ne.b32 p, %57, 0;\nwgmma.mma_async.sync.aligned.m64n104k16.f32.bf16.bf16 {%0,%1,%2,%3,%4,%5,%6,%7,%8,%9,%10,%11,%12,%13,%14,%15,%16,%17,%18,%19,%20,%21,%22,%23,%24,%25,%26,%27,%28,%29,%30,%31,%32,%33,%34,%35,%36,%37,%38,%39,%40,%41,%42,%43,%44,%45,%46,%47,%48,%49,%50,%51}, {%52,%53,%54,%55}, %56, p, 1, 1, 0;\n}\n"
   : "+f"(d[0]),"+f"(d[1]),"+f"(d[2]),"+f"(d[3]),"+f"(d[4]),"+f"(d[5]),"+f"(d[6]),"+f"(d[7]),"+f"(d[8]),"+f"(d[9]),"+f"(d[10]),"+f"(d[11]),"+f"(d[12]),"+f"(d[13]),"+f"(d[14]),"+f"(d[15]),"+f"(d[16]),"+f"(d[17]),"+f"(d[18]),"+f"(d[19]),"+f"(d[20]),"+f"(d[21]),"+f"(d[22]),"+f"(d[23]),"+f"(d[24]),"+f"(d[25]),"+f"(d[26]),"+f"(d[27]),"+f"(d[28]),"+f"(d[29]),"+f"(d[30]),"+f"(d[31]),"+f"(d[32]),"+f"(d[33]),"+f"(d[34]),"+f"(d[35]),"+f"(d[36]),"+f"(d[37]),"+f"(d[38]),"+f"(d[39]),"+f"(d[40]),"+f"(d[41]),"+f"(d[42]),"+f"(d[43]),"+f"(d[44]),"+f"(d[45]),"+f"(d[46]),"+f"(d[47]),"+f"(d[48]),"+f"(d[49]),"+f"(d[50]),"+f"(d[51])
   : "r"(a[0]), "r"(a[1]), "r"(a[2]), "r"(a[3]), "l"(db), "r"(sd));
}
template<> __device__ __forceinline__ void wgmma_rs<96,0>(float* d, const uint32_t* a, uint64_t db, int sd) {
  asm volatile("{\n.reg .pred p;\nsetp.ne.b32 p, %53, 0;\nwgmma.mma_async.sync.aligned.m64n96k16.f32.bf16.bf16 {%0,%1,%2,%3,%4,%5,%6,%7,%8,%9,%10,%11,%12,%13,%14,%15,%16,%17,%18,%19,%20,%21,%22,%23,%24,%25,%26,%27,%28,%29,%30,%31,%32,%33,%34,%35,%36,%37,%38,%39,%40,%41,%42,%43,%44,%45,%46,%47}, {%48,%49,%50,%51}, %52, p, 1, 1, 0;\n}\n"
   : "+f"(d[0]),"+f"(d[1]),"+f"(d[2]),"+f"(d[3]),"+f"(d[4]),"+f"(d[5]),"+f"(d[6]),"+f"(d[7]),"+f"(d[8]),"+f"(d[9]),"+f"(d[10]),"+f"(d[11]),"+f"(d[12]),"+f"(d[13]),"+f"(d[14]),"+f"(d[15]),"+f"(d[16]),"+f"(d[17]),"+f"(d[18]),"+f"(d[19]),"+f"(d[20]),"+f"(d[21]),"+f"(d[22]),"+f"(d[23]),"+f"(d[24]),"+f"(d[25]),"+f"(d[26]),"+f"(d[27]),"+f"(d[28]),"+f"(d[29]),"+f"(d[30]),"+f"(d[31]),"+f"(d[32]),"+f"(d[33]),"+f"(d[34]),"+f"(d[35]),"+f"(d[36]),"+f"(d[37]),"+f"(d[38]),"+f"(d[39]),"+f"(d[40]),"+f"(d[41]),"+f"(d[42]),"+f"(d[43]),"+f"(d[44]),"+f"(d[45]),"+f"(d[46]),"+f"(d[47])
   : "r"(a[0]), "r"(a[1]), "r"(a[2]), "r"(a[3]), "l"(db), "r"(sd));
}
template<> __device__ __forceinline__ void wgmma_rs<88,0>(float* d, const uint32_t* a, uint64_t db, int sd) {
  asm volatile("{\n.reg .pred p;\nsetp.ne.b32 p, %49, 0;\nwgmma.mma_async.sync.aligned.m64n88k16.f32.bf16.bf16 {%0,%1,%2,%3,%4,%5,%6,%7,%8,%9,%10,%11,%12,%13,%14,%15,%16,%17,%18,%19,%20,%21,%22,%23,%24,%25,%26,%27,%28,%29,%30,%31,%32,%33,%34,%35,%36,%37,%38,%39,%40,%41,%42,%43}, {%44,%45,%46,%47}, %48, p, 1, 1, 0;\n}\n"
   : "+f"(d[0]),"+f"(d[1]),"+f"(d[2]),"+f"(d[3]),"+f"(d[4]),"+f"(d[5]),"+f"(d[6]),"+f"(d[7]),"+f"(d[8]),"+f"(d[9]),"+f"(d[10]),"+f"(d[11]),"+f"(d[12]),"+f"(d[13]),"+f"(d[14]),"+f"(d[15]),"+f"(d[16]),"+f"(d[17]),"+f"(d[18]),"+f"(d[19]),"+f"(d[20]),"+f"(d[21]),"+f"(d[22]),"+f"(d[23]),"+f"(d[24]),"+f"(d[25]),"+f"(d[26]),"+f"(d[27]),"+f"(d[28]),"+f"(d[29]),"+f"(d[30]),"+f"(d[31]),"+f"(d[32]),"+f"(d[33]),"+f"(d[34]),"+f"(d[35]),"+f"(d[36]),"+f"(d[37]),"+f"(d[38]),"+f"(d[39]),"+f"(d[40]),"+f"(d[41]),"+f"(d[42]),"+f"(d[43])
   : "r"(a[0]), "r"(a[1]), "r"(a[2]), "r"(a[3]), "l"(db), "r"(sd));
}
template<> __device__ __forceinline__ void wgmma_rs<80,0>(float* d, const uint32_t* a, uint64_t db, int sd) {
  asm volatile("{\n.reg .pred p;\nsetp.ne.b32 p, %45, 0;\nwgmma.mma_async.sync.aligned.m64n80k16.f32.bf16.bf16 {%0,%1,%2,%3,%4,%5,%6,%7,%8,%9,%10,%11,%12,%13,%14,%15,%16,%17,%18,%19,%20,%21,%22,%23,%24,%25,%26,%27,%28,%29,%30,%31,%32,%33,%34,%35,%36,%37,%38,%39}, {%40,%41,%42,%43}, %44, p, 1, 1, 0;\n}\n"
   : "+f"(d[0]),"+f"(d[1]),"+f"(d[2]),"+f"(d[3]),"+f"(d[4]),"+f"(d[5]),"+f"(d[6]),"+f"(d[7]),"+f"(d[8]),"+f"(d[9]),"+f"(d[10]),"+f"(d[11]),"+f"(d[12]),"+f"(d[13]),"+f"(d[14]),"+f"(d[15]),"+f"(d[16]),"+f"(d[17]),"+f"(d[18]),"+f"(d[19]),"+f"(d[20]),"+f"(d[21]),"+f"(d[22]),"+f"(d[23]),"+f"(d[24]),"+f"(d[25]),"+f"(d[26]),"+f"(d[27]),"+f"(d[28]),"+f"(d[29]),"+f"(d[30]),"+f"(d[31]),"+f"(d[32]),"+f"(d[33]),"+f"(d[34]),"+f"(d[35]),"+f"(d[36]),"+f"(d[37]),"+f"(d[38]),"+f"(d[39])
   : "r"(a[0]), "r"(a[1]), "r"(a[2]), "r"(a[3]), "l"(db), "r"(sd));
}
template<> __device__ __forceinline__ void wgmma_rs<72,0>(float* d, const uint32_t* a, uint64_t db, int sd) {
  asm volatile("{\n.reg .pred p;\nsetp.ne.b32 p, %41, 0;\nwgmma.mma_async.sync.aligned.m64n72k16.f32.bf16.bf16 {%0,%1,%2,%3,%4,%5,%6,%7,%8,%9,%10,%11,%12,%13,%14,%15,%16,%17,%18,%19,%20,%21,%22,%23,%24,%25,%26,%27,%28,%29,%30,%31,%32,%33,%34,%35}, {%36,%37,%38,%39}, %40, p, 1, 1, 0;\n}\n"
   : "+f"(d[0]),"+f"(d[1]),"+f"(d[2]),"+f"(d[3]),"+f"(d[4]),"+f"(d[5]),"+f"(d[6]),"+f"(d[7]),"+f"(d[8]),"+f"(d[9]),"+f"(d[10]),"+f"(d[11]),"+f"(d[12]),"+f"(d[13]),"+f"(d[14]),"+f"(d[15]),"+f"(d[16]),"+f"(d[17]),"+f"(d[18]),"+f"(d[19]),"+f"(d[20]),"+f"(d[21]),"+f"(d[22]),"+f"(d[23]),"+f"(d[24]),"+f"(d[25]),"+f"(d[26]),"+f"(d[27]),"+f"(d[28]),"+f"(d[29]),"+f"(d[30]),"+f"(d[31]),"+f"(d[32]),"+f"(d[33]),"+f"(d[34]),"+f"(d[35])
   : "r"(a[0]), "r"(a[1]), "r"(a[2]), "r"(a[3]), "l"(db), "r"(sd));
}
template<> __device__ __forceinline__ void wgmma_rs<64,0>(float* d, const uint32_t* a, uint64_t db, int sd) {
  asm volatile("{\n.reg .pred p;\nsetp.ne.b32 p, %37, 0;\nwgmma.mma_async.sync.aligned.m64n64k16.f32.bf16.bf16 {%0,%1,%2,%3,%4,%5,%6,%7,%8,%9,%10,%11,%12,%13,%14,%15,%16,%17,%18,%19,%20,%21,%22,%23,%24,%25,%26,%27,%28,%29,%30,%31}, {%32,%33,%34,%35}, %36, p, 1, 1, 0;\n}\n"
   : "+f"(d[0]),"+f"(d[1]),"+f"(d[2]),"+f"(d[3]),"+f"(d[4]),"+f"(d[5]),"+f"(d[6]),"+f"(d[7]),"+f"(d[8]),"+f"(d[9]),"+f"(d[10]),"+f"(d[11]),"+f"(d[12]),"+f"(d[13]),"+f"(d[14]),"+f"(d[15]),"+f"(d[16]),"+f"(d[17]),"+f"(d[18]),"+f"(d[19]),"+f"(d[20]),"+f"(d[21]),"+f"(d[22]),"+f"(d[23]),"+f"(d[24]),"+f"(d[25]),"+f"(d[26]),"+f"(d[27]),"+f"(d[28]),"+f"(d[29]),"+f"(d[30]),"+f"(d[31])
   : "r"(a[0]), "r"(a[1]), "r"(a[2]), "r"(a[3]), "l"(db), "r"(sd));
}
template<> __device__ __forceinline__ void wgmma_ss<64,0,1>(float* d, uint64_t da, uint64_t db, int sd) {
  asm volatile("{\n.reg .pred p;\nsetp.ne.b32 p, %34, 0;\nwgmma.mma_async.sync.aligned.m64n64k16.f32.bf16.bf16 {%0,%1,%2,%3,%4,%5,%6,%7,%8,%9,%10,%11,%12,%13,%14,%15,%16,%17,%18,%19,%20,%21,%22,%23,%24,%25,%26,%27,%28,%29,%30,%31}, %32, %33, p, 1, 1, 0, 1;\n}\n"
   : "+f"(d[0]),"+f"(d[1]),"+f"(d[2]),"+f"(d[3]),"+f"(d[4]),"+f"(d[5]),"+f"(d[6]),"+f"(d[7]),"+f"(d[8]),"+f"(d[9]),"+f"(d[10]),"+f"(d[11]),"+f"(d[12]),"+f"(d[13]),"+f"(d[14]),"+f"(d[15]),"+f"(d[16]),"+f"(d[17]),"+f"(d[18]),"+f"(d[19]),"+f"(d[20]),"+f"(d[21]),"+f"(d[22]),"+f"(d[23]),"+f"(d[24]),"+f"(d[25]),"+f"(d[26]),"+f"(d[27]),"+f"(d[28]),"+f"(d[29]),"+f"(d[30]),"+f"(d[31])
   : "l"(da), "l"(db), "r"(sd));
}
template<> __device__ __forceinline__ void wgmma_ss<64,1,1>(float* d, uint64_t da, uint64_t db, int sd) {
  asm volatile("{\n.reg .pred p;\nsetp.ne.b32 p, %34, 0;\nwgmma.mma_async.sync.aligned.m64n64k16.f32.bf16.bf16 {%0,%1,%2,%3,%4,%5,%6,%7,%8,%9,%10,%11,%12,%13,%14,%15,%16,%17,%18,%19,%20,%21,%22,%23,%24,%25,%26,%27,%28,%29,%30,%31}, %32, %33, p, 1, 1, 1, 1;\n}\n"
   : "+f"(d[0]),"+f"(d[1]),"+f"(d[2]),"+f"(d[3]),"+f"(d[4]),"+f"(d[5]),"+f"(d[6]),"+f"(d[7]),"+f"(d[8]),"+f"(d[9]),"+f"(d[10]),"+f"(d[11]),"+f"(d[12]),"+f"(d[13]),"+f"(d[14]),"+f"(d[15]),"+f"(d[16]),"+f"(d[17]),"+f"(d[18]),"+f"(d[19]),"+f"(d[20]),"+f"(d[21]),"+f"(d[22]),"+f"(d[23]),"+f"(d[24]),"+f"(d[25]),"+f"(d[26]),"+f"(d[27]),"+f"(d[28]),"+f"(d[29]),"+f"(d[30]),"+f"(d[31])
   : "l"(da), "l"(db), "r"(sd));
}
template<> __device__ __forceinline__ void wgmma_ss<192,0,1>(float* d, uint64_t da, uint64_t db, int sd) {
  asm volatile("{\n.reg .pred p;\nsetp.ne.b32 p, %98, 0;\nwgmma.mma_async.sync.aligned.m64n192k16.f32.bf16.bf16 {%0,%1,%2,%3,%4,%5,%6,%7,%8,%9,%10,%11,%12,%13,%14,%15,%16,%17,%18,%19,%20,%21,%22,%23,%24,%25,%26,%27,%28,%29,%30,%31,%32,%33,%34,%35,%36,%37,%38,%39,%40,%41,%42,%43,%44,%45,%46,%47,%48,%49,%50,%51,%52,%53,%54,%55,%56,%57,%58,%59,%60,%61,%62,%63,%64,%65,%66,%67,%68,%69,%70,%71,%72,%73,%74,%75,%76,%77,%78,%79,%80,%81,%82,%83,%84,%85,%86,%87,%88,%89,%90,%91,%92,%93,%94,%95}, %96, %97, p, 1, 1, 0, 1;\n}\n"
   : "+f"(d[0]),"+f"(d[1]),"+f"(d[2]),"+f"(d[3]),"+f"(d[4]),"+f"(d[5]),"+f"(d[6]),"+f"(d[7]),"+f"(d[8]),"+f"(d[9]),"+f"(d[10]),"+f"(d[11]),"+f"(d[12]),"+f"(d[13]),"+f"(d[14]),"+f"(d[15]),"+f"(d[16]),"+f"(d[17]),"+f"(d[18]),"+f"(d[19]),"+f"(d[20]),"+f"(d[21]),"+f"(d[22]),"+f"(d[23]),"+f"(d[24]),"+f"(d[25]),"+f"(d[26]),"+f"(d[27]),"+f"(d[28]),"+f"(d[29]),"+f"(d[30]),"+f"(d[31]),"+f"(d[32]),"+f"(d[33]),"+f"(d[34]),"+f"(d[35]),"+f"(d[36]),"+f"(d[37]),"+f"(d[38]),"+f"(d[39]),"+f"(d[40]),"+f"(d[41]),"+f"(d[42]),"+f"(d[43]),"+f"(d[44]),"+f"(d[45]),"+f"(d[46]),"+f"(d[47]),"+f"(d[48]),"+f"(d[49]),"+f"(d[50]),"+f"(d[51]),"+f"(d[52]),"+f"(d[53]),"+f"(d[54]),"+f"(d[55]),"+f"(d[56]),"+f"(d[57]),"+f"(d[58]),"+f"(d[59]),"+f"(d[60]),"+f"(d[61]),"+f"(d[62]),"+f"(d[63]),"+f"(d[64]),"+f"(d[65]),"+f"(d[66]),"+f"(d[67]),"+f"(d[68]),"+f"(d[69]),"+f"(d[70]),"+f"(d[71]),"+f"(d[72]),"+f"(d[73]),"+f"(d[74]),"+f"(d[75]),"+f"(d[76]),"+f"(d[77]),"+f"(d[78]),"+f"(d[79]),"+f"(d[80]),"+f"(d[81]),"+f"(d[82]),"+f"(d[83]),"+f"(d[84]),"+f"(d[85]),"+f"(d[86]),"+f"(d[87]),"+f"(d[88]),"+f"(d[89]),"+f"(d[90]),"+f"(d[91]),"+f"(d[92]),"+f"(d[93]),"+f"(d[94]),"+f"(d[95])
   : "l"(da), "l"(db), "r"(sd));
}
template<> __device__ __forceinline__ void wgmma_ss<192,1,1>(float* d, uint64_t da, uint64_t db, int sd) {
  asm volatile("{\n.reg .pred p;\nsetp.ne.b32 p, %98, 0;\nwgmma.mma_async.sync.aligned.m64n192k16.f32.bf16.bf16 {%0,%1,%2,%3,%4,%5,%6,%7,%8,%9,%10,%11,%12,%13,%14,%15,%16,%17,%18,%19,%20,%21,%22,%23,%24,%25,%26,%27,%28,%29,%30,%31,%32,%33,%34,%35,%36,%37,%38,%39,%40,%41,%42,%43,%44,%45,%46,%47,%48,%49,%50,%51,%52,%53,%54,%55,%56,%57,%58,%59,%60,%61,%62,%63,%64,%65,%66,%67,%68,%69,%70,%71,%72,%73,%74,%75,%76,%77,%78,%79,%80,%81,%82,%83,%84,%85,%86,%87,%88,%89,%90,%91,%92,%93,%94,%95}, %96, %97, p, 1, 1, 1, 1;\n}\n"
   : "+f"(d[0]),"+f"(d[1]),"+f"(d[2]),"+f"(d[3]),"+f"(d[4]),"+f"(d[5]),"+f"(d[6]),"+f"(d[7]),"+f"(d[8]),"+f"(d[9]),"+f"(d[10]),"+f"(d[11]),"+f"(d[12]),"+f"(d[13]),"+f"(d[14]),"+f"(d[15]),"+f"(d[16]),"+f"(d[17]),"+f"(d[18]),"+f"(d[19]),"+f"(d[20]),"+f"(d[21]),"+f"(d[22]),"+f"(d[23]),"+f"(d[24]),"+f"(d[25]),"+f"(d[26]),"+f"(d[27]),"+f"(d[28]),"+f"(d[29]),"+f"(d[30]),"+f"(d[31]),"+f"(d[32]),"+f"(d[33]),"+f"(d[34]),"+f"(d[35]),"+f"(d[36]),"+f"(d[37]),"+f"(d[38]),"+f"(d[39]),"+f"(d[40]),"+f"(d[41]),"+f"(d[42]),"+f"(d[43]),"+f"(d[44]),"+f"(d[45]),"+f"(d[46]),"+f"(d[47]),"+f"(d[48]),"+f"(d[49]),"+f"(d[50]),"+f"(d[51]),"+f"(d[52]),"+f"(d[53]),"+f"(d[54]),"+f"(d[55]),"+f"(d[56]),"+f"(d[57]),"+f"(d[58]),"+f"(d[59]),"+f"(d[60]),"+f"(d[61]),"+f"(d[62]),"+f"(d[63]),"+f"(d[64]),"+f"(d[65]),"+f"(d[66]),"+f"(d[67]),"+f"(d[68]),"+f"(d[69]),"+f"(d[70]),"+f"(d[71]),"+f"(d[72]),"+f"(d[73]),"+f"(d[74]),"+f"(d[75]),"+f"(d[76]),"+f"(d[77]),"+f"(d[78]),"+f"(d[79]),"+f"(d[80]),"+f"(d[81]),"+f"(d[82]),"+f"(d[83]),"+f"(d[84]),"+f"(d[85]),"+f"(d[86]),"+f"(d[87]),"+f"(d[88]),"+f"(d[89]),"+f"(d[90]),"+f"(d[91]),"+f"(d[92]),"+f"(d[93]),"+f"(d[94]),"+f"(d[95])
   : "l"(da), "l"(db), "r"(sd));
}

__device__ __forceinline__ void stats_publish(uint32_t sb, int layer, int rb, int hg, int ht, uint32_t tag) {
  const int lane = ht & 31, w = ht >> 5, g = lane >> 2, t = lane & 3, ks = hg & 3;
  uint32_t xa;
  if (layer == 0) {
    const int row = 16 * w + (lane & 15), kc = 2 * ks + (lane >> 4);
    xa = row * 128 + ((kc ^ (row & 7)) << 4);
  } else {
    const int k = 16 * ks + (lane & 7) + 8 * (lane >> 4), pc = 2 * w + ((lane >> 3) & 1);
    xa = k * 128 + ((pc ^ (k & 7)) << 4);
  }
  float s[4] = {0.f, 0.f, 0.f, 0.f}, q[4] = {0.f, 0.f, 0.f, 0.f};
#pragma unroll 1
  for (int c = hg >> 2; c < 8; c += 2) {
    mbar_wait(sb + SM_BAR + 8 * (B_XF + c), layer);
    if (c >= 6) ATS(48, 256);
    if (c < 2) ATS(51, 256);
    uint32_t A[2][4];
#pragma unroll
    for (int h = 0; h < 2; h++) {
      if (layer == 0) ldsm4(A[h], sb + SM_X + c * 16384 + h * 8192 + xa);
      else ldsm4t(A[h], sb + SM_X + c * 16384 + h * 8192 + xa);
    }
#pragma unroll
    for (int r = 0; r < 4; r++)
#pragma unroll
      for (int i = 0; i < 2; i++) {
        const uint32_t v = A[r >> 1][2 * i + (r & 1)];
        const float a = bf_lo(v), b = bf_hi(v);
        s[r] += a + b; q[r] = fmaf(a, a, q[r]); q[r] = fmaf(b, b, q[r]);
      }
  }
#pragma unroll
  for (int r = 0; r < 2; r++) {
    s[r] = ((t & 2) ? s[r + 2] : s[r]) + __shfl_xor_sync(~0u, (t & 2) ? s[r] : s[r + 2], 2);
    q[r] = ((t & 2) ? q[r + 2] : q[r]) + __shfl_xor_sync(~0u, (t & 2) ? q[r] : q[r + 2], 2);
  }
  s[0] = ((t & 1) ? s[1] : s[0]) + __shfl_xor_sync(~0u, (t & 1) ? s[0] : s[1], 1);
  q[0] = ((t & 1) ? q[1] : q[0]) + __shfl_xor_sync(~0u, (t & 1) ? q[0] : q[1], 1);
  st_part(&g_part[(rb * 8 + hg) * 128 + 64 * (t >> 1) + 16 * w + 8 * (t & 1) + g], s[0], q[0], tag);
  ATS(49, 256);
}
__device__ __forceinline__ void stats_gather(uint32_t sb, int rb, int ht, uint32_t tag) {
  const uint2* src = &g_part[rb * 8 * 128 + ht];
  uint2 v[8];
  bool ok;
  int it = 0;
  do {
    ok = true;
#pragma unroll
    for (int i = 0; i < 8; i++) v[i] = ld_part(src + i * 128);
#pragma unroll
    for (int i = 0; i < 8; i++) ok = ok && (v[i].y & 7u) == tag;
    if (++it > (1 << 22)) __trap();
  } while (!__all_sync(~0u, ok));
  float s = 0.f, q = 0.f;
#pragma unroll
  for (int i = 0; i < 8; i++) { s += __uint_as_float(v[i].x); q += __uint_as_float(v[i].y); }
  const float mean = s * (1.f / DM);
  const float rstd = rsqrt_approx(fmaxf(q * (1.f / DM) - mean * mean, 0.f) + 1e-5f);
  asm volatile("st.shared.v2.f32 [%0], {%1,%2};" ::"r"(sb + SM_ST + ht * 8), "f"(mean), "f"(rstd) : "memory");
  __syncwarp();
  if (elect_one()) mbar_arrive(sb + SM_BAR + 8 * B_STF);
}
__device__ __forceinline__ void halo_receive(uint32_t sb, int layer, int rb, int hg, int ht) {
  const int lane = ht & 31, h = ht >> 5;
  uint4 k4 = make_uint4(0, 0, 0, 0), v4 = k4;
  mbar_wait(sb + SM_BAR + 8 * B_SD, layer);
  if (rb > 0) {
    const uint32_t tag = 2 * lds32(sb + SM_EP) + layer + 1;
    const uint4* src = &g_halo[((rb - 1) * 8 + hg) * 384 + h * 96 + lane];
    delay<D_HALO>();
    uint4 a, b, c;
    int it = 0;
    do {
      a = ld_tagged(src); b = ld_tagged(src + 32); c = ld_tagged(src + 64);
      if (++it > (1 << 22)) __trap();
    } while (!__all_sync(~0u, a.w == tag && b.w == tag && c.w == tag));
    k4 = make_uint4(a.x, a.z, a.y, b.x);
    v4 = make_uint4(movm_t(b.y), movm_t(b.z), movm_t(c.x), movm_t(c.y));
  }
  sts128(sb + SM_KVX + h * 1024 + lane * 16, k4);
  sts128(sb + SM_KVX + h * 1024 + 512 + lane * 16, v4);
  ATS(61, 256);
  bar_arrive(7, 160);
  if (elect_one()) mbar_arrive(sb + SM_BAR + 8 * B_HF);
}

template <bool TR>
__device__ __forceinline__ void gemm_section(float* acc, float2* cs, uint32_t sb, int layer, int wg, int w, int lane) {
  const uint32_t bar = sb + SM_BAR;
  const bool leader = (w == 0) && (lane == 0);
  auto issue = [&](int c, int slot) {
    mbar_wait(bar + 8 * (B_XF + c), layer);
    mbar_wait(bar + 8 * (B_KVF + c), layer);
    const uint64_t da = mkdesc(sb + SM_X + c * 16384 + wg * 8192, TR ? 8192 : 16, 1024, 1);
    const uint64_t db = mkdesc(sb + SM_W + slot * 24576, 8192, 1024, 1);
    wg_fence();
#pragma unroll
    for (int ks = 0; ks < 4; ks++) wgmma_ss<192, TR ? 1 : 0, 1>(acc, da + (TR ? ks * 128 : ks * 2), db + ks * 128, (c | ks) != 0);
    wg_commit();
  };
  auto step = [&](int c, int slot) {
    issue(c, slot);
    wg_wait<1>();
    if (leader) mbar_arrive(bar + 8 * (B_KVE + c - 1));
  };
  issue(0, 0);
  if (threadIdx.x == 0) TS(2 + layer * 20 + 0);
  if (threadIdx.x == 128 && layer == 1) TS(60);
  step(1, 1); step(2, 2); step(3, 0); step(4, 1);
  auto ld_cs = [&](int j0) {
#pragma unroll
    for (int j = j0; j < j0 + 8; j++) cs[j] = lds64f(sb + SM_CS + 4 * (8 * j + 2 * (lane & 3)));
  };
  if (TR) ld_cs(8);
  step(5, 2);
  if (!TR) { mbar_wait(bar + 8 * B_CSF, 0); ld_cs(8); }
  ld_cs(16);
  if (wg == 0) bar_sync(5, 256);
  issue(6, 0);
  issue(7, 1);
  if (wg == 1) bar_arrive(5, 256);
}

__device__ __forceinline__ void attn_phase(const Params& p, uint32_t sb, int layer, int rb, int hg, int wg, int w) {
  const int lane = opaque_tid() & 31;
  const int g = lane >> 2, t = lane & 3;
  const uint32_t bar = sb + SM_BAR;
  const int row0 = 64 * wg + 16 * w;
  const bool leader = (w == 0) && (lane == 0);
  float acc[96];
  float2 cs[24];
  if (layer) gemm_section<true>(acc, cs, sb, layer, wg, w, lane);
  else gemm_section<false>(acc, cs, sb, layer, wg, w, lane);
  ATS(41, 224);
  mbar_wait(bar + 8 * B_STF, layer);
  const uint32_t tag = 2 * lds32(sb + SM_EP) + layer + 1;
  const float2 st0 = lds64f(sb + SM_ST + (row0 + g) * 8), st1 = lds64f(sb + SM_ST + (row0 + g + 8) * 8);
  const float mean0 = st0.x, rstd0 = st0.y, mean1 = st1.x, rstd1 = st1.y;
  wg_wait<0>();
  if (threadIdx.x == 0) TS(2 + layer * 20 + 1);
  ATS(39, 224);
  if (leader) mbar_arrive(bar + 8 * B_QDONE);

  uint32_t kb[4][8], vb[4][8], qa[4][4];
  {
    const float nm0 = -mean0 * rstd0, nm1 = -mean1 * rstd1;
    const int cw = 4 * wg + w;
    const uint32_t kvx = sb + SM_KVX + cw * 4096 + lane * 16;
    uint4* halo = &g_halo[(rb * 8 + hg) * 384 + lane];
#pragma unroll
    for (int h = 0; h < 4; h++) {
      uint32_t r[2][4];
#pragma unroll
      for (int kv = 0; kv < 2; kv++) {
#pragma unroll
        for (int dh = 0; dh < 2; dh++) {
          const int j = 8 + kv * 8 + 2 * h + dh;
          const float2 c2 = cs[j];
          const float v0 = fmaf(acc[4 * j + 0], rstd0, nm0 * c2.x), v1 = fmaf(acc[4 * j + 1], rstd0, nm0 * c2.y);
          const float v2 = fmaf(acc[4 * j + 2], rstd1, nm1 * c2.x), v3 = fmaf(acc[4 * j + 3], rstd1, nm1 * c2.y);
          r[kv][2 * dh] = packbf(v0, v1);
          r[kv][2 * dh + 1] = packbf(v2, v3);
        }
      }
      if (cw == 7) {
        st_tagged3(halo + (3 * h) * 32, r[0][0], r[0][1], r[0][2], tag);
        st_tagged3(halo + (3 * h + 1) * 32, r[0][3], r[1][0], r[1][1], tag);
        st_tagged3(halo + (3 * h + 2) * 32, r[1][2], r[1][3], 0u, tag);
      }
      kb[h][4] = r[0][0]; kb[h][5] = r[0][2]; kb[h][6] = r[0][1]; kb[h][7] = r[0][3];
#pragma unroll
      for (int k = 0; k < 4; k++) vb[h][4 + k] = movm_t(r[1][k]);
    }
    if (cw == 7) {
      if (elect_one()) mbar_arrive(bar + 8 * B_SD);
      if (layer == TLAYER && threadIdx.x == 224) TS(47);
    } else {
#pragma unroll
      for (int h = 0; h < 4; h++) {
        sts128(kvx + 4096 + h * 1024, make_uint4(kb[h][4], kb[h][5], kb[h][6], kb[h][7]));
        sts128(kvx + 4096 + h * 1024 + 512, make_uint4(vb[h][4], vb[h][5], vb[h][6], vb[h][7]));
      }
      bar_arrive(8 + cw, 64);
    }
    if (layer == TLAYER && threadIdx.x == 0) TS(45);
#pragma unroll
    for (int j = 0; j < 8; j++) cs[j] = lds64f(sb + SM_CS + 4 * (8 * j + 2 * t));
#pragma unroll
    for (int h = 0; h < 4; h++) {
#pragma unroll
      for (int dh = 0; dh < 2; dh++) {
        const int j = 2 * h + dh;
        const float2 c2 = cs[j];
        qa[h][2 * dh] = packbf(fmaf(-mean0, c2.x, acc[4 * j + 0]), fmaf(-mean0, c2.y, acc[4 * j + 1]));
        qa[h][2 * dh + 1] = packbf(fmaf(-mean1, c2.x, acc[4 * j + 2]), fmaf(-mean1, c2.y, acc[4 * j + 3]));
      }
    }
    if (threadIdx.x == 0) TS(2 + layer * 20 + 2);
    bar_sync(7 + cw, cw == 0 ? 160 : 64);
#pragma unroll
    for (int h = 0; h < 4; h++) {
      const uint4 k4 = lds128(kvx + h * 1024), v4 = lds128(kvx + h * 1024 + 512);
      kb[h][0] = k4.x; kb[h][1] = k4.y; kb[h][2] = k4.z; kb[h][3] = k4.w;
      vb[h][0] = v4.x; vb[h][1] = v4.y; vb[h][2] = v4.z; vb[h][3] = v4.w;
    }
    if (threadIdx.x == 0) TS(2 + layer * 20 + 4);
  }

  const bool first = (rb == 0 && wg == 0 && w == 0);
  const int e = t - (g >> 1);
  const bool par = g & 1, epos = e >= 1;
  const uint32_t pmask = par ? 0xffff0000u : 0x0000ffffu;
  const uint32_t mB0 = epos ? pmask : 0u, mB1 = epos ? 0u : pmask;
  const float cl2 = 0.25f * 1.4426950408889634f;
  const float sc0 = rstd0 * cl2, sc1 = rstd1 * cl2;
  const float NEG = -INFINITY;
  float vA0[4], vB0[4], vA1[4], vB1[4];
#pragma unroll
  for (int h = 0; h < 4; h++) {
    float S[4][4];
#pragma unroll
    for (int j = 0; j < 4; j++) {
      S[j][0] = S[j][1] = S[j][2] = S[j][3] = 0.f;
      mma_bf16(S[j], qa[h], kb[h][2 * j], kb[h][2 * j + 1]);
    }
    vA0[h] = par ? S[1][1] : S[1][0];
    vB0[h] = epos ? (par ? S[0][1] : S[0][0]) : (par ? S[2][1] : S[2][0]);
    vA1[h] = par ? S[2][3] : S[2][2];
    vB1[h] = epos ? (par ? S[1][3] : S[1][2]) : (par ? S[3][3] : S[3][2]);
    if (first) { vA0[h] = NEG; if (epos) { vB0[h] = NEG; vB1[h] = NEG; } }
  }
  float m0[4], m1[4];
#pragma unroll
  for (int h = 0; h < 4; h++) { m0[h] = fmaxf(vA0[h], vB0[h]); m1[h] = fmaxf(vA1[h], vB1[h]); }
#pragma unroll
  for (int o = 1; o <= 2; o <<= 1) {
#pragma unroll
    for (int h = 0; h < 4; h++) {
      m0[h] = fmaxf(m0[h], __shfl_xor_sync(~0u, m0[h], o));
      m1[h] = fmaxf(m1[h], __shfl_xor_sync(~0u, m1[h], o));
    }
  }
  float O0[4][4], O1[4][4], Z[4][4];
#pragma unroll
  for (int h = 0; h < 4; h++) {
    const float mm0 = -m0[h] * sc0, mm1 = -m1[h] * sc1;
    const float pA0 = ex2(fmaf(vA0[h], sc0, mm0)), pB0 = ex2(fmaf(vB0[h], sc0, mm0));
    const float pA1 = ex2(fmaf(vA1[h], sc1, mm1)), pB1 = ex2(fmaf(vB1[h], sc1, mm1));
    const uint32_t hA0 = packbf(pA0, pA0), hB0 = packbf(pB0, pB0), hA1 = packbf(pA1, pA1), hB1 = packbf(pB1, pB1);
    const uint32_t P0[4] = {hB0 & mB0, 0u, hA0 & pmask, hB1 & mB0};
    const uint32_t P1[4] = {hB0 & mB1, hA1 & pmask, 0u, hB1 & mB1};
#pragma unroll
    for (int k = 0; k < 4; k++) O0[h][k] = O1[h][k] = Z[h][k] = 0.f;
    mma_bf16(O0[h], P0, vb[h][0], vb[h][1]); mma_bf16(O1[h], P0, vb[h][2], vb[h][3]); mma_bf16(Z[h], P0, 0x3f803f80u, 0x3f803f80u);
    mma_bf16(O0[h], P1, vb[h][4], vb[h][5]); mma_bf16(O1[h], P1, vb[h][6], vb[h][7]); mma_bf16(Z[h], P1, 0x3f803f80u, 0x3f803f80u);
  }
  const uint32_t ob = sb + SM_OST + wg * 8192;
  const int o_row = 16 * w + (lane & 7) + 8 * ((lane >> 3) & 1);
#pragma unroll
  for (int h = 0; h < 4; h++) {
    const float i0 = rcp_approx(Z[h][0]), i1 = rcp_approx(Z[h][2]);
    const int ch = 2 * h + (lane >> 4);
    stsm4(ob + o_row * 128 + ((ch ^ (o_row & 7)) << 4), packbf(O0[h][0] * i0, O0[h][1] * i0), packbf(O0[h][2] * i1, O0[h][3] * i1),
          packbf(O1[h][0] * i0, O1[h][1] * i0), packbf(O1[h][2] * i1, O1[h][3] * i1));
  }
  if (threadIdx.x == 0) TS(2 + layer * 20 + 5);
  ATS(57, 128); ATS(20, 96);
  fence_writer();
  bar_sync(2 + wg, 128);
  if (w == 0 && elect_one()) {
    fence_reader();
    tma_st(&p.mapO, hg * 64, rb * 128 + wg * 64, ob);
    bulk_commit();
    mbar_arrive(bar + 8 * B_AD);
    bulk_wait_all();
    red_relaxed(&g_cnt[(C_O + rb) * 32]);
    mbar_arrive(bar + 8 * B_OST);
    if (threadIdx.x == 0) TS(2 + layer * 20 + 6);
  }
}

__device__ __forceinline__ void proj_phase(const Params& p, uint32_t sb, int layer, int rb, int q, int wg, int w) {
  const int lane = opaque_tid() & 31;
  const bool TR = layer != 0;
  const int t = lane & 3;
  const uint32_t bar = sb + SM_BAR;
  const uint32_t rbx = sb + SM_R + wg * 8192;
  uint32_t res[16];
  mbar_wait(bar + 8 * B_RF, layer);
  if (threadIdx.x == 0) TS(2 + layer * 20 + 7);
  if (!TR) {
#pragma unroll
    for (int j = 0; j < 8; j += 2) {
      const int mi = lane >> 3;
      const int row = 16 * w + (lane & 7) + 8 * (mi & 1), ch = j + (mi >> 1);
      ldsm4(&res[2 * j], rbx + row * 128 + ((ch ^ (row & 7)) << 4));
    }
  } else {
#pragma unroll
    for (int j = 0; j < 8; j += 2) {
      const int mi = lane >> 3;
      const int line = 8 * (j + (mi >> 1)) + (lane & 7), pc = 2 * w + (mi & 1);
      ldsm4t(&res[2 * j], rbx + line * 128 + ((pc ^ (line & 7)) << 4));
    }
  }
  bar_sync(2 + wg, 128);
  float acc[32];
#pragma unroll
  for (int i = 0; i < 16; i++) {
    asm volatile("shl.b32 %0, %1, 16;" : "=f"(acc[2 * i]) : "r"(res[i]));
    asm volatile("and.b32 %0, %1, 0xffff0000;" : "=f"(acc[2 * i + 1]) : "r"(res[i]));
  }
  const uint32_t tag = part_tag(lds32(sb + SM_EP), 2 * layer + 1);
#pragma unroll 1
  for (int c = 0; c < 8; c++) {
    if ((c & 1) == 0) mbar_wait(bar + 8 * (B_WOF + (c >> 1)), layer);
    mbar_wait(bar + 8 * (B_OF + c), layer);
    if (c == 0 && threadIdx.x == 0) TS(2 + layer * 20 + 8);
    const uint64_t da = mkdesc(sb + sm_o(c) + wg * 8192, 16, 1024, 1);
    const uint64_t db = mkdesc(sb + SM_WO + c * 8192, 8192, 1024, 1);
    wg_fence();
#pragma unroll
    for (int ks = 0; ks < 4; ks++) wgmma_ss<64, 0, 1>(acc, da + ks * 2, db + ks * 128, 1);
    wg_commit();
  }
  wg_wait<0>();
#pragma unroll
  for (int i = 0; i < 32; i++) asm volatile("" : "+f"(acc[i]) :: "memory");
  if (threadIdx.x == 0) TS(2 + layer * 20 + 9);
  if (lane == 0 && w == 0) mbar_arrive(bar + 8 * B_PDONE);
  {
    float s[4], qq[4];
#pragma unroll
    for (int k = 0; k < 4; k++) { s[k] = acc[k]; qq[k] = acc[k] * acc[k]; }
#pragma unroll
    for (int j = 1; j < 8; j++)
#pragma unroll
      for (int k = 0; k < 4; k++) { s[k] += acc[4 * j + k]; qq[k] = fmaf(acc[4 * j + k], acc[4 * j + k], qq[k]); }
    const float s0 = s[0] + s[1], s1 = s[2] + s[3], q0 = qq[0] + qq[1], q1 = qq[2] + qq[3];
    float sr = ((t & 1) ? s1 : s0) + __shfl_xor_sync(~0u, (t & 1) ? s0 : s1, 1);
    float qr = ((t & 1) ? q1 : q0) + __shfl_xor_sync(~0u, (t & 1) ? q0 : q1, 1);
    sr += __shfl_xor_sync(~0u, sr, 2);
    qr += __shfl_xor_sync(~0u, qr, 2);
    if (t < 2) st_part(&g_part[(rb * 8 + q) * 128 + 64 * wg + 16 * w + (lane >> 2) + 8 * t], sr, qr, tag);
    __syncwarp();
    if (elect_one()) mbar_arrive(bar + 8 * B_PS);
  }
#pragma unroll
  for (int j = 0; j < 8; j += 2) {
    const int mi = lane >> 3;
    const int line = 8 * (j + (mi >> 1)) + (lane & 7), pc = 2 * w + (mi & 1);
    stsm4t(rbx + line * 128 + ((pc ^ (line & 7)) << 4), packbf(acc[4 * j], acc[4 * j + 1]), packbf(acc[4 * j + 2], acc[4 * j + 3]),
           packbf(acc[4 * j + 4], acc[4 * j + 5]), packbf(acc[4 * j + 6], acc[4 * j + 7]));
  }
  fence_writer();
  bar_sync(2 + wg, 128);
  if (w == 0 && elect_one()) {
    fence_reader();
    mbar_wait(bar + 8 * B_ZF, layer);
    fence_async_global();
    tma_st(&p.mapXT, rb * 128 + wg * 64, (2 * layer) * DM + q * 64, rbx);
    bulk_commit();
    if (threadIdx.x == 0) TS(2 + layer * 20 + 10);
    asm volatile("cp.async.bulk.wait_group.read 0;" ::: "memory");
    if (wg == 0) mbar_arrive(bar + 8 * B_RE);
  }
}
__device__ __forceinline__ void proj_stats(int layer, int rb, int q, int lane, uint32_t tag) {
  const int r = 16 * q + (lane & 15);
  const uint2* src = &g_part[(rb * 8 + (lane >> 4) * 4) * 128 + r];
  uint2 v[4];
  bool ok;
  int it = 0;
  do {
    ok = true;
#pragma unroll
    for (int i = 0; i < 4; i++) v[i] = ld_part(src + i * 128);
#pragma unroll
    for (int i = 0; i < 4; i++) ok = ok && (v[i].y & 7u) == tag;
    if (++it > (1 << 22)) __trap();
  } while (!__all_sync(~0u, ok));
  float s = (__uint_as_float(v[0].x) + __uint_as_float(v[1].x)) + (__uint_as_float(v[2].x) + __uint_as_float(v[3].x));
  float qq = (__uint_as_float(v[0].y) + __uint_as_float(v[1].y)) + (__uint_as_float(v[2].y) + __uint_as_float(v[3].y));
  s += __shfl_xor_sync(~0u, s, 16);
  qq += __shfl_xor_sync(~0u, qq, 16);
  const float mean = s * (1.f / DM);
  const float rstd = rsqrt_approx(fmaxf(fmaf(qq, 1.f / DM, -mean * mean), 0.f) + 1e-5f), nm = -mean * rstd;
  const float nm1 = __shfl_xor_sync(~0u, nm, 1), rstd1 = __shfl_xor_sync(~0u, rstd, 1);
  if ((lane & 17) == 0)
    st_tagged3((uint4*)g_stats + (layer * 32 + rb * 2 + (r >> 6)) * 32 + ((r & 7) >> 1) * 8 + ((r >> 3) & 7),
               __float_as_uint(nm), __float_as_uint(rstd) | 1u, __float_as_uint(nm1), __float_as_uint(rstd1));
}

#define NA 8
template <bool GB> __host__ __device__ constexpr int grp_n() { return GB ? 17 - NA : NA; }
template <bool GB> __host__ __device__ constexpr int grp_m(int i) { return i == 0 ? (GB ? 1 : 0) : (GB ? NA + i : 1 + i); }
template <bool GB> __device__ __forceinline__ void conv_load(uint32_t* A, uint32_t pe) {
#pragma unroll
  for (int i = 0; i < grp_n<GB>(); i++) {
    A[4 * i + 2] = lds32(pe + 4 * (64 * grp_m<GB>(i) - 8));
    A[4 * i + 0] = lds32(pe + 4 * (64 * grp_m<GB>(i)));
    A[4 * i + 1] = lds32(pe + 4 * (64 * grp_m<GB>(i) + 8));
  }
}
template <bool GB> __device__ __forceinline__ void conv_dup_early(uint32_t* A, uint32_t zero) {
#pragma unroll
  for (int i = 0; i < grp_n<GB>(); i++) asm volatile("or.b32 %0, %1, %2;" : "=r"(A[4 * i + 3]) : "r"(A[4 * i + 0]), "r"(zero));
}
template <bool GB> __device__ __forceinline__ void conv_dup(uint32_t* A) {
#pragma unroll
  for (int i = 0; i < grp_n<GB>(); i++) asm volatile("mov.b32 %0, %1;" : "=r"(A[4 * i + 3]) : "r"(A[4 * i + 0]));
}
template <bool GB, int I0, int I1> __device__ __forceinline__ void conv_mmas(float* acc, const uint32_t* A, uint64_t d) {
  if constexpr (I0 < I1) {
    constexpr int M = grp_m<GB>(I0);
    wgmma_rs<128 - 8 * (M / 2), 0>(acc, A + 4 * I0, d + (uint64_t)(4 * M), M != 0);
    conv_mmas<GB, I0 + 1, I1>(acc, A, d);
  }
}
struct SumAddr { uint32_t l0, l1, se, so; };
__device__ __forceinline__ SumAddr conv_sum_addr(uint32_t sb, int c) {
  const int m = c == 127 ? -1 : c;
  const uint32_t up = m >= 1 ? ((m - 1) & 1) * CV_UH + (127 - ((m - 1) >> 1)) * 16 + 8 : 128 * 16;
  const uint32_t un = ((m + 1) & 1) * CV_UH + (127 - ((m + 1) >> 1)) * 16;
  const int ce = (m + 2) & 127, co = m + 1;
  return {sb + cv_u(0) + ((c & 1) ? un : up), sb + cv_u(0) + ((c & 1) ? up : un),
          sb + cv_s(0) + ((ce >> 3) & 1) * 1024 + (ce >> 4) * 128 + (((ce ^ (ce >> 4)) & 7) << 4),
          sb + cv_s(0) + 2048 + ((co >> 3) & 1) * 1024 + (co >> 4) * 128 + (((co ^ (co >> 4)) & 7) << 4)};
}
__device__ __forceinline__ void conv_sums(const SumAddr& sa, int lc, int c, uint4 own) {
  if (c == 127) own = make_uint4(0, 0, 0, 0);
  const bool odd = c & 1;
  const float2 v0 = lds64f(sa.l0 + lc * 32768), v1 = lds64f(sa.l1 + lc * 32768);
  const uint32_t x[8] = {__float_as_uint(odd ? v1.x : v0.x), __float_as_uint(odd ? v1.y : v0.y), own.x, own.y, own.z, own.w,
                         __float_as_uint(odd ? v0.x : v1.x), __float_as_uint(odd ? v0.y : v1.y)};
  float pv[16];
#pragma unroll
  for (int k = 0; k < 8; k++) { pv[2 * k] = bf_lo(x[k]); pv[2 * k + 1] = bf_hi(x[k]); }
  float sf[8], pf[8], s9[8], s7[8];
  sf[7] = pv[7]; pf[0] = pv[8];
#pragma unroll
  for (int i = 6; i >= 0; i--) sf[i] = sf[i + 1] + pv[i];
#pragma unroll
  for (int i = 1; i < 8; i++) pf[i] = pf[i - 1] + pv[8 + i];
#pragma unroll
  for (int i = 0; i < 8; i++) {
    s9[i] = sf[i] + pf[i];
    s7[i] = i == 0 ? sf[1] : i == 7 ? pf[6] : sf[i + 1] + pf[i - 1];
  }
  uint4 e4 = make_uint4(packbf(s9[0], s9[1]), packbf(s9[2], s9[3]), packbf(s9[4], s9[5]), packbf(s9[6], s9[7]));
  if (c == 126) e4 = make_uint4(0, 0, 0, 0);
  sts128(sa.se + lc * 32768, e4);
  sts128(sa.so + lc * 32768, make_uint4(packbf(s7[0], s7[1]), packbf(s7[2], s7[3]), packbf(s7[4], s7[5]), packbf(s7[6], s7[7])));
}

__device__ __forceinline__ void conv_epi(uint32_t sb, int layer, int cta, int ch, int c0, uint4 x0, uint4 x1) {
  uint4 v[2][4];
  const uint4 xr[2] = {x0, x1};
  mbar_wait(sb + SM_BAR + 8 * (B_P + ch), layer);
#pragma unroll
  for (int u = 0; u < 2; u++) {
    const int c = c0 + 128 * u;
    const uint32_t pb = sb + cv_pb(ch) + (c ^ ((c >> 3) & 1)) * 16;
#pragma unroll
    for (int k = 0; k < 4; k++) v[u][k] = lds128(pb + k * CV_PBW);
  }
#pragma unroll
  for (int u = 0; u < 2; u++) {
    uint4 o;
    o.x = hadd2(xr[u].x, hadd2(hadd2(v[u][0].x, v[u][1].x), hadd2(v[u][2].x, v[u][3].x)));
    o.y = hadd2(xr[u].y, hadd2(hadd2(v[u][0].y, v[u][1].y), hadd2(v[u][2].y, v[u][3].y)));
    o.z = hadd2(xr[u].z, hadd2(hadd2(v[u][0].z, v[u][1].z), hadd2(v[u][2].z, v[u][3].z)));
    o.w = hadd2(xr[u].w, hadd2(hadd2(v[u][0].w, v[u][1].w), hadd2(v[u][2].w, v[u][3].w)));
    if (layer == 0) sts128(sb + cv_s(ch) + (c0 + 128 * u) * 16, o);
    else st_tagged3((uint4*)(g_xT + (size_t)(3 * DM + cv_chan(cta, ch)) * LSEQ) + c0 + 128 * u, o.x, o.y, o.z, o.w);
  }
}
__device__ __forceinline__ void warp_release(uint32_t b) {
  fence_writer();
  __syncwarp();
  if (elect_one()) mbar_arrive(b);
}

__device__ __forceinline__ void conv_prep_load(uint32_t sb, int layer, int cta, int c, uint4 (&xr)[4], uint4 (&st)[4]) {
  mbar_wait(sb + SM_BAR + 8 * B_GB, layer);
  if (threadIdx.x == 0) TS(2 + layer * 20 + 11);
  xr[0] = ld_tagged((const uint4*)(g_xT + (size_t)(2 * layer * DM + cta) * LSEQ) + c);
#pragma unroll
  for (int i = 0; i < 4; i++) st[i] = ld_tagged((const uint4*)g_stats + (layer * 32 + (c >> 3)) * 32 + i * 8 + (c & 7));
}
template <bool HELPER>
__device__ __forceinline__ void conv_prep(uint32_t sb, int layer, int cta, int c, uint4 (&xr)[4], uint4 (&st)[4], uint4 (&un)[4], const SumAddr& sa) {
  const uint32_t bar = sb + SM_BAR;
  const uint4* xin = (const uint4*)(g_xT + (size_t)(2 * layer * DM + cta) * LSEQ) + c;
  for (int it = 0;; it++) {
    const bool okx = __all_sync(~0u, xr[0].x != ~0u);
    const bool oks = __all_sync(~0u, (st[0].y & st[1].y & st[2].y & st[3].y & 1u) != 0);
    if (okx && oks) break;
    if (it > (1 << 22)) __trap();
    if (!okx) xr[0] = ld_tagged(xin);
    if (!oks) {
#pragma unroll
      for (int i = 0; i < 4; i++) st[i] = ld_tagged((const uint4*)g_stats + (layer * 32 + (c >> 3)) * 32 + i * 8 + (c & 7));
    }
  }
  if (threadIdx.x == 0) TS(2 + layer * 20 + 12);
  const int a = c >> 1, h = c & 1;
#pragma unroll
  for (int i = 0; i < 4; i++) {
    if (i == 1) {
#pragma unroll
      for (int j = 1; j < 4; j++) xr[j] = ld_tagged(xin + j * (128 * LSEQ / 8));
      if (HELPER) {
        bar_sync(4, 128);
        conv_sums(sa, 0, c, un[0]);
        fence_async_smem();
        warp_release(bar + 8 * B_S);
        if (layer == 1 && c == 0) TS(46);
        mbar_wait(bar + 8 * B_GB, layer);
      }
      for (int it = 0; !__all_sync(~0u, xr[1].x != ~0u && xr[2].x != ~0u && xr[3].x != ~0u); it++) {
        if (it > (1 << 22)) __trap();
#pragma unroll
        for (int j = 1; j < 4; j++) xr[j] = ld_tagged(xin + j * (128 * LSEQ / 8));
      }
    }
    const uint32_t x[4] = {xr[i].x, xr[i].y, xr[i].z, xr[i].w};
    uint32_t u[4];
#pragma unroll
    for (int k = 0; k < 4; k++)
      u[k] = packbf(fmaf(bf_lo(x[k]), __uint_as_float(st[k].y), __uint_as_float(st[k].x)), fmaf(bf_hi(x[k]), __uint_as_float(st[k].w), __uint_as_float(st[k].z)));
    un[i] = make_uint4(u[0], u[1], u[2], u[3]);
    sts128(sb + cv_u(i) + h * CV_UH + (127 - a) * 16, un[i]);
    warp_release(bar + 8 * (B_U + i));
  }
}
__device__ __forceinline__ void conv_zero(uint32_t sb, int ht) {
  if (ht < 96) {
    const int ch = ht / 24, h2 = (ht / 12) & 1, qq = ht % 12;
    sts128(sb + cv_u(ch) + h2 * CV_UH + (128 + qq) * 16, make_uint4(0, 0, 0, 0));
  }
  if (ht >= 80) {
    const int i = ht - 80, ch = i / 12, q2 = i % 12;
    const int w2 = q2 < 2 ? 1 : q2 < 6 ? 2 : 3, cc = q2 < 2 ? q2 : q2 < 6 ? q2 - 2 : q2 - 6;
    sts128(sb + cv_pb(ch) + w2 * CV_PBW + cc * 16, make_uint4(0, 0, 0, 0));
  }
}

#define LD_AT 0
#define HANDOVER 12
template <int R>
__device__ __forceinline__ void conv_round(uint32_t sb, int layer, int wg, uint32_t* FA, uint32_t* FB, uint32_t pb, uint32_t pe2) {
  const uint32_t bar = sb + SM_BAR;
  const int ch = 2 * R + 1 - wg;
  float acc[64];
  const uint64_t d = mkdesc(sb + cv_u(ch), CV_UH, 128, 0);
  const bool leader = (opaque_tid() & 127) == 0;
  FTS(39);
  if (R == 0) {
    mbar_wait(bar + 8 * (B_U + ch), layer);
    fence_reader();
  }
  if (ch > 0) mbar_wait(bar + 8 * (B_T + ch - 1), layer);
  FTS(41);
  if (ch == 0 && threadIdx.x == 128) TS(2 + layer * 20 + 13);
  if (R == 1 && LD_AT == 0) conv_load<true>(FB, pe2);
  wg_fence();
  conv_mmas<false, 0, (HANDOVER < NA ? HANDOVER : NA)>(acc, FA, d);
  if (HANDOVER <= NA) mbar_arrive_if(bar + 8 * (B_T + ch), leader);
  conv_mmas<false, (HANDOVER < NA ? HANDOVER : NA), NA>(acc, FA, d);
  wg_commit();
  if (R == 1 && LD_AT == 1) conv_load<true>(FB, pe2);
  FTS(51);
  mbar_wait(bar + 8 * (B_S + ch), layer);
  if (R == 1) conv_dup<true>(FB);
  wg_fence();
  conv_mmas<true, 0, (HANDOVER > NA ? HANDOVER - NA : 0)>(acc, FB, d);
  if (HANDOVER > NA) mbar_arrive_if(bar + 8 * (B_T + ch), leader);
  conv_mmas<true, (HANDOVER > NA ? HANDOVER - NA : 0), 17 - NA>(acc, FB, d);
  wgmma_ss<64, 1, 1>(acc, mkdesc(sb + cv_s(ch), 1024, 1024, 1), mkdesc(sb + cv_ft(ch), 256, 16, 0), 1);
  wgmma_ss<64, 1, 1>(acc, mkdesc(sb + cv_s(ch) + 2048, 1024, 1024, 1), mkdesc(sb + cv_ft(ch) + 512, 256, 16, 0), 1);
  wg_commit();
  FTS(61);
  wg_wait<0>();
#pragma unroll
  for (int j = 0; j < 16; j += 2)
    stsm4t(pb + R * 65536 - j * 256, packbf(acc[4 * j], acc[4 * j + 1]), packbf(acc[4 * j + 2], acc[4 * j + 3]),
           packbf(acc[4 * j + 4], acc[4 * j + 5]), packbf(acc[4 * j + 6], acc[4 * j + 7]));
  __syncwarp();
  if (elect_one()) mbar_arrive(bar + 8 * (B_P + ch));
  if (threadIdx.x == 0) TS(2 + layer * 20 + 14 + R);
  FTS(57);
  if (R == 0) {
    mbar_wait(bar + 8 * (B_S + ch + 2), layer);
    fence_reader();
  }
}
__device__ __forceinline__ void conv_phase(const Params& p, uint32_t sb, int layer, int cta) {
  const int tid = opaque_tid();
  const int wg = __shfl_sync(~0u, tid >> 7, 0), w = __shfl_sync(~0u, (tid >> 5) & 3, 0);
  const uint32_t bar = sb + SM_BAR;
  uint32_t FA0[4 * NA], FA1[4 * NA], FB[4 * (17 - NA)];
  const uint32_t pe = sb + cv_pe(1 - wg) + 4 * (16 + 16 * w + ((tid & 31) >> 2) - 2 * (tid & 3));
  mbar_wait(bar + 8 * B_PE, layer);
  conv_load<false>(FA0, pe); conv_load<true>(FB, pe);
  const uint32_t zero = tid >> 10;
  conv_dup_early<false>(FA0, zero); conv_dup_early<true>(FB, zero);
  if (wg == 0) {
    uint4 xr[4], st[4], un[4];
    conv_prep_load(sb, layer, cta, tid + 128, xr, st);
    conv_load<false>(FA1, pe + 65536);
    conv_dup_early<false>(FA1, zero);
    conv_prep<false>(sb, layer, cta, opaque_tid() + 128, xr, st, un, SumAddr());
  } else {
    conv_load<false>(FA1, pe + 65536);
    conv_dup_early<false>(FA1, zero);
  }
  uint32_t pb;
  {
    const int l2 = opaque_tid() & 31, mt = l2 >> 3;
    const int c = 2 * (127 - 8 * (mt >> 1) - (l2 & 7) + w) + (mt & 1);
    pb = sb + cv_pb(1 - wg) + w * CV_PBW + (c ^ ((c >> 3) & 1)) * 16;
  }
  conv_round<0>(sb, layer, wg, FA0, FB, pb, 0);
  conv_round<1>(sb, layer, wg, FA1, FB, pb, pe + 65536);
  if (wg == 1 && layer == 0) mbar_wait(bar + 8 * (B_T + 3), layer);
}

__device__ __forceinline__ void final_phase(const Params& p, uint32_t sb, int cta, int wg, int w) {
  if (wg == 1 && w == 3) return;
  const int lane = opaque_tid() & 31, g = lane >> 2, t = lane & 3;
  const int lc = wg ? w : 3;
  const int pos0 = (cta & 31) * 64, ch0 = 128 * lc + (cta >> 5) * 32;
  const bf16* src = g_xT + (size_t)(3 * DM + ch0 + 8 * (g >> 1) + (g & 1)) * LSEQ + pos0;
  bf16* dst = p.out + (size_t)pos0 * DM + ch0 + 8 * t;
  int it = 0;
  mbar_wait(sb + SM_BAR + 8 * (B_E + lc), 1);
  delay<D_FIN>();
  if (wg == 0) {
    uint2 v[4];
    do {
#pragma unroll
      for (int q = 0; q < 4; q++)
        asm volatile("ld.relaxed.gpu.global.v2.u32 {%0,%1}, [%2];" : "=r"(v[q].x), "=r"(v[q].y) : "l"(src + 2 * q * LSEQ + 16 * w + 4 * t) : "memory");
      if (++it > (1 << 22)) __trap();
    } while (!__all_sync(~0u, v[0].x != ~0u && v[1].x != ~0u && v[2].x != ~0u && v[3].x != ~0u));
    if (threadIdx.x == 0) TS(42);
    dst += (16 * w + 4 * (g >> 1) + (g & 1)) * DM;
    *(uint4*)dst = make_uint4(movm_t(v[0].x), movm_t(v[1].x), movm_t(v[2].x), movm_t(v[3].x));
    *(uint4*)(dst + 2 * DM) = make_uint4(movm_t(v[0].y), movm_t(v[1].y), movm_t(v[2].y), movm_t(v[3].y));
  } else {
    uint4 v[2][4];
    bool ok;
    do {
      ok = true;
#pragma unroll
      for (int h = 0; h < 2; h++)
#pragma unroll
        for (int q = 0; q < 4; q++) v[h][q] = ld_tagged((const uint4*)(src + 2 * q * LSEQ + 32 * h + 8 * t));
#pragma unroll
      for (int h = 0; h < 2; h++)
#pragma unroll
        for (int q = 0; q < 4; q++) ok = ok && v[h][q].x != ~0u;
      if (++it > (1 << 22)) __trap();
    } while (!__all_sync(~0u, ok));
    dst += (8 * (g >> 1) + (g & 1)) * DM;
#pragma unroll
    for (int h = 0; h < 2; h++) {
      *(uint4*)(dst + (32 * h + 0) * DM) = make_uint4(movm_t(v[h][0].x), movm_t(v[h][1].x), movm_t(v[h][2].x), movm_t(v[h][3].x));
      *(uint4*)(dst + (32 * h + 2) * DM) = make_uint4(movm_t(v[h][0].y), movm_t(v[h][1].y), movm_t(v[h][2].y), movm_t(v[h][3].y));
      *(uint4*)(dst + (32 * h + 4) * DM) = make_uint4(movm_t(v[h][0].z), movm_t(v[h][1].z), movm_t(v[h][2].z), movm_t(v[h][3].z));
      *(uint4*)(dst + (32 * h + 6) * DM) = make_uint4(movm_t(v[h][0].w), movm_t(v[h][1].w), movm_t(v[h][2].w), movm_t(v[h][3].w));
    }
  }
  if (threadIdx.x == 0) TS(43);
  if (threadIdx.x == 192) TS(63);
  if (threadIdx.x == 0) LTS(1);
}

struct cplx { float r, i; };
__device__ __forceinline__ cplx cmul(cplx a, cplx b) { return {fmaf(a.r, b.r, -a.i * b.i), fmaf(a.r, b.i, a.i * b.r)}; }
__device__ __forceinline__ cplx csqr(cplx a) { return {fmaf(a.r, a.r, -a.i * a.i), (a.r + a.r) * a.i}; }
__device__ __forceinline__ cplx cexp_l(float ar2, float ai, float l) {
  const float m = ex2(ar2 * l);
  const float x = ai * l;
  return {m * __cosf(x), m * __sinf(x)};
}

__device__ __forceinline__ void colsum_publish(uint32_t sb, int rb, int hg, int ht, uint32_t tag) {
  const int lane = ht & 31, q = lane & 15, h = lane >> 4;
  const uint32_t src = sb + SM_CW + (ht >> 5) * 4096 + h * 128 + (q & 1) * 8;
  float s[4] = {0.f, 0.f, 0.f, 0.f};
#pragma unroll
  for (int r = 0; r < 16; r++) {
    const float2 v = lds64f(src + r * 256 + (((q >> 1) ^ ((2 * r + h) & 7)) << 4));
    s[0] += bf_lo(__float_as_uint(v.x)); s[1] += bf_hi(__float_as_uint(v.x));
    s[2] += bf_lo(__float_as_uint(v.y)); s[3] += bf_hi(__float_as_uint(v.y));
  }
#pragma unroll
  for (int k = 0; k < 4; k++) s[k] += __shfl_xor_sync(~0u, s[k], 16);
  if (h == 0)
    st_tagged3(&g_colsum[(hg * 16 + rb) * 48 + (ht >> 5) * 16 + q], (__float_as_uint(s[0]) & ~7u) | tag, __float_as_uint(s[1]),
               __float_as_uint(s[2]), __float_as_uint(s[3]));
}
__device__ __forceinline__ void colsum_gather(uint32_t sb, int hg, int ht, uint32_t tag) {
  const int lane = ht & 31, rec = (ht >> 5) * 16 + (lane & 15);
  const uint4* src = &g_colsum[(hg * 16 + (lane >> 4) * 8) * 48 + rec];
  uint4 v[8];
  bool ok;
  int it = 0;
  do {
    ok = true;
#pragma unroll
    for (int i = 0; i < 8; i++) v[i] = ld_tagged(src + i * 48);
#pragma unroll
    for (int i = 0; i < 8; i++) ok = ok && (v[i].x & 7u) == tag;
    if (++it > (1 << 22)) __trap();
  } while (!__all_sync(~0u, ok));
  float s[4] = {0.f, 0.f, 0.f, 0.f};
#pragma unroll
  for (int i = 0; i < 8; i++) {
    s[0] += __uint_as_float(v[i].x & ~7u); s[1] += __uint_as_float(v[i].y); s[2] += __uint_as_float(v[i].z); s[3] += __uint_as_float(v[i].w);
  }
#pragma unroll
  for (int k = 0; k < 4; k++) s[k] += __shfl_xor_sync(~0u, s[k], 16);
  if (lane < 16) sts128f(sb + SM_CS + rec * 16, s[0], s[1], s[2], s[3]);
}

__device__ __forceinline__ uint32_t packh(float lo, float hi) { uint32_t r; asm("cvt.rn.f16x2.f32 %0, %1, %2;" : "=r"(r) : "f"(hi), "f"(lo)); return r; }
__device__ __forceinline__ void mma_f16(float* d, uint32_t a0, uint32_t a1, uint32_t a2, uint32_t a3, uint32_t b0, uint32_t b1) {
  asm volatile("mma.sync.aligned.m16n8k16.row.col.f32.f16.f16.f32 {%0,%1,%2,%3}, {%4,%5,%6,%7}, {%8,%9}, {%0,%1,%2,%3};"
      : "+f"(d[0]), "+f"(d[1]), "+f"(d[2]), "+f"(d[3]) : "r"(a0), "r"(a1), "r"(a2), "r"(a3), "r"(b0), "r"(b1));
}
struct HSeed { uint32_t r, i; };
__device__ __forceinline__ HSeed hseed(cplx s) { return {packh(s.r, s.r), packh(s.i, s.i)}; }
__device__ __forceinline__ void hcmul(uint32_t& o_r, uint32_t& o_i, uint32_t br, uint32_t bi, HSeed s) {
  asm("{\n.reg .b32 t, u;\nmul.rn.f16x2 t, %3, %5;\nneg.f16x2 t, t;\nmul.rn.f16x2 u, %3, %4;\nfma.rn.f16x2 %0, %2, %4, t;\nfma.rn.f16x2 %1, %2, %5, u;\n}"
      : "=&r"(o_r), "=&r"(o_i) : "r"(br), "r"(bi), "r"(s.r), "r"(s.i));
}
struct HTile { uint32_t r[4], i[4]; };
__device__ __forceinline__ void tile_set(HTile& t, int k, cplx a, cplx b) { t.r[k] = packh(a.r, b.r); t.i[k] = packh(a.i, b.i); }
__device__ __forceinline__ void tile_upper(HTile& t, HSeed s) { hcmul(t.r[2], t.i[2], t.r[0], t.i[0], s); hcmul(t.r[3], t.i[3], t.r[1], t.i[1], s); }
__device__ __forceinline__ HTile tile_shift(const HTile& t, HSeed s) {
  HTile o;
#pragma unroll
  for (int k = 0; k < 4; k++) hcmul(o.r[k], o.i[k], t.r[k], t.i[k], s);
  return o;
}
__device__ __forceinline__ void tile_put(const HTile& t, uint32_t a) {
  sts128(a, make_uint4(t.r[0], t.r[1], t.r[2], t.r[3]));
  sts128(a + 512, make_uint4(t.i[0], t.i[1], t.i[2], t.i[3]));
}
__device__ __forceinline__ HTile tile_get(uint32_t a) { HTile o; ldsm4t(o.r, a); ldsm4t(o.i, a + 512); return o; }
__device__ __forceinline__ void tile_mma(float* T, const HTile& a0, const HTile& a1, const HTile& b) {
  mma_f16(T, a0.r[0], a0.r[1], a0.r[2], a0.r[3], b.r[0], b.r[1]);
  mma_f16(T, a0.i[0], a0.i[1], a0.i[2], a0.i[3], b.i[0], b.i[1]);
  mma_f16(T, a1.r[0], a1.r[1], a1.r[2], a1.r[3], b.r[2], b.r[3]);
  mma_f16(T, a1.i[0], a1.i[1], a1.i[2], a1.i[3], b.i[2], b.i[3]);
}
__device__ __forceinline__ void tile_mma2(float* T, float* U, const HTile& a0, const HTile& a1, const HTile& b, const HTile& c) {
  mma_f16(T, a0.r[0], a0.r[1], a0.r[2], a0.r[3], b.r[0], b.r[1]);
  mma_f16(U, a0.r[0], a0.r[1], a0.r[2], a0.r[3], c.r[0], c.r[1]);
  mma_f16(T, a0.i[0], a0.i[1], a0.i[2], a0.i[3], b.i[0], b.i[1]);
  mma_f16(U, a0.i[0], a0.i[1], a0.i[2], a0.i[3], c.i[0], c.i[1]);
  mma_f16(T, a1.r[0], a1.r[1], a1.r[2], a1.r[3], b.r[2], b.r[3]);
  mma_f16(U, a1.r[0], a1.r[1], a1.r[2], a1.r[3], c.r[2], c.r[3]);
  mma_f16(T, a1.i[0], a1.i[1], a1.i[2], a1.i[3], b.i[2], b.i[3]);
  mma_f16(U, a1.i[0], a1.i[1], a1.i[2], a1.i[3], c.i[2], c.i[3]);
}
__device__ __forceinline__ void kgen_unit(uint32_t tab, uint32_t taba, float ar2, float ai, cplx c, float (&T)[5][4]) {
  const cplx z1 = cexp_l(ar2, ai, 1.f), z16 = cexp_l(ar2, ai, 16.f), z256 = cexp_l(ar2, ai, 256.f);
  HTile a0, a1, b0, b1;
  {
    const cplx y1 = {z16.r, -z16.i}, y2 = csqr(y1), y3 = cmul(y2, y1), y4 = csqr(y2), y5 = cmul(y4, y1), y6 = csqr(y3), y7 = cmul(y4, y3);
    HTile t;
    tile_set(t, 0, {1.f, 0.f}, y1); tile_set(t, 1, y2, y3); tile_set(t, 2, y4, y5); tile_set(t, 3, y6, y7);
    const HTile u = tile_shift(t, hseed(csqr(y4)));
    __syncwarp();
    tile_put(t, tab); tile_put(u, tab + 1024);
    __syncwarp();
    a0 = tile_get(taba); a1 = tile_get(taba + 256);
  }
  const cplx z2 = csqr(z1), z4 = csqr(z2), z8 = csqr(z4);
  const HSeed h8 = hseed(z8);
  const cplx d = cmul(c, z256), e = cmul(d, z256);
  {
    const cplx z512 = csqr(z256), f = cmul(e, z512), f8 = cmul(f, z8), f16 = cmul(f, z16), e4 = cmul(e, z4);
    HTile t, u;
    tile_set(t, 0, e4, cmul(e, z8)); tile_set(t, 1, cmul(e4, z8), cmul(e, z16));
    tile_upper(t, hseed(z256));
    tile_set(u, 0, f8, f16); tile_set(u, 1, cmul(f8, z256), cmul(f16, z256));
    tile_upper(u, hseed(z512));
    __syncwarp();
    tile_put(t, tab); tile_put(u, tab + 1024);
    __syncwarp();
    b0 = tile_get(tab); b1 = tile_get(tab + 1024);
  }
  {
    const cplx d2 = cmul(d, z2), d4 = cmul(d, z4);
    HTile t;
    tile_set(t, 0, d2, d4); tile_set(t, 1, cmul(d2, z4), cmul(d, z8));
    tile_upper(t, h8);
    __syncwarp();
    tile_put(t, tab);
    __syncwarp();
    tile_mma2(T[3], T[4], a0, a1, b0, b1);
    b0 = tile_get(tab);
  }
  {
    const cplx c1 = cmul(c, z1), c2 = cmul(c, z2), c3 = cmul(c1, z2), c4 = cmul(c, z4);
    HTile t;
    tile_set(t, 0, c1, c2); tile_set(t, 1, c3, c4); tile_set(t, 2, cmul(c1, z4), cmul(c2, z4)); tile_set(t, 3, cmul(c3, z4), cmul(c4, z4));
    const HTile u = tile_shift(t, h8);
    __syncwarp();
    tile_put(t, tab); tile_put(u, tab + 1024);
    __syncwarp();
    tile_mma(T[2], a0, a1, b0);
    b0 = tile_get(tab); b1 = tile_get(tab + 1024);
    tile_mma2(T[0], T[1], a0, a1, b0, b1);
  }
}
struct ModeIn { uint2 ar, ai, br, bi, cr, ci; };
__device__ __forceinline__ ModeIn load_modes(const Params& p, int idx) {
  return {*(const uint2*)(p.a_re + idx), *(const uint2*)(p.a_im + idx), *(const uint2*)(p.b_re + idx),
          *(const uint2*)(p.b_im + idx), *(const uint2*)(p.c_re + idx), *(const uint2*)(p.c_im + idx)};
}
__device__ __forceinline__ float bf_el(uint2 v, int k) { const uint32_t x = (k & 2) ? v.y : v.x; return (k & 1) ? bf_hi(x) : bf_lo(x); }
struct KGen { float4 cur; float T[5][4]; };
__device__ __forceinline__ uint32_t kgen_slot(uint32_t sb, int ht, int u) {
  return sb + (u < 3 ? SM_KC + (ht >> 5) * (KC_STRIDE * 2) + (u - 1) * 512 + (ht & 31) * 16 + 16 : SM_HALO + 1024 + ht * 16);
}
__device__ __forceinline__ void kgen_setup(KGen& s, uint32_t sb, int cta, int ht, const ModeIn& in, bf16 logdt, bf16 dskip) {
  const float dt = __bfloat162float(__float2bfloat16_rn(expf(__bfloat162float(logdt))));
  float mx = 0.f, k0 = 0.f, ar2[4];
  cplx c[4];
#pragma unroll
  for (int k = 0; k < 4; k++) {
    ar2[k] = (dt * bf_el(in.ar, k)) * 1.4426950408889634f;
    c[k] = cmul({bf_el(in.cr, k), bf_el(in.ci, k)}, {dt * bf_el(in.br, k), dt * bf_el(in.bi, k)});
    k0 += c[k].r;
    mx = fmaxf(mx, fmaxf(fabsf(c[k].r), fabsf(c[k].i)) * ex2(fmaxf(ar2[k] * 2048.f, 0.f)));
  }
  const int ex = min(max(267 - (int)(__reduce_max_sync(~0u, __float_as_uint(mx)) >> 23), 1), 253);
  const float sc = __uint_as_float(ex << 23);
#pragma unroll
  for (int o = 16; o > 0; o >>= 1) k0 += __shfl_xor_sync(~0u, k0, o);
  if ((ht & 31) == 0) {
    const uint32_t kc = sb + SM_KC + (ht >> 5) * (KC_STRIDE * 2);
    sts16(kc, __bfloat16_as_ushort(__float2bfloat16_rn(k0 + __bfloat162float(dskip))));
    sts16(kc + 641 * 2, 0);
    sts32f(kc + 644 * 2, __uint_as_float((254 - ex) << 23));
  }
  s.cur = make_float4(ar2[0], dt * bf_el(in.ai, 0), c[0].r * sc, c[0].i * sc);
#pragma unroll
  for (int k = 1; k < 4; k++) sts128f(kgen_slot(sb, ht, k), ar2[k], dt * bf_el(in.ai, k), c[k].r * sc, c[k].i * sc);
#pragma unroll
  for (int i = 0; i < 5; i++) s.T[i][0] = s.T[i][1] = s.T[i][2] = s.T[i][3] = 0.f;
}
__device__ __forceinline__ void kgen_finish(KGen& s, uint32_t sb, int cta, int ht) {
  const int w = ht >> 5, lane = ht & 31, g = lane >> 2, t = lane & 3;
  const uint32_t kc = sb + SM_KC + w * KC_STRIDE * 2;
  __syncwarp();
  const float inv = __uint_as_float(lds32(kc + 644 * 2));
  auto put = [&](int idx, float v) {
    sts16(kc + idx * 2, __bfloat16_as_ushort(__float2bfloat16_rn(v)));
  };
#pragma unroll
  for (int hi = 0; hi < 2; hi++)
#pragma unroll
    for (int lo = 0; lo < 2; lo++) {
      const int i = g + 8 * hi, j = 2 * t + lo, e = 2 * hi + lo;
      put(16 * i + 1 + j, s.T[0][e] * inv);
      put(16 * i + 9 + j, s.T[1][e] * inv);
      put(257 + 8 * i + j, s.T[2][e] * inv);
      put(385 + 4 * i + (j & 3) + 64 * (j >> 2), s.T[3][e] * inv);
      put(513 + 2 * i + lo + 32 * t, s.T[4][e] * inv);
    }
}

__device__ __forceinline__ void expand_taps(uint32_t sb, int ht) {
  const int ch = ht >> 5, lane = ht & 31;
  const uint32_t kc = sb + SM_KC + ch * KC_STRIDE * 2;
  const uint32_t dst0 = sb + cv_pe(ch);
  auto put = [&](int G, uint32_t v0, uint32_t v1, uint32_t v2, uint32_t v3, uint32_t v4, uint32_t v5, uint32_t v6, uint32_t v7, uint32_t v8) {
    const uint32_t dst = dst0 + G * 32;
    sts128(dst, make_uint4(v1 | (v0 << 16), v2 | (v1 << 16), v3 | (v2 << 16), v4 | (v3 << 16)));
    sts128(dst + 16, make_uint4(v5 | (v4 << 16), v6 | (v5 << 16), v7 | (v6 << 16), v8 | (v7 << 16)));
  };
  {
    const uint4 q = lds128(kc + lane * 16);
    const uint32_t pv = lane ? lds16(kc + lane * 16 - 2) : 0u;
    const uint32_t dst = dst0 + (lane + 2) * 32;
    sts128(dst, make_uint4(__byte_perm(q.x, pv, 0x5410), __byte_perm(q.x, q.x, 0x1032), __byte_perm(q.y, q.x, 0x7610), __byte_perm(q.y, q.y, 0x1032)));
    sts128(dst + 16, make_uint4(__byte_perm(q.z, q.y, 0x7610), __byte_perm(q.z, q.z, 0x1032), __byte_perm(q.w, q.z, 0x7610), __byte_perm(q.w, q.w, 0x1032)));
    if (lane < 4) sts128(dst0 + lane * 16, make_uint4(0, 0, 0, 0));
  }
  uint32_t a[5], b[2][3], fv[4];
  {
    const uint32_t s1 = kc + 2 * (256 + 4 * lane);
#pragma unroll
    for (int k = 0; k < 5; k++) a[k] = lds16(s1 + 2 * k);
#pragma unroll
    for (int u = 0; u < 2; u++) {
      const uint32_t s2 = kc + 2 * (384 + 2 * (lane + 32 * u));
#pragma unroll
      for (int k = 0; k < 3; k++) b[u][k] = lds16(s2 + 2 * k);
    }
#pragma unroll
    for (int k = 0; k < 4; k++) fv[k] = lds16(kc + 2 * (640 - 4 * lane - k));
  }
  const uint32_t k255 = lds16(kc + 2 * 255), k1024 = lds16(kc + 2 * 512);
  put(34 + lane, lane == 0 ? k255 : a[0], a[0], a[0], a[1], a[2], a[2], a[2], a[3], a[4]);
#pragma unroll
  for (int u = 0; u < 2; u++) put(66 + lane + 32 * u, b[u][0], b[u][0], b[u][0], b[u][0], b[u][1], b[u][1], b[u][1], b[u][2], b[u][2]);
  if (lane < 10) {
    const uint32_t v = lane == 0 ? k1024 : 0u;
    put(130 + lane, v, v, v, v, v, v, 0u, 0u, 0u);
  }
  const uint32_t ft = sb + cv_ft(ch) + 4 * lane;
#pragma unroll
  for (int ty = 0; ty < 2; ty++) {
    const uint32_t v = fv[ty] | (fv[ty + 2] << 16);
    sts32f(ft + ty * 512, __uint_as_float(v));
    sts32f(ft + ty * 512 + 128, 0.f);
    sts32f(ft + ty * 512 + 256 + (lane < 2 ? 120 : -8), __uint_as_float(lane < 2 ? 0u : v));
    sts32f(ft + ty * 512 + 384, 0.f);
  }
}

template <bool SMID> __device__ __forceinline__ int role_id() {
  uint32_t v;
  if (!SMID) { asm volatile("mov.u32 %0, %%ctaid.x;" : "=r"(v)); return v; }
  asm volatile("mov.u32 %0, %%smid;" : "=r"(v));
  const int tp = v >> 1, q = ((tp - 32) * 37) >> 8;
  const int r = tp < 32 ? (tp & 7) * 8 + (tp >> 3) : tp < 60 ? (tp - 31 - 7 * q) * 8 + 4 + q : tp < 62 ? tp + 4 : tp - 58;
  return __shfl_sync(~0u, 2 * r + (v & 1), 0);
}
__device__ __forceinline__ int role_rb(int cta) { return ((cta >> 4) & 3) * 4 + ((cta >> 2) & 3); }
__device__ __forceinline__ int role_hg(int cta) { return (cta >> 6) * 4 + (cta & 3); }
__device__ __forceinline__ int role_rb2(int cta) { return cta >> 3; }
__device__ __forceinline__ int role_q2(int cta) { return cta & 7; }

template <bool SMID> __global__ void __launch_bounds__(NTHREADS, 1) fused_kernel(const __grid_constant__ Params p) {
  extern __shared__ __align__(1024) uint8_t smem[];
  const uint32_t sb = s32(smem);
  const int tid = threadIdx.x, lane = tid & 31;
  const int warp = __shfl_sync(~0u, tid >> 5, 0);
  constexpr unsigned NARR = SMID ? 132 : NCTA;
  const uint32_t bar = sb + SM_BAR;
  if (tid == 0) TS(0);
  const int cta0 = role_id<SMID>();
  if (warp == 0 && (!SMID || cta0 < NCTA) && elect_one()) {
    const int rb = role_rb(cta0), hg = role_hg(cta0);
    mbar_init(bar + 8 * B_XF, 1); mbar_init(bar + 8 * B_KVF, 1);
    fence_async_smem();
#pragma unroll
    for (int c = 0; c < 8; c++) {
      mbar_expect(bar + 8 * (B_XF + c), 16384);
      tma_ld(sb + SM_X + c * 16384, &p.mapX128, c * 64, rb * 128, bar + 8 * (B_XF + c));
      if (c < 3) {
        mbar_expect(bar + 8 * (B_KVF + c), 24576);
        tma_ld3(sb + SM_W + c * 24576, &p.mapW3, hg * 64, c * 64, 0, bar + 8 * (B_KVF + c));
      }
      if (c == 0) {
#pragma unroll
        for (int i = 1; i < 8; i++) mbar_init(bar + 8 * (B_XF + i), 1);
        mbar_init(bar + 8 * (B_KVF + 1), 1); mbar_init(bar + 8 * (B_KVF + 2), 1); mbar_init(bar + 8 * B_CW, 1);
        fence_async_smem();
      }
      if (c == PF_AT) {
        mbar_expect(bar + 8 * B_CW, 12288);
        tma_ld3(sb + SM_CW, &p.mapW3h, hg * 64, rb * 32, 0, bar + 8 * B_CW);
      }
    }
    TS(56);
  }
  if (SMID && cta0 >= NCTA) {
    if (tid == 0) spin_until(&g_cnt[C_CS * 32], (atomicAdd(&g_cnt[C_CS * 32], 1u) / NARR + 1) * NARR);
    return;
  }
  if (warp >= 1 && warp < 5 && elect_one()) {
#pragma unroll
    for (int q = 0; q < 4; q++) {
      if (warp == q + 1) {
#pragma unroll
        for (int i = 11 + 15 * q; i < 26 + 15 * q && i < B_COUNT; i++) {
          if (i < B_KVF + 3 || i == B_CW) continue;
          int cnt = 1;
          if ((i >= B_KVE && i < B_KVE + 5) || i == B_QDONE || i == B_PDONE || i == B_OST || i == B_AD) cnt = 2;
          if ((i >= B_U && i < B_U + 4) || i == B_PS) cnt = 8;
          if ((i >= B_S && i < B_S + 4) || (i >= B_E && i < B_E + 4) || (i >= B_P && i < B_P + 4) || i == B_PE || i == B_STF || i == B_HF) cnt = 4;
          if (i == B_CSF) cnt = 3;
          mbar_init(bar + 8 * i, cnt);
        }
      }
    }
    fence_async_smem();
  }

  if (warp < 8) {
    bar_sync(0, NTHREADS);
    if (tid == 0) TS(1);
    asm volatile("setmaxnreg.inc.sync.aligned.u32 %0;" ::"n"(R_CONS));
    const int cw = __shfl_sync(~0u, opaque_tid() >> 5, 0);
    const int wg = cw >> 2, w = cw & 3;
    const int cta = role_id<SMID>();
    if (tid == 0) TS(54);
#pragma unroll 1
    for (int layer = 0; layer < 2; layer++) {
      attn_phase(p, sb, layer, role_rb(cta), role_hg(cta), wg, w);
      if (p.stop == 1 + 3 * layer) return;
      proj_phase(p, sb, layer, role_rb2(cta), role_q2(cta), wg, w);
      if (p.stop == 2 + 3 * layer) return;
      conv_phase(p, sb, layer, cta);
      if (p.stop == 3 + 3 * layer) return;
    }
    final_phase(p, sb, cta, wg, w);
  } else if (warp < 12) {
    asm volatile("setmaxnreg.dec.sync.aligned.u32 %0;" ::"n"(R_HELP));
    const int ht = tid - 256;
    const int cta = role_id<SMID>(), rb = role_rb(cta), hg = role_hg(cta);
    unsigned ep0 = 0;
    if (ht == 0) ep0 = ld_relaxed(&g_cnt[C_CS * 32]);
    bar_sync(0, NTHREADS);
    if (ht == 0) {
      asm volatile("st.shared.u32 [%0], %1;" ::"r"(sb + SM_EP), "r"(ep0 / NARR) : "memory");
      mbar_arrive(bar + 8 * B_EP);
    }
    mbar_wait(bar + 8 * B_EP, 0);
    const uint32_t cs_tag = lds32(sb + SM_EP) % 7 + 1;
    if (ht < 96) {
      mbar_wait(bar + 8 * B_CW, 0);
      colsum_publish(sb, rb, hg, ht, cs_tag);
    }
    if (ht == 0) TS(50);
    if (ht < 48) {
      const bf16* q = (&p.a_re)[ht >> 3];
      asm volatile("prefetch.global.L2 [%0];" ::"l"(q + cv_chan(cta, (ht >> 1) & 3) * 128 + (ht & 1) * 64));
    }
    stats_publish(sb, 0, rb, hg, opaque_tid() - 256, part_tag(lds32(sb + SM_EP), 0));
    {
      KGen kg;
      const uint32_t tab0 = sb + ((ht >> 5) < 2 ? SM_T : SM_T2 - 4096) + (ht >> 5) * 2048;
      const uint32_t tab = tab0 + (ht & 31) * 16, taba = tab0 + ((ht >> 3) & 1) * 1024 + (((ht >> 1) & 8) + (ht & 7)) * 16;
      mbar_wait(bar + 8 * (B_KVF + CS_AT), 0);
      if (ht < 96) {
        colsum_gather(sb, hg, ht, cs_tag);
        __syncwarp();
        if (elect_one()) mbar_arrive(bar + 8 * B_CSF);
      }
      stats_gather(sb, rb, opaque_tid() - 256, part_tag(lds32(sb + SM_EP), 0));
      if (ht == 0) TS(40);
      const int chn = cv_chan(cta, ht >> 5);
      kgen_setup(kg, sb, cta, ht, load_modes(p, chn * 128 + (ht & 31) * 4), p.log_dt[chn], p.dskip[chn]);
      halo_receive(sb, 0, rb, hg, opaque_tid() - 256);
#pragma unroll 1
      for (int u = 0; u < 4; u++) {
        if (u == KG_PRE) {
          KTS(39);
          mbar_wait(bar + 8 * B_AD, 0);
          KTS(41);
        }
        if (u == 4 - KG_LAST) mbar_wait(bar + 8 * (KG_PD ? B_PDONE : B_PS), 0);
        kgen_unit(tab, taba, kg.cur.x, kg.cur.y, {kg.cur.z, kg.cur.w}, kg.T);
        kg.cur = lds128f(kgen_slot(sb, opaque_tid() - 256, u + 1));
      }
      kgen_finish(kg, sb, cta, opaque_tid() - 256);
    }
    KTS(51);
    bar_sync(4, 128);
#pragma unroll 1
    for (int layer = 0; layer < 2; layer++) {
      if (p.stop <= 1 + 3 * layer) return;
      mbar_wait(bar + 8 * (EXP_LATE ? B_PS : B_PDONE), layer);
      expand_taps(sb, opaque_tid() - 256);
      conv_zero(sb, opaque_tid() - 256);
      if (ht == 0) TS(52 + layer);
      warp_release(bar + 8 * B_PE);
      if (p.stop <= 2 + 3 * layer) return;
      {
        uint4 xr[4], st[4], un[4];
        const int c = opaque_tid() - 256;
        const SumAddr sa = conv_sum_addr(sb, c);
        conv_prep_load(sb, layer, cta, c, xr, st);
        conv_prep<true>(sb, layer, cta, c, xr, st, un, sa);
        if (layer == 1 && ht == 0) TS(62);
        bar_sync(4, 128);
        conv_sums(sa, 1, c, un[1]);
        fence_async_smem();
        warp_release(bar + 8 * (B_S + 1));
        conv_sums(sa, 2, c, un[2]);
        mbar_wait(bar + 8 * (B_U + 3), layer);
        warp_release(bar + 8 * (B_S + 2));
        const bf16* xup = g_xT + (size_t)(2 * layer * DM + cta) * LSEQ + (c + 128) * 8;
        st[0] = ldcg128(xup);
        conv_sums(sa, 3, c, un[3]);
        warp_release(bar + 8 * (B_S + 3));
#pragma unroll
        for (int lc = 0; lc < 4; lc++) {
          if (lc < 3) st[lc + 1] = ldcg128(xup + (lc + 1) * 128 * LSEQ);
          conv_epi(sb, layer, cta, lc, c, xr[lc], st[lc]);
          warp_release(bar + 8 * (B_E + lc));
          if (layer == 1 && lc == 3 && ht == 0) TS(38);
        }
      }
      if (layer == 0 && p.stop > 3) {
        const int c1 = role_id<SMID>();
        stats_publish(sb, 1, role_rb(c1), role_hg(c1), opaque_tid() - 256, part_tag(lds32(sb + SM_EP), 2));
        delay<D_ST>();
        stats_gather(sb, role_rb(c1), opaque_tid() - 256, part_tag(lds32(sb + SM_EP), 2));
        if (ht == 0) TS(25);
        halo_receive(sb, 1, role_rb(c1), role_hg(c1), opaque_tid() - 256);
      }
    }
  } else {
    asm volatile("setmaxnreg.dec.sync.aligned.u32 %0;" ::"n"(512 - 2 * R_CONS - R_HELP));
    const int cta = role_id<SMID>(), rb = role_rb(cta), hg = role_hg(cta), rb2 = role_rb2(cta), q2 = role_q2(cta);
    bar_sync(0, NTHREADS);
    if (warp == 12) {
      if (elect_one()) {
        unsigned epoch = 0;
#pragma unroll 1
        for (int layer = 0; layer < 2; layer++) {
          auto ld_w = [&](int c, int slot) {
            const uint32_t b = bar + 8 * (B_KVF + c);
            mbar_expect(b, 24576);
            tma_ld3(sb + SM_W + slot * 24576, &p.mapW3, hg * 64, c * 64, 0, b);
          };
          if (layer == 0) {
            TS(55);
            mbar_wait(bar + 8 * (B_KVF + 2), 0);
            if (rb2 < 4) tma_prefetch2(&p.mapWo128, q2 * 64, rb2 * 128);
            asm volatile("prefetch.tensormap [%0];" ::"l"(&p.mapO) : "memory");
            asm volatile("prefetch.tensormap [%0];" ::"l"(&p.mapO128) : "memory");
            asm volatile("prefetch.tensormap [%0];" ::"l"(&p.mapXT) : "memory");
            asm volatile("prefetch.tensormap [%0];" ::"l"(&p.mapXT3) : "memory");
            mbar_wait(bar + 8 * B_EP, 0);
            epoch = lds32(sb + SM_EP);
          } else {
            mbar_wait(bar + 8 * B_PDONE, 0);
            ld_w(0, 0); ld_w(1, 1);
            mbar_wait(bar + 8 * (W2_LATE ? B_U : B_RE), 0);
            ld_w(2, 2);
          }
          {
            int slot = 0;
#pragma unroll 1
            for (int c = 3; c < 8; c++) {
              mbar_wait(bar + 8 * (B_KVE + c - 3), layer);
              ld_w(c, slot);
              slot = slot == 2 ? 0 : slot + 1;
            }
          }
          if (p.stop <= 1 + 3 * layer) return;
          mbar_wait(bar + 8 * B_QDONE, layer);
          mbar_wait(bar + 8 * B_HF, layer);
#pragma unroll 1
          for (int c = 0; c < 4; c++) {
            const uint32_t b = bar + 8 * (B_WOF + c);
            mbar_expect(b, 16384);
            tma_ld(sb + SM_WO + c * 16384, &p.mapWo128, q2 * 64, c * 128, b);
          }
          {
            const uint32_t b = bar + 8 * B_RF;
            mbar_expect(b, 16384);
            if (layer == 0) tma_ld(sb + SM_R, &p.mapX128, q2 * 64, rb2 * 128, b);
            else tma_ld3(sb + SM_R, &p.mapXT3, 0, DM + q2 * 64, rb2 * 2, b);
          }
          spin_until(&g_cnt[(C_O + rb2) * 32], (2 * epoch + layer + 1) * 16);
          fence_async_global();
#pragma unroll 1
          for (int c = 0; c < 8; c++) {
            const uint32_t b = bar + 8 * (B_OF + c);
            if (c == 4) { mbar_wait(bar + 8 * B_OST, layer); fence_async_smem(); }
            mbar_expect(b, 16384);
            tma_ld(sb + sm_o(c), &p.mapO128, c * 64, rb2 * 128, b);
          }
          if (p.stop <= 3 + 3 * layer) return;
        }
      }
    } else if (warp == 13) {
      if (elect_one() && p.stop > 3) {
        mbar_wait(bar + 8 * B_GB, 0);
        const unsigned target = (lds32(sb + SM_EP) + 1) * NCTA;
        auto ld_x = [&](int c) {
          mbar_expect(bar + 8 * (B_XF + c), 16384);
          tma_ld3(sb + SM_X + c * 16384, &p.mapXT3, 0, DM + c * 64, rb * 2, bar + 8 * (B_XF + c));
        };
        int done = 0, it = 0;
        while (done < 4) {
          const uint4 v = ld_tagged((const uint4*)&g_cnt[C_G1 * 32]);
          const int n = (int)(v.x - target) < 0 ? 0 : (int)(v.y - target) < 0 ? 1 : (int)(v.z - target) < 0 ? 2 : (int)(v.w - target) < 0 ? 3 : 4;
          if (++it > (1 << 23)) __trap();
          if (n == done) continue;
          if (n == 4) TS(44);
          fence_async_global();
          fence_async_smem();
          const int first = n == 4 && done > 1 ? 6 + (hg >> 2) : -1;
          if (first >= 0) ld_x(first);
#pragma unroll 1
          for (int c = 2 * done; c < 2 * n; c++)
            if (c != first) ld_x(c);
          done = n;
        }
      }
    } else if (warp == 15) {
      mbar_wait(bar + 8 * B_EP, 0);
      const unsigned epoch = lds32(sb + SM_EP);
#pragma unroll 1
      for (int layer = 0; layer < 2; layer++) {
#pragma unroll 1
        for (int i = 0; i < 6; i++) {
          mbar_wait(bar + 8 * (B_KVF + (FILL_AT + i < 7 ? FILL_AT + i : 7)), layer);
          uint4* dst = (uint4*)(g_xT + (size_t)(i < 4 ? 2 * layer * DM + cv_chan(cta, i) : 3 * DM + cv_chan(cta, 2 * layer + i - 4)) * LSEQ) + lane;
#pragma unroll
          for (int k = 0; k < 8; k++) dst[32 * k] = make_uint4(~0u, ~0u, ~0u, ~0u);
        }
        if (lane < 8) ((uint4*)g_stats)[layer * 1024 + cta * 8 + lane] = make_uint4(0, 0, 0, 0);
        __syncwarp();
        if (elect_one()) {
          red_release(&g_cnt[C_CS * 32 + layer]);
          spin_until(&g_cnt[C_CS * 32 + layer], (epoch + 1) * (layer ? NCTA : NARR));
          mbar_arrive(bar + 8 * B_ZF);
          if (layer == 0 && p.stop > 2) {
#pragma unroll 1
            for (int lc = 0; lc < 4; lc++) {
              mbar_wait(bar + 8 * (B_E + lc), 0);
              fence_reader();
              bulk_st(g_xT + (size_t)(DM + cv_chan(cta, lc)) * LSEQ, sb + cv_s(lc), 4096);
              bulk_commit();
              bulk_wait_all();
              red_relaxed(&g_cnt[C_G1 * 32 + lc]);
              if (lc == 3) TS(18);
            }
          }
        }
        __syncwarp();
        if (p.stop <= 3) return;
      }
    } else if (warp == 14) {
      mbar_wait(bar + 8 * B_EP, 0);
      const unsigned epoch = lds32(sb + SM_EP);
#pragma unroll 1
      for (int layer = 0; layer < 2; layer++) {
        if (p.stop <= 1 + 3 * layer) return;
        mbar_wait(bar + 8 * B_ZF, layer);
        mbar_wait(bar + 8 * (EXP_LATE ? B_PS : B_PDONE), layer);
        delay<D_PST>();
        proj_stats(layer, rb2, q2, lane, part_tag(epoch, 2 * layer + 1));
        if (layer == 1 && lane == 0) TS(5);
        delay<D_PREP>();
        if (lane == 0) mbar_arrive(bar + 8 * B_GB);
      }
    }
  }
}

typedef CUresult (*EncodeFn)(CUtensorMap*, CUtensorMapDataType, cuuint32_t, void*, const cuuint64_t*, const cuuint64_t*,
                             const cuuint32_t*, const cuuint32_t*, CUtensorMapInterleave, CUtensorMapSwizzle,
                             CUtensorMapL2promotion, CUtensorMapFloatOOBfill);

static void make_map(EncodeFn enc, CUtensorMap* m, void* ptr, uint64_t cols, uint64_t rows, uint32_t box_rows) {
  cuuint64_t dims[2] = {cols, rows};
  cuuint64_t strides[1] = {cols * 2};
  cuuint32_t box[2] = {64, box_rows};
  cuuint32_t es[2] = {1, 1};
  enc(m, CU_TENSOR_MAP_DATA_TYPE_BFLOAT16, 2, ptr, dims, strides, box, es, CU_TENSOR_MAP_INTERLEAVE_NONE,
      CU_TENSOR_MAP_SWIZZLE_128B, CU_TENSOR_MAP_L2_PROMOTION_L2_128B, CU_TENSOR_MAP_FLOAT_OOB_FILL_NONE);
}
static void make_map3(EncodeFn enc, CUtensorMap* m, void* ptr, uint64_t d0, uint64_t cols, uint64_t rows, uint64_t blk_stride,
                      uint64_t nblocks, uint32_t nblk, uint32_t box_rows = 64) {
  cuuint64_t dims[3] = {d0, rows, nblocks};
  cuuint64_t strides[2] = {cols * 2, blk_stride * 2};
  cuuint32_t box[3] = {64, box_rows, nblk};
  cuuint32_t es[3] = {1, 1, 1};
  enc(m, CU_TENSOR_MAP_DATA_TYPE_BFLOAT16, 3, ptr, dims, strides, box, es, CU_TENSOR_MAP_INTERLEAVE_NONE,
      CU_TENSOR_MAP_SWIZZLE_128B, CU_TENSOR_MAP_L2_PROMOTION_L2_128B, CU_TENSOR_MAP_FLOAT_OOB_FILL_NONE);
}

extern "C" void kernel_launch(void* const* d_in, const int* in_sizes, int n_in, void* d_out, int out_size) {
  static Params prm;
  static void* cached[13] = {nullptr};
  static bool attr_done = false, by_smid = false;
  bool same = attr_done && cached[12] == d_out;
  for (int i = 0; i < 12 && same; i++) same = cached[i] == d_in[i];
  if (!same) {
    void* fn = nullptr;
    cudaDriverEntryPointQueryResult qr;
    cudaGetDriverEntryPoint("cuTensorMapEncodeTiled", &fn, cudaEnableDefault, &qr);
    EncodeFn enc = (EncodeFn)fn;
    void *pO, *pXT;
    cudaGetSymbolAddress(&pO, g_O);
    cudaGetSymbolAddress(&pXT, g_xT);
    make_map(enc, &prm.mapO, pO, DM, LSEQ, 64);
    make_map(enc, &prm.mapXT, pXT, LSEQ, 4 * DM, 64);
    prm.out = (bf16*)d_out;
    make_map(enc, &prm.mapX128, d_in[0], DM, LSEQ, 128);
    make_map(enc, &prm.mapWo128, d_in[2], DM, DM, 128);
    make_map(enc, &prm.mapO128, pO, DM, LSEQ, 128);
    make_map3(enc, &prm.mapW3, d_in[1], DM, 3 * DM, DM, DM, 3, 3);
    make_map3(enc, &prm.mapW3h, d_in[1], DM, 3 * DM, DM, DM, 3, 3, 32);
    make_map3(enc, &prm.mapXT3, pXT, 64, LSEQ, 4 * DM, 64, 32, 2);
    prm.a_re = (const bf16*)d_in[4]; prm.a_im = (const bf16*)d_in[5];
    prm.b_re = (const bf16*)d_in[6]; prm.b_im = (const bf16*)d_in[7];
    prm.c_re = (const bf16*)d_in[8]; prm.c_im = (const bf16*)d_in[9];
    prm.log_dt = (const bf16*)d_in[10]; prm.dskip = (const bf16*)d_in[11];
    int dev = 0, sms = 0;
    cudaGetDevice(&dev);
    cudaDeviceGetAttribute(&sms, cudaDevAttrMultiProcessorCount, dev);
    by_smid = sms == 132;
    cudaFuncSetAttribute(fused_kernel<true>, cudaFuncAttributeMaxDynamicSharedMemorySize, SM_TOTAL);
    cudaFuncSetAttribute(fused_kernel<false>, cudaFuncAttributeMaxDynamicSharedMemorySize, SM_TOTAL);
    for (int i = 0; i < 12; i++) cached[i] = d_in[i];
    cached[12] = d_out;
    attr_done = true;
  }
  prm.stop = 100;
    if (by_smid) fused_kernel<true><<<132, NTHREADS, SM_TOTAL>>>(prm);
  else fused_kernel<false><<<NCTA, NTHREADS, SM_TOTAL>>>(prm);
}
```

```cpp
#include <cuda_runtime.h>
#include <cuda_bf16.h>
#include <cuda.h>
#include <stdint.h>

typedef __nv_bfloat16 bf16;

constexpr int LSEQ = 2048;
constexpr int DM = 512;
constexpr int NCTA = 128;
constexpr int NTHREADS = 512;
#define RR 0
#define KG_PRE 2
#define W2_LATE 0
#define FILL_AT 2
#define EXP_LATE 1
#define RFENCE 1
#define D_FIN 550
#define D_PREP 500
#define D_PST 0
#define D_HALO 300
#define STAG 2
#define D_ST 0
#define TLAYER 1
#define KG_PD 0
#define SUM_F32 0
#define CS_AT 4
#define KG_LAST 1
#define X_JIT 0
#define PF_AT 2
#define KG_GATE 2
#define R_CONS 192
#define R_HELP 88

constexpr int SM_X = 0;
constexpr int SM_W = 131072;
constexpr int SM_KVX = SM_X;
constexpr int SM_OST = SM_X + 32768;
constexpr int SM_WO = SM_X + 65536;
__host__ __device__ constexpr int sm_o(int c) { return c < 4 ? SM_W + c * 16384 : SM_X + (c - 4) * 16384; }
constexpr int SM_R = 196608;
constexpr int SM_T = 212992;
constexpr int SM_KC = 217088;
constexpr int KC_STRIDE = 648;
constexpr int SM_CS = SM_KC + 4 * KC_STRIDE * 2;
constexpr int SM_CW = SM_R + 8192;
constexpr int SM_EP = SM_CS + 768;
constexpr int SM_BAR = SM_EP + 16;
constexpr int SM_T2 = SM_BAR + 832;
constexpr int SM_HALO = SM_T2 + 4096;
constexpr int SM_ST = SM_HALO + 3072;
constexpr int SM_TOTAL = SM_HALO + 4096;
static_assert(SM_TOTAL <= 232448, "shared memory");

constexpr int CV_UH = 140 * 16;
constexpr int CV_PECH = 1120 * 4;
constexpr int CV_PBW = 2112 * 2;
__host__ __device__ constexpr int cv_s(int lc) { return SM_X + lc * 32768; }
__host__ __device__ constexpr int cv_u(int lc) { return cv_s(lc) + 4096; }
__host__ __device__ constexpr int cv_pe(int lc) { return cv_u(lc) + 2 * CV_UH; }
__host__ __device__ constexpr int cv_pb(int lc) { return cv_pe(lc) + CV_PECH; }
__host__ __device__ constexpr int cv_ft(int lc) { return cv_pb(lc) + 4 * CV_PBW; }
static_assert(cv_ft(0) + 1024 <= 32768, "conv buffers");
__host__ __device__ constexpr int cv_chan(int cta, int lc) { return cta + 128 * lc; }

enum {
  B_XF = 0,
  B_KVF = 8,
  B_KVE = 16,
  B_AD = 21,
  B_OST = 22,
  B_RF = 23,
  B_U = 24,
  B_S = 28,
  B_T = 32,
  B_WOF = 36,
  B_E = 40,
  B_OF = 44,
  B_P = 64,
  B_RE = 52,
  B_CW = 53,
  B_HF = 54,
  B_STF = 55,
  B_CSF = 61,
  B_SD = 68,
  B_QDONE = 56,
  B_PDONE = 57,
  B_PS = 58,
  B_PE = 59,
  B_GB = 60,
  B_EP = 62,
  B_ZF = 63,
  B_COUNT = 69
};

enum {
  C_CS = 0,
  C_G1 = 2,
  C_O = 4,
  C_COUNT = 20
};

__device__ __align__(128) unsigned g_cnt[C_COUNT * 32];
__device__ __align__(1024) bf16 g_O[LSEQ * DM];
__device__ __align__(1024) bf16 g_xT[4 * DM * LSEQ];
__device__ __align__(1024) float g_stats[2 * LSEQ * 2];
__device__ __align__(1024) uint4 g_colsum[8 * 16 * 48];
__device__ __align__(1024) uint4 g_halo[16 * 8 * 192];
__device__ __align__(1024) uint2 g_part[16 * 8 * 128];
#define TS(i) do { } while (0)

#define ATS(i, th) do { } while (0)
#define KTS(i) do { if (ht == 0) TS(i); } while (0)
#define FTS(i) do { } while (0)
#define LTS(i) do { } while (0)

struct Params {
  CUtensorMap mapO, mapXT, mapX128, mapWo128, mapO128, mapW3, mapW3h, mapXT3;
  const bf16 *a_re, *a_im, *b_re, *b_im, *c_re, *c_im, *log_dt, *dskip;
  bf16* out;
  int stop;
};

__device__ __forceinline__ uint32_t s32(const void* p) { return (uint32_t)__cvta_generic_to_shared(p); }
__device__ __forceinline__ void mbar_init(uint32_t b, int c) { asm volatile("mbarrier.init.shared::cta.b64 [%0], %1;" ::"r"(b), "r"(c) : "memory"); }
__device__ __forceinline__ void mbar_expect(uint32_t b, int bytes) { asm volatile("mbarrier.arrive.expect_tx.shared::cta.b64 _, [%0], %1;" ::"r"(b), "r"(bytes) : "memory"); }
__device__ __forceinline__ void mbar_arrive(uint32_t b) { asm volatile("mbarrier.arrive.shared::cta.b64 _, [%0];" ::"r"(b) : "memory"); }
__device__ __forceinline__ void mbar_arrive_if(uint32_t b, bool c) {
  asm volatile("{\n.reg .pred p;\nsetp.ne.u32 p, %1, 0;\n@p mbarrier.arrive.shared::cta.b64 _, [%0];\n}" ::"r"(b), "r"((uint32_t)c) : "memory");
}
__device__ __forceinline__ void mbar_wait(uint32_t b, int parity) {
  asm volatile("{\n.reg .pred p;\nWAIT_LOOP:\nmbarrier.try_wait.parity.shared::cta.b64 p, [%0], %1;\n@p bra WAIT_DONE;\nbra WAIT_LOOP;\nWAIT_DONE:\n}" ::"r"(b), "r"(parity) : "memory");
}
template <int N> __device__ __forceinline__ void delay() {
  if constexpr (N > 0) {
    uint32_t t0, t;
    asm volatile("mov.u32 %0, %%clock;" : "=r"(t0));
    do { asm volatile("mov.u32 %0, %%clock;" : "=r"(t)); } while (t - t0 < N);
  }
}
__device__ __forceinline__ int opaque_tid() { int v; asm volatile("mov.u32 %0, %%tid.x;" : "=r"(v)); return v; }
__device__ __forceinline__ bool elect_one() {
  uint32_t r;
  asm volatile("{\n.reg .pred p;\nelect.sync _|p, 0xffffffff;\nselp.u32 %0, 1, 0, p;\n}" : "=r"(r));
  return r != 0;
}
__device__ __forceinline__ void tma_ld(uint32_t dst, const CUtensorMap* m, int c0, int c1, uint32_t bar) {
  asm volatile("cp.async.bulk.tensor.2d.shared::cluster.global.mbarrier::complete_tx::bytes [%0], [%1, {%3, %4}], [%2];"
               ::"r"(dst), "l"(m), "r"(bar), "r"(c0), "r"(c1) : "memory");
}
__device__ __forceinline__ void tma_ld3(uint32_t dst, const CUtensorMap* m, int c0, int c1, int c2, uint32_t bar) {
  asm volatile("cp.async.bulk.tensor.3d.shared::cluster.global.mbarrier::complete_tx::bytes [%0], [%1, {%3, %4, %5}], [%2];"
               ::"r"(dst), "l"(m), "r"(bar), "r"(c0), "r"(c1), "r"(c2) : "memory");
}
__device__ __forceinline__ void tma_prefetch2(const CUtensorMap* m, int c0, int c1) {
  asm volatile("cp.async.bulk.prefetch.tensor.2d.L2.global.tile [%0, {%1, %2}];" ::"l"(m), "r"(c0), "r"(c1) : "memory");
}
__device__ __forceinline__ void tma_prefetch3(const CUtensorMap* m, int c0, int c1, int c2) {
  asm volatile("cp.async.bulk.prefetch.tensor.3d.L2.global.tile [%0, {%1, %2, %3}];" ::"l"(m), "r"(c0), "r"(c1), "r"(c2) : "memory");
}
__device__ __forceinline__ void tma_st(const CUtensorMap* m, int c0, int c1, uint32_t src) {
  asm volatile("cp.async.bulk.tensor.2d.global.shared::cta.bulk_group [%0, {%2, %3}], [%1];" ::"l"(m), "r"(src), "r"(c0), "r"(c1) : "memory");
}
__device__ __forceinline__ void bulk_ld(uint32_t dst, const void* src, int bytes, uint32_t bar) {
  asm volatile("cp.async.bulk.shared::cluster.global.mbarrier::complete_tx::bytes [%0], [%1], %2, [%3];" ::"r"(dst), "l"(src), "r"(bytes), "r"(bar) : "memory");
}
__device__ __forceinline__ void bulk_st(void* dst, uint32_t src, int bytes) {
  asm volatile("cp.async.bulk.global.shared::cta.bulk_group [%0], [%1], %2;" ::"l"(dst), "r"(src), "r"(bytes) : "memory");
}
__device__ __forceinline__ void bulk_red_add_f32(void* dst, uint32_t src, int bytes) {
  asm volatile("cp.reduce.async.bulk.global.shared::cta.bulk_group.add.f32 [%0], [%1], %2;" ::"l"(dst), "r"(src), "r"(bytes) : "memory");
}
__device__ __forceinline__ void bulk_commit() { asm volatile("cp.async.bulk.commit_group;" ::: "memory"); }
__device__ __forceinline__ void bulk_wait_all() { asm volatile("cp.async.bulk.wait_group 0;" ::: "memory"); }
__device__ __forceinline__ void fence_async_smem() { asm volatile("fence.proxy.async.shared::cta;" ::: "memory"); }
__device__ __forceinline__ void fence_writer() { if (!RFENCE) fence_async_smem(); }
__device__ __forceinline__ void fence_reader() { if (RFENCE) fence_async_smem(); }
__device__ __forceinline__ void fence_async_global() { asm volatile("fence.proxy.async.global;" ::: "memory"); }
__device__ __forceinline__ void bar_sync(int id, int n) { asm volatile("bar.sync %0, %1;" ::"r"(id), "r"(n) : "memory"); }
__device__ __forceinline__ void bar_arrive(int id, int n) { asm volatile("bar.arrive %0, %1;" ::"r"(id), "r"(n) : "memory"); }
__device__ __forceinline__ void wg_fence() { asm volatile("wgmma.fence.sync.aligned;" ::: "memory"); }
__device__ __forceinline__ void wg_commit() { asm volatile("wgmma.commit_group.sync.aligned;" ::: "memory"); }
template <int N> __device__ __forceinline__ void wg_wait() { asm volatile("wgmma.wait_group.sync.aligned %0;" ::"n"(N) : "memory"); }
__device__ __forceinline__ uint64_t mkdesc(uint32_t addr, uint32_t lbo, uint32_t sbo, int sw) {
  return (uint64_t)((addr & 0x3FFFF) >> 4) | ((uint64_t)(lbo >> 4) << 16) | ((uint64_t)(sbo >> 4) << 32) | ((uint64_t)sw << 62);
}
__device__ __forceinline__ void ldsm4(uint32_t* r, uint32_t a) {
  asm volatile("ldmatrix.sync.aligned.m8n8.x4.shared.b16 {%0,%1,%2,%3}, [%4];" : "=r"(r[0]), "=r"(r[1]), "=r"(r[2]), "=r"(r[3]) : "r"(a) : "memory");
}
__device__ __forceinline__ void ldsm4t(uint32_t* r, uint32_t a) {
  asm volatile("ldmatrix.sync.aligned.m8n8.x4.trans.shared.b16 {%0,%1,%2,%3}, [%4];" : "=r"(r[0]), "=r"(r[1]), "=r"(r[2]), "=r"(r[3]) : "r"(a) : "memory");
}
__device__ __forceinline__ void stsm4(uint32_t a, uint32_t r0, uint32_t r1, uint32_t r2, uint32_t r3) {
  asm volatile("stmatrix.sync.aligned.m8n8.x4.shared.b16 [%0], {%1,%2,%3,%4};" ::"r"(a), "r"(r0), "r"(r1), "r"(r2), "r"(r3) : "memory");
}
__device__ __forceinline__ void stsm4t(uint32_t a, uint32_t r0, uint32_t r1, uint32_t r2, uint32_t r3) {
  asm volatile("stmatrix.sync.aligned.m8n8.x4.trans.shared.b16 [%0], {%1,%2,%3,%4};" ::"r"(a), "r"(r0), "r"(r1), "r"(r2), "r"(r3) : "memory");
}
__device__ __forceinline__ uint32_t movm_t(uint32_t a) { uint32_t r; asm volatile("movmatrix.sync.aligned.m8n8.trans.b16 %0, %1;" : "=r"(r) : "r"(a)); return r; }
__device__ __forceinline__ uint32_t lds32(uint32_t a) { uint32_t v; asm volatile("ld.shared.b32 %0, [%1];" : "=r"(v) : "r"(a) : "memory"); return v; }
__device__ __forceinline__ float2 lds64f(uint32_t a) { float2 v; asm volatile("ld.shared.v2.f32 {%0,%1}, [%2];" : "=f"(v.x), "=f"(v.y) : "r"(a) : "memory"); return v; }
__device__ __forceinline__ float4 lds128f(uint32_t a) { float4 v; asm volatile("ld.shared.v4.f32 {%0,%1,%2,%3}, [%4];" : "=f"(v.x), "=f"(v.y), "=f"(v.z), "=f"(v.w) : "r"(a) : "memory"); return v; }
__device__ __forceinline__ uint4 lds128(uint32_t a) { uint4 v; asm volatile("ld.shared.v4.b32 {%0,%1,%2,%3}, [%4];" : "=r"(v.x), "=r"(v.y), "=r"(v.z), "=r"(v.w) : "r"(a) : "memory"); return v; }
__device__ __forceinline__ void sts128(uint32_t a, uint4 v) { asm volatile("st.shared.v4.b32 [%0], {%1,%2,%3,%4};" ::"r"(a), "r"(v.x), "r"(v.y), "r"(v.z), "r"(v.w) : "memory"); }
__device__ __forceinline__ void sts128f(uint32_t a, float x, float y, float z, float w) { asm volatile("st.shared.v4.f32 [%0], {%1,%2,%3,%4};" ::"r"(a), "f"(x), "f"(y), "f"(z), "f"(w) : "memory"); }
__device__ __forceinline__ void sts32f(uint32_t a, float v) { asm volatile("st.shared.f32 [%0], %1;" ::"r"(a), "f"(v) : "memory"); }
__device__ __forceinline__ void sts16(uint32_t a, uint16_t v) { asm volatile("st.shared.u16 [%0], %1;" ::"r"(a), "h"(v) : "memory"); }
__device__ __forceinline__ uint32_t lds16(uint32_t a) { uint16_t v; asm volatile("ld.shared.u16 %0, [%1];" : "=h"(v) : "r"(a) : "memory"); return v; }
__device__ __forceinline__ uint32_t packbf(float lo, float hi) { uint32_t r; asm("cvt.rn.bf16x2.f32 %0, %1, %2;" : "=r"(r) : "f"(hi), "f"(lo)); return r; }
__device__ __forceinline__ float bf_lo(uint32_t v) { return __uint_as_float(v << 16); }
__device__ __forceinline__ float bf_hi(uint32_t v) { return __uint_as_float(v & 0xffff0000u); }
__device__ __forceinline__ float ex2(float x) { float r; asm("ex2.approx.ftz.f32 %0, %1;" : "=f"(r) : "f"(x)); return r; }
__device__ __forceinline__ float rsqrt_approx(float x) { float r; asm("rsqrt.approx.ftz.f32 %0, %1;" : "=f"(r) : "f"(x)); return r; }
__device__ __forceinline__ float rcp_approx(float x) { float r; asm("rcp.approx.ftz.f32 %0, %1;" : "=f"(r) : "f"(x)); return r; }
__device__ __forceinline__ void mma_bf16(float* d, const uint32_t* a, uint32_t b0, uint32_t b1) {
  asm("mma.sync.aligned.m16n8k16.row.col.f32.bf16.bf16.f32 {%0,%1,%2,%3}, {%4,%5,%6,%7}, {%8,%9}, {%0,%1,%2,%3};"
               : "+f"(d[0]), "+f"(d[1]), "+f"(d[2]), "+f"(d[3]) : "r"(a[0]), "r"(a[1]), "r"(a[2]), "r"(a[3]), "r"(b0), "r"(b1));
}
__device__ __forceinline__ void mma_bf16_k8(float* d, uint32_t a0, uint32_t a1, uint32_t b) {
  asm("mma.sync.aligned.m16n8k8.row.col.f32.bf16.bf16.f32 {%0,%1,%2,%3}, {%4,%5}, {%6}, {%0,%1,%2,%3};"
      : "+f"(d[0]), "+f"(d[1]), "+f"(d[2]), "+f"(d[3]) : "r"(a0), "r"(a1), "r"(b));
}
__device__ __forceinline__ void red_release(unsigned* p) { asm volatile("red.release.gpu.global.add.u32 [%0], 1;" ::"l"(p) : "memory"); }
__device__ __forceinline__ void red_relaxed(unsigned* p) { asm volatile("red.relaxed.gpu.global.add.u32 [%0], 1;" ::"l"(p) : "memory"); }
__device__ __forceinline__ unsigned ld_relaxed(const unsigned* p) { unsigned v; asm volatile("ld.relaxed.gpu.global.u32 %0, [%1];" : "=r"(v) : "l"(p) : "memory"); return v; }
__device__ __forceinline__ void spin_until(const unsigned* p, unsigned target) {
  int it = 0;
  while ((int)(ld_relaxed(p) - target) < 0) {
    if (++it > (1 << 23)) __trap();
  }
}
__device__ __forceinline__ uint4 ldcg128(const void* p) { uint4 v; asm volatile("ld.global.cg.v4.b32 {%0,%1,%2,%3}, [%4];" : "=r"(v.x), "=r"(v.y), "=r"(v.z), "=r"(v.w) : "l"(p) : "memory"); return v; }
__device__ __forceinline__ uint4 ld_tagged(const uint4* p) { uint4 v; asm volatile("ld.relaxed.gpu.global.v4.u32 {%0,%1,%2,%3}, [%4];" : "=r"(v.x), "=r"(v.y), "=r"(v.z), "=r"(v.w) : "l"(p) : "memory"); return v; }
__device__ __forceinline__ uint2 ld_part(const uint2* p) { uint2 v; asm volatile("ld.relaxed.gpu.global.v2.u32 {%0,%1}, [%2];" : "=r"(v.x), "=r"(v.y) : "l"(p) : "memory"); return v; }
__device__ __forceinline__ void st_part(uint2* p, float s, float q, uint32_t tag) {
  asm volatile("st.relaxed.gpu.global.v2.u32 [%0], {%1,%2};" ::"l"(p), "r"(__float_as_uint(s)), "r"((__float_as_uint(q) & ~7u) | tag) : "memory");
}
__device__ __forceinline__ uint32_t part_tag(uint32_t epoch, int k) { return (4 * (epoch % 7) + k) % 7 + 1; }
__device__ __forceinline__ void st_tagged3(uint4* p, uint32_t a, uint32_t b, uint32_t c, uint32_t tag) { asm volatile("st.relaxed.gpu.global.v4.u32 [%0], {%1,%2,%3,%4};" ::"l"(p), "r"(a), "r"(b), "r"(c), "r"(tag) : "memory"); }
__device__ __forceinline__ uint32_t hadd2(uint32_t a, uint32_t b) { uint32_t r; asm("add.rn.bf16x2 %0, %1, %2;" : "=r"(r) : "r"(a), "r"(b)); return r; }
__device__ __forceinline__ uint32_t hmul2(uint32_t a, uint32_t b) { uint32_t r; asm("mul.rn.bf16x2 %0, %1, %2;" : "=r"(r) : "r"(a), "r"(b)); return r; }

template<int N,int TB> __device__ __forceinline__ void wgmma_rs(float* d, const uint32_t* a, uint64_t db, int sd);
template<int N,int TA,int TB> __device__ __forceinline__ void wgmma_ss(float* d, uint64_t da, uint64_t db, int sd);
template<> __device__ __forceinline__ void wgmma_rs<128,0>(float* d, const uint32_t* a, uint64_t db, int sd) {
  asm volatile("{\n.reg .pred p;\nsetp.ne.b32 p, %69, 0;\nwgmma.mma_async.sync.aligned.m64n128k16.f32.bf16.bf16 {%0,%1,%2,%3,%4,%5,%6,%7,%8,%9,%10,%11,%12,%13,%14,%15,%16,%17,%18,%19,%20,%21,%22,%23,%24,%25,%26,%27,%28,%29,%30,%31,%32,%33,%34,%35,%36,%37,%38,%39,%40,%41,%42,%43,%44,%45,%46,%47,%48,%49,%50,%51,%52,%53,%54,%55,%56,%57,%58,%59,%60,%61,%62,%63}, {%64,%65,%66,%67}, %68, p, 1, 1, 0;\n}\n"
   : "+f"(d[0]),"+f"(d[1]),"+f"(d[2]),"+f"(d[3]),"+f"(d[4]),"+f"(d[5]),"+f"(d[6]),"+f"(d[7]),"+f"(d[8]),"+f"(d[9]),"+f"(d[10]),"+f"(d[11]),"+f"(d[12]),"+f"(d[13]),"+f"(d[14]),"+f"(d[15]),"+f"(d[16]),"+f"(d[17]),"+f"(d[18]),"+f"(d[19]),"+f"(d[20]),"+f"(d[21]),"+f"(d[22]),"+f"(d[23]),"+f"(d[24]),"+f"(d[25]),"+f"(d[26]),"+f"(d[27]),"+f"(d[28]),"+f"(d[29]),"+f"(d[30]),"+f"(d[31]),"+f"(d[32]),"+f"(d[33]),"+f"(d[34]),"+f"(d[35]),"+f"(d[36]),"+f"(d[37]),"+f"(d[38]),"+f"(d[39]),"+f"(d[40]),"+f"(d[41]),"+f"(d[42]),"+f"(d[43]),"+f"(d[44]),"+f"(d[45]),"+f"(d[46]),"+f"(d[47]),"+f"(d[48]),"+f"(d[49]),"+f"(d[50]),"+f"(d[51]),"+f"(d[52]),"+f"(d[53]),"+f"(d[54]),"+f"(d[55]),"+f"(d[56]),"+f"(d[57]),"+f"(d[58]),"+f"(d[59]),"+f"(d[60]),"+f"(d[61]),"+f"(d[62]),"+f"(d[63])
   : "r"(a[0]), "r"(a[1]), "r"(a[2]), "r"(a[3]), "l"(db), "r"(sd));
}
template<> __device__ __forceinline__ void wgmma_rs<120,0>(float* d, const uint32_t* a, uint64_t db, int sd) {
  asm volatile("{\n.reg .pred p;\nsetp.ne.b32 p, %65, 0;\nwgmma.mma_async.sync.aligned.m64n120k16.f32.bf16.bf16 {%0,%1,%2,%3,%4,%5,%6,%7,%8,%9,%10,%11,%12,%13,%14,%15,%16,%17,%18,%19,%20,%21,%22,%23,%24,%25,%26,%27,%28,%29,%30,%31,%32,%33,%34,%35,%36,%37,%38,%39,%40,%41,%42,%43,%44,%45,%46,%47,%48,%49,%50,%51,%52,%53,%54,%55,%56,%57,%58,%59}, {%60,%61,%62,%63}, %64, p, 1, 1, 0;\n}\n"
   : "+f"(d[0]),"+f"(d[1]),"+f"(d[2]),"+f"(d[3]),"+f"(d[4]),"+f"(d[5]),"+f"(d[6]),"+f"(d[7]),"+f"(d[8]),"+f"(d[9]),"+f"(d[10]),"+f"(d[11]),"+f"(d[12]),"+f"(d[13]),"+f"(d[14]),"+f"(d[15]),"+f"(d[16]),"+f"(d[17]),"+f"(d[18]),"+f"(d[19]),"+f"(d[20]),"+f"(d[21]),"+f"(d[22]),"+f"(d[23]),"+f"(d[24]),"+f"(d[25]),"+f"(d[26]),"+f"(d[27]),"+f"(d[28]),"+f"(d[29]),"+f"(d[30]),"+f"(d[31]),"+f"(d[32]),"+f"(d[33]),"+f"(d[34]),"+f"(d[35]),"+f"(d[36]),"+f"(d[37]),"+f"(d[38]),"+f"(d[39]),"+f"(d[40]),"+f"(d[41]),"+f"(d[42]),"+f"(d[43]),"+f"(d[44]),"+f"(d[45]),"+f"(d[46]),"+f"(d[47]),"+f"(d[48]),"+f"(d[49]),"+f"(d[50]),"+f"(d[51]),"+f"(d[52]),"+f"(d[53]),"+f"(d[54]),"+f"(d[55]),"+f"(d[56]),"+f"(d[57]),"+f"(d[58]),"+f"(d[59])
   : "r"(a[0]), "r"(a[1]), "r"(a[2]), "r"(a[3]), "l"(db), "r"(sd));
}
template<> __device__ __forceinline__ void wgmma_rs<112,0>(float* d, const uint32_t* a, uint64_t db, int sd) {
  asm volatile("{\n.reg .pred p;\nsetp.ne.b32 p, %61, 0;\nwgmma.mma_async.sync.aligned.m64n112k16.f32.bf16.bf16 {%0,%1,%2,%3,%4,%5,%6,%7,%8,%9,%10,%11,%12,%13,%14,%15,%16,%17,%18,%19,%20,%21,%22,%23,%24,%25,%26,%27,%28,%29,%30,%31,%32,%33,%34,%35,%36,%37,%38,%39,%40,%41,%42,%43,%44,%45,%46,%47,%48,%49,%50,%51,%52,%53,%54,%55}, {%56,%57,%58,%59}, %60, p, 1, 1, 0;\n}\n"
   : "+f"(d[0]),"+f"(d[1]),"+f"(d[2]),"+f"(d[3]),"+f"(d[4]),"+f"(d[5]),"+f"(d[6]),"+f"(d[7]),"+f"(d[8]),"+f"(d[9]),"+f"(d[10]),"+f"(d[11]),"+f"(d[12]),"+f"(d[13]),"+f"(d[14]),"+f"(d[15]),"+f"(d[16]),"+f"(d[17]),"+f"(d[18]),"+f"(d[19]),"+f"(d[20]),"+f"(d[21]),"+f"(d[22]),"+f"(d[23]),"+f"(d[24]),"+f"(d[25]),"+f"(d[26]),"+f"(d[27]),"+f"(d[28]),"+f"(d[29]),"+f"(d[30]),"+f"(d[31]),"+f"(d[32]),"+f"(d[33]),"+f"(d[34]),"+f"(d[35]),"+f"(d[36]),"+f"(d[37]),"+f"(d[38]),"+f"(d[39]),"+f"(d[40]),"+f"(d[41]),"+f"(d[42]),"+f"(d[43]),"+f"(d[44]),"+f"(d[45]),"+f"(d[46]),"+f"(d[47]),"+f"(d[48]),"+f"(d[49]),"+f"(d[50]),"+f"(d[51]),"+f"(d[52]),"+f"(d[53]),"+f"(d[54]),"+f"(d[55])
   : "r"(a[0]), "r"(a[1]), "r"(a[2]), "r"(a[3]), "l"(db), "r"(sd));
}
template<> __device__ __forceinline__ void wgmma_rs<104,0>(float* d, const uint32_t* a, uint64_t db, int sd) {
  asm volatile("{\n.reg .pred p;\nsetp.ne.b32 p, %57, 0;\nwgmma.mma_async.sync.aligned.m64n104k16.f32.bf16.bf16 {%0,%1,%2,%3,%4,%5,%6,%7,%8,%9,%10,%11,%12,%13,%14,%15,%16,%17,%18,%19,%20,%21,%22,%23,%24,%25,%26,%27,%28,%29,%30,%31,%32,%33,%34,%35,%36,%37,%38,%39,%40,%41,%42,%43,%44,%45,%46,%47,%48,%49,%50,%51}, {%52,%53,%54,%55}, %56, p, 1, 1, 0;\n}\n"
   : "+f"(d[0]),"+f"(d[1]),"+f"(d[2]),"+f"(d[3]),"+f"(d[4]),"+f"(d[5]),"+f"(d[6]),"+f"(d[7]),"+f"(d[8]),"+f"(d[9]),"+f"(d[10]),"+f"(d[11]),"+f"(d[12]),"+f"(d[13]),"+f"(d[14]),"+f"(d[15]),"+f"(d[16]),"+f"(d[17]),"+f"(d[18]),"+f"(d[19]),"+f"(d[20]),"+f"(d[21]),"+f"(d[22]),"+f"(d[23]),"+f"(d[24]),"+f"(d[25]),"+f"(d[26]),"+f"(d[27]),"+f"(d[28]),"+f"(d[29]),"+f"(d[30]),"+f"(d[31]),"+f"(d[32]),"+f"(d[33]),"+f"(d[34]),"+f"(d[35]),"+f"(d[36]),"+f"(d[37]),"+f"(d[38]),"+f"(d[39]),"+f"(d[40]),"+f"(d[41]),"+f"(d[42]),"+f"(d[43]),"+f"(d[44]),"+f"(d[45]),"+f"(d[46]),"+f"(d[47]),"+f"(d[48]),"+f"(d[49]),"+f"(d[50]),"+f"(d[51])
   : "r"(a[0]), "r"(a[1]), "r"(a[2]), "r"(a[3]), "l"(db), "r"(sd));
}
template<> __device__ __forceinline__ void wgmma_rs<96,0>(float* d, const uint32_t* a, uint64_t db, int sd) {
  asm volatile("{\n.reg .pred p;\nsetp.ne.b32 p, %53, 0;\nwgmma.mma_async.sync.aligned.m64n96k16.f32.bf16.bf16 {%0,%1,%2,%3,%4,%5,%6,%7,%8,%9,%10,%11,%12,%13,%14,%15,%16,%17,%18,%19,%20,%21,%22,%23,%24,%25,%26,%27,%28,%29,%30,%31,%32,%33,%34,%35,%36,%37,%38,%39,%40,%41,%42,%43,%44,%45,%46,%47}, {%48,%49,%50,%51}, %52, p, 1, 1, 0;\n}\n"
   : "+f"(d[0]),"+f"(d[1]),"+f"(d[2]),"+f"(d[3]),"+f"(d[4]),"+f"(d[5]),"+f"(d[6]),"+f"(d[7]),"+f"(d[8]),"+f"(d[9]),"+f"(d[10]),"+f"(d[11]),"+f"(d[12]),"+f"(d[13]),"+f"(d[14]),"+f"(d[15]),"+f"(d[16]),"+f"(d[17]),"+f"(d[18]),"+f"(d[19]),"+f"(d[20]),"+f"(d[21]),"+f"(d[22]),"+f"(d[23]),"+f"(d[24]),"+f"(d[25]),"+f"(d[26]),"+f"(d[27]),"+f"(d[28]),"+f"(d[29]),"+f"(d[30]),"+f"(d[31]),"+f"(d[32]),"+f"(d[33]),"+f"(d[34]),"+f"(d[35]),"+f"(d[36]),"+f"(d[37]),"+f"(d[38]),"+f"(d[39]),"+f"(d[40]),"+f"(d[41]),"+f"(d[42]),"+f"(d[43]),"+f"(d[44]),"+f"(d[45]),"+f"(d[46]),"+f"(d[47])
   : "r"(a[0]), "r"(a[1]), "r"(a[2]), "r"(a[3]), "l"(db), "r"(sd));
}
template<> __device__ __forceinline__ void wgmma_rs<88,0>(float* d, const uint32_t* a, uint64_t db, int sd) {
  asm volatile("{\n.reg .pred p;\nsetp.ne.b32 p, %49, 0;\nwgmma.mma_async.sync.aligned.m64n88k16.f32.bf16.bf16 {%0,%1,%2,%3,%4,%5,%6,%7,%8,%9,%10,%11,%12,%13,%14,%15,%16,%17,%18,%19,%20,%21,%22,%23,%24,%25,%26,%27,%28,%29,%30,%31,%32,%33,%34,%35,%36,%37,%38,%39,%40,%41,%42,%43}, {%44,%45,%46,%47}, %48, p, 1, 1, 0;\n}\n"
   : "+f"(d[0]),"+f"(d[1]),"+f"(d[2]),"+f"(d[3]),"+f"(d[4]),"+f"(d[5]),"+f"(d[6]),"+f"(d[7]),"+f"(d[8]),"+f"(d[9]),"+f"(d[10]),"+f"(d[11]),"+f"(d[12]),"+f"(d[13]),"+f"(d[14]),"+f"(d[15]),"+f"(d[16]),"+f"(d[17]),"+f"(d[18]),"+f"(d[19]),"+f"(d[20]),"+f"(d[21]),"+f"(d[22]),"+f"(d[23]),"+f"(d[24]),"+f"(d[25]),"+f"(d[26]),"+f"(d[27]),"+f"(d[28]),"+f"(d[29]),"+f"(d[30]),"+f"(d[31]),"+f"(d[32]),"+f"(d[33]),"+f"(d[34]),"+f"(d[35]),"+f"(d[36]),"+f"(d[37]),"+f"(d[38]),"+f"(d[39]),"+f"(d[40]),"+f"(d[41]),"+f"(d[42]),"+f"(d[43])
   : "r"(a[0]), "r"(a[1]), "r"(a[2]), "r"(a[3]), "l"(db), "r"(sd));
}
template<> __device__ __forceinline__ void wgmma_rs<80,0>(float* d, const uint32_t* a, uint64_t db, int sd) {
  asm volatile("{\n.reg .pred p;\nsetp.ne.b32 p, %45, 0;\nwgmma.mma_async.sync.aligned.m64n80k16.f32.bf16.bf16 {%0,%1,%2,%3,%4,%5,%6,%7,%8,%9,%10,%11,%12,%13,%14,%15,%16,%17,%18,%19,%20,%21,%22,%23,%24,%25,%26,%27,%28,%29,%30,%31,%32,%33,%34,%35,%36,%37,%38,%39}, {%40,%41,%42,%43}, %44, p, 1, 1, 0;\n}\n"
   : "+f"(d[0]),"+f"(d[1]),"+f"(d[2]),"+f"(d[3]),"+f"(d[4]),"+f"(d[5]),"+f"(d[6]),"+f"(d[7]),"+f"(d[8]),"+f"(d[9]),"+f"(d[10]),"+f"(d[11]),"+f"(d[12]),"+f"(d[13]),"+f"(d[14]),"+f"(d[15]),"+f"(d[16]),"+f"(d[17]),"+f"(d[18]),"+f"(d[19]),"+f"(d[20]),"+f"(d[21]),"+f"(d[22]),"+f"(d[23]),"+f"(d[24]),"+f"(d[25]),"+f"(d[26]),"+f"(d[27]),"+f"(d[28]),"+f"(d[29]),"+f"(d[30]),"+f"(d[31]),"+f"(d[32]),"+f"(d[33]),"+f"(d[34]),"+f"(d[35]),"+f"(d[36]),"+f"(d[37]),"+f"(d[38]),"+f"(d[39])
   : "r"(a[0]), "r"(a[1]), "r"(a[2]), "r"(a[3]), "l"(db), "r"(sd));
}
template<> __device__ __forceinline__ void wgmma_rs<72,0>(float* d, const uint32_t* a, uint64_t db, int sd) {
  asm volatile("{\n.reg .pred p;\nsetp.ne.b32 p, %41, 0;\nwgmma.mma_async.sync.aligned.m64n72k16.f32.bf16.bf16 {%0,%1,%2,%3,%4,%5,%6,%7,%8,%9,%10,%11,%12,%13,%14,%15,%16,%17,%18,%19,%20,%21,%22,%23,%24,%25,%26,%27,%28,%29,%30,%31,%32,%33,%34,%35}, {%36,%37,%38,%39}, %40, p, 1, 1, 0;\n}\n"
   : "+f"(d[0]),"+f"(d[1]),"+f"(d[2]),"+f"(d[3]),"+f"(d[4]),"+f"(d[5]),"+f"(d[6]),"+f"(d[7]),"+f"(d[8]),"+f"(d[9]),"+f"(d[10]),"+f"(d[11]),"+f"(d[12]),"+f"(d[13]),"+f"(d[14]),"+f"(d[15]),"+f"(d[16]),"+f"(d[17]),"+f"(d[18]),"+f"(d[19]),"+f"(d[20]),"+f"(d[21]),"+f"(d[22]),"+f"(d[23]),"+f"(d[24]),"+f"(d[25]),"+f"(d[26]),"+f"(d[27]),"+f"(d[28]),"+f"(d[29]),"+f"(d[30]),"+f"(d[31]),"+f"(d[32]),"+f"(d[33]),"+f"(d[34]),"+f"(d[35])
   : "r"(a[0]), "r"(a[1]), "r"(a[2]), "r"(a[3]), "l"(db), "r"(sd));
}
template<> __device__ __forceinline__ void wgmma_rs<64,0>(float* d, const uint32_t* a, uint64_t db, int sd) {
  asm volatile("{\n.reg .pred p;\nsetp.ne.b32 p, %37, 0;\nwgmma.mma_async.sync.aligned.m64n64k16.f32.bf16.bf16 {%0,%1,%2,%3,%4,%5,%6,%7,%8,%9,%10,%11,%12,%13,%14,%15,%16,%17,%18,%19,%20,%21,%22,%23,%24,%25,%26,%27,%28,%29,%30,%31}, {%32,%33,%34,%35}, %36, p, 1, 1, 0;\n}\n"
   : "+f"(d[0]),"+f"(d[1]),"+f"(d[2]),"+f"(d[3]),"+f"(d[4]),"+f"(d[5]),"+f"(d[6]),"+f"(d[7]),"+f"(d[8]),"+f"(d[9]),"+f"(d[10]),"+f"(d[11]),"+f"(d[12]),"+f"(d[13]),"+f"(d[14]),"+f"(d[15]),"+f"(d[16]),"+f"(d[17]),"+f"(d[18]),"+f"(d[19]),"+f"(d[20]),"+f"(d[21]),"+f"(d[22]),"+f"(d[23]),"+f"(d[24]),"+f"(d[25]),"+f"(d[26]),"+f"(d[27]),"+f"(d[28]),"+f"(d[29]),"+f"(d[30]),"+f"(d[31])
   : "r"(a[0]), "r"(a[1]), "r"(a[2]), "r"(a[3]), "l"(db), "r"(sd));
}
template<> __device__ __forceinline__ void wgmma_ss<64,0,1>(float* d, uint64_t da, uint64_t db, int sd) {
  asm volatile("{\n.reg .pred p;\nsetp.ne.b32 p, %34, 0;\nwgmma.mma_async.sync.aligned.m64n64k16.f32.bf16.bf16 {%0,%1,%2,%3,%4,%5,%6,%7,%8,%9,%10,%11,%12,%13,%14,%15,%16,%17,%18,%19,%20,%21,%22,%23,%24,%25,%26,%27,%28,%29,%30,%31}, %32, %33, p, 1, 1, 0, 1;\n}\n"
   : "+f"(d[0]),"+f"(d[1]),"+f"(d[2]),"+f"(d[3]),"+f"(d[4]),"+f"(d[5]),"+f"(d[6]),"+f"(d[7]),"+f"(d[8]),"+f"(d[9]),"+f"(d[10]),"+f"(d[11]),"+f"(d[12]),"+f"(d[13]),"+f"(d[14]),"+f"(d[15]),"+f"(d[16]),"+f"(d[17]),"+f"(d[18]),"+f"(d[19]),"+f"(d[20]),"+f"(d[21]),"+f"(d[22]),"+f"(d[23]),"+f"(d[24]),"+f"(d[25]),"+f"(d[26]),"+f"(d[27]),"+f"(d[28]),"+f"(d[29]),"+f"(d[30]),"+f"(d[31])
   : "l"(da), "l"(db), "r"(sd));
}
template<> __device__ __forceinline__ void wgmma_ss<64,1,1>(float* d, uint64_t da, uint64_t db, int sd) {
  asm volatile("{\n.reg .pred p;\nsetp.ne.b32 p, %34, 0;\nwgmma.mma_async.sync.aligned.m64n64k16.f32.bf16.bf16 {%0,%1,%2,%3,%4,%5,%6,%7,%8,%9,%10,%11,%12,%13,%14,%15,%16,%17,%18,%19,%20,%21,%22,%23,%24,%25,%26,%27,%28,%29,%30,%31}, %32, %33, p, 1, 1, 1, 1;\n}\n"
   : "+f"(d[0]),"+f"(d[1]),"+f"(d[2]),"+f"(d[3]),"+f"(d[4]),"+f"(d[5]),"+f"(d[6]),"+f"(d[7]),"+f"(d[8]),"+f"(d[9]),"+f"(d[10]),"+f"(d[11]),"+f"(d[12]),"+f"(d[13]),"+f"(d[14]),"+f"(d[15]),"+f"(d[16]),"+f"(d[17]),"+f"(d[18]),"+f"(d[19]),"+f"(d[20]),"+f"(d[21]),"+f"(d[22]),"+f"(d[23]),"+f"(d[24]),"+f"(d[25]),"+f"(d[26]),"+f"(d[27]),"+f"(d[28]),"+f"(d[29]),"+f"(d[30]),"+f"(d[31])
   : "l"(da), "l"(db), "r"(sd));
}
template<> __device__ __forceinline__ void wgmma_ss<192,0,1>(float* d, uint64_t da, uint64_t db, int sd) {
  asm volatile("{\n.reg .pred p;\nsetp.ne.b32 p, %98, 0;\nwgmma.mma_async.sync.aligned.m64n192k16.f32.bf16.bf16 {%0,%1,%2,%3,%4,%5,%6,%7,%8,%9,%10,%11,%12,%13,%14,%15,%16,%17,%18,%19,%20,%21,%22,%23,%24,%25,%26,%27,%28,%29,%30,%31,%32,%33,%34,%35,%36,%37,%38,%39,%40,%41,%42,%43,%44,%45,%46,%47,%48,%49,%50,%51,%52,%53,%54,%55,%56,%57,%58,%59,%60,%61,%62,%63,%64,%65,%66,%67,%68,%69,%70,%71,%72,%73,%74,%75,%76,%77,%78,%79,%80,%81,%82,%83,%84,%85,%86,%87,%88,%89,%90,%91,%92,%93,%94,%95}, %96, %97, p, 1, 1, 0, 1;\n}\n"
   : "+f"(d[0]),"+f"(d[1]),"+f"(d[2]),"+f"(d[3]),"+f"(d[4]),"+f"(d[5]),"+f"(d[6]),"+f"(d[7]),"+f"(d[8]),"+f"(d[9]),"+f"(d[10]),"+f"(d[11]),"+f"(d[12]),"+f"(d[13]),"+f"(d[14]),"+f"(d[15]),"+f"(d[16]),"+f"(d[17]),"+f"(d[18]),"+f"(d[19]),"+f"(d[20]),"+f"(d[21]),"+f"(d[22]),"+f"(d[23]),"+f"(d[24]),"+f"(d[25]),"+f"(d[26]),"+f"(d[27]),"+f"(d[28]),"+f"(d[29]),"+f"(d[30]),"+f"(d[31]),"+f"(d[32]),"+f"(d[33]),"+f"(d[34]),"+f"(d[35]),"+f"(d[36]),"+f"(d[37]),"+f"(d[38]),"+f"(d[39]),"+f"(d[40]),"+f"(d[41]),"+f"(d[42]),"+f"(d[43]),"+f"(d[44]),"+f"(d[45]),"+f"(d[46]),"+f"(d[47]),"+f"(d[48]),"+f"(d[49]),"+f"(d[50]),"+f"(d[51]),"+f"(d[52]),"+f"(d[53]),"+f"(d[54]),"+f"(d[55]),"+f"(d[56]),"+f"(d[57]),"+f"(d[58]),"+f"(d[59]),"+f"(d[60]),"+f"(d[61]),"+f"(d[62]),"+f"(d[63]),"+f"(d[64]),"+f"(d[65]),"+f"(d[66]),"+f"(d[67]),"+f"(d[68]),"+f"(d[69]),"+f"(d[70]),"+f"(d[71]),"+f"(d[72]),"+f"(d[73]),"+f"(d[74]),"+f"(d[75]),"+f"(d[76]),"+f"(d[77]),"+f"(d[78]),"+f"(d[79]),"+f"(d[80]),"+f"(d[81]),"+f"(d[82]),"+f"(d[83]),"+f"(d[84]),"+f"(d[85]),"+f"(d[86]),"+f"(d[87]),"+f"(d[88]),"+f"(d[89]),"+f"(d[90]),"+f"(d[91]),"+f"(d[92]),"+f"(d[93]),"+f"(d[94]),"+f"(d[95])
   : "l"(da), "l"(db), "r"(sd));
}
template<> __device__ __forceinline__ void wgmma_ss<192,1,1>(float* d, uint64_t da, uint64_t db, int sd) {
  asm volatile("{\n.reg .pred p;\nsetp.ne.b32 p, %98, 0;\nwgmma.mma_async.sync.aligned.m64n192k16.f32.bf16.bf16 {%0,%1,%2,%3,%4,%5,%6,%7,%8,%9,%10,%11,%12,%13,%14,%15,%16,%17,%18,%19,%20,%21,%22,%23,%24,%25,%26,%27,%28,%29,%30,%31,%32,%33,%34,%35,%36,%37,%38,%39,%40,%41,%42,%43,%44,%45,%46,%47,%48,%49,%50,%51,%52,%53,%54,%55,%56,%57,%58,%59,%60,%61,%62,%63,%64,%65,%66,%67,%68,%69,%70,%71,%72,%73,%74,%75,%76,%77,%78,%79,%80,%81,%82,%83,%84,%85,%86,%87,%88,%89,%90,%91,%92,%93,%94,%95}, %96, %97, p, 1, 1, 1, 1;\n}\n"
   : "+f"(d[0]),"+f"(d[1]),"+f"(d[2]),"+f"(d[3]),"+f"(d[4]),"+f"(d[5]),"+f"(d[6]),"+f"(d[7]),"+f"(d[8]),"+f"(d[9]),"+f"(d[10]),"+f"(d[11]),"+f"(d[12]),"+f"(d[13]),"+f"(d[14]),"+f"(d[15]),"+f"(d[16]),"+f"(d[17]),"+f"(d[18]),"+f"(d[19]),"+f"(d[20]),"+f"(d[21]),"+f"(d[22]),"+f"(d[23]),"+f"(d[24]),"+f"(d[25]),"+f"(d[26]),"+f"(d[27]),"+f"(d[28]),"+f"(d[29]),"+f"(d[30]),"+f"(d[31]),"+f"(d[32]),"+f"(d[33]),"+f"(d[34]),"+f"(d[35]),"+f"(d[36]),"+f"(d[37]),"+f"(d[38]),"+f"(d[39]),"+f"(d[40]),"+f"(d[41]),"+f"(d[42]),"+f"(d[43]),"+f"(d[44]),"+f"(d[45]),"+f"(d[46]),"+f"(d[47]),"+f"(d[48]),"+f"(d[49]),"+f"(d[50]),"+f"(d[51]),"+f"(d[52]),"+f"(d[53]),"+f"(d[54]),"+f"(d[55]),"+f"(d[56]),"+f"(d[57]),"+f"(d[58]),"+f"(d[59]),"+f"(d[60]),"+f"(d[61]),"+f"(d[62]),"+f"(d[63]),"+f"(d[64]),"+f"(d[65]),"+f"(d[66]),"+f"(d[67]),"+f"(d[68]),"+f"(d[69]),"+f"(d[70]),"+f"(d[71]),"+f"(d[72]),"+f"(d[73]),"+f"(d[74]),"+f"(d[75]),"+f"(d[76]),"+f"(d[77]),"+f"(d[78]),"+f"(d[79]),"+f"(d[80]),"+f"(d[81]),"+f"(d[82]),"+f"(d[83]),"+f"(d[84]),"+f"(d[85]),"+f"(d[86]),"+f"(d[87]),"+f"(d[88]),"+f"(d[89]),"+f"(d[90]),"+f"(d[91]),"+f"(d[92]),"+f"(d[93]),"+f"(d[94]),"+f"(d[95])
   : "l"(da), "l"(db), "r"(sd));
}

__device__ __forceinline__ void stats_publish(uint32_t sb, int layer, int rb, int hg, int ht, uint32_t tag) {
  const int lane = ht & 31, w = ht >> 5, g = lane >> 2, t = lane & 3, ks = hg & 3;
  uint32_t xa;
  if (layer == 0) {
    const int row = 16 * w + (lane & 15), kc = 2 * ks + (lane >> 4);
    xa = row * 128 + ((kc ^ (row & 7)) << 4);
  } else {
    const int k = 16 * ks + (lane & 7) + 8 * (lane >> 4), pc = 2 * w + ((lane >> 3) & 1);
    xa = k * 128 + ((pc ^ (k & 7)) << 4);
  }
  float s[4] = {0.f, 0.f, 0.f, 0.f}, q[4] = {0.f, 0.f, 0.f, 0.f};
#pragma unroll 1
  for (int c = hg >> 2; c < 8; c += 2) {
    mbar_wait(sb + SM_BAR + 8 * (B_XF + c), layer);
    if (c >= 6) ATS(48, 256);
    if (c < 2) ATS(51, 256);
    uint32_t A[2][4];
#pragma unroll
    for (int h = 0; h < 2; h++) {
      if (layer == 0) ldsm4(A[h], sb + SM_X + c * 16384 + h * 8192 + xa);
      else ldsm4t(A[h], sb + SM_X + c * 16384 + h * 8192 + xa);
    }
#pragma unroll
    for (int r = 0; r < 4; r++)
#pragma unroll
      for (int i = 0; i < 2; i++) {
        const uint32_t v = A[r >> 1][2 * i + (r & 1)];
        const float a = bf_lo(v), b = bf_hi(v);
        s[r] += a + b; q[r] = fmaf(a, a, q[r]); q[r] = fmaf(b, b, q[r]);
      }
  }
#pragma unroll
  for (int r = 0; r < 2; r++) {
    s[r] = ((t & 2) ? s[r + 2] : s[r]) + __shfl_xor_sync(~0u, (t & 2) ? s[r] : s[r + 2], 2);
    q[r] = ((t & 2) ? q[r + 2] : q[r]) + __shfl_xor_sync(~0u, (t & 2) ? q[r] : q[r + 2], 2);
  }
  s[0] = ((t & 1) ? s[1] : s[0]) + __shfl_xor_sync(~0u, (t & 1) ? s[0] : s[1], 1);
  q[0] = ((t & 1) ? q[1] : q[0]) + __shfl_xor_sync(~0u, (t & 1) ? q[0] : q[1], 1);
  st_part(&g_part[(rb * 8 + hg) * 128 + 64 * (t >> 1) + 16 * w + 8 * (t & 1) + g], s[0], q[0], tag);
  ATS(49, 256);
}
__device__ __forceinline__ void stats_gather(uint32_t sb, int rb, int ht, uint32_t tag) {
  const uint2* src = &g_part[rb * 8 * 128 + ht];
  uint2 v[8];
  bool ok;
  int it = 0;
  do {
    ok = true;
#pragma unroll
    for (int i = 0; i < 8; i++) v[i] = ld_part(src + i * 128);
#pragma unroll
    for (int i = 0; i < 8; i++) ok = ok && (v[i].y & 7u) == tag;
    if (++it > (1 << 22)) __trap();
  } while (!__all_sync(~0u, ok));
  float s = 0.f, q = 0.f;
#pragma unroll
  for (int i = 0; i < 8; i++) { s += __uint_as_float(v[i].x); q += __uint_as_float(v[i].y); }
  const float mean = s * (1.f / DM);
  const float rstd = rsqrt_approx(fmaxf(q * (1.f / DM) - mean * mean, 0.f) + 1e-5f);
  asm volatile("st.shared.v2.f32 [%0], {%1,%2};" ::"r"(sb + SM_ST + ht * 8), "f"(mean), "f"(rstd) : "memory");
  __syncwarp();
  if (elect_one()) mbar_arrive(sb + SM_BAR + 8 * B_STF);
}
__device__ __forceinline__ void halo_receive(uint32_t sb, int layer, int rb, int hg, int ht) {
  const int lane = ht & 31, h = ht >> 5;
  uint4 kv = make_uint4(0, 0, 0, 0);
  mbar_wait(sb + SM_BAR + 8 * B_SD, layer);
  if (rb & 7) {
    const uint32_t tag = 2 * lds32(sb + SM_EP) + layer + 1;
    const uint4* src = &g_halo[((rb - 1) * 8 + hg) * 192 + h * 48];
    delay<D_HALO>();
    uint4 a;
    uint2 b;
    int it = 0;
    do {
      a = ld_tagged(src + lane); b = ld_part((const uint2*)(src + 32) + lane);
      if (++it > (1 << 22)) __trap();
    } while (!__all_sync(~0u, a.w == tag && b.y == tag));
    kv = make_uint4(a.x, a.y, movm_t(a.z), movm_t(b.x));
  }
  sts128(sb + SM_KVX + h * 512 + lane * 16, kv);
  ATS(61, 256);
  bar_arrive(7, 160);
  if (elect_one()) mbar_arrive(sb + SM_BAR + 8 * B_HF);
}

template <bool TR>
__device__ __forceinline__ void gemm_section(float* acc, float2* cs, uint32_t sb, int layer, int wg, int w, int lane) {
  const uint32_t bar = sb + SM_BAR;
  const bool leader = (w == 0) && (lane == 0);
  auto issue = [&](int c, int slot) {
    mbar_wait(bar + 8 * (B_XF + c), layer);
    mbar_wait(bar + 8 * (B_KVF + c), layer);
    const uint64_t da = mkdesc(sb + SM_X + c * 16384 + wg * 8192, TR ? 8192 : 16, 1024, 1);
    const uint64_t db = mkdesc(sb + SM_W + slot * 24576, 8192, 1024, 1);
    wg_fence();
#pragma unroll
    for (int ks = 0; ks < 4; ks++) wgmma_ss<192, TR ? 1 : 0, 1>(acc, da + (TR ? ks * 128 : ks * 2), db + ks * 128, (c | ks) != 0);
    wg_commit();
  };
  auto step = [&](int c, int slot) {
    issue(c, slot);
    wg_wait<1>();
    if (leader) mbar_arrive(bar + 8 * (B_KVE + c - 1));
  };
  issue(0, 0);
  if (threadIdx.x == 0) TS(2 + layer * 20 + 0);
  if (threadIdx.x == 128 && layer == 1) TS(60);
  step(1, 1); step(2, 2); step(3, 0); step(4, 1);
  auto ld_cs = [&](int j0) {
#pragma unroll
    for (int j = j0; j < j0 + 8; j++) cs[j] = lds64f(sb + SM_CS + 4 * (8 * j + 2 * (lane & 3)));
  };
  if (TR) ld_cs(8);
  step(5, 2);
  if (!TR) { mbar_wait(bar + 8 * B_CSF, 0); ld_cs(8); }
  ld_cs(16);
  if (wg == 0) bar_sync(5, 256);
  issue(6, 0);
  issue(7, 1);
  if (wg == 1) bar_arrive(5, 256);
}

__device__ __forceinline__ void attn_phase(const Params& p, uint32_t sb, int layer, int rb, int hg, int wg, int w) {
  const int lane = opaque_tid() & 31;
  const int g = lane >> 2, t = lane & 3;
  const uint32_t bar = sb + SM_BAR;
  const int row0 = 64 * wg + 16 * w;
  const bool leader = (w == 0) && (lane == 0);
  float acc[96];
  float2 cs[24];
  if (layer) gemm_section<true>(acc, cs, sb, layer, wg, w, lane);
  else gemm_section<false>(acc, cs, sb, layer, wg, w, lane);
  ATS(41, 224);
  mbar_wait(bar + 8 * B_STF, layer);
  const uint32_t tag = 2 * lds32(sb + SM_EP) + layer + 1;
  const float2 st0 = lds64f(sb + SM_ST + (row0 + g) * 8), st1 = lds64f(sb + SM_ST + (row0 + g + 8) * 8);
  const float mean0 = st0.x, rstd0 = st0.y, mean1 = st1.x, rstd1 = st1.y;
  wg_wait<0>();
  if (threadIdx.x == 0) TS(2 + layer * 20 + 1);
  ATS(39, 224);
  if (leader) mbar_arrive(bar + 8 * B_QDONE);

  uint32_t fp[4][4], fl[4][4], fh[4][4], qa[4][4];
  const int cw = 4 * wg + w;
  {
    const float nm0 = -mean0 * rstd0, nm1 = -mean1 * rstd1;
    const uint32_t kvx = sb + SM_KVX + cw * 2048 + lane * 16;
#pragma unroll
    for (int h = 0; h < 4; h++)
#pragma unroll
      for (int k = 0; k < 4; k++) {
        const int j = 8 + (k >> 1) * 8 + 2 * h + (k & 1);
        fh[h][k] = packbf(fmaf(acc[4 * j + 2], rstd1, nm1 * cs[j].x), fmaf(acc[4 * j + 3], rstd1, nm1 * cs[j].y));
      }
    if (cw == 7) {
      uint4* halo = &g_halo[(rb * 8 + hg) * 192];
#pragma unroll
      for (int h = 0; h < 4; h++) {
        st_tagged3(halo + h * 48 + lane, fh[h][0], fh[h][1], fh[h][2], tag);
        asm volatile("st.relaxed.gpu.global.v2.u32 [%0], {%1,%2};" ::"l"((uint2*)(halo + h * 48 + 32) + lane), "r"(fh[h][3]), "r"(tag) : "memory");
      }
      if (elect_one()) mbar_arrive(bar + 8 * B_SD);
      if (layer == TLAYER && threadIdx.x == 224) TS(47);
    }
#pragma unroll
    for (int h = 0; h < 4; h++) { fh[h][2] = movm_t(fh[h][2]); fh[h][3] = movm_t(fh[h][3]); }
    if (cw != 7) {
#pragma unroll
      for (int h = 0; h < 4; h++) sts128(kvx + 2048 + h * 512, make_uint4(fh[h][0], fh[h][1], fh[h][2], fh[h][3]));
      bar_arrive(8 + cw, 64);
    }
    if (layer == TLAYER && threadIdx.x == 0) TS(45);
#pragma unroll
    for (int j = 0; j < 8; j++) cs[j] = lds64f(sb + SM_CS + 4 * (8 * j + 2 * t));
#pragma unroll
    for (int h = 0; h < 4; h++)
#pragma unroll
      for (int k = 0; k < 4; k++) {
        const int j = 8 + (k >> 1) * 8 + 2 * h + (k & 1);
        fl[h][k] = packbf(fmaf(acc[4 * j], rstd0, nm0 * cs[j].x), fmaf(acc[4 * j + 1], rstd0, nm0 * cs[j].y));
        if (k >= 2) fl[h][k] = movm_t(fl[h][k]);
      }
#pragma unroll
    for (int h = 0; h < 4; h++) {
#pragma unroll
      for (int dh = 0; dh < 2; dh++) {
        const int j = 2 * h + dh;
        const float2 c2 = cs[j];
        qa[h][2 * dh] = packbf(fmaf(-mean0, c2.x, acc[4 * j + 0]), fmaf(-mean0, c2.y, acc[4 * j + 1]));
        qa[h][2 * dh + 1] = packbf(fmaf(-mean1, c2.x, acc[4 * j + 2]), fmaf(-mean1, c2.y, acc[4 * j + 3]));
      }
    }
    if (threadIdx.x == 0) TS(2 + layer * 20 + 2);
    bar_sync(7 + cw, cw == 0 ? 160 : 64);
#pragma unroll
    for (int h = 0; h < 4; h++) {
      const uint4 v = lds128(kvx + h * 512);
      fp[h][0] = v.x; fp[h][1] = v.y; fp[h][2] = v.z; fp[h][3] = v.w;
    }
    if (threadIdx.x == 0) TS(2 + layer * 20 + 4);
  }

  const bool u0 = 2 * t > g, u1 = 2 * t + 1 > g;
  const uint32_t mU = (u0 ? 0x0000ffffu : 0u) | (u1 ? 0xffff0000u : 0u);
  const float cl2 = 0.25f * 1.4426950408889634f;
  const float sc0 = rstd0 * cl2, sc1 = rstd1 * cl2;
  const float cneg = ((rb & 7) == 0 && cw == 0) ? -INFINITY : 0.f;
  float v[4][4];
#pragma unroll
  for (int h = 0; h < 4; h++) {
    float T0[4] = {cneg, cneg, cneg, cneg}, T1[4] = {0.f, 0.f, 0.f, 0.f}, T2[4] = {0.f, 0.f, 0.f, 0.f};
    mma_bf16(T1, qa[h], fl[h][0], fl[h][1]);
    mma_bf16(T2, qa[h], fh[h][0], fh[h][1]);
    mma_bf16(T0, qa[h], fp[h][0], fp[h][1]);
    v[h][0] = u0 ? T0[0] : T1[0]; v[h][1] = u1 ? T0[1] : T1[1];
    v[h][2] = u0 ? T1[2] : T2[2]; v[h][3] = u1 ? T1[3] : T2[3];
  }
  float m0[4], m1[4];
#pragma unroll
  for (int h = 0; h < 4; h++) { m0[h] = fmaxf(v[h][0], v[h][1]); m1[h] = fmaxf(v[h][2], v[h][3]); }
#pragma unroll
  for (int o = 1; o <= 2; o <<= 1) {
#pragma unroll
    for (int h = 0; h < 4; h++) {
      m0[h] = fmaxf(m0[h], __shfl_xor_sync(~0u, m0[h], o));
      m1[h] = fmaxf(m1[h], __shfl_xor_sync(~0u, m1[h], o));
    }
  }
  float O0[4][4], O1[4][4], Z[4][4];
#pragma unroll
  for (int h = 0; h < 4; h++) {
    const float mm0 = -m0[h] * sc0, mm1 = -m1[h] * sc1;
    const uint32_t P0 = packbf(ex2(fmaf(v[h][0], sc0, mm0)), ex2(fmaf(v[h][1], sc0, mm0)));
    const uint32_t P1 = packbf(ex2(fmaf(v[h][2], sc1, mm1)), ex2(fmaf(v[h][3], sc1, mm1)));
#pragma unroll
    for (int k = 0; k < 4; k++) O0[h][k] = O1[h][k] = Z[h][k] = 0.f;
    mma_bf16_k8(Z[h], P0, P1, 0x3f803f80u);
    mma_bf16_k8(O0[h], P0 & ~mU, P1 & mU, fl[h][2]); mma_bf16_k8(O1[h], P0 & ~mU, P1 & mU, fl[h][3]);
    mma_bf16_k8(O0[h], P0 & mU, 0u, fp[h][2]); mma_bf16_k8(O1[h], P0 & mU, 0u, fp[h][3]);
    mma_bf16_k8(O0[h], 0u, P1 & ~mU, fh[h][2]); mma_bf16_k8(O1[h], 0u, P1 & ~mU, fh[h][3]);
  }
  const uint32_t ob = sb + SM_OST + wg * 8192;
  const int o_row = 16 * w + (lane & 7) + 8 * ((lane >> 3) & 1);
#pragma unroll
  for (int h = 0; h < 4; h++) {
    const float i0 = rcp_approx(Z[h][0]), i1 = rcp_approx(Z[h][2]);
    const int ch = 2 * h + (lane >> 4);
    stsm4(ob + o_row * 128 + ((ch ^ (o_row & 7)) << 4), packbf(O0[h][0] * i0, O0[h][1] * i0), packbf(O0[h][2] * i1, O0[h][3] * i1),
          packbf(O1[h][0] * i0, O1[h][1] * i0), packbf(O1[h][2] * i1, O1[h][3] * i1));
  }
  if (threadIdx.x == 0) TS(2 + layer * 20 + 5);
  ATS(57, 128); ATS(20, 96);
  fence_writer();
  bar_sync(2 + wg, 128);
  if (w == 0 && elect_one()) {
    fence_reader();
    tma_st(&p.mapO, hg * 64, rb * 128 + wg * 64, ob);
    bulk_commit();
    mbar_arrive(bar + 8 * B_AD);
    bulk_wait_all();
    red_relaxed(&g_cnt[(C_O + rb) * 32]);
    mbar_arrive(bar + 8 * B_OST);
    if (threadIdx.x == 0) TS(2 + layer * 20 + 6);
  }
}

__device__ __forceinline__ void proj_phase(const Params& p, uint32_t sb, int layer, int rb, int q, int wg, int w) {
  const int lane = opaque_tid() & 31;
  const bool TR = layer != 0;
  const int t = lane & 3;
  const uint32_t bar = sb + SM_BAR;
  const uint32_t rbx = sb + SM_R + wg * 8192;
  uint32_t res[16];
  mbar_wait(bar + 8 * B_RF, layer);
  if (threadIdx.x == 0) TS(2 + layer * 20 + 7);
  if (!TR) {
#pragma unroll
    for (int j = 0; j < 8; j += 2) {
      const int mi = lane >> 3;
      const int row = 16 * w + (lane & 7) + 8 * (mi & 1), ch = j + (mi >> 1);
      ldsm4(&res[2 * j], rbx + row * 128 + ((ch ^ (row & 7)) << 4));
    }
  } else {
#pragma unroll
    for (int j = 0; j < 8; j += 2) {
      const int mi = lane >> 3;
      const int line = 8 * (j + (mi >> 1)) + (lane & 7), pc = 2 * w + (mi & 1);
      ldsm4t(&res[2 * j], rbx + line * 128 + ((pc ^ (line & 7)) << 4));
    }
  }
  bar_sync(2 + wg, 128);
  float acc[32];
#pragma unroll
  for (int i = 0; i < 16; i++) {
    asm volatile("shl.b32 %0, %1, 16;" : "=f"(acc[2 * i]) : "r"(res[i]));
    asm volatile("and.b32 %0, %1, 0xffff0000;" : "=f"(acc[2 * i + 1]) : "r"(res[i]));
  }
  const uint32_t tag = part_tag(lds32(sb + SM_EP), 2 * layer + 1);
#pragma unroll 1
  for (int c = 0; c < 8; c++) {
    if ((c & 1) == 0) mbar_wait(bar + 8 * (B_WOF + (c >> 1)), layer);
    mbar_wait(bar + 8 * (B_OF + c), layer);
    if (c == 0 && threadIdx.x == 0) TS(2 + layer * 20 + 8);
    const uint64_t da = mkdesc(sb + sm_o(c) + wg * 8192, 16, 1024, 1);
    const uint64_t db = mkdesc(sb + SM_WO + c * 8192, 8192, 1024, 1);
    wg_fence();
#pragma unroll
    for (int ks = 0; ks < 4; ks++) wgmma_ss<64, 0, 1>(acc, da + ks * 2, db + ks * 128, 1);
    wg_commit();
  }
  wg_wait<0>();
#pragma unroll
  for (int i = 0; i < 32; i++) asm volatile("" : "+f"(acc[i]) :: "memory");
  if (threadIdx.x == 0) TS(2 + layer * 20 + 9);
  if (lane == 0 && w == 0) mbar_arrive(bar + 8 * B_PDONE);
  {
    float s[4], qq[4];
#pragma unroll
    for (int k = 0; k < 4; k++) { s[k] = acc[k]; qq[k] = acc[k] * acc[k]; }
#pragma unroll
    for (int j = 1; j < 8; j++)
#pragma unroll
      for (int k = 0; k < 4; k++) { s[k] += acc[4 * j + k]; qq[k] = fmaf(acc[4 * j + k], acc[4 * j + k], qq[k]); }
    const float s0 = s[0] + s[1], s1 = s[2] + s[3], q0 = qq[0] + qq[1], q1 = qq[2] + qq[3];
    float sr = ((t & 1) ? s1 : s0) + __shfl_xor_sync(~0u, (t & 1) ? s0 : s1, 1);
    float qr = ((t & 1) ? q1 : q0) + __shfl_xor_sync(~0u, (t & 1) ? q0 : q1, 1);
    sr += __shfl_xor_sync(~0u, sr, 2);
    qr += __shfl_xor_sync(~0u, qr, 2);
    if (t < 2) st_part(&g_part[(rb * 8 + q) * 128 + 64 * wg + 16 * w + (lane >> 2) + 8 * t], sr, qr, tag);
    __syncwarp();
    if (elect_one()) mbar_arrive(bar + 8 * B_PS);
  }
#pragma unroll
  for (int j = 0; j < 8; j += 2) {
    const int mi = lane >> 3;
    const int line = 8 * (j + (mi >> 1)) + (lane & 7), pc = 2 * w + (mi & 1);
    stsm4t(rbx + line * 128 + ((pc ^ (line & 7)) << 4), packbf(acc[4 * j], acc[4 * j + 1]), packbf(acc[4 * j + 2], acc[4 * j + 3]),
           packbf(acc[4 * j + 4], acc[4 * j + 5]), packbf(acc[4 * j + 6], acc[4 * j + 7]));
  }
  fence_writer();
  bar_sync(2 + wg, 128);
  if (w == 0 && elect_one()) {
    fence_reader();
    mbar_wait(bar + 8 * B_ZF, layer);
    fence_async_global();
    tma_st(&p.mapXT, rb * 128 + wg * 64, (2 * layer) * DM + q * 64, rbx);
    bulk_commit();
    if (threadIdx.x == 0) TS(2 + layer * 20 + 10);
    asm volatile("cp.async.bulk.wait_group.read 0;" ::: "memory");
    if (wg == 0) mbar_arrive(bar + 8 * B_RE);
  }
}
__device__ __forceinline__ void proj_stats(int layer, int rb, int q, int lane, uint32_t tag) {
  const int r = 16 * q + (lane & 15);
  const uint2* src = &g_part[(rb * 8 + (lane >> 4) * 4) * 128 + r];
  uint2 v[4];
  bool ok;
  int it = 0;
  do {
    ok = true;
#pragma unroll
    for (int i = 0; i < 4; i++) v[i] = ld_part(src + i * 128);
#pragma unroll
    for (int i = 0; i < 4; i++) ok = ok && (v[i].y & 7u) == tag;
    if (++it > (1 << 22)) __trap();
  } while (!__all_sync(~0u, ok));
  float s = (__uint_as_float(v[0].x) + __uint_as_float(v[1].x)) + (__uint_as_float(v[2].x) + __uint_as_float(v[3].x));
  float qq = (__uint_as_float(v[0].y) + __uint_as_float(v[1].y)) + (__uint_as_float(v[2].y) + __uint_as_float(v[3].y));
  s += __shfl_xor_sync(~0u, s, 16);
  qq += __shfl_xor_sync(~0u, qq, 16);
  const float mean = s * (1.f / DM);
  const float rstd = rsqrt_approx(fmaxf(fmaf(qq, 1.f / DM, -mean * mean), 0.f) + 1e-5f), nm = -mean * rstd;
  const float nm1 = __shfl_xor_sync(~0u, nm, 1), rstd1 = __shfl_xor_sync(~0u, rstd, 1);
  if ((lane & 17) == 0)
    st_tagged3((uint4*)g_stats + (layer * 32 + rb * 2 + (r >> 6)) * 32 + ((r & 7) >> 1) * 8 + ((r >> 3) & 7),
               __float_as_uint(nm), __float_as_uint(rstd) | 1u, __float_as_uint(nm1), __float_as_uint(rstd1));
}

#define NA 8
template <bool GB> __host__ __device__ constexpr int grp_n() { return GB ? 17 - NA : NA; }
template <bool GB> __host__ __device__ constexpr int grp_m(int i) { return i == 0 ? (GB ? 1 : 0) : (GB ? NA + i : 1 + i); }
template <bool GB> __device__ __forceinline__ void conv_load(uint32_t* A, uint32_t pe) {
#pragma unroll
  for (int i = 0; i < grp_n<GB>(); i++) {
    asm volatile("ld.shared.v2.b32 {%0,%1}, [%2];" : "=r"(A[4 * i]), "=r"(A[4 * i + 1]) : "r"(pe + 4 * (64 * grp_m<GB>(i))) : "memory");
    A[4 * i + 2] = lds32(pe + 4 * (64 * grp_m<GB>(i) - 1));
  }
}
template <bool GB> __device__ __forceinline__ void conv_dup_early(uint32_t* A, uint32_t zero) {
#pragma unroll
  for (int i = 0; i < grp_n<GB>(); i++) asm volatile("or.b32 %0, %1, %2;" : "=r"(A[4 * i + 3]) : "r"(A[4 * i + 0]), "r"(zero));
}
template <bool GB> __device__ __forceinline__ void conv_dup(uint32_t* A) {
#pragma unroll
  for (int i = 0; i < grp_n<GB>(); i++) asm volatile("mov.b32 %0, %1;" : "=r"(A[4 * i + 3]) : "r"(A[4 * i + 0]));
}
template <bool GB, int I0, int I1> __device__ __forceinline__ void conv_mmas(float* acc, const uint32_t* A, uint64_t d) {
  if constexpr (I0 < I1) {
    constexpr int M = grp_m<GB>(I0);
    wgmma_rs<128 - 8 * (M / 2), 0>(acc, A + 4 * I0, d + (uint64_t)(4 * M), M != 0);
    conv_mmas<GB, I0 + 1, I1>(acc, A, d);
  }
}
struct SumAddr { uint32_t l0, l1, l2, se, so; };
__device__ __forceinline__ SumAddr conv_sum_addr(uint32_t sb, int c) {
  auto ua = [&](int j) { return sb + cv_u(0) + (127 - (j >> 3)) * 16 + (j & 7) * 2; };
  auto sa = [&](int hc) { const int ci = hc & ~1; return sb + cv_s(0) + ((ci >> 3) & 1) * 1024 + (ci >> 4) * 128 + (((ci ^ (ci >> 4)) & 7) << 4) + (hc & 1) * 8; };
  const int j0 = 4 * (c - 1);
  return {ua(j0 - 2), ua(j0), ua(j0 + 4), sa((c + 1) & 127), sa(c) + 2048};
}
__device__ __forceinline__ void sts64(uint32_t a, uint32_t x, uint32_t y) { asm volatile("st.shared.v2.b32 [%0], {%1,%2};" ::"r"(a), "r"(x), "r"(y) : "memory"); }
__device__ __forceinline__ void conv_sums(const SumAddr& sa, int lc, int c) {
  uint32_t e[4], o[4];
  {
    const float2 em = lds64f(sa.l1 + lc * 32768), om = lds64f(sa.l1 + lc * 32768 + CV_UH);
    e[0] = lds32(sa.l0 + lc * 32768); o[0] = lds32(sa.l0 + lc * 32768 + CV_UH);
    e[3] = lds32(sa.l2 + lc * 32768); o[3] = lds32(sa.l2 + lc * 32768 + CV_UH);
    e[1] = __float_as_uint(em.x); e[2] = __float_as_uint(em.y); o[1] = __float_as_uint(om.x); o[2] = __float_as_uint(om.y);
  }
  uint32_t s7e[2], s7o[2], s9e[2], s9o[2];
  uint32_t pw[4], sh[3];
#pragma unroll
  for (int k = 0; k < 4; k++) pw[k] = hadd2(e[k], o[k]);
#pragma unroll
  for (int k = 0; k < 3; k++) sh[k] = __byte_perm(pw[k], pw[k + 1], 0x5432);
#pragma unroll
  for (int k = 0; k < 2; k++) {
    const uint32_t t3 = hadd2(hadd2(sh[k], sh[k + 1]), pw[k + 1]);
    s7e[k] = hadd2(t3, o[k]); s7o[k] = hadd2(t3, e[k + 2]);
    s9e[k] = hadd2(s7o[k], pw[k]); s9o[k] = hadd2(s7e[k], pw[k + 2]);
  }
  if (c == 127) s9e[0] = s9e[1] = s9o[0] = s9o[1] = 0u;
  sts64(sa.se + lc * 32768, s9e[0], s9e[1]); sts64((sa.se ^ 16) + lc * 32768, s9o[0], s9o[1]);
  sts64(sa.so + lc * 32768, s7e[0], s7e[1]); sts64((sa.so ^ 16) + lc * 32768, s7o[0], s7o[1]);
}

__device__ __forceinline__ void conv_epi(uint32_t sb, int layer, int cta, int ch, int c0, uint4 x0, uint4 x1) {
  uint4 v[2][4];
  const uint4 xr[2] = {x0, x1};
  mbar_wait(sb + SM_BAR + 8 * (B_P + ch), layer);
#pragma unroll
  for (int u = 0; u < 2; u++) {
    const uint32_t pb = sb + cv_pb(ch) + u * (CV_PBW / 2) + c0 * 16;
#pragma unroll
    for (int k = 0; k < 4; k++) v[u][k] = lds128(pb + k * CV_PBW);
  }
#pragma unroll
  for (int u = 0; u < 2; u++) {
    uint4 o;
    o.x = hadd2(xr[u].x, hadd2(hadd2(v[u][0].x, v[u][1].x), hadd2(v[u][2].x, v[u][3].x)));
    o.y = hadd2(xr[u].y, hadd2(hadd2(v[u][0].y, v[u][1].y), hadd2(v[u][2].y, v[u][3].y)));
    o.z = hadd2(xr[u].z, hadd2(hadd2(v[u][0].z, v[u][1].z), hadd2(v[u][2].z, v[u][3].z)));
    o.w = hadd2(xr[u].w, hadd2(hadd2(v[u][0].w, v[u][1].w), hadd2(v[u][2].w, v[u][3].w)));
    if (layer == 0) sts128(sb + cv_s(ch) + (c0 + 128 * u) * 16, o);
    else st_tagged3((uint4*)(g_xT + (size_t)(3 * DM + cv_chan(cta, ch)) * LSEQ) + c0 + 128 * u, o.x, o.y, o.z, o.w);
  }
}
__device__ __forceinline__ void warp_release(uint32_t b) {
  fence_writer();
  __syncwarp();
  if (elect_one()) mbar_arrive(b);
}

__device__ __forceinline__ void conv_prep_load(uint32_t sb, int layer, int cta, int c, uint4 (&xr)[4], uint4 (&st)[4]) {
  mbar_wait(sb + SM_BAR + 8 * B_GB, layer);
  if (threadIdx.x == 0) TS(2 + layer * 20 + 11);
  xr[0] = ld_tagged((const uint4*)(g_xT + (size_t)(2 * layer * DM + cta) * LSEQ) + c);
#pragma unroll
  for (int i = 0; i < 4; i++) st[i] = ld_tagged((const uint4*)g_stats + (layer * 32 + (c >> 3)) * 32 + i * 8 + (c & 7));
}
template <bool HELPER>
__device__ __forceinline__ void conv_prep(uint32_t sb, int layer, int cta, int c, uint4 (&xr)[4], uint4 (&st)[4], const SumAddr& sa) {
  const uint32_t bar = sb + SM_BAR;
  const uint4* xin = (const uint4*)(g_xT + (size_t)(2 * layer * DM + cta) * LSEQ) + c;
  for (int it = 0;; it++) {
    const bool okx = __all_sync(~0u, xr[0].x != ~0u);
    const bool oks = __all_sync(~0u, (st[0].y & st[1].y & st[2].y & st[3].y & 1u) != 0);
    if (okx && oks) break;
    if (it > (1 << 22)) __trap();
    if (!okx) xr[0] = ld_tagged(xin);
    if (!oks) {
#pragma unroll
      for (int i = 0; i < 4; i++) st[i] = ld_tagged((const uint4*)g_stats + (layer * 32 + (c >> 3)) * 32 + i * 8 + (c & 7));
    }
  }
  if (threadIdx.x == 0) TS(2 + layer * 20 + 12);
  const int a = c & 127, h = c >> 7;
#pragma unroll
  for (int i = 0; i < 4; i++) {
    if (i == 1) {
#pragma unroll
      for (int j = 1; j < 4; j++) xr[j] = ld_tagged(xin + j * (128 * LSEQ / 8));
      if (HELPER) {
        mbar_wait(bar + 8 * B_U, layer);
        conv_sums(sa, 0, c);
        fence_async_smem();
        warp_release(bar + 8 * B_S);
        if (layer == 1 && c == 0) TS(46);
        mbar_wait(bar + 8 * B_GB, layer);
      }
      for (int it = 0; !__all_sync(~0u, xr[1].x != ~0u && xr[2].x != ~0u && xr[3].x != ~0u); it++) {
        if (it > (1 << 22)) __trap();
#pragma unroll
        for (int j = 1; j < 4; j++) xr[j] = ld_tagged(xin + j * (128 * LSEQ / 8));
      }
    }
    const uint32_t x[4] = {xr[i].x, xr[i].y, xr[i].z, xr[i].w};
    uint32_t u[4];
#pragma unroll
    for (int k = 0; k < 4; k++)
      u[k] = packbf(fmaf(bf_lo(x[k]), __uint_as_float(st[k].y), __uint_as_float(st[k].x)), fmaf(bf_hi(x[k]), __uint_as_float(st[k].w), __uint_as_float(st[k].z)));
    sts128(sb + cv_u(i) + h * CV_UH + (127 - a) * 16, make_uint4(u[0], u[1], u[2], u[3]));
    warp_release(bar + 8 * (B_U + i));
  }
}
__device__ __forceinline__ void conv_zero(uint32_t sb, int ht) {
  if (ht < 96) {
    const int ch = ht / 24, h2 = (ht / 12) & 1, qq = ht % 12;
    sts128(sb + cv_u(ch) + h2 * CV_UH + (128 + qq) * 16, make_uint4(0, 0, 0, 0));
  }
  if (ht >= 80) {
    const int i = ht - 80, ch = i / 12, q2 = i % 12;
    const int w2 = q2 < 2 ? 1 : q2 < 6 ? 2 : 3, cc = q2 < 2 ? q2 : q2 < 6 ? q2 - 2 : q2 - 6;
    sts128(sb + cv_pb(ch) + w2 * CV_PBW + (cc & 1) * (CV_PBW / 2) + (cc >> 1) * 16, make_uint4(0, 0, 0, 0));
  }
}

#define LD_AT 0
#define HANDOVER 12
template <int R>
__device__ __forceinline__ void conv_round(uint32_t sb, int layer, int wg, uint32_t* FA, uint32_t* FB, uint32_t pb, uint32_t pe2) {
  const uint32_t bar = sb + SM_BAR;
  const int ch = 2 * R + 1 - wg;
  float acc[64];
  const uint64_t d = mkdesc(sb + cv_u(ch), CV_UH, 128, 0);
  const bool leader = (opaque_tid() & 127) == 0;
  FTS(39);
  if (R == 0) {
    mbar_wait(bar + 8 * (B_U + ch), layer);
    fence_reader();
  }
  if (ch > 0) mbar_wait(bar + 8 * (B_T + ch - 1), layer);
  FTS(41);
  if (ch == 0 && threadIdx.x == 128) TS(2 + layer * 20 + 13);
  if (R == 1 && LD_AT == 0) conv_load<true>(FB, pe2);
  wg_fence();
  conv_mmas<false, 0, (HANDOVER < NA ? HANDOVER : NA)>(acc, FA, d);
  if (HANDOVER <= NA) mbar_arrive_if(bar + 8 * (B_T + ch), leader);
  conv_mmas<false, (HANDOVER < NA ? HANDOVER : NA), NA>(acc, FA, d);
  wg_commit();
  if (R == 1 && LD_AT == 1) conv_load<true>(FB, pe2);
  FTS(51);
  mbar_wait(bar + 8 * (B_S + ch), layer);
  if (R == 1) conv_dup<true>(FB);
  wg_fence();
  conv_mmas<true, 0, (HANDOVER > NA ? HANDOVER - NA : 0)>(acc, FB, d);
  if (HANDOVER > NA) mbar_arrive_if(bar + 8 * (B_T + ch), leader);
  conv_mmas<true, (HANDOVER > NA ? HANDOVER - NA : 0), 17 - NA>(acc, FB, d);
  wgmma_ss<64, 1, 1>(acc, mkdesc(sb + cv_s(ch), 1024, 1024, 1), mkdesc(sb + cv_ft(ch), 256, 16, 0), 1);
  wgmma_ss<64, 1, 1>(acc, mkdesc(sb + cv_s(ch) + 2048, 1024, 1024, 1), mkdesc(sb + cv_ft(ch) + 512, 256, 16, 0), 1);
  wg_commit();
  FTS(61);
  wg_wait<0>();
#pragma unroll
  for (int j = 0; j < 16; j += 2)
    stsm4t(pb + R * 65536 - j * 128, packbf(acc[4 * j], acc[4 * j + 1]), packbf(acc[4 * j + 2], acc[4 * j + 3]),
           packbf(acc[4 * j + 4], acc[4 * j + 5]), packbf(acc[4 * j + 6], acc[4 * j + 7]));
  __syncwarp();
  if (elect_one()) mbar_arrive(bar + 8 * (B_P + ch));
  if (threadIdx.x == 0) TS(2 + layer * 20 + 14 + R);
  FTS(57);
  if (R == 0) {
    mbar_wait(bar + 8 * (B_S + ch + 2), layer);
    fence_reader();
  }
}
__device__ __forceinline__ void conv_phase(const Params& p, uint32_t sb, int layer, int cta) {
  const int tid = opaque_tid();
  const int wg = __shfl_sync(~0u, tid >> 7, 0), w = __shfl_sync(~0u, (tid >> 5) & 3, 0);
  const uint32_t bar = sb + SM_BAR;
  uint32_t FA0[4 * NA], FA1[4 * NA], FB[4 * (17 - NA)];
  const uint32_t pe = sb + cv_pe(1 - wg) + 4 * (16 + 16 * w + 2 * ((tid & 31) >> 2) - 4 * (tid & 3));
  mbar_wait(bar + 8 * B_PE, layer);
  conv_load<false>(FA0, pe); conv_load<true>(FB, pe);
  const uint32_t zero = tid >> 10;
  conv_dup_early<false>(FA0, zero); conv_dup_early<true>(FB, zero);
  if (wg == 0) {
    uint4 xr[4], st[4];
    conv_prep_load(sb, layer, cta, tid + 128, xr, st);
    conv_load<false>(FA1, pe + 65536);
    conv_dup_early<false>(FA1, zero);
    conv_prep<false>(sb, layer, cta, opaque_tid() + 128, xr, st, SumAddr());
  } else {
    conv_load<false>(FA1, pe + 65536);
    conv_dup_early<false>(FA1, zero);
  }
  uint32_t pb;
  {
    const int l2 = opaque_tid() & 31, mt = l2 >> 3;
    pb = sb + cv_pb(1 - wg) + w * CV_PBW + (mt & 1) * (CV_PBW / 2) + (127 - 8 * (mt >> 1) - (l2 & 7) + w) * 16;
  }
  conv_round<0>(sb, layer, wg, FA0, FB, pb, 0);
  conv_round<1>(sb, layer, wg, FA1, FB, pb, pe + 65536);
  if (wg == 1 && layer == 0) mbar_wait(bar + 8 * (B_T + 3), layer);
}

__device__ __forceinline__ void final_phase(const Params& p, uint32_t sb, int cta, int wg, int w) {
  if (wg == 1 && w == 3) return;
  const int lane = opaque_tid() & 31, g = lane >> 2, t = lane & 3;
  const int lc = wg ? w : 3;
  const int pos0 = (cta & 31) * 64, ch0 = 128 * lc + (cta >> 5) * 32;
  const bf16* src = g_xT + (size_t)(3 * DM + ch0 + 8 * (g >> 1) + (g & 1)) * LSEQ + pos0;
  bf16* dst = p.out + (size_t)(2 * (pos0 & 1023) + (pos0 >> 10)) * DM + ch0 + 8 * t;
  constexpr int RS = 2 * DM;
  int it = 0;
  mbar_wait(sb + SM_BAR + 8 * (B_E + lc), 1);
  delay<D_FIN>();
  if (wg == 0) {
    uint2 v[4];
    do {
#pragma unroll
      for (int q = 0; q < 4; q++)
        asm volatile("ld.relaxed.gpu.global.v2.u32 {%0,%1}, [%2];" : "=r"(v[q].x), "=r"(v[q].y) : "l"(src + 2 * q * LSEQ + 16 * w + 4 * t) : "memory");
      if (++it > (1 << 22)) __trap();
    } while (!__all_sync(~0u, v[0].x != ~0u && v[1].x != ~0u && v[2].x != ~0u && v[3].x != ~0u));
    if (threadIdx.x == 0) TS(42);
    dst += (16 * w + 4 * (g >> 1) + (g & 1)) * RS;
    *(uint4*)dst = make_uint4(movm_t(v[0].x), movm_t(v[1].x), movm_t(v[2].x), movm_t(v[3].x));
    *(uint4*)(dst + 2 * RS) = make_uint4(movm_t(v[0].y), movm_t(v[1].y), movm_t(v[2].y), movm_t(v[3].y));
  } else {
    uint4 v[2][4];
    bool ok;
    do {
      ok = true;
#pragma unroll
      for (int h = 0; h < 2; h++)
#pragma unroll
        for (int q = 0; q < 4; q++) v[h][q] = ld_tagged((const uint4*)(src + 2 * q * LSEQ + 32 * h + 8 * t));
#pragma unroll
      for (int h = 0; h < 2; h++)
#pragma unroll
        for (int q = 0; q < 4; q++) ok = ok && v[h][q].x != ~0u;
      if (++it > (1 << 22)) __trap();
    } while (!__all_sync(~0u, ok));
    dst += (8 * (g >> 1) + (g & 1)) * RS;
#pragma unroll
    for (int h = 0; h < 2; h++) {
      *(uint4*)(dst + (32 * h + 0) * RS) = make_uint4(movm_t(v[h][0].x), movm_t(v[h][1].x), movm_t(v[h][2].x), movm_t(v[h][3].x));
      *(uint4*)(dst + (32 * h + 2) * RS) = make_uint4(movm_t(v[h][0].y), movm_t(v[h][1].y), movm_t(v[h][2].y), movm_t(v[h][3].y));
      *(uint4*)(dst + (32 * h + 4) * RS) = make_uint4(movm_t(v[h][0].z), movm_t(v[h][1].z), movm_t(v[h][2].z), movm_t(v[h][3].z));
      *(uint4*)(dst + (32 * h + 6) * RS) = make_uint4(movm_t(v[h][0].w), movm_t(v[h][1].w), movm_t(v[h][2].w), movm_t(v[h][3].w));
    }
  }
  if (threadIdx.x == 0) TS(43);
  if (threadIdx.x == 192) TS(63);
  if (threadIdx.x == 0) LTS(1);
}

struct cplx { float r, i; };
__device__ __forceinline__ cplx cmul(cplx a, cplx b) { return {fmaf(a.r, b.r, -a.i * b.i), fmaf(a.r, b.i, a.i * b.r)}; }
__device__ __forceinline__ cplx csqr(cplx a) { return {fmaf(a.r, a.r, -a.i * a.i), (a.r + a.r) * a.i}; }
__device__ __forceinline__ cplx cexp_l(float ar2, float ai, float l) {
  const float m = ex2(ar2 * l);
  const float x = ai * l;
  return {m * __cosf(x), m * __sinf(x)};
}

__device__ __forceinline__ void colsum_publish(uint32_t sb, int rb, int hg, int ht, uint32_t tag) {
  const int lane = ht & 31, q = lane & 15, h = lane >> 4;
  const uint32_t src = sb + SM_CW + (ht >> 5) * 4096 + h * 128 + (q & 1) * 8;
  float s[4] = {0.f, 0.f, 0.f, 0.f};
#pragma unroll
  for (int r = 0; r < 16; r++) {
    const float2 v = lds64f(src + r * 256 + (((q >> 1) ^ ((2 * r + h) & 7)) << 4));
    s[0] += bf_lo(__float_as_uint(v.x)); s[1] += bf_hi(__float_as_uint(v.x));
    s[2] += bf_lo(__float_as_uint(v.y)); s[3] += bf_hi(__float_as_uint(v.y));
  }
#pragma unroll
  for (int k = 0; k < 4; k++) s[k] += __shfl_xor_sync(~0u, s[k], 16);
  if (h == 0)
    st_tagged3(&g_colsum[(hg * 16 + rb) * 48 + (ht >> 5) * 16 + q], (__float_as_uint(s[0]) & ~7u) | tag, __float_as_uint(s[1]),
               __float_as_uint(s[2]), __float_as_uint(s[3]));
}
__device__ __forceinline__ void colsum_gather(uint32_t sb, int hg, int ht, uint32_t tag) {
  const int lane = ht & 31, rec = (ht >> 5) * 16 + (lane & 15);
  const uint4* src = &g_colsum[(hg * 16 + (lane >> 4) * 8) * 48 + rec];
  uint4 v[8];
  bool ok;
  int it = 0;
  do {
    ok = true;
#pragma unroll
    for (int i = 0; i < 8; i++) v[i] = ld_tagged(src + i * 48);
#pragma unroll
    for (int i = 0; i < 8; i++) ok = ok && (v[i].x & 7u) == tag;
    if (++it > (1 << 22)) __trap();
  } while (!__all_sync(~0u, ok));
  float s[4] = {0.f, 0.f, 0.f, 0.f};
#pragma unroll
  for (int i = 0; i < 8; i++) {
    s[0] += __uint_as_float(v[i].x & ~7u); s[1] += __uint_as_float(v[i].y); s[2] += __uint_as_float(v[i].z); s[3] += __uint_as_float(v[i].w);
  }
#pragma unroll
  for (int k = 0; k < 4; k++) s[k] += __shfl_xor_sync(~0u, s[k], 16);
  if (lane < 16) sts128f(sb + SM_CS + rec * 16, s[0], s[1], s[2], s[3]);
}

__device__ __forceinline__ uint32_t packh(float lo, float hi) { uint32_t r; asm("cvt.rn.f16x2.f32 %0, %1, %2;" : "=r"(r) : "f"(hi), "f"(lo)); return r; }
__device__ __forceinline__ void mma_f16(float* d, uint32_t a0, uint32_t a1, uint32_t a2, uint32_t a3, uint32_t b0, uint32_t b1) {
  asm volatile("mma.sync.aligned.m16n8k16.row.col.f32.f16.f16.f32 {%0,%1,%2,%3}, {%4,%5,%6,%7}, {%8,%9}, {%0,%1,%2,%3};"
      : "+f"(d[0]), "+f"(d[1]), "+f"(d[2]), "+f"(d[3]) : "r"(a0), "r"(a1), "r"(a2), "r"(a3), "r"(b0), "r"(b1));
}
struct HSeed { uint32_t r, i; };
__device__ __forceinline__ HSeed hseed(cplx s) { return {packh(s.r, s.r), packh(s.i, s.i)}; }
__device__ __forceinline__ void hcmul(uint32_t& o_r, uint32_t& o_i, uint32_t br, uint32_t bi, HSeed s) {
  asm("{\n.reg .b32 t, u;\nmul.rn.f16x2 t, %3, %5;\nneg.f16x2 t, t;\nmul.rn.f16x2 u, %3, %4;\nfma.rn.f16x2 %0, %2, %4, t;\nfma.rn.f16x2 %1, %2, %5, u;\n}"
      : "=&r"(o_r), "=&r"(o_i) : "r"(br), "r"(bi), "r"(s.r), "r"(s.i));
}
struct HTile { uint32_t r[4], i[4]; };
__device__ __forceinline__ void tile_set(HTile& t, int k, cplx a, cplx b) { t.r[k] = packh(a.r, b.r); t.i[k] = packh(a.i, b.i); }
__device__ __forceinline__ void tile_upper(HTile& t, HSeed s) { hcmul(t.r[2], t.i[2], t.r[0], t.i[0], s); hcmul(t.r[3], t.i[3], t.r[1], t.i[1], s); }
__device__ __forceinline__ HTile tile_shift(const HTile& t, HSeed s) {
  HTile o;
#pragma unroll
  for (int k = 0; k < 4; k++) hcmul(o.r[k], o.i[k], t.r[k], t.i[k], s);
  return o;
}
__device__ __forceinline__ void tile_put(const HTile& t, uint32_t a) {
  sts128(a, make_uint4(t.r[0], t.r[1], t.r[2], t.r[3]));
  sts128(a + 512, make_uint4(t.i[0], t.i[1], t.i[2], t.i[3]));
}
__device__ __forceinline__ HTile tile_get(uint32_t a) { HTile o; ldsm4t(o.r, a); ldsm4t(o.i, a + 512); return o; }
__device__ __forceinline__ void tile_mma(float* T, const HTile& a0, const HTile& a1, const HTile& b) {
  mma_f16(T, a0.r[0], a0.r[1], a0.r[2], a0.r[3], b.r[0], b.r[1]);
  mma_f16(T, a0.i[0], a0.i[1], a0.i[2], a0.i[3], b.i[0], b.i[1]);
  mma_f16(T, a1.r[0], a1.r[1], a1.r[2], a1.r[3], b.r[2], b.r[3]);
  mma_f16(T, a1.i[0], a1.i[1], a1.i[2], a1.i[3], b.i[2], b.i[3]);
}
__device__ __forceinline__ void tile_mma2(float* T, float* U, const HTile& a0, const HTile& a1, const HTile& b, const HTile& c) {
  mma_f16(T, a0.r[0], a0.r[1], a0.r[2], a0.r[3], b.r[0], b.r[1]);
  mma_f16(U, a0.r[0], a0.r[1], a0.r[2], a0.r[3], c.r[0], c.r[1]);
  mma_f16(T, a0.i[0], a0.i[1], a0.i[2], a0.i[3], b.i[0], b.i[1]);
  mma_f16(U, a0.i[0], a0.i[1], a0.i[2], a0.i[3], c.i[0], c.i[1]);
  mma_f16(T, a1.r[0], a1.r[1], a1.r[2], a1.r[3], b.r[2], b.r[3]);
  mma_f16(U, a1.r[0], a1.r[1], a1.r[2], a1.r[3], c.r[2], c.r[3]);
  mma_f16(T, a1.i[0], a1.i[1], a1.i[2], a1.i[3], b.i[2], b.i[3]);
  mma_f16(U, a1.i[0], a1.i[1], a1.i[2], a1.i[3], c.i[2], c.i[3]);
}
__device__ __forceinline__ void kgen_unit(uint32_t tab, uint32_t taba, float ar2, float ai, cplx c, float (&T)[5][4]) {
  const cplx z1 = cexp_l(ar2, ai, 1.f), z16 = cexp_l(ar2, ai, 16.f), z256 = cexp_l(ar2, ai, 256.f);
  HTile a0, a1, b0, b1;
  {
    const cplx y1 = {z16.r, -z16.i}, y2 = csqr(y1), y3 = cmul(y2, y1), y4 = csqr(y2), y5 = cmul(y4, y1), y6 = csqr(y3), y7 = cmul(y4, y3);
    HTile t;
    tile_set(t, 0, {1.f, 0.f}, y1); tile_set(t, 1, y2, y3); tile_set(t, 2, y4, y5); tile_set(t, 3, y6, y7);
    const HTile u = tile_shift(t, hseed(csqr(y4)));
    __syncwarp();
    tile_put(t, tab); tile_put(u, tab + 1024);
    __syncwarp();
    a0 = tile_get(taba); a1 = tile_get(taba + 256);
  }
  const cplx z2 = csqr(z1), z4 = csqr(z2), z8 = csqr(z4);
  const HSeed h8 = hseed(z8);
  const cplx d = cmul(c, z256), e = cmul(d, z256);
  {
    const cplx z512 = csqr(z256), f = cmul(e, z512), f8 = cmul(f, z8), f16 = cmul(f, z16), e4 = cmul(e, z4);
    HTile t, u;
    tile_set(t, 0, e4, cmul(e, z8)); tile_set(t, 1, cmul(e4, z8), cmul(e, z16));
    tile_upper(t, hseed(z256));
    tile_set(u, 0, f8, f16); tile_set(u, 1, cmul(f8, z256), cmul(f16, z256));
    tile_upper(u, hseed(z512));
    __syncwarp();
    tile_put(t, tab); tile_put(u, tab + 1024);
    __syncwarp();
    b0 = tile_get(tab); b1 = tile_get(tab + 1024);
  }
  {
    const cplx d2 = cmul(d, z2), d4 = cmul(d, z4);
    HTile t;
    tile_set(t, 0, d2, d4); tile_set(t, 1, cmul(d2, z4), cmul(d, z8));
    tile_upper(t, h8);
    __syncwarp();
    tile_put(t, tab);
    __syncwarp();
    tile_mma2(T[3], T[4], a0, a1, b0, b1);
    b0 = tile_get(tab);
  }
  {
    const cplx c1 = cmul(c, z1), c2 = cmul(c, z2), c3 = cmul(c1, z2), c4 = cmul(c, z4);
    HTile t;
    tile_set(t, 0, c1, c2); tile_set(t, 1, c3, c4); tile_set(t, 2, cmul(c1, z4), cmul(c2, z4)); tile_set(t, 3, cmul(c3, z4), cmul(c4, z4));
    const HTile u = tile_shift(t, h8);
    __syncwarp();
    tile_put(t, tab); tile_put(u, tab + 1024);
    __syncwarp();
    tile_mma(T[2], a0, a1, b0);
    b0 = tile_get(tab); b1 = tile_get(tab + 1024);
    tile_mma2(T[0], T[1], a0, a1, b0, b1);
  }
}
struct ModeIn { uint2 ar, ai, br, bi, cr, ci; };
__device__ __forceinline__ ModeIn load_modes(const Params& p, int idx) {
  return {*(const uint2*)(p.a_re + idx), *(const uint2*)(p.a_im + idx), *(const uint2*)(p.b_re + idx),
          *(const uint2*)(p.b_im + idx), *(const uint2*)(p.c_re + idx), *(const uint2*)(p.c_im + idx)};
}
__device__ __forceinline__ float bf_el(uint2 v, int k) { const uint32_t x = (k & 2) ? v.y : v.x; return (k & 1) ? bf_hi(x) : bf_lo(x); }
struct KGen { float4 cur; float T[5][4]; };
__device__ __forceinline__ uint32_t kgen_slot(uint32_t sb, int ht, int u) {
  return sb + (u < 3 ? SM_KC + (ht >> 5) * (KC_STRIDE * 2) + (u - 1) * 512 + (ht & 31) * 16 + 16 : SM_HALO + 1024 + ht * 16);
}
__device__ __forceinline__ void kgen_setup(KGen& s, uint32_t sb, int cta, int ht, const ModeIn& in, bf16 logdt, bf16 dskip) {
  const float dt = __bfloat162float(__float2bfloat16_rn(expf(__bfloat162float(logdt))));
  float mx = 0.f, k0 = 0.f, ar2[4];
  cplx c[4];
#pragma unroll
  for (int k = 0; k < 4; k++) {
    ar2[k] = (dt * bf_el(in.ar, k)) * 1.4426950408889634f;
    c[k] = cmul({bf_el(in.cr, k), bf_el(in.ci, k)}, {dt * bf_el(in.br, k), dt * bf_el(in.bi, k)});
    k0 += c[k].r;
    mx = fmaxf(mx, fmaxf(fabsf(c[k].r), fabsf(c[k].i)) * ex2(fmaxf(ar2[k] * 2048.f, 0.f)));
  }
  const int ex = min(max(267 - (int)(__reduce_max_sync(~0u, __float_as_uint(mx)) >> 23), 1), 253);
  const float sc = __uint_as_float(ex << 23);
#pragma unroll
  for (int o = 16; o > 0; o >>= 1) k0 += __shfl_xor_sync(~0u, k0, o);
  if ((ht & 31) == 0) {
    const uint32_t kc = sb + SM_KC + (ht >> 5) * (KC_STRIDE * 2);
    sts16(kc, __bfloat16_as_ushort(__float2bfloat16_rn(k0 + __bfloat162float(dskip))));
    sts16(kc + 641 * 2, 0);
    sts32f(kc + 644 * 2, __uint_as_float((254 - ex) << 23));
  }
  s.cur = make_float4(ar2[0], dt * bf_el(in.ai, 0), c[0].r * sc, c[0].i * sc);
#pragma unroll
  for (int k = 1; k < 4; k++) sts128f(kgen_slot(sb, ht, k), ar2[k], dt * bf_el(in.ai, k), c[k].r * sc, c[k].i * sc);
#pragma unroll
  for (int i = 0; i < 5; i++) s.T[i][0] = s.T[i][1] = s.T[i][2] = s.T[i][3] = 0.f;
}
__device__ __forceinline__ void kgen_finish(KGen& s, uint32_t sb, int cta, int ht) {
  const int w = ht >> 5, lane = ht & 31, g = lane >> 2, t = lane & 3;
  const uint32_t kc = sb + SM_KC + w * KC_STRIDE * 2;
  __syncwarp();
  const float inv = __uint_as_float(lds32(kc + 644 * 2));
  auto put = [&](int idx, float v) {
    sts16(kc + idx * 2, __bfloat16_as_ushort(__float2bfloat16_rn(v)));
  };
#pragma unroll
  for (int hi = 0; hi < 2; hi++)
#pragma unroll
    for (int lo = 0; lo < 2; lo++) {
      const int i = g + 8 * hi, j = 2 * t + lo, e = 2 * hi + lo;
      put(16 * i + 1 + j, s.T[0][e] * inv);
      put(16 * i + 9 + j, s.T[1][e] * inv);
      put(257 + 8 * i + j, s.T[2][e] * inv);
      put(385 + 4 * i + (j & 3) + 64 * (j >> 2), s.T[3][e] * inv);
      put(513 + 2 * i + lo + 32 * t, s.T[4][e] * inv);
    }
}

__device__ __forceinline__ void expand_taps(uint32_t sb, int ht) {
  const int ch = ht >> 5, lane = ht & 31;
  const uint32_t kc = sb + SM_KC + ch * KC_STRIDE * 2;
  const uint32_t dst0 = sb + cv_pe(ch);
  auto put = [&](int G, uint32_t u0, uint32_t u1, uint32_t v0, uint32_t v1, uint32_t v2, uint32_t v3, uint32_t v4, uint32_t v5, uint32_t v6, uint32_t v7) {
    const uint32_t dst = dst0 + G * 32;
    sts128(dst, make_uint4(v0 | (u0 << 16), v1 | (u1 << 16), v2 | (v0 << 16), v3 | (v1 << 16)));
    sts128(dst + 16, make_uint4(v4 | (v2 << 16), v5 | (v3 << 16), v6 | (v4 << 16), v7 | (v5 << 16)));
  };
  {
    const uint4 q = lds128(kc + lane * 16);
    const uint32_t pv = lane ? lds32(kc + lane * 16 - 4) : 0u;
    const uint32_t dst = dst0 + (lane + 2) * 32;
    sts128(dst, make_uint4(__byte_perm(q.x, pv, 0x5410), __byte_perm(q.x, pv, 0x7632), __byte_perm(q.y, q.x, 0x5410), __byte_perm(q.y, q.x, 0x7632)));
    sts128(dst + 16, make_uint4(__byte_perm(q.z, q.y, 0x5410), __byte_perm(q.z, q.y, 0x7632), __byte_perm(q.w, q.z, 0x5410), __byte_perm(q.w, q.z, 0x7632)));
    if (lane < 4) sts128(dst0 + lane * 16, make_uint4(0, 0, 0, 0));
  }
  uint32_t a[5], b[2][3], fv[4];
  {
    const uint32_t s1 = kc + 2 * (256 + 4 * lane);
#pragma unroll
    for (int k = 0; k < 5; k++) a[k] = lds16(s1 + 2 * k);
#pragma unroll
    for (int u = 0; u < 2; u++) {
      const uint32_t s2 = kc + 2 * (384 + 2 * (lane + 32 * u));
#pragma unroll
      for (int k = 0; k < 3; k++) b[u][k] = lds16(s2 + 2 * k);
    }
#pragma unroll
    for (int k = 0; k < 4; k++) fv[k] = lds16(kc + 2 * (640 - 4 * lane - k));
  }
  const uint32_t am1 = lds16(kc + 2 * (lane ? 256 + 4 * lane : 255)), am2 = lds16(kc + 2 * (lane ? 255 + 4 * lane : 254));
  const uint32_t bm2 = lds16(kc + 2 * (lane ? 384 + 2 * lane : 383)), k1024 = lds16(kc + 2 * 512);
  put(34 + lane, am2, am1, a[0], a[0], a[1], a[2], a[2], a[2], a[3], a[4]);
#pragma unroll
  for (int u = 0; u < 2; u++) put(66 + lane + 32 * u, u ? b[u][0] : bm2, b[u][0], b[u][0], b[u][0], b[u][0], b[u][1], b[u][1], b[u][1], b[u][2], b[u][2]);
  if (lane < 10) {
    const uint32_t v = lane == 0 ? k1024 : 0u;
    put(130 + lane, v, v, v, v, v, v, v, 0u, 0u, 0u);
  }
  const uint32_t ft = sb + cv_ft(ch) + 4 * lane;
#pragma unroll
  for (int ty = 0; ty < 2; ty++) {
    const uint32_t v = fv[ty] | (fv[ty + 2] << 16);
    sts32f(ft + ty * 512, __uint_as_float(v));
    sts32f(ft + ty * 512 + 128, 0.f);
    sts32f(ft + ty * 512 + 256 + (lane < 2 ? 120 : -8), __uint_as_float(lane < 2 ? 0u : v));
    sts32f(ft + ty * 512 + 384, 0.f);
  }
}

template <bool SMID> __device__ __forceinline__ int role_id() {
  uint32_t v;
  if (!SMID) { asm volatile("mov.u32 %0, %%ctaid.x;" : "=r"(v)); return v; }
  asm volatile("mov.u32 %0, %%smid;" : "=r"(v));
  const int tp = v >> 1, q = ((tp - 32) * 37) >> 8;
  const int r = tp < 32 ? (tp & 7) * 8 + (tp >> 3) : tp < 60 ? (tp - 31 - 7 * q) * 8 + 4 + q : tp < 62 ? tp + 4 : tp - 58;
  return __shfl_sync(~0u, 2 * r + (v & 1), 0);
}
__device__ __forceinline__ int role_rb(int cta) { return ((cta >> 4) & 3) * 4 + ((cta >> 2) & 3); }
__device__ __forceinline__ int role_hg(int cta) { return (cta >> 6) * 4 + (cta & 3); }
__device__ __forceinline__ int role_rb2(int cta) { return cta >> 3; }
__device__ __forceinline__ int role_q2(int cta) { return cta & 7; }

template <bool SMID> __global__ void __launch_bounds__(NTHREADS, 1) fused_kernel(const __grid_constant__ Params p) {
  extern __shared__ __align__(1024) uint8_t smem[];
  const uint32_t sb = s32(smem);
  const int tid = threadIdx.x, lane = tid & 31;
  const int warp = __shfl_sync(~0u, tid >> 5, 0);
  constexpr unsigned NARR = SMID ? 132 : NCTA;
  const uint32_t bar = sb + SM_BAR;
  if (tid == 0) TS(0);
  const int cta0 = role_id<SMID>();
  if (warp == 0 && (!SMID || cta0 < NCTA) && elect_one()) {
    const int rb = role_rb(cta0), hg = role_hg(cta0);
    mbar_init(bar + 8 * B_XF, 1); mbar_init(bar + 8 * B_KVF, 1);
    fence_async_smem();
#pragma unroll
    for (int c = 0; c < 8; c++) {
      mbar_expect(bar + 8 * (B_XF + c), 16384);
      tma_ld(sb + SM_X + c * 16384, &p.mapX128, (rb >> 3) * DM + c * 64, (rb & 7) * 128, bar + 8 * (B_XF + c));
      if (c < 3) {
        mbar_expect(bar + 8 * (B_KVF + c), 24576);
        tma_ld3(sb + SM_W + c * 24576, &p.mapW3, hg * 64, c * 64, 0, bar + 8 * (B_KVF + c));
      }
      if (c == 0) {
#pragma unroll
        for (int i = 1; i < 8; i++) mbar_init(bar + 8 * (B_XF + i), 1);
        mbar_init(bar + 8 * (B_KVF + 1), 1); mbar_init(bar + 8 * (B_KVF + 2), 1); mbar_init(bar + 8 * B_CW, 1);
        fence_async_smem();
      }
      if (c == PF_AT) {
        mbar_expect(bar + 8 * B_CW, 12288);
        tma_ld3(sb + SM_CW, &p.mapW3h, hg * 64, rb * 32, 0, bar + 8 * B_CW);
      }
    }
    TS(56);
  }
  if (SMID && cta0 >= NCTA) {
    if (tid == 0) spin_until(&g_cnt[C_CS * 32], (atomicAdd(&g_cnt[C_CS * 32], 1u) / NARR + 1) * NARR);
    return;
  }
  if (warp >= 1 && warp < 5 && elect_one()) {
#pragma unroll
    for (int q = 0; q < 4; q++) {
      if (warp == q + 1) {
#pragma unroll
        for (int i = 11 + 15 * q; i < 26 + 15 * q && i < B_COUNT; i++) {
          if (i < B_KVF + 3 || i == B_CW) continue;
          int cnt = 1;
          if ((i >= B_KVE && i < B_KVE + 5) || i == B_QDONE || i == B_PDONE || i == B_OST || i == B_AD) cnt = 2;
          if ((i >= B_U && i < B_U + 4) || i == B_PS) cnt = 8;
          if ((i >= B_S && i < B_S + 4) || (i >= B_E && i < B_E + 4) || (i >= B_P && i < B_P + 4) || i == B_PE || i == B_STF || i == B_HF) cnt = 4;
          if (i == B_CSF) cnt = 3;
          mbar_init(bar + 8 * i, cnt);
        }
      }
    }
    fence_async_smem();
  }

  if (warp < 8) {
    bar_sync(0, NTHREADS);
    if (tid == 0) TS(1);
    asm volatile("setmaxnreg.inc.sync.aligned.u32 %0;" ::"n"(R_CONS));
    const int cta = role_id<SMID>();
    auto warp_id = [] { return __shfl_sync(~0u, opaque_tid() >> 5, 0); };
    if (tid == 0) TS(54);
#pragma unroll 1
    for (int layer = 0; layer < 2; layer++) {
      { const int cw = warp_id(); attn_phase(p, sb, layer, role_rb(cta), role_hg(cta), cw >> 2, cw & 3); }
      if (p.stop == 1 + 3 * layer) return;
      { const int cw = warp_id(); proj_phase(p, sb, layer, role_rb2(cta), role_q2(cta), cw >> 2, cw & 3); }
      if (p.stop == 2 + 3 * layer) return;
      conv_phase(p, sb, layer, cta);
      if (p.stop == 3 + 3 * layer) return;
    }
    { const int cw = warp_id(); final_phase(p, sb, cta, cw >> 2, cw & 3); }
  } else if (warp < 12) {
    asm volatile("setmaxnreg.dec.sync.aligned.u32 %0;" ::"n"(R_HELP));
    const int ht = tid - 256;
    const int cta = role_id<SMID>(), rb = role_rb(cta), hg = role_hg(cta);
    unsigned ep0 = 0;
    if (ht == 0) ep0 = ld_relaxed(&g_cnt[C_CS * 32]);
    bar_sync(0, NTHREADS);
    if (ht == 0) {
      asm volatile("st.shared.u32 [%0], %1;" ::"r"(sb + SM_EP), "r"(ep0 / NARR) : "memory");
      mbar_arrive(bar + 8 * B_EP);
    }
    mbar_wait(bar + 8 * B_EP, 0);
    const uint32_t cs_tag = lds32(sb + SM_EP) % 7 + 1;
    if (ht < 96) {
      mbar_wait(bar + 8 * B_CW, 0);
      colsum_publish(sb, rb, hg, ht, cs_tag);
    }
    if (ht == 0) TS(50);
    if (ht < 48) {
      const bf16* q = (&p.a_re)[ht >> 3];
      asm volatile("prefetch.global.L2 [%0];" ::"l"(q + cv_chan(cta, (ht >> 1) & 3) * 128 + (ht & 1) * 64));
    }
    stats_publish(sb, 0, rb, hg, opaque_tid() - 256, part_tag(lds32(sb + SM_EP), 0));
    {
      KGen kg;
      const uint32_t tab0 = sb + ((ht >> 5) < 2 ? SM_T : SM_T2 - 4096) + (ht >> 5) * 2048;
      const uint32_t tab = tab0 + (ht & 31) * 16, taba = tab0 + ((ht >> 3) & 1) * 1024 + (((ht >> 1) & 8) + (ht & 7)) * 16;
      mbar_wait(bar + 8 * (B_KVF + CS_AT), 0);
      if (ht < 96) {
        colsum_gather(sb, hg, ht, cs_tag);
        __syncwarp();
        if (elect_one()) mbar_arrive(bar + 8 * B_CSF);
      }
      stats_gather(sb, rb, opaque_tid() - 256, part_tag(lds32(sb + SM_EP), 0));
      if (ht == 0) TS(40);
      const int chn = cv_chan(cta, ht >> 5);
      const ModeIn modes = load_modes(p, chn * 128 + (ht & 31) * 4);
      const bf16 logdt = p.log_dt[chn], dskip = p.dskip[chn];
      halo_receive(sb, 0, rb, hg, opaque_tid() - 256);
      kgen_setup(kg, sb, cta, ht, modes, logdt, dskip);
#pragma unroll 1
      for (int u = 0; u < 4; u++) {
        if (u == KG_PRE) {
          KTS(39);
          mbar_wait(bar + 8 * B_AD, 0);
          KTS(41);
        }
        if (u == 4 - KG_LAST) mbar_wait(bar + 8 * (KG_PD ? B_PDONE : B_PS), 0);
        kgen_unit(tab, taba, kg.cur.x, kg.cur.y, {kg.cur.z, kg.cur.w}, kg.T);
        kg.cur = lds128f(kgen_slot(sb, opaque_tid() - 256, u + 1));
      }
      kgen_finish(kg, sb, cta, opaque_tid() - 256);
    }
    KTS(51);
    bar_sync(4, 128);
#pragma unroll 1
    for (int layer = 0; layer < 2; layer++) {
      if (p.stop <= 1 + 3 * layer) return;
      mbar_wait(bar + 8 * (EXP_LATE ? B_PS : B_PDONE), layer);
      expand_taps(sb, opaque_tid() - 256);
      conv_zero(sb, opaque_tid() - 256);
      if (ht == 0) TS(52 + layer);
      warp_release(bar + 8 * B_PE);
      if (p.stop <= 2 + 3 * layer) return;
      {
        uint4 xr[4], st[4];
        const int c = opaque_tid() - 256;
        const SumAddr sa = conv_sum_addr(sb, c);
        conv_prep_load(sb, layer, cta, c, xr, st);
        conv_prep<true>(sb, layer, cta, c, xr, st, sa);
        if (layer == 1 && ht == 0) TS(62);
        mbar_wait(bar + 8 * (B_U + 1), layer);
        conv_sums(sa, 1, c);
        fence_async_smem();
        warp_release(bar + 8 * (B_S + 1));
        mbar_wait(bar + 8 * (B_U + 3), layer);
        conv_sums(sa, 2, c);
        warp_release(bar + 8 * (B_S + 2));
        const bf16* xup = g_xT + (size_t)(2 * layer * DM + cta) * LSEQ + (c + 128) * 8;
        st[0] = ldcg128(xup);
        conv_sums(sa, 3, c);
        warp_release(bar + 8 * (B_S + 3));
#pragma unroll
        for (int lc = 0; lc < 4; lc++) {
          if (lc < 3) st[lc + 1] = ldcg128(xup + (lc + 1) * 128 * LSEQ);
          conv_epi(sb, layer, cta, lc, c, xr[lc], st[lc]);
          warp_release(bar + 8 * (B_E + lc));
          if (layer == 1 && lc == 3 && ht == 0) TS(38);
        }
      }
      if (layer == 0 && p.stop > 3) {
        const int c1 = role_id<SMID>();
        stats_publish(sb, 1, role_rb(c1), role_hg(c1), opaque_tid() - 256, part_tag(lds32(sb + SM_EP), 2));
        delay<D_ST>();
        stats_gather(sb, role_rb(c1), opaque_tid() - 256, part_tag(lds32(sb + SM_EP), 2));
        if (ht == 0) TS(25);
        halo_receive(sb, 1, role_rb(c1), role_hg(c1), opaque_tid() - 256);
      }
    }
  } else {
    asm volatile("setmaxnreg.dec.sync.aligned.u32 %0;" ::"n"(512 - 2 * R_CONS - R_HELP));
    const int cta = role_id<SMID>(), rb = role_rb(cta), hg = role_hg(cta), rb2 = role_rb2(cta), q2 = role_q2(cta);
    bar_sync(0, NTHREADS);
    if (warp == 12) {
      if (elect_one()) {
        unsigned epoch = 0;
#pragma unroll 1
        for (int layer = 0; layer < 2; layer++) {
          auto ld_w = [&](int c, int slot) {
            const uint32_t b = bar + 8 * (B_KVF + c);
            mbar_expect(b, 24576);
            tma_ld3(sb + SM_W + slot * 24576, &p.mapW3, hg * 64, c * 64, 0, b);
          };
          if (layer == 0) {
            TS(55);
            mbar_wait(bar + 8 * (B_KVF + 2), 0);
            if (rb2 < 4) tma_prefetch2(&p.mapWo128, q2 * 64, rb2 * 128);
            asm volatile("prefetch.tensormap [%0];" ::"l"(&p.mapO) : "memory");
            asm volatile("prefetch.tensormap [%0];" ::"l"(&p.mapO128) : "memory");
            asm volatile("prefetch.tensormap [%0];" ::"l"(&p.mapXT) : "memory");
            asm volatile("prefetch.tensormap [%0];" ::"l"(&p.mapXT3) : "memory");
            mbar_wait(bar + 8 * B_EP, 0);
            epoch = lds32(sb + SM_EP);
          } else {
            mbar_wait(bar + 8 * B_PDONE, 0);
            ld_w(0, 0); ld_w(1, 1);
            mbar_wait(bar + 8 * (W2_LATE ? B_U : B_RE), 0);
            ld_w(2, 2);
          }
          {
            int slot = 0;
#pragma unroll 1
            for (int c = 3; c < 8; c++) {
              mbar_wait(bar + 8 * (B_KVE + c - 3), layer);
              ld_w(c, slot);
              slot = slot == 2 ? 0 : slot + 1;
            }
          }
          if (p.stop <= 1 + 3 * layer) return;
          mbar_wait(bar + 8 * B_QDONE, layer);
          mbar_wait(bar + 8 * B_HF, layer);
#pragma unroll 1
          for (int c = 0; c < 4; c++) {
            const uint32_t b = bar + 8 * (B_WOF + c);
            mbar_expect(b, 16384);
            tma_ld(sb + SM_WO + c * 16384, &p.mapWo128, q2 * 64, c * 128, b);
          }
          {
            const uint32_t b = bar + 8 * B_RF;
            mbar_expect(b, 16384);
            if (layer == 0) tma_ld(sb + SM_R, &p.mapX128, (rb2 >> 3) * DM + q2 * 64, (rb2 & 7) * 128, b);
            else tma_ld3(sb + SM_R, &p.mapXT3, 0, DM + q2 * 64, rb2 * 2, b);
          }
          spin_until(&g_cnt[(C_O + rb2) * 32], (2 * epoch + layer + 1) * 16);
          fence_async_global();
#pragma unroll 1
          for (int c = 0; c < 8; c++) {
            const uint32_t b = bar + 8 * (B_OF + c);
            if (c == 4) { mbar_wait(bar + 8 * B_OST, layer); fence_async_smem(); }
            mbar_expect(b, 16384);
            tma_ld(sb + sm_o(c), &p.mapO128, c * 64, rb2 * 128, b);
          }
          if (p.stop <= 3 + 3 * layer) return;
        }
      }
    } else if (warp == 13) {
      if (elect_one() && p.stop > 3) {
        mbar_wait(bar + 8 * B_GB, 0);
        const unsigned target = (lds32(sb + SM_EP) + 1) * NCTA;
        auto ld_x = [&](int c) {
          mbar_expect(bar + 8 * (B_XF + c), 16384);
          tma_ld3(sb + SM_X + c * 16384, &p.mapXT3, 0, DM + c * 64, rb * 2, bar + 8 * (B_XF + c));
        };
        int done = 0, it = 0;
        while (done < 4) {
          const uint4 v = ld_tagged((const uint4*)&g_cnt[C_G1 * 32]);
          const int n = (int)(v.x - target) < 0 ? 0 : (int)(v.y - target) < 0 ? 1 : (int)(v.z - target) < 0 ? 2 : (int)(v.w - target) < 0 ? 3 : 4;
          if (++it > (1 << 23)) __trap();
          if (n == done) continue;
          if (n == 4) TS(44);
          fence_async_global();
          fence_async_smem();
          const int first = n == 4 && done > 1 ? 6 + (hg >> 2) : -1;
          if (first >= 0) ld_x(first);
#pragma unroll 1
          for (int c = 2 * done; c < 2 * n; c++)
            if (c != first) ld_x(c);
          done = n;
        }
      }
    } else if (warp == 15) {
      mbar_wait(bar + 8 * B_EP, 0);
      const unsigned epoch = lds32(sb + SM_EP);
#pragma unroll 1
      for (int layer = 0; layer < 2; layer++) {
#pragma unroll 1
        for (int i = 0; i < 6; i++) {
          mbar_wait(bar + 8 * (B_KVF + (FILL_AT + i < 7 ? FILL_AT + i : 7)), layer);
          uint4* dst = (uint4*)(g_xT + (size_t)(i < 4 ? 2 * layer * DM + cv_chan(cta, i) : 3 * DM + cv_chan(cta, 2 * layer + i - 4)) * LSEQ) + lane;
#pragma unroll
          for (int k = 0; k < 8; k++) dst[32 * k] = make_uint4(~0u, ~0u, ~0u, ~0u);
        }
        if (lane < 8) ((uint4*)g_stats)[layer * 1024 + cta * 8 + lane] = make_uint4(0, 0, 0, 0);
        __syncwarp();
        if (elect_one()) {
          red_release(&g_cnt[C_CS * 32 + layer]);
          spin_until(&g_cnt[C_CS * 32 + layer], (epoch + 1) * (layer ? NCTA : NARR));
          mbar_arrive(bar + 8 * B_ZF);
          if (layer == 0 && p.stop > 2) {
#pragma unroll 1
            for (int lc = 0; lc < 4; lc++) {
              mbar_wait(bar + 8 * (B_E + lc), 0);
              fence_reader();
              bulk_st(g_xT + (size_t)(DM + cv_chan(cta, lc)) * LSEQ, sb + cv_s(lc), 4096);
              bulk_commit();
              bulk_wait_all();
              red_relaxed(&g_cnt[C_G1 * 32 + lc]);
              if (lc == 3) TS(18);
            }
          }
        }
        __syncwarp();
        if (p.stop <= 3) return;
      }
    } else if (warp == 14) {
      mbar_wait(bar + 8 * B_EP, 0);
      const unsigned epoch = lds32(sb + SM_EP);
#pragma unroll 1
      for (int layer = 0; layer < 2; layer++) {
        if (p.stop <= 1 + 3 * layer) return;
        mbar_wait(bar + 8 * B_ZF, layer);
        mbar_wait(bar + 8 * (EXP_LATE ? B_PS : B_PDONE), layer);
        delay<D_PST>();
        proj_stats(layer, rb2, q2, lane, part_tag(epoch, 2 * layer + 1));
        if (layer == 1 && lane == 0) TS(5);
        delay<D_PREP>();
        if (lane == 0) mbar_arrive(bar + 8 * B_GB);
      }
    }
  }
}

typedef CUresult (*EncodeFn)(CUtensorMap*, CUtensorMapDataType, cuuint32_t, void*, const cuuint64_t*, const cuuint64_t*,
                             const cuuint32_t*, const cuuint32_t*, CUtensorMapInterleave, CUtensorMapSwizzle,
                             CUtensorMapL2promotion, CUtensorMapFloatOOBfill);

static void make_map(EncodeFn enc, CUtensorMap* m, void* ptr, uint64_t cols, uint64_t rows, uint32_t box_rows) {
  cuuint64_t dims[2] = {cols, rows};
  cuuint64_t strides[1] = {cols * 2};
  cuuint32_t box[2] = {64, box_rows};
  cuuint32_t es[2] = {1, 1};
  enc(m, CU_TENSOR_MAP_DATA_TYPE_BFLOAT16, 2, ptr, dims, strides, box, es, CU_TENSOR_MAP_INTERLEAVE_NONE,
      CU_TENSOR_MAP_SWIZZLE_128B, CU_TENSOR_MAP_L2_PROMOTION_L2_128B, CU_TENSOR_MAP_FLOAT_OOB_FILL_NONE);
}
static void make_map3(EncodeFn enc, CUtensorMap* m, void* ptr, uint64_t d0, uint64_t cols, uint64_t rows, uint64_t blk_stride,
                      uint64_t nblocks, uint32_t nblk, uint32_t box_rows = 64) {
  cuuint64_t dims[3] = {d0, rows, nblocks};
  cuuint64_t strides[2] = {cols * 2, blk_stride * 2};
  cuuint32_t box[3] = {64, box_rows, nblk};
  cuuint32_t es[3] = {1, 1, 1};
  enc(m, CU_TENSOR_MAP_DATA_TYPE_BFLOAT16, 3, ptr, dims, strides, box, es, CU_TENSOR_MAP_INTERLEAVE_NONE,
      CU_TENSOR_MAP_SWIZZLE_128B, CU_TENSOR_MAP_L2_PROMOTION_L2_128B, CU_TENSOR_MAP_FLOAT_OOB_FILL_NONE);
}

extern "C" void kernel_launch(void* const* d_in, const int* in_sizes, int n_in, void* d_out, int out_size) {
  static Params prm;
  static void* cached[13] = {nullptr};
  static bool attr_done = false, by_smid = false;
  bool same = attr_done && cached[12] == d_out;
  for (int i = 0; i < 12 && same; i++) same = cached[i] == d_in[i];
  if (!same) {
    void* fn = nullptr;
    cudaDriverEntryPointQueryResult qr;
    cudaGetDriverEntryPoint("cuTensorMapEncodeTiled", &fn, cudaEnableDefault, &qr);
    EncodeFn enc = (EncodeFn)fn;
    void *pO, *pXT;
    cudaGetSymbolAddress(&pO, g_O);
    cudaGetSymbolAddress(&pXT, g_xT);
    make_map(enc, &prm.mapO, pO, DM, LSEQ, 64);
    make_map(enc, &prm.mapXT, pXT, LSEQ, 4 * DM, 64);
    prm.out = (bf16*)d_out;
    make_map(enc, &prm.mapX128, d_in[0], 2 * DM, LSEQ / 2, 128);
    make_map(enc, &prm.mapWo128, d_in[2], DM, DM, 128);
    make_map(enc, &prm.mapO128, pO, DM, LSEQ, 128);
    make_map3(enc, &prm.mapW3, d_in[1], DM, 3 * DM, DM, DM, 3, 3);
    make_map3(enc, &prm.mapW3h, d_in[1], DM, 3 * DM, DM, DM, 3, 3, 32);
    make_map3(enc, &prm.mapXT3, pXT, 64, LSEQ, 4 * DM, 64, 32, 2);
    prm.a_re = (const bf16*)d_in[4]; prm.a_im = (const bf16*)d_in[5];
    prm.b_re = (const bf16*)d_in[6]; prm.b_im = (const bf16*)d_in[7];
    prm.c_re = (const bf16*)d_in[8]; prm.c_im = (const bf16*)d_in[9];
    prm.log_dt = (const bf16*)d_in[10]; prm.dskip = (const bf16*)d_in[11];
    int dev = 0, sms = 0;
    cudaGetDevice(&dev);
    cudaDeviceGetAttribute(&sms, cudaDevAttrMultiProcessorCount, dev);
    by_smid = sms == 132;
    cudaFuncSetAttribute(fused_kernel<true>, cudaFuncAttributeMaxDynamicSharedMemorySize, SM_TOTAL);
    cudaFuncSetAttribute(fused_kernel<false>, cudaFuncAttributeMaxDynamicSharedMemorySize, SM_TOTAL);
    for (int i = 0; i < 12; i++) cached[i] = d_in[i];
    cached[12] = d_out;
    attr_done = true;
  }
  prm.stop = 100;
    if (by_smid) fused_kernel<true><<<132, NTHREADS, SM_TOTAL>>>(prm);
  else fused_kernel<false><<<NCTA, NTHREADS, SM_TOTAL>>>(prm);
}
```

```cpp
#include <cuda_runtime.h>
#include <cuda_bf16.h>
#include <cuda.h>
#include <stdint.h>

typedef __nv_bfloat16 bf16;

constexpr int LSEQ = 2048;
constexpr int DM = 512;
constexpr int NCTA = 128;
constexpr int NTHREADS = 512;
#define RR 0
#define KG_PRE 2
#define W2_LATE 0
#define FILL_AT 2
#define EXP_LATE 1
#define RFENCE 1
#define D_FIN 550
#define D_PREP 500
#define D_PST 0
#define D_HALO 300
#define STAG 2
#define D_ST 0
#define TLAYER 1
#define KG_PD 0
#define SUM_F32 0
#define CS_LATE0 0
#define D_HALO1 0
#define CS_FIRST 0
#define H_ORDER 1
#define CS_AT 4
#define KG_LAST 1
#define X_JIT 0
#define PF_AT 1
#define KG_GATE 2
#define R_CONS 192
#define R_HELP 88

constexpr int SM_X = 0;
constexpr int SM_W = 131072;
constexpr int SM_KVX = SM_X;
constexpr int SM_OST = SM_X + 32768;
constexpr int SM_WO = SM_X + 65536;
__host__ __device__ constexpr int sm_o(int c) { return c < 4 ? SM_W + c * 16384 : SM_X + (c - 4) * 16384; }
constexpr int SM_R = 196608;
constexpr int SM_T = 212992;
constexpr int SM_KC = 217088;
constexpr int KC_STRIDE = 648;
constexpr int SM_CS = SM_KC + 4 * KC_STRIDE * 2;
constexpr int SM_CW = SM_R + 8192;
constexpr int SM_EP = SM_CS + 768;
constexpr int SM_BAR = SM_EP + 16;
constexpr int SM_T2 = SM_BAR + 832;
constexpr int SM_HALO = SM_T2 + 4096;
constexpr int SM_ST = SM_HALO + 3072;
constexpr int SM_TOTAL = SM_HALO + 4096;
static_assert(SM_TOTAL <= 232448, "shared memory");

constexpr int CV_UH = 140 * 16;
constexpr int CV_PECH = 1120 * 4;
constexpr int CV_PBW = 2112 * 2;
__host__ __device__ constexpr int cv_s(int lc) { return SM_X + lc * 32768; }
__host__ __device__ constexpr int cv_u(int lc) { return cv_s(lc) + 4096; }
__host__ __device__ constexpr int cv_pe(int lc) { return cv_u(lc) + 2 * CV_UH; }
__host__ __device__ constexpr int cv_pb(int lc) { return cv_pe(lc) + CV_PECH; }
__host__ __device__ constexpr int cv_ft(int lc) { return cv_pb(lc) + 4 * CV_PBW; }
static_assert(cv_ft(0) + 1024 <= 32768, "conv buffers");
__host__ __device__ constexpr int cv_chan(int cta, int lc) { return cta + 128 * lc; }

enum {
  B_XF = 0,
  B_KVF = 8,
  B_KVE = 16,
  B_AD = 21,
  B_OST = 22,
  B_RF = 23,
  B_U = 24,
  B_S = 28,
  B_T = 32,
  B_WOF = 36,
  B_E = 40,
  B_OF = 44,
  B_P = 64,
  B_RE = 52,
  B_CW = 53,
  B_HF = 54,
  B_STF = 55,
  B_CSF = 61,
  B_SD = 68,
  B_QDONE = 56,
  B_PDONE = 57,
  B_PS = 58,
  B_PE = 59,
  B_GB = 60,
  B_EP = 62,
  B_ZF = 63,
  B_COUNT = 69
};

enum {
  C_CS = 0,
  C_G1 = 2,
  C_O = 4,
  C_COUNT = 20
};

__device__ __align__(128) unsigned g_cnt[C_COUNT * 32];
__device__ __align__(1024) bf16 g_O[LSEQ * DM];
__device__ __align__(1024) bf16 g_xT[4 * DM * LSEQ];
__device__ __align__(1024) float g_stats[2 * LSEQ * 2];
__device__ __align__(1024) uint4 g_colsum[8 * 16 * 48];
__device__ __align__(1024) uint4 g_halo[16 * 8 * 192];
__device__ __align__(1024) uint2 g_part[16 * 8 * 128];
#define TS(i) do { } while (0)

#define ATS(i, th) do { } while (0)
#define KTS(i) do { if (ht == 0) TS(i); } while (0)
#define FTS(i) do { } while (0)
#define LTS(i) do { } while (0)

struct Params {
  CUtensorMap mapO, mapXT, mapX128, mapWo128, mapO128, mapW3, mapW3h, mapXT3;
  const bf16 *a_re, *a_im, *b_re, *b_im, *c_re, *c_im, *log_dt, *dskip;
  bf16* out;
  int stop;
};

__device__ __forceinline__ uint32_t s32(const void* p) { return (uint32_t)__cvta_generic_to_shared(p); }
__device__ __forceinline__ void mbar_init(uint32_t b, int c) { asm volatile("mbarrier.init.shared::cta.b64 [%0], %1;" ::"r"(b), "r"(c) : "memory"); }
__device__ __forceinline__ void mbar_expect(uint32_t b, int bytes) { asm volatile("mbarrier.arrive.expect_tx.shared::cta.b64 _, [%0], %1;" ::"r"(b), "r"(bytes) : "memory"); }
__device__ __forceinline__ void mbar_arrive(uint32_t b) { asm volatile("mbarrier.arrive.shared::cta.b64 _, [%0];" ::"r"(b) : "memory"); }
__device__ __forceinline__ void mbar_arrive_if(uint32_t b, bool c) {
  asm volatile("{\n.reg .pred p;\nsetp.ne.u32 p, %1, 0;\n@p mbarrier.arrive.shared::cta.b64 _, [%0];\n}" ::"r"(b), "r"((uint32_t)c) : "memory");
}
__device__ __forceinline__ void mbar_wait(uint32_t b, int parity) {
  asm volatile("{\n.reg .pred p;\nWAIT_LOOP:\nmbarrier.try_wait.parity.shared::cta.b64 p, [%0], %1;\n@p bra WAIT_DONE;\nbra WAIT_LOOP;\nWAIT_DONE:\n}" ::"r"(b), "r"(parity) : "memory");
}
template <int N> __device__ __forceinline__ void delay() {
  if constexpr (N > 0) {
    uint32_t t0, t;
    asm volatile("mov.u32 %0, %%clock;" : "=r"(t0));
    do { asm volatile("mov.u32 %0, %%clock;" : "=r"(t)); } while (t - t0 < N);
  }
}
__device__ __forceinline__ int opaque_tid() { int v; asm volatile("mov.u32 %0, %%tid.x;" : "=r"(v)); return v; }
__device__ __forceinline__ bool elect_one() {
  uint32_t r;
  asm volatile("{\n.reg .pred p;\nelect.sync _|p, 0xffffffff;\nselp.u32 %0, 1, 0, p;\n}" : "=r"(r));
  return r != 0;
}
__device__ __forceinline__ void tma_ld(uint32_t dst, const CUtensorMap* m, int c0, int c1, uint32_t bar) {
  asm volatile("cp.async.bulk.tensor.2d.shared::cluster.global.mbarrier::complete_tx::bytes [%0], [%1, {%3, %4}], [%2];"
               ::"r"(dst), "l"(m), "r"(bar), "r"(c0), "r"(c1) : "memory");
}
__device__ __forceinline__ void tma_ld3(uint32_t dst, const CUtensorMap* m, int c0, int c1, int c2, uint32_t bar) {
  asm volatile("cp.async.bulk.tensor.3d.shared::cluster.global.mbarrier::complete_tx::bytes [%0], [%1, {%3, %4, %5}], [%2];"
               ::"r"(dst), "l"(m), "r"(bar), "r"(c0), "r"(c1), "r"(c2) : "memory");
}
__device__ __forceinline__ void tma_prefetch2(const CUtensorMap* m, int c0, int c1) {
  asm volatile("cp.async.bulk.prefetch.tensor.2d.L2.global.tile [%0, {%1, %2}];" ::"l"(m), "r"(c0), "r"(c1) : "memory");
}
__device__ __forceinline__ void tma_prefetch3(const CUtensorMap* m, int c0, int c1, int c2) {
  asm volatile("cp.async.bulk.prefetch.tensor.3d.L2.global.tile [%0, {%1, %2, %3}];" ::"l"(m), "r"(c0), "r"(c1), "r"(c2) : "memory");
}
__device__ __forceinline__ void tma_st(const CUtensorMap* m, int c0, int c1, uint32_t src) {
  asm volatile("cp.async.bulk.tensor.2d.global.shared::cta.bulk_group [%0, {%2, %3}], [%1];" ::"l"(m), "r"(src), "r"(c0), "r"(c1) : "memory");
}
__device__ __forceinline__ void bulk_ld(uint32_t dst, const void* src, int bytes, uint32_t bar) {
  asm volatile("cp.async.bulk.shared::cluster.global.mbarrier::complete_tx::bytes [%0], [%1], %2, [%3];" ::"r"(dst), "l"(src), "r"(bytes), "r"(bar) : "memory");
}
__device__ __forceinline__ void bulk_st(void* dst, uint32_t src, int bytes) {
  asm volatile("cp.async.bulk.global.shared::cta.bulk_group [%0], [%1], %2;" ::"l"(dst), "r"(src), "r"(bytes) : "memory");
}
__device__ __forceinline__ void bulk_red_add_f32(void* dst, uint32_t src, int bytes) {
  asm volatile("cp.reduce.async.bulk.global.shared::cta.bulk_group.add.f32 [%0], [%1], %2;" ::"l"(dst), "r"(src), "r"(bytes) : "memory");
}
__device__ __forceinline__ void bulk_commit() { asm volatile("cp.async.bulk.commit_group;" ::: "memory"); }
__device__ __forceinline__ void bulk_wait_all() { asm volatile("cp.async.bulk.wait_group 0;" ::: "memory"); }
__device__ __forceinline__ void fence_async_smem() { asm volatile("fence.proxy.async.shared::cta;" ::: "memory"); }
__device__ __forceinline__ void fence_writer() { if (!RFENCE) fence_async_smem(); }
__device__ __forceinline__ void fence_reader() { if (RFENCE) fence_async_smem(); }
__device__ __forceinline__ void fence_async_global() { asm volatile("fence.proxy.async.global;" ::: "memory"); }
__device__ __forceinline__ void bar_sync(int id, int n) { asm volatile("bar.sync %0, %1;" ::"r"(id), "r"(n) : "memory"); }
__device__ __forceinline__ void bar_arrive(int id, int n) { asm volatile("bar.arrive %0, %1;" ::"r"(id), "r"(n) : "memory"); }
__device__ __forceinline__ void wg_fence() { asm volatile("wgmma.fence.sync.aligned;" ::: "memory"); }
__device__ __forceinline__ void wg_commit() { asm volatile("wgmma.commit_group.sync.aligned;" ::: "memory"); }
template <int N> __device__ __forceinline__ void wg_wait() { asm volatile("wgmma.wait_group.sync.aligned %0;" ::"n"(N) : "memory"); }
__device__ __forceinline__ uint64_t mkdesc(uint32_t addr, uint32_t lbo, uint32_t sbo, int sw) {
  return (uint64_t)((addr & 0x3FFFF) >> 4) | ((uint64_t)(lbo >> 4) << 16) | ((uint64_t)(sbo >> 4) << 32) | ((uint64_t)sw << 62);
}
__device__ __forceinline__ void ldsm4(uint32_t* r, uint32_t a) {
  asm volatile("ldmatrix.sync.aligned.m8n8.x4.shared.b16 {%0,%1,%2,%3}, [%4];" : "=r"(r[0]), "=r"(r[1]), "=r"(r[2]), "=r"(r[3]) : "r"(a) : "memory");
}
__device__ __forceinline__ void ldsm4t(uint32_t* r, uint32_t a) {
  asm volatile("ldmatrix.sync.aligned.m8n8.x4.trans.shared.b16 {%0,%1,%2,%3}, [%4];" : "=r"(r[0]), "=r"(r[1]), "=r"(r[2]), "=r"(r[3]) : "r"(a) : "memory");
}
__device__ __forceinline__ void stsm4(uint32_t a, uint32_t r0, uint32_t r1, uint32_t r2, uint32_t r3) {
  asm volatile("stmatrix.sync.aligned.m8n8.x4.shared.b16 [%0], {%1,%2,%3,%4};" ::"r"(a), "r"(r0), "r"(r1), "r"(r2), "r"(r3) : "memory");
}
__device__ __forceinline__ void stsm4t(uint32_t a, uint32_t r0, uint32_t r1, uint32_t r2, uint32_t r3) {
  asm volatile("stmatrix.sync.aligned.m8n8.x4.trans.shared.b16 [%0], {%1,%2,%3,%4};" ::"r"(a), "r"(r0), "r"(r1), "r"(r2), "r"(r3) : "memory");
}
__device__ __forceinline__ uint32_t movm_t(uint32_t a) { uint32_t r; asm volatile("movmatrix.sync.aligned.m8n8.trans.b16 %0, %1;" : "=r"(r) : "r"(a)); return r; }
__device__ __forceinline__ uint32_t lds32(uint32_t a) { uint32_t v; asm volatile("ld.shared.b32 %0, [%1];" : "=r"(v) : "r"(a) : "memory"); return v; }
__device__ __forceinline__ float2 lds64f(uint32_t a) { float2 v; asm volatile("ld.shared.v2.f32 {%0,%1}, [%2];" : "=f"(v.x), "=f"(v.y) : "r"(a) : "memory"); return v; }
__device__ __forceinline__ float4 lds128f(uint32_t a) { float4 v; asm volatile("ld.shared.v4.f32 {%0,%1,%2,%3}, [%4];" : "=f"(v.x), "=f"(v.y), "=f"(v.z), "=f"(v.w) : "r"(a) : "memory"); return v; }
__device__ __forceinline__ uint4 lds128(uint32_t a) { uint4 v; asm volatile("ld.shared.v4.b32 {%0,%1,%2,%3}, [%4];" : "=r"(v.x), "=r"(v.y), "=r"(v.z), "=r"(v.w) : "r"(a) : "memory"); return v; }
__device__ __forceinline__ void sts128(uint32_t a, uint4 v) { asm volatile("st.shared.v4.b32 [%0], {%1,%2,%3,%4};" ::"r"(a), "r"(v.x), "r"(v.y), "r"(v.z), "r"(v.w) : "memory"); }
__device__ __forceinline__ void sts128f(uint32_t a, float x, float y, float z, float w) { asm volatile("st.shared.v4.f32 [%0], {%1,%2,%3,%4};" ::"r"(a), "f"(x), "f"(y), "f"(z), "f"(w) : "memory"); }
__device__ __forceinline__ void sts32f(uint32_t a, float v) { asm volatile("st.shared.f32 [%0], %1;" ::"r"(a), "f"(v) : "memory"); }
__device__ __forceinline__ void sts16(uint32_t a, uint16_t v) { asm volatile("st.shared.u16 [%0], %1;" ::"r"(a), "h"(v) : "memory"); }
__device__ __forceinline__ uint32_t lds16(uint32_t a) { uint16_t v; asm volatile("ld.shared.u16 %0, [%1];" : "=h"(v) : "r"(a) : "memory"); return v; }
__device__ __forceinline__ uint32_t packbf(float lo, float hi) { uint32_t r; asm("cvt.rn.bf16x2.f32 %0, %1, %2;" : "=r"(r) : "f"(hi), "f"(lo)); return r; }
__device__ __forceinline__ float bf_lo(uint32_t v) { return __uint_as_float(v << 16); }
__device__ __forceinline__ float bf_hi(uint32_t v) { return __uint_as_float(v & 0xffff0000u); }
__device__ __forceinline__ float ex2(float x) { float r; asm("ex2.approx.ftz.f32 %0, %1;" : "=f"(r) : "f"(x)); return r; }
__device__ __forceinline__ float rsqrt_approx(float x) { float r; asm("rsqrt.approx.ftz.f32 %0, %1;" : "=f"(r) : "f"(x)); return r; }
__device__ __forceinline__ float rcp_approx(float x) { float r; asm("rcp.approx.ftz.f32 %0, %1;" : "=f"(r) : "f"(x)); return r; }
__device__ __forceinline__ void mma_bf16(float* d, const uint32_t* a, uint32_t b0, uint32_t b1) {
  asm("mma.sync.aligned.m16n8k16.row.col.f32.bf16.bf16.f32 {%0,%1,%2,%3}, {%4,%5,%6,%7}, {%8,%9}, {%0,%1,%2,%3};"
               : "+f"(d[0]), "+f"(d[1]), "+f"(d[2]), "+f"(d[3]) : "r"(a[0]), "r"(a[1]), "r"(a[2]), "r"(a[3]), "r"(b0), "r"(b1));
}
__device__ __forceinline__ void mma_bf16_k8(float* d, uint32_t a0, uint32_t a1, uint32_t b) {
  asm("mma.sync.aligned.m16n8k8.row.col.f32.bf16.bf16.f32 {%0,%1,%2,%3}, {%4,%5}, {%6}, {%0,%1,%2,%3};"
      : "+f"(d[0]), "+f"(d[1]), "+f"(d[2]), "+f"(d[3]) : "r"(a0), "r"(a1), "r"(b));
}
__device__ __forceinline__ void red_release(unsigned* p) { asm volatile("red.release.gpu.global.add.u32 [%0], 1;" ::"l"(p) : "memory"); }
__device__ __forceinline__ void red_relaxed(unsigned* p) { asm volatile("red.relaxed.gpu.global.add.u32 [%0], 1;" ::"l"(p) : "memory"); }
__device__ __forceinline__ unsigned ld_relaxed(const unsigned* p) { unsigned v; asm volatile("ld.relaxed.gpu.global.u32 %0, [%1];" : "=r"(v) : "l"(p) : "memory"); return v; }
__device__ __forceinline__ void spin_until(const unsigned* p, unsigned target) {
  int it = 0;
  while ((int)(ld_relaxed(p) - target) < 0) {
    if (++it > (1 << 23)) __trap();
  }
}
__device__ __forceinline__ uint4 ldcg128(const void* p) { uint4 v; asm volatile("ld.global.cg.v4.b32 {%0,%1,%2,%3}, [%4];" : "=r"(v.x), "=r"(v.y), "=r"(v.z), "=r"(v.w) : "l"(p) : "memory"); return v; }
__device__ __forceinline__ uint4 ld_tagged(const uint4* p) { uint4 v; asm volatile("ld.relaxed.gpu.global.v4.u32 {%0,%1,%2,%3}, [%4];" : "=r"(v.x), "=r"(v.y), "=r"(v.z), "=r"(v.w) : "l"(p) : "memory"); return v; }
__device__ __forceinline__ uint2 ld_part(const uint2* p) { uint2 v; asm volatile("ld.relaxed.gpu.global.v2.u32 {%0,%1}, [%2];" : "=r"(v.x), "=r"(v.y) : "l"(p) : "memory"); return v; }
__device__ __forceinline__ void st_part(uint2* p, float s, float q, uint32_t tag) {
  asm volatile("st.relaxed.gpu.global.v2.u32 [%0], {%1,%2};" ::"l"(p), "r"(__float_as_uint(s)), "r"((__float_as_uint(q) & ~7u) | tag) : "memory");
}
__device__ __forceinline__ uint32_t part_tag(uint32_t epoch, int k) { return (4 * (epoch % 7) + k) % 7 + 1; }
__device__ __forceinline__ void st_tagged3(uint4* p, uint32_t a, uint32_t b, uint32_t c, uint32_t tag) { asm volatile("st.relaxed.gpu.global.v4.u32 [%0], {%1,%2,%3,%4};" ::"l"(p), "r"(a), "r"(b), "r"(c), "r"(tag) : "memory"); }
__device__ __forceinline__ uint32_t hadd2(uint32_t a, uint32_t b) { uint32_t r; asm("add.rn.bf16x2 %0, %1, %2;" : "=r"(r) : "r"(a), "r"(b)); return r; }
__device__ __forceinline__ uint32_t hmul2(uint32_t a, uint32_t b) { uint32_t r; asm("mul.rn.bf16x2 %0, %1, %2;" : "=r"(r) : "r"(a), "r"(b)); return r; }

template<int N,int TB> __device__ __forceinline__ void wgmma_rs(float* d, const uint32_t* a, uint64_t db, int sd);
template<int N,int TA,int TB> __device__ __forceinline__ void wgmma_ss(float* d, uint64_t da, uint64_t db, int sd);
template<> __device__ __forceinline__ void wgmma_rs<128,0>(float* d, const uint32_t* a, uint64_t db, int sd) {
  asm volatile("{\n.reg .pred p;\nsetp.ne.b32 p, %69, 0;\nwgmma.mma_async.sync.aligned.m64n128k16.f32.bf16.bf16 {%0,%1,%2,%3,%4,%5,%6,%7,%8,%9,%10,%11,%12,%13,%14,%15,%16,%17,%18,%19,%20,%21,%22,%23,%24,%25,%26,%27,%28,%29,%30,%31,%32,%33,%34,%35,%36,%37,%38,%39,%40,%41,%42,%43,%44,%45,%46,%47,%48,%49,%50,%51,%52,%53,%54,%55,%56,%57,%58,%59,%60,%61,%62,%63}, {%64,%65,%66,%67}, %68, p, 1, 1, 0;\n}\n"
   : "+f"(d[0]),"+f"(d[1]),"+f"(d[2]),"+f"(d[3]),"+f"(d[4]),"+f"(d[5]),"+f"(d[6]),"+f"(d[7]),"+f"(d[8]),"+f"(d[9]),"+f"(d[10]),"+f"(d[11]),"+f"(d[12]),"+f"(d[13]),"+f"(d[14]),"+f"(d[15]),"+f"(d[16]),"+f"(d[17]),"+f"(d[18]),"+f"(d[19]),"+f"(d[20]),"+f"(d[21]),"+f"(d[22]),"+f"(d[23]),"+f"(d[24]),"+f"(d[25]),"+f"(d[26]),"+f"(d[27]),"+f"(d[28]),"+f"(d[29]),"+f"(d[30]),"+f"(d[31]),"+f"(d[32]),"+f"(d[33]),"+f"(d[34]),"+f"(d[35]),"+f"(d[36]),"+f"(d[37]),"+f"(d[38]),"+f"(d[39]),"+f"(d[40]),"+f"(d[41]),"+f"(d[42]),"+f"(d[43]),"+f"(d[44]),"+f"(d[45]),"+f"(d[46]),"+f"(d[47]),"+f"(d[48]),"+f"(d[49]),"+f"(d[50]),"+f"(d[51]),"+f"(d[52]),"+f"(d[53]),"+f"(d[54]),"+f"(d[55]),"+f"(d[56]),"+f"(d[57]),"+f"(d[58]),"+f"(d[59]),"+f"(d[60]),"+f"(d[61]),"+f"(d[62]),"+f"(d[63])
   : "r"(a[0]), "r"(a[1]), "r"(a[2]), "r"(a[3]), "l"(db), "r"(sd));
}
template<> __device__ __forceinline__ void wgmma_rs<120,0>(float* d, const uint32_t* a, uint64_t db, int sd) {
  asm volatile("{\n.reg .pred p;\nsetp.ne.b32 p, %65, 0;\nwgmma.mma_async.sync.aligned.m64n120k16.f32.bf16.bf16 {%0,%1,%2,%3,%4,%5,%6,%7,%8,%9,%10,%11,%12,%13,%14,%15,%16,%17,%18,%19,%20,%21,%22,%23,%24,%25,%26,%27,%28,%29,%30,%31,%32,%33,%34,%35,%36,%37,%38,%39,%40,%41,%42,%43,%44,%45,%46,%47,%48,%49,%50,%51,%52,%53,%54,%55,%56,%57,%58,%59}, {%60,%61,%62,%63}, %64, p, 1, 1, 0;\n}\n"
   : "+f"(d[0]),"+f"(d[1]),"+f"(d[2]),"+f"(d[3]),"+f"(d[4]),"+f"(d[5]),"+f"(d[6]),"+f"(d[7]),"+f"(d[8]),"+f"(d[9]),"+f"(d[10]),"+f"(d[11]),"+f"(d[12]),"+f"(d[13]),"+f"(d[14]),"+f"(d[15]),"+f"(d[16]),"+f"(d[17]),"+f"(d[18]),"+f"(d[19]),"+f"(d[20]),"+f"(d[21]),"+f"(d[22]),"+f"(d[23]),"+f"(d[24]),"+f"(d[25]),"+f"(d[26]),"+f"(d[27]),"+f"(d[28]),"+f"(d[29]),"+f"(d[30]),"+f"(d[31]),"+f"(d[32]),"+f"(d[33]),"+f"(d[34]),"+f"(d[35]),"+f"(d[36]),"+f"(d[37]),"+f"(d[38]),"+f"(d[39]),"+f"(d[40]),"+f"(d[41]),"+f"(d[42]),"+f"(d[43]),"+f"(d[44]),"+f"(d[45]),"+f"(d[46]),"+f"(d[47]),"+f"(d[48]),"+f"(d[49]),"+f"(d[50]),"+f"(d[51]),"+f"(d[52]),"+f"(d[53]),"+f"(d[54]),"+f"(d[55]),"+f"(d[56]),"+f"(d[57]),"+f"(d[58]),"+f"(d[59])
   : "r"(a[0]), "r"(a[1]), "r"(a[2]), "r"(a[3]), "l"(db), "r"(sd));
}
template<> __device__ __forceinline__ void wgmma_rs<112,0>(float* d, const uint32_t* a, uint64_t db, int sd) {
  asm volatile("{\n.reg .pred p;\nsetp.ne.b32 p, %61, 0;\nwgmma.mma_async.sync.aligned.m64n112k16.f32.bf16.bf16 {%0,%1,%2,%3,%4,%5,%6,%7,%8,%9,%10,%11,%12,%13,%14,%15,%16,%17,%18,%19,%20,%21,%22,%23,%24,%25,%26,%27,%28,%29,%30,%31,%32,%33,%34,%35,%36,%37,%38,%39,%40,%41,%42,%43,%44,%45,%46,%47,%48,%49,%50,%51,%52,%53,%54,%55}, {%56,%57,%58,%59}, %60, p, 1, 1, 0;\n}\n"
   : "+f"(d[0]),"+f"(d[1]),"+f"(d[2]),"+f"(d[3]),"+f"(d[4]),"+f"(d[5]),"+f"(d[6]),"+f"(d[7]),"+f"(d[8]),"+f"(d[9]),"+f"(d[10]),"+f"(d[11]),"+f"(d[12]),"+f"(d[13]),"+f"(d[14]),"+f"(d[15]),"+f"(d[16]),"+f"(d[17]),"+f"(d[18]),"+f"(d[19]),"+f"(d[20]),"+f"(d[21]),"+f"(d[22]),"+f"(d[23]),"+f"(d[24]),"+f"(d[25]),"+f"(d[26]),"+f"(d[27]),"+f"(d[28]),"+f"(d[29]),"+f"(d[30]),"+f"(d[31]),"+f"(d[32]),"+f"(d[33]),"+f"(d[34]),"+f"(d[35]),"+f"(d[36]),"+f"(d[37]),"+f"(d[38]),"+f"(d[39]),"+f"(d[40]),"+f"(d[41]),"+f"(d[42]),"+f"(d[43]),"+f"(d[44]),"+f"(d[45]),"+f"(d[46]),"+f"(d[47]),"+f"(d[48]),"+f"(d[49]),"+f"(d[50]),"+f"(d[51]),"+f"(d[52]),"+f"(d[53]),"+f"(d[54]),"+f"(d[55])
   : "r"(a[0]), "r"(a[1]), "r"(a[2]), "r"(a[3]), "l"(db), "r"(sd));
}
template<> __device__ __forceinline__ void wgmma_rs<104,0>(float* d, const uint32_t* a, uint64_t db, int sd) {
  asm volatile("{\n.reg .pred p;\nsetp.ne.b32 p, %57, 0;\nwgmma.mma_async.sync.aligned.m64n104k16.f32.bf16.bf16 {%0,%1,%2,%3,%4,%5,%6,%7,%8,%9,%10,%11,%12,%13,%14,%15,%16,%17,%18,%19,%20,%21,%22,%23,%24,%25,%26,%27,%28,%29,%30,%31,%32,%33,%34,%35,%36,%37,%38,%39,%40,%41,%42,%43,%44,%45,%46,%47,%48,%49,%50,%51}, {%52,%53,%54,%55}, %56, p, 1, 1, 0;\n}\n"
   : "+f"(d[0]),"+f"(d[1]),"+f"(d[2]),"+f"(d[3]),"+f"(d[4]),"+f"(d[5]),"+f"(d[6]),"+f"(d[7]),"+f"(d[8]),"+f"(d[9]),"+f"(d[10]),"+f"(d[11]),"+f"(d[12]),"+f"(d[13]),"+f"(d[14]),"+f"(d[15]),"+f"(d[16]),"+f"(d[17]),"+f"(d[18]),"+f"(d[19]),"+f"(d[20]),"+f"(d[21]),"+f"(d[22]),"+f"(d[23]),"+f"(d[24]),"+f"(d[25]),"+f"(d[26]),"+f"(d[27]),"+f"(d[28]),"+f"(d[29]),"+f"(d[30]),"+f"(d[31]),"+f"(d[32]),"+f"(d[33]),"+f"(d[34]),"+f"(d[35]),"+f"(d[36]),"+f"(d[37]),"+f"(d[38]),"+f"(d[39]),"+f"(d[40]),"+f"(d[41]),"+f"(d[42]),"+f"(d[43]),"+f"(d[44]),"+f"(d[45]),"+f"(d[46]),"+f"(d[47]),"+f"(d[48]),"+f"(d[49]),"+f"(d[50]),"+f"(d[51])
   : "r"(a[0]), "r"(a[1]), "r"(a[2]), "r"(a[3]), "l"(db), "r"(sd));
}
template<> __device__ __forceinline__ void wgmma_rs<96,0>(float* d, const uint32_t* a, uint64_t db, int sd) {
  asm volatile("{\n.reg .pred p;\nsetp.ne.b32 p, %53, 0;\nwgmma.mma_async.sync.aligned.m64n96k16.f32.bf16.bf16 {%0,%1,%2,%3,%4,%5,%6,%7,%8,%9,%10,%11,%12,%13,%14,%15,%16,%17,%18,%19,%20,%21,%22,%23,%24,%25,%26,%27,%28,%29,%30,%31,%32,%33,%34,%35,%36,%37,%38,%39,%40,%41,%42,%43,%44,%45,%46,%47}, {%48,%49,%50,%51}, %52, p, 1, 1, 0;\n}\n"
   : "+f"(d[0]),"+f"(d[1]),"+f"(d[2]),"+f"(d[3]),"+f"(d[4]),"+f"(d[5]),"+f"(d[6]),"+f"(d[7]),"+f"(d[8]),"+f"(d[9]),"+f"(d[10]),"+f"(d[11]),"+f"(d[12]),"+f"(d[13]),"+f"(d[14]),"+f"(d[15]),"+f"(d[16]),"+f"(d[17]),"+f"(d[18]),"+f"(d[19]),"+f"(d[20]),"+f"(d[21]),"+f"(d[22]),"+f"(d[23]),"+f"(d[24]),"+f"(d[25]),"+f"(d[26]),"+f"(d[27]),"+f"(d[28]),"+f"(d[29]),"+f"(d[30]),"+f"(d[31]),"+f"(d[32]),"+f"(d[33]),"+f"(d[34]),"+f"(d[35]),"+f"(d[36]),"+f"(d[37]),"+f"(d[38]),"+f"(d[39]),"+f"(d[40]),"+f"(d[41]),"+f"(d[42]),"+f"(d[43]),"+f"(d[44]),"+f"(d[45]),"+f"(d[46]),"+f"(d[47])
   : "r"(a[0]), "r"(a[1]), "r"(a[2]), "r"(a[3]), "l"(db), "r"(sd));
}
template<> __device__ __forceinline__ void wgmma_rs<88,0>(float* d, const uint32_t* a, uint64_t db, int sd) {
  asm volatile("{\n.reg .pred p;\nsetp.ne.b32 p, %49, 0;\nwgmma.mma_async.sync.aligned.m64n88k16.f32.bf16.bf16 {%0,%1,%2,%3,%4,%5,%6,%7,%8,%9,%10,%11,%12,%13,%14,%15,%16,%17,%18,%19,%20,%21,%22,%23,%24,%25,%26,%27,%28,%29,%30,%31,%32,%33,%34,%35,%36,%37,%38,%39,%40,%41,%42,%43}, {%44,%45,%46,%47}, %48, p, 1, 1, 0;\n}\n"
   : "+f"(d[0]),"+f"(d[1]),"+f"(d[2]),"+f"(d[3]),"+f"(d[4]),"+f"(d[5]),"+f"(d[6]),"+f"(d[7]),"+f"(d[8]),"+f"(d[9]),"+f"(d[10]),"+f"(d[11]),"+f"(d[12]),"+f"(d[13]),"+f"(d[14]),"+f"(d[15]),"+f"(d[16]),"+f"(d[17]),"+f"(d[18]),"+f"(d[19]),"+f"(d[20]),"+f"(d[21]),"+f"(d[22]),"+f"(d[23]),"+f"(d[24]),"+f"(d[25]),"+f"(d[26]),"+f"(d[27]),"+f"(d[28]),"+f"(d[29]),"+f"(d[30]),"+f"(d[31]),"+f"(d[32]),"+f"(d[33]),"+f"(d[34]),"+f"(d[35]),"+f"(d[36]),"+f"(d[37]),"+f"(d[38]),"+f"(d[39]),"+f"(d[40]),"+f"(d[41]),"+f"(d[42]),"+f"(d[43])
   : "r"(a[0]), "r"(a[1]), "r"(a[2]), "r"(a[3]), "l"(db), "r"(sd));
}
template<> __device__ __forceinline__ void wgmma_rs<80,0>(float* d, const uint32_t* a, uint64_t db, int sd) {
  asm volatile("{\n.reg .pred p;\nsetp.ne.b32 p, %45, 0;\nwgmma.mma_async.sync.aligned.m64n80k16.f32.bf16.bf16 {%0,%1,%2,%3,%4,%5,%6,%7,%8,%9,%10,%11,%12,%13,%14,%15,%16,%17,%18,%19,%20,%21,%22,%23,%24,%25,%26,%27,%28,%29,%30,%31,%32,%33,%34,%35,%36,%37,%38,%39}, {%40,%41,%42,%43}, %44, p, 1, 1, 0;\n}\n"
   : "+f"(d[0]),"+f"(d[1]),"+f"(d[2]),"+f"(d[3]),"+f"(d[4]),"+f"(d[5]),"+f"(d[6]),"+f"(d[7]),"+f"(d[8]),"+f"(d[9]),"+f"(d[10]),"+f"(d[11]),"+f"(d[12]),"+f"(d[13]),"+f"(d[14]),"+f"(d[15]),"+f"(d[16]),"+f"(d[17]),"+f"(d[18]),"+f"(d[19]),"+f"(d[20]),"+f"(d[21]),"+f"(d[22]),"+f"(d[23]),"+f"(d[24]),"+f"(d[25]),"+f"(d[26]),"+f"(d[27]),"+f"(d[28]),"+f"(d[29]),"+f"(d[30]),"+f"(d[31]),"+f"(d[32]),"+f"(d[33]),"+f"(d[34]),"+f"(d[35]),"+f"(d[36]),"+f"(d[37]),"+f"(d[38]),"+f"(d[39])
   : "r"(a[0]), "r"(a[1]), "r"(a[2]), "r"(a[3]), "l"(db), "r"(sd));
}
template<> __device__ __forceinline__ void wgmma_rs<72,0>(float* d, const uint32_t* a, uint64_t db, int sd) {
  asm volatile("{\n.reg .pred p;\nsetp.ne.b32 p, %41, 0;\nwgmma.mma_async.sync.aligned.m64n72k16.f32.bf16.bf16 {%0,%1,%2,%3,%4,%5,%6,%7,%8,%9,%10,%11,%12,%13,%14,%15,%16,%17,%18,%19,%20,%21,%22,%23,%24,%25,%26,%27,%28,%29,%30,%31,%32,%33,%34,%35}, {%36,%37,%38,%39}, %40, p, 1, 1, 0;\n}\n"
   : "+f"(d[0]),"+f"(d[1]),"+f"(d[2]),"+f"(d[3]),"+f"(d[4]),"+f"(d[5]),"+f"(d[6]),"+f"(d[7]),"+f"(d[8]),"+f"(d[9]),"+f"(d[10]),"+f"(d[11]),"+f"(d[12]),"+f"(d[13]),"+f"(d[14]),"+f"(d[15]),"+f"(d[16]),"+f"(d[17]),"+f"(d[18]),"+f"(d[19]),"+f"(d[20]),"+f"(d[21]),"+f"(d[22]),"+f"(d[23]),"+f"(d[24]),"+f"(d[25]),"+f"(d[26]),"+f"(d[27]),"+f"(d[28]),"+f"(d[29]),"+f"(d[30]),"+f"(d[31]),"+f"(d[32]),"+f"(d[33]),"+f"(d[34]),"+f"(d[35])
   : "r"(a[0]), "r"(a[1]), "r"(a[2]), "r"(a[3]), "l"(db), "r"(sd));
}
template<> __device__ __forceinline__ void wgmma_rs<64,0>(float* d, const uint32_t* a, uint64_t db, int sd) {
  asm volatile("{\n.reg .pred p;\nsetp.ne.b32 p, %37, 0;\nwgmma.mma_async.sync.aligned.m64n64k16.f32.bf16.bf16 {%0,%1,%2,%3,%4,%5,%6,%7,%8,%9,%10,%11,%12,%13,%14,%15,%16,%17,%18,%19,%20,%21,%22,%23,%24,%25,%26,%27,%28,%29,%30,%31}, {%32,%33,%34,%35}, %36, p, 1, 1, 0;\n}\n"
   : "+f"(d[0]),"+f"(d[1]),"+f"(d[2]),"+f"(d[3]),"+f"(d[4]),"+f"(d[5]),"+f"(d[6]),"+f"(d[7]),"+f"(d[8]),"+f"(d[9]),"+f"(d[10]),"+f"(d[11]),"+f"(d[12]),"+f"(d[13]),"+f"(d[14]),"+f"(d[15]),"+f"(d[16]),"+f"(d[17]),"+f"(d[18]),"+f"(d[19]),"+f"(d[20]),"+f"(d[21]),"+f"(d[22]),"+f"(d[23]),"+f"(d[24]),"+f"(d[25]),"+f"(d[26]),"+f"(d[27]),"+f"(d[28]),"+f"(d[29]),"+f"(d[30]),"+f"(d[31])
   : "r"(a[0]), "r"(a[1]), "r"(a[2]), "r"(a[3]), "l"(db), "r"(sd));
}
template<> __device__ __forceinline__ void wgmma_ss<64,0,1>(float* d, uint64_t da, uint64_t db, int sd) {
  asm volatile("{\n.reg .pred p;\nsetp.ne.b32 p, %34, 0;\nwgmma.mma_async.sync.aligned.m64n64k16.f32.bf16.bf16 {%0,%1,%2,%3,%4,%5,%6,%7,%8,%9,%10,%11,%12,%13,%14,%15,%16,%17,%18,%19,%20,%21,%22,%23,%24,%25,%26,%27,%28,%29,%30,%31}, %32, %33, p, 1, 1, 0, 1;\n}\n"
   : "+f"(d[0]),"+f"(d[1]),"+f"(d[2]),"+f"(d[3]),"+f"(d[4]),"+f"(d[5]),"+f"(d[6]),"+f"(d[7]),"+f"(d[8]),"+f"(d[9]),"+f"(d[10]),"+f"(d[11]),"+f"(d[12]),"+f"(d[13]),"+f"(d[14]),"+f"(d[15]),"+f"(d[16]),"+f"(d[17]),"+f"(d[18]),"+f"(d[19]),"+f"(d[20]),"+f"(d[21]),"+f"(d[22]),"+f"(d[23]),"+f"(d[24]),"+f"(d[25]),"+f"(d[26]),"+f"(d[27]),"+f"(d[28]),"+f"(d[29]),"+f"(d[30]),"+f"(d[31])
   : "l"(da), "l"(db), "r"(sd));
}
template<> __device__ __forceinline__ void wgmma_ss<64,1,1>(float* d, uint64_t da, uint64_t db, int sd) {
  asm volatile("{\n.reg .pred p;\nsetp.ne.b32 p, %34, 0;\nwgmma.mma_async.sync.aligned.m64n64k16.f32.bf16.bf16 {%0,%1,%2,%3,%4,%5,%6,%7,%8,%9,%10,%11,%12,%13,%14,%15,%16,%17,%18,%19,%20,%21,%22,%23,%24,%25,%26,%27,%28,%29,%30,%31}, %32, %33, p, 1, 1, 1, 1;\n}\n"
   : "+f"(d[0]),"+f"(d[1]),"+f"(d[2]),"+f"(d[3]),"+f"(d[4]),"+f"(d[5]),"+f"(d[6]),"+f"(d[7]),"+f"(d[8]),"+f"(d[9]),"+f"(d[10]),"+f"(d[11]),"+f"(d[12]),"+f"(d[13]),"+f"(d[14]),"+f"(d[15]),"+f"(d[16]),"+f"(d[17]),"+f"(d[18]),"+f"(d[19]),"+f"(d[20]),"+f"(d[21]),"+f"(d[22]),"+f"(d[23]),"+f"(d[24]),"+f"(d[25]),"+f"(d[26]),"+f"(d[27]),"+f"(d[28]),"+f"(d[29]),"+f"(d[30]),"+f"(d[31])
   : "l"(da), "l"(db), "r"(sd));
}
template<> __device__ __forceinline__ void wgmma_ss<192,0,1>(float* d, uint64_t da, uint64_t db, int sd) {
  asm volatile("{\n.reg .pred p;\nsetp.ne.b32 p, %98, 0;\nwgmma.mma_async.sync.aligned.m64n192k16.f32.bf16.bf16 {%0,%1,%2,%3,%4,%5,%6,%7,%8,%9,%10,%11,%12,%13,%14,%15,%16,%17,%18,%19,%20,%21,%22,%23,%24,%25,%26,%27,%28,%29,%30,%31,%32,%33,%34,%35,%36,%37,%38,%39,%40,%41,%42,%43,%44,%45,%46,%47,%48,%49,%50,%51,%52,%53,%54,%55,%56,%57,%58,%59,%60,%61,%62,%63,%64,%65,%66,%67,%68,%69,%70,%71,%72,%73,%74,%75,%76,%77,%78,%79,%80,%81,%82,%83,%84,%85,%86,%87,%88,%89,%90,%91,%92,%93,%94,%95}, %96, %97, p, 1, 1, 0, 1;\n}\n"
   : "+f"(d[0]),"+f"(d[1]),"+f"(d[2]),"+f"(d[3]),"+f"(d[4]),"+f"(d[5]),"+f"(d[6]),"+f"(d[7]),"+f"(d[8]),"+f"(d[9]),"+f"(d[10]),"+f"(d[11]),"+f"(d[12]),"+f"(d[13]),"+f"(d[14]),"+f"(d[15]),"+f"(d[16]),"+f"(d[17]),"+f"(d[18]),"+f"(d[19]),"+f"(d[20]),"+f"(d[21]),"+f"(d[22]),"+f"(d[23]),"+f"(d[24]),"+f"(d[25]),"+f"(d[26]),"+f"(d[27]),"+f"(d[28]),"+f"(d[29]),"+f"(d[30]),"+f"(d[31]),"+f"(d[32]),"+f"(d[33]),"+f"(d[34]),"+f"(d[35]),"+f"(d[36]),"+f"(d[37]),"+f"(d[38]),"+f"(d[39]),"+f"(d[40]),"+f"(d[41]),"+f"(d[42]),"+f"(d[43]),"+f"(d[44]),"+f"(d[45]),"+f"(d[46]),"+f"(d[47]),"+f"(d[48]),"+f"(d[49]),"+f"(d[50]),"+f"(d[51]),"+f"(d[52]),"+f"(d[53]),"+f"(d[54]),"+f"(d[55]),"+f"(d[56]),"+f"(d[57]),"+f"(d[58]),"+f"(d[59]),"+f"(d[60]),"+f"(d[61]),"+f"(d[62]),"+f"(d[63]),"+f"(d[64]),"+f"(d[65]),"+f"(d[66]),"+f"(d[67]),"+f"(d[68]),"+f"(d[69]),"+f"(d[70]),"+f"(d[71]),"+f"(d[72]),"+f"(d[73]),"+f"(d[74]),"+f"(d[75]),"+f"(d[76]),"+f"(d[77]),"+f"(d[78]),"+f"(d[79]),"+f"(d[80]),"+f"(d[81]),"+f"(d[82]),"+f"(d[83]),"+f"(d[84]),"+f"(d[85]),"+f"(d[86]),"+f"(d[87]),"+f"(d[88]),"+f"(d[89]),"+f"(d[90]),"+f"(d[91]),"+f"(d[92]),"+f"(d[93]),"+f"(d[94]),"+f"(d[95])
   : "l"(da), "l"(db), "r"(sd));
}
template<> __device__ __forceinline__ void wgmma_ss<192,1,1>(float* d, uint64_t da, uint64_t db, int sd) {
  asm volatile("{\n.reg .pred p;\nsetp.ne.b32 p, %98, 0;\nwgmma.mma_async.sync.aligned.m64n192k16.f32.bf16.bf16 {%0,%1,%2,%3,%4,%5,%6,%7,%8,%9,%10,%11,%12,%13,%14,%15,%16,%17,%18,%19,%20,%21,%22,%23,%24,%25,%26,%27,%28,%29,%30,%31,%32,%33,%34,%35,%36,%37,%38,%39,%40,%41,%42,%43,%44,%45,%46,%47,%48,%49,%50,%51,%52,%53,%54,%55,%56,%57,%58,%59,%60,%61,%62,%63,%64,%65,%66,%67,%68,%69,%70,%71,%72,%73,%74,%75,%76,%77,%78,%79,%80,%81,%82,%83,%84,%85,%86,%87,%88,%89,%90,%91,%92,%93,%94,%95}, %96, %97, p, 1, 1, 1, 1;\n}\n"
   : "+f"(d[0]),"+f"(d[1]),"+f"(d[2]),"+f"(d[3]),"+f"(d[4]),"+f"(d[5]),"+f"(d[6]),"+f"(d[7]),"+f"(d[8]),"+f"(d[9]),"+f"(d[10]),"+f"(d[11]),"+f"(d[12]),"+f"(d[13]),"+f"(d[14]),"+f"(d[15]),"+f"(d[16]),"+f"(d[17]),"+f"(d[18]),"+f"(d[19]),"+f"(d[20]),"+f"(d[21]),"+f"(d[22]),"+f"(d[23]),"+f"(d[24]),"+f"(d[25]),"+f"(d[26]),"+f"(d[27]),"+f"(d[28]),"+f"(d[29]),"+f"(d[30]),"+f"(d[31]),"+f"(d[32]),"+f"(d[33]),"+f"(d[34]),"+f"(d[35]),"+f"(d[36]),"+f"(d[37]),"+f"(d[38]),"+f"(d[39]),"+f"(d[40]),"+f"(d[41]),"+f"(d[42]),"+f"(d[43]),"+f"(d[44]),"+f"(d[45]),"+f"(d[46]),"+f"(d[47]),"+f"(d[48]),"+f"(d[49]),"+f"(d[50]),"+f"(d[51]),"+f"(d[52]),"+f"(d[53]),"+f"(d[54]),"+f"(d[55]),"+f"(d[56]),"+f"(d[57]),"+f"(d[58]),"+f"(d[59]),"+f"(d[60]),"+f"(d[61]),"+f"(d[62]),"+f"(d[63]),"+f"(d[64]),"+f"(d[65]),"+f"(d[66]),"+f"(d[67]),"+f"(d[68]),"+f"(d[69]),"+f"(d[70]),"+f"(d[71]),"+f"(d[72]),"+f"(d[73]),"+f"(d[74]),"+f"(d[75]),"+f"(d[76]),"+f"(d[77]),"+f"(d[78]),"+f"(d[79]),"+f"(d[80]),"+f"(d[81]),"+f"(d[82]),"+f"(d[83]),"+f"(d[84]),"+f"(d[85]),"+f"(d[86]),"+f"(d[87]),"+f"(d[88]),"+f"(d[89]),"+f"(d[90]),"+f"(d[91]),"+f"(d[92]),"+f"(d[93]),"+f"(d[94]),"+f"(d[95])
   : "l"(da), "l"(db), "r"(sd));
}

__device__ __forceinline__ void stats_publish(uint32_t sb, int layer, int rb, int hg, int ht, uint32_t tag) {
  const int lane = ht & 31, w = ht >> 5, g = lane >> 2, t = lane & 3, ks = hg & 3;
  uint32_t xa;
  if (layer == 0) {
    const int row = 16 * w + (lane & 15), kc = 2 * ks + (lane >> 4);
    xa = row * 128 + ((kc ^ (row & 7)) << 4);
  } else {
    const int k = 16 * ks + (lane & 7) + 8 * (lane >> 4), pc = 2 * w + ((lane >> 3) & 1);
    xa = k * 128 + ((pc ^ (k & 7)) << 4);
  }
  float s[4] = {0.f, 0.f, 0.f, 0.f}, q[4] = {0.f, 0.f, 0.f, 0.f};
#pragma unroll 1
  for (int c = hg >> 2; c < 8; c += 2) {
    mbar_wait(sb + SM_BAR + 8 * (B_XF + c), layer);
    if (c >= 6) ATS(48, 256);
    if (c < 2) ATS(51, 256);
    uint32_t A[2][4];
#pragma unroll
    for (int h = 0; h < 2; h++) {
      if (layer == 0) ldsm4(A[h], sb + SM_X + c * 16384 + h * 8192 + xa);
      else ldsm4t(A[h], sb + SM_X + c * 16384 + h * 8192 + xa);
    }
#pragma unroll
    for (int r = 0; r < 4; r++)
#pragma unroll
      for (int i = 0; i < 2; i++) {
        const uint32_t v = A[r >> 1][2 * i + (r & 1)];
        const float a = bf_lo(v), b = bf_hi(v);
        s[r] += a + b; q[r] = fmaf(a, a, q[r]); q[r] = fmaf(b, b, q[r]);
      }
  }
#pragma unroll
  for (int r = 0; r < 2; r++) {
    s[r] = ((t & 2) ? s[r + 2] : s[r]) + __shfl_xor_sync(~0u, (t & 2) ? s[r] : s[r + 2], 2);
    q[r] = ((t & 2) ? q[r + 2] : q[r]) + __shfl_xor_sync(~0u, (t & 2) ? q[r] : q[r + 2], 2);
  }
  s[0] = ((t & 1) ? s[1] : s[0]) + __shfl_xor_sync(~0u, (t & 1) ? s[0] : s[1], 1);
  q[0] = ((t & 1) ? q[1] : q[0]) + __shfl_xor_sync(~0u, (t & 1) ? q[0] : q[1], 1);
  st_part(&g_part[(rb * 8 + hg) * 128 + 64 * (t >> 1) + 16 * w + 8 * (t & 1) + g], s[0], q[0], tag);
  ATS(49, 256);
}
__device__ __forceinline__ void stats_gather(uint32_t sb, int rb, int ht, uint32_t tag) {
  const uint2* src = &g_part[rb * 8 * 128 + ht];
  uint2 v[8];
  bool ok;
  int it = 0;
  do {
    ok = true;
#pragma unroll
    for (int i = 0; i < 8; i++) v[i] = ld_part(src + i * 128);
#pragma unroll
    for (int i = 0; i < 8; i++) ok = ok && (v[i].y & 7u) == tag;
    if (++it > (1 << 22)) __trap();
  } while (!__all_sync(~0u, ok));
  float s = 0.f, q = 0.f;
#pragma unroll
  for (int i = 0; i < 8; i++) { s += __uint_as_float(v[i].x); q += __uint_as_float(v[i].y); }
  const float mean = s * (1.f / DM);
  const float rstd = rsqrt_approx(fmaxf(q * (1.f / DM) - mean * mean, 0.f) + 1e-5f);
  asm volatile("st.shared.v2.f32 [%0], {%1,%2};" ::"r"(sb + SM_ST + ht * 8), "f"(mean), "f"(rstd) : "memory");
  __syncwarp();
  if (elect_one()) mbar_arrive(sb + SM_BAR + 8 * B_STF);
}
__device__ __forceinline__ void halo_receive(uint32_t sb, int layer, int rb, int hg, int ht) {
  const int lane = ht & 31, h = ht >> 5;
  uint4 kv = make_uint4(0, 0, 0, 0);
  mbar_wait(sb + SM_BAR + 8 * B_SD, layer);
  if (rb & 7) {
    const uint32_t tag = 2 * lds32(sb + SM_EP) + layer + 1;
    const uint4* src = &g_halo[((rb - 1) * 8 + hg) * 192 + h * 48];
    if (layer == 0) delay<D_HALO>(); else delay<D_HALO1>();
    uint4 a;
    uint2 b;
    int it = 0;
    do {
      a = ld_tagged(src + lane); b = ld_part((const uint2*)(src + 32) + lane);
      if (++it > (1 << 22)) __trap();
    } while (!__all_sync(~0u, a.w == tag && b.y == tag));
    kv = make_uint4(a.x, a.y, movm_t(a.z), movm_t(b.x));
  }
  sts128(sb + SM_KVX + h * 512 + lane * 16, kv);
  ATS(61, 256);
  bar_arrive(7, 160);
  if (elect_one()) mbar_arrive(sb + SM_BAR + 8 * B_HF);
}

template <bool TR>
__device__ __forceinline__ void gemm_section(float* acc, float2* cs, uint32_t sb, int layer, int wg, int w, int lane) {
  const uint32_t bar = sb + SM_BAR;
  const bool leader = (w == 0) && (lane == 0);
  auto issue = [&](int c, int slot) {
    mbar_wait(bar + 8 * (B_XF + c), layer);
    mbar_wait(bar + 8 * (B_KVF + c), layer);
    const uint64_t da = mkdesc(sb + SM_X + c * 16384 + wg * 8192, TR ? 8192 : 16, 1024, 1);
    const uint64_t db = mkdesc(sb + SM_W + slot * 24576, 8192, 1024, 1);
    wg_fence();
#pragma unroll
    for (int ks = 0; ks < 4; ks++) wgmma_ss<192, TR ? 1 : 0, 1>(acc, da + (TR ? ks * 128 : ks * 2), db + ks * 128, (c | ks) != 0);
    wg_commit();
  };
  auto step = [&](int c, int slot) {
    issue(c, slot);
    wg_wait<1>();
    if (leader) mbar_arrive(bar + 8 * (B_KVE + c - 1));
  };
  issue(0, 0);
  if (threadIdx.x == 0) TS(2 + layer * 20 + 0);
  if (threadIdx.x == 128 && layer == 1) TS(60);
  step(1, 1); step(2, 2); step(3, 0); step(4, 1);
  auto ld_cs = [&](int j0) {
#pragma unroll
    for (int j = j0; j < j0 + 8; j++) cs[j] = lds64f(sb + SM_CS + 4 * (8 * j + 2 * (lane & 3)));
  };
  if (TR) ld_cs(8);
  step(5, 2);
  if (!TR && !CS_LATE0) { mbar_wait(bar + 8 * B_CSF, 0); ld_cs(8); }
  if (TR || !CS_LATE0) ld_cs(16);
  if (wg == 0) bar_sync(5, 256);
  issue(6, 0);
  issue(7, 1);
  if (wg == 1) bar_arrive(5, 256);
  if (!TR && CS_LATE0) { mbar_wait(bar + 8 * B_CSF, 0); ld_cs(8); ld_cs(16); }
}

__device__ __forceinline__ void attn_phase(const Params& p, uint32_t sb, int layer, int rb, int hg, int wg, int w) {
  const int lane = opaque_tid() & 31;
  const int g = lane >> 2, t = lane & 3;
  const uint32_t bar = sb + SM_BAR;
  const int row0 = 64 * wg + 16 * w;
  const bool leader = (w == 0) && (lane == 0);
  float acc[96];
  float2 cs[24];
  if (layer) gemm_section<true>(acc, cs, sb, layer, wg, w, lane);
  else gemm_section<false>(acc, cs, sb, layer, wg, w, lane);
  ATS(41, 224);
  mbar_wait(bar + 8 * B_STF, layer);
  const uint32_t tag = 2 * lds32(sb + SM_EP) + layer + 1;
  const float2 st0 = lds64f(sb + SM_ST + (row0 + g) * 8), st1 = lds64f(sb + SM_ST + (row0 + g + 8) * 8);
  const float mean0 = st0.x, rstd0 = st0.y, mean1 = st1.x, rstd1 = st1.y;
  wg_wait<0>();
  if (threadIdx.x == 0) TS(2 + layer * 20 + 1);
  ATS(39, 224);
  if (leader) mbar_arrive(bar + 8 * B_QDONE);

  uint32_t fp[4][4], fl[4][4], fh[4][4], qa[4][4];
  const int cw = 4 * wg + w;
  {
    const float nm0 = -mean0 * rstd0, nm1 = -mean1 * rstd1;
    const uint32_t kvx = sb + SM_KVX + cw * 2048 + lane * 16;
#pragma unroll
    for (int h = 0; h < 4; h++)
#pragma unroll
      for (int k = 0; k < 4; k++) {
        const int j = 8 + (k >> 1) * 8 + 2 * h + (k & 1);
        fh[h][k] = packbf(fmaf(acc[4 * j + 2], rstd1, nm1 * cs[j].x), fmaf(acc[4 * j + 3], rstd1, nm1 * cs[j].y));
      }
    if (cw == 7) {
      uint4* halo = &g_halo[(rb * 8 + hg) * 192];
#pragma unroll
      for (int h = 0; h < 4; h++) {
        st_tagged3(halo + h * 48 + lane, fh[h][0], fh[h][1], fh[h][2], tag);
        asm volatile("st.relaxed.gpu.global.v2.u32 [%0], {%1,%2};" ::"l"((uint2*)(halo + h * 48 + 32) + lane), "r"(fh[h][3]), "r"(tag) : "memory");
      }
      if (elect_one()) mbar_arrive(bar + 8 * B_SD);
      if (layer == TLAYER && threadIdx.x == 224) TS(47);
    }
#pragma unroll
    for (int h = 0; h < 4; h++) { fh[h][2] = movm_t(fh[h][2]); fh[h][3] = movm_t(fh[h][3]); }
    if (cw != 7) {
#pragma unroll
      for (int h = 0; h < 4; h++) sts128(kvx + 2048 + h * 512, make_uint4(fh[h][0], fh[h][1], fh[h][2], fh[h][3]));
      bar_arrive(8 + cw, 64);
    }
    if (layer == TLAYER && threadIdx.x == 0) TS(45);
#pragma unroll
    for (int j = 0; j < 8; j++) cs[j] = lds64f(sb + SM_CS + 4 * (8 * j + 2 * t));
#pragma unroll
    for (int h = 0; h < 4; h++)
#pragma unroll
      for (int k = 0; k < 4; k++) {
        const int j = 8 + (k >> 1) * 8 + 2 * h + (k & 1);
        fl[h][k] = packbf(fmaf(acc[4 * j], rstd0, nm0 * cs[j].x), fmaf(acc[4 * j + 1], rstd0, nm0 * cs[j].y));
        if (k >= 2) fl[h][k] = movm_t(fl[h][k]);
      }
#pragma unroll
    for (int h = 0; h < 4; h++) {
#pragma unroll
      for (int dh = 0; dh < 2; dh++) {
        const int j = 2 * h + dh;
        const float2 c2 = cs[j];
        qa[h][2 * dh] = packbf(fmaf(-mean0, c2.x, acc[4 * j + 0]), fmaf(-mean0, c2.y, acc[4 * j + 1]));
        qa[h][2 * dh + 1] = packbf(fmaf(-mean1, c2.x, acc[4 * j + 2]), fmaf(-mean1, c2.y, acc[4 * j + 3]));
      }
    }
    if (threadIdx.x == 0) TS(2 + layer * 20 + 2);
    bar_sync(7 + cw, cw == 0 ? 160 : 64);
#pragma unroll
    for (int h = 0; h < 4; h++) {
      const uint4 v = lds128(kvx + h * 512);
      fp[h][0] = v.x; fp[h][1] = v.y; fp[h][2] = v.z; fp[h][3] = v.w;
    }
    if (threadIdx.x == 0) TS(2 + layer * 20 + 4);
  }

  const bool u0 = 2 * t > g, u1 = 2 * t + 1 > g;
  const uint32_t mU = (u0 ? 0x0000ffffu : 0u) | (u1 ? 0xffff0000u : 0u);
  const float cl2 = 0.25f * 1.4426950408889634f;
  const float sc0 = rstd0 * cl2, sc1 = rstd1 * cl2;
  const float cneg = ((rb & 7) == 0 && cw == 0) ? -INFINITY : 0.f;
  float v[4][4];
#pragma unroll
  for (int h = 0; h < 4; h++) {
    float T0[4] = {cneg, cneg, cneg, cneg}, T1[4] = {0.f, 0.f, 0.f, 0.f}, T2[4] = {0.f, 0.f, 0.f, 0.f};
    mma_bf16(T1, qa[h], fl[h][0], fl[h][1]);
    mma_bf16(T2, qa[h], fh[h][0], fh[h][1]);
    mma_bf16(T0, qa[h], fp[h][0], fp[h][1]);
    v[h][0] = u0 ? T0[0] : T1[0]; v[h][1] = u1 ? T0[1] : T1[1];
    v[h][2] = u0 ? T1[2] : T2[2]; v[h][3] = u1 ? T1[3] : T2[3];
  }
  float m0[4], m1[4];
#pragma unroll
  for (int h = 0; h < 4; h++) { m0[h] = fmaxf(v[h][0], v[h][1]); m1[h] = fmaxf(v[h][2], v[h][3]); }
#pragma unroll
  for (int o = 1; o <= 2; o <<= 1) {
#pragma unroll
    for (int h = 0; h < 4; h++) {
      m0[h] = fmaxf(m0[h], __shfl_xor_sync(~0u, m0[h], o));
      m1[h] = fmaxf(m1[h], __shfl_xor_sync(~0u, m1[h], o));
    }
  }
  float O0[4][4], O1[4][4], Z[4][4];
#pragma unroll
  for (int h = 0; h < 4; h++) {
    const float mm0 = -m0[h] * sc0, mm1 = -m1[h] * sc1;
    const uint32_t P0 = packbf(ex2(fmaf(v[h][0], sc0, mm0)), ex2(fmaf(v[h][1], sc0, mm0)));
    const uint32_t P1 = packbf(ex2(fmaf(v[h][2], sc1, mm1)), ex2(fmaf(v[h][3], sc1, mm1)));
#pragma unroll
    for (int k = 0; k < 4; k++) O0[h][k] = O1[h][k] = Z[h][k] = 0.f;
    mma_bf16_k8(Z[h], P0, P1, 0x3f803f80u);
    mma_bf16_k8(O0[h], P0 & ~mU, P1 & mU, fl[h][2]); mma_bf16_k8(O1[h], P0 & ~mU, P1 & mU, fl[h][3]);
    mma_bf16_k8(O0[h], P0 & mU, 0u, fp[h][2]); mma_bf16_k8(O1[h], P0 & mU, 0u, fp[h][3]);
    mma_bf16_k8(O0[h], 0u, P1 & ~mU, fh[h][2]); mma_bf16_k8(O1[h], 0u, P1 & ~mU, fh[h][3]);
  }
  const uint32_t ob = sb + SM_OST + wg * 8192;
  const int o_row = 16 * w + (lane & 7) + 8 * ((lane >> 3) & 1);
#pragma unroll
  for (int h = 0; h < 4; h++) {
    const float i0 = rcp_approx(Z[h][0]), i1 = rcp_approx(Z[h][2]);
    const int ch = 2 * h + (lane >> 4);
    stsm4(ob + o_row * 128 + ((ch ^ (o_row & 7)) << 4), packbf(O0[h][0] * i0, O0[h][1] * i0), packbf(O0[h][2] * i1, O0[h][3] * i1),
          packbf(O1[h][0] * i0, O1[h][1] * i0), packbf(O1[h][2] * i1, O1[h][3] * i1));
  }
  if (threadIdx.x == 0) TS(2 + layer * 20 + 5);
  ATS(57, 128); ATS(20, 96);
  fence_writer();
  bar_sync(2 + wg, 128);
  if (w == 0 && elect_one()) {
    fence_reader();
    tma_st(&p.mapO, hg * 64, rb * 128 + wg * 64, ob);
    bulk_commit();
    mbar_arrive(bar + 8 * B_AD);
    bulk_wait_all();
    red_relaxed(&g_cnt[(C_O + rb) * 32]);
    mbar_arrive(bar + 8 * B_OST);
    if (threadIdx.x == 0) TS(2 + layer * 20 + 6);
  }
}

__device__ __forceinline__ void proj_phase(const Params& p, uint32_t sb, int layer, int rb, int q, int wg, int w) {
  const int lane = opaque_tid() & 31;
  const bool TR = layer != 0;
  const int t = lane & 3;
  const uint32_t bar = sb + SM_BAR;
  const uint32_t rbx = sb + SM_R + wg * 8192;
  uint32_t res[16];
  mbar_wait(bar + 8 * B_RF, layer);
  if (threadIdx.x == 0) TS(2 + layer * 20 + 7);
  if (!TR) {
#pragma unroll
    for (int j = 0; j < 8; j += 2) {
      const int mi = lane >> 3;
      const int row = 16 * w + (lane & 7) + 8 * (mi & 1), ch = j + (mi >> 1);
      ldsm4(&res[2 * j], rbx + row * 128 + ((ch ^ (row & 7)) << 4));
    }
  } else {
#pragma unroll
    for (int j = 0; j < 8; j += 2) {
      const int mi = lane >> 3;
      const int line = 8 * (j + (mi >> 1)) + (lane & 7), pc = 2 * w + (mi & 1);
      ldsm4t(&res[2 * j], rbx + line * 128 + ((pc ^ (line & 7)) << 4));
    }
  }
  bar_sync(2 + wg, 128);
  float acc[32];
#pragma unroll
  for (int i = 0; i < 16; i++) {
    asm volatile("shl.b32 %0, %1, 16;" : "=f"(acc[2 * i]) : "r"(res[i]));
    asm volatile("and.b32 %0, %1, 0xffff0000;" : "=f"(acc[2 * i + 1]) : "r"(res[i]));
  }
  const uint32_t tag = part_tag(lds32(sb + SM_EP), 2 * layer + 1);
#pragma unroll 1
  for (int c = 0; c < 8; c++) {
    if ((c & 1) == 0) mbar_wait(bar + 8 * (B_WOF + (c >> 1)), layer);
    mbar_wait(bar + 8 * (B_OF + c), layer);
    if (c == 0 && threadIdx.x == 0) TS(2 + layer * 20 + 8);
    const uint64_t da = mkdesc(sb + sm_o(c) + wg * 8192, 16, 1024, 1);
    const uint64_t db = mkdesc(sb + SM_WO + c * 8192, 8192, 1024, 1);
    wg_fence();
#pragma unroll
    for (int ks = 0; ks < 4; ks++) wgmma_ss<64, 0, 1>(acc, da + ks * 2, db + ks * 128, 1);
    wg_commit();
  }
  wg_wait<0>();
#pragma unroll
  for (int i = 0; i < 32; i++) asm volatile("" : "+f"(acc[i]) :: "memory");
  if (threadIdx.x == 0) TS(2 + layer * 20 + 9);
  if (lane == 0 && w == 0) mbar_arrive(bar + 8 * B_PDONE);
  {
    float s[4], qq[4];
#pragma unroll
    for (int k = 0; k < 4; k++) { s[k] = acc[k]; qq[k] = acc[k] * acc[k]; }
#pragma unroll
    for (int j = 1; j < 8; j++)
#pragma unroll
      for (int k = 0; k < 4; k++) { s[k] += acc[4 * j + k]; qq[k] = fmaf(acc[4 * j + k], acc[4 * j + k], qq[k]); }
    const float s0 = s[0] + s[1], s1 = s[2] + s[3], q0 = qq[0] + qq[1], q1 = qq[2] + qq[3];
    float sr = ((t & 1) ? s1 : s0) + __shfl_xor_sync(~0u, (t & 1) ? s0 : s1, 1);
    float qr = ((t & 1) ? q1 : q0) + __shfl_xor_sync(~0u, (t & 1) ? q0 : q1, 1);
    sr += __shfl_xor_sync(~0u, sr, 2);
    qr += __shfl_xor_sync(~0u, qr, 2);
    if (t < 2) st_part(&g_part[(rb * 8 + q) * 128 + 64 * wg + 16 * w + (lane >> 2) + 8 * t], sr, qr, tag);
    __syncwarp();
    if (elect_one()) mbar_arrive(bar + 8 * B_PS);
  }
#pragma unroll
  for (int j = 0; j < 8; j += 2) {
    const int mi = lane >> 3;
    const int line = 8 * (j + (mi >> 1)) + (lane & 7), pc = 2 * w + (mi & 1);
    stsm4t(rbx + line * 128 + ((pc ^ (line & 7)) << 4), packbf(acc[4 * j], acc[4 * j + 1]), packbf(acc[4 * j + 2], acc[4 * j + 3]),
           packbf(acc[4 * j + 4], acc[4 * j + 5]), packbf(acc[4 * j + 6], acc[4 * j + 7]));
  }
  fence_writer();
  bar_sync(2 + wg, 128);
  if (w == 0 && elect_one()) {
    fence_reader();
    mbar_wait(bar + 8 * B_ZF, layer);
    fence_async_global();
    tma_st(&p.mapXT, rb * 128 + wg * 64, (2 * layer) * DM + q * 64, rbx);
    bulk_commit();
    if (threadIdx.x == 0) TS(2 + layer * 20 + 10);
    asm volatile("cp.async.bulk.wait_group.read 0;" ::: "memory");
    if (wg == 0) mbar_arrive(bar + 8 * B_RE);
  }
}
__device__ __forceinline__ void proj_stats(int layer, int rb, int q, int lane, uint32_t tag) {
  const int r = 16 * q + (lane & 15);
  const uint2* src = &g_part[(rb * 8 + (lane >> 4) * 4) * 128 + r];
  uint2 v[4];
  bool ok;
  int it = 0;
  do {
    ok = true;
#pragma unroll
    for (int i = 0; i < 4; i++) v[i] = ld_part(src + i * 128);
#pragma unroll
    for (int i = 0; i < 4; i++) ok = ok && (v[i].y & 7u) == tag;
    if (++it > (1 << 22)) __trap();
  } while (!__all_sync(~0u, ok));
  float s = (__uint_as_float(v[0].x) + __uint_as_float(v[1].x)) + (__uint_as_float(v[2].x) + __uint_as_float(v[3].x));
  float qq = (__uint_as_float(v[0].y) + __uint_as_float(v[1].y)) + (__uint_as_float(v[2].y) + __uint_as_float(v[3].y));
  s += __shfl_xor_sync(~0u, s, 16);
  qq += __shfl_xor_sync(~0u, qq, 16);
  const float mean = s * (1.f / DM);
  const float rstd = rsqrt_approx(fmaxf(fmaf(qq, 1.f / DM, -mean * mean), 0.f) + 1e-5f), nm = -mean * rstd;
  const float nm1 = __shfl_xor_sync(~0u, nm, 1), rstd1 = __shfl_xor_sync(~0u, rstd, 1);
  if ((lane & 17) == 0)
    st_tagged3((uint4*)g_stats + (layer * 32 + rb * 2 + (r >> 6)) * 32 + ((r & 7) >> 1) * 8 + ((r >> 3) & 7),
               __float_as_uint(nm), __float_as_uint(rstd) | 1u, __float_as_uint(nm1), __float_as_uint(rstd1));
}

#define NA 8
template <bool GB> __host__ __device__ constexpr int grp_n() { return GB ? 17 - NA : NA; }
template <bool GB> __host__ __device__ constexpr int grp_m(int i) { return i == 0 ? (GB ? 1 : 0) : (GB ? NA + i : 1 + i); }
template <bool GB> __device__ __forceinline__ void conv_load(uint32_t* A, uint32_t pe) {
#pragma unroll
  for (int i = 0; i < grp_n<GB>(); i++) {
    asm volatile("ld.shared.v2.b32 {%0,%1}, [%2];" : "=r"(A[4 * i]), "=r"(A[4 * i + 1]) : "r"(pe + 4 * (64 * grp_m<GB>(i))) : "memory");
    A[4 * i + 2] = lds32(pe + 4 * (64 * grp_m<GB>(i) - 1));
  }
}
template <bool GB> __device__ __forceinline__ void conv_dup_early(uint32_t* A, uint32_t zero) {
#pragma unroll
  for (int i = 0; i < grp_n<GB>(); i++) asm volatile("or.b32 %0, %1, %2;" : "=r"(A[4 * i + 3]) : "r"(A[4 * i + 0]), "r"(zero));
}
template <bool GB> __device__ __forceinline__ void conv_dup(uint32_t* A) {
#pragma unroll
  for (int i = 0; i < grp_n<GB>(); i++) asm volatile("mov.b32 %0, %1;" : "=r"(A[4 * i + 3]) : "r"(A[4 * i + 0]));
}
template <bool GB, int I0, int I1> __device__ __forceinline__ void conv_mmas(float* acc, const uint32_t* A, uint64_t d) {
  if constexpr (I0 < I1) {
    constexpr int M = grp_m<GB>(I0);
    wgmma_rs<128 - 8 * (M / 2), 0>(acc, A + 4 * I0, d + (uint64_t)(4 * M), M != 0);
    conv_mmas<GB, I0 + 1, I1>(acc, A, d);
  }
}
struct SumAddr { uint32_t l0, l1, l2, se, so; };
__device__ __forceinline__ SumAddr conv_sum_addr(uint32_t sb, int c) {
  auto ua = [&](int j) { return sb + cv_u(0) + (127 - (j >> 3)) * 16 + (j & 7) * 2; };
  auto sa = [&](int hc) { const int ci = hc & ~1; return sb + cv_s(0) + ((ci >> 3) & 1) * 1024 + (ci >> 4) * 128 + (((ci ^ (ci >> 4)) & 7) << 4) + (hc & 1) * 8; };
  const int j0 = 4 * (c - 1);
  return {ua(j0 - 2), ua(j0), ua(j0 + 4), sa((c + 1) & 127), sa(c) + 2048};
}
__device__ __forceinline__ void sts64(uint32_t a, uint32_t x, uint32_t y) { asm volatile("st.shared.v2.b32 [%0], {%1,%2};" ::"r"(a), "r"(x), "r"(y) : "memory"); }
__device__ __forceinline__ void conv_sums(const SumAddr& sa, int lc, int c) {
  uint32_t e[4], o[4];
  {
    const float2 em = lds64f(sa.l1 + lc * 32768), om = lds64f(sa.l1 + lc * 32768 + CV_UH);
    e[0] = lds32(sa.l0 + lc * 32768); o[0] = lds32(sa.l0 + lc * 32768 + CV_UH);
    e[3] = lds32(sa.l2 + lc * 32768); o[3] = lds32(sa.l2 + lc * 32768 + CV_UH);
    e[1] = __float_as_uint(em.x); e[2] = __float_as_uint(em.y); o[1] = __float_as_uint(om.x); o[2] = __float_as_uint(om.y);
  }
  uint32_t s7e[2], s7o[2], s9e[2], s9o[2];
  uint32_t pw[4], sh[3];
#pragma unroll
  for (int k = 0; k < 4; k++) pw[k] = hadd2(e[k], o[k]);
#pragma unroll
  for (int k = 0; k < 3; k++) sh[k] = __byte_perm(pw[k], pw[k + 1], 0x5432);
#pragma unroll
  for (int k = 0; k < 2; k++) {
    const uint32_t t3 = hadd2(hadd2(sh[k], sh[k + 1]), pw[k + 1]);
    s7e[k] = hadd2(t3, o[k]); s7o[k] = hadd2(t3, e[k + 2]);
    s9e[k] = hadd2(s7o[k], pw[k]); s9o[k] = hadd2(s7e[k], pw[k + 2]);
  }
  if (c == 127) s9e[0] = s9e[1] = s9o[0] = s9o[1] = 0u;
  sts64(sa.se + lc * 32768, s9e[0], s9e[1]); sts64((sa.se ^ 16) + lc * 32768, s9o[0], s9o[1]);
  sts64(sa.so + lc * 32768, s7e[0], s7e[1]); sts64((sa.so ^ 16) + lc * 32768, s7o[0], s7o[1]);
}

__device__ __forceinline__ void conv_epi(uint32_t sb, int layer, int cta, int ch, int c0, uint4 x0, uint4 x1) {
  uint4 v[2][4];
  const uint4 xr[2] = {x0, x1};
  mbar_wait(sb + SM_BAR + 8 * (B_P + ch), layer);
#pragma unroll
  for (int u = 0; u < 2; u++) {
    const uint32_t pb = sb + cv_pb(ch) + u * (CV_PBW / 2) + c0 * 16;
#pragma unroll
    for (int k = 0; k < 4; k++) v[u][k] = lds128(pb + k * CV_PBW);
  }
#pragma unroll
  for (int u = 0; u < 2; u++) {
    uint4 o;
    o.x = hadd2(xr[u].x, hadd2(hadd2(v[u][0].x, v[u][1].x), hadd2(v[u][2].x, v[u][3].x)));
    o.y = hadd2(xr[u].y, hadd2(hadd2(v[u][0].y, v[u][1].y), hadd2(v[u][2].y, v[u][3].y)));
    o.z = hadd2(xr[u].z, hadd2(hadd2(v[u][0].z, v[u][1].z), hadd2(v[u][2].z, v[u][3].z)));
    o.w = hadd2(xr[u].w, hadd2(hadd2(v[u][0].w, v[u][1].w), hadd2(v[u][2].w, v[u][3].w)));
    if (layer == 0) sts128(sb + cv_s(ch) + (c0 + 128 * u) * 16, o);
    else st_tagged3((uint4*)(g_xT + (size_t)(3 * DM + cv_chan(cta, ch)) * LSEQ) + c0 + 128 * u, o.x, o.y, o.z, o.w);
  }
}
__device__ __forceinline__ void warp_release(uint32_t b) {
  fence_writer();
  __syncwarp();
  if (elect_one()) mbar_arrive(b);
}

__device__ __forceinline__ void conv_prep_load(uint32_t sb, int layer, int cta, int c, uint4 (&xr)[4], uint4 (&st)[4]) {
  mbar_wait(sb + SM_BAR + 8 * B_GB, layer);
  if (threadIdx.x == 0) TS(2 + layer * 20 + 11);
  xr[0] = ld_tagged((const uint4*)(g_xT + (size_t)(2 * layer * DM + cta) * LSEQ) + c);
#pragma unroll
  for (int i = 0; i < 4; i++) st[i] = ld_tagged((const uint4*)g_stats + (layer * 32 + (c >> 3)) * 32 + i * 8 + (c & 7));
}
template <bool HELPER>
__device__ __forceinline__ void conv_prep(uint32_t sb, int layer, int cta, int c, uint4 (&xr)[4], uint4 (&st)[4], const SumAddr& sa) {
  const uint32_t bar = sb + SM_BAR;
  const uint4* xin = (const uint4*)(g_xT + (size_t)(2 * layer * DM + cta) * LSEQ) + c;
  for (int it = 0;; it++) {
    const bool okx = __all_sync(~0u, xr[0].x != ~0u);
    const bool oks = __all_sync(~0u, (st[0].y & st[1].y & st[2].y & st[3].y & 1u) != 0);
    if (okx && oks) break;
    if (it > (1 << 22)) __trap();
    if (!okx) xr[0] = ld_tagged(xin);
    if (!oks) {
#pragma unroll
      for (int i = 0; i < 4; i++) st[i] = ld_tagged((const uint4*)g_stats + (layer * 32 + (c >> 3)) * 32 + i * 8 + (c & 7));
    }
  }
  if (threadIdx.x == 0) TS(2 + layer * 20 + 12);
  const int a = c & 127, h = c >> 7;
#pragma unroll
  for (int i = 0; i < 4; i++) {
    if (i == 1) {
#pragma unroll
      for (int j = 1; j < 4; j++) xr[j] = ld_tagged(xin + j * (128 * LSEQ / 8));
      if (HELPER) {
        mbar_wait(bar + 8 * B_U, layer);
        conv_sums(sa, 0, c);
        fence_async_smem();
        warp_release(bar + 8 * B_S);
        if (layer == 1 && c == 0) TS(46);
        mbar_wait(bar + 8 * B_GB, layer);
      }
      for (int it = 0; !__all_sync(~0u, xr[1].x != ~0u && xr[2].x != ~0u && xr[3].x != ~0u); it++) {
        if (it > (1 << 22)) __trap();
#pragma unroll
        for (int j = 1; j < 4; j++) xr[j] = ld_tagged(xin + j * (128 * LSEQ / 8));
      }
    }
    const uint32_t x[4] = {xr[i].x, xr[i].y, xr[i].z, xr[i].w};
    uint32_t u[4];
#pragma unroll
    for (int k = 0; k < 4; k++)
      u[k] = packbf(fmaf(bf_lo(x[k]), __uint_as_float(st[k].y), __uint_as_float(st[k].x)), fmaf(bf_hi(x[k]), __uint_as_float(st[k].w), __uint_as_float(st[k].z)));
    sts128(sb + cv_u(i) + h * CV_UH + (127 - a) * 16, make_uint4(u[0], u[1], u[2], u[3]));
    warp_release(bar + 8 * (B_U + i));
  }
}
__device__ __forceinline__ void conv_zero(uint32_t sb, int ht) {
  if (ht < 96) {
    const int ch = ht / 24, h2 = (ht / 12) & 1, qq = ht % 12;
    sts128(sb + cv_u(ch) + h2 * CV_UH + (128 + qq) * 16, make_uint4(0, 0, 0, 0));
  }
  if (ht >= 80) {
    const int i = ht - 80, ch = i / 12, q2 = i % 12;
    const int w2 = q2 < 2 ? 1 : q2 < 6 ? 2 : 3, cc = q2 < 2 ? q2 : q2 < 6 ? q2 - 2 : q2 - 6;
    sts128(sb + cv_pb(ch) + w2 * CV_PBW + (cc & 1) * (CV_PBW / 2) + (cc >> 1) * 16, make_uint4(0, 0, 0, 0));
  }
}

#define LD_AT 0
#define HANDOVER 12
template <int R>
__device__ __forceinline__ void conv_round(uint32_t sb, int layer, int wg, uint32_t* FA, uint32_t* FB, uint32_t pb, uint32_t pe2) {
  const uint32_t bar = sb + SM_BAR;
  const int ch = 2 * R + 1 - wg;
  float acc[64];
  const uint64_t d = mkdesc(sb + cv_u(ch), CV_UH, 128, 0);
  const bool leader = (opaque_tid() & 127) == 0;
  FTS(39);
  if (R == 0) {
    mbar_wait(bar + 8 * (B_U + ch), layer);
    fence_reader();
  }
  if (ch > 0) mbar_wait(bar + 8 * (B_T + ch - 1), layer);
  FTS(41);
  if (ch == 0 && threadIdx.x == 128) TS(2 + layer * 20 + 13);
  if (R == 1 && LD_AT == 0) conv_load<true>(FB, pe2);
  wg_fence();
  conv_mmas<false, 0, (HANDOVER < NA ? HANDOVER : NA)>(acc, FA, d);
  if (HANDOVER <= NA) mbar_arrive_if(bar + 8 * (B_T + ch), leader);
  conv_mmas<false, (HANDOVER < NA ? HANDOVER : NA), NA>(acc, FA, d);
  wg_commit();
  if (R == 1 && LD_AT == 1) conv_load<true>(FB, pe2);
  FTS(51);
  mbar_wait(bar + 8 * (B_S + ch), layer);
  if (R == 1) conv_dup<true>(FB);
  wg_fence();
  conv_mmas<true, 0, (HANDOVER > NA ? HANDOVER - NA : 0)>(acc, FB, d);
  if (HANDOVER > NA) mbar_arrive_if(bar + 8 * (B_T + ch), leader);
  conv_mmas<true, (HANDOVER > NA ? HANDOVER - NA : 0), 17 - NA>(acc, FB, d);
  wgmma_ss<64, 1, 1>(acc, mkdesc(sb + cv_s(ch), 1024, 1024, 1), mkdesc(sb + cv_ft(ch), 256, 16, 0), 1);
  wgmma_ss<64, 1, 1>(acc, mkdesc(sb + cv_s(ch) + 2048, 1024, 1024, 1), mkdesc(sb + cv_ft(ch) + 512, 256, 16, 0), 1);
  wg_commit();
  FTS(61);
  wg_wait<0>();
#pragma unroll
  for (int j = 0; j < 16; j += 2)
    stsm4t(pb + R * 65536 - j * 128, packbf(acc[4 * j], acc[4 * j + 1]), packbf(acc[4 * j + 2], acc[4 * j + 3]),
           packbf(acc[4 * j + 4], acc[4 * j + 5]), packbf(acc[4 * j + 6], acc[4 * j + 7]));
  __syncwarp();
  if (elect_one()) mbar_arrive(bar + 8 * (B_P + ch));
  if (threadIdx.x == 0) TS(2 + layer * 20 + 14 + R);
  FTS(57);
  if (R == 0) {
    mbar_wait(bar + 8 * (B_U + ch + 2), layer);
    fence_reader();
  }
}
__device__ __forceinline__ void conv_phase(const Params& p, uint32_t sb, int layer, int cta) {
  const int tid = opaque_tid();
  const int wg = __shfl_sync(~0u, tid >> 7, 0), w = __shfl_sync(~0u, (tid >> 5) & 3, 0);
  const uint32_t bar = sb + SM_BAR;
  uint32_t FA0[4 * NA], FA1[4 * NA], FB[4 * (17 - NA)];
  const uint32_t pe = sb + cv_pe(1 - wg) + 4 * (16 + 16 * w + 2 * ((tid & 31) >> 2) - 4 * (tid & 3));
  mbar_wait(bar + 8 * B_PE, layer);
  conv_load<false>(FA0, pe); conv_load<true>(FB, pe);
  const uint32_t zero = tid >> 10;
  conv_dup_early<false>(FA0, zero); conv_dup_early<true>(FB, zero);
  if (wg == 0) {
    uint4 xr[4], st[4];
    conv_prep_load(sb, layer, cta, tid + 128, xr, st);
    conv_load<false>(FA1, pe + 65536);
    conv_dup_early<false>(FA1, zero);
    conv_prep<false>(sb, layer, cta, opaque_tid() + 128, xr, st, SumAddr());
  } else {
    conv_load<false>(FA1, pe + 65536);
    conv_dup_early<false>(FA1, zero);
  }
  uint32_t pb;
  {
    const int l2 = opaque_tid() & 31, mt = l2 >> 3;
    pb = sb + cv_pb(1 - wg) + w * CV_PBW + (mt & 1) * (CV_PBW / 2) + (127 - 8 * (mt >> 1) - (l2 & 7) + w) * 16;
  }
  conv_round<0>(sb, layer, wg, FA0, FB, pb, 0);
  conv_round<1>(sb, layer, wg, FA1, FB, pb, pe + 65536);
  if (wg == 1 && layer == 0) mbar_wait(bar + 8 * (B_T + 3), layer);
}

__device__ __forceinline__ void final_phase(const Params& p, uint32_t sb, int cta, int wg, int w) {
  if (wg == 1 && w == 3) return;
  const int lane = opaque_tid() & 31, g = lane >> 2, t = lane & 3;
  const int lc = wg ? w : 3;
  const int pos0 = (cta & 31) * 64, ch0 = 128 * lc + (cta >> 5) * 32;
  const bf16* src = g_xT + (size_t)(3 * DM + ch0 + 8 * (g >> 1) + (g & 1)) * LSEQ + pos0;
  bf16* dst = p.out + (size_t)(2 * (pos0 & 1023) + (pos0 >> 10)) * DM + ch0 + 8 * t;
  constexpr int RS = 2 * DM;
  int it = 0;
  mbar_wait(sb + SM_BAR + 8 * (B_E + lc), 1);
  delay<D_FIN>();
  if (wg == 0) {
    uint2 v[4];
    do {
#pragma unroll
      for (int q = 0; q < 4; q++)
        asm volatile("ld.relaxed.gpu.global.v2.u32 {%0,%1}, [%2];" : "=r"(v[q].x), "=r"(v[q].y) : "l"(src + 2 * q * LSEQ + 16 * w + 4 * t) : "memory");
      if (++it > (1 << 22)) __trap();
    } while (!__all_sync(~0u, v[0].x != ~0u && v[1].x != ~0u && v[2].x != ~0u && v[3].x != ~0u));
    if (threadIdx.x == 0) TS(42);
    dst += (16 * w + 4 * (g >> 1) + (g & 1)) * RS;
    *(uint4*)dst = make_uint4(movm_t(v[0].x), movm_t(v[1].x), movm_t(v[2].x), movm_t(v[3].x));
    *(uint4*)(dst + 2 * RS) = make_uint4(movm_t(v[0].y), movm_t(v[1].y), movm_t(v[2].y), movm_t(v[3].y));
  } else {
    uint4 v[2][4];
    bool ok;
    do {
      ok = true;
#pragma unroll
      for (int h = 0; h < 2; h++)
#pragma unroll
        for (int q = 0; q < 4; q++) v[h][q] = ld_tagged((const uint4*)(src + 2 * q * LSEQ + 32 * h + 8 * t));
#pragma unroll
      for (int h = 0; h < 2; h++)
#pragma unroll
        for (int q = 0; q < 4; q++) ok = ok && v[h][q].x != ~0u;
      if (++it > (1 << 22)) __trap();
    } while (!__all_sync(~0u, ok));
    dst += (8 * (g >> 1) + (g & 1)) * RS;
#pragma unroll
    for (int h = 0; h < 2; h++) {
      *(uint4*)(dst + (32 * h + 0) * RS) = make_uint4(movm_t(v[h][0].x), movm_t(v[h][1].x), movm_t(v[h][2].x), movm_t(v[h][3].x));
      *(uint4*)(dst + (32 * h + 2) * RS) = make_uint4(movm_t(v[h][0].y), movm_t(v[h][1].y), movm_t(v[h][2].y), movm_t(v[h][3].y));
      *(uint4*)(dst + (32 * h + 4) * RS) = make_uint4(movm_t(v[h][0].z), movm_t(v[h][1].z), movm_t(v[h][2].z), movm_t(v[h][3].z));
      *(uint4*)(dst + (32 * h + 6) * RS) = make_uint4(movm_t(v[h][0].w), movm_t(v[h][1].w), movm_t(v[h][2].w), movm_t(v[h][3].w));
    }
  }
  if (threadIdx.x == 0) TS(43);
  if (threadIdx.x == 192) TS(63);
  if (threadIdx.x == 0) LTS(1);
}

struct cplx { float r, i; };
__device__ __forceinline__ cplx cmul(cplx a, cplx b) { return {fmaf(a.r, b.r, -a.i * b.i), fmaf(a.r, b.i, a.i * b.r)}; }
__device__ __forceinline__ cplx csqr(cplx a) { return {fmaf(a.r, a.r, -a.i * a.i), (a.r + a.r) * a.i}; }
__device__ __forceinline__ cplx cexp_l(float ar2, float ai, float l) {
  const float m = ex2(ar2 * l);
  const float x = ai * l;
  return {m * __cosf(x), m * __sinf(x)};
}

__device__ __forceinline__ void colsum_publish(uint32_t sb, int rb, int hg, int ht, uint32_t tag) {
  const int lane = ht & 31, q = lane & 15, h = lane >> 4;
  const uint32_t src = sb + SM_CW + (ht >> 5) * 4096 + h * 128 + (q & 1) * 8;
  float s[4] = {0.f, 0.f, 0.f, 0.f};
#pragma unroll
  for (int r = 0; r < 16; r++) {
    const float2 v = lds64f(src + r * 256 + (((q >> 1) ^ ((2 * r + h) & 7)) << 4));
    s[0] += bf_lo(__float_as_uint(v.x)); s[1] += bf_hi(__float_as_uint(v.x));
    s[2] += bf_lo(__float_as_uint(v.y)); s[3] += bf_hi(__float_as_uint(v.y));
  }
#pragma unroll
  for (int k = 0; k < 4; k++) s[k] += __shfl_xor_sync(~0u, s[k], 16);
  if (h == 0)
    st_tagged3(&g_colsum[(hg * 16 + rb) * 48 + (ht >> 5) * 16 + q], (__float_as_uint(s[0]) & ~7u) | tag, __float_as_uint(s[1]),
               __float_as_uint(s[2]), __float_as_uint(s[3]));
}
__device__ __forceinline__ void colsum_gather(uint32_t sb, int hg, int ht, uint32_t tag) {
  const int lane = ht & 31, rec = (ht >> 5) * 16 + (lane & 15);
  const uint4* src = &g_colsum[(hg * 16 + (lane >> 4) * 8) * 48 + rec];
  uint4 v[8];
  bool ok;
  int it = 0;
  do {
    ok = true;
#pragma unroll
    for (int i = 0; i < 8; i++) v[i] = ld_tagged(src + i * 48);
#pragma unroll
    for (int i = 0; i < 8; i++) ok = ok && (v[i].x & 7u) == tag;
    if (++it > (1 << 22)) __trap();
  } while (!__all_sync(~0u, ok));
  float s[4] = {0.f, 0.f, 0.f, 0.f};
#pragma unroll
  for (int i = 0; i < 8; i++) {
    s[0] += __uint_as_float(v[i].x & ~7u); s[1] += __uint_as_float(v[i].y); s[2] += __uint_as_float(v[i].z); s[3] += __uint_as_float(v[i].w);
  }
#pragma unroll
  for (int k = 0; k < 4; k++) s[k] += __shfl_xor_sync(~0u, s[k], 16);
  if (lane < 16) sts128f(sb + SM_CS + rec * 16, s[0], s[1], s[2], s[3]);
}

__device__ __forceinline__ uint32_t packh(float lo, float hi) { uint32_t r; asm("cvt.rn.f16x2.f32 %0, %1, %2;" : "=r"(r) : "f"(hi), "f"(lo)); return r; }
__device__ __forceinline__ void mma_f16(float* d, uint32_t a0, uint32_t a1, uint32_t a2, uint32_t a3, uint32_t b0, uint32_t b1) {
  asm volatile("mma.sync.aligned.m16n8k16.row.col.f32.f16.f16.f32 {%0,%1,%2,%3}, {%4,%5,%6,%7}, {%8,%9}, {%0,%1,%2,%3};"
      : "+f"(d[0]), "+f"(d[1]), "+f"(d[2]), "+f"(d[3]) : "r"(a0), "r"(a1), "r"(a2), "r"(a3), "r"(b0), "r"(b1));
}
struct HSeed { uint32_t r, i; };
__device__ __forceinline__ HSeed hseed(cplx s) { return {packh(s.r, s.r), packh(s.i, s.i)}; }
__device__ __forceinline__ void hcmul(uint32_t& o_r, uint32_t& o_i, uint32_t br, uint32_t bi, HSeed s) {
  asm("{\n.reg .b32 t, u;\nmul.rn.f16x2 t, %3, %5;\nneg.f16x2 t, t;\nmul.rn.f16x2 u, %3, %4;\nfma.rn.f16x2 %0, %2, %4, t;\nfma.rn.f16x2 %1, %2, %5, u;\n}"
      : "=&r"(o_r), "=&r"(o_i) : "r"(br), "r"(bi), "r"(s.r), "r"(s.i));
}
struct HTile { uint32_t r[4], i[4]; };
__device__ __forceinline__ void tile_set(HTile& t, int k, cplx a, cplx b) { t.r[k] = packh(a.r, b.r); t.i[k] = packh(a.i, b.i); }
__device__ __forceinline__ void tile_upper(HTile& t, HSeed s) { hcmul(t.r[2], t.i[2], t.r[0], t.i[0], s); hcmul(t.r[3], t.i[3], t.r[1], t.i[1], s); }
__device__ __forceinline__ HTile tile_shift(const HTile& t, HSeed s) {
  HTile o;
#pragma unroll
  for (int k = 0; k < 4; k++) hcmul(o.r[k], o.i[k], t.r[k], t.i[k], s);
  return o;
}
__device__ __forceinline__ void tile_put(const HTile& t, uint32_t a) {
  sts128(a, make_uint4(t.r[0], t.r[1], t.r[2], t.r[3]));
  sts128(a + 512, make_uint4(t.i[0], t.i[1], t.i[2], t.i[3]));
}
__device__ __forceinline__ HTile tile_get(uint32_t a) { HTile o; ldsm4t(o.r, a); ldsm4t(o.i, a + 512); return o; }
__device__ __forceinline__ void tile_mma(float* T, const HTile& a0, const HTile& a1, const HTile& b) {
  mma_f16(T, a0.r[0], a0.r[1], a0.r[2], a0.r[3], b.r[0], b.r[1]);
  mma_f16(T, a0.i[0], a0.i[1], a0.i[2], a0.i[3], b.i[0], b.i[1]);
  mma_f16(T, a1.r[0], a1.r[1], a1.r[2], a1.r[3], b.r[2], b.r[3]);
  mma_f16(T, a1.i[0], a1.i[1], a1.i[2], a1.i[3], b.i[2], b.i[3]);
}
__device__ __forceinline__ void tile_mma2(float* T, float* U, const HTile& a0, const HTile& a1, const HTile& b, const HTile& c) {
  mma_f16(T, a0.r[0], a0.r[1], a0.r[2], a0.r[3], b.r[0], b.r[1]);
  mma_f16(U, a0.r[0], a0.r[1], a0.r[2], a0.r[3], c.r[0], c.r[1]);
  mma_f16(T, a0.i[0], a0.i[1], a0.i[2], a0.i[3], b.i[0], b.i[1]);
  mma_f16(U, a0.i[0], a0.i[1], a0.i[2], a0.i[3], c.i[0], c.i[1]);
  mma_f16(T, a1.r[0], a1.r[1], a1.r[2], a1.r[3], b.r[2], b.r[3]);
  mma_f16(U, a1.r[0], a1.r[1], a1.r[2], a1.r[3], c.r[2], c.r[3]);
  mma_f16(T, a1.i[0], a1.i[1], a1.i[2], a1.i[3], b.i[2], b.i[3]);
  mma_f16(U, a1.i[0], a1.i[1], a1.i[2], a1.i[3], c.i[2], c.i[3]);
}
__device__ __forceinline__ void kgen_unit(uint32_t tab, uint32_t taba, float ar2, float ai, cplx c, float (&T)[5][4]) {
  const cplx z1 = cexp_l(ar2, ai, 1.f), z16 = cexp_l(ar2, ai, 16.f), z256 = cexp_l(ar2, ai, 256.f);
  HTile a0, a1, b0, b1;
  {
    const cplx y1 = {z16.r, -z16.i}, y2 = csqr(y1), y3 = cmul(y2, y1), y4 = csqr(y2), y5 = cmul(y4, y1), y6 = csqr(y3), y7 = cmul(y4, y3);
    HTile t;
    tile_set(t, 0, {1.f, 0.f}, y1); tile_set(t, 1, y2, y3); tile_set(t, 2, y4, y5); tile_set(t, 3, y6, y7);
    const HTile u = tile_shift(t, hseed(csqr(y4)));
    __syncwarp();
    tile_put(t, tab); tile_put(u, tab + 1024);
    __syncwarp();
    a0 = tile_get(taba); a1 = tile_get(taba + 256);
  }
  const cplx z2 = csqr(z1), z4 = csqr(z2), z8 = csqr(z4);
  const HSeed h8 = hseed(z8);
  const cplx d = cmul(c, z256), e = cmul(d, z256);
  {
    const cplx z512 = csqr(z256), f = cmul(e, z512), f8 = cmul(f, z8), f16 = cmul(f, z16), e4 = cmul(e, z4);
    HTile t, u;
    tile_set(t, 0, e4, cmul(e, z8)); tile_set(t, 1, cmul(e4, z8), cmul(e, z16));
    tile_upper(t, hseed(z256));
    tile_set(u, 0, f8, f16); tile_set(u, 1, cmul(f8, z256), cmul(f16, z256));
    tile_upper(u, hseed(z512));
    __syncwarp();
    tile_put(t, tab); tile_put(u, tab + 1024);
    __syncwarp();
    b0 = tile_get(tab); b1 = tile_get(tab + 1024);
  }
  {
    const cplx d2 = cmul(d, z2), d4 = cmul(d, z4);
    HTile t;
    tile_set(t, 0, d2, d4); tile_set(t, 1, cmul(d2, z4), cmul(d, z8));
    tile_upper(t, h8);
    __syncwarp();
    tile_put(t, tab);
    __syncwarp();
    tile_mma2(T[3], T[4], a0, a1, b0, b1);
    b0 = tile_get(tab);
  }
  {
    const cplx c1 = cmul(c, z1), c2 = cmul(c, z2), c3 = cmul(c1, z2), c4 = cmul(c, z4);
    HTile t;
    tile_set(t, 0, c1, c2); tile_set(t, 1, c3, c4); tile_set(t, 2, cmul(c1, z4), cmul(c2, z4)); tile_set(t, 3, cmul(c3, z4), cmul(c4, z4));
    const HTile u = tile_shift(t, h8);
    __syncwarp();
    tile_put(t, tab); tile_put(u, tab + 1024);
    __syncwarp();
    tile_mma(T[2], a0, a1, b0);
    b0 = tile_get(tab); b1 = tile_get(tab + 1024);
    tile_mma2(T[0], T[1], a0, a1, b0, b1);
  }
}
struct ModeIn { uint2 ar, ai, br, bi, cr, ci; };
__device__ __forceinline__ ModeIn load_modes(const Params& p, int idx) {
  return {*(const uint2*)(p.a_re + idx), *(const uint2*)(p.a_im + idx), *(const uint2*)(p.b_re + idx),
          *(const uint2*)(p.b_im + idx), *(const uint2*)(p.c_re + idx), *(const uint2*)(p.c_im + idx)};
}
__device__ __forceinline__ float bf_el(uint2 v, int k) { const uint32_t x = (k & 2) ? v.y : v.x; return (k & 1) ? bf_hi(x) : bf_lo(x); }
struct KGen { float4 cur; float T[5][4]; };
__device__ __forceinline__ uint32_t kgen_slot(uint32_t sb, int ht, int u) {
  return sb + (u < 3 ? SM_KC + (ht >> 5) * (KC_STRIDE * 2) + (u - 1) * 512 + (ht & 31) * 16 + 16 : SM_HALO + 1024 + ht * 16);
}
__device__ __forceinline__ void kgen_setup(KGen& s, uint32_t sb, int cta, int ht, const ModeIn& in, bf16 logdt, bf16 dskip) {
  const float dt = __bfloat162float(__float2bfloat16_rn(expf(__bfloat162float(logdt))));
  float mx = 0.f, k0 = 0.f, ar2[4];
  cplx c[4];
#pragma unroll
  for (int k = 0; k < 4; k++) {
    ar2[k] = (dt * bf_el(in.ar, k)) * 1.4426950408889634f;
    c[k] = cmul({bf_el(in.cr, k), bf_el(in.ci, k)}, {dt * bf_el(in.br, k), dt * bf_el(in.bi, k)});
    k0 += c[k].r;
    mx = fmaxf(mx, fmaxf(fabsf(c[k].r), fabsf(c[k].i)) * ex2(fmaxf(ar2[k] * 2048.f, 0.f)));
  }
  const int ex = min(max(267 - (int)(__reduce_max_sync(~0u, __float_as_uint(mx)) >> 23), 1), 253);
  const float sc = __uint_as_float(ex << 23);
#pragma unroll
  for (int o = 16; o > 0; o >>= 1) k0 += __shfl_xor_sync(~0u, k0, o);
  if ((ht & 31) == 0) {
    const uint32_t kc = sb + SM_KC + (ht >> 5) * (KC_STRIDE * 2);
    sts16(kc, __bfloat16_as_ushort(__float2bfloat16_rn(k0 + __bfloat162float(dskip))));
    sts16(kc + 641 * 2, 0);
    sts32f(kc + 644 * 2, __uint_as_float((254 - ex) << 23));
  }
  s.cur = make_float4(ar2[0], dt * bf_el(in.ai, 0), c[0].r * sc, c[0].i * sc);
#pragma unroll
  for (int k = 1; k < 4; k++) sts128f(kgen_slot(sb, ht, k), ar2[k], dt * bf_el(in.ai, k), c[k].r * sc, c[k].i * sc);
#pragma unroll
  for (int i = 0; i < 5; i++) s.T[i][0] = s.T[i][1] = s.T[i][2] = s.T[i][3] = 0.f;
}
__device__ __forceinline__ void kgen_finish(KGen& s, uint32_t sb, int cta, int ht) {
  const int w = ht >> 5, lane = ht & 31, g = lane >> 2, t = lane & 3;
  const uint32_t kc = sb + SM_KC + w * KC_STRIDE * 2;
  __syncwarp();
  const float inv = __uint_as_float(lds32(kc + 644 * 2));
  auto put = [&](int idx, float v) {
    sts16(kc + idx * 2, __bfloat16_as_ushort(__float2bfloat16_rn(v)));
  };
#pragma unroll
  for (int hi = 0; hi < 2; hi++)
#pragma unroll
    for (int lo = 0; lo < 2; lo++) {
      const int i = g + 8 * hi, j = 2 * t + lo, e = 2 * hi + lo;
      put(16 * i + 1 + j, s.T[0][e] * inv);
      put(16 * i + 9 + j, s.T[1][e] * inv);
      put(257 + 8 * i + j, s.T[2][e] * inv);
      put(385 + 4 * i + (j & 3) + 64 * (j >> 2), s.T[3][e] * inv);
      put(513 + 2 * i + lo + 32 * t, s.T[4][e] * inv);
    }
}

__device__ __forceinline__ void expand_taps(uint32_t sb, int ht) {
  const int ch = ht >> 5, lane = ht & 31;
  const uint32_t kc = sb + SM_KC + ch * KC_STRIDE * 2;
  const uint32_t dst0 = sb + cv_pe(ch);
  auto put = [&](int G, uint32_t u0, uint32_t u1, uint32_t v0, uint32_t v1, uint32_t v2, uint32_t v3, uint32_t v4, uint32_t v5, uint32_t v6, uint32_t v7) {
    const uint32_t dst = dst0 + G * 32;
    sts128(dst, make_uint4(v0 | (u0 << 16), v1 | (u1 << 16), v2 | (v0 << 16), v3 | (v1 << 16)));
    sts128(dst + 16, make_uint4(v4 | (v2 << 16), v5 | (v3 << 16), v6 | (v4 << 16), v7 | (v5 << 16)));
  };
  {
    const uint4 q = lds128(kc + lane * 16);
    const uint32_t pv = lane ? lds32(kc + lane * 16 - 4) : 0u;
    const uint32_t dst = dst0 + (lane + 2) * 32;
    sts128(dst, make_uint4(__byte_perm(q.x, pv, 0x5410), __byte_perm(q.x, pv, 0x7632), __byte_perm(q.y, q.x, 0x5410), __byte_perm(q.y, q.x, 0x7632)));
    sts128(dst + 16, make_uint4(__byte_perm(q.z, q.y, 0x5410), __byte_perm(q.z, q.y, 0x7632), __byte_perm(q.w, q.z, 0x5410), __byte_perm(q.w, q.z, 0x7632)));
    if (lane < 4) sts128(dst0 + lane * 16, make_uint4(0, 0, 0, 0));
  }
  uint32_t a[5], b[2][3], fv[4];
  {
    const uint32_t s1 = kc + 2 * (256 + 4 * lane);
#pragma unroll
    for (int k = 0; k < 5; k++) a[k] = lds16(s1 + 2 * k);
#pragma unroll
    for (int u = 0; u < 2; u++) {
      const uint32_t s2 = kc + 2 * (384 + 2 * (lane + 32 * u));
#pragma unroll
      for (int k = 0; k < 3; k++) b[u][k] = lds16(s2 + 2 * k);
    }
#pragma unroll
    for (int k = 0; k < 4; k++) fv[k] = lds16(kc + 2 * (640 - 4 * lane - k));
  }
  const uint32_t am1 = lds16(kc + 2 * (lane ? 256 + 4 * lane : 255)), am2 = lds16(kc + 2 * (lane ? 255 + 4 * lane : 254));
  const uint32_t bm2 = lds16(kc + 2 * (lane ? 384 + 2 * lane : 383)), k1024 = lds16(kc + 2 * 512);
  put(34 + lane, am2, am1, a[0], a[0], a[1], a[2], a[2], a[2], a[3], a[4]);
#pragma unroll
  for (int u = 0; u < 2; u++) put(66 + lane + 32 * u, u ? b[u][0] : bm2, b[u][0], b[u][0], b[u][0], b[u][0], b[u][1], b[u][1], b[u][1], b[u][2], b[u][2]);
  if (lane < 10) {
    const uint32_t v = lane == 0 ? k1024 : 0u;
    put(130 + lane, v, v, v, v, v, v, v, 0u, 0u, 0u);
  }
  const uint32_t ft = sb + cv_ft(ch) + 4 * lane;
#pragma unroll
  for (int ty = 0; ty < 2; ty++) {
    const uint32_t v = fv[ty] | (fv[ty + 2] << 16);
    sts32f(ft + ty * 512, __uint_as_float(v));
    sts32f(ft + ty * 512 + 128, 0.f);
    sts32f(ft + ty * 512 + 256 + (lane < 2 ? 120 : -8), __uint_as_float(lane < 2 ? 0u : v));
    sts32f(ft + ty * 512 + 384, 0.f);
  }
}

template <bool SMID> __device__ __forceinline__ int role_id() {
  uint32_t v;
  if (!SMID) { asm volatile("mov.u32 %0, %%ctaid.x;" : "=r"(v)); return v; }
  asm volatile("mov.u32 %0, %%smid;" : "=r"(v));
  const int tp = v >> 1, q = ((tp - 32) * 37) >> 8;
  const int r = tp < 32 ? (tp & 7) * 8 + (tp >> 3) : tp < 60 ? (tp - 31 - 7 * q) * 8 + 4 + q : tp < 62 ? tp + 4 : tp - 58;
  return __shfl_sync(~0u, 2 * r + (v & 1), 0);
}
__device__ __forceinline__ int role_rb(int cta) { return ((cta >> 4) & 3) * 4 + ((cta >> 2) & 3); }
__device__ __forceinline__ int role_hg(int cta) { return (cta >> 6) * 4 + (cta & 3); }
__device__ __forceinline__ int role_rb2(int cta) { return cta >> 3; }
__device__ __forceinline__ int role_q2(int cta) { return cta & 7; }

template <bool SMID> __global__ void __launch_bounds__(NTHREADS, 1) fused_kernel(const __grid_constant__ Params p) {
  extern __shared__ __align__(1024) uint8_t smem[];
  const uint32_t sb = s32(smem);
  const int tid = threadIdx.x, lane = tid & 31;
  const int warp = __shfl_sync(~0u, tid >> 5, 0);
  constexpr unsigned NARR = SMID ? 132 : NCTA;
  const uint32_t bar = sb + SM_BAR;
  if (tid == 0) TS(0);
  const int cta0 = role_id<SMID>();
  if (warp == 0 && (!SMID || cta0 < NCTA) && elect_one()) {
    const int rb = role_rb(cta0), hg = role_hg(cta0);
    mbar_init(bar + 8 * B_XF, 1); mbar_init(bar + 8 * B_KVF, 1);
    fence_async_smem();
#pragma unroll
    for (int c = 0; c < 8; c++) {
      mbar_expect(bar + 8 * (B_XF + c), 16384);
      tma_ld(sb + SM_X + c * 16384, &p.mapX128, (rb >> 3) * DM + c * 64, (rb & 7) * 128, bar + 8 * (B_XF + c));
      if (c < 3) {
        mbar_expect(bar + 8 * (B_KVF + c), 24576);
        tma_ld3(sb + SM_W + c * 24576, &p.mapW3, hg * 64, c * 64, 0, bar + 8 * (B_KVF + c));
      }
      if (c == 0) {
#pragma unroll
        for (int i = 1; i < 8; i++) mbar_init(bar + 8 * (B_XF + i), 1);
        mbar_init(bar + 8 * (B_KVF + 1), 1); mbar_init(bar + 8 * (B_KVF + 2), 1); mbar_init(bar + 8 * B_CW, 1);
        fence_async_smem();
      }
      if (c == PF_AT) {
        mbar_expect(bar + 8 * B_CW, 12288);
        tma_ld3(sb + SM_CW, &p.mapW3h, hg * 64, rb * 32, 0, bar + 8 * B_CW);
      }
    }
    TS(56);
  }
  if (SMID && cta0 >= NCTA) {
    if (tid == 0) spin_until(&g_cnt[C_CS * 32], (atomicAdd(&g_cnt[C_CS * 32], 1u) / NARR + 1) * NARR);
    return;
  }
  if (warp >= 1 && warp < 5 && elect_one()) {
#pragma unroll
    for (int q = 0; q < 4; q++) {
      if (warp == q + 1) {
#pragma unroll
        for (int i = 11 + 15 * q; i < 26 + 15 * q && i < B_COUNT; i++) {
          if (i < B_KVF + 3 || i == B_CW) continue;
          int cnt = 1;
          if ((i >= B_KVE && i < B_KVE + 5) || i == B_QDONE || i == B_PDONE || i == B_OST || i == B_AD) cnt = 2;
          if ((i >= B_U && i < B_U + 4) || i == B_PS) cnt = 8;
          if ((i >= B_S && i < B_S + 4) || (i >= B_E && i < B_E + 4) || (i >= B_P && i < B_P + 4) || i == B_PE || i == B_STF || i == B_HF) cnt = 4;
          if (i == B_CSF) cnt = 3;
          mbar_init(bar + 8 * i, cnt);
        }
      }
    }
    fence_async_smem();
  }

  if (warp < 8) {
    bar_sync(0, NTHREADS);
    if (tid == 0) TS(1);
    asm volatile("setmaxnreg.inc.sync.aligned.u32 %0;" ::"n"(R_CONS));
    const int cta = role_id<SMID>();
    auto warp_id = [] { return __shfl_sync(~0u, opaque_tid() >> 5, 0); };
    if (tid == 0) TS(54);
#pragma unroll 1
    for (int layer = 0; layer < 2; layer++) {
      { const int cw = warp_id(); attn_phase(p, sb, layer, role_rb(cta), role_hg(cta), cw >> 2, cw & 3); }
      if (p.stop == 1 + 3 * layer) return;
      { const int cw = warp_id(); proj_phase(p, sb, layer, role_rb2(cta), role_q2(cta), cw >> 2, cw & 3); }
      if (p.stop == 2 + 3 * layer) return;
      conv_phase(p, sb, layer, cta);
      if (p.stop == 3 + 3 * layer) return;
    }
    { const int cw = warp_id(); final_phase(p, sb, cta, cw >> 2, cw & 3); }
  } else if (warp < 12) {
    asm volatile("setmaxnreg.dec.sync.aligned.u32 %0;" ::"n"(R_HELP));
    const int ht = tid - 256;
    const int cta = role_id<SMID>(), rb = role_rb(cta), hg = role_hg(cta);
    unsigned ep0 = 0;
    if (ht == 0) ep0 = ld_relaxed(&g_cnt[C_CS * 32]);
    bar_sync(0, NTHREADS);
    if (ht == 0) {
      asm volatile("st.shared.u32 [%0], %1;" ::"r"(sb + SM_EP), "r"(ep0 / NARR) : "memory");
      mbar_arrive(bar + 8 * B_EP);
    }
    mbar_wait(bar + 8 * B_EP, 0);
    const uint32_t cs_tag = lds32(sb + SM_EP) % 7 + 1;
    if (ht < 96) {
      mbar_wait(bar + 8 * B_CW, 0);
      colsum_publish(sb, rb, hg, ht, cs_tag);
    }
    if (ht == 0) TS(50);
    if (ht < 48) {
      const bf16* q = (&p.a_re)[ht >> 3];
      asm volatile("prefetch.global.L2 [%0];" ::"l"(q + cv_chan(cta, (ht >> 1) & 3) * 128 + (ht & 1) * 64));
    }
    if (!CS_FIRST) stats_publish(sb, 0, rb, hg, opaque_tid() - 256, part_tag(lds32(sb + SM_EP), 0));
    {
      KGen kg;
      const uint32_t tab0 = sb + ((ht >> 5) < 2 ? SM_T : SM_T2 - 4096) + (ht >> 5) * 2048;
      const uint32_t tab = tab0 + (ht & 31) * 16, taba = tab0 + ((ht >> 3) & 1) * 1024 + (((ht >> 1) & 8) + (ht & 7)) * 16;
      mbar_wait(bar + 8 * (B_KVF + CS_AT), 0);
      if (ht < 96) {
        colsum_gather(sb, hg, ht, cs_tag);
        __syncwarp();
        if (elect_one()) mbar_arrive(bar + 8 * B_CSF);
      }
      if (CS_FIRST) stats_publish(sb, 0, rb, hg, opaque_tid() - 256, part_tag(lds32(sb + SM_EP), 0));
      stats_gather(sb, rb, opaque_tid() - 256, part_tag(lds32(sb + SM_EP), 0));
      if (ht == 0) TS(40);
      const int chn = cv_chan(cta, ht >> 5);
      const ModeIn modes = load_modes(p, chn * 128 + (ht & 31) * 4);
      const bf16 logdt = p.log_dt[chn], dskip = p.dskip[chn];
      halo_receive(sb, 0, rb, hg, opaque_tid() - 256);
      kgen_setup(kg, sb, cta, ht, modes, logdt, dskip);
#pragma unroll 1
      for (int u = 0; u < 4; u++) {
        if (u == KG_PRE) {
          KTS(39);
          mbar_wait(bar + 8 * B_AD, 0);
          KTS(41);
        }
        if (u == 4 - KG_LAST) mbar_wait(bar + 8 * (KG_PD ? B_PDONE : B_PS), 0);
        kgen_unit(tab, taba, kg.cur.x, kg.cur.y, {kg.cur.z, kg.cur.w}, kg.T);
        kg.cur = lds128f(kgen_slot(sb, opaque_tid() - 256, u + 1));
      }
      kgen_finish(kg, sb, cta, opaque_tid() - 256);
    }
    KTS(51);
    bar_sync(4, 128);
#pragma unroll 1
    for (int layer = 0; layer < 2; layer++) {
      if (p.stop <= 1 + 3 * layer) return;
      mbar_wait(bar + 8 * (EXP_LATE ? B_PS : B_PDONE), layer);
      expand_taps(sb, opaque_tid() - 256);
      conv_zero(sb, opaque_tid() - 256);
      if (ht == 0) TS(52 + layer);
      warp_release(bar + 8 * B_PE);
      if (p.stop <= 2 + 3 * layer) return;
      {
        uint4 xr[4], st[4];
        const int c = opaque_tid() - 256;
        const SumAddr sa = conv_sum_addr(sb, c);
        conv_prep_load(sb, layer, cta, c, xr, st);
        conv_prep<true>(sb, layer, cta, c, xr, st, sa);
        if (layer == 1 && ht == 0) TS(62);
        const bf16* xup = g_xT + (size_t)(2 * layer * DM + cta) * LSEQ + (c + 128) * 8;
        st[0] = ldcg128(xup);
        mbar_wait(bar + 8 * (B_U + 3), layer);
#pragma unroll
        for (int lc = 0; lc < 4; lc++) {
          if (lc < 3) {
            conv_sums(sa, lc + 1, c);
            fence_async_smem();
            warp_release(bar + 8 * (B_S + lc + 1));
            st[lc + 1] = ldcg128(xup + (lc + 1) * 128 * LSEQ);
          }
          conv_epi(sb, layer, cta, lc, c, xr[lc], st[lc]);
          warp_release(bar + 8 * (B_E + lc));
          if (layer == 1 && lc == 3 && ht == 0) TS(38);
        }
      }
      if (layer == 0 && p.stop > 3) {
        const int c1 = role_id<SMID>();
        stats_publish(sb, 1, role_rb(c1), role_hg(c1), opaque_tid() - 256, part_tag(lds32(sb + SM_EP), 2));
        delay<D_ST>();
        stats_gather(sb, role_rb(c1), opaque_tid() - 256, part_tag(lds32(sb + SM_EP), 2));
        if (ht == 0) TS(25);
        halo_receive(sb, 1, role_rb(c1), role_hg(c1), opaque_tid() - 256);
      }
    }
  } else {
    asm volatile("setmaxnreg.dec.sync.aligned.u32 %0;" ::"n"(512 - 2 * R_CONS - R_HELP));
    const int cta = role_id<SMID>(), rb = role_rb(cta), hg = role_hg(cta), rb2 = role_rb2(cta), q2 = role_q2(cta);
    bar_sync(0, NTHREADS);
    if (warp == 12) {
      if (elect_one()) {
        unsigned epoch = 0;
#pragma unroll 1
        for (int layer = 0; layer < 2; layer++) {
          auto ld_w = [&](int c, int slot) {
            const uint32_t b = bar + 8 * (B_KVF + c);
            mbar_expect(b, 24576);
            tma_ld3(sb + SM_W + slot * 24576, &p.mapW3, hg * 64, c * 64, 0, b);
          };
          if (layer == 0) {
            TS(55);
            mbar_wait(bar + 8 * (B_KVF + 2), 0);
            if (rb2 < 4) tma_prefetch2(&p.mapWo128, q2 * 64, rb2 * 128);
            asm volatile("prefetch.tensormap [%0];" ::"l"(&p.mapO) : "memory");
            asm volatile("prefetch.tensormap [%0];" ::"l"(&p.mapO128) : "memory");
            asm volatile("prefetch.tensormap [%0];" ::"l"(&p.mapXT) : "memory");
            asm volatile("prefetch.tensormap [%0];" ::"l"(&p.mapXT3) : "memory");
            mbar_wait(bar + 8 * B_EP, 0);
            epoch = lds32(sb + SM_EP);
          } else {
            mbar_wait(bar + 8 * B_PDONE, 0);
            ld_w(0, 0); ld_w(1, 1);
            mbar_wait(bar + 8 * (W2_LATE ? B_U : B_RE), 0);
            ld_w(2, 2);
          }
          {
            int slot = 0;
#pragma unroll 1
            for (int c = 3; c < 8; c++) {
              mbar_wait(bar + 8 * (B_KVE + c - 3), layer);
              ld_w(c, slot);
              slot = slot == 2 ? 0 : slot + 1;
            }
          }
          if (p.stop <= 1 + 3 * layer) return;
          mbar_wait(bar + 8 * B_QDONE, layer);
          mbar_wait(bar + 8 * B_HF, layer);
#pragma unroll 1
          for (int c = 0; c < 4; c++) {
            const uint32_t b = bar + 8 * (B_WOF + c);
            mbar_expect(b, 16384);
            tma_ld(sb + SM_WO + c * 16384, &p.mapWo128, q2 * 64, c * 128, b);
          }
          {
            const uint32_t b = bar + 8 * B_RF;
            mbar_expect(b, 16384);
            if (layer == 0) tma_ld(sb + SM_R, &p.mapX128, (rb2 >> 3) * DM + q2 * 64, (rb2 & 7) * 128, b);
            else tma_ld3(sb + SM_R, &p.mapXT3, 0, DM + q2 * 64, rb2 * 2, b);
          }
          spin_until(&g_cnt[(C_O + rb2) * 32], (2 * epoch + layer + 1) * 16);
          fence_async_global();
#pragma unroll 1
          for (int c = 0; c < 8; c++) {
            const uint32_t b = bar + 8 * (B_OF + c);
            if (c == 4) { mbar_wait(bar + 8 * B_OST, layer); fence_async_smem(); }
            mbar_expect(b, 16384);
            tma_ld(sb + sm_o(c), &p.mapO128, c * 64, rb2 * 128, b);
          }
          if (p.stop <= 3 + 3 * layer) return;
        }
      }
    } else if (warp == 13) {
      if (elect_one() && p.stop > 3) {
        mbar_wait(bar + 8 * B_GB, 0);
        const unsigned target = (lds32(sb + SM_EP) + 1) * NCTA;
        auto ld_x = [&](int c) {
          mbar_expect(bar + 8 * (B_XF + c), 16384);
          tma_ld3(sb + SM_X + c * 16384, &p.mapXT3, 0, DM + c * 64, rb * 2, bar + 8 * (B_XF + c));
        };
        int done = 0, it = 0;
        while (done < 4) {
          const uint4 v = ld_tagged((const uint4*)&g_cnt[C_G1 * 32]);
          const int n = (int)(v.x - target) < 0 ? 0 : (int)(v.y - target) < 0 ? 1 : (int)(v.z - target) < 0 ? 2 : (int)(v.w - target) < 0 ? 3 : 4;
          if (++it > (1 << 23)) __trap();
          if (n == done) continue;
          if (n == 4) TS(44);
          fence_async_global();
          fence_async_smem();
          const int first = n == 4 && done > 1 ? 6 + (hg >> 2) : -1;
          if (first >= 0) ld_x(first);
#pragma unroll 1
          for (int c = 2 * done; c < 2 * n; c++)
            if (c != first) ld_x(c);
          done = n;
        }
      }
    } else if (warp == 15) {
      mbar_wait(bar + 8 * B_EP, 0);
      const unsigned epoch = lds32(sb + SM_EP);
#pragma unroll 1
      for (int layer = 0; layer < 2; layer++) {
#pragma unroll 1
        for (int i = 0; i < 6; i++) {
          mbar_wait(bar + 8 * (B_KVF + (FILL_AT + i < 7 ? FILL_AT + i : 7)), layer);
          uint4* dst = (uint4*)(g_xT + (size_t)(i < 4 ? 2 * layer * DM + cv_chan(cta, i) : 3 * DM + cv_chan(cta, 2 * layer + i - 4)) * LSEQ) + lane;
#pragma unroll
          for (int k = 0; k < 8; k++) dst[32 * k] = make_uint4(~0u, ~0u, ~0u, ~0u);
        }
        if (lane < 8) ((uint4*)g_stats)[layer * 1024 + cta * 8 + lane] = make_uint4(0, 0, 0, 0);
        __syncwarp();
        if (elect_one()) {
          red_release(&g_cnt[C_CS * 32 + layer]);
          spin_until(&g_cnt[C_CS * 32 + layer], (epoch + 1) * (layer ? NCTA : NARR));
          mbar_arrive(bar + 8 * B_ZF);
          if (layer == 0 && p.stop > 2) {
#pragma unroll 1
            for (int lc = 0; lc < 4; lc++) {
              mbar_wait(bar + 8 * (B_E + lc), 0);
              fence_reader();
              bulk_st(g_xT + (size_t)(DM + cv_chan(cta, lc)) * LSEQ, sb + cv_s(lc), 4096);
              bulk_commit();
              bulk_wait_all();
              red_relaxed(&g_cnt[C_G1 * 32 + lc]);
              if (lc == 3) TS(18);
            }
          }
        }
        __syncwarp();
        if (p.stop <= 3) return;
      }
    } else if (warp == 14) {
      mbar_wait(bar + 8 * B_EP, 0);
      const unsigned epoch = lds32(sb + SM_EP);
#pragma unroll 1
      for (int layer = 0; layer < 2; layer++) {
        if (p.stop <= 1 + 3 * layer) return;
        mbar_wait(bar + 8 * B_ZF, layer);
        mbar_wait(bar + 8 * (EXP_LATE ? B_PS : B_PDONE), layer);
        delay<D_PST>();
        proj_stats(layer, rb2, q2, lane, part_tag(epoch, 2 * layer + 1));
        if (layer == 1 && lane == 0) TS(5);
        delay<D_PREP>();
        if (lane == 0) mbar_arrive(bar + 8 * B_GB);
      }
    }
  }
}

typedef CUresult (*EncodeFn)(CUtensorMap*, CUtensorMapDataType, cuuint32_t, void*, const cuuint64_t*, const cuuint64_t*,
                             const cuuint32_t*, const cuuint32_t*, CUtensorMapInterleave, CUtensorMapSwizzle,
                             CUtensorMapL2promotion, CUtensorMapFloatOOBfill);

static void make_map(EncodeFn enc, CUtensorMap* m, void* ptr, uint64_t cols, uint64_t rows, uint32_t box_rows) {
  cuuint64_t dims[2] = {cols, rows};
  cuuint64_t strides[1] = {cols * 2};
  cuuint32_t box[2] = {64, box_rows};
  cuuint32_t es[2] = {1, 1};
  enc(m, CU_TENSOR_MAP_DATA_TYPE_BFLOAT16, 2, ptr, dims, strides, box, es, CU_TENSOR_MAP_INTERLEAVE_NONE,
      CU_TENSOR_MAP_SWIZZLE_128B, CU_TENSOR_MAP_L2_PROMOTION_L2_128B, CU_TENSOR_MAP_FLOAT_OOB_FILL_NONE);
}
static void make_map3(EncodeFn enc, CUtensorMap* m, void* ptr, uint64_t d0, uint64_t cols, uint64_t rows, uint64_t blk_stride,
                      uint64_t nblocks, uint32_t nblk, uint32_t box_rows = 64) {
  cuuint64_t dims[3] = {d0, rows, nblocks};
  cuuint64_t strides[2] = {cols * 2, blk_stride * 2};
  cuuint32_t box[3] = {64, box_rows, nblk};
  cuuint32_t es[3] = {1, 1, 1};
  enc(m, CU_TENSOR_MAP_DATA_TYPE_BFLOAT16, 3, ptr, dims, strides, box, es, CU_TENSOR_MAP_INTERLEAVE_NONE,
      CU_TENSOR_MAP_SWIZZLE_128B, CU_TENSOR_MAP_L2_PROMOTION_L2_128B, CU_TENSOR_MAP_FLOAT_OOB_FILL_NONE);
}

extern "C" void kernel_launch(void* const* d_in, const int* in_sizes, int n_in, void* d_out, int out_size) {
  static Params prm;
  static void* cached[13] = {nullptr};
  static bool attr_done = false, by_smid = false;
  bool same = attr_done && cached[12] == d_out;
  for (int i = 0; i < 12 && same; i++) same = cached[i] == d_in[i];
  if (!same) {
    void* fn = nullptr;
    cudaDriverEntryPointQueryResult qr;
    cudaGetDriverEntryPoint("cuTensorMapEncodeTiled", &fn, cudaEnableDefault, &qr);
    EncodeFn enc = (EncodeFn)fn;
    void *pO, *pXT;
    cudaGetSymbolAddress(&pO, g_O);
    cudaGetSymbolAddress(&pXT, g_xT);
    make_map(enc, &prm.mapO, pO, DM, LSEQ, 64);
    make_map(enc, &prm.mapXT, pXT, LSEQ, 4 * DM, 64);
    prm.out = (bf16*)d_out;
    make_map(enc, &prm.mapX128, d_in[0], 2 * DM, LSEQ / 2, 128);
    make_map(enc, &prm.mapWo128, d_in[2], DM, DM, 128);
    make_map(enc, &prm.mapO128, pO, DM, LSEQ, 128);
    make_map3(enc, &prm.mapW3, d_in[1], DM, 3 * DM, DM, DM, 3, 3);
    make_map3(enc, &prm.mapW3h, d_in[1], DM, 3 * DM, DM, DM, 3, 3, 32);
    make_map3(enc, &prm.mapXT3, pXT, 64, LSEQ, 4 * DM, 64, 32, 2);
    prm.a_re = (const bf16*)d_in[4]; prm.a_im = (const bf16*)d_in[5];
    prm.b_re = (const bf16*)d_in[6]; prm.b_im = (const bf16*)d_in[7];
    prm.c_re = (const bf16*)d_in[8]; prm.c_im = (const bf16*)d_in[9];
    prm.log_dt = (const bf16*)d_in[10]; prm.dskip = (const bf16*)d_in[11];
    int dev = 0, sms = 0;
    cudaGetDevice(&dev);
    cudaDeviceGetAttribute(&sms, cudaDevAttrMultiProcessorCount, dev);
    by_smid = sms == 132;
    cudaFuncSetAttribute(fused_kernel<true>, cudaFuncAttributeMaxDynamicSharedMemorySize, SM_TOTAL);
    cudaFuncSetAttribute(fused_kernel<false>, cudaFuncAttributeMaxDynamicSharedMemorySize, SM_TOTAL);
    for (int i = 0; i < 12; i++) cached[i] = d_in[i];
    cached[12] = d_out;
    attr_done = true;
  }
  prm.stop = 100;
    if (by_smid) fused_kernel<true><<<132, NTHREADS, SM_TOTAL>>>(prm);
  else fused_kernel<false><<<NCTA, NTHREADS, SM_TOTAL>>>(prm);
}
```

```cpp
#include <cuda_runtime.h>
#include <cuda_bf16.h>
#include <cuda.h>
#include <stdint.h>

typedef __nv_bfloat16 bf16;

constexpr int LSEQ = 2048;
constexpr int DM = 512;
constexpr int NCTA = 128;
constexpr int NTHREADS = 512;
#define RR 0
#define KG_PRE 2
#define W2_LATE 0
#define FILL_AT 2
#define EXP_LATE 1
#define RFENCE 1
#define D_FIN 550
#define D_PREP 500
#define D_PST 0
#define D_HALO 300
#define STAG 2
#define D_ST 0
#define TLAYER 1
#define KG_PD 0
#define SUM_F32 0
#define CS_LATE0 0
#define D_HALO1 0
#define CS_FIRST 0
#define H_ORDER 1
#define D_START 200
#define CS_AT 4
#define KG_LAST 1
#define X_JIT 0
#define KG_GATE 2
#define R_CONS 192
#define R_HELP 88

constexpr int SM_X = 0;
constexpr int SM_W = 131072;
constexpr int SM_KVX = SM_X;
constexpr int SM_OST = SM_X + 32768;
constexpr int SM_WO = SM_X + 65536;
__host__ __device__ constexpr int sm_o(int c) { return c < 4 ? SM_W + c * 16384 : SM_X + (c - 4) * 16384; }
constexpr int SM_R = 196608;
constexpr int SM_T = 212992;
constexpr int SM_KC = 217088;
constexpr int KC_STRIDE = 648;
constexpr int SM_CS = SM_KC + 4 * KC_STRIDE * 2;
constexpr int SM_CW = SM_R + 8192;
constexpr int SM_EP = SM_CS + 768;
constexpr int SM_BAR = SM_EP + 16;
constexpr int SM_T2 = SM_BAR + 896;
constexpr int SM_HALO = SM_T2 + 4096;
constexpr int SM_ST = SM_HALO + 3072;
constexpr int SM_TOTAL = SM_HALO + 4096;
static_assert(SM_TOTAL <= 232448, "shared memory");

constexpr int CV_UH = 140 * 16;
constexpr int CV_PECH = 1120 * 4;
constexpr int CV_PBW = 2112 * 2;
__host__ __device__ constexpr int cv_s(int lc) { return SM_X + lc * 32768; }
__host__ __device__ constexpr int cv_u(int lc) { return cv_s(lc) + 4096; }
__host__ __device__ constexpr int cv_pe(int lc) { return cv_u(lc) + 2 * CV_UH; }
__host__ __device__ constexpr int cv_pb(int lc) { return cv_pe(lc) + CV_PECH; }
__host__ __device__ constexpr int cv_ft(int lc) { return cv_pb(lc) + 4 * CV_PBW; }
static_assert(cv_ft(0) + 1024 <= 32768, "conv buffers");
__host__ __device__ constexpr int cv_chan(int cta, int lc) { return cta + 128 * lc; }

enum {
  B_XF = 0,
  B_KVF = 8,
  B_OF = 16,
  B_WOF = 24,
  B_T = 31,
  B_RF = 28,
  B_RE = 29,
  B_CW = 30,
  B_GB = 35,
  B_EP = 36,
  B_ZF = 37,
  B_SD = 38,
  B_KVE = 40,
  B_AD = 45,
  B_OST = 46,
  B_QDONE = 47,
  B_PDONE = 48,
  B_S = 50,
  B_E = 54,
  B_P = 58,
  B_PE = 62,
  B_STF = 63,
  B_CSF = 64,
  B_HF = 65,
  B_U = 70,
  B_PS = 74,
  B_COUNT = 80
};

enum {
  C_CS = 0,
  C_G1 = 2,
  C_O = 4,
  C_COUNT = 20
};

__device__ __align__(128) unsigned g_cnt[C_COUNT * 32];
__device__ __align__(1024) bf16 g_O[LSEQ * DM];
__device__ __align__(1024) bf16 g_xT[4 * DM * LSEQ];
__device__ __align__(1024) float g_stats[2 * LSEQ * 2];
__device__ __align__(1024) uint4 g_colsum[8 * 16 * 48];
__device__ __align__(1024) uint4 g_halo[16 * 8 * 192];
__device__ __align__(1024) uint2 g_part[16 * 8 * 128];
#define TS(i) do { } while (0)

#define ATS(i, th) do { } while (0)
#define KTS(i) do { if (ht == 0) TS(i); } while (0)
#define FTS(i) do { } while (0)
#define LTS(i) do { } while (0)

struct Params {
  CUtensorMap mapO, mapXT, mapX128, mapWo128, mapO128, mapW3, mapW3h, mapXT3;
  const bf16 *a_re, *a_im, *b_re, *b_im, *c_re, *c_im, *log_dt, *dskip;
  bf16* out;
  int stop;
};

__device__ __forceinline__ uint32_t s32(const void* p) { return (uint32_t)__cvta_generic_to_shared(p); }
__device__ __forceinline__ void mbar_init(uint32_t b, int c) { asm volatile("mbarrier.init.shared::cta.b64 [%0], %1;" ::"r"(b), "r"(c) : "memory"); }
__device__ __forceinline__ void mbar_expect(uint32_t b, int bytes) { asm volatile("mbarrier.arrive.expect_tx.shared::cta.b64 _, [%0], %1;" ::"r"(b), "r"(bytes) : "memory"); }
__device__ __forceinline__ void mbar_arrive(uint32_t b) { asm volatile("mbarrier.arrive.shared::cta.b64 _, [%0];" ::"r"(b) : "memory"); }
__device__ __forceinline__ void mbar_arrive_if(uint32_t b, bool c) {
  asm volatile("{\n.reg .pred p;\nsetp.ne.u32 p, %1, 0;\n@p mbarrier.arrive.shared::cta.b64 _, [%0];\n}" ::"r"(b), "r"((uint32_t)c) : "memory");
}
__device__ __forceinline__ void mbar_wait(uint32_t b, int parity) {
  asm volatile("{\n.reg .pred p;\nWAIT_LOOP:\nmbarrier.try_wait.parity.shared::cta.b64 p, [%0], %1;\n@p bra WAIT_DONE;\nbra WAIT_LOOP;\nWAIT_DONE:\n}" ::"r"(b), "r"(parity) : "memory");
}
template <int N> __device__ __forceinline__ void delay() {
  if constexpr (N > 0) {
    uint32_t t0, t;
    asm volatile("mov.u32 %0, %%clock;" : "=r"(t0));
    do { asm volatile("mov.u32 %0, %%clock;" : "=r"(t)); } while (t - t0 < N);
  }
}
__device__ __forceinline__ int opaque_tid() { int v; asm volatile("mov.u32 %0, %%tid.x;" : "=r"(v)); return v; }
__device__ __forceinline__ bool elect_one() {
  uint32_t r;
  asm volatile("{\n.reg .pred p;\nelect.sync _|p, 0xffffffff;\nselp.u32 %0, 1, 0, p;\n}" : "=r"(r));
  return r != 0;
}
__device__ __forceinline__ void tma_ld(uint32_t dst, const CUtensorMap* m, int c0, int c1, uint32_t bar) {
  asm volatile("cp.async.bulk.tensor.2d.shared::cluster.global.mbarrier::complete_tx::bytes [%0], [%1, {%3, %4}], [%2];"
               ::"r"(dst), "l"(m), "r"(bar), "r"(c0), "r"(c1) : "memory");
}
__device__ __forceinline__ void tma_ld3(uint32_t dst, const CUtensorMap* m, int c0, int c1, int c2, uint32_t bar) {
  asm volatile("cp.async.bulk.tensor.3d.shared::cluster.global.mbarrier::complete_tx::bytes [%0], [%1, {%3, %4, %5}], [%2];"
               ::"r"(dst), "l"(m), "r"(bar), "r"(c0), "r"(c1), "r"(c2) : "memory");
}
__device__ __forceinline__ void tma_prefetch2(const CUtensorMap* m, int c0, int c1) {
  asm volatile("cp.async.bulk.prefetch.tensor.2d.L2.global.tile [%0, {%1, %2}];" ::"l"(m), "r"(c0), "r"(c1) : "memory");
}
__device__ __forceinline__ void tma_prefetch3(const CUtensorMap* m, int c0, int c1, int c2) {
  asm volatile("cp.async.bulk.prefetch.tensor.3d.L2.global.tile [%0, {%1, %2, %3}];" ::"l"(m), "r"(c0), "r"(c1), "r"(c2) : "memory");
}
__device__ __forceinline__ void tma_st(const CUtensorMap* m, int c0, int c1, uint32_t src) {
  asm volatile("cp.async.bulk.tensor.2d.global.shared::cta.bulk_group [%0, {%2, %3}], [%1];" ::"l"(m), "r"(src), "r"(c0), "r"(c1) : "memory");
}
__device__ __forceinline__ void bulk_ld(uint32_t dst, const void* src, int bytes, uint32_t bar) {
  asm volatile("cp.async.bulk.shared::cluster.global.mbarrier::complete_tx::bytes [%0], [%1], %2, [%3];" ::"r"(dst), "l"(src), "r"(bytes), "r"(bar) : "memory");
}
__device__ __forceinline__ void bulk_st(void* dst, uint32_t src, int bytes) {
  asm volatile("cp.async.bulk.global.shared::cta.bulk_group [%0], [%1], %2;" ::"l"(dst), "r"(src), "r"(bytes) : "memory");
}
__device__ __forceinline__ void bulk_red_add_f32(void* dst, uint32_t src, int bytes) {
  asm volatile("cp.reduce.async.bulk.global.shared::cta.bulk_group.add.f32 [%0], [%1], %2;" ::"l"(dst), "r"(src), "r"(bytes) : "memory");
}
__device__ __forceinline__ void bulk_commit() { asm volatile("cp.async.bulk.commit_group;" ::: "memory"); }
__device__ __forceinline__ void bulk_wait_all() { asm volatile("cp.async.bulk.wait_group 0;" ::: "memory"); }
__device__ __forceinline__ void fence_async_smem() { asm volatile("fence.proxy.async.shared::cta;" ::: "memory"); }
__device__ __forceinline__ void fence_writer() { if (!RFENCE) fence_async_smem(); }
__device__ __forceinline__ void fence_reader() { if (RFENCE) fence_async_smem(); }
__device__ __forceinline__ void fence_async_global() { asm volatile("fence.proxy.async.global;" ::: "memory"); }
__device__ __forceinline__ void bar_sync(int id, int n) { asm volatile("bar.sync %0, %1;" ::"r"(id), "r"(n) : "memory"); }
__device__ __forceinline__ void bar_arrive(int id, int n) { asm volatile("bar.arrive %0, %1;" ::"r"(id), "r"(n) : "memory"); }
__device__ __forceinline__ void wg_fence() { asm volatile("wgmma.fence.sync.aligned;" ::: "memory"); }
__device__ __forceinline__ void wg_commit() { asm volatile("wgmma.commit_group.sync.aligned;" ::: "memory"); }
template <int N> __device__ __forceinline__ void wg_wait() { asm volatile("wgmma.wait_group.sync.aligned %0;" ::"n"(N) : "memory"); }
__device__ __forceinline__ uint64_t mkdesc(uint32_t addr, uint32_t lbo, uint32_t sbo, int sw) {
  return (uint64_t)((addr & 0x3FFFF) >> 4) | ((uint64_t)(lbo >> 4) << 16) | ((uint64_t)(sbo >> 4) << 32) | ((uint64_t)sw << 62);
}
__device__ __forceinline__ void ldsm4(uint32_t* r, uint32_t a) {
  asm volatile("ldmatrix.sync.aligned.m8n8.x4.shared.b16 {%0,%1,%2,%3}, [%4];" : "=r"(r[0]), "=r"(r[1]), "=r"(r[2]), "=r"(r[3]) : "r"(a) : "memory");
}
__device__ __forceinline__ void ldsm4t(uint32_t* r, uint32_t a) {
  asm volatile("ldmatrix.sync.aligned.m8n8.x4.trans.shared.b16 {%0,%1,%2,%3}, [%4];" : "=r"(r[0]), "=r"(r[1]), "=r"(r[2]), "=r"(r[3]) : "r"(a) : "memory");
}
__device__ __forceinline__ void stsm4(uint32_t a, uint32_t r0, uint32_t r1, uint32_t r2, uint32_t r3) {
  asm volatile("stmatrix.sync.aligned.m8n8.x4.shared.b16 [%0], {%1,%2,%3,%4};" ::"r"(a), "r"(r0), "r"(r1), "r"(r2), "r"(r3) : "memory");
}
__device__ __forceinline__ void stsm4t(uint32_t a, uint32_t r0, uint32_t r1, uint32_t r2, uint32_t r3) {
  asm volatile("stmatrix.sync.aligned.m8n8.x4.trans.shared.b16 [%0], {%1,%2,%3,%4};" ::"r"(a), "r"(r0), "r"(r1), "r"(r2), "r"(r3) : "memory");
}
__device__ __forceinline__ uint32_t movm_t(uint32_t a) { uint32_t r; asm volatile("movmatrix.sync.aligned.m8n8.trans.b16 %0, %1;" : "=r"(r) : "r"(a)); return r; }
__device__ __forceinline__ uint32_t lds32(uint32_t a) { uint32_t v; asm volatile("ld.shared.b32 %0, [%1];" : "=r"(v) : "r"(a) : "memory"); return v; }
__device__ __forceinline__ float2 lds64f(uint32_t a) { float2 v; asm volatile("ld.shared.v2.f32 {%0,%1}, [%2];" : "=f"(v.x), "=f"(v.y) : "r"(a) : "memory"); return v; }
__device__ __forceinline__ float4 lds128f(uint32_t a) { float4 v; asm volatile("ld.shared.v4.f32 {%0,%1,%2,%3}, [%4];" : "=f"(v.x), "=f"(v.y), "=f"(v.z), "=f"(v.w) : "r"(a) : "memory"); return v; }
__device__ __forceinline__ uint4 lds128(uint32_t a) { uint4 v; asm volatile("ld.shared.v4.b32 {%0,%1,%2,%3}, [%4];" : "=r"(v.x), "=r"(v.y), "=r"(v.z), "=r"(v.w) : "r"(a) : "memory"); return v; }
__device__ __forceinline__ void sts128(uint32_t a, uint4 v) { asm volatile("st.shared.v4.b32 [%0], {%1,%2,%3,%4};" ::"r"(a), "r"(v.x), "r"(v.y), "r"(v.z), "r"(v.w) : "memory"); }
__device__ __forceinline__ void sts128f(uint32_t a, float x, float y, float z, float w) { asm volatile("st.shared.v4.f32 [%0], {%1,%2,%3,%4};" ::"r"(a), "f"(x), "f"(y), "f"(z), "f"(w) : "memory"); }
__device__ __forceinline__ void sts32f(uint32_t a, float v) { asm volatile("st.shared.f32 [%0], %1;" ::"r"(a), "f"(v) : "memory"); }
__device__ __forceinline__ void sts16(uint32_t a, uint16_t v) { asm volatile("st.shared.u16 [%0], %1;" ::"r"(a), "h"(v) : "memory"); }
__device__ __forceinline__ uint32_t lds16(uint32_t a) { uint16_t v; asm volatile("ld.shared.u16 %0, [%1];" : "=h"(v) : "r"(a) : "memory"); return v; }
__device__ __forceinline__ uint32_t packbf(float lo, float hi) { uint32_t r; asm("cvt.rn.bf16x2.f32 %0, %1, %2;" : "=r"(r) : "f"(hi), "f"(lo)); return r; }
__device__ __forceinline__ float bf_lo(uint32_t v) { return __uint_as_float(v << 16); }
__device__ __forceinline__ float bf_hi(uint32_t v) { return __uint_as_float(v & 0xffff0000u); }
__device__ __forceinline__ float ex2(float x) { float r; asm("ex2.approx.ftz.f32 %0, %1;" : "=f"(r) : "f"(x)); return r; }
__device__ __forceinline__ float rsqrt_approx(float x) { float r; asm("rsqrt.approx.ftz.f32 %0, %1;" : "=f"(r) : "f"(x)); return r; }
__device__ __forceinline__ float rcp_approx(float x) { float r; asm("rcp.approx.ftz.f32 %0, %1;" : "=f"(r) : "f"(x)); return r; }
__device__ __forceinline__ void mma_bf16(float* d, const uint32_t* a, uint32_t b0, uint32_t b1) {
  asm("mma.sync.aligned.m16n8k16.row.col.f32.bf16.bf16.f32 {%0,%1,%2,%3}, {%4,%5,%6,%7}, {%8,%9}, {%0,%1,%2,%3};"
               : "+f"(d[0]), "+f"(d[1]), "+f"(d[2]), "+f"(d[3]) : "r"(a[0]), "r"(a[1]), "r"(a[2]), "r"(a[3]), "r"(b0), "r"(b1));
}
__device__ __forceinline__ void mma_bf16_k8(float* d, uint32_t a0, uint32_t a1, uint32_t b) {
  asm("mma.sync.aligned.m16n8k8.row.col.f32.bf16.bf16.f32 {%0,%1,%2,%3}, {%4,%5}, {%6}, {%0,%1,%2,%3};"
      : "+f"(d[0]), "+f"(d[1]), "+f"(d[2]), "+f"(d[3]) : "r"(a0), "r"(a1), "r"(b));
}
__device__ __forceinline__ void red_release(unsigned* p) { asm volatile("red.release.gpu.global.add.u32 [%0], 1;" ::"l"(p) : "memory"); }
__device__ __forceinline__ void red_relaxed(unsigned* p) { asm volatile("red.relaxed.gpu.global.add.u32 [%0], 1;" ::"l"(p) : "memory"); }
__device__ __forceinline__ unsigned ld_relaxed(const unsigned* p) { unsigned v; asm volatile("ld.relaxed.gpu.global.u32 %0, [%1];" : "=r"(v) : "l"(p) : "memory"); return v; }
__device__ __forceinline__ void spin_until(const unsigned* p, unsigned target) {
  int it = 0;
  while ((int)(ld_relaxed(p) - target) < 0) {
    if (++it > (1 << 23)) __trap();
  }
}
__device__ __forceinline__ uint4 ldcg128(const void* p) { uint4 v; asm volatile("ld.global.cg.v4.b32 {%0,%1,%2,%3}, [%4];" : "=r"(v.x), "=r"(v.y), "=r"(v.z), "=r"(v.w) : "l"(p) : "memory"); return v; }
__device__ __forceinline__ uint4 ld_tagged(const uint4* p) { uint4 v; asm volatile("ld.relaxed.gpu.global.v4.u32 {%0,%1,%2,%3}, [%4];" : "=r"(v.x), "=r"(v.y), "=r"(v.z), "=r"(v.w) : "l"(p) : "memory"); return v; }
__device__ __forceinline__ uint2 ld_part(const uint2* p) { uint2 v; asm volatile("ld.relaxed.gpu.global.v2.u32 {%0,%1}, [%2];" : "=r"(v.x), "=r"(v.y) : "l"(p) : "memory"); return v; }
__device__ __forceinline__ void st_part(uint2* p, float s, float q, uint32_t tag) {
  asm volatile("st.relaxed.gpu.global.v2.u32 [%0], {%1,%2};" ::"l"(p), "r"(__float_as_uint(s)), "r"((__float_as_uint(q) & ~7u) | tag) : "memory");
}
__device__ __forceinline__ uint32_t part_tag(uint32_t epoch, int k) { return (4 * (epoch % 7) + k) % 7 + 1; }
__device__ __forceinline__ void st_tagged3(uint4* p, uint32_t a, uint32_t b, uint32_t c, uint32_t tag) { asm volatile("st.relaxed.gpu.global.v4.u32 [%0], {%1,%2,%3,%4};" ::"l"(p), "r"(a), "r"(b), "r"(c), "r"(tag) : "memory"); }
__device__ __forceinline__ uint32_t hadd2(uint32_t a, uint32_t b) { uint32_t r; asm("add.rn.bf16x2 %0, %1, %2;" : "=r"(r) : "r"(a), "r"(b)); return r; }
__device__ __forceinline__ uint32_t hmul2(uint32_t a, uint32_t b) { uint32_t r; asm("mul.rn.bf16x2 %0, %1, %2;" : "=r"(r) : "r"(a), "r"(b)); return r; }

template<int N,int TB> __device__ __forceinline__ void wgmma_rs(float* d, const uint32_t* a, uint64_t db, int sd);
template<int N,int TA,int TB> __device__ __forceinline__ void wgmma_ss(float* d, uint64_t da, uint64_t db, int sd);
template<> __device__ __forceinline__ void wgmma_rs<128,0>(float* d, const uint32_t* a, uint64_t db, int sd) {
  asm volatile("{\n.reg .pred p;\nsetp.ne.b32 p, %69, 0;\nwgmma.mma_async.sync.aligned.m64n128k16.f32.bf16.bf16 {%0,%1,%2,%3,%4,%5,%6,%7,%8,%9,%10,%11,%12,%13,%14,%15,%16,%17,%18,%19,%20,%21,%22,%23,%24,%25,%26,%27,%28,%29,%30,%31,%32,%33,%34,%35,%36,%37,%38,%39,%40,%41,%42,%43,%44,%45,%46,%47,%48,%49,%50,%51,%52,%53,%54,%55,%56,%57,%58,%59,%60,%61,%62,%63}, {%64,%65,%66,%67}, %68, p, 1, 1, 0;\n}\n"
   : "+f"(d[0]),"+f"(d[1]),"+f"(d[2]),"+f"(d[3]),"+f"(d[4]),"+f"(d[5]),"+f"(d[6]),"+f"(d[7]),"+f"(d[8]),"+f"(d[9]),"+f"(d[10]),"+f"(d[11]),"+f"(d[12]),"+f"(d[13]),"+f"(d[14]),"+f"(d[15]),"+f"(d[16]),"+f"(d[17]),"+f"(d[18]),"+f"(d[19]),"+f"(d[20]),"+f"(d[21]),"+f"(d[22]),"+f"(d[23]),"+f"(d[24]),"+f"(d[25]),"+f"(d[26]),"+f"(d[27]),"+f"(d[28]),"+f"(d[29]),"+f"(d[30]),"+f"(d[31]),"+f"(d[32]),"+f"(d[33]),"+f"(d[34]),"+f"(d[35]),"+f"(d[36]),"+f"(d[37]),"+f"(d[38]),"+f"(d[39]),"+f"(d[40]),"+f"(d[41]),"+f"(d[42]),"+f"(d[43]),"+f"(d[44]),"+f"(d[45]),"+f"(d[46]),"+f"(d[47]),"+f"(d[48]),"+f"(d[49]),"+f"(d[50]),"+f"(d[51]),"+f"(d[52]),"+f"(d[53]),"+f"(d[54]),"+f"(d[55]),"+f"(d[56]),"+f"(d[57]),"+f"(d[58]),"+f"(d[59]),"+f"(d[60]),"+f"(d[61]),"+f"(d[62]),"+f"(d[63])
   : "r"(a[0]), "r"(a[1]), "r"(a[2]), "r"(a[3]), "l"(db), "r"(sd));
}
template<> __device__ __forceinline__ void wgmma_rs<120,0>(float* d, const uint32_t* a, uint64_t db, int sd) {
  asm volatile("{\n.reg .pred p;\nsetp.ne.b32 p, %65, 0;\nwgmma.mma_async.sync.aligned.m64n120k16.f32.bf16.bf16 {%0,%1,%2,%3,%4,%5,%6,%7,%8,%9,%10,%11,%12,%13,%14,%15,%16,%17,%18,%19,%20,%21,%22,%23,%24,%25,%26,%27,%28,%29,%30,%31,%32,%33,%34,%35,%36,%37,%38,%39,%40,%41,%42,%43,%44,%45,%46,%47,%48,%49,%50,%51,%52,%53,%54,%55,%56,%57,%58,%59}, {%60,%61,%62,%63}, %64, p, 1, 1, 0;\n}\n"
   : "+f"(d[0]),"+f"(d[1]),"+f"(d[2]),"+f"(d[3]),"+f"(d[4]),"+f"(d[5]),"+f"(d[6]),"+f"(d[7]),"+f"(d[8]),"+f"(d[9]),"+f"(d[10]),"+f"(d[11]),"+f"(d[12]),"+f"(d[13]),"+f"(d[14]),"+f"(d[15]),"+f"(d[16]),"+f"(d[17]),"+f"(d[18]),"+f"(d[19]),"+f"(d[20]),"+f"(d[21]),"+f"(d[22]),"+f"(d[23]),"+f"(d[24]),"+f"(d[25]),"+f"(d[26]),"+f"(d[27]),"+f"(d[28]),"+f"(d[29]),"+f"(d[30]),"+f"(d[31]),"+f"(d[32]),"+f"(d[33]),"+f"(d[34]),"+f"(d[35]),"+f"(d[36]),"+f"(d[37]),"+f"(d[38]),"+f"(d[39]),"+f"(d[40]),"+f"(d[41]),"+f"(d[42]),"+f"(d[43]),"+f"(d[44]),"+f"(d[45]),"+f"(d[46]),"+f"(d[47]),"+f"(d[48]),"+f"(d[49]),"+f"(d[50]),"+f"(d[51]),"+f"(d[52]),"+f"(d[53]),"+f"(d[54]),"+f"(d[55]),"+f"(d[56]),"+f"(d[57]),"+f"(d[58]),"+f"(d[59])
   : "r"(a[0]), "r"(a[1]), "r"(a[2]), "r"(a[3]), "l"(db), "r"(sd));
}
template<> __device__ __forceinline__ void wgmma_rs<112,0>(float* d, const uint32_t* a, uint64_t db, int sd) {
  asm volatile("{\n.reg .pred p;\nsetp.ne.b32 p, %61, 0;\nwgmma.mma_async.sync.aligned.m64n112k16.f32.bf16.bf16 {%0,%1,%2,%3,%4,%5,%6,%7,%8,%9,%10,%11,%12,%13,%14,%15,%16,%17,%18,%19,%20,%21,%22,%23,%24,%25,%26,%27,%28,%29,%30,%31,%32,%33,%34,%35,%36,%37,%38,%39,%40,%41,%42,%43,%44,%45,%46,%47,%48,%49,%50,%51,%52,%53,%54,%55}, {%56,%57,%58,%59}, %60, p, 1, 1, 0;\n}\n"
   : "+f"(d[0]),"+f"(d[1]),"+f"(d[2]),"+f"(d[3]),"+f"(d[4]),"+f"(d[5]),"+f"(d[6]),"+f"(d[7]),"+f"(d[8]),"+f"(d[9]),"+f"(d[10]),"+f"(d[11]),"+f"(d[12]),"+f"(d[13]),"+f"(d[14]),"+f"(d[15]),"+f"(d[16]),"+f"(d[17]),"+f"(d[18]),"+f"(d[19]),"+f"(d[20]),"+f"(d[21]),"+f"(d[22]),"+f"(d[23]),"+f"(d[24]),"+f"(d[25]),"+f"(d[26]),"+f"(d[27]),"+f"(d[28]),"+f"(d[29]),"+f"(d[30]),"+f"(d[31]),"+f"(d[32]),"+f"(d[33]),"+f"(d[34]),"+f"(d[35]),"+f"(d[36]),"+f"(d[37]),"+f"(d[38]),"+f"(d[39]),"+f"(d[40]),"+f"(d[41]),"+f"(d[42]),"+f"(d[43]),"+f"(d[44]),"+f"(d[45]),"+f"(d[46]),"+f"(d[47]),"+f"(d[48]),"+f"(d[49]),"+f"(d[50]),"+f"(d[51]),"+f"(d[52]),"+f"(d[53]),"+f"(d[54]),"+f"(d[55])
   : "r"(a[0]), "r"(a[1]), "r"(a[2]), "r"(a[3]), "l"(db), "r"(sd));
}
template<> __device__ __forceinline__ void wgmma_rs<104,0>(float* d, const uint32_t* a, uint64_t db, int sd) {
  asm volatile("{\n.reg .pred p;\nsetp.ne.b32 p, %57, 0;\nwgmma.mma_async.sync.aligned.m64n104k16.f32.bf16.bf16 {%0,%1,%2,%3,%4,%5,%6,%7,%8,%9,%10,%11,%12,%13,%14,%15,%16,%17,%18,%19,%20,%21,%22,%23,%24,%25,%26,%27,%28,%29,%30,%31,%32,%33,%34,%35,%36,%37,%38,%39,%40,%41,%42,%43,%44,%45,%46,%47,%48,%49,%50,%51}, {%52,%53,%54,%55}, %56, p, 1, 1, 0;\n}\n"
   : "+f"(d[0]),"+f"(d[1]),"+f"(d[2]),"+f"(d[3]),"+f"(d[4]),"+f"(d[5]),"+f"(d[6]),"+f"(d[7]),"+f"(d[8]),"+f"(d[9]),"+f"(d[10]),"+f"(d[11]),"+f"(d[12]),"+f"(d[13]),"+f"(d[14]),"+f"(d[15]),"+f"(d[16]),"+f"(d[17]),"+f"(d[18]),"+f"(d[19]),"+f"(d[20]),"+f"(d[21]),"+f"(d[22]),"+f"(d[23]),"+f"(d[24]),"+f"(d[25]),"+f"(d[26]),"+f"(d[27]),"+f"(d[28]),"+f"(d[29]),"+f"(d[30]),"+f"(d[31]),"+f"(d[32]),"+f"(d[33]),"+f"(d[34]),"+f"(d[35]),"+f"(d[36]),"+f"(d[37]),"+f"(d[38]),"+f"(d[39]),"+f"(d[40]),"+f"(d[41]),"+f"(d[42]),"+f"(d[43]),"+f"(d[44]),"+f"(d[45]),"+f"(d[46]),"+f"(d[47]),"+f"(d[48]),"+f"(d[49]),"+f"(d[50]),"+f"(d[51])
   : "r"(a[0]), "r"(a[1]), "r"(a[2]), "r"(a[3]), "l"(db), "r"(sd));
}
template<> __device__ __forceinline__ void wgmma_rs<96,0>(float* d, const uint32_t* a, uint64_t db, int sd) {
  asm volatile("{\n.reg .pred p;\nsetp.ne.b32 p, %53, 0;\nwgmma.mma_async.sync.aligned.m64n96k16.f32.bf16.bf16 {%0,%1,%2,%3,%4,%5,%6,%7,%8,%9,%10,%11,%12,%13,%14,%15,%16,%17,%18,%19,%20,%21,%22,%23,%24,%25,%26,%27,%28,%29,%30,%31,%32,%33,%34,%35,%36,%37,%38,%39,%40,%41,%42,%43,%44,%45,%46,%47}, {%48,%49,%50,%51}, %52, p, 1, 1, 0;\n}\n"
   : "+f"(d[0]),"+f"(d[1]),"+f"(d[2]),"+f"(d[3]),"+f"(d[4]),"+f"(d[5]),"+f"(d[6]),"+f"(d[7]),"+f"(d[8]),"+f"(d[9]),"+f"(d[10]),"+f"(d[11]),"+f"(d[12]),"+f"(d[13]),"+f"(d[14]),"+f"(d[15]),"+f"(d[16]),"+f"(d[17]),"+f"(d[18]),"+f"(d[19]),"+f"(d[20]),"+f"(d[21]),"+f"(d[22]),"+f"(d[23]),"+f"(d[24]),"+f"(d[25]),"+f"(d[26]),"+f"(d[27]),"+f"(d[28]),"+f"(d[29]),"+f"(d[30]),"+f"(d[31]),"+f"(d[32]),"+f"(d[33]),"+f"(d[34]),"+f"(d[35]),"+f"(d[36]),"+f"(d[37]),"+f"(d[38]),"+f"(d[39]),"+f"(d[40]),"+f"(d[41]),"+f"(d[42]),"+f"(d[43]),"+f"(d[44]),"+f"(d[45]),"+f"(d[46]),"+f"(d[47])
   : "r"(a[0]), "r"(a[1]), "r"(a[2]), "r"(a[3]), "l"(db), "r"(sd));
}
template<> __device__ __forceinline__ void wgmma_rs<88,0>(float* d, const uint32_t* a, uint64_t db, int sd) {
  asm volatile("{\n.reg .pred p;\nsetp.ne.b32 p, %49, 0;\nwgmma.mma_async.sync.aligned.m64n88k16.f32.bf16.bf16 {%0,%1,%2,%3,%4,%5,%6,%7,%8,%9,%10,%11,%12,%13,%14,%15,%16,%17,%18,%19,%20,%21,%22,%23,%24,%25,%26,%27,%28,%29,%30,%31,%32,%33,%34,%35,%36,%37,%38,%39,%40,%41,%42,%43}, {%44,%45,%46,%47}, %48, p, 1, 1, 0;\n}\n"
   : "+f"(d[0]),"+f"(d[1]),"+f"(d[2]),"+f"(d[3]),"+f"(d[4]),"+f"(d[5]),"+f"(d[6]),"+f"(d[7]),"+f"(d[8]),"+f"(d[9]),"+f"(d[10]),"+f"(d[11]),"+f"(d[12]),"+f"(d[13]),"+f"(d[14]),"+f"(d[15]),"+f"(d[16]),"+f"(d[17]),"+f"(d[18]),"+f"(d[19]),"+f"(d[20]),"+f"(d[21]),"+f"(d[22]),"+f"(d[23]),"+f"(d[24]),"+f"(d[25]),"+f"(d[26]),"+f"(d[27]),"+f"(d[28]),"+f"(d[29]),"+f"(d[30]),"+f"(d[31]),"+f"(d[32]),"+f"(d[33]),"+f"(d[34]),"+f"(d[35]),"+f"(d[36]),"+f"(d[37]),"+f"(d[38]),"+f"(d[39]),"+f"(d[40]),"+f"(d[41]),"+f"(d[42]),"+f"(d[43])
   : "r"(a[0]), "r"(a[1]), "r"(a[2]), "r"(a[3]), "l"(db), "r"(sd));
}
template<> __device__ __forceinline__ void wgmma_rs<80,0>(float* d, const uint32_t* a, uint64_t db, int sd) {
  asm volatile("{\n.reg .pred p;\nsetp.ne.b32 p, %45, 0;\nwgmma.mma_async.sync.aligned.m64n80k16.f32.bf16.bf16 {%0,%1,%2,%3,%4,%5,%6,%7,%8,%9,%10,%11,%12,%13,%14,%15,%16,%17,%18,%19,%20,%21,%22,%23,%24,%25,%26,%27,%28,%29,%30,%31,%32,%33,%34,%35,%36,%37,%38,%39}, {%40,%41,%42,%43}, %44, p, 1, 1, 0;\n}\n"
   : "+f"(d[0]),"+f"(d[1]),"+f"(d[2]),"+f"(d[3]),"+f"(d[4]),"+f"(d[5]),"+f"(d[6]),"+f"(d[7]),"+f"(d[8]),"+f"(d[9]),"+f"(d[10]),"+f"(d[11]),"+f"(d[12]),"+f"(d[13]),"+f"(d[14]),"+f"(d[15]),"+f"(d[16]),"+f"(d[17]),"+f"(d[18]),"+f"(d[19]),"+f"(d[20]),"+f"(d[21]),"+f"(d[22]),"+f"(d[23]),"+f"(d[24]),"+f"(d[25]),"+f"(d[26]),"+f"(d[27]),"+f"(d[28]),"+f"(d[29]),"+f"(d[30]),"+f"(d[31]),"+f"(d[32]),"+f"(d[33]),"+f"(d[34]),"+f"(d[35]),"+f"(d[36]),"+f"(d[37]),"+f"(d[38]),"+f"(d[39])
   : "r"(a[0]), "r"(a[1]), "r"(a[2]), "r"(a[3]), "l"(db), "r"(sd));
}
template<> __device__ __forceinline__ void wgmma_rs<72,0>(float* d, const uint32_t* a, uint64_t db, int sd) {
  asm volatile("{\n.reg .pred p;\nsetp.ne.b32 p, %41, 0;\nwgmma.mma_async.sync.aligned.m64n72k16.f32.bf16.bf16 {%0,%1,%2,%3,%4,%5,%6,%7,%8,%9,%10,%11,%12,%13,%14,%15,%16,%17,%18,%19,%20,%21,%22,%23,%24,%25,%26,%27,%28,%29,%30,%31,%32,%33,%34,%35}, {%36,%37,%38,%39}, %40, p, 1, 1, 0;\n}\n"
   : "+f"(d[0]),"+f"(d[1]),"+f"(d[2]),"+f"(d[3]),"+f"(d[4]),"+f"(d[5]),"+f"(d[6]),"+f"(d[7]),"+f"(d[8]),"+f"(d[9]),"+f"(d[10]),"+f"(d[11]),"+f"(d[12]),"+f"(d[13]),"+f"(d[14]),"+f"(d[15]),"+f"(d[16]),"+f"(d[17]),"+f"(d[18]),"+f"(d[19]),"+f"(d[20]),"+f"(d[21]),"+f"(d[22]),"+f"(d[23]),"+f"(d[24]),"+f"(d[25]),"+f"(d[26]),"+f"(d[27]),"+f"(d[28]),"+f"(d[29]),"+f"(d[30]),"+f"(d[31]),"+f"(d[32]),"+f"(d[33]),"+f"(d[34]),"+f"(d[35])
   : "r"(a[0]), "r"(a[1]), "r"(a[2]), "r"(a[3]), "l"(db), "r"(sd));
}
template<> __device__ __forceinline__ void wgmma_rs<64,0>(float* d, const uint32_t* a, uint64_t db, int sd) {
  asm volatile("{\n.reg .pred p;\nsetp.ne.b32 p, %37, 0;\nwgmma.mma_async.sync.aligned.m64n64k16.f32.bf16.bf16 {%0,%1,%2,%3,%4,%5,%6,%7,%8,%9,%10,%11,%12,%13,%14,%15,%16,%17,%18,%19,%20,%21,%22,%23,%24,%25,%26,%27,%28,%29,%30,%31}, {%32,%33,%34,%35}, %36, p, 1, 1, 0;\n}\n"
   : "+f"(d[0]),"+f"(d[1]),"+f"(d[2]),"+f"(d[3]),"+f"(d[4]),"+f"(d[5]),"+f"(d[6]),"+f"(d[7]),"+f"(d[8]),"+f"(d[9]),"+f"(d[10]),"+f"(d[11]),"+f"(d[12]),"+f"(d[13]),"+f"(d[14]),"+f"(d[15]),"+f"(d[16]),"+f"(d[17]),"+f"(d[18]),"+f"(d[19]),"+f"(d[20]),"+f"(d[21]),"+f"(d[22]),"+f"(d[23]),"+f"(d[24]),"+f"(d[25]),"+f"(d[26]),"+f"(d[27]),"+f"(d[28]),"+f"(d[29]),"+f"(d[30]),"+f"(d[31])
   : "r"(a[0]), "r"(a[1]), "r"(a[2]), "r"(a[3]), "l"(db), "r"(sd));
}
template<> __device__ __forceinline__ void wgmma_ss<64,0,1>(float* d, uint64_t da, uint64_t db, int sd) {
  asm volatile("{\n.reg .pred p;\nsetp.ne.b32 p, %34, 0;\nwgmma.mma_async.sync.aligned.m64n64k16.f32.bf16.bf16 {%0,%1,%2,%3,%4,%5,%6,%7,%8,%9,%10,%11,%12,%13,%14,%15,%16,%17,%18,%19,%20,%21,%22,%23,%24,%25,%26,%27,%28,%29,%30,%31}, %32, %33, p, 1, 1, 0, 1;\n}\n"
   : "+f"(d[0]),"+f"(d[1]),"+f"(d[2]),"+f"(d[3]),"+f"(d[4]),"+f"(d[5]),"+f"(d[6]),"+f"(d[7]),"+f"(d[8]),"+f"(d[9]),"+f"(d[10]),"+f"(d[11]),"+f"(d[12]),"+f"(d[13]),"+f"(d[14]),"+f"(d[15]),"+f"(d[16]),"+f"(d[17]),"+f"(d[18]),"+f"(d[19]),"+f"(d[20]),"+f"(d[21]),"+f"(d[22]),"+f"(d[23]),"+f"(d[24]),"+f"(d[25]),"+f"(d[26]),"+f"(d[27]),"+f"(d[28]),"+f"(d[29]),"+f"(d[30]),"+f"(d[31])
   : "l"(da), "l"(db), "r"(sd));
}
template<> __device__ __forceinline__ void wgmma_ss<64,1,1>(float* d, uint64_t da, uint64_t db, int sd) {
  asm volatile("{\n.reg .pred p;\nsetp.ne.b32 p, %34, 0;\nwgmma.mma_async.sync.aligned.m64n64k16.f32.bf16.bf16 {%0,%1,%2,%3,%4,%5,%6,%7,%8,%9,%10,%11,%12,%13,%14,%15,%16,%17,%18,%19,%20,%21,%22,%23,%24,%25,%26,%27,%28,%29,%30,%31}, %32, %33, p, 1, 1, 1, 1;\n}\n"
   : "+f"(d[0]),"+f"(d[1]),"+f"(d[2]),"+f"(d[3]),"+f"(d[4]),"+f"(d[5]),"+f"(d[6]),"+f"(d[7]),"+f"(d[8]),"+f"(d[9]),"+f"(d[10]),"+f"(d[11]),"+f"(d[12]),"+f"(d[13]),"+f"(d[14]),"+f"(d[15]),"+f"(d[16]),"+f"(d[17]),"+f"(d[18]),"+f"(d[19]),"+f"(d[20]),"+f"(d[21]),"+f"(d[22]),"+f"(d[23]),"+f"(d[24]),"+f"(d[25]),"+f"(d[26]),"+f"(d[27]),"+f"(d[28]),"+f"(d[29]),"+f"(d[30]),"+f"(d[31])
   : "l"(da), "l"(db), "r"(sd));
}
template<> __device__ __forceinline__ void wgmma_ss<192,0,1>(float* d, uint64_t da, uint64_t db, int sd) {
  asm volatile("{\n.reg .pred p;\nsetp.ne.b32 p, %98, 0;\nwgmma.mma_async.sync.aligned.m64n192k16.f32.bf16.bf16 {%0,%1,%2,%3,%4,%5,%6,%7,%8,%9,%10,%11,%12,%13,%14,%15,%16,%17,%18,%19,%20,%21,%22,%23,%24,%25,%26,%27,%28,%29,%30,%31,%32,%33,%34,%35,%36,%37,%38,%39,%40,%41,%42,%43,%44,%45,%46,%47,%48,%49,%50,%51,%52,%53,%54,%55,%56,%57,%58,%59,%60,%61,%62,%63,%64,%65,%66,%67,%68,%69,%70,%71,%72,%73,%74,%75,%76,%77,%78,%79,%80,%81,%82,%83,%84,%85,%86,%87,%88,%89,%90,%91,%92,%93,%94,%95}, %96, %97, p, 1, 1, 0, 1;\n}\n"
   : "+f"(d[0]),"+f"(d[1]),"+f"(d[2]),"+f"(d[3]),"+f"(d[4]),"+f"(d[5]),"+f"(d[6]),"+f"(d[7]),"+f"(d[8]),"+f"(d[9]),"+f"(d[10]),"+f"(d[11]),"+f"(d[12]),"+f"(d[13]),"+f"(d[14]),"+f"(d[15]),"+f"(d[16]),"+f"(d[17]),"+f"(d[18]),"+f"(d[19]),"+f"(d[20]),"+f"(d[21]),"+f"(d[22]),"+f"(d[23]),"+f"(d[24]),"+f"(d[25]),"+f"(d[26]),"+f"(d[27]),"+f"(d[28]),"+f"(d[29]),"+f"(d[30]),"+f"(d[31]),"+f"(d[32]),"+f"(d[33]),"+f"(d[34]),"+f"(d[35]),"+f"(d[36]),"+f"(d[37]),"+f"(d[38]),"+f"(d[39]),"+f"(d[40]),"+f"(d[41]),"+f"(d[42]),"+f"(d[43]),"+f"(d[44]),"+f"(d[45]),"+f"(d[46]),"+f"(d[47]),"+f"(d[48]),"+f"(d[49]),"+f"(d[50]),"+f"(d[51]),"+f"(d[52]),"+f"(d[53]),"+f"(d[54]),"+f"(d[55]),"+f"(d[56]),"+f"(d[57]),"+f"(d[58]),"+f"(d[59]),"+f"(d[60]),"+f"(d[61]),"+f"(d[62]),"+f"(d[63]),"+f"(d[64]),"+f"(d[65]),"+f"(d[66]),"+f"(d[67]),"+f"(d[68]),"+f"(d[69]),"+f"(d[70]),"+f"(d[71]),"+f"(d[72]),"+f"(d[73]),"+f"(d[74]),"+f"(d[75]),"+f"(d[76]),"+f"(d[77]),"+f"(d[78]),"+f"(d[79]),"+f"(d[80]),"+f"(d[81]),"+f"(d[82]),"+f"(d[83]),"+f"(d[84]),"+f"(d[85]),"+f"(d[86]),"+f"(d[87]),"+f"(d[88]),"+f"(d[89]),"+f"(d[90]),"+f"(d[91]),"+f"(d[92]),"+f"(d[93]),"+f"(d[94]),"+f"(d[95])
   : "l"(da), "l"(db), "r"(sd));
}
template<> __device__ __forceinline__ void wgmma_ss<192,1,1>(float* d, uint64_t da, uint64_t db, int sd) {
  asm volatile("{\n.reg .pred p;\nsetp.ne.b32 p, %98, 0;\nwgmma.mma_async.sync.aligned.m64n192k16.f32.bf16.bf16 {%0,%1,%2,%3,%4,%5,%6,%7,%8,%9,%10,%11,%12,%13,%14,%15,%16,%17,%18,%19,%20,%21,%22,%23,%24,%25,%26,%27,%28,%29,%30,%31,%32,%33,%34,%35,%36,%37,%38,%39,%40,%41,%42,%43,%44,%45,%46,%47,%48,%49,%50,%51,%52,%53,%54,%55,%56,%57,%58,%59,%60,%61,%62,%63,%64,%65,%66,%67,%68,%69,%70,%71,%72,%73,%74,%75,%76,%77,%78,%79,%80,%81,%82,%83,%84,%85,%86,%87,%88,%89,%90,%91,%92,%93,%94,%95}, %96, %97, p, 1, 1, 1, 1;\n}\n"
   : "+f"(d[0]),"+f"(d[1]),"+f"(d[2]),"+f"(d[3]),"+f"(d[4]),"+f"(d[5]),"+f"(d[6]),"+f"(d[7]),"+f"(d[8]),"+f"(d[9]),"+f"(d[10]),"+f"(d[11]),"+f"(d[12]),"+f"(d[13]),"+f"(d[14]),"+f"(d[15]),"+f"(d[16]),"+f"(d[17]),"+f"(d[18]),"+f"(d[19]),"+f"(d[20]),"+f"(d[21]),"+f"(d[22]),"+f"(d[23]),"+f"(d[24]),"+f"(d[25]),"+f"(d[26]),"+f"(d[27]),"+f"(d[28]),"+f"(d[29]),"+f"(d[30]),"+f"(d[31]),"+f"(d[32]),"+f"(d[33]),"+f"(d[34]),"+f"(d[35]),"+f"(d[36]),"+f"(d[37]),"+f"(d[38]),"+f"(d[39]),"+f"(d[40]),"+f"(d[41]),"+f"(d[42]),"+f"(d[43]),"+f"(d[44]),"+f"(d[45]),"+f"(d[46]),"+f"(d[47]),"+f"(d[48]),"+f"(d[49]),"+f"(d[50]),"+f"(d[51]),"+f"(d[52]),"+f"(d[53]),"+f"(d[54]),"+f"(d[55]),"+f"(d[56]),"+f"(d[57]),"+f"(d[58]),"+f"(d[59]),"+f"(d[60]),"+f"(d[61]),"+f"(d[62]),"+f"(d[63]),"+f"(d[64]),"+f"(d[65]),"+f"(d[66]),"+f"(d[67]),"+f"(d[68]),"+f"(d[69]),"+f"(d[70]),"+f"(d[71]),"+f"(d[72]),"+f"(d[73]),"+f"(d[74]),"+f"(d[75]),"+f"(d[76]),"+f"(d[77]),"+f"(d[78]),"+f"(d[79]),"+f"(d[80]),"+f"(d[81]),"+f"(d[82]),"+f"(d[83]),"+f"(d[84]),"+f"(d[85]),"+f"(d[86]),"+f"(d[87]),"+f"(d[88]),"+f"(d[89]),"+f"(d[90]),"+f"(d[91]),"+f"(d[92]),"+f"(d[93]),"+f"(d[94]),"+f"(d[95])
   : "l"(da), "l"(db), "r"(sd));
}

__device__ __forceinline__ void stats_publish(uint32_t sb, int layer, int rb, int hg, int ht, uint32_t tag) {
  const int lane = ht & 31, w = ht >> 5, g = lane >> 2, t = lane & 3, ks = hg & 3;
  uint32_t xa;
  if (layer == 0) {
    const int row = 16 * w + (lane & 15), kc = 2 * ks + (lane >> 4);
    xa = row * 128 + ((kc ^ (row & 7)) << 4);
  } else {
    const int k = 16 * ks + (lane & 7) + 8 * (lane >> 4), pc = 2 * w + ((lane >> 3) & 1);
    xa = k * 128 + ((pc ^ (k & 7)) << 4);
  }
  float s[4] = {0.f, 0.f, 0.f, 0.f}, q[4] = {0.f, 0.f, 0.f, 0.f};
#pragma unroll 1
  for (int c = hg >> 2; c < 8; c += 2) {
    mbar_wait(sb + SM_BAR + 8 * (B_XF + c), layer);
    if (c >= 6) ATS(48, 256);
    if (c < 2) ATS(51, 256);
    uint32_t A[2][4];
#pragma unroll
    for (int h = 0; h < 2; h++) {
      if (layer == 0) ldsm4(A[h], sb + SM_X + c * 16384 + h * 8192 + xa);
      else ldsm4t(A[h], sb + SM_X + c * 16384 + h * 8192 + xa);
    }
#pragma unroll
    for (int r = 0; r < 4; r++)
#pragma unroll
      for (int i = 0; i < 2; i++) {
        const uint32_t v = A[r >> 1][2 * i + (r & 1)];
        const float a = bf_lo(v), b = bf_hi(v);
        s[r] += a + b; q[r] = fmaf(a, a, q[r]); q[r] = fmaf(b, b, q[r]);
      }
  }
#pragma unroll
  for (int r = 0; r < 2; r++) {
    s[r] = ((t & 2) ? s[r + 2] : s[r]) + __shfl_xor_sync(~0u, (t & 2) ? s[r] : s[r + 2], 2);
    q[r] = ((t & 2) ? q[r + 2] : q[r]) + __shfl_xor_sync(~0u, (t & 2) ? q[r] : q[r + 2], 2);
  }
  s[0] = ((t & 1) ? s[1] : s[0]) + __shfl_xor_sync(~0u, (t & 1) ? s[0] : s[1], 1);
  q[0] = ((t & 1) ? q[1] : q[0]) + __shfl_xor_sync(~0u, (t & 1) ? q[0] : q[1], 1);
  st_part(&g_part[(rb * 8 + hg) * 128 + 64 * (t >> 1) + 16 * w + 8 * (t & 1) + g], s[0], q[0], tag);
  ATS(49, 256);
}
__device__ __forceinline__ void stats_gather(uint32_t sb, int rb, int ht, uint32_t tag) {
  const uint2* src = &g_part[rb * 8 * 128 + ht];
  uint2 v[8];
  bool ok;
  int it = 0;
  do {
    ok = true;
#pragma unroll
    for (int i = 0; i < 8; i++) v[i] = ld_part(src + i * 128);
#pragma unroll
    for (int i = 0; i < 8; i++) ok = ok && (v[i].y & 7u) == tag;
    if (++it > (1 << 22)) __trap();
  } while (!__all_sync(~0u, ok));
  float s = 0.f, q = 0.f;
#pragma unroll
  for (int i = 0; i < 8; i++) { s += __uint_as_float(v[i].x); q += __uint_as_float(v[i].y); }
  const float mean = s * (1.f / DM);
  const float rstd = rsqrt_approx(fmaxf(q * (1.f / DM) - mean * mean, 0.f) + 1e-5f);
  asm volatile("st.shared.v2.f32 [%0], {%1,%2};" ::"r"(sb + SM_ST + ht * 8), "f"(mean), "f"(rstd) : "memory");
  __syncwarp();
  if (elect_one()) mbar_arrive(sb + SM_BAR + 8 * B_STF);
}
__device__ __forceinline__ void halo_receive(uint32_t sb, int layer, int rb, int hg, int ht) {
  const int lane = ht & 31, h = ht >> 5;
  uint4 kv = make_uint4(0, 0, 0, 0);
  mbar_wait(sb + SM_BAR + 8 * B_SD, layer);
  if (rb & 7) {
    const uint32_t tag = 2 * lds32(sb + SM_EP) + layer + 1;
    const uint4* src = &g_halo[((rb - 1) * 8 + hg) * 192 + h * 48];
    if (layer == 0) delay<D_HALO>(); else delay<D_HALO1>();
    uint4 a;
    uint2 b;
    int it = 0;
    do {
      a = ld_tagged(src + lane); b = ld_part((const uint2*)(src + 32) + lane);
      if (++it > (1 << 22)) __trap();
    } while (!__all_sync(~0u, a.w == tag && b.y == tag));
    kv = make_uint4(a.x, a.y, movm_t(a.z), movm_t(b.x));
  }
  sts128(sb + SM_KVX + h * 512 + lane * 16, kv);
  ATS(61, 256);
  bar_arrive(7, 160);
  if (elect_one()) mbar_arrive(sb + SM_BAR + 8 * B_HF);
}

template <bool TR>
__device__ __forceinline__ void gemm_section(float* acc, float2* cs, uint32_t sb, int layer, int wg, int w, int lane) {
  const uint32_t bar = sb + SM_BAR;
  const bool leader = (w == 0) && (lane == 0);
  auto issue = [&](int c, int slot) {
    mbar_wait(bar + 8 * (B_XF + c), layer);
    mbar_wait(bar + 8 * (B_KVF + c), layer);
    const uint64_t da = mkdesc(sb + SM_X + c * 16384 + wg * 8192, TR ? 8192 : 16, 1024, 1);
    const uint64_t db = mkdesc(sb + SM_W + slot * 24576, 8192, 1024, 1);
    wg_fence();
#pragma unroll
    for (int ks = 0; ks < 4; ks++) wgmma_ss<192, TR ? 1 : 0, 1>(acc, da + (TR ? ks * 128 : ks * 2), db + ks * 128, (c | ks) != 0);
    wg_commit();
  };
  auto step = [&](int c, int slot) {
    issue(c, slot);
    wg_wait<1>();
    if (leader) mbar_arrive(bar + 8 * (B_KVE + c - 1));
  };
  if (!TR) bar_sync(0, NTHREADS);
  issue(0, 0);
  if (threadIdx.x == 0) TS(2 + layer * 20 + 0);
  if (threadIdx.x == 128 && layer == 1) TS(60);
  step(1, 1); step(2, 2); step(3, 0); step(4, 1);
  auto ld_cs = [&](int j0) {
#pragma unroll
    for (int j = j0; j < j0 + 8; j++) cs[j] = lds64f(sb + SM_CS + 4 * (8 * j + 2 * (lane & 3)));
  };
  if (TR) ld_cs(8);
  step(5, 2);
  if (!TR && !CS_LATE0) { mbar_wait(bar + 8 * B_CSF, 0); ld_cs(8); }
  if (TR || !CS_LATE0) ld_cs(16);
  if (wg == 0) bar_sync(5, 256);
  issue(6, 0);
  issue(7, 1);
  if (wg == 1) bar_arrive(5, 256);
  if (!TR && CS_LATE0) { mbar_wait(bar + 8 * B_CSF, 0); ld_cs(8); ld_cs(16); }
}

__device__ __forceinline__ void attn_phase(const Params& p, uint32_t sb, int layer, int rb, int hg, int wg, int w) {
  const int lane = opaque_tid() & 31;
  const int g = lane >> 2, t = lane & 3;
  const uint32_t bar = sb + SM_BAR;
  const int row0 = 64 * wg + 16 * w;
  const bool leader = (w == 0) && (lane == 0);
  float acc[96];
  float2 cs[24];
  if (layer) gemm_section<true>(acc, cs, sb, layer, wg, w, lane);
  else gemm_section<false>(acc, cs, sb, layer, wg, w, lane);
  ATS(41, 224);
  mbar_wait(bar + 8 * B_STF, layer);
  const uint32_t tag = 2 * lds32(sb + SM_EP) + layer + 1;
  const float2 st0 = lds64f(sb + SM_ST + (row0 + g) * 8), st1 = lds64f(sb + SM_ST + (row0 + g + 8) * 8);
  const float mean0 = st0.x, rstd0 = st0.y, mean1 = st1.x, rstd1 = st1.y;
  wg_wait<0>();
  if (threadIdx.x == 0) TS(2 + layer * 20 + 1);
  ATS(39, 224);
  if (leader) mbar_arrive(bar + 8 * B_QDONE);

  uint32_t fp[4][4], fl[4][4], fh[4][4], qa[4][4];
  const int cw = 4 * wg + w;
  {
    const float nm0 = -mean0 * rstd0, nm1 = -mean1 * rstd1;
    const uint32_t kvx = sb + SM_KVX + cw * 2048 + lane * 16;
#pragma unroll
    for (int h = 0; h < 4; h++)
#pragma unroll
      for (int k = 0; k < 4; k++) {
        const int j = 8 + (k >> 1) * 8 + 2 * h + (k & 1);
        fh[h][k] = packbf(fmaf(acc[4 * j + 2], rstd1, nm1 * cs[j].x), fmaf(acc[4 * j + 3], rstd1, nm1 * cs[j].y));
      }
    if (cw == 7) {
      uint4* halo = &g_halo[(rb * 8 + hg) * 192];
#pragma unroll
      for (int h = 0; h < 4; h++) {
        st_tagged3(halo + h * 48 + lane, fh[h][0], fh[h][1], fh[h][2], tag);
        asm volatile("st.relaxed.gpu.global.v2.u32 [%0], {%1,%2};" ::"l"((uint2*)(halo + h * 48 + 32) + lane), "r"(fh[h][3]), "r"(tag) : "memory");
      }
      if (elect_one()) mbar_arrive(bar + 8 * B_SD);
      if (layer == TLAYER && threadIdx.x == 224) TS(47);
    }
#pragma unroll
    for (int h = 0; h < 4; h++) { fh[h][2] = movm_t(fh[h][2]); fh[h][3] = movm_t(fh[h][3]); }
    if (cw != 7) {
#pragma unroll
      for (int h = 0; h < 4; h++) sts128(kvx + 2048 + h * 512, make_uint4(fh[h][0], fh[h][1], fh[h][2], fh[h][3]));
      bar_arrive(8 + cw, 64);
    }
    if (layer == TLAYER && threadIdx.x == 0) TS(45);
#pragma unroll
    for (int j = 0; j < 8; j++) cs[j] = lds64f(sb + SM_CS + 4 * (8 * j + 2 * t));
#pragma unroll
    for (int h = 0; h < 4; h++)
#pragma unroll
      for (int k = 0; k < 4; k++) {
        const int j = 8 + (k >> 1) * 8 + 2 * h + (k & 1);
        fl[h][k] = packbf(fmaf(acc[4 * j], rstd0, nm0 * cs[j].x), fmaf(acc[4 * j + 1], rstd0, nm0 * cs[j].y));
        if (k >= 2) fl[h][k] = movm_t(fl[h][k]);
      }
#pragma unroll
    for (int h = 0; h < 4; h++) {
#pragma unroll
      for (int dh = 0; dh < 2; dh++) {
        const int j = 2 * h + dh;
        const float2 c2 = cs[j];
        qa[h][2 * dh] = packbf(fmaf(-mean0, c2.x, acc[4 * j + 0]), fmaf(-mean0, c2.y, acc[4 * j + 1]));
        qa[h][2 * dh + 1] = packbf(fmaf(-mean1, c2.x, acc[4 * j + 2]), fmaf(-mean1, c2.y, acc[4 * j + 3]));
      }
    }
    if (threadIdx.x == 0) TS(2 + layer * 20 + 2);
    bar_sync(7 + cw, cw == 0 ? 160 : 64);
#pragma unroll
    for (int h = 0; h < 4; h++) {
      const uint4 v = lds128(kvx + h * 512);
      fp[h][0] = v.x; fp[h][1] = v.y; fp[h][2] = v.z; fp[h][3] = v.w;
    }
    if (threadIdx.x == 0) TS(2 + layer * 20 + 4);
  }

  const bool u0 = 2 * t > g, u1 = 2 * t + 1 > g;
  const uint32_t mU = (u0 ? 0x0000ffffu : 0u) | (u1 ? 0xffff0000u : 0u);
  const float cl2 = 0.25f * 1.4426950408889634f;
  const float sc0 = rstd0 * cl2, sc1 = rstd1 * cl2;
  const float cneg = ((rb & 7) == 0 && cw == 0) ? -INFINITY : 0.f;
  float v[4][4];
#pragma unroll
  for (int h = 0; h < 4; h++) {
    float T0[4] = {cneg, cneg, cneg, cneg}, T1[4] = {0.f, 0.f, 0.f, 0.f}, T2[4] = {0.f, 0.f, 0.f, 0.f};
    mma_bf16(T1, qa[h], fl[h][0], fl[h][1]);
    mma_bf16(T2, qa[h], fh[h][0], fh[h][1]);
    mma_bf16(T0, qa[h], fp[h][0], fp[h][1]);
    v[h][0] = u0 ? T0[0] : T1[0]; v[h][1] = u1 ? T0[1] : T1[1];
    v[h][2] = u0 ? T1[2] : T2[2]; v[h][3] = u1 ? T1[3] : T2[3];
  }
  float m0[4], m1[4];
#pragma unroll
  for (int h = 0; h < 4; h++) { m0[h] = fmaxf(v[h][0], v[h][1]); m1[h] = fmaxf(v[h][2], v[h][3]); }
#pragma unroll
  for (int o = 1; o <= 2; o <<= 1) {
#pragma unroll
    for (int h = 0; h < 4; h++) {
      m0[h] = fmaxf(m0[h], __shfl_xor_sync(~0u, m0[h], o));
      m1[h] = fmaxf(m1[h], __shfl_xor_sync(~0u, m1[h], o));
    }
  }
  float O0[4][4], O1[4][4], Z[4][4];
#pragma unroll
  for (int h = 0; h < 4; h++) {
    const float mm0 = -m0[h] * sc0, mm1 = -m1[h] * sc1;
    const uint32_t P0 = packbf(ex2(fmaf(v[h][0], sc0, mm0)), ex2(fmaf(v[h][1], sc0, mm0)));
    const uint32_t P1 = packbf(ex2(fmaf(v[h][2], sc1, mm1)), ex2(fmaf(v[h][3], sc1, mm1)));
#pragma unroll
    for (int k = 0; k < 4; k++) O0[h][k] = O1[h][k] = Z[h][k] = 0.f;
    mma_bf16_k8(Z[h], P0, P1, 0x3f803f80u);
    mma_bf16_k8(O0[h], P0 & ~mU, P1 & mU, fl[h][2]); mma_bf16_k8(O1[h], P0 & ~mU, P1 & mU, fl[h][3]);
    mma_bf16_k8(O0[h], P0 & mU, 0u, fp[h][2]); mma_bf16_k8(O1[h], P0 & mU, 0u, fp[h][3]);
    mma_bf16_k8(O0[h], 0u, P1 & ~mU, fh[h][2]); mma_bf16_k8(O1[h], 0u, P1 & ~mU, fh[h][3]);
  }
  const uint32_t ob = sb + SM_OST + wg * 8192;
  const int o_row = 16 * w + (lane & 7) + 8 * ((lane >> 3) & 1);
#pragma unroll
  for (int h = 0; h < 4; h++) {
    const float i0 = rcp_approx(Z[h][0]), i1 = rcp_approx(Z[h][2]);
    const int ch = 2 * h + (lane >> 4);
    stsm4(ob + o_row * 128 + ((ch ^ (o_row & 7)) << 4), packbf(O0[h][0] * i0, O0[h][1] * i0), packbf(O0[h][2] * i1, O0[h][3] * i1),
          packbf(O1[h][0] * i0, O1[h][1] * i0), packbf(O1[h][2] * i1, O1[h][3] * i1));
  }
  if (threadIdx.x == 0) TS(2 + layer * 20 + 5);
  ATS(57, 128); ATS(20, 96);
  bar_sync(2 + wg, 128);
  if (w == 0 && elect_one()) {
    fence_async_smem();
    tma_st(&p.mapO, hg * 64, rb * 128 + wg * 64, ob);
    bulk_commit();
    mbar_arrive(bar + 8 * B_AD);
    bulk_wait_all();
    red_relaxed(&g_cnt[(C_O + rb) * 32]);
    mbar_arrive(bar + 8 * B_OST);
    if (threadIdx.x == 0) TS(2 + layer * 20 + 6);
  }
}

__device__ __forceinline__ void proj_phase(const Params& p, uint32_t sb, int layer, int rb, int q, int wg, int w) {
  const int lane = opaque_tid() & 31;
  const bool TR = layer != 0;
  const int t = lane & 3;
  const uint32_t bar = sb + SM_BAR;
  const uint32_t rbx = sb + SM_R + wg * 8192;
  uint32_t res[16];
  mbar_wait(bar + 8 * B_RF, layer);
  if (threadIdx.x == 0) TS(2 + layer * 20 + 7);
  if (!TR) {
#pragma unroll
    for (int j = 0; j < 8; j += 2) {
      const int mi = lane >> 3;
      const int row = 16 * w + (lane & 7) + 8 * (mi & 1), ch = j + (mi >> 1);
      ldsm4(&res[2 * j], rbx + row * 128 + ((ch ^ (row & 7)) << 4));
    }
  } else {
#pragma unroll
    for (int j = 0; j < 8; j += 2) {
      const int mi = lane >> 3;
      const int line = 8 * (j + (mi >> 1)) + (lane & 7), pc = 2 * w + (mi & 1);
      ldsm4t(&res[2 * j], rbx + line * 128 + ((pc ^ (line & 7)) << 4));
    }
  }
  bar_sync(2 + wg, 128);
  float acc[32];
#pragma unroll
  for (int i = 0; i < 16; i++) {
    asm volatile("shl.b32 %0, %1, 16;" : "=f"(acc[2 * i]) : "r"(res[i]));
    asm volatile("and.b32 %0, %1, 0xffff0000;" : "=f"(acc[2 * i + 1]) : "r"(res[i]));
  }
  const uint32_t tag = part_tag(lds32(sb + SM_EP), 2 * layer + 1);
#pragma unroll 1
  for (int c = 0; c < 8; c++) {
    if ((c & 1) == 0) mbar_wait(bar + 8 * (B_WOF + (c >> 1)), layer);
    mbar_wait(bar + 8 * (B_OF + c), layer);
    if (c == 0 && threadIdx.x == 0) TS(2 + layer * 20 + 8);
    const uint64_t da = mkdesc(sb + sm_o(c) + wg * 8192, 16, 1024, 1);
    const uint64_t db = mkdesc(sb + SM_WO + c * 8192, 8192, 1024, 1);
    wg_fence();
#pragma unroll
    for (int ks = 0; ks < 4; ks++) wgmma_ss<64, 0, 1>(acc, da + ks * 2, db + ks * 128, 1);
    wg_commit();
  }
  wg_wait<0>();
#pragma unroll
  for (int i = 0; i < 32; i++) asm volatile("" : "+f"(acc[i]) :: "memory");
  if (threadIdx.x == 0) TS(2 + layer * 20 + 9);
  if (lane == 0 && w == 0) mbar_arrive(bar + 8 * B_PDONE);
  {
    float s[4], qq[4];
#pragma unroll
    for (int k = 0; k < 4; k++) { s[k] = acc[k]; qq[k] = acc[k] * acc[k]; }
#pragma unroll
    for (int j = 1; j < 8; j++)
#pragma unroll
      for (int k = 0; k < 4; k++) { s[k] += acc[4 * j + k]; qq[k] = fmaf(acc[4 * j + k], acc[4 * j + k], qq[k]); }
    const float s0 = s[0] + s[1], s1 = s[2] + s[3], q0 = qq[0] + qq[1], q1 = qq[2] + qq[3];
    float sr = ((t & 1) ? s1 : s0) + __shfl_xor_sync(~0u, (t & 1) ? s0 : s1, 1);
    float qr = ((t & 1) ? q1 : q0) + __shfl_xor_sync(~0u, (t & 1) ? q0 : q1, 1);
    sr += __shfl_xor_sync(~0u, sr, 2);
    qr += __shfl_xor_sync(~0u, qr, 2);
    if (t < 2) st_part(&g_part[(rb * 8 + q) * 128 + 64 * wg + 16 * w + (lane >> 2) + 8 * t], sr, qr, tag);
    __syncwarp();
    if (elect_one()) mbar_arrive(bar + 8 * B_PS);
  }
#pragma unroll
  for (int j = 0; j < 8; j += 2) {
    const int mi = lane >> 3;
    const int line = 8 * (j + (mi >> 1)) + (lane & 7), pc = 2 * w + (mi & 1);
    stsm4t(rbx + line * 128 + ((pc ^ (line & 7)) << 4), packbf(acc[4 * j], acc[4 * j + 1]), packbf(acc[4 * j + 2], acc[4 * j + 3]),
           packbf(acc[4 * j + 4], acc[4 * j + 5]), packbf(acc[4 * j + 6], acc[4 * j + 7]));
  }
  fence_writer();
  bar_sync(2 + wg, 128);
  if (w == 0 && elect_one()) {
    fence_reader();
    mbar_wait(bar + 8 * B_ZF, layer);
    fence_async_global();
    tma_st(&p.mapXT, rb * 128 + wg * 64, (2 * layer) * DM + q * 64, rbx);
    bulk_commit();
    if (threadIdx.x == 0) TS(2 + layer * 20 + 10);
    asm volatile("cp.async.bulk.wait_group.read 0;" ::: "memory");
    if (wg == 0) mbar_arrive(bar + 8 * B_RE);
  }
}
__device__ __forceinline__ void proj_stats(int layer, int rb, int q, int lane, uint32_t tag) {
  const int r = 16 * q + (lane & 15);
  const uint2* src = &g_part[(rb * 8 + (lane >> 4) * 4) * 128 + r];
  uint2 v[4];
  bool ok;
  int it = 0;
  do {
    ok = true;
#pragma unroll
    for (int i = 0; i < 4; i++) v[i] = ld_part(src + i * 128);
#pragma unroll
    for (int i = 0; i < 4; i++) ok = ok && (v[i].y & 7u) == tag;
    if (++it > (1 << 22)) __trap();
  } while (!__all_sync(~0u, ok));
  float s = (__uint_as_float(v[0].x) + __uint_as_float(v[1].x)) + (__uint_as_float(v[2].x) + __uint_as_float(v[3].x));
  float qq = (__uint_as_float(v[0].y) + __uint_as_float(v[1].y)) + (__uint_as_float(v[2].y) + __uint_as_float(v[3].y));
  s += __shfl_xor_sync(~0u, s, 16);
  qq += __shfl_xor_sync(~0u, qq, 16);
  const float mean = s * (1.f / DM);
  const float rstd = rsqrt_approx(fmaxf(fmaf(qq, 1.f / DM, -mean * mean), 0.f) + 1e-5f), nm = -mean * rstd;
  const float nm1 = __shfl_xor_sync(~0u, nm, 1), rstd1 = __shfl_xor_sync(~0u, rstd, 1);
  if ((lane & 17) == 0)
    st_tagged3((uint4*)g_stats + (layer * 32 + rb * 2 + (r >> 6)) * 32 + ((r & 7) >> 1) * 8 + ((r >> 3) & 7),
               __float_as_uint(nm), __float_as_uint(rstd) | 1u, __float_as_uint(nm1), __float_as_uint(rstd1));
}

#define NA 8
template <bool GB> __host__ __device__ constexpr int grp_n() { return GB ? 17 - NA : NA; }
template <bool GB> __host__ __device__ constexpr int grp_m(int i) { return i == 0 ? (GB ? 1 : 0) : (GB ? NA + i : 1 + i); }
template <bool GB> __device__ __forceinline__ void conv_load(uint32_t* A, uint32_t pe) {
#pragma unroll
  for (int i = 0; i < grp_n<GB>(); i++) {
    asm volatile("ld.shared.v2.b32 {%0,%1}, [%2];" : "=r"(A[4 * i]), "=r"(A[4 * i + 1]) : "r"(pe + 4 * (64 * grp_m<GB>(i))) : "memory");
    A[4 * i + 2] = lds32(pe + 4 * (64 * grp_m<GB>(i) - 1));
  }
}
template <bool GB> __device__ __forceinline__ void conv_dup_early(uint32_t* A, uint32_t zero) {
#pragma unroll
  for (int i = 0; i < grp_n<GB>(); i++) asm volatile("or.b32 %0, %1, %2;" : "=r"(A[4 * i + 3]) : "r"(A[4 * i + 0]), "r"(zero));
}
template <bool GB> __device__ __forceinline__ void conv_dup(uint32_t* A) {
#pragma unroll
  for (int i = 0; i < grp_n<GB>(); i++) asm volatile("mov.b32 %0, %1;" : "=r"(A[4 * i + 3]) : "r"(A[4 * i + 0]));
}
template <bool GB, int I0, int I1> __device__ __forceinline__ void conv_mmas(float* acc, const uint32_t* A, uint64_t d) {
  if constexpr (I0 < I1) {
    constexpr int M = grp_m<GB>(I0);
    wgmma_rs<128 - 8 * (M / 2), 0>(acc, A + 4 * I0, d + (uint64_t)(4 * M), M != 0);
    conv_mmas<GB, I0 + 1, I1>(acc, A, d);
  }
}
struct SumAddr { uint32_t l0, l1, l2, se, so; };
__device__ __forceinline__ SumAddr conv_sum_addr(uint32_t sb, int c) {
  auto ua = [&](int j) { return sb + cv_u(0) + (127 - (j >> 3)) * 16 + (j & 7) * 2; };
  auto sa = [&](int hc) { const int ci = hc & ~1; return sb + cv_s(0) + ((ci >> 3) & 1) * 1024 + (ci >> 4) * 128 + (((ci ^ (ci >> 4)) & 7) << 4) + (hc & 1) * 8; };
  const int j0 = 4 * (c - 1);
  return {ua(j0 - 2), ua(j0), ua(j0 + 4), sa((c + 1) & 127), sa(c) + 2048};
}
__device__ __forceinline__ void sts64(uint32_t a, uint32_t x, uint32_t y) { asm volatile("st.shared.v2.b32 [%0], {%1,%2};" ::"r"(a), "r"(x), "r"(y) : "memory"); }
__device__ __forceinline__ void conv_sums(const SumAddr& sa, int lc, int c) {
  uint32_t e[4], o[4];
  {
    const float2 em = lds64f(sa.l1 + lc * 32768), om = lds64f(sa.l1 + lc * 32768 + CV_UH);
    e[0] = lds32(sa.l0 + lc * 32768); o[0] = lds32(sa.l0 + lc * 32768 + CV_UH);
    e[3] = lds32(sa.l2 + lc * 32768); o[3] = lds32(sa.l2 + lc * 32768 + CV_UH);
    e[1] = __float_as_uint(em.x); e[2] = __float_as_uint(em.y); o[1] = __float_as_uint(om.x); o[2] = __float_as_uint(om.y);
  }
  uint32_t s7e[2], s7o[2], s9e[2], s9o[2];
  uint32_t pw[4], sh[3];
#pragma unroll
  for (int k = 0; k < 4; k++) pw[k] = hadd2(e[k], o[k]);
#pragma unroll
  for (int k = 0; k < 3; k++) sh[k] = __byte_perm(pw[k], pw[k + 1], 0x5432);
#pragma unroll
  for (int k = 0; k < 2; k++) {
    const uint32_t t3 = hadd2(hadd2(sh[k], sh[k + 1]), pw[k + 1]);
    s7e[k] = hadd2(t3, o[k]); s7o[k] = hadd2(t3, e[k + 2]);
    s9e[k] = hadd2(s7o[k], pw[k]); s9o[k] = hadd2(s7e[k], pw[k + 2]);
  }
  if (c == 127) s9e[0] = s9e[1] = s9o[0] = s9o[1] = 0u;
  sts64(sa.se + lc * 32768, s9e[0], s9e[1]); sts64((sa.se ^ 16) + lc * 32768, s9o[0], s9o[1]);
  sts64(sa.so + lc * 32768, s7e[0], s7e[1]); sts64((sa.so ^ 16) + lc * 32768, s7o[0], s7o[1]);
}

__device__ __forceinline__ void conv_epi(uint32_t sb, int layer, int cta, int ch, int c0, uint4 x0, uint4 x1) {
  uint4 v[2][4];
  const uint4 xr[2] = {x0, x1};
  mbar_wait(sb + SM_BAR + 8 * (B_P + ch), layer);
#pragma unroll
  for (int u = 0; u < 2; u++) {
    const uint32_t pb = sb + cv_pb(ch) + u * (CV_PBW / 2) + c0 * 16;
#pragma unroll
    for (int k = 0; k < 4; k++) v[u][k] = lds128(pb + k * CV_PBW);
  }
#pragma unroll
  for (int u = 0; u < 2; u++) {
    uint4 o;
    o.x = hadd2(xr[u].x, hadd2(hadd2(v[u][0].x, v[u][1].x), hadd2(v[u][2].x, v[u][3].x)));
    o.y = hadd2(xr[u].y, hadd2(hadd2(v[u][0].y, v[u][1].y), hadd2(v[u][2].y, v[u][3].y)));
    o.z = hadd2(xr[u].z, hadd2(hadd2(v[u][0].z, v[u][1].z), hadd2(v[u][2].z, v[u][3].z)));
    o.w = hadd2(xr[u].w, hadd2(hadd2(v[u][0].w, v[u][1].w), hadd2(v[u][2].w, v[u][3].w)));
    if (layer == 0) sts128(sb + cv_s(ch) + (c0 + 128 * u) * 16, o);
    else st_tagged3((uint4*)(g_xT + (size_t)(3 * DM + cv_chan(cta, ch)) * LSEQ) + c0 + 128 * u, o.x, o.y, o.z, o.w);
  }
}
__device__ __forceinline__ void warp_release(uint32_t b) {
  fence_writer();
  __syncwarp();
  if (elect_one()) mbar_arrive(b);
}

__device__ __forceinline__ void conv_prep_load(uint32_t sb, int layer, int cta, int c, uint4 (&xr)[4], uint4 (&st)[4]) {
  mbar_wait(sb + SM_BAR + 8 * B_GB, layer);
  if (threadIdx.x == 0) TS(2 + layer * 20 + 11);
  xr[0] = ld_tagged((const uint4*)(g_xT + (size_t)(2 * layer * DM + cta) * LSEQ) + c);
#pragma unroll
  for (int i = 0; i < 4; i++) st[i] = ld_tagged((const uint4*)g_stats + (layer * 32 + (c >> 3)) * 32 + i * 8 + (c & 7));
}
template <bool HELPER>
__device__ __forceinline__ void conv_prep(uint32_t sb, int layer, int cta, int c, uint4 (&xr)[4], uint4 (&st)[4], const SumAddr& sa) {
  const uint32_t bar = sb + SM_BAR;
  const uint4* xin = (const uint4*)(g_xT + (size_t)(2 * layer * DM + cta) * LSEQ) + c;
  for (int it = 0;; it++) {
    const bool okx = __all_sync(~0u, xr[0].x != ~0u);
    const bool oks = __all_sync(~0u, (st[0].y & st[1].y & st[2].y & st[3].y & 1u) != 0);
    if (okx && oks) break;
    if (it > (1 << 22)) __trap();
    if (!okx) xr[0] = ld_tagged(xin);
    if (!oks) {
#pragma unroll
      for (int i = 0; i < 4; i++) st[i] = ld_tagged((const uint4*)g_stats + (layer * 32 + (c >> 3)) * 32 + i * 8 + (c & 7));
    }
  }
  if (threadIdx.x == 0) TS(2 + layer * 20 + 12);
  const int a = c & 127, h = c >> 7;
#pragma unroll
  for (int i = 0; i < 4; i++) {
    if (i == 1) {
#pragma unroll
      for (int j = 1; j < 4; j++) xr[j] = ld_tagged(xin + j * (128 * LSEQ / 8));
      if (HELPER) {
        mbar_wait(bar + 8 * B_U, layer);
        conv_sums(sa, 0, c);
        fence_async_smem();
        warp_release(bar + 8 * B_S);
        if (layer == 1 && c == 0) TS(46);
        mbar_wait(bar + 8 * B_GB, layer);
      }
      for (int it = 0; !__all_sync(~0u, xr[1].x != ~0u && xr[2].x != ~0u && xr[3].x != ~0u); it++) {
        if (it > (1 << 22)) __trap();
#pragma unroll
        for (int j = 1; j < 4; j++) xr[j] = ld_tagged(xin + j * (128 * LSEQ / 8));
      }
    }
    const uint32_t x[4] = {xr[i].x, xr[i].y, xr[i].z, xr[i].w};
    uint32_t u[4];
#pragma unroll
    for (int k = 0; k < 4; k++)
      u[k] = packbf(fmaf(bf_lo(x[k]), __uint_as_float(st[k].y), __uint_as_float(st[k].x)), fmaf(bf_hi(x[k]), __uint_as_float(st[k].w), __uint_as_float(st[k].z)));
    sts128(sb + cv_u(i) + h * CV_UH + (127 - a) * 16, make_uint4(u[0], u[1], u[2], u[3]));
    warp_release(bar + 8 * (B_U + i));
  }
}
__device__ __forceinline__ void conv_zero(uint32_t sb, int ht) {
  if (ht < 96) {
    const int ch = ht / 24, h2 = (ht / 12) & 1, qq = ht % 12;
    sts128(sb + cv_u(ch) + h2 * CV_UH + (128 + qq) * 16, make_uint4(0, 0, 0, 0));
  }
  if (ht >= 80) {
    const int i = ht - 80, ch = i / 12, q2 = i % 12;
    const int w2 = q2 < 2 ? 1 : q2 < 6 ? 2 : 3, cc = q2 < 2 ? q2 : q2 < 6 ? q2 - 2 : q2 - 6;
    sts128(sb + cv_pb(ch) + w2 * CV_PBW + (cc & 1) * (CV_PBW / 2) + (cc >> 1) * 16, make_uint4(0, 0, 0, 0));
  }
}

#define LD_AT 0
#define HANDOVER 12
template <int R>
__device__ __forceinline__ void conv_round(uint32_t sb, int layer, int wg, uint32_t* FA, uint32_t* FB, uint32_t pb, uint32_t pe2) {
  const uint32_t bar = sb + SM_BAR;
  const int ch = 2 * R + 1 - wg;
  float acc[64];
  const uint64_t d = mkdesc(sb + cv_u(ch), CV_UH, 128, 0);
  const bool leader = (opaque_tid() & 127) == 0;
  FTS(39);
  if (R == 0) {
    mbar_wait(bar + 8 * (B_U + ch), layer);
    fence_reader();
  }
  if (ch > 0) mbar_wait(bar + 8 * (B_T + ch - 1), layer);
  FTS(41);
  if (ch == 0 && threadIdx.x == 128) TS(2 + layer * 20 + 13);
  if (R == 1 && LD_AT == 0) conv_load<true>(FB, pe2);
  wg_fence();
  conv_mmas<false, 0, (HANDOVER < NA ? HANDOVER : NA)>(acc, FA, d);
  if (HANDOVER <= NA) mbar_arrive_if(bar + 8 * (B_T + ch), leader);
  conv_mmas<false, (HANDOVER < NA ? HANDOVER : NA), NA>(acc, FA, d);
  wg_commit();
  if (R == 1 && LD_AT == 1) conv_load<true>(FB, pe2);
  FTS(51);
  mbar_wait(bar + 8 * (B_S + ch), layer);
  if (R == 1) conv_dup<true>(FB);
  wg_fence();
  conv_mmas<true, 0, (HANDOVER > NA ? HANDOVER - NA : 0)>(acc, FB, d);
  if (HANDOVER > NA) mbar_arrive_if(bar + 8 * (B_T + ch), leader);
  conv_mmas<true, (HANDOVER > NA ? HANDOVER - NA : 0), 17 - NA>(acc, FB, d);
  wgmma_ss<64, 1, 1>(acc, mkdesc(sb + cv_s(ch), 1024, 1024, 1), mkdesc(sb + cv_ft(ch), 256, 16, 0), 1);
  wgmma_ss<64, 1, 1>(acc, mkdesc(sb + cv_s(ch) + 2048, 1024, 1024, 1), mkdesc(sb + cv_ft(ch) + 512, 256, 16, 0), 1);
  wg_commit();
  FTS(61);
  wg_wait<0>();
#pragma unroll
  for (int j = 0; j < 16; j += 2)
    stsm4t(pb + R * 65536 - j * 128, packbf(acc[4 * j], acc[4 * j + 1]), packbf(acc[4 * j + 2], acc[4 * j + 3]),
           packbf(acc[4 * j + 4], acc[4 * j + 5]), packbf(acc[4 * j + 6], acc[4 * j + 7]));
  __syncwarp();
  if (elect_one()) mbar_arrive(bar + 8 * (B_P + ch));
  if (threadIdx.x == 0) TS(2 + layer * 20 + 14 + R);
  FTS(57);
  if (R == 0) {
    mbar_wait(bar + 8 * (B_U + ch + 2), layer);
    fence_reader();
  }
}
__device__ __forceinline__ void conv_phase(const Params& p, uint32_t sb, int layer, int cta) {
  const int tid = opaque_tid();
  const int wg = __shfl_sync(~0u, tid >> 7, 0), w = __shfl_sync(~0u, (tid >> 5) & 3, 0);
  const uint32_t bar = sb + SM_BAR;
  uint32_t FA0[4 * NA], FA1[4 * NA], FB[4 * (17 - NA)];
  const uint32_t pe = sb + cv_pe(1 - wg) + 4 * (16 + 16 * w + 2 * ((tid & 31) >> 2) - 4 * (tid & 3));
  mbar_wait(bar + 8 * B_PE, layer);
  conv_load<false>(FA0, pe); conv_load<true>(FB, pe);
  const uint32_t zero = tid >> 10;
  conv_dup_early<false>(FA0, zero); conv_dup_early<true>(FB, zero);
  if (wg == 0) {
    uint4 xr[4], st[4];
    conv_prep_load(sb, layer, cta, tid + 128, xr, st);
    conv_load<false>(FA1, pe + 65536);
    conv_dup_early<false>(FA1, zero);
    conv_prep<false>(sb, layer, cta, opaque_tid() + 128, xr, st, SumAddr());
  } else {
    conv_load<false>(FA1, pe + 65536);
    conv_dup_early<false>(FA1, zero);
  }
  uint32_t pb;
  {
    const int l2 = opaque_tid() & 31, mt = l2 >> 3;
    pb = sb + cv_pb(1 - wg) + w * CV_PBW + (mt & 1) * (CV_PBW / 2) + (127 - 8 * (mt >> 1) - (l2 & 7) + w) * 16;
  }
  conv_round<0>(sb, layer, wg, FA0, FB, pb, 0);
  conv_round<1>(sb, layer, wg, FA1, FB, pb, pe + 65536);
  if (wg == 1 && layer == 0) mbar_wait(bar + 8 * (B_T + 3), layer);
}

__device__ __forceinline__ void final_phase(const Params& p, uint32_t sb, int cta, int wg, int w) {
  if (wg == 1 && w == 3) return;
  const int lane = opaque_tid() & 31, g = lane >> 2, t = lane & 3;
  const int lc = wg ? w : 3;
  const int pos0 = (cta & 31) * 64, ch0 = 128 * lc + (cta >> 5) * 32;
  const bf16* src = g_xT + (size_t)(3 * DM + ch0 + 8 * (g >> 1) + (g & 1)) * LSEQ + pos0;
  bf16* dst = p.out + (size_t)(2 * (pos0 & 1023) + (pos0 >> 10)) * DM + ch0 + 8 * t;
  constexpr int RS = 2 * DM;
  int it = 0;
  mbar_wait(sb + SM_BAR + 8 * (B_E + lc), 1);
  delay<D_FIN>();
  if (wg == 0) {
    uint2 v[4];
    do {
#pragma unroll
      for (int q = 0; q < 4; q++)
        asm volatile("ld.relaxed.gpu.global.v2.u32 {%0,%1}, [%2];" : "=r"(v[q].x), "=r"(v[q].y) : "l"(src + 2 * q * LSEQ + 16 * w + 4 * t) : "memory");
      if (++it > (1 << 22)) __trap();
    } while (!__all_sync(~0u, v[0].x != ~0u && v[1].x != ~0u && v[2].x != ~0u && v[3].x != ~0u));
    if (threadIdx.x == 0) TS(42);
    dst += (16 * w + 4 * (g >> 1) + (g & 1)) * RS;
    *(uint4*)dst = make_uint4(movm_t(v[0].x), movm_t(v[1].x), movm_t(v[2].x), movm_t(v[3].x));
    *(uint4*)(dst + 2 * RS) = make_uint4(movm_t(v[0].y), movm_t(v[1].y), movm_t(v[2].y), movm_t(v[3].y));
  } else {
    uint4 v[2][4];
    bool ok;
    do {
      ok = true;
#pragma unroll
      for (int h = 0; h < 2; h++)
#pragma unroll
        for (int q = 0; q < 4; q++) v[h][q] = ld_tagged((const uint4*)(src + 2 * q * LSEQ + 32 * h + 8 * t));
#pragma unroll
      for (int h = 0; h < 2; h++)
#pragma unroll
        for (int q = 0; q < 4; q++) ok = ok && v[h][q].x != ~0u;
      if (++it > (1 << 22)) __trap();
    } while (!__all_sync(~0u, ok));
    dst += (8 * (g >> 1) + (g & 1)) * RS;
#pragma unroll
    for (int h = 0; h < 2; h++) {
      *(uint4*)(dst + (32 * h + 0) * RS) = make_uint4(movm_t(v[h][0].x), movm_t(v[h][1].x), movm_t(v[h][2].x), movm_t(v[h][3].x));
      *(uint4*)(dst + (32 * h + 2) * RS) = make_uint4(movm_t(v[h][0].y), movm_t(v[h][1].y), movm_t(v[h][2].y), movm_t(v[h][3].y));
      *(uint4*)(dst + (32 * h + 4) * RS) = make_uint4(movm_t(v[h][0].z), movm_t(v[h][1].z), movm_t(v[h][2].z), movm_t(v[h][3].z));
      *(uint4*)(dst + (32 * h + 6) * RS) = make_uint4(movm_t(v[h][0].w), movm_t(v[h][1].w), movm_t(v[h][2].w), movm_t(v[h][3].w));
    }
  }
  if (threadIdx.x == 0) TS(43);
  if (threadIdx.x == 192) TS(63);
  if (threadIdx.x == 0) LTS(1);
}

struct cplx { float r, i; };
__device__ __forceinline__ cplx cmul(cplx a, cplx b) { return {fmaf(a.r, b.r, -a.i * b.i), fmaf(a.r, b.i, a.i * b.r)}; }
__device__ __forceinline__ cplx csqr(cplx a) { return {fmaf(a.r, a.r, -a.i * a.i), (a.r + a.r) * a.i}; }
__device__ __forceinline__ cplx cexp_l(float ar2, float ai, float l) {
  const float m = ex2(ar2 * l);
  const float x = ai * l;
  return {m * __cosf(x), m * __sinf(x)};
}

__device__ __forceinline__ void colsum_publish(uint32_t sb, int rb, int hg, int ht, uint32_t tag) {
  const int lane = ht & 31, q = lane & 15, h = lane >> 4;
  const uint32_t src = sb + SM_CW + (ht >> 5) * 4096 + h * 128 + (q & 1) * 8;
  float s[4] = {0.f, 0.f, 0.f, 0.f};
#pragma unroll
  for (int r = 0; r < 16; r++) {
    const float2 v = lds64f(src + r * 256 + (((q >> 1) ^ ((2 * r + h) & 7)) << 4));
    s[0] += bf_lo(__float_as_uint(v.x)); s[1] += bf_hi(__float_as_uint(v.x));
    s[2] += bf_lo(__float_as_uint(v.y)); s[3] += bf_hi(__float_as_uint(v.y));
  }
#pragma unroll
  for (int k = 0; k < 4; k++) s[k] += __shfl_xor_sync(~0u, s[k], 16);
  if (h == 0)
    st_tagged3(&g_colsum[(hg * 16 + rb) * 48 + (ht >> 5) * 16 + q], (__float_as_uint(s[0]) & ~7u) | tag, __float_as_uint(s[1]),
               __float_as_uint(s[2]), __float_as_uint(s[3]));
}
__device__ __forceinline__ void colsum_gather(uint32_t sb, int hg, int ht, uint32_t tag) {
  const int lane = ht & 31, rec = (ht >> 5) * 16 + (lane & 15);
  const uint4* src = &g_colsum[(hg * 16 + (lane >> 4) * 8) * 48 + rec];
  uint4 v[8];
  bool ok;
  int it = 0;
  do {
    ok = true;
#pragma unroll
    for (int i = 0; i < 8; i++) v[i] = ld_tagged(src + i * 48);
#pragma unroll
    for (int i = 0; i < 8; i++) ok = ok && (v[i].x & 7u) == tag;
    if (++it > (1 << 22)) __trap();
  } while (!__all_sync(~0u, ok));
  float s[4] = {0.f, 0.f, 0.f, 0.f};
#pragma unroll
  for (int i = 0; i < 8; i++) {
    s[0] += __uint_as_float(v[i].x & ~7u); s[1] += __uint_as_float(v[i].y); s[2] += __uint_as_float(v[i].z); s[3] += __uint_as_float(v[i].w);
  }
#pragma unroll
  for (int k = 0; k < 4; k++) s[k] += __shfl_xor_sync(~0u, s[k], 16);
  if (lane < 16) sts128f(sb + SM_CS + rec * 16, s[0], s[1], s[2], s[3]);
}

__device__ __forceinline__ uint32_t packh(float lo, float hi) { uint32_t r; asm("cvt.rn.f16x2.f32 %0, %1, %2;" : "=r"(r) : "f"(hi), "f"(lo)); return r; }
__device__ __forceinline__ void mma_f16(float* d, uint32_t a0, uint32_t a1, uint32_t a2, uint32_t a3, uint32_t b0, uint32_t b1) {
  asm volatile("mma.sync.aligned.m16n8k16.row.col.f32.f16.f16.f32 {%0,%1,%2,%3}, {%4,%5,%6,%7}, {%8,%9}, {%0,%1,%2,%3};"
      : "+f"(d[0]), "+f"(d[1]), "+f"(d[2]), "+f"(d[3]) : "r"(a0), "r"(a1), "r"(a2), "r"(a3), "r"(b0), "r"(b1));
}
struct HSeed { uint32_t r, i; };
__device__ __forceinline__ HSeed hseed(cplx s) { return {packh(s.r, s.r), packh(s.i, s.i)}; }
__device__ __forceinline__ void hcmul(uint32_t& o_r, uint32_t& o_i, uint32_t br, uint32_t bi, HSeed s) {
  asm("{\n.reg .b32 t, u;\nmul.rn.f16x2 t, %3, %5;\nneg.f16x2 t, t;\nmul.rn.f16x2 u, %3, %4;\nfma.rn.f16x2 %0, %2, %4, t;\nfma.rn.f16x2 %1, %2, %5, u;\n}"
      : "=&r"(o_r), "=&r"(o_i) : "r"(br), "r"(bi), "r"(s.r), "r"(s.i));
}
struct HTile { uint32_t r[4], i[4]; };
__device__ __forceinline__ void tile_set(HTile& t, int k, cplx a, cplx b) { t.r[k] = packh(a.r, b.r); t.i[k] = packh(a.i, b.i); }
__device__ __forceinline__ void tile_upper(HTile& t, HSeed s) { hcmul(t.r[2], t.i[2], t.r[0], t.i[0], s); hcmul(t.r[3], t.i[3], t.r[1], t.i[1], s); }
__device__ __forceinline__ HTile tile_shift(const HTile& t, HSeed s) {
  HTile o;
#pragma unroll
  for (int k = 0; k < 4; k++) hcmul(o.r[k], o.i[k], t.r[k], t.i[k], s);
  return o;
}
__device__ __forceinline__ void tile_put(const HTile& t, uint32_t a) {
  sts128(a, make_uint4(t.r[0], t.r[1], t.r[2], t.r[3]));
  sts128(a + 512, make_uint4(t.i[0], t.i[1], t.i[2], t.i[3]));
}
__device__ __forceinline__ HTile tile_get(uint32_t a) { HTile o; ldsm4t(o.r, a); ldsm4t(o.i, a + 512); return o; }
__device__ __forceinline__ void tile_mma(float* T, const HTile& a0, const HTile& a1, const HTile& b) {
  mma_f16(T, a0.r[0], a0.r[1], a0.r[2], a0.r[3], b.r[0], b.r[1]);
  mma_f16(T, a0.i[0], a0.i[1], a0.i[2], a0.i[3], b.i[0], b.i[1]);
  mma_f16(T, a1.r[0], a1.r[1], a1.r[2], a1.r[3], b.r[2], b.r[3]);
  mma_f16(T, a1.i[0], a1.i[1], a1.i[2], a1.i[3], b.i[2], b.i[3]);
}
__device__ __forceinline__ void tile_mma2(float* T, float* U, const HTile& a0, const HTile& a1, const HTile& b, const HTile& c) {
  mma_f16(T, a0.r[0], a0.r[1], a0.r[2], a0.r[3], b.r[0], b.r[1]);
  mma_f16(U, a0.r[0], a0.r[1], a0.r[2], a0.r[3], c.r[0], c.r[1]);
  mma_f16(T, a0.i[0], a0.i[1], a0.i[2], a0.i[3], b.i[0], b.i[1]);
  mma_f16(U, a0.i[0], a0.i[1], a0.i[2], a0.i[3], c.i[0], c.i[1]);
  mma_f16(T, a1.r[0], a1.r[1], a1.r[2], a1.r[3], b.r[2], b.r[3]);
  mma_f16(U, a1.r[0], a1.r[1], a1.r[2], a1.r[3], c.r[2], c.r[3]);
  mma_f16(T, a1.i[0], a1.i[1], a1.i[2], a1.i[3], b.i[2], b.i[3]);
  mma_f16(U, a1.i[0], a1.i[1], a1.i[2], a1.i[3], c.i[2], c.i[3]);
}
__device__ __forceinline__ void kgen_unit(uint32_t tab, uint32_t taba, float ar2, float ai, cplx c, float (&T)[5][4]) {
  const cplx z1 = cexp_l(ar2, ai, 1.f), z16 = cexp_l(ar2, ai, 16.f), z256 = cexp_l(ar2, ai, 256.f);
  HTile a0, a1, b0, b1;
  {
    const cplx y1 = {z16.r, -z16.i}, y2 = csqr(y1), y3 = cmul(y2, y1), y4 = csqr(y2), y5 = cmul(y4, y1), y6 = csqr(y3), y7 = cmul(y4, y3);
    HTile t;
    tile_set(t, 0, {1.f, 0.f}, y1); tile_set(t, 1, y2, y3); tile_set(t, 2, y4, y5); tile_set(t, 3, y6, y7);
    const HTile u = tile_shift(t, hseed(csqr(y4)));
    __syncwarp();
    tile_put(t, tab); tile_put(u, tab + 1024);
    __syncwarp();
    a0 = tile_get(taba); a1 = tile_get(taba + 256);
  }
  const cplx z2 = csqr(z1), z4 = csqr(z2), z8 = csqr(z4);
  const HSeed h8 = hseed(z8);
  const cplx d = cmul(c, z256), e = cmul(d, z256);
  {
    const cplx z512 = csqr(z256), f = cmul(e, z512), f8 = cmul(f, z8), f16 = cmul(f, z16), e4 = cmul(e, z4);
    HTile t, u;
    tile_set(t, 0, e4, cmul(e, z8)); tile_set(t, 1, cmul(e4, z8), cmul(e, z16));
    tile_upper(t, hseed(z256));
    tile_set(u, 0, f8, f16); tile_set(u, 1, cmul(f8, z256), cmul(f16, z256));
    tile_upper(u, hseed(z512));
    __syncwarp();
    tile_put(t, tab); tile_put(u, tab + 1024);
    __syncwarp();
    b0 = tile_get(tab); b1 = tile_get(tab + 1024);
  }
  {
    const cplx d2 = cmul(d, z2), d4 = cmul(d, z4);
    HTile t;
    tile_set(t, 0, d2, d4); tile_set(t, 1, cmul(d2, z4), cmul(d, z8));
    tile_upper(t, h8);
    __syncwarp();
    tile_put(t, tab);
    __syncwarp();
    tile_mma2(T[3], T[4], a0, a1, b0, b1);
    b0 = tile_get(tab);
  }
  {
    const cplx c1 = cmul(c, z1), c2 = cmul(c, z2), c3 = cmul(c1, z2), c4 = cmul(c, z4);
    HTile t;
    tile_set(t, 0, c1, c2); tile_set(t, 1, c3, c4); tile_set(t, 2, cmul(c1, z4), cmul(c2, z4)); tile_set(t, 3, cmul(c3, z4), cmul(c4, z4));
    const HTile u = tile_shift(t, h8);
    __syncwarp();
    tile_put(t, tab); tile_put(u, tab + 1024);
    __syncwarp();
    tile_mma(T[2], a0, a1, b0);
    b0 = tile_get(tab); b1 = tile_get(tab + 1024);
    tile_mma2(T[0], T[1], a0, a1, b0, b1);
  }
}
struct ModeIn { uint2 ar, ai, br, bi, cr, ci; };
__device__ __forceinline__ ModeIn load_modes(const Params& p, int idx) {
  return {*(const uint2*)(p.a_re + idx), *(const uint2*)(p.a_im + idx), *(const uint2*)(p.b_re + idx),
          *(const uint2*)(p.b_im + idx), *(const uint2*)(p.c_re + idx), *(const uint2*)(p.c_im + idx)};
}
__device__ __forceinline__ float bf_el(uint2 v, int k) { const uint32_t x = (k & 2) ? v.y : v.x; return (k & 1) ? bf_hi(x) : bf_lo(x); }
struct KGen { float4 cur; float T[5][4]; };
__device__ __forceinline__ uint32_t kgen_slot(uint32_t sb, int ht, int u) {
  return sb + (u < 3 ? SM_KC + (ht >> 5) * (KC_STRIDE * 2) + (u - 1) * 512 + (ht & 31) * 16 + 16 : SM_HALO + 1024 + ht * 16);
}
__device__ __forceinline__ void kgen_setup(KGen& s, uint32_t sb, int cta, int ht, const ModeIn& in, bf16 logdt, bf16 dskip) {
  const float dt = __bfloat162float(__float2bfloat16_rn(expf(__bfloat162float(logdt))));
  float mx = 0.f, k0 = 0.f, ar2[4];
  cplx c[4];
#pragma unroll
  for (int k = 0; k < 4; k++) {
    ar2[k] = (dt * bf_el(in.ar, k)) * 1.4426950408889634f;
    c[k] = cmul({bf_el(in.cr, k), bf_el(in.ci, k)}, {dt * bf_el(in.br, k), dt * bf_el(in.bi, k)});
    k0 += c[k].r;
    mx = fmaxf(mx, fmaxf(fabsf(c[k].r), fabsf(c[k].i)) * ex2(fmaxf(ar2[k] * 2048.f, 0.f)));
  }
  const int ex = min(max(267 - (int)(__reduce_max_sync(~0u, __float_as_uint(mx)) >> 23), 1), 253);
  const float sc = __uint_as_float(ex << 23);
#pragma unroll
  for (int o = 16; o > 0; o >>= 1) k0 += __shfl_xor_sync(~0u, k0, o);
  if ((ht & 31) == 0) {
    const uint32_t kc = sb + SM_KC + (ht >> 5) * (KC_STRIDE * 2);
    sts16(kc, __bfloat16_as_ushort(__float2bfloat16_rn(k0 + __bfloat162float(dskip))));
    sts16(kc + 641 * 2, 0);
    sts32f(kc + 644 * 2, __uint_as_float((254 - ex) << 23));
  }
  s.cur = make_float4(ar2[0], dt * bf_el(in.ai, 0), c[0].r * sc, c[0].i * sc);
#pragma unroll
  for (int k = 1; k < 4; k++) sts128f(kgen_slot(sb, ht, k), ar2[k], dt * bf_el(in.ai, k), c[k].r * sc, c[k].i * sc);
#pragma unroll
  for (int i = 0; i < 5; i++) s.T[i][0] = s.T[i][1] = s.T[i][2] = s.T[i][3] = 0.f;
}
__device__ __forceinline__ void kgen_finish(KGen& s, uint32_t sb, int cta, int ht) {
  const int w = ht >> 5, lane = ht & 31, g = lane >> 2, t = lane & 3;
  const uint32_t kc = sb + SM_KC + w * KC_STRIDE * 2;
  __syncwarp();
  const float inv = __uint_as_float(lds32(kc + 644 * 2));
  auto put = [&](int idx, float v) {
    sts16(kc + idx * 2, __bfloat16_as_ushort(__float2bfloat16_rn(v)));
  };
#pragma unroll
  for (int hi = 0; hi < 2; hi++)
#pragma unroll
    for (int lo = 0; lo < 2; lo++) {
      const int i = g + 8 * hi, j = 2 * t + lo, e = 2 * hi + lo;
      put(16 * i + 1 + j, s.T[0][e] * inv);
      put(16 * i + 9 + j, s.T[1][e] * inv);
      put(257 + 8 * i + j, s.T[2][e] * inv);
      put(385 + 4 * i + (j & 3) + 64 * (j >> 2), s.T[3][e] * inv);
      put(513 + 2 * i + lo + 32 * t, s.T[4][e] * inv);
    }
}

__device__ __forceinline__ void expand_taps(uint32_t sb, int ht) {
  const int ch = ht >> 5, lane = ht & 31;
  const uint32_t kc = sb + SM_KC + ch * KC_STRIDE * 2;
  const uint32_t dst0 = sb + cv_pe(ch);
  auto put = [&](int G, uint32_t u0, uint32_t u1, uint32_t v0, uint32_t v1, uint32_t v2, uint32_t v3, uint32_t v4, uint32_t v5, uint32_t v6, uint32_t v7) {
    const uint32_t dst = dst0 + G * 32;
    sts128(dst, make_uint4(v0 | (u0 << 16), v1 | (u1 << 16), v2 | (v0 << 16), v3 | (v1 << 16)));
    sts128(dst + 16, make_uint4(v4 | (v2 << 16), v5 | (v3 << 16), v6 | (v4 << 16), v7 | (v5 << 16)));
  };
  {
    const uint4 q = lds128(kc + lane * 16);
    const uint32_t pv = lane ? lds32(kc + lane * 16 - 4) : 0u;
    const uint32_t dst = dst0 + (lane + 2) * 32;
    sts128(dst, make_uint4(__byte_perm(q.x, pv, 0x5410), __byte_perm(q.x, pv, 0x7632), __byte_perm(q.y, q.x, 0x5410), __byte_perm(q.y, q.x, 0x7632)));
    sts128(dst + 16, make_uint4(__byte_perm(q.z, q.y, 0x5410), __byte_perm(q.z, q.y, 0x7632), __byte_perm(q.w, q.z, 0x5410), __byte_perm(q.w, q.z, 0x7632)));
    if (lane < 4) sts128(dst0 + lane * 16, make_uint4(0, 0, 0, 0));
  }
  uint32_t a[5], b[2][3], fv[4];
  {
    const uint32_t s1 = kc + 2 * (256 + 4 * lane);
#pragma unroll
    for (int k = 0; k < 5; k++) a[k] = lds16(s1 + 2 * k);
#pragma unroll
    for (int u = 0; u < 2; u++) {
      const uint32_t s2 = kc + 2 * (384 + 2 * (lane + 32 * u));
#pragma unroll
      for (int k = 0; k < 3; k++) b[u][k] = lds16(s2 + 2 * k);
    }
#pragma unroll
    for (int k = 0; k < 4; k++) fv[k] = lds16(kc + 2 * (640 - 4 * lane - k));
  }
  const uint32_t am1 = lds16(kc + 2 * (lane ? 256 + 4 * lane : 255)), am2 = lds16(kc + 2 * (lane ? 255 + 4 * lane : 254));
  const uint32_t bm2 = lds16(kc + 2 * (lane ? 384 + 2 * lane : 383)), k1024 = lds16(kc + 2 * 512);
  put(34 + lane, am2, am1, a[0], a[0], a[1], a[2], a[2], a[2], a[3], a[4]);
#pragma unroll
  for (int u = 0; u < 2; u++) put(66 + lane + 32 * u, u ? b[u][0] : bm2, b[u][0], b[u][0], b[u][0], b[u][0], b[u][1], b[u][1], b[u][1], b[u][2], b[u][2]);
  if (lane < 10) {
    const uint32_t v = lane == 0 ? k1024 : 0u;
    put(130 + lane, v, v, v, v, v, v, v, 0u, 0u, 0u);
  }
  const uint32_t ft = sb + cv_ft(ch) + 4 * lane;
#pragma unroll
  for (int ty = 0; ty < 2; ty++) {
    const uint32_t v = fv[ty] | (fv[ty + 2] << 16);
    sts32f(ft + ty * 512, __uint_as_float(v));
    sts32f(ft + ty * 512 + 128, 0.f);
    sts32f(ft + ty * 512 + 256 + (lane < 2 ? 120 : -8), __uint_as_float(lane < 2 ? 0u : v));
    sts32f(ft + ty * 512 + 384, 0.f);
  }
}

template <bool SMID> __device__ __forceinline__ int role_id() {
  uint32_t v;
  if (!SMID) { asm volatile("mov.u32 %0, %%ctaid.x;" : "=r"(v)); return v; }
  asm volatile("mov.u32 %0, %%smid;" : "=r"(v));
  const int tp = v >> 1, q = ((tp - 32) * 37) >> 8;
  const int r = tp < 32 ? (tp & 7) * 8 + (tp >> 3) : tp < 60 ? (tp - 31 - 7 * q) * 8 + 4 + q : tp < 62 ? tp + 4 : tp - 58;
  return __shfl_sync(~0u, 2 * r + (v & 1), 0);
}
__device__ __forceinline__ int role_rb(int cta) { return ((cta >> 4) & 3) * 4 + ((cta >> 2) & 3); }
__device__ __forceinline__ int role_hg(int cta) { return (cta >> 6) * 4 + (cta & 3); }
__device__ __forceinline__ int role_rb2(int cta) { return cta >> 3; }
__device__ __forceinline__ int role_q2(int cta) { return cta & 7; }

template <bool SMID> __global__ void __launch_bounds__(NTHREADS, 1) fused_kernel(const __grid_constant__ Params p) {
  extern __shared__ __align__(1024) uint8_t smem[];
  const uint32_t sb = s32(smem);
  const int tid = threadIdx.x, lane = tid & 31;
  const int warp = __shfl_sync(~0u, tid >> 5, 0);
  constexpr unsigned NARR = SMID ? 132 : NCTA;
  const uint32_t bar = sb + SM_BAR;
  if (tid == 0) TS(0);
  const int cta0 = role_id<SMID>();
  if (warp == 0 && (!SMID || cta0 < NCTA) && elect_one()) {
    const int rb = role_rb(cta0), hg = role_hg(cta0);
#pragma unroll
    for (int c = 0; c < 2; c++) { mbar_init(bar + 8 * (B_XF + c), 1); mbar_init(bar + 8 * (B_KVF + c), 1); }
    fence_async_smem();
#pragma unroll
    for (int c = 0; c < 2; c++) {
      mbar_expect(bar + 8 * (B_XF + c), 16384);
      tma_ld(sb + SM_X + c * 16384, &p.mapX128, (rb >> 3) * DM + c * 64, (rb & 7) * 128, bar + 8 * (B_XF + c));
      mbar_expect(bar + 8 * (B_KVF + c), 24576);
      tma_ld3(sb + SM_W + c * 24576, &p.mapW3, hg * 64, c * 64, 0, bar + 8 * (B_KVF + c));
    }
  }
  if (warp == 1 && (!SMID || cta0 < NCTA) && elect_one()) {
    const int rb = role_rb(cta0), hg = role_hg(cta0);
#pragma unroll
    for (int c = 2; c < 8; c++) mbar_init(bar + 8 * (B_XF + c), 1);
    mbar_init(bar + 8 * (B_KVF + 2), 1); mbar_init(bar + 8 * B_CW, 1);
    fence_async_smem();
    delay<D_START>();
    mbar_expect(bar + 8 * B_CW, 12288);
    tma_ld3(sb + SM_CW, &p.mapW3h, hg * 64, rb * 32, 0, bar + 8 * B_CW);
#pragma unroll
    for (int c = 2; c < 8; c++) {
      mbar_expect(bar + 8 * (B_XF + c), 16384);
      tma_ld(sb + SM_X + c * 16384, &p.mapX128, (rb >> 3) * DM + c * 64, (rb & 7) * 128, bar + 8 * (B_XF + c));
      if (c < 3) {
        mbar_expect(bar + 8 * (B_KVF + c), 24576);
        tma_ld3(sb + SM_W + c * 24576, &p.mapW3, hg * 64, c * 64, 0, bar + 8 * (B_KVF + c));
      }
    }
    TS(56);
  }
  if (SMID && cta0 >= NCTA) {
    if (tid == 0) spin_until(&g_cnt[C_CS * 32], (atomicAdd(&g_cnt[C_CS * 32], 1u) / NARR + 1) * NARR);
    return;
  }
  if ((warp & 2) != 0 && warp < 15 && elect_one()) {
    const int grp = 1 + (warp & 1) + 2 * (warp >> 2), cnt = grp < 4 ? 1 : grp < 5 ? 2 : grp < 7 ? 4 : 8;
#pragma unroll
    for (int k = 0; k < 10; k++)
      if (k != 0 || grp > 3 || grp == 2) mbar_init(bar + 8 * (10 * grp + k), cnt);
    fence_async_smem();
  }

  if (warp < 8) {
    if (tid == 0) TS(1);
    asm volatile("setmaxnreg.inc.sync.aligned.u32 %0;" ::"n"(R_CONS));
    const int cta = role_id<SMID>();
    auto warp_id = [] { return __shfl_sync(~0u, opaque_tid() >> 5, 0); };
    if (tid == 0) TS(54);
#pragma unroll 1
    for (int layer = 0; layer < 2; layer++) {
      { const int cw = warp_id(); attn_phase(p, sb, layer, role_rb(cta), role_hg(cta), cw >> 2, cw & 3); }
      if (p.stop == 1 + 3 * layer) return;
      { const int cw = warp_id(); proj_phase(p, sb, layer, role_rb2(cta), role_q2(cta), cw >> 2, cw & 3); }
      if (p.stop == 2 + 3 * layer) return;
      conv_phase(p, sb, layer, cta);
      if (p.stop == 3 + 3 * layer) return;
    }
    { const int cw = warp_id(); final_phase(p, sb, cta, cw >> 2, cw & 3); }
  } else if (warp < 12) {
    asm volatile("setmaxnreg.dec.sync.aligned.u32 %0;" ::"n"(R_HELP));
    const int ht = tid - 256;
    const int cta = role_id<SMID>(), rb = role_rb(cta), hg = role_hg(cta);
    unsigned ep0 = 0;
    if (ht == 0) ep0 = ld_relaxed(&g_cnt[C_CS * 32]);
    bar_sync(0, NTHREADS);
    if (ht == 0) {
      asm volatile("st.shared.u32 [%0], %1;" ::"r"(sb + SM_EP), "r"(ep0 / NARR) : "memory");
      mbar_arrive(bar + 8 * B_EP);
    }
    mbar_wait(bar + 8 * B_EP, 0);
    const uint32_t cs_tag = lds32(sb + SM_EP) % 7 + 1;
    if (ht < 96) {
      mbar_wait(bar + 8 * B_CW, 0);
      colsum_publish(sb, rb, hg, ht, cs_tag);
    }
    if (ht == 0) TS(50);
    if (ht < 48) {
      const bf16* q = (&p.a_re)[ht >> 3];
      asm volatile("prefetch.global.L2 [%0];" ::"l"(q + cv_chan(cta, (ht >> 1) & 3) * 128 + (ht & 1) * 64));
    }
    if (!CS_FIRST) stats_publish(sb, 0, rb, hg, opaque_tid() - 256, part_tag(lds32(sb + SM_EP), 0));
    {
      KGen kg;
      const uint32_t tab0 = sb + ((ht >> 5) < 2 ? SM_T : SM_T2 - 4096) + (ht >> 5) * 2048;
      const uint32_t tab = tab0 + (ht & 31) * 16, taba = tab0 + ((ht >> 3) & 1) * 1024 + (((ht >> 1) & 8) + (ht & 7)) * 16;
      mbar_wait(bar + 8 * (B_KVF + CS_AT), 0);
      if (ht < 96) colsum_gather(sb, hg, ht, cs_tag);
      __syncwarp();
      if (elect_one()) mbar_arrive(bar + 8 * B_CSF);
      if (CS_FIRST) stats_publish(sb, 0, rb, hg, opaque_tid() - 256, part_tag(lds32(sb + SM_EP), 0));
      stats_gather(sb, rb, opaque_tid() - 256, part_tag(lds32(sb + SM_EP), 0));
      if (ht == 0) TS(40);
      const int chn = cv_chan(cta, ht >> 5);
      const ModeIn modes = load_modes(p, chn * 128 + (ht & 31) * 4);
      const bf16 logdt = p.log_dt[chn], dskip = p.dskip[chn];
      halo_receive(sb, 0, rb, hg, opaque_tid() - 256);
      kgen_setup(kg, sb, cta, ht, modes, logdt, dskip);
#pragma unroll 1
      for (int u = 0; u < 4; u++) {
        if (u == KG_PRE) {
          KTS(39);
          mbar_wait(bar + 8 * B_AD, 0);
          KTS(41);
        }
        if (u == 4 - KG_LAST) mbar_wait(bar + 8 * (KG_PD ? B_PDONE : B_PS), 0);
        kgen_unit(tab, taba, kg.cur.x, kg.cur.y, {kg.cur.z, kg.cur.w}, kg.T);
        kg.cur = lds128f(kgen_slot(sb, opaque_tid() - 256, u + 1));
      }
      kgen_finish(kg, sb, cta, opaque_tid() - 256);
    }
    KTS(51);
    bar_sync(4, 128);
#pragma unroll 1
    for (int layer = 0; layer < 2; layer++) {
      if (p.stop <= 1 + 3 * layer) return;
      mbar_wait(bar + 8 * (EXP_LATE ? B_PS : B_PDONE), layer);
      expand_taps(sb, opaque_tid() - 256);
      conv_zero(sb, opaque_tid() - 256);
      if (ht == 0) TS(52 + layer);
      warp_release(bar + 8 * B_PE);
      if (p.stop <= 2 + 3 * layer) return;
      {
        uint4 xr[4], st[4];
        const int c = opaque_tid() - 256;
        const SumAddr sa = conv_sum_addr(sb, c);
        conv_prep_load(sb, layer, cta, c, xr, st);
        conv_prep<true>(sb, layer, cta, c, xr, st, sa);
        if (layer == 1 && ht == 0) TS(62);
        const bf16* xup = g_xT + (size_t)(2 * layer * DM + cta) * LSEQ + (c + 128) * 8;
        st[0] = ldcg128(xup);
        mbar_wait(bar + 8 * (B_U + 3), layer);
#pragma unroll
        for (int lc = 0; lc < 4; lc++) {
          if (lc < 3) {
            conv_sums(sa, lc + 1, c);
            fence_async_smem();
            warp_release(bar + 8 * (B_S + lc + 1));
            st[lc + 1] = ldcg128(xup + (lc + 1) * 128 * LSEQ);
          }
          conv_epi(sb, layer, cta, lc, c, xr[lc], st[lc]);
          warp_release(bar + 8 * (B_E + lc));
          if (layer == 1 && lc == 3 && ht == 0) TS(38);
        }
      }
      if (layer == 0 && p.stop > 3) {
        const int c1 = role_id<SMID>();
        stats_publish(sb, 1, role_rb(c1), role_hg(c1), opaque_tid() - 256, part_tag(lds32(sb + SM_EP), 2));
        delay<D_ST>();
        stats_gather(sb, role_rb(c1), opaque_tid() - 256, part_tag(lds32(sb + SM_EP), 2));
        if (ht == 0) TS(25);
        halo_receive(sb, 1, role_rb(c1), role_hg(c1), opaque_tid() - 256);
      }
    }
  } else {
    asm volatile("setmaxnreg.dec.sync.aligned.u32 %0;" ::"n"(512 - 2 * R_CONS - R_HELP));
    const int cta = role_id<SMID>(), rb = role_rb(cta), hg = role_hg(cta), rb2 = role_rb2(cta), q2 = role_q2(cta);
    bar_sync(0, NTHREADS);
    if (warp == 12) {
      if (elect_one()) {
        unsigned epoch = 0;
#pragma unroll 1
        for (int layer = 0; layer < 2; layer++) {
          auto ld_w = [&](int c, int slot) {
            const uint32_t b = bar + 8 * (B_KVF + c);
            mbar_expect(b, 24576);
            tma_ld3(sb + SM_W + slot * 24576, &p.mapW3, hg * 64, c * 64, 0, b);
          };
          if (layer == 0) {
            TS(55);
            mbar_wait(bar + 8 * (B_KVF + 2), 0);
            if (rb2 < 4) tma_prefetch2(&p.mapWo128, q2 * 64, rb2 * 128);
            asm volatile("prefetch.tensormap [%0];" ::"l"(&p.mapO) : "memory");
            asm volatile("prefetch.tensormap [%0];" ::"l"(&p.mapO128) : "memory");
            asm volatile("prefetch.tensormap [%0];" ::"l"(&p.mapXT) : "memory");
            asm volatile("prefetch.tensormap [%0];" ::"l"(&p.mapXT3) : "memory");
            mbar_wait(bar + 8 * B_EP, 0);
            epoch = lds32(sb + SM_EP);
          } else {
            mbar_wait(bar + 8 * B_PDONE, 0);
            ld_w(0, 0); ld_w(1, 1);
            mbar_wait(bar + 8 * (W2_LATE ? B_U : B_RE), 0);
            ld_w(2, 2);
          }
          {
            int slot = 0;
#pragma unroll 1
            for (int c = 3; c < 8; c++) {
              mbar_wait(bar + 8 * (B_KVE + c - 3), layer);
              ld_w(c, slot);
              slot = slot == 2 ? 0 : slot + 1;
            }
          }
          if (p.stop <= 1 + 3 * layer) return;
          mbar_wait(bar + 8 * B_QDONE, layer);
          mbar_wait(bar + 8 * B_HF, layer);
#pragma unroll 1
          for (int c = 0; c < 4; c++) {
            const uint32_t b = bar + 8 * (B_WOF + c);
            mbar_expect(b, 16384);
            tma_ld(sb + SM_WO + c * 16384, &p.mapWo128, q2 * 64, c * 128, b);
          }
          {
            const uint32_t b = bar + 8 * B_RF;
            mbar_expect(b, 16384);
            if (layer == 0) tma_ld(sb + SM_R, &p.mapX128, (rb2 >> 3) * DM + q2 * 64, (rb2 & 7) * 128, b);
            else tma_ld3(sb + SM_R, &p.mapXT3, 0, DM + q2 * 64, rb2 * 2, b);
          }
          spin_until(&g_cnt[(C_O + rb2) * 32], (2 * epoch + layer + 1) * 16);
          fence_async_global();
#pragma unroll 1
          for (int c = 0; c < 8; c++) {
            const uint32_t b = bar + 8 * (B_OF + c);
            if (c == 4) { mbar_wait(bar + 8 * B_OST, layer); fence_async_smem(); }
            mbar_expect(b, 16384);
            tma_ld(sb + sm_o(c), &p.mapO128, c * 64, rb2 * 128, b);
          }
          if (p.stop <= 3 + 3 * layer) return;
        }
      }
    } else if (warp == 13) {
      if (elect_one() && p.stop > 3) {
        mbar_wait(bar + 8 * B_GB, 0);
        const unsigned target = (lds32(sb + SM_EP) + 1) * NCTA;
        auto ld_x = [&](int c) {
          mbar_expect(bar + 8 * (B_XF + c), 16384);
          tma_ld3(sb + SM_X + c * 16384, &p.mapXT3, 0, DM + c * 64, rb * 2, bar + 8 * (B_XF + c));
        };
        int done = 0, it = 0;
        while (done < 4) {
          const uint4 v = ld_tagged((const uint4*)&g_cnt[C_G1 * 32]);
          const int n = (int)(v.x - target) < 0 ? 0 : (int)(v.y - target) < 0 ? 1 : (int)(v.z - target) < 0 ? 2 : (int)(v.w - target) < 0 ? 3 : 4;
          if (++it > (1 << 23)) __trap();
          if (n == done) continue;
          if (n == 4) TS(44);
          fence_async_global();
          fence_async_smem();
          const int first = n == 4 && done > 1 ? 6 + (hg >> 2) : -1;
          if (first >= 0) ld_x(first);
#pragma unroll 1
          for (int c = 2 * done; c < 2 * n; c++)
            if (c != first) ld_x(c);
          done = n;
        }
      }
    } else if (warp == 15) {
      mbar_wait(bar + 8 * B_EP, 0);
      const unsigned epoch = lds32(sb + SM_EP);
#pragma unroll 1
      for (int layer = 0; layer < 2; layer++) {
#pragma unroll 1
        for (int i = 0; i < 6; i++) {
          mbar_wait(bar + 8 * (B_KVF + (FILL_AT + i < 7 ? FILL_AT + i : 7)), layer);
          uint4* dst = (uint4*)(g_xT + (size_t)(i < 4 ? 2 * layer * DM + cv_chan(cta, i) : 3 * DM + cv_chan(cta, 2 * layer + i - 4)) * LSEQ) + lane;
#pragma unroll
          for (int k = 0; k < 8; k++) dst[32 * k] = make_uint4(~0u, ~0u, ~0u, ~0u);
        }
        if (lane < 8) ((uint4*)g_stats)[layer * 1024 + cta * 8 + lane] = make_uint4(0, 0, 0, 0);
        __syncwarp();
        if (elect_one()) {
          red_release(&g_cnt[C_CS * 32 + layer]);
          spin_until(&g_cnt[C_CS * 32 + layer], (epoch + 1) * (layer ? NCTA : NARR));
          mbar_arrive(bar + 8 * B_ZF);
          if (layer == 0 && p.stop > 2) {
#pragma unroll 1
            for (int lc = 0; lc < 4; lc++) {
              mbar_wait(bar + 8 * (B_E + lc), 0);
              fence_reader();
              bulk_st(g_xT + (size_t)(DM + cv_chan(cta, lc)) * LSEQ, sb + cv_s(lc), 4096);
              bulk_commit();
              bulk_wait_all();
              red_relaxed(&g_cnt[C_G1 * 32 + lc]);
              if (lc == 3) TS(18);
            }
          }
        }
        __syncwarp();
        if (p.stop <= 3) return;
      }
    } else if (warp == 14) {
      mbar_wait(bar + 8 * B_EP, 0);
      const unsigned epoch = lds32(sb + SM_EP);
#pragma unroll 1
      for (int layer = 0; layer < 2; layer++) {
        if (p.stop <= 1 + 3 * layer) return;
        mbar_wait(bar + 8 * B_ZF, layer);
        mbar_wait(bar + 8 * (EXP_LATE ? B_PS : B_PDONE), layer);
        delay<D_PST>();
        proj_stats(layer, rb2, q2, lane, part_tag(epoch, 2 * layer + 1));
        if (layer == 1 && lane == 0) TS(5);
        delay<D_PREP>();
        if (lane == 0) mbar_arrive(bar + 8 * B_GB);
      }
    }
  }
}

typedef CUresult (*EncodeFn)(CUtensorMap*, CUtensorMapDataType, cuuint32_t, void*, const cuuint64_t*, const cuuint64_t*,
                             const cuuint32_t*, const cuuint32_t*, CUtensorMapInterleave, CUtensorMapSwizzle,
                             CUtensorMapL2promotion, CUtensorMapFloatOOBfill);

static void make_map(EncodeFn enc, CUtensorMap* m, void* ptr, uint64_t cols, uint64_t rows, uint32_t box_rows) {
  cuuint64_t dims[2] = {cols, rows};
  cuuint64_t strides[1] = {cols * 2};
  cuuint32_t box[2] = {64, box_rows};
  cuuint32_t es[2] = {1, 1};
  enc(m, CU_TENSOR_MAP_DATA_TYPE_BFLOAT16, 2, ptr, dims, strides, box, es, CU_TENSOR_MAP_INTERLEAVE_NONE,
      CU_TENSOR_MAP_SWIZZLE_128B, CU_TENSOR_MAP_L2_PROMOTION_L2_128B, CU_TENSOR_MAP_FLOAT_OOB_FILL_NONE);
}
static void make_map3(EncodeFn enc, CUtensorMap* m, void* ptr, uint64_t d0, uint64_t cols, uint64_t rows, uint64_t blk_stride,
                      uint64_t nblocks, uint32_t nblk, uint32_t box_rows = 64) {
  cuuint64_t dims[3] = {d0, rows, nblocks};
  cuuint64_t strides[2] = {cols * 2, blk_stride * 2};
  cuuint32_t box[3] = {64, box_rows, nblk};
  cuuint32_t es[3] = {1, 1, 1};
  enc(m, CU_TENSOR_MAP_DATA_TYPE_BFLOAT16, 3, ptr, dims, strides, box, es, CU_TENSOR_MAP_INTERLEAVE_NONE,
      CU_TENSOR_MAP_SWIZZLE_128B, CU_TENSOR_MAP_L2_PROMOTION_L2_128B, CU_TENSOR_MAP_FLOAT_OOB_FILL_NONE);
}

extern "C" void kernel_launch(void* const* d_in, const int* in_sizes, int n_in, void* d_out, int out_size) {
  static Params prm;
  static void* cached[13] = {nullptr};
  static bool attr_done = false, by_smid = false;
  bool same = attr_done && cached[12] == d_out;
  for (int i = 0; i < 12 && same; i++) same = cached[i] == d_in[i];
  if (!same) {
    void* fn = nullptr;
    cudaDriverEntryPointQueryResult qr;
    cudaGetDriverEntryPoint("cuTensorMapEncodeTiled", &fn, cudaEnableDefault, &qr);
    EncodeFn enc = (EncodeFn)fn;
    void *pO, *pXT;
    cudaGetSymbolAddress(&pO, g_O);
    cudaGetSymbolAddress(&pXT, g_xT);
    make_map(enc, &prm.mapO, pO, DM, LSEQ, 64);
    make_map(enc, &prm.mapXT, pXT, LSEQ, 4 * DM, 64);
    prm.out = (bf16*)d_out;
    make_map(enc, &prm.mapX128, d_in[0], 2 * DM, LSEQ / 2, 128);
    make_map(enc, &prm.mapWo128, d_in[2], DM, DM, 128);
    make_map(enc, &prm.mapO128, pO, DM, LSEQ, 128);
    make_map3(enc, &prm.mapW3, d_in[1], DM, 3 * DM, DM, DM, 3, 3);
    make_map3(enc, &prm.mapW3h, d_in[1], DM, 3 * DM, DM, DM, 3, 3, 32);
    make_map3(enc, &prm.mapXT3, pXT, 64, LSEQ, 4 * DM, 64, 32, 2);
    prm.a_re = (const bf16*)d_in[4]; prm.a_im = (const bf16*)d_in[5];
    prm.b_re = (const bf16*)d_in[6]; prm.b_im = (const bf16*)d_in[7];
    prm.c_re = (const bf16*)d_in[8]; prm.c_im = (const bf16*)d_in[9];
    prm.log_dt = (const bf16*)d_in[10]; prm.dskip = (const bf16*)d_in[11];
    int dev = 0, sms = 0;
    cudaGetDevice(&dev);
    cudaDeviceGetAttribute(&sms, cudaDevAttrMultiProcessorCount, dev);
    by_smid = sms == 132;
    cudaFuncSetAttribute(fused_kernel<true>, cudaFuncAttributeMaxDynamicSharedMemorySize, SM_TOTAL);
    cudaFuncSetAttribute(fused_kernel<false>, cudaFuncAttributeMaxDynamicSharedMemorySize, SM_TOTAL);
    for (int i = 0; i < 12; i++) cached[i] = d_in[i];
    cached[12] = d_out;
    attr_done = true;
  }
  prm.stop = 100;
    if (by_smid) fused_kernel<true><<<132, NTHREADS, SM_TOTAL>>>(prm);
  else fused_kernel<false><<<NCTA, NTHREADS, SM_TOTAL>>>(prm);
}
```

```cpp
#include <cuda_runtime.h>
#include <cuda_bf16.h>
#include <cuda.h>
#include <stdint.h>

typedef __nv_bfloat16 bf16;

constexpr int LSEQ = 2048;
constexpr int DM = 512;
constexpr int NCTA = 128;
constexpr int NTHREADS = 512;
#define RR 0
#define KG_PRE 2
#define W2_LATE 1
#define FILL_AT 2
#define EXP_LATE 1
#define RFENCE 1
#define D_FIN 550
#define D_PREP 500
#define D_PST 0
#define D_HALO 300
#define STAG 2
#define D_ST 0
#define TLAYER 1
#define KG_PD 1
#define SUM_F32 0
#define CS_LATE0 1
#define D_HALO1 0
#define H_ORDER 1
#define D_START 200
#define D_CS 300
#define D_ST0 400
#define KG_LAST 1
#define X_JIT 0
#define KG_GATE 2
#define R_CONS 192
#define R_HELP 88

constexpr int SM_X = 0;
constexpr int SM_W = 131072;
constexpr int SM_KVX = SM_X;
constexpr int SM_OST = SM_X + 32768;
constexpr int SM_WO = SM_X + 65536;
__host__ __device__ constexpr int sm_o(int c) { return c < 4 ? SM_W + c * 16384 : SM_X + (c - 4) * 16384; }
constexpr int SM_R = 196608;
constexpr int SM_T = 212992;
constexpr int SM_KC = 217088;
constexpr int KC_STRIDE = 648;
constexpr int SM_CS = SM_KC + 4 * KC_STRIDE * 2;
constexpr int SM_CW = SM_R + 8192;
constexpr int SM_EP = SM_CS + 768;
constexpr int SM_BAR = SM_EP + 16;
constexpr int SM_T2 = SM_BAR + 896;
constexpr int SM_HALO = SM_T2 + 4096;
constexpr int SM_ST = SM_HALO + 3072;
constexpr int SM_TOTAL = SM_HALO + 4096;
static_assert(SM_TOTAL <= 232448, "shared memory");

constexpr int CV_UH = 140 * 16;
constexpr int CV_PECH = 1120 * 4;
constexpr int CV_PBW = 2112 * 2;
__host__ __device__ constexpr int cv_s(int lc) { return SM_X + lc * 32768; }
__host__ __device__ constexpr int cv_u(int lc) { return cv_s(lc) + 4096; }
__host__ __device__ constexpr int cv_pe(int lc) { return cv_u(lc) + 2 * CV_UH; }
__host__ __device__ constexpr int cv_pb(int lc) { return cv_pe(lc) + CV_PECH; }
__host__ __device__ constexpr int cv_ft(int lc) { return cv_pb(lc) + 4 * CV_PBW; }
static_assert(cv_ft(0) + 1024 <= 32768, "conv buffers");
__host__ __device__ constexpr int cv_chan(int cta, int lc) { return cta + 128 * lc; }

enum {
  B_XF = 0,
  B_KVF = 8,
  B_OF = 16,
  B_WOF = 24,
  B_T = 31,
  B_RF = 28,
  B_RE = 29,
  B_CW = 30,
  B_GB = 35,
  B_EP = 36,
  B_ZF = 37,
  B_SD = 38,
  B_KVE = 40,
  B_AD = 45,
  B_OST = 46,
  B_QDONE = 47,
  B_PDONE = 48,
  B_S = 50,
  B_E = 54,
  B_P = 58,
  B_PE = 62,
  B_STF = 63,
  B_CSF = 64,
  B_HF = 65,
  B_U = 70,
  B_PS = 74,
  B_COUNT = 80
};

enum {
  C_CS = 0,
  C_G1 = 2,
  C_O = 4,
  C_COUNT = 20
};

__device__ __align__(128) unsigned g_cnt[C_COUNT * 32];
__device__ __align__(1024) bf16 g_O[LSEQ * DM];
__device__ __align__(1024) bf16 g_xT[4 * DM * LSEQ];
__device__ __align__(1024) float g_stats[2 * LSEQ * 2];
__device__ __align__(1024) uint4 g_colsum[8 * 16 * 48];
__device__ __align__(1024) uint4 g_halo[16 * 8 * 192];
__device__ __align__(1024) uint2 g_part[16 * 8 * 128];
#define TS(i) do { } while (0)

#define ATS(i, th) do { } while (0)
#define KTS(i) do { if (ht == 0) TS(i); } while (0)
#define FTS(i) do { } while (0)
#define LTS(i) do { } while (0)

struct Params {
  CUtensorMap mapO, mapXT, mapX128, mapWo128, mapO128, mapW3, mapW3h, mapXT3;
  const bf16 *a_re, *a_im, *b_re, *b_im, *c_re, *c_im, *log_dt, *dskip;
  bf16* out;
  int stop;
};

__device__ __forceinline__ uint32_t s32(const void* p) { return (uint32_t)__cvta_generic_to_shared(p); }
__device__ __forceinline__ void mbar_init(uint32_t b, int c) { asm volatile("mbarrier.init.shared::cta.b64 [%0], %1;" ::"r"(b), "r"(c) : "memory"); }
__device__ __forceinline__ void mbar_expect(uint32_t b, int bytes) { asm volatile("mbarrier.arrive.expect_tx.shared::cta.b64 _, [%0], %1;" ::"r"(b), "r"(bytes) : "memory"); }
__device__ __forceinline__ void mbar_arrive(uint32_t b) { asm volatile("mbarrier.arrive.shared::cta.b64 _, [%0];" ::"r"(b) : "memory"); }
__device__ __forceinline__ void mbar_arrive_if(uint32_t b, bool c) {
  asm volatile("{\n.reg .pred p;\nsetp.ne.u32 p, %1, 0;\n@p mbarrier.arrive.shared::cta.b64 _, [%0];\n}" ::"r"(b), "r"((uint32_t)c) : "memory");
}
__device__ __forceinline__ void mbar_wait(uint32_t b, int parity) {
  asm volatile("{\n.reg .pred p;\nWAIT_LOOP:\nmbarrier.try_wait.parity.shared::cta.b64 p, [%0], %1;\n@p bra WAIT_DONE;\nbra WAIT_LOOP;\nWAIT_DONE:\n}" ::"r"(b), "r"(parity) : "memory");
}
template <int N> __device__ __forceinline__ void delay() {
  if constexpr (N > 0) {
    uint32_t t0, t;
    asm volatile("mov.u32 %0, %%clock;" : "=r"(t0));
    do { asm volatile("mov.u32 %0, %%clock;" : "=r"(t)); } while (t - t0 < N);
  }
}
__device__ __forceinline__ int opaque_tid() { int v; asm volatile("mov.u32 %0, %%tid.x;" : "=r"(v)); return v; }
__device__ __forceinline__ bool elect_one() {
  uint32_t r;
  asm volatile("{\n.reg .pred p;\nelect.sync _|p, 0xffffffff;\nselp.u32 %0, 1, 0, p;\n}" : "=r"(r));
  return r != 0;
}
__device__ __forceinline__ void tma_ld(uint32_t dst, const CUtensorMap* m, int c0, int c1, uint32_t bar) {
  asm volatile("cp.async.bulk.tensor.2d.shared::cluster.global.mbarrier::complete_tx::bytes [%0], [%1, {%3, %4}], [%2];"
               ::"r"(dst), "l"(m), "r"(bar), "r"(c0), "r"(c1) : "memory");
}
__device__ __forceinline__ void tma_ld3(uint32_t dst, const CUtensorMap* m, int c0, int c1, int c2, uint32_t bar) {
  asm volatile("cp.async.bulk.tensor.3d.shared::cluster.global.mbarrier::complete_tx::bytes [%0], [%1, {%3, %4, %5}], [%2];"
               ::"r"(dst), "l"(m), "r"(bar), "r"(c0), "r"(c1), "r"(c2) : "memory");
}
__device__ __forceinline__ void tma_prefetch2(const CUtensorMap* m, int c0, int c1) {
  asm volatile("cp.async.bulk.prefetch.tensor.2d.L2.global.tile [%0, {%1, %2}];" ::"l"(m), "r"(c0), "r"(c1) : "memory");
}
__device__ __forceinline__ void tma_prefetch3(const CUtensorMap* m, int c0, int c1, int c2) {
  asm volatile("cp.async.bulk.prefetch.tensor.3d.L2.global.tile [%0, {%1, %2, %3}];" ::"l"(m), "r"(c0), "r"(c1), "r"(c2) : "memory");
}
__device__ __forceinline__ void tma_st(const CUtensorMap* m, int c0, int c1, uint32_t src) {
  asm volatile("cp.async.bulk.tensor.2d.global.shared::cta.bulk_group [%0, {%2, %3}], [%1];" ::"l"(m), "r"(src), "r"(c0), "r"(c1) : "memory");
}
__device__ __forceinline__ void bulk_ld(uint32_t dst, const void* src, int bytes, uint32_t bar) {
  asm volatile("cp.async.bulk.shared::cluster.global.mbarrier::complete_tx::bytes [%0], [%1], %2, [%3];" ::"r"(dst), "l"(src), "r"(bytes), "r"(bar) : "memory");
}
__device__ __forceinline__ void bulk_st(void* dst, uint32_t src, int bytes) {
  asm volatile("cp.async.bulk.global.shared::cta.bulk_group [%0], [%1], %2;" ::"l"(dst), "r"(src), "r"(bytes) : "memory");
}
__device__ __forceinline__ void bulk_red_add_f32(void* dst, uint32_t src, int bytes) {
  asm volatile("cp.reduce.async.bulk.global.shared::cta.bulk_group.add.f32 [%0], [%1], %2;" ::"l"(dst), "r"(src), "r"(bytes) : "memory");
}
__device__ __forceinline__ void bulk_commit() { asm volatile("cp.async.bulk.commit_group;" ::: "memory"); }
__device__ __forceinline__ void bulk_wait_all() { asm volatile("cp.async.bulk.wait_group 0;" ::: "memory"); }
__device__ __forceinline__ void fence_async_smem() { asm volatile("fence.proxy.async.shared::cta;" ::: "memory"); }
__device__ __forceinline__ void fence_writer() { if (!RFENCE) fence_async_smem(); }
__device__ __forceinline__ void fence_reader() { if (RFENCE) fence_async_smem(); }
__device__ __forceinline__ void fence_async_global() { asm volatile("fence.proxy.async.global;" ::: "memory"); }
__device__ __forceinline__ void bar_sync(int id, int n) { asm volatile("bar.sync %0, %1;" ::"r"(id), "r"(n) : "memory"); }
__device__ __forceinline__ void bar_arrive(int id, int n) { asm volatile("bar.arrive %0, %1;" ::"r"(id), "r"(n) : "memory"); }
__device__ __forceinline__ void wg_fence() { asm volatile("wgmma.fence.sync.aligned;" ::: "memory"); }
__device__ __forceinline__ void wg_commit() { asm volatile("wgmma.commit_group.sync.aligned;" ::: "memory"); }
template <int N> __device__ __forceinline__ void wg_wait() { asm volatile("wgmma.wait_group.sync.aligned %0;" ::"n"(N) : "memory"); }
__device__ __forceinline__ uint64_t mkdesc(uint32_t addr, uint32_t lbo, uint32_t sbo, int sw) {
  return (uint64_t)((addr & 0x3FFFF) >> 4) | ((uint64_t)(lbo >> 4) << 16) | ((uint64_t)(sbo >> 4) << 32) | ((uint64_t)sw << 62);
}
__device__ __forceinline__ void ldsm4(uint32_t* r, uint32_t a) {
  asm volatile("ldmatrix.sync.aligned.m8n8.x4.shared.b16 {%0,%1,%2,%3}, [%4];" : "=r"(r[0]), "=r"(r[1]), "=r"(r[2]), "=r"(r[3]) : "r"(a) : "memory");
}
__device__ __forceinline__ void ldsm4t(uint32_t* r, uint32_t a) {
  asm volatile("ldmatrix.sync.aligned.m8n8.x4.trans.shared.b16 {%0,%1,%2,%3}, [%4];" : "=r"(r[0]), "=r"(r[1]), "=r"(r[2]), "=r"(r[3]) : "r"(a) : "memory");
}
__device__ __forceinline__ void stsm4(uint32_t a, uint32_t r0, uint32_t r1, uint32_t r2, uint32_t r3) {
  asm volatile("stmatrix.sync.aligned.m8n8.x4.shared.b16 [%0], {%1,%2,%3,%4};" ::"r"(a), "r"(r0), "r"(r1), "r"(r2), "r"(r3) : "memory");
}
__device__ __forceinline__ void stsm4t(uint32_t a, uint32_t r0, uint32_t r1, uint32_t r2, uint32_t r3) {
  asm volatile("stmatrix.sync.aligned.m8n8.x4.trans.shared.b16 [%0], {%1,%2,%3,%4};" ::"r"(a), "r"(r0), "r"(r1), "r"(r2), "r"(r3) : "memory");
}
__device__ __forceinline__ uint32_t movm_t(uint32_t a) { uint32_t r; asm volatile("movmatrix.sync.aligned.m8n8.trans.b16 %0, %1;" : "=r"(r) : "r"(a)); return r; }
__device__ __forceinline__ uint32_t lds32(uint32_t a) { uint32_t v; asm volatile("ld.shared.b32 %0, [%1];" : "=r"(v) : "r"(a) : "memory"); return v; }
__device__ __forceinline__ float2 lds64f(uint32_t a) { float2 v; asm volatile("ld.shared.v2.f32 {%0,%1}, [%2];" : "=f"(v.x), "=f"(v.y) : "r"(a) : "memory"); return v; }
__device__ __forceinline__ float4 lds128f(uint32_t a) { float4 v; asm volatile("ld.shared.v4.f32 {%0,%1,%2,%3}, [%4];" : "=f"(v.x), "=f"(v.y), "=f"(v.z), "=f"(v.w) : "r"(a) : "memory"); return v; }
__device__ __forceinline__ uint4 lds128(uint32_t a) { uint4 v; asm volatile("ld.shared.v4.b32 {%0,%1,%2,%3}, [%4];" : "=r"(v.x), "=r"(v.y), "=r"(v.z), "=r"(v.w) : "r"(a) : "memory"); return v; }
__device__ __forceinline__ void sts128(uint32_t a, uint4 v) { asm volatile("st.shared.v4.b32 [%0], {%1,%2,%3,%4};" ::"r"(a), "r"(v.x), "r"(v.y), "r"(v.z), "r"(v.w) : "memory"); }
__device__ __forceinline__ void sts128f(uint32_t a, float x, float y, float z, float w) { asm volatile("st.shared.v4.f32 [%0], {%1,%2,%3,%4};" ::"r"(a), "f"(x), "f"(y), "f"(z), "f"(w) : "memory"); }
__device__ __forceinline__ void sts32f(uint32_t a, float v) { asm volatile("st.shared.f32 [%0], %1;" ::"r"(a), "f"(v) : "memory"); }
__device__ __forceinline__ void sts16(uint32_t a, uint16_t v) { asm volatile("st.shared.u16 [%0], %1;" ::"r"(a), "h"(v) : "memory"); }
__device__ __forceinline__ uint32_t lds16(uint32_t a) { uint16_t v; asm volatile("ld.shared.u16 %0, [%1];" : "=h"(v) : "r"(a) : "memory"); return v; }
__device__ __forceinline__ uint32_t packbf(float lo, float hi) { uint32_t r; asm("cvt.rn.bf16x2.f32 %0, %1, %2;" : "=r"(r) : "f"(hi), "f"(lo)); return r; }
__device__ __forceinline__ float bf_lo(uint32_t v) { return __uint_as_float(v << 16); }
__device__ __forceinline__ float bf_hi(uint32_t v) { return __uint_as_float(v & 0xffff0000u); }
__device__ __forceinline__ float ex2(float x) { float r; asm("ex2.approx.ftz.f32 %0, %1;" : "=f"(r) : "f"(x)); return r; }
__device__ __forceinline__ float rsqrt_approx(float x) { float r; asm("rsqrt.approx.ftz.f32 %0, %1;" : "=f"(r) : "f"(x)); return r; }
__device__ __forceinline__ float rcp_approx(float x) { float r; asm("rcp.approx.ftz.f32 %0, %1;" : "=f"(r) : "f"(x)); return r; }
__device__ __forceinline__ void mma_bf16(float* d, const uint32_t* a, uint32_t b0, uint32_t b1) {
  asm("mma.sync.aligned.m16n8k16.row.col.f32.bf16.bf16.f32 {%0,%1,%2,%3}, {%4,%5,%6,%7}, {%8,%9}, {%0,%1,%2,%3};"
               : "+f"(d[0]), "+f"(d[1]), "+f"(d[2]), "+f"(d[3]) : "r"(a[0]), "r"(a[1]), "r"(a[2]), "r"(a[3]), "r"(b0), "r"(b1));
}
__device__ __forceinline__ void mma_bf16_k8(float* d, uint32_t a0, uint32_t a1, uint32_t b) {
  asm("mma.sync.aligned.m16n8k8.row.col.f32.bf16.bf16.f32 {%0,%1,%2,%3}, {%4,%5}, {%6}, {%0,%1,%2,%3};"
      : "+f"(d[0]), "+f"(d[1]), "+f"(d[2]), "+f"(d[3]) : "r"(a0), "r"(a1), "r"(b));
}
__device__ __forceinline__ void red_release(unsigned* p) { asm volatile("red.release.gpu.global.add.u32 [%0], 1;" ::"l"(p) : "memory"); }
__device__ __forceinline__ void red_relaxed(unsigned* p) { asm volatile("red.relaxed.gpu.global.add.u32 [%0], 1;" ::"l"(p) : "memory"); }
__device__ __forceinline__ unsigned ld_relaxed(const unsigned* p) { unsigned v; asm volatile("ld.relaxed.gpu.global.u32 %0, [%1];" : "=r"(v) : "l"(p) : "memory"); return v; }
__device__ __forceinline__ void spin_until(const unsigned* p, unsigned target) {
  int it = 0;
  while ((int)(ld_relaxed(p) - target) < 0) {
    if (++it > (1 << 23)) __trap();
  }
}
__device__ __forceinline__ uint4 ldcg128(const void* p) { uint4 v; asm volatile("ld.global.cg.v4.b32 {%0,%1,%2,%3}, [%4];" : "=r"(v.x), "=r"(v.y), "=r"(v.z), "=r"(v.w) : "l"(p) : "memory"); return v; }
__device__ __forceinline__ uint4 ld_tagged(const uint4* p) { uint4 v; asm volatile("ld.relaxed.gpu.global.v4.u32 {%0,%1,%2,%3}, [%4];" : "=r"(v.x), "=r"(v.y), "=r"(v.z), "=r"(v.w) : "l"(p) : "memory"); return v; }
__device__ __forceinline__ uint2 ld_part(const uint2* p) { uint2 v; asm volatile("ld.relaxed.gpu.global.v2.u32 {%0,%1}, [%2];" : "=r"(v.x), "=r"(v.y) : "l"(p) : "memory"); return v; }
__device__ __forceinline__ void st_part(uint2* p, float s, float q, uint32_t tag) {
  asm volatile("st.relaxed.gpu.global.v2.u32 [%0], {%1,%2};" ::"l"(p), "r"(__float_as_uint(s)), "r"((__float_as_uint(q) & ~7u) | tag) : "memory");
}
__device__ __forceinline__ uint32_t part_tag(uint32_t epoch, int k) { return (4 * (epoch % 7) + k) % 7 + 1; }
__device__ __forceinline__ void st_tagged3(uint4* p, uint32_t a, uint32_t b, uint32_t c, uint32_t tag) { asm volatile("st.relaxed.gpu.global.v4.u32 [%0], {%1,%2,%3,%4};" ::"l"(p), "r"(a), "r"(b), "r"(c), "r"(tag) : "memory"); }
__device__ __forceinline__ uint32_t hadd2(uint32_t a, uint32_t b) { uint32_t r; asm("add.rn.bf16x2 %0, %1, %2;" : "=r"(r) : "r"(a), "r"(b)); return r; }
__device__ __forceinline__ uint32_t hmul2(uint32_t a, uint32_t b) { uint32_t r; asm("mul.rn.bf16x2 %0, %1, %2;" : "=r"(r) : "r"(a), "r"(b)); return r; }

template<int N,int TB> __device__ __forceinline__ void wgmma_rs(float* d, const uint32_t* a, uint64_t db, int sd);
template<int N,int TA,int TB> __device__ __forceinline__ void wgmma_ss(float* d, uint64_t da, uint64_t db, int sd);
template<> __device__ __forceinline__ void wgmma_rs<128,0>(float* d, const uint32_t* a, uint64_t db, int sd) {
  asm volatile("{\n.reg .pred p;\nsetp.ne.b32 p, %69, 0;\nwgmma.mma_async.sync.aligned.m64n128k16.f32.bf16.bf16 {%0,%1,%2,%3,%4,%5,%6,%7,%8,%9,%10,%11,%12,%13,%14,%15,%16,%17,%18,%19,%20,%21,%22,%23,%24,%25,%26,%27,%28,%29,%30,%31,%32,%33,%34,%35,%36,%37,%38,%39,%40,%41,%42,%43,%44,%45,%46,%47,%48,%49,%50,%51,%52,%53,%54,%55,%56,%57,%58,%59,%60,%61,%62,%63}, {%64,%65,%66,%67}, %68, p, 1, 1, 0;\n}\n"
   : "+f"(d[0]),"+f"(d[1]),"+f"(d[2]),"+f"(d[3]),"+f"(d[4]),"+f"(d[5]),"+f"(d[6]),"+f"(d[7]),"+f"(d[8]),"+f"(d[9]),"+f"(d[10]),"+f"(d[11]),"+f"(d[12]),"+f"(d[13]),"+f"(d[14]),"+f"(d[15]),"+f"(d[16]),"+f"(d[17]),"+f"(d[18]),"+f"(d[19]),"+f"(d[20]),"+f"(d[21]),"+f"(d[22]),"+f"(d[23]),"+f"(d[24]),"+f"(d[25]),"+f"(d[26]),"+f"(d[27]),"+f"(d[28]),"+f"(d[29]),"+f"(d[30]),"+f"(d[31]),"+f"(d[32]),"+f"(d[33]),"+f"(d[34]),"+f"(d[35]),"+f"(d[36]),"+f"(d[37]),"+f"(d[38]),"+f"(d[39]),"+f"(d[40]),"+f"(d[41]),"+f"(d[42]),"+f"(d[43]),"+f"(d[44]),"+f"(d[45]),"+f"(d[46]),"+f"(d[47]),"+f"(d[48]),"+f"(d[49]),"+f"(d[50]),"+f"(d[51]),"+f"(d[52]),"+f"(d[53]),"+f"(d[54]),"+f"(d[55]),"+f"(d[56]),"+f"(d[57]),"+f"(d[58]),"+f"(d[59]),"+f"(d[60]),"+f"(d[61]),"+f"(d[62]),"+f"(d[63])
   : "r"(a[0]), "r"(a[1]), "r"(a[2]), "r"(a[3]), "l"(db), "r"(sd));
}
template<> __device__ __forceinline__ void wgmma_rs<120,0>(float* d, const uint32_t* a, uint64_t db, int sd) {
  asm volatile("{\n.reg .pred p;\nsetp.ne.b32 p, %65, 0;\nwgmma.mma_async.sync.aligned.m64n120k16.f32.bf16.bf16 {%0,%1,%2,%3,%4,%5,%6,%7,%8,%9,%10,%11,%12,%13,%14,%15,%16,%17,%18,%19,%20,%21,%22,%23,%24,%25,%26,%27,%28,%29,%30,%31,%32,%33,%34,%35,%36,%37,%38,%39,%40,%41,%42,%43,%44,%45,%46,%47,%48,%49,%50,%51,%52,%53,%54,%55,%56,%57,%58,%59}, {%60,%61,%62,%63}, %64, p, 1, 1, 0;\n}\n"
   : "+f"(d[0]),"+f"(d[1]),"+f"(d[2]),"+f"(d[3]),"+f"(d[4]),"+f"(d[5]),"+f"(d[6]),"+f"(d[7]),"+f"(d[8]),"+f"(d[9]),"+f"(d[10]),"+f"(d[11]),"+f"(d[12]),"+f"(d[13]),"+f"(d[14]),"+f"(d[15]),"+f"(d[16]),"+f"(d[17]),"+f"(d[18]),"+f"(d[19]),"+f"(d[20]),"+f"(d[21]),"+f"(d[22]),"+f"(d[23]),"+f"(d[24]),"+f"(d[25]),"+f"(d[26]),"+f"(d[27]),"+f"(d[28]),"+f"(d[29]),"+f"(d[30]),"+f"(d[31]),"+f"(d[32]),"+f"(d[33]),"+f"(d[34]),"+f"(d[35]),"+f"(d[36]),"+f"(d[37]),"+f"(d[38]),"+f"(d[39]),"+f"(d[40]),"+f"(d[41]),"+f"(d[42]),"+f"(d[43]),"+f"(d[44]),"+f"(d[45]),"+f"(d[46]),"+f"(d[47]),"+f"(d[48]),"+f"(d[49]),"+f"(d[50]),"+f"(d[51]),"+f"(d[52]),"+f"(d[53]),"+f"(d[54]),"+f"(d[55]),"+f"(d[56]),"+f"(d[57]),"+f"(d[58]),"+f"(d[59])
   : "r"(a[0]), "r"(a[1]), "r"(a[2]), "r"(a[3]), "l"(db), "r"(sd));
}
template<> __device__ __forceinline__ void wgmma_rs<112,0>(float* d, const uint32_t* a, uint64_t db, int sd) {
  asm volatile("{\n.reg .pred p;\nsetp.ne.b32 p, %61, 0;\nwgmma.mma_async.sync.aligned.m64n112k16.f32.bf16.bf16 {%0,%1,%2,%3,%4,%5,%6,%7,%8,%9,%10,%11,%12,%13,%14,%15,%16,%17,%18,%19,%20,%21,%22,%23,%24,%25,%26,%27,%28,%29,%30,%31,%32,%33,%34,%35,%36,%37,%38,%39,%40,%41,%42,%43,%44,%45,%46,%47,%48,%49,%50,%51,%52,%53,%54,%55}, {%56,%57,%58,%59}, %60, p, 1, 1, 0;\n}\n"
   : "+f"(d[0]),"+f"(d[1]),"+f"(d[2]),"+f"(d[3]),"+f"(d[4]),"+f"(d[5]),"+f"(d[6]),"+f"(d[7]),"+f"(d[8]),"+f"(d[9]),"+f"(d[10]),"+f"(d[11]),"+f"(d[12]),"+f"(d[13]),"+f"(d[14]),"+f"(d[15]),"+f"(d[16]),"+f"(d[17]),"+f"(d[18]),"+f"(d[19]),"+f"(d[20]),"+f"(d[21]),"+f"(d[22]),"+f"(d[23]),"+f"(d[24]),"+f"(d[25]),"+f"(d[26]),"+f"(d[27]),"+f"(d[28]),"+f"(d[29]),"+f"(d[30]),"+f"(d[31]),"+f"(d[32]),"+f"(d[33]),"+f"(d[34]),"+f"(d[35]),"+f"(d[36]),"+f"(d[37]),"+f"(d[38]),"+f"(d[39]),"+f"(d[40]),"+f"(d[41]),"+f"(d[42]),"+f"(d[43]),"+f"(d[44]),"+f"(d[45]),"+f"(d[46]),"+f"(d[47]),"+f"(d[48]),"+f"(d[49]),"+f"(d[50]),"+f"(d[51]),"+f"(d[52]),"+f"(d[53]),"+f"(d[54]),"+f"(d[55])
   : "r"(a[0]), "r"(a[1]), "r"(a[2]), "r"(a[3]), "l"(db), "r"(sd));
}
template<> __device__ __forceinline__ void wgmma_rs<104,0>(float* d, const uint32_t* a, uint64_t db, int sd) {
  asm volatile("{\n.reg .pred p;\nsetp.ne.b32 p, %57, 0;\nwgmma.mma_async.sync.aligned.m64n104k16.f32.bf16.bf16 {%0,%1,%2,%3,%4,%5,%6,%7,%8,%9,%10,%11,%12,%13,%14,%15,%16,%17,%18,%19,%20,%21,%22,%23,%24,%25,%26,%27,%28,%29,%30,%31,%32,%33,%34,%35,%36,%37,%38,%39,%40,%41,%42,%43,%44,%45,%46,%47,%48,%49,%50,%51}, {%52,%53,%54,%55}, %56, p, 1, 1, 0;\n}\n"
   : "+f"(d[0]),"+f"(d[1]),"+f"(d[2]),"+f"(d[3]),"+f"(d[4]),"+f"(d[5]),"+f"(d[6]),"+f"(d[7]),"+f"(d[8]),"+f"(d[9]),"+f"(d[10]),"+f"(d[11]),"+f"(d[12]),"+f"(d[13]),"+f"(d[14]),"+f"(d[15]),"+f"(d[16]),"+f"(d[17]),"+f"(d[18]),"+f"(d[19]),"+f"(d[20]),"+f"(d[21]),"+f"(d[22]),"+f"(d[23]),"+f"(d[24]),"+f"(d[25]),"+f"(d[26]),"+f"(d[27]),"+f"(d[28]),"+f"(d[29]),"+f"(d[30]),"+f"(d[31]),"+f"(d[32]),"+f"(d[33]),"+f"(d[34]),"+f"(d[35]),"+f"(d[36]),"+f"(d[37]),"+f"(d[38]),"+f"(d[39]),"+f"(d[40]),"+f"(d[41]),"+f"(d[42]),"+f"(d[43]),"+f"(d[44]),"+f"(d[45]),"+f"(d[46]),"+f"(d[47]),"+f"(d[48]),"+f"(d[49]),"+f"(d[50]),"+f"(d[51])
   : "r"(a[0]), "r"(a[1]), "r"(a[2]), "r"(a[3]), "l"(db), "r"(sd));
}
template<> __device__ __forceinline__ void wgmma_rs<96,0>(float* d, const uint32_t* a, uint64_t db, int sd) {
  asm volatile("{\n.reg .pred p;\nsetp.ne.b32 p, %53, 0;\nwgmma.mma_async.sync.aligned.m64n96k16.f32.bf16.bf16 {%0,%1,%2,%3,%4,%5,%6,%7,%8,%9,%10,%11,%12,%13,%14,%15,%16,%17,%18,%19,%20,%21,%22,%23,%24,%25,%26,%27,%28,%29,%30,%31,%32,%33,%34,%35,%36,%37,%38,%39,%40,%41,%42,%43,%44,%45,%46,%47}, {%48,%49,%50,%51}, %52, p, 1, 1, 0;\n}\n"
   : "+f"(d[0]),"+f"(d[1]),"+f"(d[2]),"+f"(d[3]),"+f"(d[4]),"+f"(d[5]),"+f"(d[6]),"+f"(d[7]),"+f"(d[8]),"+f"(d[9]),"+f"(d[10]),"+f"(d[11]),"+f"(d[12]),"+f"(d[13]),"+f"(d[14]),"+f"(d[15]),"+f"(d[16]),"+f"(d[17]),"+f"(d[18]),"+f"(d[19]),"+f"(d[20]),"+f"(d[21]),"+f"(d[22]),"+f"(d[23]),"+f"(d[24]),"+f"(d[25]),"+f"(d[26]),"+f"(d[27]),"+f"(d[28]),"+f"(d[29]),"+f"(d[30]),"+f"(d[31]),"+f"(d[32]),"+f"(d[33]),"+f"(d[34]),"+f"(d[35]),"+f"(d[36]),"+f"(d[37]),"+f"(d[38]),"+f"(d[39]),"+f"(d[40]),"+f"(d[41]),"+f"(d[42]),"+f"(d[43]),"+f"(d[44]),"+f"(d[45]),"+f"(d[46]),"+f"(d[47])
   : "r"(a[0]), "r"(a[1]), "r"(a[2]), "r"(a[3]), "l"(db), "r"(sd));
}
template<> __device__ __forceinline__ void wgmma_rs<88,0>(float* d, const uint32_t* a, uint64_t db, int sd) {
  asm volatile("{\n.reg .pred p;\nsetp.ne.b32 p, %49, 0;\nwgmma.mma_async.sync.aligned.m64n88k16.f32.bf16.bf16 {%0,%1,%2,%3,%4,%5,%6,%7,%8,%9,%10,%11,%12,%13,%14,%15,%16,%17,%18,%19,%20,%21,%22,%23,%24,%25,%26,%27,%28,%29,%30,%31,%32,%33,%34,%35,%36,%37,%38,%39,%40,%41,%42,%43}, {%44,%45,%46,%47}, %48, p, 1, 1, 0;\n}\n"
   : "+f"(d[0]),"+f"(d[1]),"+f"(d[2]),"+f"(d[3]),"+f"(d[4]),"+f"(d[5]),"+f"(d[6]),"+f"(d[7]),"+f"(d[8]),"+f"(d[9]),"+f"(d[10]),"+f"(d[11]),"+f"(d[12]),"+f"(d[13]),"+f"(d[14]),"+f"(d[15]),"+f"(d[16]),"+f"(d[17]),"+f"(d[18]),"+f"(d[19]),"+f"(d[20]),"+f"(d[21]),"+f"(d[22]),"+f"(d[23]),"+f"(d[24]),"+f"(d[25]),"+f"(d[26]),"+f"(d[27]),"+f"(d[28]),"+f"(d[29]),"+f"(d[30]),"+f"(d[31]),"+f"(d[32]),"+f"(d[33]),"+f"(d[34]),"+f"(d[35]),"+f"(d[36]),"+f"(d[37]),"+f"(d[38]),"+f"(d[39]),"+f"(d[40]),"+f"(d[41]),"+f"(d[42]),"+f"(d[43])
   : "r"(a[0]), "r"(a[1]), "r"(a[2]), "r"(a[3]), "l"(db), "r"(sd));
}
template<> __device__ __forceinline__ void wgmma_rs<80,0>(float* d, const uint32_t* a, uint64_t db, int sd) {
  asm volatile("{\n.reg .pred p;\nsetp.ne.b32 p, %45, 0;\nwgmma.mma_async.sync.aligned.m64n80k16.f32.bf16.bf16 {%0,%1,%2,%3,%4,%5,%6,%7,%8,%9,%10,%11,%12,%13,%14,%15,%16,%17,%18,%19,%20,%21,%22,%23,%24,%25,%26,%27,%28,%29,%30,%31,%32,%33,%34,%35,%36,%37,%38,%39}, {%40,%41,%42,%43}, %44, p, 1, 1, 0;\n}\n"
   : "+f"(d[0]),"+f"(d[1]),"+f"(d[2]),"+f"(d[3]),"+f"(d[4]),"+f"(d[5]),"+f"(d[6]),"+f"(d[7]),"+f"(d[8]),"+f"(d[9]),"+f"(d[10]),"+f"(d[11]),"+f"(d[12]),"+f"(d[13]),"+f"(d[14]),"+f"(d[15]),"+f"(d[16]),"+f"(d[17]),"+f"(d[18]),"+f"(d[19]),"+f"(d[20]),"+f"(d[21]),"+f"(d[22]),"+f"(d[23]),"+f"(d[24]),"+f"(d[25]),"+f"(d[26]),"+f"(d[27]),"+f"(d[28]),"+f"(d[29]),"+f"(d[30]),"+f"(d[31]),"+f"(d[32]),"+f"(d[33]),"+f"(d[34]),"+f"(d[35]),"+f"(d[36]),"+f"(d[37]),"+f"(d[38]),"+f"(d[39])
   : "r"(a[0]), "r"(a[1]), "r"(a[2]), "r"(a[3]), "l"(db), "r"(sd));
}
template<> __device__ __forceinline__ void wgmma_rs<72,0>(float* d, const uint32_t* a, uint64_t db, int sd) {
  asm volatile("{\n.reg .pred p;\nsetp.ne.b32 p, %41, 0;\nwgmma.mma_async.sync.aligned.m64n72k16.f32.bf16.bf16 {%0,%1,%2,%3,%4,%5,%6,%7,%8,%9,%10,%11,%12,%13,%14,%15,%16,%17,%18,%19,%20,%21,%22,%23,%24,%25,%26,%27,%28,%29,%30,%31,%32,%33,%34,%35}, {%36,%37,%38,%39}, %40, p, 1, 1, 0;\n}\n"
   : "+f"(d[0]),"+f"(d[1]),"+f"(d[2]),"+f"(d[3]),"+f"(d[4]),"+f"(d[5]),"+f"(d[6]),"+f"(d[7]),"+f"(d[8]),"+f"(d[9]),"+f"(d[10]),"+f"(d[11]),"+f"(d[12]),"+f"(d[13]),"+f"(d[14]),"+f"(d[15]),"+f"(d[16]),"+f"(d[17]),"+f"(d[18]),"+f"(d[19]),"+f"(d[20]),"+f"(d[21]),"+f"(d[22]),"+f"(d[23]),"+f"(d[24]),"+f"(d[25]),"+f"(d[26]),"+f"(d[27]),"+f"(d[28]),"+f"(d[29]),"+f"(d[30]),"+f"(d[31]),"+f"(d[32]),"+f"(d[33]),"+f"(d[34]),"+f"(d[35])
   : "r"(a[0]), "r"(a[1]), "r"(a[2]), "r"(a[3]), "l"(db), "r"(sd));
}
template<> __device__ __forceinline__ void wgmma_rs<64,0>(float* d, const uint32_t* a, uint64_t db, int sd) {
  asm volatile("{\n.reg .pred p;\nsetp.ne.b32 p, %37, 0;\nwgmma.mma_async.sync.aligned.m64n64k16.f32.bf16.bf16 {%0,%1,%2,%3,%4,%5,%6,%7,%8,%9,%10,%11,%12,%13,%14,%15,%16,%17,%18,%19,%20,%21,%22,%23,%24,%25,%26,%27,%28,%29,%30,%31}, {%32,%33,%34,%35}, %36, p, 1, 1, 0;\n}\n"
   : "+f"(d[0]),"+f"(d[1]),"+f"(d[2]),"+f"(d[3]),"+f"(d[4]),"+f"(d[5]),"+f"(d[6]),"+f"(d[7]),"+f"(d[8]),"+f"(d[9]),"+f"(d[10]),"+f"(d[11]),"+f"(d[12]),"+f"(d[13]),"+f"(d[14]),"+f"(d[15]),"+f"(d[16]),"+f"(d[17]),"+f"(d[18]),"+f"(d[19]),"+f"(d[20]),"+f"(d[21]),"+f"(d[22]),"+f"(d[23]),"+f"(d[24]),"+f"(d[25]),"+f"(d[26]),"+f"(d[27]),"+f"(d[28]),"+f"(d[29]),"+f"(d[30]),"+f"(d[31])
   : "r"(a[0]), "r"(a[1]), "r"(a[2]), "r"(a[3]), "l"(db), "r"(sd));
}
template<> __device__ __forceinline__ void wgmma_ss<64,0,1>(float* d, uint64_t da, uint64_t db, int sd) {
  asm volatile("{\n.reg .pred p;\nsetp.ne.b32 p, %34, 0;\nwgmma.mma_async.sync.aligned.m64n64k16.f32.bf16.bf16 {%0,%1,%2,%3,%4,%5,%6,%7,%8,%9,%10,%11,%12,%13,%14,%15,%16,%17,%18,%19,%20,%21,%22,%23,%24,%25,%26,%27,%28,%29,%30,%31}, %32, %33, p, 1, 1, 0, 1;\n}\n"
   : "+f"(d[0]),"+f"(d[1]),"+f"(d[2]),"+f"(d[3]),"+f"(d[4]),"+f"(d[5]),"+f"(d[6]),"+f"(d[7]),"+f"(d[8]),"+f"(d[9]),"+f"(d[10]),"+f"(d[11]),"+f"(d[12]),"+f"(d[13]),"+f"(d[14]),"+f"(d[15]),"+f"(d[16]),"+f"(d[17]),"+f"(d[18]),"+f"(d[19]),"+f"(d[20]),"+f"(d[21]),"+f"(d[22]),"+f"(d[23]),"+f"(d[24]),"+f"(d[25]),"+f"(d[26]),"+f"(d[27]),"+f"(d[28]),"+f"(d[29]),"+f"(d[30]),"+f"(d[31])
   : "l"(da), "l"(db), "r"(sd));
}
template<> __device__ __forceinline__ void wgmma_ss<64,1,1>(float* d, uint64_t da, uint64_t db, int sd) {
  asm volatile("{\n.reg .pred p;\nsetp.ne.b32 p, %34, 0;\nwgmma.mma_async.sync.aligned.m64n64k16.f32.bf16.bf16 {%0,%1,%2,%3,%4,%5,%6,%7,%8,%9,%10,%11,%12,%13,%14,%15,%16,%17,%18,%19,%20,%21,%22,%23,%24,%25,%26,%27,%28,%29,%30,%31}, %32, %33, p, 1, 1, 1, 1;\n}\n"
   : "+f"(d[0]),"+f"(d[1]),"+f"(d[2]),"+f"(d[3]),"+f"(d[4]),"+f"(d[5]),"+f"(d[6]),"+f"(d[7]),"+f"(d[8]),"+f"(d[9]),"+f"(d[10]),"+f"(d[11]),"+f"(d[12]),"+f"(d[13]),"+f"(d[14]),"+f"(d[15]),"+f"(d[16]),"+f"(d[17]),"+f"(d[18]),"+f"(d[19]),"+f"(d[20]),"+f"(d[21]),"+f"(d[22]),"+f"(d[23]),"+f"(d[24]),"+f"(d[25]),"+f"(d[26]),"+f"(d[27]),"+f"(d[28]),"+f"(d[29]),"+f"(d[30]),"+f"(d[31])
   : "l"(da), "l"(db), "r"(sd));
}
template<> __device__ __forceinline__ void wgmma_ss<192,0,1>(float* d, uint64_t da, uint64_t db, int sd) {
  asm volatile("{\n.reg .pred p;\nsetp.ne.b32 p, %98, 0;\nwgmma.mma_async.sync.aligned.m64n192k16.f32.bf16.bf16 {%0,%1,%2,%3,%4,%5,%6,%7,%8,%9,%10,%11,%12,%13,%14,%15,%16,%17,%18,%19,%20,%21,%22,%23,%24,%25,%26,%27,%28,%29,%30,%31,%32,%33,%34,%35,%36,%37,%38,%39,%40,%41,%42,%43,%44,%45,%46,%47,%48,%49,%50,%51,%52,%53,%54,%55,%56,%57,%58,%59,%60,%61,%62,%63,%64,%65,%66,%67,%68,%69,%70,%71,%72,%73,%74,%75,%76,%77,%78,%79,%80,%81,%82,%83,%84,%85,%86,%87,%88,%89,%90,%91,%92,%93,%94,%95}, %96, %97, p, 1, 1, 0, 1;\n}\n"
   : "+f"(d[0]),"+f"(d[1]),"+f"(d[2]),"+f"(d[3]),"+f"(d[4]),"+f"(d[5]),"+f"(d[6]),"+f"(d[7]),"+f"(d[8]),"+f"(d[9]),"+f"(d[10]),"+f"(d[11]),"+f"(d[12]),"+f"(d[13]),"+f"(d[14]),"+f"(d[15]),"+f"(d[16]),"+f"(d[17]),"+f"(d[18]),"+f"(d[19]),"+f"(d[20]),"+f"(d[21]),"+f"(d[22]),"+f"(d[23]),"+f"(d[24]),"+f"(d[25]),"+f"(d[26]),"+f"(d[27]),"+f"(d[28]),"+f"(d[29]),"+f"(d[30]),"+f"(d[31]),"+f"(d[32]),"+f"(d[33]),"+f"(d[34]),"+f"(d[35]),"+f"(d[36]),"+f"(d[37]),"+f"(d[38]),"+f"(d[39]),"+f"(d[40]),"+f"(d[41]),"+f"(d[42]),"+f"(d[43]),"+f"(d[44]),"+f"(d[45]),"+f"(d[46]),"+f"(d[47]),"+f"(d[48]),"+f"(d[49]),"+f"(d[50]),"+f"(d[51]),"+f"(d[52]),"+f"(d[53]),"+f"(d[54]),"+f"(d[55]),"+f"(d[56]),"+f"(d[57]),"+f"(d[58]),"+f"(d[59]),"+f"(d[60]),"+f"(d[61]),"+f"(d[62]),"+f"(d[63]),"+f"(d[64]),"+f"(d[65]),"+f"(d[66]),"+f"(d[67]),"+f"(d[68]),"+f"(d[69]),"+f"(d[70]),"+f"(d[71]),"+f"(d[72]),"+f"(d[73]),"+f"(d[74]),"+f"(d[75]),"+f"(d[76]),"+f"(d[77]),"+f"(d[78]),"+f"(d[79]),"+f"(d[80]),"+f"(d[81]),"+f"(d[82]),"+f"(d[83]),"+f"(d[84]),"+f"(d[85]),"+f"(d[86]),"+f"(d[87]),"+f"(d[88]),"+f"(d[89]),"+f"(d[90]),"+f"(d[91]),"+f"(d[92]),"+f"(d[93]),"+f"(d[94]),"+f"(d[95])
   : "l"(da), "l"(db), "r"(sd));
}
template<> __device__ __forceinline__ void wgmma_ss<192,1,1>(float* d, uint64_t da, uint64_t db, int sd) {
  asm volatile("{\n.reg .pred p;\nsetp.ne.b32 p, %98, 0;\nwgmma.mma_async.sync.aligned.m64n192k16.f32.bf16.bf16 {%0,%1,%2,%3,%4,%5,%6,%7,%8,%9,%10,%11,%12,%13,%14,%15,%16,%17,%18,%19,%20,%21,%22,%23,%24,%25,%26,%27,%28,%29,%30,%31,%32,%33,%34,%35,%36,%37,%38,%39,%40,%41,%42,%43,%44,%45,%46,%47,%48,%49,%50,%51,%52,%53,%54,%55,%56,%57,%58,%59,%60,%61,%62,%63,%64,%65,%66,%67,%68,%69,%70,%71,%72,%73,%74,%75,%76,%77,%78,%79,%80,%81,%82,%83,%84,%85,%86,%87,%88,%89,%90,%91,%92,%93,%94,%95}, %96, %97, p, 1, 1, 1, 1;\n}\n"
   : "+f"(d[0]),"+f"(d[1]),"+f"(d[2]),"+f"(d[3]),"+f"(d[4]),"+f"(d[5]),"+f"(d[6]),"+f"(d[7]),"+f"(d[8]),"+f"(d[9]),"+f"(d[10]),"+f"(d[11]),"+f"(d[12]),"+f"(d[13]),"+f"(d[14]),"+f"(d[15]),"+f"(d[16]),"+f"(d[17]),"+f"(d[18]),"+f"(d[19]),"+f"(d[20]),"+f"(d[21]),"+f"(d[22]),"+f"(d[23]),"+f"(d[24]),"+f"(d[25]),"+f"(d[26]),"+f"(d[27]),"+f"(d[28]),"+f"(d[29]),"+f"(d[30]),"+f"(d[31]),"+f"(d[32]),"+f"(d[33]),"+f"(d[34]),"+f"(d[35]),"+f"(d[36]),"+f"(d[37]),"+f"(d[38]),"+f"(d[39]),"+f"(d[40]),"+f"(d[41]),"+f"(d[42]),"+f"(d[43]),"+f"(d[44]),"+f"(d[45]),"+f"(d[46]),"+f"(d[47]),"+f"(d[48]),"+f"(d[49]),"+f"(d[50]),"+f"(d[51]),"+f"(d[52]),"+f"(d[53]),"+f"(d[54]),"+f"(d[55]),"+f"(d[56]),"+f"(d[57]),"+f"(d[58]),"+f"(d[59]),"+f"(d[60]),"+f"(d[61]),"+f"(d[62]),"+f"(d[63]),"+f"(d[64]),"+f"(d[65]),"+f"(d[66]),"+f"(d[67]),"+f"(d[68]),"+f"(d[69]),"+f"(d[70]),"+f"(d[71]),"+f"(d[72]),"+f"(d[73]),"+f"(d[74]),"+f"(d[75]),"+f"(d[76]),"+f"(d[77]),"+f"(d[78]),"+f"(d[79]),"+f"(d[80]),"+f"(d[81]),"+f"(d[82]),"+f"(d[83]),"+f"(d[84]),"+f"(d[85]),"+f"(d[86]),"+f"(d[87]),"+f"(d[88]),"+f"(d[89]),"+f"(d[90]),"+f"(d[91]),"+f"(d[92]),"+f"(d[93]),"+f"(d[94]),"+f"(d[95])
   : "l"(da), "l"(db), "r"(sd));
}

__device__ __forceinline__ void stats_publish(uint32_t sb, int layer, int rb, int hg, int ht, uint32_t tag) {
  const int lane = ht & 31, w = ht >> 5, g = lane >> 2, t = lane & 3, ks = hg & 3;
  uint32_t xa;
  if (layer == 0) {
    const int row = 16 * w + (lane & 15), kc = 2 * ks + (lane >> 4);
    xa = row * 128 + ((kc ^ (row & 7)) << 4);
  } else {
    const int k = 16 * ks + (lane & 7) + 8 * (lane >> 4), pc = 2 * w + ((lane >> 3) & 1);
    xa = k * 128 + ((pc ^ (k & 7)) << 4);
  }
  float s[4] = {0.f, 0.f, 0.f, 0.f}, q[4] = {0.f, 0.f, 0.f, 0.f};
#pragma unroll 1
  for (int c = hg >> 2; c < 8; c += 2) {
    mbar_wait(sb + SM_BAR + 8 * (B_XF + c), layer);
    if (c >= 6) ATS(48, 256);
    if (c < 2) ATS(51, 256);
    uint32_t A[2][4];
#pragma unroll
    for (int h = 0; h < 2; h++) {
      if (layer == 0) ldsm4(A[h], sb + SM_X + c * 16384 + h * 8192 + xa);
      else ldsm4t(A[h], sb + SM_X + c * 16384 + h * 8192 + xa);
    }
#pragma unroll
    for (int r = 0; r < 4; r++)
#pragma unroll
      for (int i = 0; i < 2; i++) {
        const uint32_t v = A[r >> 1][2 * i + (r & 1)];
        const float a = bf_lo(v), b = bf_hi(v);
        s[r] += a + b; q[r] = fmaf(a, a, q[r]); q[r] = fmaf(b, b, q[r]);
      }
  }
#pragma unroll
  for (int r = 0; r < 2; r++) {
    s[r] = ((t & 2) ? s[r + 2] : s[r]) + __shfl_xor_sync(~0u, (t & 2) ? s[r] : s[r + 2], 2);
    q[r] = ((t & 2) ? q[r + 2] : q[r]) + __shfl_xor_sync(~0u, (t & 2) ? q[r] : q[r + 2], 2);
  }
  s[0] = ((t & 1) ? s[1] : s[0]) + __shfl_xor_sync(~0u, (t & 1) ? s[0] : s[1], 1);
  q[0] = ((t & 1) ? q[1] : q[0]) + __shfl_xor_sync(~0u, (t & 1) ? q[0] : q[1], 1);
  st_part(&g_part[(rb * 8 + hg) * 128 + 64 * (t >> 1) + 16 * w + 8 * (t & 1) + g], s[0], q[0], tag);
  ATS(49, 256);
}
__device__ __forceinline__ void stats_gather(uint32_t sb, int rb, int ht, uint32_t tag) {
  const uint2* src = &g_part[rb * 8 * 128 + ht];
  uint2 v[8];
  bool ok;
  int it = 0;
  do {
    ok = true;
#pragma unroll
    for (int i = 0; i < 8; i++) v[i] = ld_part(src + i * 128);
#pragma unroll
    for (int i = 0; i < 8; i++) ok = ok && (v[i].y & 7u) == tag;
    if (++it > (1 << 22)) __trap();
  } while (!__all_sync(~0u, ok));
  float s = 0.f, q = 0.f;
#pragma unroll
  for (int i = 0; i < 8; i++) { s += __uint_as_float(v[i].x); q += __uint_as_float(v[i].y); }
  const float mean = s * (1.f / DM);
  const float rstd = rsqrt_approx(fmaxf(q * (1.f / DM) - mean * mean, 0.f) + 1e-5f);
  asm volatile("st.shared.v2.f32 [%0], {%1,%2};" ::"r"(sb + SM_ST + ht * 8), "f"(mean), "f"(rstd) : "memory");
  __syncwarp();
  if (elect_one()) mbar_arrive(sb + SM_BAR + 8 * B_STF);
}
__device__ __forceinline__ void halo_receive(uint32_t sb, int layer, int rb, int hg, int ht) {
  const int lane = ht & 31, h = ht >> 5;
  uint4 kv = make_uint4(0, 0, 0, 0);
  mbar_wait(sb + SM_BAR + 8 * B_SD, layer);
  if (rb & 7) {
    const uint32_t tag = 2 * lds32(sb + SM_EP) + layer + 1;
    const uint4* src = &g_halo[((rb - 1) * 8 + hg) * 192 + h * 48];
    if (layer == 0) delay<D_HALO>(); else delay<D_HALO1>();
    uint4 a;
    uint2 b;
    int it = 0;
    do {
      a = ld_tagged(src + lane); b = ld_part((const uint2*)(src + 32) + lane);
      if (++it > (1 << 22)) __trap();
    } while (!__all_sync(~0u, a.w == tag && b.y == tag));
    kv = make_uint4(a.x, a.y, movm_t(a.z), movm_t(b.x));
  }
  sts128(sb + SM_KVX + h * 512 + lane * 16, kv);
  ATS(61, 256);
  bar_arrive(7, 160);
  if (elect_one()) mbar_arrive(sb + SM_BAR + 8 * B_HF);
}

template <bool TR>
__device__ __forceinline__ void gemm_section(float* acc, float2* cs, uint32_t sb, int layer, int wg, int w, int lane) {
  const uint32_t bar = sb + SM_BAR;
  const bool leader = (w == 0) && (lane == 0);
  auto issue = [&](int c, int slot) {
    mbar_wait(bar + 8 * (B_XF + c), layer);
    mbar_wait(bar + 8 * (B_KVF + c), layer);
    const uint64_t da = mkdesc(sb + SM_X + c * 16384 + wg * 8192, TR ? 8192 : 16, 1024, 1);
    const uint64_t db = mkdesc(sb + SM_W + slot * 24576, 8192, 1024, 1);
    wg_fence();
#pragma unroll
    for (int ks = 0; ks < 4; ks++) wgmma_ss<192, TR ? 1 : 0, 1>(acc, da + (TR ? ks * 128 : ks * 2), db + ks * 128, (c | ks) != 0);
    wg_commit();
  };
  auto step = [&](int c, int slot) {
    issue(c, slot);
    wg_wait<1>();
    if (leader) mbar_arrive(bar + 8 * (B_KVE + c - 1));
  };
  if (!TR) bar_sync(0, NTHREADS);
  issue(0, 0);
  if (threadIdx.x == 0) TS(2 + layer * 20 + 0);
  if (threadIdx.x == 128 && layer == 1) TS(60);
  step(1, 1); step(2, 2); step(3, 0); step(4, 1);
  auto ld_cs = [&](int j0) {
#pragma unroll
    for (int j = j0; j < j0 + 8; j++) cs[j] = lds64f(sb + SM_CS + 4 * (8 * j + 2 * (lane & 3)));
  };
  if (TR) ld_cs(8);
  step(5, 2);
  if (!TR && !CS_LATE0) { mbar_wait(bar + 8 * B_CSF, 0); ld_cs(8); }
  if (TR || !CS_LATE0) ld_cs(16);
  if (wg == 0) bar_sync(5, 256);
  issue(6, 0);
  issue(7, 1);
  if (wg == 1) bar_arrive(5, 256);
  if (!TR && CS_LATE0) { mbar_wait(bar + 8 * B_CSF, 0); ld_cs(8); ld_cs(16); }
}

__device__ __forceinline__ void attn_phase(const Params& p, uint32_t sb, int layer, int rb, int hg, int wg, int w) {
  const int lane = opaque_tid() & 31;
  const int g = lane >> 2, t = lane & 3;
  const uint32_t bar = sb + SM_BAR;
  const int row0 = 64 * wg + 16 * w;
  const bool leader = (w == 0) && (lane == 0);
  float acc[96];
  float2 cs[24];
  if (layer) gemm_section<true>(acc, cs, sb, layer, wg, w, lane);
  else gemm_section<false>(acc, cs, sb, layer, wg, w, lane);
  ATS(41, 224);
  mbar_wait(bar + 8 * B_STF, layer);
  const uint32_t tag = 2 * lds32(sb + SM_EP) + layer + 1;
  const float2 st0 = lds64f(sb + SM_ST + (row0 + g) * 8), st1 = lds64f(sb + SM_ST + (row0 + g + 8) * 8);
  const float mean0 = st0.x, rstd0 = st0.y, mean1 = st1.x, rstd1 = st1.y;
  wg_wait<0>();
  if (threadIdx.x == 0) TS(2 + layer * 20 + 1);
  ATS(39, 224);
  if (leader) mbar_arrive(bar + 8 * B_QDONE);

  uint32_t fp[4][4], fl[4][4], fh[4][4], qa[4][4];
  const int cw = 4 * wg + w;
  {
    const float nm0 = -mean0 * rstd0, nm1 = -mean1 * rstd1;
    const uint32_t kvx = sb + SM_KVX + cw * 2048 + lane * 16;
#pragma unroll
    for (int h = 0; h < 4; h++)
#pragma unroll
      for (int k = 0; k < 4; k++) {
        const int j = 8 + (k >> 1) * 8 + 2 * h + (k & 1);
        fh[h][k] = packbf(fmaf(acc[4 * j + 2], rstd1, nm1 * cs[j].x), fmaf(acc[4 * j + 3], rstd1, nm1 * cs[j].y));
      }
    if (cw == 7) {
      uint4* halo = &g_halo[(rb * 8 + hg) * 192];
#pragma unroll
      for (int h = 0; h < 4; h++) {
        st_tagged3(halo + h * 48 + lane, fh[h][0], fh[h][1], fh[h][2], tag);
        asm volatile("st.relaxed.gpu.global.v2.u32 [%0], {%1,%2};" ::"l"((uint2*)(halo + h * 48 + 32) + lane), "r"(fh[h][3]), "r"(tag) : "memory");
      }
      if (elect_one()) mbar_arrive(bar + 8 * B_SD);
      if (layer == TLAYER && threadIdx.x == 224) TS(47);
    }
#pragma unroll
    for (int h = 0; h < 4; h++) { fh[h][2] = movm_t(fh[h][2]); fh[h][3] = movm_t(fh[h][3]); }
    if (cw != 7) {
#pragma unroll
      for (int h = 0; h < 4; h++) sts128(kvx + 2048 + h * 512, make_uint4(fh[h][0], fh[h][1], fh[h][2], fh[h][3]));
      bar_arrive(8 + cw, 64);
    }
    if (layer == TLAYER && threadIdx.x == 0) TS(45);
#pragma unroll
    for (int j = 0; j < 8; j++) cs[j] = lds64f(sb + SM_CS + 4 * (8 * j + 2 * t));
#pragma unroll
    for (int h = 0; h < 4; h++)
#pragma unroll
      for (int k = 0; k < 4; k++) {
        const int j = 8 + (k >> 1) * 8 + 2 * h + (k & 1);
        fl[h][k] = packbf(fmaf(acc[4 * j], rstd0, nm0 * cs[j].x), fmaf(acc[4 * j + 1], rstd0, nm0 * cs[j].y));
        if (k >= 2) fl[h][k] = movm_t(fl[h][k]);
      }
#pragma unroll
    for (int h = 0; h < 4; h++) {
#pragma unroll
      for (int dh = 0; dh < 2; dh++) {
        const int j = 2 * h + dh;
        const float2 c2 = cs[j];
        qa[h][2 * dh] = packbf(fmaf(-mean0, c2.x, acc[4 * j + 0]), fmaf(-mean0, c2.y, acc[4 * j + 1]));
        qa[h][2 * dh + 1] = packbf(fmaf(-mean1, c2.x, acc[4 * j + 2]), fmaf(-mean1, c2.y, acc[4 * j + 3]));
      }
    }
    if (threadIdx.x == 0) TS(2 + layer * 20 + 2);
    bar_sync(7 + cw, cw == 0 ? 160 : 64);
#pragma unroll
    for (int h = 0; h < 4; h++) {
      const uint4 v = lds128(kvx + h * 512);
      fp[h][0] = v.x; fp[h][1] = v.y; fp[h][2] = v.z; fp[h][3] = v.w;
    }
    if (threadIdx.x == 0) TS(2 + layer * 20 + 4);
  }

  const bool u0 = 2 * t > g, u1 = 2 * t + 1 > g;
  const uint32_t mU = (u0 ? 0x0000ffffu : 0u) | (u1 ? 0xffff0000u : 0u);
  const float cl2 = 0.25f * 1.4426950408889634f;
  const float sc0 = rstd0 * cl2, sc1 = rstd1 * cl2;
  const float cneg = ((rb & 7) == 0 && cw == 0) ? -INFINITY : 0.f;
  float v[4][4];
#pragma unroll
  for (int h = 0; h < 4; h++) {
    float T0[4] = {cneg, cneg, cneg, cneg}, T1[4] = {0.f, 0.f, 0.f, 0.f}, T2[4] = {0.f, 0.f, 0.f, 0.f};
    mma_bf16(T1, qa[h], fl[h][0], fl[h][1]);
    mma_bf16(T2, qa[h], fh[h][0], fh[h][1]);
    mma_bf16(T0, qa[h], fp[h][0], fp[h][1]);
    v[h][0] = u0 ? T0[0] : T1[0]; v[h][1] = u1 ? T0[1] : T1[1];
    v[h][2] = u0 ? T1[2] : T2[2]; v[h][3] = u1 ? T1[3] : T2[3];
  }
  float m0[4], m1[4];
#pragma unroll
  for (int h = 0; h < 4; h++) { m0[h] = fmaxf(v[h][0], v[h][1]); m1[h] = fmaxf(v[h][2], v[h][3]); }
#pragma unroll
  for (int o = 1; o <= 2; o <<= 1) {
#pragma unroll
    for (int h = 0; h < 4; h++) {
      m0[h] = fmaxf(m0[h], __shfl_xor_sync(~0u, m0[h], o));
      m1[h] = fmaxf(m1[h], __shfl_xor_sync(~0u, m1[h], o));
    }
  }
  float O0[4][4], O1[4][4], Z[4][4];
#pragma unroll
  for (int h = 0; h < 4; h++) {
    const float mm0 = -m0[h] * sc0, mm1 = -m1[h] * sc1;
    const uint32_t P0 = packbf(ex2(fmaf(v[h][0], sc0, mm0)), ex2(fmaf(v[h][1], sc0, mm0)));
    const uint32_t P1 = packbf(ex2(fmaf(v[h][2], sc1, mm1)), ex2(fmaf(v[h][3], sc1, mm1)));
#pragma unroll
    for (int k = 0; k < 4; k++) O0[h][k] = O1[h][k] = Z[h][k] = 0.f;
    mma_bf16_k8(Z[h], P0, P1, 0x3f803f80u);
    mma_bf16_k8(O0[h], P0 & ~mU, P1 & mU, fl[h][2]); mma_bf16_k8(O1[h], P0 & ~mU, P1 & mU, fl[h][3]);
    mma_bf16_k8(O0[h], P0 & mU, 0u, fp[h][2]); mma_bf16_k8(O1[h], P0 & mU, 0u, fp[h][3]);
    mma_bf16_k8(O0[h], 0u, P1 & ~mU, fh[h][2]); mma_bf16_k8(O1[h], 0u, P1 & ~mU, fh[h][3]);
  }
  const uint32_t ob = sb + SM_OST + wg * 8192;
  const int o_row = 16 * w + (lane & 7) + 8 * ((lane >> 3) & 1);
#pragma unroll
  for (int h = 0; h < 4; h++) {
    const float i0 = rcp_approx(Z[h][0]), i1 = rcp_approx(Z[h][2]);
    const int ch = 2 * h + (lane >> 4);
    stsm4(ob + o_row * 128 + ((ch ^ (o_row & 7)) << 4), packbf(O0[h][0] * i0, O0[h][1] * i0), packbf(O0[h][2] * i1, O0[h][3] * i1),
          packbf(O1[h][0] * i0, O1[h][1] * i0), packbf(O1[h][2] * i1, O1[h][3] * i1));
  }
  if (threadIdx.x == 0) TS(2 + layer * 20 + 5);
  ATS(57, 128); ATS(20, 96);
  bar_sync(2 + wg, 128);
  if (w == 0 && elect_one()) {
    fence_async_smem();
    tma_st(&p.mapO, hg * 64, rb * 128 + wg * 64, ob);
    bulk_commit();
    mbar_arrive(bar + 8 * B_AD);
    bulk_wait_all();
    red_relaxed(&g_cnt[(C_O + rb) * 32]);
    mbar_arrive(bar + 8 * B_OST);
    if (threadIdx.x == 0) TS(2 + layer * 20 + 6);
  }
}

__device__ __forceinline__ void proj_phase(const Params& p, uint32_t sb, int layer, int rb, int q, int wg, int w) {
  const int lane = opaque_tid() & 31;
  const bool TR = layer != 0;
  const int t = lane & 3;
  const uint32_t bar = sb + SM_BAR;
  const uint32_t rbx = sb + SM_R + wg * 8192;
  uint32_t res[16];
  mbar_wait(bar + 8 * B_RF, layer);
  if (threadIdx.x == 0) TS(2 + layer * 20 + 7);
  if (!TR) {
#pragma unroll
    for (int j = 0; j < 8; j += 2) {
      const int mi = lane >> 3;
      const int row = 16 * w + (lane & 7) + 8 * (mi & 1), ch = j + (mi >> 1);
      ldsm4(&res[2 * j], rbx + row * 128 + ((ch ^ (row & 7)) << 4));
    }
  } else {
#pragma unroll
    for (int j = 0; j < 8; j += 2) {
      const int mi = lane >> 3;
      const int line = 8 * (j + (mi >> 1)) + (lane & 7), pc = 2 * w + (mi & 1);
      ldsm4t(&res[2 * j], rbx + line * 128 + ((pc ^ (line & 7)) << 4));
    }
  }
  bar_sync(2 + wg, 128);
  float acc[32];
#pragma unroll
  for (int i = 0; i < 16; i++) {
    asm volatile("shl.b32 %0, %1, 16;" : "=f"(acc[2 * i]) : "r"(res[i]));
    asm volatile("and.b32 %0, %1, 0xffff0000;" : "=f"(acc[2 * i + 1]) : "r"(res[i]));
  }
  const uint32_t tag = part_tag(lds32(sb + SM_EP), 2 * layer + 1);
#pragma unroll 1
  for (int c = 0; c < 8; c++) {
    if ((c & 1) == 0) mbar_wait(bar + 8 * (B_WOF + (c >> 1)), layer);
    mbar_wait(bar + 8 * (B_OF + c), layer);
    if (c == 0 && threadIdx.x == 0) TS(2 + layer * 20 + 8);
    const uint64_t da = mkdesc(sb + sm_o(c) + wg * 8192, 16, 1024, 1);
    const uint64_t db = mkdesc(sb + SM_WO + c * 8192, 8192, 1024, 1);
    wg_fence();
#pragma unroll
    for (int ks = 0; ks < 4; ks++) wgmma_ss<64, 0, 1>(acc, da + ks * 2, db + ks * 128, 1);
    wg_commit();
  }
  wg_wait<0>();
#pragma unroll
  for (int i = 0; i < 32; i++) asm volatile("" : "+f"(acc[i]) :: "memory");
  if (threadIdx.x == 0) TS(2 + layer * 20 + 9);
  if (lane == 0 && w == 0) mbar_arrive(bar + 8 * B_PDONE);
  {
    float s[4], qq[4];
#pragma unroll
    for (int k = 0; k < 4; k++) { s[k] = acc[k]; qq[k] = acc[k] * acc[k]; }
#pragma unroll
    for (int j = 1; j < 8; j++)
#pragma unroll
      for (int k = 0; k < 4; k++) { s[k] += acc[4 * j + k]; qq[k] = fmaf(acc[4 * j + k], acc[4 * j + k], qq[k]); }
    const float s0 = s[0] + s[1], s1 = s[2] + s[3], q0 = qq[0] + qq[1], q1 = qq[2] + qq[3];
    float sr = ((t & 1) ? s1 : s0) + __shfl_xor_sync(~0u, (t & 1) ? s0 : s1, 1);
    float qr = ((t & 1) ? q1 : q0) + __shfl_xor_sync(~0u, (t & 1) ? q0 : q1, 1);
    sr += __shfl_xor_sync(~0u, sr, 2);
    qr += __shfl_xor_sync(~0u, qr, 2);
    if (t < 2) st_part(&g_part[(rb * 8 + q) * 128 + 64 * wg + 16 * w + (lane >> 2) + 8 * t], sr, qr, tag);
    __syncwarp();
    if (elect_one()) mbar_arrive(bar + 8 * B_PS);
  }
#pragma unroll
  for (int j = 0; j < 8; j += 2) {
    const int mi = lane >> 3;
    const int line = 8 * (j + (mi >> 1)) + (lane & 7), pc = 2 * w + (mi & 1);
    stsm4t(rbx + line * 128 + ((pc ^ (line & 7)) << 4), packbf(acc[4 * j], acc[4 * j + 1]), packbf(acc[4 * j + 2], acc[4 * j + 3]),
           packbf(acc[4 * j + 4], acc[4 * j + 5]), packbf(acc[4 * j + 6], acc[4 * j + 7]));
  }
  fence_writer();
  bar_sync(2 + wg, 128);
  if (w == 0 && elect_one()) {
    fence_reader();
    mbar_wait(bar + 8 * B_ZF, layer);
    fence_async_global();
    tma_st(&p.mapXT, rb * 128 + wg * 64, (2 * layer) * DM + q * 64, rbx);
    bulk_commit();
    if (threadIdx.x == 0) TS(2 + layer * 20 + 10);
    asm volatile("cp.async.bulk.wait_group.read 0;" ::: "memory");
    if (wg == 0) mbar_arrive(bar + 8 * B_RE);
  }
}
__device__ __forceinline__ void proj_stats(int layer, int rb, int q, int lane, uint32_t tag) {
  const int r = 16 * q + (lane & 15);
  const uint2* src = &g_part[(rb * 8 + (lane >> 4) * 4) * 128 + r];
  uint2 v[4];
  bool ok;
  int it = 0;
  do {
    ok = true;
#pragma unroll
    for (int i = 0; i < 4; i++) v[i] = ld_part(src + i * 128);
#pragma unroll
    for (int i = 0; i < 4; i++) ok = ok && (v[i].y & 7u) == tag;
    if (++it > (1 << 22)) __trap();
  } while (!__all_sync(~0u, ok));
  float s = (__uint_as_float(v[0].x) + __uint_as_float(v[1].x)) + (__uint_as_float(v[2].x) + __uint_as_float(v[3].x));
  float qq = (__uint_as_float(v[0].y) + __uint_as_float(v[1].y)) + (__uint_as_float(v[2].y) + __uint_as_float(v[3].y));
  s += __shfl_xor_sync(~0u, s, 16);
  qq += __shfl_xor_sync(~0u, qq, 16);
  const float mean = s * (1.f / DM);
  const float rstd = rsqrt_approx(fmaxf(fmaf(qq, 1.f / DM, -mean * mean), 0.f) + 1e-5f), nm = -mean * rstd;
  const float nm1 = __shfl_xor_sync(~0u, nm, 1), rstd1 = __shfl_xor_sync(~0u, rstd, 1);
  if ((lane & 17) == 0)
    st_tagged3((uint4*)g_stats + (layer * 32 + rb * 2 + (r >> 6)) * 32 + ((r & 7) >> 1) * 8 + ((r >> 3) & 7),
               __float_as_uint(nm), __float_as_uint(rstd) | 1u, __float_as_uint(nm1), __float_as_uint(rstd1));
}

#define NA 8
template <bool GB> __host__ __device__ constexpr int grp_n() { return GB ? 17 - NA : NA; }
template <bool GB> __host__ __device__ constexpr int grp_m(int i) { return i == 0 ? (GB ? 1 : 0) : (GB ? NA + i : 1 + i); }
template <bool GB> __device__ __forceinline__ void conv_load(uint32_t* A, uint32_t pe) {
#pragma unroll
  for (int i = 0; i < grp_n<GB>(); i++) {
    asm volatile("ld.shared.v2.b32 {%0,%1}, [%2];" : "=r"(A[4 * i]), "=r"(A[4 * i + 1]) : "r"(pe + 4 * (64 * grp_m<GB>(i))) : "memory");
    A[4 * i + 2] = lds32(pe + 4 * (64 * grp_m<GB>(i) - 1));
  }
}
template <bool GB> __device__ __forceinline__ void conv_dup_early(uint32_t* A, uint32_t zero) {
#pragma unroll
  for (int i = 0; i < grp_n<GB>(); i++) asm volatile("or.b32 %0, %1, %2;" : "=r"(A[4 * i + 3]) : "r"(A[4 * i + 0]), "r"(zero));
}
template <bool GB> __device__ __forceinline__ void conv_dup(uint32_t* A) {
#pragma unroll
  for (int i = 0; i < grp_n<GB>(); i++) asm volatile("mov.b32 %0, %1;" : "=r"(A[4 * i + 3]) : "r"(A[4 * i + 0]));
}
template <bool GB, int I0, int I1> __device__ __forceinline__ void conv_mmas(float* acc, const uint32_t* A, uint64_t d) {
  if constexpr (I0 < I1) {
    constexpr int M = grp_m<GB>(I0);
    wgmma_rs<128 - 8 * (M / 2), 0>(acc, A + 4 * I0, d + (uint64_t)(4 * M), M != 0);
    conv_mmas<GB, I0 + 1, I1>(acc, A, d);
  }
}
struct SumAddr { uint32_t l0, l1, l2, se, so; };
__device__ __forceinline__ SumAddr conv_sum_addr(uint32_t sb, int c) {
  auto ua = [&](int j) { return sb + cv_u(0) + (127 - (j >> 3)) * 16 + (j & 7) * 2; };
  auto sa = [&](int hc) { const int ci = hc & ~1; return sb + cv_s(0) + ((ci >> 3) & 1) * 1024 + (ci >> 4) * 128 + (((ci ^ (ci >> 4)) & 7) << 4) + (hc & 1) * 8; };
  const int j0 = 4 * (c - 1);
  return {ua(j0 - 2), ua(j0), ua(j0 + 4), sa((c + 1) & 127), sa(c) + 2048};
}
__device__ __forceinline__ void sts64(uint32_t a, uint32_t x, uint32_t y) { asm volatile("st.shared.v2.b32 [%0], {%1,%2};" ::"r"(a), "r"(x), "r"(y) : "memory"); }
__device__ __forceinline__ void conv_sums(const SumAddr& sa, int lc, int c) {
  uint32_t e[4], o[4];
  {
    const float2 em = lds64f(sa.l1 + lc * 32768), om = lds64f(sa.l1 + lc * 32768 + CV_UH);
    e[0] = lds32(sa.l0 + lc * 32768); o[0] = lds32(sa.l0 + lc * 32768 + CV_UH);
    e[3] = lds32(sa.l2 + lc * 32768); o[3] = lds32(sa.l2 + lc * 32768 + CV_UH);
    e[1] = __float_as_uint(em.x); e[2] = __float_as_uint(em.y); o[1] = __float_as_uint(om.x); o[2] = __float_as_uint(om.y);
  }
  uint32_t s7e[2], s7o[2], s9e[2], s9o[2];
  uint32_t pw[4], sh[3];
#pragma unroll
  for (int k = 0; k < 4; k++) pw[k] = hadd2(e[k], o[k]);
#pragma unroll
  for (int k = 0; k < 3; k++) sh[k] = __byte_perm(pw[k], pw[k + 1], 0x5432);
#pragma unroll
  for (int k = 0; k < 2; k++) {
    const uint32_t t3 = hadd2(hadd2(sh[k], sh[k + 1]), pw[k + 1]);
    s7e[k] = hadd2(t3, o[k]); s7o[k] = hadd2(t3, e[k + 2]);
    s9e[k] = hadd2(s7o[k], pw[k]); s9o[k] = hadd2(s7e[k], pw[k + 2]);
  }
  if (c == 127) s9e[0] = s9e[1] = s9o[0] = s9o[1] = 0u;
  sts64(sa.se + lc * 32768, s9e[0], s9e[1]); sts64((sa.se ^ 16) + lc * 32768, s9o[0], s9o[1]);
  sts64(sa.so + lc * 32768, s7e[0], s7e[1]); sts64((sa.so ^ 16) + lc * 32768, s7o[0], s7o[1]);
}

__device__ __forceinline__ void conv_epi(uint32_t sb, int layer, int cta, int ch, int c0, uint4 x0, uint4 x1) {
  uint4 v[2][4];
  const uint4 xr[2] = {x0, x1};
  mbar_wait(sb + SM_BAR + 8 * (B_P + ch), layer);
#pragma unroll
  for (int u = 0; u < 2; u++) {
    const uint32_t pb = sb + cv_pb(ch) + u * (CV_PBW / 2) + c0 * 16;
#pragma unroll
    for (int k = 0; k < 4; k++) v[u][k] = lds128(pb + k * CV_PBW);
  }
#pragma unroll
  for (int u = 0; u < 2; u++) {
    uint4 o;
    o.x = hadd2(xr[u].x, hadd2(hadd2(v[u][0].x, v[u][1].x), hadd2(v[u][2].x, v[u][3].x)));
    o.y = hadd2(xr[u].y, hadd2(hadd2(v[u][0].y, v[u][1].y), hadd2(v[u][2].y, v[u][3].y)));
    o.z = hadd2(xr[u].z, hadd2(hadd2(v[u][0].z, v[u][1].z), hadd2(v[u][2].z, v[u][3].z)));
    o.w = hadd2(xr[u].w, hadd2(hadd2(v[u][0].w, v[u][1].w), hadd2(v[u][2].w, v[u][3].w)));
    if (layer == 0) sts128(sb + cv_s(ch) + (c0 + 128 * u) * 16, o);
    else st_tagged3((uint4*)(g_xT + (size_t)(3 * DM + cv_chan(cta, ch)) * LSEQ) + c0 + 128 * u, o.x, o.y, o.z, o.w);
  }
}
__device__ __forceinline__ void warp_release(uint32_t b) {
  fence_writer();
  __syncwarp();
  if (elect_one()) mbar_arrive(b);
}

__device__ __forceinline__ void conv_prep_load(uint32_t sb, int layer, int cta, int c, uint4 (&xr)[4], uint4 (&st)[4]) {
  mbar_wait(sb + SM_BAR + 8 * B_GB, layer);
  if (threadIdx.x == 0) TS(2 + layer * 20 + 11);
  xr[0] = ld_tagged((const uint4*)(g_xT + (size_t)(2 * layer * DM + cta) * LSEQ) + c);
#pragma unroll
  for (int i = 0; i < 4; i++) st[i] = ld_tagged((const uint4*)g_stats + (layer * 32 + (c >> 3)) * 32 + i * 8 + (c & 7));
}
template <bool HELPER>
__device__ __forceinline__ void conv_prep(uint32_t sb, int layer, int cta, int c, uint4 (&xr)[4], uint4 (&st)[4], const SumAddr& sa) {
  const uint32_t bar = sb + SM_BAR;
  const uint4* xin = (const uint4*)(g_xT + (size_t)(2 * layer * DM + cta) * LSEQ) + c;
  for (int it = 0;; it++) {
    const bool okx = __all_sync(~0u, xr[0].x != ~0u);
    const bool oks = __all_sync(~0u, (st[0].y & st[1].y & st[2].y & st[3].y & 1u) != 0);
    if (okx && oks) break;
    if (it > (1 << 22)) __trap();
    if (!okx) xr[0] = ld_tagged(xin);
    if (!oks) {
#pragma unroll
      for (int i = 0; i < 4; i++) st[i] = ld_tagged((const uint4*)g_stats + (layer * 32 + (c >> 3)) * 32 + i * 8 + (c & 7));
    }
  }
  if (threadIdx.x == 0) TS(2 + layer * 20 + 12);
  const int a = c & 127, h = c >> 7;
#pragma unroll
  for (int i = 0; i < 4; i++) {
    if (i == 1) {
#pragma unroll
      for (int j = 1; j < 4; j++) xr[j] = ld_tagged(xin + j * (128 * LSEQ / 8));
      if (HELPER) {
        mbar_wait(bar + 8 * B_U, layer);
        conv_sums(sa, 0, c);
        fence_async_smem();
        warp_release(bar + 8 * B_S);
        if (layer == 1 && c == 0) TS(46);
        mbar_wait(bar + 8 * B_GB, layer);
      }
      for (int it = 0; !__all_sync(~0u, xr[1].x != ~0u && xr[2].x != ~0u && xr[3].x != ~0u); it++) {
        if (it > (1 << 22)) __trap();
#pragma unroll
        for (int j = 1; j < 4; j++) xr[j] = ld_tagged(xin + j * (128 * LSEQ / 8));
      }
    }
    const uint32_t x[4] = {xr[i].x, xr[i].y, xr[i].z, xr[i].w};
    uint32_t u[4];
#pragma unroll
    for (int k = 0; k < 4; k++)
      u[k] = packbf(fmaf(bf_lo(x[k]), __uint_as_float(st[k].y), __uint_as_float(st[k].x)), fmaf(bf_hi(x[k]), __uint_as_float(st[k].w), __uint_as_float(st[k].z)));
    sts128(sb + cv_u(i) + h * CV_UH + (127 - a) * 16, make_uint4(u[0], u[1], u[2], u[3]));
    warp_release(bar + 8 * (B_U + i));
  }
}
__device__ __forceinline__ void conv_zero(uint32_t sb, int ht) {
  if (ht < 96) {
    const int ch = ht / 24, h2 = (ht / 12) & 1, qq = ht % 12;
    sts128(sb + cv_u(ch) + h2 * CV_UH + (128 + qq) * 16, make_uint4(0, 0, 0, 0));
  }
  if (ht >= 80) {
    const int i = ht - 80, ch = i / 12, q2 = i % 12;
    const int w2 = q2 < 2 ? 1 : q2 < 6 ? 2 : 3, cc = q2 < 2 ? q2 : q2 < 6 ? q2 - 2 : q2 - 6;
    sts128(sb + cv_pb(ch) + w2 * CV_PBW + (cc & 1) * (CV_PBW / 2) + (cc >> 1) * 16, make_uint4(0, 0, 0, 0));
  }
}

#define LD_AT 0
#define HANDOVER 12
template <int R>
__device__ __forceinline__ void conv_round(uint32_t sb, int layer, int wg, uint32_t* FA, uint32_t* FB, uint32_t pb, uint32_t pe2) {
  const uint32_t bar = sb + SM_BAR;
  const int ch = 2 * R + 1 - wg;
  float acc[64];
  const uint64_t d = mkdesc(sb + cv_u(ch), CV_UH, 128, 0);
  const bool leader = (opaque_tid() & 127) == 0;
  FTS(39);
  if (R == 0) {
    mbar_wait(bar + 8 * (B_U + ch), layer);
    fence_reader();
  }
  if (ch > 0) mbar_wait(bar + 8 * (B_T + ch - 1), layer);
  FTS(41);
  if (ch == 0 && threadIdx.x == 128) TS(2 + layer * 20 + 13);
  if (R == 1 && LD_AT == 0) conv_load<true>(FB, pe2);
  wg_fence();
  conv_mmas<false, 0, (HANDOVER < NA ? HANDOVER : NA)>(acc, FA, d);
  if (HANDOVER <= NA) mbar_arrive_if(bar + 8 * (B_T + ch), leader);
  conv_mmas<false, (HANDOVER < NA ? HANDOVER : NA), NA>(acc, FA, d);
  wg_commit();
  if (R == 1 && LD_AT == 1) conv_load<true>(FB, pe2);
  FTS(51);
  mbar_wait(bar + 8 * (B_S + ch), layer);
  if (R == 1) conv_dup<true>(FB);
  wg_fence();
  conv_mmas<true, 0, (HANDOVER > NA ? HANDOVER - NA : 0)>(acc, FB, d);
  if (HANDOVER > NA) mbar_arrive_if(bar + 8 * (B_T + ch), leader);
  conv_mmas<true, (HANDOVER > NA ? HANDOVER - NA : 0), 17 - NA>(acc, FB, d);
  wgmma_ss<64, 1, 1>(acc, mkdesc(sb + cv_s(ch), 1024, 1024, 1), mkdesc(sb + cv_ft(ch), 256, 16, 0), 1);
  wgmma_ss<64, 1, 1>(acc, mkdesc(sb + cv_s(ch) + 2048, 1024, 1024, 1), mkdesc(sb + cv_ft(ch) + 512, 256, 16, 0), 1);
  wg_commit();
  FTS(61);
  wg_wait<0>();
#pragma unroll
  for (int j = 0; j < 16; j += 2)
    stsm4t(pb + R * 65536 - j * 128, packbf(acc[4 * j], acc[4 * j + 1]), packbf(acc[4 * j + 2], acc[4 * j + 3]),
           packbf(acc[4 * j + 4], acc[4 * j + 5]), packbf(acc[4 * j + 6], acc[4 * j + 7]));
  __syncwarp();
  if (elect_one()) mbar_arrive(bar + 8 * (B_P + ch));
  if (threadIdx.x == 0) TS(2 + layer * 20 + 14 + R);
  FTS(57);
  if (R == 0) {
    mbar_wait(bar + 8 * (B_U + ch + 2), layer);
    fence_reader();
  }
}
__device__ __forceinline__ void conv_phase(const Params& p, uint32_t sb, int layer, int cta) {
  const int tid = opaque_tid();
  const int wg = __shfl_sync(~0u, tid >> 7, 0), w = __shfl_sync(~0u, (tid >> 5) & 3, 0);
  const uint32_t bar = sb + SM_BAR;
  uint32_t FA0[4 * NA], FA1[4 * NA], FB[4 * (17 - NA)];
  const uint32_t pe = sb + cv_pe(1 - wg) + 4 * (16 + 16 * w + 2 * ((tid & 31) >> 2) - 4 * (tid & 3));
  mbar_wait(bar + 8 * B_PE, layer);
  conv_load<false>(FA0, pe); conv_load<true>(FB, pe);
  const uint32_t zero = tid >> 10;
  conv_dup_early<false>(FA0, zero); conv_dup_early<true>(FB, zero);
  if (wg == 0) {
    uint4 xr[4], st[4];
    conv_prep_load(sb, layer, cta, tid + 128, xr, st);
    conv_load<false>(FA1, pe + 65536);
    conv_dup_early<false>(FA1, zero);
    conv_prep<false>(sb, layer, cta, opaque_tid() + 128, xr, st, SumAddr());
  } else {
    conv_load<false>(FA1, pe + 65536);
    conv_dup_early<false>(FA1, zero);
  }
  uint32_t pb;
  {
    const int l2 = opaque_tid() & 31, mt = l2 >> 3;
    pb = sb + cv_pb(1 - wg) + w * CV_PBW + (mt & 1) * (CV_PBW / 2) + (127 - 8 * (mt >> 1) - (l2 & 7) + w) * 16;
  }
  conv_round<0>(sb, layer, wg, FA0, FB, pb, 0);
  conv_round<1>(sb, layer, wg, FA1, FB, pb, pe + 65536);
  if (wg == 1 && layer == 0) mbar_wait(bar + 8 * (B_T + 3), layer);
}

__device__ __forceinline__ void final_phase(const Params& p, uint32_t sb, int cta, int wg, int w) {
  if (wg == 1 && w == 3) return;
  const int lane = opaque_tid() & 31, g = lane >> 2, t = lane & 3;
  const int lc = wg ? w : 3;
  const int pos0 = (cta & 31) * 64, ch0 = 128 * lc + (cta >> 5) * 32;
  const bf16* src = g_xT + (size_t)(3 * DM + ch0 + 8 * (g >> 1) + (g & 1)) * LSEQ + pos0;
  bf16* dst = p.out + (size_t)(2 * (pos0 & 1023) + (pos0 >> 10)) * DM + ch0 + 8 * t;
  constexpr int RS = 2 * DM;
  int it = 0;
  mbar_wait(sb + SM_BAR + 8 * (B_E + lc), 1);
  delay<D_FIN>();
  if (wg == 0) {
    uint2 v[4];
    do {
#pragma unroll
      for (int q = 0; q < 4; q++)
        asm volatile("ld.relaxed.gpu.global.v2.u32 {%0,%1}, [%2];" : "=r"(v[q].x), "=r"(v[q].y) : "l"(src + 2 * q * LSEQ + 16 * w + 4 * t) : "memory");
      if (++it > (1 << 22)) __trap();
    } while (!__all_sync(~0u, v[0].x != ~0u && v[1].x != ~0u && v[2].x != ~0u && v[3].x != ~0u));
    if (threadIdx.x == 0) TS(42);
    dst += (16 * w + 4 * (g >> 1) + (g & 1)) * RS;
    *(uint4*)dst = make_uint4(movm_t(v[0].x), movm_t(v[1].x), movm_t(v[2].x), movm_t(v[3].x));
    *(uint4*)(dst + 2 * RS) = make_uint4(movm_t(v[0].y), movm_t(v[1].y), movm_t(v[2].y), movm_t(v[3].y));
  } else {
    uint4 v[2][4];
    bool ok;
    do {
      ok = true;
#pragma unroll
      for (int h = 0; h < 2; h++)
#pragma unroll
        for (int q = 0; q < 4; q++) v[h][q] = ld_tagged((const uint4*)(src + 2 * q * LSEQ + 32 * h + 8 * t));
#pragma unroll
      for (int h = 0; h < 2; h++)
#pragma unroll
        for (int q = 0; q < 4; q++) ok = ok && v[h][q].x != ~0u;
      if (++it > (1 << 22)) __trap();
    } while (!__all_sync(~0u, ok));
    dst += (8 * (g >> 1) + (g & 1)) * RS;
#pragma unroll
    for (int h = 0; h < 2; h++) {
      *(uint4*)(dst + (32 * h + 0) * RS) = make_uint4(movm_t(v[h][0].x), movm_t(v[h][1].x), movm_t(v[h][2].x), movm_t(v[h][3].x));
      *(uint4*)(dst + (32 * h + 2) * RS) = make_uint4(movm_t(v[h][0].y), movm_t(v[h][1].y), movm_t(v[h][2].y), movm_t(v[h][3].y));
      *(uint4*)(dst + (32 * h + 4) * RS) = make_uint4(movm_t(v[h][0].z), movm_t(v[h][1].z), movm_t(v[h][2].z), movm_t(v[h][3].z));
      *(uint4*)(dst + (32 * h + 6) * RS) = make_uint4(movm_t(v[h][0].w), movm_t(v[h][1].w), movm_t(v[h][2].w), movm_t(v[h][3].w));
    }
  }
  if (threadIdx.x == 0) TS(43);
  if (threadIdx.x == 192) TS(63);
  if (threadIdx.x == 0) LTS(1);
}

struct cplx { float r, i; };
__device__ __forceinline__ cplx cmul(cplx a, cplx b) { return {fmaf(a.r, b.r, -a.i * b.i), fmaf(a.r, b.i, a.i * b.r)}; }
__device__ __forceinline__ cplx csqr(cplx a) { return {fmaf(a.r, a.r, -a.i * a.i), (a.r + a.r) * a.i}; }
__device__ __forceinline__ cplx cexp_l(float ar2, float ai, float l) {
  const float m = ex2(ar2 * l);
  const float x = ai * l;
  return {m * __cosf(x), m * __sinf(x)};
}

__device__ __forceinline__ void colsum_publish(uint32_t sb, int rb, int hg, int ht, uint32_t tag) {
  const int lane = ht & 31, q = lane & 15, h = lane >> 4;
  const uint32_t src = sb + SM_CW + (ht >> 5) * 4096 + h * 128 + (q & 1) * 8;
  float s[4] = {0.f, 0.f, 0.f, 0.f};
#pragma unroll 8
  for (int r = 0; r < 16; r++) {
    const float2 v = lds64f(src + r * 256 + (((q >> 1) ^ ((2 * r + h) & 7)) << 4));
    s[0] += bf_lo(__float_as_uint(v.x)); s[1] += bf_hi(__float_as_uint(v.x));
    s[2] += bf_lo(__float_as_uint(v.y)); s[3] += bf_hi(__float_as_uint(v.y));
  }
#pragma unroll
  for (int k = 0; k < 4; k++) s[k] += __shfl_xor_sync(~0u, s[k], 16);
  if (h == 0)
    st_tagged3(&g_colsum[(hg * 16 + rb) * 48 + (ht >> 5) * 16 + q], (__float_as_uint(s[0]) & ~7u) | tag, __float_as_uint(s[1]),
               __float_as_uint(s[2]), __float_as_uint(s[3]));
}
__device__ __forceinline__ void colsum_gather(uint32_t sb, int hg, int ht, uint32_t tag) {
  const int lane = ht & 31, rec = (ht >> 5) * 16 + (lane & 15);
  const uint4* src = &g_colsum[(hg * 16 + (lane >> 4) * 8) * 48 + rec];
  float s[4] = {0.f, 0.f, 0.f, 0.f};
#pragma unroll 1
  for (int h = 0; h < 2; h++, src += 4 * 48) {
    uint4 v[4];
    int it = 0;
    do {
#pragma unroll
      for (int i = 0; i < 4; i++) v[i] = ld_tagged(src + i * 48);
      if (++it > (1 << 22)) __trap();
    } while (!__all_sync(~0u, (v[0].x & 7u) == tag && (v[1].x & 7u) == tag && (v[2].x & 7u) == tag && (v[3].x & 7u) == tag));
#pragma unroll
    for (int i = 0; i < 4; i++) {
      s[0] += __uint_as_float(v[i].x & ~7u); s[1] += __uint_as_float(v[i].y); s[2] += __uint_as_float(v[i].z); s[3] += __uint_as_float(v[i].w);
    }
  }
#pragma unroll
  for (int k = 0; k < 4; k++) s[k] += __shfl_xor_sync(~0u, s[k], 16);
  if (lane < 16) sts128f(sb + SM_CS + rec * 16, s[0], s[1], s[2], s[3]);
}

__device__ __forceinline__ uint32_t packh(float lo, float hi) { uint32_t r; asm("cvt.rn.f16x2.f32 %0, %1, %2;" : "=r"(r) : "f"(hi), "f"(lo)); return r; }
__device__ __forceinline__ void mma_f16(float* d, uint32_t a0, uint32_t a1, uint32_t a2, uint32_t a3, uint32_t b0, uint32_t b1) {
  asm volatile("mma.sync.aligned.m16n8k16.row.col.f32.f16.f16.f32 {%0,%1,%2,%3}, {%4,%5,%6,%7}, {%8,%9}, {%0,%1,%2,%3};"
      : "+f"(d[0]), "+f"(d[1]), "+f"(d[2]), "+f"(d[3]) : "r"(a0), "r"(a1), "r"(a2), "r"(a3), "r"(b0), "r"(b1));
}
struct HSeed { uint32_t r, i; };
__device__ __forceinline__ HSeed hseed(cplx s) { return {packh(s.r, s.r), packh(s.i, s.i)}; }
__device__ __forceinline__ void hcmul(uint32_t& o_r, uint32_t& o_i, uint32_t br, uint32_t bi, HSeed s) {
  asm("{\n.reg .b32 t, u;\nmul.rn.f16x2 t, %3, %5;\nneg.f16x2 t, t;\nmul.rn.f16x2 u, %3, %4;\nfma.rn.f16x2 %0, %2, %4, t;\nfma.rn.f16x2 %1, %2, %5, u;\n}"
      : "=&r"(o_r), "=&r"(o_i) : "r"(br), "r"(bi), "r"(s.r), "r"(s.i));
}
struct HTile { uint32_t r[4], i[4]; };
__device__ __forceinline__ void tile_set(HTile& t, int k, cplx a, cplx b) { t.r[k] = packh(a.r, b.r); t.i[k] = packh(a.i, b.i); }
__device__ __forceinline__ void tile_upper(HTile& t, HSeed s) { hcmul(t.r[2], t.i[2], t.r[0], t.i[0], s); hcmul(t.r[3], t.i[3], t.r[1], t.i[1], s); }
__device__ __forceinline__ HTile tile_shift(const HTile& t, HSeed s) {
  HTile o;
#pragma unroll
  for (int k = 0; k < 4; k++) hcmul(o.r[k], o.i[k], t.r[k], t.i[k], s);
  return o;
}
__device__ __forceinline__ void tile_put(const HTile& t, uint32_t a) {
  sts128(a, make_uint4(t.r[0], t.r[1], t.r[2], t.r[3]));
  sts128(a + 512, make_uint4(t.i[0], t.i[1], t.i[2], t.i[3]));
}
__device__ __forceinline__ HTile tile_get(uint32_t a) { HTile o; ldsm4t(o.r, a); ldsm4t(o.i, a + 512); return o; }
__device__ __forceinline__ void tile_mma(float* T, const HTile& a0, const HTile& a1, const HTile& b) {
  mma_f16(T, a0.r[0], a0.r[1], a0.r[2], a0.r[3], b.r[0], b.r[1]);
  mma_f16(T, a0.i[0], a0.i[1], a0.i[2], a0.i[3], b.i[0], b.i[1]);
  mma_f16(T, a1.r[0], a1.r[1], a1.r[2], a1.r[3], b.r[2], b.r[3]);
  mma_f16(T, a1.i[0], a1.i[1], a1.i[2], a1.i[3], b.i[2], b.i[3]);
}
__device__ __forceinline__ void tile_mma2(float* T, float* U, const HTile& a0, const HTile& a1, const HTile& b, const HTile& c) {
  mma_f16(T, a0.r[0], a0.r[1], a0.r[2], a0.r[3], b.r[0], b.r[1]);
  mma_f16(U, a0.r[0], a0.r[1], a0.r[2], a0.r[3], c.r[0], c.r[1]);
  mma_f16(T, a0.i[0], a0.i[1], a0.i[2], a0.i[3], b.i[0], b.i[1]);
  mma_f16(U, a0.i[0], a0.i[1], a0.i[2], a0.i[3], c.i[0], c.i[1]);
  mma_f16(T, a1.r[0], a1.r[1], a1.r[2], a1.r[3], b.r[2], b.r[3]);
  mma_f16(U, a1.r[0], a1.r[1], a1.r[2], a1.r[3], c.r[2], c.r[3]);
  mma_f16(T, a1.i[0], a1.i[1], a1.i[2], a1.i[3], b.i[2], b.i[3]);
  mma_f16(U, a1.i[0], a1.i[1], a1.i[2], a1.i[3], c.i[2], c.i[3]);
}
__device__ __forceinline__ void kgen_unit(uint32_t tab, uint32_t taba, float ar2, float ai, cplx c, float (&T)[5][4]) {
  const cplx z1 = cexp_l(ar2, ai, 1.f), z16 = cexp_l(ar2, ai, 16.f), z256 = cexp_l(ar2, ai, 256.f);
  HTile a0, a1, b0, b1;
  {
    const cplx y1 = {z16.r, -z16.i}, y2 = csqr(y1), y3 = cmul(y2, y1), y4 = csqr(y2), y5 = cmul(y4, y1), y6 = csqr(y3), y7 = cmul(y4, y3);
    HTile t;
    tile_set(t, 0, {1.f, 0.f}, y1); tile_set(t, 1, y2, y3); tile_set(t, 2, y4, y5); tile_set(t, 3, y6, y7);
    const HTile u = tile_shift(t, hseed(csqr(y4)));
    __syncwarp();
    tile_put(t, tab); tile_put(u, tab + 1024);
    __syncwarp();
    a0 = tile_get(taba); a1 = tile_get(taba + 256);
  }
  const cplx z2 = csqr(z1), z4 = csqr(z2), z8 = csqr(z4);
  const HSeed h8 = hseed(z8);
  const cplx d = cmul(c, z256), e = cmul(d, z256);
  {
    const cplx z512 = csqr(z256), f = cmul(e, z512), f8 = cmul(f, z8), f16 = cmul(f, z16), e4 = cmul(e, z4);
    HTile t, u;
    tile_set(t, 0, e4, cmul(e, z8)); tile_set(t, 1, cmul(e4, z8), cmul(e, z16));
    tile_upper(t, hseed(z256));
    tile_set(u, 0, f8, f16); tile_set(u, 1, cmul(f8, z256), cmul(f16, z256));
    tile_upper(u, hseed(z512));
    __syncwarp();
    tile_put(t, tab); tile_put(u, tab + 1024);
    __syncwarp();
    b0 = tile_get(tab); b1 = tile_get(tab + 1024);
  }
  {
    const cplx d2 = cmul(d, z2), d4 = cmul(d, z4);
    HTile t;
    tile_set(t, 0, d2, d4); tile_set(t, 1, cmul(d2, z4), cmul(d, z8));
    tile_upper(t, h8);
    __syncwarp();
    tile_put(t, tab);
    __syncwarp();
    tile_mma2(T[3], T[4], a0, a1, b0, b1);
    b0 = tile_get(tab);
  }
  {
    const cplx c1 = cmul(c, z1), c2 = cmul(c, z2), c3 = cmul(c1, z2), c4 = cmul(c, z4);
    HTile t;
    tile_set(t, 0, c1, c2); tile_set(t, 1, c3, c4); tile_set(t, 2, cmul(c1, z4), cmul(c2, z4)); tile_set(t, 3, cmul(c3, z4), cmul(c4, z4));
    const HTile u = tile_shift(t, h8);
    __syncwarp();
    tile_put(t, tab); tile_put(u, tab + 1024);
    __syncwarp();
    tile_mma(T[2], a0, a1, b0);
    b0 = tile_get(tab); b1 = tile_get(tab + 1024);
    tile_mma2(T[0], T[1], a0, a1, b0, b1);
  }
}
struct ModeIn { uint2 ar, ai, br, bi, cr, ci; };
__device__ __forceinline__ ModeIn load_modes(const Params& p, int idx) {
  return {*(const uint2*)(p.a_re + idx), *(const uint2*)(p.a_im + idx), *(const uint2*)(p.b_re + idx),
          *(const uint2*)(p.b_im + idx), *(const uint2*)(p.c_re + idx), *(const uint2*)(p.c_im + idx)};
}
__device__ __forceinline__ float bf_el(uint2 v, int k) { const uint32_t x = (k & 2) ? v.y : v.x; return (k & 1) ? bf_hi(x) : bf_lo(x); }
struct KGen { float4 cur; float T[5][4]; };
__device__ __forceinline__ uint32_t kgen_slot(uint32_t sb, int ht, int u) {
  return sb + (u < 3 ? SM_KC + (ht >> 5) * (KC_STRIDE * 2) + (u - 1) * 512 + (ht & 31) * 16 + 16 : SM_HALO + 1024 + ht * 16);
}
__device__ __forceinline__ void kgen_setup(KGen& s, uint32_t sb, int cta, int ht, const ModeIn& in, bf16 logdt, bf16 dskip) {
  const float dt = __bfloat162float(__float2bfloat16_rn(expf(__bfloat162float(logdt))));
  float mx = 0.f, k0 = 0.f, ar2[4];
  cplx c[4];
#pragma unroll
  for (int k = 0; k < 4; k++) {
    ar2[k] = (dt * bf_el(in.ar, k)) * 1.4426950408889634f;
    c[k] = cmul({bf_el(in.cr, k), bf_el(in.ci, k)}, {dt * bf_el(in.br, k), dt * bf_el(in.bi, k)});
    k0 += c[k].r;
    mx = fmaxf(mx, fmaxf(fabsf(c[k].r), fabsf(c[k].i)) * ex2(fmaxf(ar2[k] * 2048.f, 0.f)));
  }
  const int ex = min(max(267 - (int)(__reduce_max_sync(~0u, __float_as_uint(mx)) >> 23), 1), 253);
  const float sc = __uint_as_float(ex << 23);
#pragma unroll
  for (int o = 16; o > 0; o >>= 1) k0 += __shfl_xor_sync(~0u, k0, o);
  if ((ht & 31) == 0) {
    const uint32_t kc = sb + SM_KC + (ht >> 5) * (KC_STRIDE * 2);
    sts16(kc, __bfloat16_as_ushort(__float2bfloat16_rn(k0 + __bfloat162float(dskip))));
    sts16(kc + 641 * 2, 0);
    sts32f(kc + 644 * 2, __uint_as_float((254 - ex) << 23));
  }
  s.cur = make_float4(ar2[0], dt * bf_el(in.ai, 0), c[0].r * sc, c[0].i * sc);
#pragma unroll
  for (int k = 1; k < 4; k++) sts128f(kgen_slot(sb, ht, k), ar2[k], dt * bf_el(in.ai, k), c[k].r * sc, c[k].i * sc);
#pragma unroll
  for (int i = 0; i < 5; i++) s.T[i][0] = s.T[i][1] = s.T[i][2] = s.T[i][3] = 0.f;
}
__device__ __forceinline__ void kgen_finish(KGen& s, uint32_t sb, int cta, int ht) {
  const int w = ht >> 5, lane = ht & 31, g = lane >> 2, t = lane & 3;
  const uint32_t kc = sb + SM_KC + w * KC_STRIDE * 2;
  __syncwarp();
  const float inv = __uint_as_float(lds32(kc + 644 * 2));
  auto put = [&](int idx, float v) {
    sts16(kc + idx * 2, __bfloat16_as_ushort(__float2bfloat16_rn(v)));
  };
#pragma unroll
  for (int hi = 0; hi < 2; hi++)
#pragma unroll
    for (int lo = 0; lo < 2; lo++) {
      const int i = g + 8 * hi, j = 2 * t + lo, e = 2 * hi + lo;
      put(16 * i + 1 + j, s.T[0][e] * inv);
      put(16 * i + 9 + j, s.T[1][e] * inv);
      put(257 + 8 * i + j, s.T[2][e] * inv);
      put(385 + 4 * i + (j & 3) + 64 * (j >> 2), s.T[3][e] * inv);
      put(513 + 2 * i + lo + 32 * t, s.T[4][e] * inv);
    }
}

__device__ __forceinline__ void expand_taps(uint32_t sb, int ht) {
  const int ch = ht >> 5, lane = ht & 31;
  const uint32_t kc = sb + SM_KC + ch * KC_STRIDE * 2;
  const uint32_t dst0 = sb + cv_pe(ch);
  auto put = [&](int G, uint32_t u0, uint32_t u1, uint32_t v0, uint32_t v1, uint32_t v2, uint32_t v3, uint32_t v4, uint32_t v5, uint32_t v6, uint32_t v7) {
    const uint32_t dst = dst0 + G * 32;
    sts128(dst, make_uint4(v0 | (u0 << 16), v1 | (u1 << 16), v2 | (v0 << 16), v3 | (v1 << 16)));
    sts128(dst + 16, make_uint4(v4 | (v2 << 16), v5 | (v3 << 16), v6 | (v4 << 16), v7 | (v5 << 16)));
  };
  {
    const uint4 q = lds128(kc + lane * 16);
    const uint32_t pv = lane ? lds32(kc + lane * 16 - 4) : 0u;
    const uint32_t dst = dst0 + (lane + 2) * 32;
    sts128(dst, make_uint4(__byte_perm(q.x, pv, 0x5410), __byte_perm(q.x, pv, 0x7632), __byte_perm(q.y, q.x, 0x5410), __byte_perm(q.y, q.x, 0x7632)));
    sts128(dst + 16, make_uint4(__byte_perm(q.z, q.y, 0x5410), __byte_perm(q.z, q.y, 0x7632), __byte_perm(q.w, q.z, 0x5410), __byte_perm(q.w, q.z, 0x7632)));
    if (lane < 4) sts128(dst0 + lane * 16, make_uint4(0, 0, 0, 0));
  }
  uint32_t a[5], b[2][3], fv[4];
  {
    const uint32_t s1 = kc + 2 * (256 + 4 * lane);
#pragma unroll
    for (int k = 0; k < 5; k++) a[k] = lds16(s1 + 2 * k);
#pragma unroll
    for (int u = 0; u < 2; u++) {
      const uint32_t s2 = kc + 2 * (384 + 2 * (lane + 32 * u));
#pragma unroll
      for (int k = 0; k < 3; k++) b[u][k] = lds16(s2 + 2 * k);
    }
#pragma unroll
    for (int k = 0; k < 4; k++) fv[k] = lds16(kc + 2 * (640 - 4 * lane - k));
  }
  const uint32_t am1 = lds16(kc + 2 * (lane ? 256 + 4 * lane : 255)), am2 = lds16(kc + 2 * (lane ? 255 + 4 * lane : 254));
  const uint32_t bm2 = lds16(kc + 2 * (lane ? 384 + 2 * lane : 383)), k1024 = lds16(kc + 2 * 512);
  put(34 + lane, am2, am1, a[0], a[0], a[1], a[2], a[2], a[2], a[3], a[4]);
#pragma unroll
  for (int u = 0; u < 2; u++) put(66 + lane + 32 * u, u ? b[u][0] : bm2, b[u][0], b[u][0], b[u][0], b[u][0], b[u][1], b[u][1], b[u][1], b[u][2], b[u][2]);
  if (lane < 10) {
    const uint32_t v = lane == 0 ? k1024 : 0u;
    put(130 + lane, v, v, v, v, v, v, v, 0u, 0u, 0u);
  }
  const uint32_t ft = sb + cv_ft(ch) + 4 * lane;
#pragma unroll
  for (int ty = 0; ty < 2; ty++) {
    const uint32_t v = fv[ty] | (fv[ty + 2] << 16);
    sts32f(ft + ty * 512, __uint_as_float(v));
    sts32f(ft + ty * 512 + 128, 0.f);
    sts32f(ft + ty * 512 + 256 + (lane < 2 ? 120 : -8), __uint_as_float(lane < 2 ? 0u : v));
    sts32f(ft + ty * 512 + 384, 0.f);
  }
}

__device__ __forceinline__ int role_id() { int v; asm volatile("mov.u32 %0, %%ctaid.x;" : "=r"(v)); return v; }
#define GMAP 8
__device__ __forceinline__ int role_rb(int cta) { return 4 * (cta >> 5) + (cta & 3); }
__device__ __forceinline__ int role_hg(int cta) { return 2 * (((cta >> 3) & 3) ^ (((cta >> 5) & 1) * 3)) + ((cta >> 2) & 1); }
__device__ __forceinline__ int role_rb2(int cta) { return cta >> 3; }
__device__ __forceinline__ int role_q2(int cta) { return cta & 7; }

__global__ void __launch_bounds__(NTHREADS, 1) fused_kernel(const __grid_constant__ Params p) {
  extern __shared__ __align__(1024) uint8_t smem[];
  const uint32_t sb = s32(smem);
  const int tid = threadIdx.x, lane = tid & 31;
  const int warp = __shfl_sync(~0u, tid >> 5, 0);
  const uint32_t bar = sb + SM_BAR;
  if (tid == 0) TS(0);
  const int cta0 = role_id();
  if (warp == 0 && elect_one()) {
    const int rb = role_rb(cta0), hg = role_hg(cta0);
#pragma unroll
    for (int c = 0; c < 2; c++) { mbar_init(bar + 8 * (B_XF + c), 1); mbar_init(bar + 8 * (B_KVF + c), 1); }
    fence_async_smem();
#pragma unroll
    for (int c = 0; c < 2; c++) {
      mbar_expect(bar + 8 * (B_XF + c), 16384);
      tma_ld(sb + SM_X + c * 16384, &p.mapX128, (rb >> 3) * DM + c * 64, (rb & 7) * 128, bar + 8 * (B_XF + c));
      mbar_expect(bar + 8 * (B_KVF + c), 24576);
      tma_ld3(sb + SM_W + c * 24576, &p.mapW3, hg * 64, c * 64, 0, bar + 8 * (B_KVF + c));
    }
  }
  if (warp == 1 && elect_one()) {
    const int rb = role_rb(cta0), hg = role_hg(cta0);
#pragma unroll
    for (int c = 2; c < 8; c++) mbar_init(bar + 8 * (B_XF + c), 1);
    mbar_init(bar + 8 * (B_KVF + 2), 1); mbar_init(bar + 8 * B_CW, 1);
    fence_async_smem();
    delay<D_START>();
    mbar_expect(bar + 8 * B_CW, 12288);
    tma_ld3(sb + SM_CW, &p.mapW3h, hg * 64, rb * 32, 0, bar + 8 * B_CW);
#pragma unroll
    for (int c = 2; c < 8; c++) {
      mbar_expect(bar + 8 * (B_XF + c), 16384);
      tma_ld(sb + SM_X + c * 16384, &p.mapX128, (rb >> 3) * DM + c * 64, (rb & 7) * 128, bar + 8 * (B_XF + c));
      if (c < 3) {
        mbar_expect(bar + 8 * (B_KVF + c), 24576);
        tma_ld3(sb + SM_W + c * 24576, &p.mapW3, hg * 64, c * 64, 0, bar + 8 * (B_KVF + c));
      }
    }
    TS(56);
  }
  if ((warp & 2) != 0 && warp < 15 && elect_one()) {
    const int grp = 1 + (warp & 1) + 2 * (warp >> 2), cnt = grp < 4 ? 1 : grp < 5 ? 2 : grp < 7 ? 4 : 8;
#pragma unroll
    for (int k = 0; k < 10; k++)
      if (k != 0 || grp > 3 || grp == 2) mbar_init(bar + 8 * (10 * grp + k), cnt);
    fence_async_smem();
  }

  if (warp < 8) {
    if (tid == 0) TS(1);
    asm volatile("setmaxnreg.inc.sync.aligned.u32 %0;" ::"n"(R_CONS));
    const int cta = role_id();
    auto warp_id = [] { return __shfl_sync(~0u, opaque_tid() >> 5, 0); };
    if (tid == 0) TS(54);
#pragma unroll 1
    for (int layer = 0; layer < 2; layer++) {
      { const int cw = warp_id(); attn_phase(p, sb, layer, role_rb(cta), role_hg(cta), cw >> 2, cw & 3); }
      if (p.stop == 1 + 3 * layer) return;
      { const int cw = warp_id(); proj_phase(p, sb, layer, role_rb2(cta), role_q2(cta), cw >> 2, cw & 3); }
      if (p.stop == 2 + 3 * layer) return;
      conv_phase(p, sb, layer, cta);
      if (p.stop == 3 + 3 * layer) return;
    }
    { const int cw = warp_id(); final_phase(p, sb, cta, cw >> 2, cw & 3); }
  } else if (warp < 12) {
    asm volatile("setmaxnreg.dec.sync.aligned.u32 %0;" ::"n"(R_HELP));
    const int ht = tid - 256;
    const int cta = role_id(), rb = role_rb(cta), hg = role_hg(cta);
    unsigned ep0 = 0;
    if (ht == 0) ep0 = ld_relaxed(&g_cnt[C_CS * 32]);
    bar_sync(0, NTHREADS);
    if (ht == 0) {
      asm volatile("st.shared.u32 [%0], %1;" ::"r"(sb + SM_EP), "r"(ep0 / NCTA) : "memory");
      mbar_arrive(bar + 8 * B_EP);
    }
    mbar_wait(bar + 8 * B_EP, 0);
    stats_publish(sb, 0, rb, hg, opaque_tid() - 256, part_tag(lds32(sb + SM_EP), 0));
    if (ht < 48) {
      const bf16* q = (&p.a_re)[ht >> 3];
      asm volatile("prefetch.global.L2 [%0];" ::"l"(q + cv_chan(cta, (ht >> 1) & 3) * 128 + (ht & 1) * 64));
    }
    {
      KGen kg;
      const uint32_t tab0 = sb + ((ht >> 5) < 2 ? SM_T : SM_T2 - 4096) + (ht >> 5) * 2048;
      const uint32_t tab = tab0 + (ht & 31) * 16, taba = tab0 + ((ht >> 3) & 1) * 1024 + (((ht >> 1) & 8) + (ht & 7)) * 16;
      delay<D_ST0>();
      stats_gather(sb, rb, opaque_tid() - 256, part_tag(lds32(sb + SM_EP), 0));
      if (ht == 0) TS(40);
      const int chn = cv_chan(cta, ht >> 5);
      const ModeIn modes = load_modes(p, chn * 128 + (ht & 31) * 4);
      const bf16 logdt = p.log_dt[chn], dskip = p.dskip[chn];
      halo_receive(sb, 0, rb, hg, opaque_tid() - 256);
      kgen_setup(kg, sb, cta, ht, modes, logdt, dskip);
#pragma unroll 1
      for (int u = 0; u < 4; u++) {
        if (u == KG_PRE) {
          KTS(39);
          mbar_wait(bar + 8 * B_AD, 0);
          KTS(41);
        }
        if (u == 4 - KG_LAST) mbar_wait(bar + 8 * (KG_PD ? B_PDONE : B_PS), 0);
        kgen_unit(tab, taba, kg.cur.x, kg.cur.y, {kg.cur.z, kg.cur.w}, kg.T);
        kg.cur = lds128f(kgen_slot(sb, opaque_tid() - 256, u + 1));
      }
      kgen_finish(kg, sb, cta, opaque_tid() - 256);
    }
    KTS(51);
    bar_sync(4, 128);
#pragma unroll 1
    for (int layer = 0; layer < 2; layer++) {
      if (p.stop <= 1 + 3 * layer) return;
      mbar_wait(bar + 8 * (EXP_LATE ? B_PS : B_PDONE), layer);
      expand_taps(sb, opaque_tid() - 256);
      conv_zero(sb, opaque_tid() - 256);
      if (ht == 0) TS(52 + layer);
      warp_release(bar + 8 * B_PE);
      if (p.stop <= 2 + 3 * layer) return;
      {
        uint4 xr[4], st[4];
        const int c = opaque_tid() - 256;
        const SumAddr sa = conv_sum_addr(sb, c);
        conv_prep_load(sb, layer, cta, c, xr, st);
        conv_prep<true>(sb, layer, cta, c, xr, st, sa);
        if (layer == 1 && ht == 0) TS(62);
        const bf16* xup = g_xT + (size_t)(2 * layer * DM + cta) * LSEQ + (c + 128) * 8;
        st[0] = ldcg128(xup);
        mbar_wait(bar + 8 * (B_U + 3), layer);
#pragma unroll
        for (int lc = 0; lc < 4; lc++) {
          if (lc < 3) {
            conv_sums(sa, lc + 1, c);
            fence_async_smem();
            warp_release(bar + 8 * (B_S + lc + 1));
            st[lc + 1] = ldcg128(xup + (lc + 1) * 128 * LSEQ);
          }
          conv_epi(sb, layer, cta, lc, c, xr[lc], st[lc]);
          warp_release(bar + 8 * (B_E + lc));
          if (layer == 1 && lc == 3 && ht == 0) TS(38);
        }
      }
      if (layer == 0 && p.stop > 3) {
        const int c1 = role_id();
        stats_publish(sb, 1, role_rb(c1), role_hg(c1), opaque_tid() - 256, part_tag(lds32(sb + SM_EP), 2));
        delay<D_ST>();
        stats_gather(sb, role_rb(c1), opaque_tid() - 256, part_tag(lds32(sb + SM_EP), 2));
        if (ht == 0) TS(25);
        halo_receive(sb, 1, role_rb(c1), role_hg(c1), opaque_tid() - 256);
      }
    }
  } else {
    asm volatile("setmaxnreg.dec.sync.aligned.u32 %0;" ::"n"(512 - 2 * R_CONS - R_HELP));
    const int cta = role_id(), rb = role_rb(cta), hg = role_hg(cta), rb2 = role_rb2(cta), q2 = role_q2(cta);
    bar_sync(0, NTHREADS);
    if (warp != 12) {
      mbar_wait(bar + 8 * B_EP, 0);
      const uint32_t tag = lds32(sb + SM_EP) % 7 + 1;
      mbar_wait(bar + 8 * B_CW, 0);
      colsum_publish(sb, rb, hg, tid - 416, tag);
      if (tid == 416) TS(50);
      delay<D_CS>();
      colsum_gather(sb, hg, tid - 416, tag);
      __syncwarp();
      if (tid == 416) TS(55);
    }
    if (elect_one()) mbar_arrive(bar + 8 * B_CSF);
    if (warp == 12) {
      if (elect_one()) {
        unsigned epoch = 0;
#pragma unroll 1
        for (int layer = 0; layer < 2; layer++) {
          auto ld_w = [&](int c, int slot) {
            const uint32_t b = bar + 8 * (B_KVF + c);
            mbar_expect(b, 24576);
            tma_ld3(sb + SM_W + slot * 24576, &p.mapW3, hg * 64, c * 64, 0, b);
          };
          if (layer == 0) {
            mbar_wait(bar + 8 * (B_KVF + 2), 0);
            if (rb2 < 4) tma_prefetch2(&p.mapWo128, q2 * 64, rb2 * 128);
            asm volatile("prefetch.tensormap [%0];" ::"l"(&p.mapO) : "memory");
            asm volatile("prefetch.tensormap [%0];" ::"l"(&p.mapO128) : "memory");
            asm volatile("prefetch.tensormap [%0];" ::"l"(&p.mapXT) : "memory");
            asm volatile("prefetch.tensormap [%0];" ::"l"(&p.mapXT3) : "memory");
            mbar_wait(bar + 8 * B_EP, 0);
            epoch = lds32(sb + SM_EP);
          } else {
            mbar_wait(bar + 8 * B_PDONE, 0);
            ld_w(0, 0); ld_w(1, 1);
            mbar_wait(bar + 8 * (W2_LATE ? B_U : B_RE), 0);
            ld_w(2, 2);
          }
          {
            int slot = 0;
#pragma unroll 1
            for (int c = 3; c < 8; c++) {
              mbar_wait(bar + 8 * (B_KVE + c - 3), layer);
              ld_w(c, slot);
              slot = slot == 2 ? 0 : slot + 1;
            }
          }
          if (p.stop <= 1 + 3 * layer) return;
          mbar_wait(bar + 8 * B_QDONE, layer);
          mbar_wait(bar + 8 * B_HF, layer);
#pragma unroll 1
          for (int c = 0; c < 4; c++) {
            const uint32_t b = bar + 8 * (B_WOF + c);
            mbar_expect(b, 16384);
            tma_ld(sb + SM_WO + c * 16384, &p.mapWo128, q2 * 64, c * 128, b);
          }
          {
            const uint32_t b = bar + 8 * B_RF;
            mbar_expect(b, 16384);
            if (layer == 0) tma_ld(sb + SM_R, &p.mapX128, (rb2 >> 3) * DM + q2 * 64, (rb2 & 7) * 128, b);
            else tma_ld3(sb + SM_R, &p.mapXT3, 0, DM + q2 * 64, rb2 * 2, b);
          }
          spin_until(&g_cnt[(C_O + rb2) * 32], (2 * epoch + layer + 1) * 16);
          fence_async_global();
#pragma unroll 1
          for (int c = 0; c < 8; c++) {
            const uint32_t b = bar + 8 * (B_OF + c);
            if (c == 4) { mbar_wait(bar + 8 * B_OST, layer); fence_async_smem(); }
            mbar_expect(b, 16384);
            tma_ld(sb + sm_o(c), &p.mapO128, c * 64, rb2 * 128, b);
          }
          if (p.stop <= 3 + 3 * layer) return;
        }
      }
    } else if (warp == 13) {
      if (elect_one() && p.stop > 3) {
        mbar_wait(bar + 8 * B_GB, 0);
        const unsigned target = (lds32(sb + SM_EP) + 1) * NCTA;
        auto ld_x = [&](int c) {
          mbar_expect(bar + 8 * (B_XF + c), 16384);
          tma_ld3(sb + SM_X + c * 16384, &p.mapXT3, 0, DM + c * 64, rb * 2, bar + 8 * (B_XF + c));
        };
        int done = 0, it = 0;
        while (done < 4) {
          const uint4 v = ld_tagged((const uint4*)&g_cnt[C_G1 * 32]);
          const int n = (int)(v.x - target) < 0 ? 0 : (int)(v.y - target) < 0 ? 1 : (int)(v.z - target) < 0 ? 2 : (int)(v.w - target) < 0 ? 3 : 4;
          if (++it > (1 << 23)) __trap();
          if (n == done) continue;
          if (n == 4) TS(44);
          fence_async_global();
          fence_async_smem();
          const int first = n == 4 && done > 1 ? 6 + (hg >> 2) : -1;
          if (first >= 0) ld_x(first);
#pragma unroll 1
          for (int c = 2 * done; c < 2 * n; c++)
            if (c != first) ld_x(c);
          done = n;
        }
      }
    } else if (warp == 15) {
      mbar_wait(bar + 8 * B_EP, 0);
      const unsigned epoch = lds32(sb + SM_EP);
#pragma unroll 1
      for (int layer = 0; layer < 2; layer++) {
#pragma unroll 1
        for (int i = 0; i < 6; i++) {
          mbar_wait(bar + 8 * (B_KVF + (FILL_AT + i < 7 ? FILL_AT + i : 7)), layer);
          uint4* dst = (uint4*)(g_xT + (size_t)(i < 4 ? 2 * layer * DM + cv_chan(cta, i) : 3 * DM + cv_chan(cta, 2 * layer + i - 4)) * LSEQ) + lane;
#pragma unroll
          for (int k = 0; k < 8; k++) dst[32 * k] = make_uint4(~0u, ~0u, ~0u, ~0u);
        }
        if (lane < 8) ((uint4*)g_stats)[layer * 1024 + cta * 8 + lane] = make_uint4(0, 0, 0, 0);
        __syncwarp();
        if (elect_one()) {
          red_release(&g_cnt[C_CS * 32 + layer]);
          spin_until(&g_cnt[C_CS * 32 + layer], (epoch + 1) * NCTA);
          mbar_arrive(bar + 8 * B_ZF);
          if (layer == 0 && p.stop > 2) {
#pragma unroll 1
            for (int lc = 0; lc < 4; lc++) {
              mbar_wait(bar + 8 * (B_E + lc), 0);
              fence_reader();
              bulk_st(g_xT + (size_t)(DM + cv_chan(cta, lc)) * LSEQ, sb + cv_s(lc), 4096);
              bulk_commit();
              bulk_wait_all();
              red_relaxed(&g_cnt[C_G1 * 32 + lc]);
              if (lc == 3) TS(18);
            }
          }
        }
        __syncwarp();
        if (p.stop <= 3) return;
      }
    } else if (warp == 14) {
      mbar_wait(bar + 8 * B_EP, 0);
      const unsigned epoch = lds32(sb + SM_EP);
#pragma unroll 1
      for (int layer = 0; layer < 2; layer++) {
        if (p.stop <= 1 + 3 * layer) return;
        mbar_wait(bar + 8 * B_ZF, layer);
        mbar_wait(bar + 8 * (EXP_LATE ? B_PS : B_PDONE), layer);
        delay<D_PST>();
        proj_stats(layer, rb2, q2, lane, part_tag(epoch, 2 * layer + 1));
        if (layer == 1 && lane == 0) TS(5);
        delay<D_PREP>();
        if (lane == 0) mbar_arrive(bar + 8 * B_GB);
      }
    }
  }
}

typedef CUresult (*EncodeFn)(CUtensorMap*, CUtensorMapDataType, cuuint32_t, void*, const cuuint64_t*, const cuuint64_t*,
                             const cuuint32_t*, const cuuint32_t*, CUtensorMapInterleave, CUtensorMapSwizzle,
                             CUtensorMapL2promotion, CUtensorMapFloatOOBfill);

static void make_map(EncodeFn enc, CUtensorMap* m, void* ptr, uint64_t cols, uint64_t rows, uint32_t box_rows) {
  cuuint64_t dims[2] = {cols, rows};
  cuuint64_t strides[1] = {cols * 2};
  cuuint32_t box[2] = {64, box_rows};
  cuuint32_t es[2] = {1, 1};
  enc(m, CU_TENSOR_MAP_DATA_TYPE_BFLOAT16, 2, ptr, dims, strides, box, es, CU_TENSOR_MAP_INTERLEAVE_NONE,
      CU_TENSOR_MAP_SWIZZLE_128B, CU_TENSOR_MAP_L2_PROMOTION_L2_128B, CU_TENSOR_MAP_FLOAT_OOB_FILL_NONE);
}
static void make_map3(EncodeFn enc, CUtensorMap* m, void* ptr, uint64_t d0, uint64_t cols, uint64_t rows, uint64_t blk_stride,
                      uint64_t nblocks, uint32_t nblk, uint32_t box_rows = 64) {
  cuuint64_t dims[3] = {d0, rows, nblocks};
  cuuint64_t strides[2] = {cols * 2, blk_stride * 2};
  cuuint32_t box[3] = {64, box_rows, nblk};
  cuuint32_t es[3] = {1, 1, 1};
  enc(m, CU_TENSOR_MAP_DATA_TYPE_BFLOAT16, 3, ptr, dims, strides, box, es, CU_TENSOR_MAP_INTERLEAVE_NONE,
      CU_TENSOR_MAP_SWIZZLE_128B, CU_TENSOR_MAP_L2_PROMOTION_L2_128B, CU_TENSOR_MAP_FLOAT_OOB_FILL_NONE);
}

extern "C" void kernel_launch(void* const* d_in, const int* in_sizes, int n_in, void* d_out, int out_size) {
  static Params prm;
  static void* cached[13] = {nullptr};
  static bool attr_done = false;
  bool same = attr_done && cached[12] == d_out;
  for (int i = 0; i < 12 && same; i++) same = cached[i] == d_in[i];
  if (!same) {
    void* fn = nullptr;
    cudaDriverEntryPointQueryResult qr;
    cudaGetDriverEntryPoint("cuTensorMapEncodeTiled", &fn, cudaEnableDefault, &qr);
    EncodeFn enc = (EncodeFn)fn;
    void *pO, *pXT;
    cudaGetSymbolAddress(&pO, g_O);
    cudaGetSymbolAddress(&pXT, g_xT);
    make_map(enc, &prm.mapO, pO, DM, LSEQ, 64);
    make_map(enc, &prm.mapXT, pXT, LSEQ, 4 * DM, 64);
    prm.out = (bf16*)d_out;
    make_map(enc, &prm.mapX128, d_in[0], 2 * DM, LSEQ / 2, 128);
    make_map(enc, &prm.mapWo128, d_in[2], DM, DM, 128);
    make_map(enc, &prm.mapO128, pO, DM, LSEQ, 128);
    make_map3(enc, &prm.mapW3, d_in[1], DM, 3 * DM, DM, DM, 3, 3);
    make_map3(enc, &prm.mapW3h, d_in[1], DM, 3 * DM, DM, DM, 3, 3, 32);
    make_map3(enc, &prm.mapXT3, pXT, 64, LSEQ, 4 * DM, 64, 32, 2);
    prm.a_re = (const bf16*)d_in[4]; prm.a_im = (const bf16*)d_in[5];
    prm.b_re = (const bf16*)d_in[6]; prm.b_im = (const bf16*)d_in[7];
    prm.c_re = (const bf16*)d_in[8]; prm.c_im = (const bf16*)d_in[9];
    prm.log_dt = (const bf16*)d_in[10]; prm.dskip = (const bf16*)d_in[11];
    cudaFuncSetAttribute(fused_kernel, cudaFuncAttributeMaxDynamicSharedMemorySize, SM_TOTAL);
    for (int i = 0; i < 12; i++) cached[i] = d_in[i];
    cached[12] = d_out;
    attr_done = true;
  }
  prm.stop = 100;
    fused_kernel<<<NCTA, NTHREADS, SM_TOTAL>>>(prm);
}
```

```cpp
#include <cuda_runtime.h>
#include <cuda_bf16.h>
#include <cuda.h>
#include <stdint.h>

typedef __nv_bfloat16 bf16;

constexpr int LSEQ = 2048;
constexpr int DM = 512;
constexpr int NCTA = 128;
constexpr int NTHREADS = 512;
#define RR 0
#define KG_PRE 2
#define W2_LATE 1
#define FILL_AT 2
#define EXP_LATE 1
#define RFENCE 1
#define D_FIN 550
#define D_PREP 500
#define D_PST 0
#define D_HALO 500
#define STAG 2
#define D_ST 0
#define TLAYER 1
#define KG_PD 1
#define SUM_F32 0
#define CS_LATE0 1
#define D_HALO1 0
#define KG_START 0
#define G_WAIT 0
#define S_OWN 0
#define HALO_W14 1
#define D_START 200
#define D_CS 300
#define D_ST0 400
#define KG_LAST 0
#define X_JIT 0
#define KG_GATE 2
#define R_CONS 192
#define R_HELP 88

constexpr int SM_X = 0;
constexpr int SM_W = 131072;
constexpr int SM_KVX = SM_X;
constexpr int SM_OST = SM_X + 32768;
constexpr int SM_WO = SM_X + 65536;
__host__ __device__ constexpr int sm_o(int c) { return c < 4 ? SM_W + c * 16384 : SM_X + (c - 4) * 16384; }
constexpr int SM_R = 196608;
constexpr int SM_T = 212992;
constexpr int SM_KC = 217088;
constexpr int KC_STRIDE = 648;
constexpr int SM_CS = SM_KC + 4 * KC_STRIDE * 2;
constexpr int SM_CW = SM_R + 8192;
constexpr int SM_EP = SM_CS + 768;
constexpr int SM_BAR = SM_EP + 16;
constexpr int SM_T2 = SM_BAR + 896;
constexpr int SM_HALO = SM_T2 + 4096;
constexpr int SM_ST = SM_HALO + 3072;
constexpr int SM_TOTAL = SM_HALO + 4096;
static_assert(SM_TOTAL <= 232448, "shared memory");

constexpr int CV_UH = 140 * 16;
constexpr int CV_PECH = 1120 * 4;
constexpr int CV_PBW = 2112 * 2;
__host__ __device__ constexpr int cv_s(int lc) { return SM_X + lc * 32768; }
__host__ __device__ constexpr int cv_u(int lc) { return cv_s(lc) + 4096; }
__host__ __device__ constexpr int cv_pe(int lc) { return cv_u(lc) + 2 * CV_UH; }
__host__ __device__ constexpr int cv_pb(int lc) { return cv_pe(lc) + CV_PECH; }
__host__ __device__ constexpr int cv_ft(int lc) { return cv_pb(lc) + 4 * CV_PBW; }
static_assert(cv_ft(0) + 1024 <= 32768, "conv buffers");
__host__ __device__ constexpr int cv_chan(int cta, int lc) { return cta + 128 * lc; }

enum {
  B_XF = 0,
  B_KVF = 8,
  B_OF = 16,
  B_WOF = 24,
  B_T = 31,
  B_RF = 28,
  B_RE = 29,
  B_CW = 30,
  B_GB = 35,
  B_EP = 36,
  B_ZF = 37,
  B_SD = 38,
  B_KVE = 40,
  B_AD = 45,
  B_OST = 46,
  B_QDONE = 47,
  B_PDONE = 48,
  B_S = 50,
  B_E = 54,
  B_P = 58,
  B_PE = 62,
  B_STF = 63,
  B_CSF = 64,
  B_HF = 65,
  B_U = 70,
  B_PS = 74,
  B_COUNT = 80
};

enum {
  C_CS = 0,
  C_G1 = 2,
  C_O = 4,
  C_COUNT = 20
};

__device__ __align__(128) unsigned g_cnt[C_COUNT * 32];
__device__ __align__(1024) bf16 g_O[LSEQ * DM];
__device__ __align__(1024) bf16 g_xT[4 * DM * LSEQ];
__device__ __align__(1024) float g_stats[2 * LSEQ * 2];
__device__ __align__(1024) uint4 g_colsum[8 * 16 * 48];
__device__ __align__(1024) uint4 g_halo[16 * 8 * 192];
__device__ __align__(1024) uint2 g_part[16 * 8 * 128];
#define TS(i) do { } while (0)

#define ATS(i, th) do { } while (0)
#define KTS(i) do { if (ht == 0) TS(i); } while (0)
#define FTS(i) do { } while (0)
#define LTS(i) do { } while (0)

struct Params {
  CUtensorMap mapO, mapXT, mapX128, mapWo128, mapO128, mapW3, mapW3h, mapXT3;
  const bf16 *a_re, *a_im, *b_re, *b_im, *c_re, *c_im, *log_dt, *dskip;
  bf16* out;
  int stop;
};

__device__ __forceinline__ uint32_t s32(const void* p) { return (uint32_t)__cvta_generic_to_shared(p); }
__device__ __forceinline__ void mbar_init(uint32_t b, int c) { asm volatile("mbarrier.init.shared::cta.b64 [%0], %1;" ::"r"(b), "r"(c) : "memory"); }
__device__ __forceinline__ void mbar_expect(uint32_t b, int bytes) { asm volatile("mbarrier.arrive.expect_tx.shared::cta.b64 _, [%0], %1;" ::"r"(b), "r"(bytes) : "memory"); }
__device__ __forceinline__ void mbar_arrive(uint32_t b) { asm volatile("mbarrier.arrive.shared::cta.b64 _, [%0];" ::"r"(b) : "memory"); }
__device__ __forceinline__ void mbar_arrive_if(uint32_t b, bool c) {
  asm volatile("{\n.reg .pred p;\nsetp.ne.u32 p, %1, 0;\n@p mbarrier.arrive.shared::cta.b64 _, [%0];\n}" ::"r"(b), "r"((uint32_t)c) : "memory");
}
__device__ __forceinline__ void mbar_wait(uint32_t b, int parity) {
  asm volatile("{\n.reg .pred p;\nWAIT_LOOP:\nmbarrier.try_wait.parity.shared::cta.b64 p, [%0], %1;\n@p bra WAIT_DONE;\nbra WAIT_LOOP;\nWAIT_DONE:\n}" ::"r"(b), "r"(parity) : "memory");
}
template <int N> __device__ __forceinline__ void delay() {
  if constexpr (N > 0) {
    uint32_t t0, t;
    asm volatile("mov.u32 %0, %%clock;" : "=r"(t0));
    do { asm volatile("mov.u32 %0, %%clock;" : "=r"(t)); } while (t - t0 < N);
  }
}
__device__ __forceinline__ int opaque_tid() { int v; asm volatile("mov.u32 %0, %%tid.x;" : "=r"(v)); return v; }
__device__ __forceinline__ bool elect_one() {
  uint32_t r;
  asm volatile("{\n.reg .pred p;\nelect.sync _|p, 0xffffffff;\nselp.u32 %0, 1, 0, p;\n}" : "=r"(r));
  return r != 0;
}
__device__ __forceinline__ void tma_ld(uint32_t dst, const CUtensorMap* m, int c0, int c1, uint32_t bar) {
  asm volatile("cp.async.bulk.tensor.2d.shared::cluster.global.mbarrier::complete_tx::bytes [%0], [%1, {%3, %4}], [%2];"
               ::"r"(dst), "l"(m), "r"(bar), "r"(c0), "r"(c1) : "memory");
}
__device__ __forceinline__ void tma_ld3(uint32_t dst, const CUtensorMap* m, int c0, int c1, int c2, uint32_t bar) {
  asm volatile("cp.async.bulk.tensor.3d.shared::cluster.global.mbarrier::complete_tx::bytes [%0], [%1, {%3, %4, %5}], [%2];"
               ::"r"(dst), "l"(m), "r"(bar), "r"(c0), "r"(c1), "r"(c2) : "memory");
}
__device__ __forceinline__ void tma_prefetch2(const CUtensorMap* m, int c0, int c1) {
  asm volatile("cp.async.bulk.prefetch.tensor.2d.L2.global.tile [%0, {%1, %2}];" ::"l"(m), "r"(c0), "r"(c1) : "memory");
}
__device__ __forceinline__ void tma_prefetch3(const CUtensorMap* m, int c0, int c1, int c2) {
  asm volatile("cp.async.bulk.prefetch.tensor.3d.L2.global.tile [%0, {%1, %2, %3}];" ::"l"(m), "r"(c0), "r"(c1), "r"(c2) : "memory");
}
__device__ __forceinline__ void tma_st(const CUtensorMap* m, int c0, int c1, uint32_t src) {
  asm volatile("cp.async.bulk.tensor.2d.global.shared::cta.bulk_group [%0, {%2, %3}], [%1];" ::"l"(m), "r"(src), "r"(c0), "r"(c1) : "memory");
}
__device__ __forceinline__ void bulk_ld(uint32_t dst, const void* src, int bytes, uint32_t bar) {
  asm volatile("cp.async.bulk.shared::cluster.global.mbarrier::complete_tx::bytes [%0], [%1], %2, [%3];" ::"r"(dst), "l"(src), "r"(bytes), "r"(bar) : "memory");
}
__device__ __forceinline__ void bulk_st(void* dst, uint32_t src, int bytes) {
  asm volatile("cp.async.bulk.global.shared::cta.bulk_group [%0], [%1], %2;" ::"l"(dst), "r"(src), "r"(bytes) : "memory");
}
__device__ __forceinline__ void bulk_red_add_f32(void* dst, uint32_t src, int bytes) {
  asm volatile("cp.reduce.async.bulk.global.shared::cta.bulk_group.add.f32 [%0], [%1], %2;" ::"l"(dst), "r"(src), "r"(bytes) : "memory");
}
__device__ __forceinline__ void bulk_commit() { asm volatile("cp.async.bulk.commit_group;" ::: "memory"); }
__device__ __forceinline__ void bulk_wait_all() { asm volatile("cp.async.bulk.wait_group 0;" ::: "memory"); }
__device__ __forceinline__ void fence_async_smem() { asm volatile("fence.proxy.async.shared::cta;" ::: "memory"); }
__device__ __forceinline__ void fence_writer() { if (!RFENCE) fence_async_smem(); }
__device__ __forceinline__ void fence_reader() { if (RFENCE) fence_async_smem(); }
__device__ __forceinline__ void fence_async_global() { asm volatile("fence.proxy.async.global;" ::: "memory"); }
__device__ __forceinline__ void bar_sync(int id, int n) { asm volatile("bar.sync %0, %1;" ::"r"(id), "r"(n) : "memory"); }
__device__ __forceinline__ void bar_arrive(int id, int n) { asm volatile("bar.arrive %0, %1;" ::"r"(id), "r"(n) : "memory"); }
__device__ __forceinline__ void wg_fence() { asm volatile("wgmma.fence.sync.aligned;" ::: "memory"); }
__device__ __forceinline__ void wg_commit() { asm volatile("wgmma.commit_group.sync.aligned;" ::: "memory"); }
template <int N> __device__ __forceinline__ void wg_wait() { asm volatile("wgmma.wait_group.sync.aligned %0;" ::"n"(N) : "memory"); }
__device__ __forceinline__ uint64_t mkdesc(uint32_t addr, uint32_t lbo, uint32_t sbo, int sw) {
  return (uint64_t)((addr & 0x3FFFF) >> 4) | ((uint64_t)(lbo >> 4) << 16) | ((uint64_t)(sbo >> 4) << 32) | ((uint64_t)sw << 62);
}
__device__ __forceinline__ void ldsm4(uint32_t* r, uint32_t a) {
  asm volatile("ldmatrix.sync.aligned.m8n8.x4.shared.b16 {%0,%1,%2,%3}, [%4];" : "=r"(r[0]), "=r"(r[1]), "=r"(r[2]), "=r"(r[3]) : "r"(a) : "memory");
}
__device__ __forceinline__ void ldsm4t(uint32_t* r, uint32_t a) {
  asm volatile("ldmatrix.sync.aligned.m8n8.x4.trans.shared.b16 {%0,%1,%2,%3}, [%4];" : "=r"(r[0]), "=r"(r[1]), "=r"(r[2]), "=r"(r[3]) : "r"(a) : "memory");
}
__device__ __forceinline__ void stsm4(uint32_t a, uint32_t r0, uint32_t r1, uint32_t r2, uint32_t r3) {
  asm volatile("stmatrix.sync.aligned.m8n8.x4.shared.b16 [%0], {%1,%2,%3,%4};" ::"r"(a), "r"(r0), "r"(r1), "r"(r2), "r"(r3) : "memory");
}
__device__ __forceinline__ void stsm4t(uint32_t a, uint32_t r0, uint32_t r1, uint32_t r2, uint32_t r3) {
  asm volatile("stmatrix.sync.aligned.m8n8.x4.trans.shared.b16 [%0], {%1,%2,%3,%4};" ::"r"(a), "r"(r0), "r"(r1), "r"(r2), "r"(r3) : "memory");
}
__device__ __forceinline__ uint32_t movm_t(uint32_t a) { uint32_t r; asm volatile("movmatrix.sync.aligned.m8n8.trans.b16 %0, %1;" : "=r"(r) : "r"(a)); return r; }
__device__ __forceinline__ uint32_t lds32(uint32_t a) { uint32_t v; asm volatile("ld.shared.b32 %0, [%1];" : "=r"(v) : "r"(a) : "memory"); return v; }
__device__ __forceinline__ float2 lds64f(uint32_t a) { float2 v; asm volatile("ld.shared.v2.f32 {%0,%1}, [%2];" : "=f"(v.x), "=f"(v.y) : "r"(a) : "memory"); return v; }
__device__ __forceinline__ float4 lds128f(uint32_t a) { float4 v; asm volatile("ld.shared.v4.f32 {%0,%1,%2,%3}, [%4];" : "=f"(v.x), "=f"(v.y), "=f"(v.z), "=f"(v.w) : "r"(a) : "memory"); return v; }
__device__ __forceinline__ uint4 lds128(uint32_t a) { uint4 v; asm volatile("ld.shared.v4.b32 {%0,%1,%2,%3}, [%4];" : "=r"(v.x), "=r"(v.y), "=r"(v.z), "=r"(v.w) : "r"(a) : "memory"); return v; }
__device__ __forceinline__ void sts128(uint32_t a, uint4 v) { asm volatile("st.shared.v4.b32 [%0], {%1,%2,%3,%4};" ::"r"(a), "r"(v.x), "r"(v.y), "r"(v.z), "r"(v.w) : "memory"); }
__device__ __forceinline__ void sts128f(uint32_t a, float x, float y, float z, float w) { asm volatile("st.shared.v4.f32 [%0], {%1,%2,%3,%4};" ::"r"(a), "f"(x), "f"(y), "f"(z), "f"(w) : "memory"); }
__device__ __forceinline__ void sts32f(uint32_t a, float v) { asm volatile("st.shared.f32 [%0], %1;" ::"r"(a), "f"(v) : "memory"); }
__device__ __forceinline__ void sts16(uint32_t a, uint16_t v) { asm volatile("st.shared.u16 [%0], %1;" ::"r"(a), "h"(v) : "memory"); }
__device__ __forceinline__ uint32_t lds16(uint32_t a) { uint16_t v; asm volatile("ld.shared.u16 %0, [%1];" : "=h"(v) : "r"(a) : "memory"); return v; }
__device__ __forceinline__ uint32_t packbf(float lo, float hi) { uint32_t r; asm("cvt.rn.bf16x2.f32 %0, %1, %2;" : "=r"(r) : "f"(hi), "f"(lo)); return r; }
__device__ __forceinline__ float bf_lo(uint32_t v) { return __uint_as_float(v << 16); }
__device__ __forceinline__ float bf_hi(uint32_t v) { return __uint_as_float(v & 0xffff0000u); }
__device__ __forceinline__ float ex2(float x) { float r; asm("ex2.approx.ftz.f32 %0, %1;" : "=f"(r) : "f"(x)); return r; }
__device__ __forceinline__ float rsqrt_approx(float x) { float r; asm("rsqrt.approx.ftz.f32 %0, %1;" : "=f"(r) : "f"(x)); return r; }
__device__ __forceinline__ float rcp_approx(float x) { float r; asm("rcp.approx.ftz.f32 %0, %1;" : "=f"(r) : "f"(x)); return r; }
__device__ __forceinline__ void mma_bf16(float* d, const uint32_t* a, uint32_t b0, uint32_t b1) {
  asm("mma.sync.aligned.m16n8k16.row.col.f32.bf16.bf16.f32 {%0,%1,%2,%3}, {%4,%5,%6,%7}, {%8,%9}, {%0,%1,%2,%3};"
               : "+f"(d[0]), "+f"(d[1]), "+f"(d[2]), "+f"(d[3]) : "r"(a[0]), "r"(a[1]), "r"(a[2]), "r"(a[3]), "r"(b0), "r"(b1));
}
__device__ __forceinline__ void mma_bf16_k8(float* d, uint32_t a0, uint32_t a1, uint32_t b) {
  asm("mma.sync.aligned.m16n8k8.row.col.f32.bf16.bf16.f32 {%0,%1,%2,%3}, {%4,%5}, {%6}, {%0,%1,%2,%3};"
      : "+f"(d[0]), "+f"(d[1]), "+f"(d[2]), "+f"(d[3]) : "r"(a0), "r"(a1), "r"(b));
}
__device__ __forceinline__ void red_release(unsigned* p) { asm volatile("red.release.gpu.global.add.u32 [%0], 1;" ::"l"(p) : "memory"); }
__device__ __forceinline__ void red_relaxed(unsigned* p) { asm volatile("red.relaxed.gpu.global.add.u32 [%0], 1;" ::"l"(p) : "memory"); }
__device__ __forceinline__ unsigned ld_relaxed(const unsigned* p) { unsigned v; asm volatile("ld.relaxed.gpu.global.u32 %0, [%1];" : "=r"(v) : "l"(p) : "memory"); return v; }
__device__ __forceinline__ void spin_until(const unsigned* p, unsigned target) {
  int it = 0;
  while ((int)(ld_relaxed(p) - target) < 0) {
    if (++it > (1 << 23)) __trap();
  }
}
__device__ __forceinline__ uint4 ldcg128(const void* p) { uint4 v; asm volatile("ld.global.cg.v4.b32 {%0,%1,%2,%3}, [%4];" : "=r"(v.x), "=r"(v.y), "=r"(v.z), "=r"(v.w) : "l"(p) : "memory"); return v; }
__device__ __forceinline__ uint4 ld_tagged(const uint4* p) { uint4 v; asm volatile("ld.relaxed.gpu.global.v4.u32 {%0,%1,%2,%3}, [%4];" : "=r"(v.x), "=r"(v.y), "=r"(v.z), "=r"(v.w) : "l"(p) : "memory"); return v; }
__device__ __forceinline__ uint2 ld_part(const uint2* p) { uint2 v; asm volatile("ld.relaxed.gpu.global.v2.u32 {%0,%1}, [%2];" : "=r"(v.x), "=r"(v.y) : "l"(p) : "memory"); return v; }
__device__ __forceinline__ void st_part(uint2* p, float s, float q, uint32_t tag) {
  asm volatile("st.relaxed.gpu.global.v2.u32 [%0], {%1,%2};" ::"l"(p), "r"(__float_as_uint(s)), "r"((__float_as_uint(q) & ~7u) | tag) : "memory");
}
__device__ __forceinline__ uint32_t part_tag(uint32_t epoch, int k) { return (4 * (epoch % 7) + k) % 7 + 1; }
__device__ __forceinline__ void st_tagged3(uint4* p, uint32_t a, uint32_t b, uint32_t c, uint32_t tag) { asm volatile("st.relaxed.gpu.global.v4.u32 [%0], {%1,%2,%3,%4};" ::"l"(p), "r"(a), "r"(b), "r"(c), "r"(tag) : "memory"); }
__device__ __forceinline__ uint32_t hadd2(uint32_t a, uint32_t b) { uint32_t r; asm("add.rn.bf16x2 %0, %1, %2;" : "=r"(r) : "r"(a), "r"(b)); return r; }
__device__ __forceinline__ uint32_t hmul2(uint32_t a, uint32_t b) { uint32_t r; asm("mul.rn.bf16x2 %0, %1, %2;" : "=r"(r) : "r"(a), "r"(b)); return r; }

template<int N,int TB> __device__ __forceinline__ void wgmma_rs(float* d, const uint32_t* a, uint64_t db, int sd);
template<int N,int TA,int TB> __device__ __forceinline__ void wgmma_ss(float* d, uint64_t da, uint64_t db, int sd);
template<> __device__ __forceinline__ void wgmma_rs<128,0>(float* d, const uint32_t* a, uint64_t db, int sd) {
  asm volatile("{\n.reg .pred p;\nsetp.ne.b32 p, %69, 0;\nwgmma.mma_async.sync.aligned.m64n128k16.f32.bf16.bf16 {%0,%1,%2,%3,%4,%5,%6,%7,%8,%9,%10,%11,%12,%13,%14,%15,%16,%17,%18,%19,%20,%21,%22,%23,%24,%25,%26,%27,%28,%29,%30,%31,%32,%33,%34,%35,%36,%37,%38,%39,%40,%41,%42,%43,%44,%45,%46,%47,%48,%49,%50,%51,%52,%53,%54,%55,%56,%57,%58,%59,%60,%61,%62,%63}, {%64,%65,%66,%67}, %68, p, 1, 1, 0;\n}\n"
   : "+f"(d[0]),"+f"(d[1]),"+f"(d[2]),"+f"(d[3]),"+f"(d[4]),"+f"(d[5]),"+f"(d[6]),"+f"(d[7]),"+f"(d[8]),"+f"(d[9]),"+f"(d[10]),"+f"(d[11]),"+f"(d[12]),"+f"(d[13]),"+f"(d[14]),"+f"(d[15]),"+f"(d[16]),"+f"(d[17]),"+f"(d[18]),"+f"(d[19]),"+f"(d[20]),"+f"(d[21]),"+f"(d[22]),"+f"(d[23]),"+f"(d[24]),"+f"(d[25]),"+f"(d[26]),"+f"(d[27]),"+f"(d[28]),"+f"(d[29]),"+f"(d[30]),"+f"(d[31]),"+f"(d[32]),"+f"(d[33]),"+f"(d[34]),"+f"(d[35]),"+f"(d[36]),"+f"(d[37]),"+f"(d[38]),"+f"(d[39]),"+f"(d[40]),"+f"(d[41]),"+f"(d[42]),"+f"(d[43]),"+f"(d[44]),"+f"(d[45]),"+f"(d[46]),"+f"(d[47]),"+f"(d[48]),"+f"(d[49]),"+f"(d[50]),"+f"(d[51]),"+f"(d[52]),"+f"(d[53]),"+f"(d[54]),"+f"(d[55]),"+f"(d[56]),"+f"(d[57]),"+f"(d[58]),"+f"(d[59]),"+f"(d[60]),"+f"(d[61]),"+f"(d[62]),"+f"(d[63])
   : "r"(a[0]), "r"(a[1]), "r"(a[2]), "r"(a[3]), "l"(db), "r"(sd));
}
template<> __device__ __forceinline__ void wgmma_rs<120,0>(float* d, const uint32_t* a, uint64_t db, int sd) {
  asm volatile("{\n.reg .pred p;\nsetp.ne.b32 p, %65, 0;\nwgmma.mma_async.sync.aligned.m64n120k16.f32.bf16.bf16 {%0,%1,%2,%3,%4,%5,%6,%7,%8,%9,%10,%11,%12,%13,%14,%15,%16,%17,%18,%19,%20,%21,%22,%23,%24,%25,%26,%27,%28,%29,%30,%31,%32,%33,%34,%35,%36,%37,%38,%39,%40,%41,%42,%43,%44,%45,%46,%47,%48,%49,%50,%51,%52,%53,%54,%55,%56,%57,%58,%59}, {%60,%61,%62,%63}, %64, p, 1, 1, 0;\n}\n"
   : "+f"(d[0]),"+f"(d[1]),"+f"(d[2]),"+f"(d[3]),"+f"(d[4]),"+f"(d[5]),"+f"(d[6]),"+f"(d[7]),"+f"(d[8]),"+f"(d[9]),"+f"(d[10]),"+f"(d[11]),"+f"(d[12]),"+f"(d[13]),"+f"(d[14]),"+f"(d[15]),"+f"(d[16]),"+f"(d[17]),"+f"(d[18]),"+f"(d[19]),"+f"(d[20]),"+f"(d[21]),"+f"(d[22]),"+f"(d[23]),"+f"(d[24]),"+f"(d[25]),"+f"(d[26]),"+f"(d[27]),"+f"(d[28]),"+f"(d[29]),"+f"(d[30]),"+f"(d[31]),"+f"(d[32]),"+f"(d[33]),"+f"(d[34]),"+f"(d[35]),"+f"(d[36]),"+f"(d[37]),"+f"(d[38]),"+f"(d[39]),"+f"(d[40]),"+f"(d[41]),"+f"(d[42]),"+f"(d[43]),"+f"(d[44]),"+f"(d[45]),"+f"(d[46]),"+f"(d[47]),"+f"(d[48]),"+f"(d[49]),"+f"(d[50]),"+f"(d[51]),"+f"(d[52]),"+f"(d[53]),"+f"(d[54]),"+f"(d[55]),"+f"(d[56]),"+f"(d[57]),"+f"(d[58]),"+f"(d[59])
   : "r"(a[0]), "r"(a[1]), "r"(a[2]), "r"(a[3]), "l"(db), "r"(sd));
}
template<> __device__ __forceinline__ void wgmma_rs<112,0>(float* d, const uint32_t* a, uint64_t db, int sd) {
  asm volatile("{\n.reg .pred p;\nsetp.ne.b32 p, %61, 0;\nwgmma.mma_async.sync.aligned.m64n112k16.f32.bf16.bf16 {%0,%1,%2,%3,%4,%5,%6,%7,%8,%9,%10,%11,%12,%13,%14,%15,%16,%17,%18,%19,%20,%21,%22,%23,%24,%25,%26,%27,%28,%29,%30,%31,%32,%33,%34,%35,%36,%37,%38,%39,%40,%41,%42,%43,%44,%45,%46,%47,%48,%49,%50,%51,%52,%53,%54,%55}, {%56,%57,%58,%59}, %60, p, 1, 1, 0;\n}\n"
   : "+f"(d[0]),"+f"(d[1]),"+f"(d[2]),"+f"(d[3]),"+f"(d[4]),"+f"(d[5]),"+f"(d[6]),"+f"(d[7]),"+f"(d[8]),"+f"(d[9]),"+f"(d[10]),"+f"(d[11]),"+f"(d[12]),"+f"(d[13]),"+f"(d[14]),"+f"(d[15]),"+f"(d[16]),"+f"(d[17]),"+f"(d[18]),"+f"(d[19]),"+f"(d[20]),"+f"(d[21]),"+f"(d[22]),"+f"(d[23]),"+f"(d[24]),"+f"(d[25]),"+f"(d[26]),"+f"(d[27]),"+f"(d[28]),"+f"(d[29]),"+f"(d[30]),"+f"(d[31]),"+f"(d[32]),"+f"(d[33]),"+f"(d[34]),"+f"(d[35]),"+f"(d[36]),"+f"(d[37]),"+f"(d[38]),"+f"(d[39]),"+f"(d[40]),"+f"(d[41]),"+f"(d[42]),"+f"(d[43]),"+f"(d[44]),"+f"(d[45]),"+f"(d[46]),"+f"(d[47]),"+f"(d[48]),"+f"(d[49]),"+f"(d[50]),"+f"(d[51]),"+f"(d[52]),"+f"(d[53]),"+f"(d[54]),"+f"(d[55])
   : "r"(a[0]), "r"(a[1]), "r"(a[2]), "r"(a[3]), "l"(db), "r"(sd));
}
template<> __device__ __forceinline__ void wgmma_rs<104,0>(float* d, const uint32_t* a, uint64_t db, int sd) {
  asm volatile("{\n.reg .pred p;\nsetp.ne.b32 p, %57, 0;\nwgmma.mma_async.sync.aligned.m64n104k16.f32.bf16.bf16 {%0,%1,%2,%3,%4,%5,%6,%7,%8,%9,%10,%11,%12,%13,%14,%15,%16,%17,%18,%19,%20,%21,%22,%23,%24,%25,%26,%27,%28,%29,%30,%31,%32,%33,%34,%35,%36,%37,%38,%39,%40,%41,%42,%43,%44,%45,%46,%47,%48,%49,%50,%51}, {%52,%53,%54,%55}, %56, p, 1, 1, 0;\n}\n"
   : "+f"(d[0]),"+f"(d[1]),"+f"(d[2]),"+f"(d[3]),"+f"(d[4]),"+f"(d[5]),"+f"(d[6]),"+f"(d[7]),"+f"(d[8]),"+f"(d[9]),"+f"(d[10]),"+f"(d[11]),"+f"(d[12]),"+f"(d[13]),"+f"(d[14]),"+f"(d[15]),"+f"(d[16]),"+f"(d[17]),"+f"(d[18]),"+f"(d[19]),"+f"(d[20]),"+f"(d[21]),"+f"(d[22]),"+f"(d[23]),"+f"(d[24]),"+f"(d[25]),"+f"(d[26]),"+f"(d[27]),"+f"(d[28]),"+f"(d[29]),"+f"(d[30]),"+f"(d[31]),"+f"(d[32]),"+f"(d[33]),"+f"(d[34]),"+f"(d[35]),"+f"(d[36]),"+f"(d[37]),"+f"(d[38]),"+f"(d[39]),"+f"(d[40]),"+f"(d[41]),"+f"(d[42]),"+f"(d[43]),"+f"(d[44]),"+f"(d[45]),"+f"(d[46]),"+f"(d[47]),"+f"(d[48]),"+f"(d[49]),"+f"(d[50]),"+f"(d[51])
   : "r"(a[0]), "r"(a[1]), "r"(a[2]), "r"(a[3]), "l"(db), "r"(sd));
}
template<> __device__ __forceinline__ void wgmma_rs<96,0>(float* d, const uint32_t* a, uint64_t db, int sd) {
  asm volatile("{\n.reg .pred p;\nsetp.ne.b32 p, %53, 0;\nwgmma.mma_async.sync.aligned.m64n96k16.f32.bf16.bf16 {%0,%1,%2,%3,%4,%5,%6,%7,%8,%9,%10,%11,%12,%13,%14,%15,%16,%17,%18,%19,%20,%21,%22,%23,%24,%25,%26,%27,%28,%29,%30,%31,%32,%33,%34,%35,%36,%37,%38,%39,%40,%41,%42,%43,%44,%45,%46,%47}, {%48,%49,%50,%51}, %52, p, 1, 1, 0;\n}\n"
   : "+f"(d[0]),"+f"(d[1]),"+f"(d[2]),"+f"(d[3]),"+f"(d[4]),"+f"(d[5]),"+f"(d[6]),"+f"(d[7]),"+f"(d[8]),"+f"(d[9]),"+f"(d[10]),"+f"(d[11]),"+f"(d[12]),"+f"(d[13]),"+f"(d[14]),"+f"(d[15]),"+f"(d[16]),"+f"(d[17]),"+f"(d[18]),"+f"(d[19]),"+f"(d[20]),"+f"(d[21]),"+f"(d[22]),"+f"(d[23]),"+f"(d[24]),"+f"(d[25]),"+f"(d[26]),"+f"(d[27]),"+f"(d[28]),"+f"(d[29]),"+f"(d[30]),"+f"(d[31]),"+f"(d[32]),"+f"(d[33]),"+f"(d[34]),"+f"(d[35]),"+f"(d[36]),"+f"(d[37]),"+f"(d[38]),"+f"(d[39]),"+f"(d[40]),"+f"(d[41]),"+f"(d[42]),"+f"(d[43]),"+f"(d[44]),"+f"(d[45]),"+f"(d[46]),"+f"(d[47])
   : "r"(a[0]), "r"(a[1]), "r"(a[2]), "r"(a[3]), "l"(db), "r"(sd));
}
template<> __device__ __forceinline__ void wgmma_rs<88,0>(float* d, const uint32_t* a, uint64_t db, int sd) {
  asm volatile("{\n.reg .pred p;\nsetp.ne.b32 p, %49, 0;\nwgmma.mma_async.sync.aligned.m64n88k16.f32.bf16.bf16 {%0,%1,%2,%3,%4,%5,%6,%7,%8,%9,%10,%11,%12,%13,%14,%15,%16,%17,%18,%19,%20,%21,%22,%23,%24,%25,%26,%27,%28,%29,%30,%31,%32,%33,%34,%35,%36,%37,%38,%39,%40,%41,%42,%43}, {%44,%45,%46,%47}, %48, p, 1, 1, 0;\n}\n"
   : "+f"(d[0]),"+f"(d[1]),"+f"(d[2]),"+f"(d[3]),"+f"(d[4]),"+f"(d[5]),"+f"(d[6]),"+f"(d[7]),"+f"(d[8]),"+f"(d[9]),"+f"(d[10]),"+f"(d[11]),"+f"(d[12]),"+f"(d[13]),"+f"(d[14]),"+f"(d[15]),"+f"(d[16]),"+f"(d[17]),"+f"(d[18]),"+f"(d[19]),"+f"(d[20]),"+f"(d[21]),"+f"(d[22]),"+f"(d[23]),"+f"(d[24]),"+f"(d[25]),"+f"(d[26]),"+f"(d[27]),"+f"(d[28]),"+f"(d[29]),"+f"(d[30]),"+f"(d[31]),"+f"(d[32]),"+f"(d[33]),"+f"(d[34]),"+f"(d[35]),"+f"(d[36]),"+f"(d[37]),"+f"(d[38]),"+f"(d[39]),"+f"(d[40]),"+f"(d[41]),"+f"(d[42]),"+f"(d[43])
   : "r"(a[0]), "r"(a[1]), "r"(a[2]), "r"(a[3]), "l"(db), "r"(sd));
}
template<> __device__ __forceinline__ void wgmma_rs<80,0>(float* d, const uint32_t* a, uint64_t db, int sd) {
  asm volatile("{\n.reg .pred p;\nsetp.ne.b32 p, %45, 0;\nwgmma.mma_async.sync.aligned.m64n80k16.f32.bf16.bf16 {%0,%1,%2,%3,%4,%5,%6,%7,%8,%9,%10,%11,%12,%13,%14,%15,%16,%17,%18,%19,%20,%21,%22,%23,%24,%25,%26,%27,%28,%29,%30,%31,%32,%33,%34,%35,%36,%37,%38,%39}, {%40,%41,%42,%43}, %44, p, 1, 1, 0;\n}\n"
   : "+f"(d[0]),"+f"(d[1]),"+f"(d[2]),"+f"(d[3]),"+f"(d[4]),"+f"(d[5]),"+f"(d[6]),"+f"(d[7]),"+f"(d[8]),"+f"(d[9]),"+f"(d[10]),"+f"(d[11]),"+f"(d[12]),"+f"(d[13]),"+f"(d[14]),"+f"(d[15]),"+f"(d[16]),"+f"(d[17]),"+f"(d[18]),"+f"(d[19]),"+f"(d[20]),"+f"(d[21]),"+f"(d[22]),"+f"(d[23]),"+f"(d[24]),"+f"(d[25]),"+f"(d[26]),"+f"(d[27]),"+f"(d[28]),"+f"(d[29]),"+f"(d[30]),"+f"(d[31]),"+f"(d[32]),"+f"(d[33]),"+f"(d[34]),"+f"(d[35]),"+f"(d[36]),"+f"(d[37]),"+f"(d[38]),"+f"(d[39])
   : "r"(a[0]), "r"(a[1]), "r"(a[2]), "r"(a[3]), "l"(db), "r"(sd));
}
template<> __device__ __forceinline__ void wgmma_rs<72,0>(float* d, const uint32_t* a, uint64_t db, int sd) {
  asm volatile("{\n.reg .pred p;\nsetp.ne.b32 p, %41, 0;\nwgmma.mma_async.sync.aligned.m64n72k16.f32.bf16.bf16 {%0,%1,%2,%3,%4,%5,%6,%7,%8,%9,%10,%11,%12,%13,%14,%15,%16,%17,%18,%19,%20,%21,%22,%23,%24,%25,%26,%27,%28,%29,%30,%31,%32,%33,%34,%35}, {%36,%37,%38,%39}, %40, p, 1, 1, 0;\n}\n"
   : "+f"(d[0]),"+f"(d[1]),"+f"(d[2]),"+f"(d[3]),"+f"(d[4]),"+f"(d[5]),"+f"(d[6]),"+f"(d[7]),"+f"(d[8]),"+f"(d[9]),"+f"(d[10]),"+f"(d[11]),"+f"(d[12]),"+f"(d[13]),"+f"(d[14]),"+f"(d[15]),"+f"(d[16]),"+f"(d[17]),"+f"(d[18]),"+f"(d[19]),"+f"(d[20]),"+f"(d[21]),"+f"(d[22]),"+f"(d[23]),"+f"(d[24]),"+f"(d[25]),"+f"(d[26]),"+f"(d[27]),"+f"(d[28]),"+f"(d[29]),"+f"(d[30]),"+f"(d[31]),"+f"(d[32]),"+f"(d[33]),"+f"(d[34]),"+f"(d[35])
   : "r"(a[0]), "r"(a[1]), "r"(a[2]), "r"(a[3]), "l"(db), "r"(sd));
}
template<> __device__ __forceinline__ void wgmma_rs<64,0>(float* d, const uint32_t* a, uint64_t db, int sd) {
  asm volatile("{\n.reg .pred p;\nsetp.ne.b32 p, %37, 0;\nwgmma.mma_async.sync.aligned.m64n64k16.f32.bf16.bf16 {%0,%1,%2,%3,%4,%5,%6,%7,%8,%9,%10,%11,%12,%13,%14,%15,%16,%17,%18,%19,%20,%21,%22,%23,%24,%25,%26,%27,%28,%29,%30,%31}, {%32,%33,%34,%35}, %36, p, 1, 1, 0;\n}\n"
   : "+f"(d[0]),"+f"(d[1]),"+f"(d[2]),"+f"(d[3]),"+f"(d[4]),"+f"(d[5]),"+f"(d[6]),"+f"(d[7]),"+f"(d[8]),"+f"(d[9]),"+f"(d[10]),"+f"(d[11]),"+f"(d[12]),"+f"(d[13]),"+f"(d[14]),"+f"(d[15]),"+f"(d[16]),"+f"(d[17]),"+f"(d[18]),"+f"(d[19]),"+f"(d[20]),"+f"(d[21]),"+f"(d[22]),"+f"(d[23]),"+f"(d[24]),"+f"(d[25]),"+f"(d[26]),"+f"(d[27]),"+f"(d[28]),"+f"(d[29]),"+f"(d[30]),"+f"(d[31])
   : "r"(a[0]), "r"(a[1]), "r"(a[2]), "r"(a[3]), "l"(db), "r"(sd));
}
template<> __device__ __forceinline__ void wgmma_ss<64,0,1>(float* d, uint64_t da, uint64_t db, int sd) {
  asm volatile("{\n.reg .pred p;\nsetp.ne.b32 p, %34, 0;\nwgmma.mma_async.sync.aligned.m64n64k16.f32.bf16.bf16 {%0,%1,%2,%3,%4,%5,%6,%7,%8,%9,%10,%11,%12,%13,%14,%15,%16,%17,%18,%19,%20,%21,%22,%23,%24,%25,%26,%27,%28,%29,%30,%31}, %32, %33, p, 1, 1, 0, 1;\n}\n"
   : "+f"(d[0]),"+f"(d[1]),"+f"(d[2]),"+f"(d[3]),"+f"(d[4]),"+f"(d[5]),"+f"(d[6]),"+f"(d[7]),"+f"(d[8]),"+f"(d[9]),"+f"(d[10]),"+f"(d[11]),"+f"(d[12]),"+f"(d[13]),"+f"(d[14]),"+f"(d[15]),"+f"(d[16]),"+f"(d[17]),"+f"(d[18]),"+f"(d[19]),"+f"(d[20]),"+f"(d[21]),"+f"(d[22]),"+f"(d[23]),"+f"(d[24]),"+f"(d[25]),"+f"(d[26]),"+f"(d[27]),"+f"(d[28]),"+f"(d[29]),"+f"(d[30]),"+f"(d[31])
   : "l"(da), "l"(db), "r"(sd));
}
template<> __device__ __forceinline__ void wgmma_ss<64,1,1>(float* d, uint64_t da, uint64_t db, int sd) {
  asm volatile("{\n.reg .pred p;\nsetp.ne.b32 p, %34, 0;\nwgmma.mma_async.sync.aligned.m64n64k16.f32.bf16.bf16 {%0,%1,%2,%3,%4,%5,%6,%7,%8,%9,%10,%11,%12,%13,%14,%15,%16,%17,%18,%19,%20,%21,%22,%23,%24,%25,%26,%27,%28,%29,%30,%31}, %32, %33, p, 1, 1, 1, 1;\n}\n"
   : "+f"(d[0]),"+f"(d[1]),"+f"(d[2]),"+f"(d[3]),"+f"(d[4]),"+f"(d[5]),"+f"(d[6]),"+f"(d[7]),"+f"(d[8]),"+f"(d[9]),"+f"(d[10]),"+f"(d[11]),"+f"(d[12]),"+f"(d[13]),"+f"(d[14]),"+f"(d[15]),"+f"(d[16]),"+f"(d[17]),"+f"(d[18]),"+f"(d[19]),"+f"(d[20]),"+f"(d[21]),"+f"(d[22]),"+f"(d[23]),"+f"(d[24]),"+f"(d[25]),"+f"(d[26]),"+f"(d[27]),"+f"(d[28]),"+f"(d[29]),"+f"(d[30]),"+f"(d[31])
   : "l"(da), "l"(db), "r"(sd));
}
template<> __device__ __forceinline__ void wgmma_ss<192,0,1>(float* d, uint64_t da, uint64_t db, int sd) {
  asm volatile("{\n.reg .pred p;\nsetp.ne.b32 p, %98, 0;\nwgmma.mma_async.sync.aligned.m64n192k16.f32.bf16.bf16 {%0,%1,%2,%3,%4,%5,%6,%7,%8,%9,%10,%11,%12,%13,%14,%15,%16,%17,%18,%19,%20,%21,%22,%23,%24,%25,%26,%27,%28,%29,%30,%31,%32,%33,%34,%35,%36,%37,%38,%39,%40,%41,%42,%43,%44,%45,%46,%47,%48,%49,%50,%51,%52,%53,%54,%55,%56,%57,%58,%59,%60,%61,%62,%63,%64,%65,%66,%67,%68,%69,%70,%71,%72,%73,%74,%75,%76,%77,%78,%79,%80,%81,%82,%83,%84,%85,%86,%87,%88,%89,%90,%91,%92,%93,%94,%95}, %96, %97, p, 1, 1, 0, 1;\n}\n"
   : "+f"(d[0]),"+f"(d[1]),"+f"(d[2]),"+f"(d[3]),"+f"(d[4]),"+f"(d[5]),"+f"(d[6]),"+f"(d[7]),"+f"(d[8]),"+f"(d[9]),"+f"(d[10]),"+f"(d[11]),"+f"(d[12]),"+f"(d[13]),"+f"(d[14]),"+f"(d[15]),"+f"(d[16]),"+f"(d[17]),"+f"(d[18]),"+f"(d[19]),"+f"(d[20]),"+f"(d[21]),"+f"(d[22]),"+f"(d[23]),"+f"(d[24]),"+f"(d[25]),"+f"(d[26]),"+f"(d[27]),"+f"(d[28]),"+f"(d[29]),"+f"(d[30]),"+f"(d[31]),"+f"(d[32]),"+f"(d[33]),"+f"(d[34]),"+f"(d[35]),"+f"(d[36]),"+f"(d[37]),"+f"(d[38]),"+f"(d[39]),"+f"(d[40]),"+f"(d[41]),"+f"(d[42]),"+f"(d[43]),"+f"(d[44]),"+f"(d[45]),"+f"(d[46]),"+f"(d[47]),"+f"(d[48]),"+f"(d[49]),"+f"(d[50]),"+f"(d[51]),"+f"(d[52]),"+f"(d[53]),"+f"(d[54]),"+f"(d[55]),"+f"(d[56]),"+f"(d[57]),"+f"(d[58]),"+f"(d[59]),"+f"(d[60]),"+f"(d[61]),"+f"(d[62]),"+f"(d[63]),"+f"(d[64]),"+f"(d[65]),"+f"(d[66]),"+f"(d[67]),"+f"(d[68]),"+f"(d[69]),"+f"(d[70]),"+f"(d[71]),"+f"(d[72]),"+f"(d[73]),"+f"(d[74]),"+f"(d[75]),"+f"(d[76]),"+f"(d[77]),"+f"(d[78]),"+f"(d[79]),"+f"(d[80]),"+f"(d[81]),"+f"(d[82]),"+f"(d[83]),"+f"(d[84]),"+f"(d[85]),"+f"(d[86]),"+f"(d[87]),"+f"(d[88]),"+f"(d[89]),"+f"(d[90]),"+f"(d[91]),"+f"(d[92]),"+f"(d[93]),"+f"(d[94]),"+f"(d[95])
   : "l"(da), "l"(db), "r"(sd));
}
template<> __device__ __forceinline__ void wgmma_ss<192,1,1>(float* d, uint64_t da, uint64_t db, int sd) {
  asm volatile("{\n.reg .pred p;\nsetp.ne.b32 p, %98, 0;\nwgmma.mma_async.sync.aligned.m64n192k16.f32.bf16.bf16 {%0,%1,%2,%3,%4,%5,%6,%7,%8,%9,%10,%11,%12,%13,%14,%15,%16,%17,%18,%19,%20,%21,%22,%23,%24,%25,%26,%27,%28,%29,%30,%31,%32,%33,%34,%35,%36,%37,%38,%39,%40,%41,%42,%43,%44,%45,%46,%47,%48,%49,%50,%51,%52,%53,%54,%55,%56,%57,%58,%59,%60,%61,%62,%63,%64,%65,%66,%67,%68,%69,%70,%71,%72,%73,%74,%75,%76,%77,%78,%79,%80,%81,%82,%83,%84,%85,%86,%87,%88,%89,%90,%91,%92,%93,%94,%95}, %96, %97, p, 1, 1, 1, 1;\n}\n"
   : "+f"(d[0]),"+f"(d[1]),"+f"(d[2]),"+f"(d[3]),"+f"(d[4]),"+f"(d[5]),"+f"(d[6]),"+f"(d[7]),"+f"(d[8]),"+f"(d[9]),"+f"(d[10]),"+f"(d[11]),"+f"(d[12]),"+f"(d[13]),"+f"(d[14]),"+f"(d[15]),"+f"(d[16]),"+f"(d[17]),"+f"(d[18]),"+f"(d[19]),"+f"(d[20]),"+f"(d[21]),"+f"(d[22]),"+f"(d[23]),"+f"(d[24]),"+f"(d[25]),"+f"(d[26]),"+f"(d[27]),"+f"(d[28]),"+f"(d[29]),"+f"(d[30]),"+f"(d[31]),"+f"(d[32]),"+f"(d[33]),"+f"(d[34]),"+f"(d[35]),"+f"(d[36]),"+f"(d[37]),"+f"(d[38]),"+f"(d[39]),"+f"(d[40]),"+f"(d[41]),"+f"(d[42]),"+f"(d[43]),"+f"(d[44]),"+f"(d[45]),"+f"(d[46]),"+f"(d[47]),"+f"(d[48]),"+f"(d[49]),"+f"(d[50]),"+f"(d[51]),"+f"(d[52]),"+f"(d[53]),"+f"(d[54]),"+f"(d[55]),"+f"(d[56]),"+f"(d[57]),"+f"(d[58]),"+f"(d[59]),"+f"(d[60]),"+f"(d[61]),"+f"(d[62]),"+f"(d[63]),"+f"(d[64]),"+f"(d[65]),"+f"(d[66]),"+f"(d[67]),"+f"(d[68]),"+f"(d[69]),"+f"(d[70]),"+f"(d[71]),"+f"(d[72]),"+f"(d[73]),"+f"(d[74]),"+f"(d[75]),"+f"(d[76]),"+f"(d[77]),"+f"(d[78]),"+f"(d[79]),"+f"(d[80]),"+f"(d[81]),"+f"(d[82]),"+f"(d[83]),"+f"(d[84]),"+f"(d[85]),"+f"(d[86]),"+f"(d[87]),"+f"(d[88]),"+f"(d[89]),"+f"(d[90]),"+f"(d[91]),"+f"(d[92]),"+f"(d[93]),"+f"(d[94]),"+f"(d[95])
   : "l"(da), "l"(db), "r"(sd));
}

__device__ __forceinline__ void stats_publish(uint32_t sb, int layer, int rb, int hg, int ht, uint32_t tag) {
  const int lane = ht & 31, w = ht >> 5, g = lane >> 2, t = lane & 3, ks = hg & 3;
  uint32_t xa;
  if (layer == 0) {
    const int row = 16 * w + (lane & 15), kc = 2 * ks + (lane >> 4);
    xa = row * 128 + ((kc ^ (row & 7)) << 4);
  } else {
    const int k = 16 * ks + (lane & 7) + 8 * (lane >> 4), pc = 2 * w + ((lane >> 3) & 1);
    xa = k * 128 + ((pc ^ (k & 7)) << 4);
  }
  float s[4] = {0.f, 0.f, 0.f, 0.f}, q[4] = {0.f, 0.f, 0.f, 0.f};
#pragma unroll 1
  for (int c = hg >> 2; c < 8; c += 2) {
    mbar_wait(sb + SM_BAR + 8 * (B_XF + c), layer);
    if (c >= 6) ATS(48, 256);
    if (c < 2) ATS(51, 256);
    uint32_t A[2][4];
#pragma unroll
    for (int h = 0; h < 2; h++) {
      if (layer == 0) ldsm4(A[h], sb + SM_X + c * 16384 + h * 8192 + xa);
      else ldsm4t(A[h], sb + SM_X + c * 16384 + h * 8192 + xa);
    }
#pragma unroll
    for (int r = 0; r < 4; r++)
#pragma unroll
      for (int i = 0; i < 2; i++) {
        const uint32_t v = A[r >> 1][2 * i + (r & 1)];
        const float a = bf_lo(v), b = bf_hi(v);
        s[r] += a + b; q[r] = fmaf(a, a, q[r]); q[r] = fmaf(b, b, q[r]);
      }
  }
#pragma unroll
  for (int r = 0; r < 2; r++) {
    s[r] = ((t & 2) ? s[r + 2] : s[r]) + __shfl_xor_sync(~0u, (t & 2) ? s[r] : s[r + 2], 2);
    q[r] = ((t & 2) ? q[r + 2] : q[r]) + __shfl_xor_sync(~0u, (t & 2) ? q[r] : q[r + 2], 2);
  }
  s[0] = ((t & 1) ? s[1] : s[0]) + __shfl_xor_sync(~0u, (t & 1) ? s[0] : s[1], 1);
  q[0] = ((t & 1) ? q[1] : q[0]) + __shfl_xor_sync(~0u, (t & 1) ? q[0] : q[1], 1);
  st_part(&g_part[(rb * 8 + hg) * 128 + 64 * (t >> 1) + 16 * w + 8 * (t & 1) + g], s[0], q[0], tag);
  ATS(49, 256);
}
__device__ __forceinline__ void stats_gather(uint32_t sb, int rb, int ht, uint32_t tag) {
  const uint2* src = &g_part[rb * 8 * 128 + ht];
  uint2 v[8];
  bool ok;
  int it = 0;
  do {
    ok = true;
#pragma unroll
    for (int i = 0; i < 8; i++) v[i] = ld_part(src + i * 128);
#pragma unroll
    for (int i = 0; i < 8; i++) ok = ok && (v[i].y & 7u) == tag;
    if (++it > (1 << 22)) __trap();
  } while (!__all_sync(~0u, ok));
  float s = 0.f, q = 0.f;
#pragma unroll
  for (int i = 0; i < 8; i++) { s += __uint_as_float(v[i].x); q += __uint_as_float(v[i].y); }
  const float mean = s * (1.f / DM);
  const float rstd = rsqrt_approx(fmaxf(q * (1.f / DM) - mean * mean, 0.f) + 1e-5f);
  asm volatile("st.shared.v2.f32 [%0], {%1,%2};" ::"r"(sb + SM_ST + ht * 8), "f"(mean), "f"(rstd) : "memory");
  __syncwarp();
  if (elect_one()) mbar_arrive(sb + SM_BAR + 8 * B_STF);
}
__device__ __forceinline__ void halo_receive(uint32_t sb, int layer, int rb, int hg, int ht) {
  const int lane = ht & 31, h = ht >> 5;
  uint4 kv = make_uint4(0, 0, 0, 0);
  mbar_wait(sb + SM_BAR + 8 * B_SD, layer);
  if (rb & 7) {
    const uint32_t tag = 2 * lds32(sb + SM_EP) + layer + 1;
    const uint4* src = &g_halo[((rb - 1) * 8 + hg) * 192 + h * 48];
    if (layer == 0) delay<D_HALO>(); else delay<D_HALO1>();
    uint4 a;
    uint2 b;
    int it = 0;
    do {
      a = ld_tagged(src + lane); b = ld_part((const uint2*)(src + 32) + lane);
      if (++it > (1 << 22)) __trap();
    } while (!__all_sync(~0u, a.w == tag && b.y == tag));
    kv = make_uint4(a.x, a.y, movm_t(a.z), movm_t(b.x));
  }
  sts128(sb + SM_KVX + h * 512 + lane * 16, kv);
  ATS(61, 256);
  bar_arrive(7, 160);
  if (elect_one()) mbar_arrive(sb + SM_BAR + 8 * B_HF);
}

__device__ __forceinline__ void halo_receive1(uint32_t sb, int layer, int rb, int hg, int lane, uint32_t tag) {
  uint4 a[4];
  uint2 b[4];
  mbar_wait(sb + SM_BAR + 8 * B_SD, layer);
  if (rb & 7) {
    const uint4* src = &g_halo[((rb - 1) * 8 + hg) * 192];
    if (layer == 0) delay<D_HALO>(); else delay<D_HALO1>();
    int it = 0;
    bool ok;
    do {
      ok = true;
#pragma unroll
      for (int h = 0; h < 4; h++) { a[h] = ld_tagged(src + h * 48 + lane); b[h] = ld_part((const uint2*)(src + h * 48 + 32) + lane); }
#pragma unroll
      for (int h = 0; h < 4; h++) ok = ok && a[h].w == tag && b[h].y == tag;
      if (++it > (1 << 22)) __trap();
    } while (!__all_sync(~0u, ok));
#pragma unroll
    for (int h = 0; h < 4; h++) { a[h].z = movm_t(a[h].z); a[h].w = movm_t(b[h].x); }
  } else {
#pragma unroll
    for (int h = 0; h < 4; h++) a[h] = make_uint4(0, 0, 0, 0);
  }
#pragma unroll
  for (int h = 0; h < 4; h++) sts128(sb + SM_KVX + h * 512 + lane * 16, a[h]);
  ATS(61, 448);
  bar_arrive(7, 64);
  if (lane < 4) mbar_arrive(sb + SM_BAR + 8 * B_HF);
}

template <bool TR>
__device__ __forceinline__ void gemm_section(float* acc, float2* cs, uint32_t sb, int layer, int wg, int w, int lane) {
  const uint32_t bar = sb + SM_BAR;
  const bool leader = (w == 0) && (lane == 0);
  auto issue = [&](int c, int slot) {
    mbar_wait(bar + 8 * (B_XF + c), layer);
    mbar_wait(bar + 8 * (B_KVF + c), layer);
    const uint64_t da = mkdesc(sb + SM_X + c * 16384 + wg * 8192, TR ? 8192 : 16, 1024, 1);
    const uint64_t db = mkdesc(sb + SM_W + slot * 24576, 8192, 1024, 1);
    wg_fence();
#pragma unroll
    for (int ks = 0; ks < 4; ks++) wgmma_ss<192, TR ? 1 : 0, 1>(acc, da + (TR ? ks * 128 : ks * 2), db + ks * 128, (c | ks) != 0);
    wg_commit();
  };
  auto step = [&](int c, int slot) {
    issue(c, slot);
    wg_wait<1>();
    if (leader) mbar_arrive(bar + 8 * (B_KVE + c - 1));
  };
  if (!TR) bar_sync(0, NTHREADS);
  issue(0, 0);
  if (threadIdx.x == 0) TS(2 + layer * 20 + 0);
  if (threadIdx.x == 128 && layer == 1) TS(60);
  step(1, 1); step(2, 2); step(3, 0); step(4, 1);
  auto ld_cs = [&](int j0) {
#pragma unroll
    for (int j = j0; j < j0 + 8; j++) cs[j] = lds64f(sb + SM_CS + 4 * (8 * j + 2 * (lane & 3)));
  };
  if (TR) ld_cs(8);
  step(5, 2);
  if (!TR && !CS_LATE0) { mbar_wait(bar + 8 * B_CSF, 0); ld_cs(8); }
  if (TR || !CS_LATE0) ld_cs(16);
  if (wg == 0) bar_sync(5, 256);
  issue(6, 0);
  issue(7, 1);
  if (wg == 1) bar_arrive(5, 256);
  if (!TR && CS_LATE0) { mbar_wait(bar + 8 * B_CSF, 0); ld_cs(8); ld_cs(16); }
}

__device__ __forceinline__ void attn_phase(const Params& p, uint32_t sb, int layer, int rb, int hg, int wg, int w) {
  const int lane = opaque_tid() & 31;
  const int g = lane >> 2, t = lane & 3;
  const uint32_t bar = sb + SM_BAR;
  const int row0 = 64 * wg + 16 * w;
  const bool leader = (w == 0) && (lane == 0);
  float acc[96];
  float2 cs[24];
  if (layer) gemm_section<true>(acc, cs, sb, layer, wg, w, lane);
  else gemm_section<false>(acc, cs, sb, layer, wg, w, lane);
  ATS(41, 224);
  mbar_wait(bar + 8 * B_STF, layer);
  const uint32_t tag = 2 * lds32(sb + SM_EP) + layer + 1;
  const float2 st0 = lds64f(sb + SM_ST + (row0 + g) * 8), st1 = lds64f(sb + SM_ST + (row0 + g + 8) * 8);
  const float mean0 = st0.x, rstd0 = st0.y, mean1 = st1.x, rstd1 = st1.y;
  wg_wait<0>();
  if (threadIdx.x == 0) TS(2 + layer * 20 + 1);
  ATS(39, 224);
  if (leader) mbar_arrive(bar + 8 * B_QDONE);

  uint32_t fp[4][4], fl[4][4], fh[4][4], qa[4][4];
  const int cw = 4 * wg + w;
  {
    const float nm0 = -mean0 * rstd0, nm1 = -mean1 * rstd1;
    const uint32_t kvx = sb + SM_KVX + cw * 2048 + lane * 16;
#pragma unroll
    for (int h = 0; h < 4; h++)
#pragma unroll
      for (int k = 0; k < 4; k++) {
        const int j = 8 + (k >> 1) * 8 + 2 * h + (k & 1);
        fh[h][k] = packbf(fmaf(acc[4 * j + 2], rstd1, nm1 * cs[j].x), fmaf(acc[4 * j + 3], rstd1, nm1 * cs[j].y));
      }
    if (cw == 7) {
      uint4* halo = &g_halo[(rb * 8 + hg) * 192];
#pragma unroll
      for (int h = 0; h < 4; h++) {
        st_tagged3(halo + h * 48 + lane, fh[h][0], fh[h][1], fh[h][2], tag);
        asm volatile("st.relaxed.gpu.global.v2.u32 [%0], {%1,%2};" ::"l"((uint2*)(halo + h * 48 + 32) + lane), "r"(fh[h][3]), "r"(tag) : "memory");
      }
      if (elect_one()) mbar_arrive(bar + 8 * B_SD);
      if (layer == TLAYER && threadIdx.x == 224) TS(47);
    }
#pragma unroll
    for (int h = 0; h < 4; h++) { fh[h][2] = movm_t(fh[h][2]); fh[h][3] = movm_t(fh[h][3]); }
    if (cw != 7) {
#pragma unroll
      for (int h = 0; h < 4; h++) sts128(kvx + 2048 + h * 512, make_uint4(fh[h][0], fh[h][1], fh[h][2], fh[h][3]));
      bar_arrive(8 + cw, 64);
    }
    if (layer == TLAYER && threadIdx.x == 0) TS(45);
#pragma unroll
    for (int j = 0; j < 8; j++) cs[j] = lds64f(sb + SM_CS + 4 * (8 * j + 2 * t));
#pragma unroll
    for (int h = 0; h < 4; h++)
#pragma unroll
      for (int k = 0; k < 4; k++) {
        const int j = 8 + (k >> 1) * 8 + 2 * h + (k & 1);
        fl[h][k] = packbf(fmaf(acc[4 * j], rstd0, nm0 * cs[j].x), fmaf(acc[4 * j + 1], rstd0, nm0 * cs[j].y));
        if (k >= 2) fl[h][k] = movm_t(fl[h][k]);
      }
#pragma unroll
    for (int h = 0; h < 4; h++) {
#pragma unroll
      for (int dh = 0; dh < 2; dh++) {
        const int j = 2 * h + dh;
        const float2 c2 = cs[j];
        qa[h][2 * dh] = packbf(fmaf(-mean0, c2.x, acc[4 * j + 0]), fmaf(-mean0, c2.y, acc[4 * j + 1]));
        qa[h][2 * dh + 1] = packbf(fmaf(-mean1, c2.x, acc[4 * j + 2]), fmaf(-mean1, c2.y, acc[4 * j + 3]));
      }
    }
    if (threadIdx.x == 0) TS(2 + layer * 20 + 2);
    bar_sync(7 + cw, cw == 0 && !HALO_W14 ? 160 : 64);
#pragma unroll
    for (int h = 0; h < 4; h++) {
      const uint4 v = lds128(kvx + h * 512);
      fp[h][0] = v.x; fp[h][1] = v.y; fp[h][2] = v.z; fp[h][3] = v.w;
    }
    if (threadIdx.x == 0) TS(2 + layer * 20 + 4);
  }

  const bool u0 = 2 * t > g, u1 = 2 * t + 1 > g;
  const uint32_t mU = (u0 ? 0x0000ffffu : 0u) | (u1 ? 0xffff0000u : 0u);
  const float cl2 = 0.25f * 1.4426950408889634f;
  const float sc0 = rstd0 * cl2, sc1 = rstd1 * cl2;
  const float cneg = ((rb & 7) == 0 && cw == 0) ? -INFINITY : 0.f;
  float v[4][4];
#pragma unroll
  for (int h = 0; h < 4; h++) {
    float T0[4] = {cneg, cneg, cneg, cneg}, T1[4] = {0.f, 0.f, 0.f, 0.f}, T2[4] = {0.f, 0.f, 0.f, 0.f};
    mma_bf16(T1, qa[h], fl[h][0], fl[h][1]);
    mma_bf16(T2, qa[h], fh[h][0], fh[h][1]);
    mma_bf16(T0, qa[h], fp[h][0], fp[h][1]);
    v[h][0] = u0 ? T0[0] : T1[0]; v[h][1] = u1 ? T0[1] : T1[1];
    v[h][2] = u0 ? T1[2] : T2[2]; v[h][3] = u1 ? T1[3] : T2[3];
  }
  float m0[4], m1[4];
#pragma unroll
  for (int h = 0; h < 4; h++) { m0[h] = fmaxf(v[h][0], v[h][1]); m1[h] = fmaxf(v[h][2], v[h][3]); }
#pragma unroll
  for (int o = 1; o <= 2; o <<= 1) {
#pragma unroll
    for (int h = 0; h < 4; h++) {
      m0[h] = fmaxf(m0[h], __shfl_xor_sync(~0u, m0[h], o));
      m1[h] = fmaxf(m1[h], __shfl_xor_sync(~0u, m1[h], o));
    }
  }
  float O0[4][4], O1[4][4], Z[4][4];
#pragma unroll
  for (int h = 0; h < 4; h++) {
    const float mm0 = -m0[h] * sc0, mm1 = -m1[h] * sc1;
    const uint32_t P0 = packbf(ex2(fmaf(v[h][0], sc0, mm0)), ex2(fmaf(v[h][1], sc0, mm0)));
    const uint32_t P1 = packbf(ex2(fmaf(v[h][2], sc1, mm1)), ex2(fmaf(v[h][3], sc1, mm1)));
#pragma unroll
    for (int k = 0; k < 4; k++) O0[h][k] = O1[h][k] = Z[h][k] = 0.f;
    mma_bf16_k8(Z[h], P0, P1, 0x3f803f80u);
    mma_bf16_k8(O0[h], P0 & ~mU, P1 & mU, fl[h][2]); mma_bf16_k8(O1[h], P0 & ~mU, P1 & mU, fl[h][3]);
    mma_bf16_k8(O0[h], P0 & mU, 0u, fp[h][2]); mma_bf16_k8(O1[h], P0 & mU, 0u, fp[h][3]);
    mma_bf16_k8(O0[h], 0u, P1 & ~mU, fh[h][2]); mma_bf16_k8(O1[h], 0u, P1 & ~mU, fh[h][3]);
  }
  const uint32_t ob = sb + SM_OST + wg * 8192;
  const int o_row = 16 * w + (lane & 7) + 8 * ((lane >> 3) & 1);
#pragma unroll
  for (int h = 0; h < 4; h++) {
    const float i0 = rcp_approx(Z[h][0]), i1 = rcp_approx(Z[h][2]);
    const int ch = 2 * h + (lane >> 4);
    stsm4(ob + o_row * 128 + ((ch ^ (o_row & 7)) << 4), packbf(O0[h][0] * i0, O0[h][1] * i0), packbf(O0[h][2] * i1, O0[h][3] * i1),
          packbf(O1[h][0] * i0, O1[h][1] * i0), packbf(O1[h][2] * i1, O1[h][3] * i1));
  }
  if (threadIdx.x == 0) TS(2 + layer * 20 + 5);
  ATS(57, 128); ATS(20, 96);
  bar_sync(2 + wg, 128);
  if (w == 0 && elect_one()) {
    fence_async_smem();
    tma_st(&p.mapO, hg * 64, rb * 128 + wg * 64, ob);
    bulk_commit();
    mbar_arrive(bar + 8 * B_AD);
    bulk_wait_all();
    red_relaxed(&g_cnt[(C_O + rb) * 32]);
    mbar_arrive(bar + 8 * B_OST);
    if (threadIdx.x == 0) TS(2 + layer * 20 + 6);
  }
}

__device__ __forceinline__ void proj_phase(const Params& p, uint32_t sb, int layer, int rb, int q, int wg, int w) {
  const int lane = opaque_tid() & 31;
  const bool TR = layer != 0;
  const int t = lane & 3;
  const uint32_t bar = sb + SM_BAR;
  const uint32_t rbx = sb + SM_R + wg * 8192;
  uint32_t res[16];
  mbar_wait(bar + 8 * B_RF, layer);
  if (threadIdx.x == 0) TS(2 + layer * 20 + 7);
  if (!TR) {
#pragma unroll
    for (int j = 0; j < 8; j += 2) {
      const int mi = lane >> 3;
      const int row = 16 * w + (lane & 7) + 8 * (mi & 1), ch = j + (mi >> 1);
      ldsm4(&res[2 * j], rbx + row * 128 + ((ch ^ (row & 7)) << 4));
    }
  } else {
#pragma unroll
    for (int j = 0; j < 8; j += 2) {
      const int mi = lane >> 3;
      const int line = 8 * (j + (mi >> 1)) + (lane & 7), pc = 2 * w + (mi & 1);
      ldsm4t(&res[2 * j], rbx + line * 128 + ((pc ^ (line & 7)) << 4));
    }
  }
  bar_sync(2 + wg, 128);
  float acc[32];
#pragma unroll
  for (int i = 0; i < 16; i++) {
    asm volatile("shl.b32 %0, %1, 16;" : "=f"(acc[2 * i]) : "r"(res[i]));
    asm volatile("and.b32 %0, %1, 0xffff0000;" : "=f"(acc[2 * i + 1]) : "r"(res[i]));
  }
  const uint32_t tag = part_tag(lds32(sb + SM_EP), 2 * layer + 1);
#pragma unroll 1
  for (int c = 0; c < 8; c++) {
    if ((c & 1) == 0) mbar_wait(bar + 8 * (B_WOF + (c >> 1)), layer);
    mbar_wait(bar + 8 * (B_OF + c), layer);
    if (c == 0 && threadIdx.x == 0) TS(2 + layer * 20 + 8);
    const uint64_t da = mkdesc(sb + sm_o(c) + wg * 8192, 16, 1024, 1);
    const uint64_t db = mkdesc(sb + SM_WO + c * 8192, 8192, 1024, 1);
    wg_fence();
#pragma unroll
    for (int ks = 0; ks < 4; ks++) wgmma_ss<64, 0, 1>(acc, da + ks * 2, db + ks * 128, 1);
    wg_commit();
  }
  wg_wait<0>();
#pragma unroll
  for (int i = 0; i < 32; i++) asm volatile("" : "+f"(acc[i]) :: "memory");
  if (threadIdx.x == 0) TS(2 + layer * 20 + 9);
  if (lane == 0 && w == 0) mbar_arrive(bar + 8 * B_PDONE);
  {
    float s[4], qq[4];
#pragma unroll
    for (int k = 0; k < 4; k++) { s[k] = acc[k]; qq[k] = acc[k] * acc[k]; }
#pragma unroll
    for (int j = 1; j < 8; j++)
#pragma unroll
      for (int k = 0; k < 4; k++) { s[k] += acc[4 * j + k]; qq[k] = fmaf(acc[4 * j + k], acc[4 * j + k], qq[k]); }
    const float s0 = s[0] + s[1], s1 = s[2] + s[3], q0 = qq[0] + qq[1], q1 = qq[2] + qq[3];
    float sr = ((t & 1) ? s1 : s0) + __shfl_xor_sync(~0u, (t & 1) ? s0 : s1, 1);
    float qr = ((t & 1) ? q1 : q0) + __shfl_xor_sync(~0u, (t & 1) ? q0 : q1, 1);
    sr += __shfl_xor_sync(~0u, sr, 2);
    qr += __shfl_xor_sync(~0u, qr, 2);
    if (t < 2) st_part(&g_part[(rb * 8 + q) * 128 + 64 * wg + 16 * w + (lane >> 2) + 8 * t], sr, qr, tag);
    __syncwarp();
    if (elect_one()) mbar_arrive(bar + 8 * B_PS);
  }
#pragma unroll
  for (int j = 0; j < 8; j += 2) {
    const int mi = lane >> 3;
    const int line = 8 * (j + (mi >> 1)) + (lane & 7), pc = 2 * w + (mi & 1);
    stsm4t(rbx + line * 128 + ((pc ^ (line & 7)) << 4), packbf(acc[4 * j], acc[4 * j + 1]), packbf(acc[4 * j + 2], acc[4 * j + 3]),
           packbf(acc[4 * j + 4], acc[4 * j + 5]), packbf(acc[4 * j + 6], acc[4 * j + 7]));
  }
  fence_writer();
  bar_sync(2 + wg, 128);
  if (w == 0 && elect_one()) {
    fence_reader();
    mbar_wait(bar + 8 * B_ZF, layer);
    fence_async_global();
    tma_st(&p.mapXT, rb * 128 + wg * 64, (2 * layer) * DM + q * 64, rbx);
    bulk_commit();
    if (threadIdx.x == 0) TS(2 + layer * 20 + 10);
    asm volatile("cp.async.bulk.wait_group.read 0;" ::: "memory");
    if (wg == 0) mbar_arrive(bar + 8 * B_RE);
  }
}
__device__ __forceinline__ void proj_stats(int layer, int rb, int q, int lane, uint32_t tag) {
  const int r = 16 * q + (lane & 15);
  const uint2* src = &g_part[(rb * 8 + (lane >> 4) * 4) * 128 + r];
  uint2 v[4];
  bool ok;
  int it = 0;
  do {
    ok = true;
#pragma unroll
    for (int i = 0; i < 4; i++) v[i] = ld_part(src + i * 128);
#pragma unroll
    for (int i = 0; i < 4; i++) ok = ok && (v[i].y & 7u) == tag;
    if (++it > (1 << 22)) __trap();
  } while (!__all_sync(~0u, ok));
  float s = (__uint_as_float(v[0].x) + __uint_as_float(v[1].x)) + (__uint_as_float(v[2].x) + __uint_as_float(v[3].x));
  float qq = (__uint_as_float(v[0].y) + __uint_as_float(v[1].y)) + (__uint_as_float(v[2].y) + __uint_as_float(v[3].y));
  s += __shfl_xor_sync(~0u, s, 16);
  qq += __shfl_xor_sync(~0u, qq, 16);
  const float mean = s * (1.f / DM);
  const float rstd = rsqrt_approx(fmaxf(fmaf(qq, 1.f / DM, -mean * mean), 0.f) + 1e-5f), nm = -mean * rstd;
  const float nm1 = __shfl_xor_sync(~0u, nm, 1), rstd1 = __shfl_xor_sync(~0u, rstd, 1);
  if ((lane & 17) == 0)
    st_tagged3((uint4*)g_stats + (layer * 32 + rb * 2 + (r >> 6)) * 32 + ((r & 7) >> 1) * 8 + ((r >> 3) & 7),
               __float_as_uint(nm), __float_as_uint(rstd) | 1u, __float_as_uint(nm1), __float_as_uint(rstd1));
}

#define NA 8
template <bool GB> __host__ __device__ constexpr int grp_n() { return GB ? 17 - NA : NA; }
template <bool GB> __host__ __device__ constexpr int grp_m(int i) { return i == 0 ? (GB ? 1 : 0) : (GB ? NA + i : 1 + i); }
template <bool GB> __device__ __forceinline__ void conv_load(uint32_t* A, uint32_t pe) {
#pragma unroll
  for (int i = 0; i < grp_n<GB>(); i++) {
    asm volatile("ld.shared.v2.b32 {%0,%1}, [%2];" : "=r"(A[4 * i]), "=r"(A[4 * i + 1]) : "r"(pe + 4 * (64 * grp_m<GB>(i))) : "memory");
    A[4 * i + 2] = lds32(pe + 4 * (64 * grp_m<GB>(i) - 1));
  }
}
template <bool GB> __device__ __forceinline__ void conv_dup_early(uint32_t* A, uint32_t zero) {
#pragma unroll
  for (int i = 0; i < grp_n<GB>(); i++) asm volatile("or.b32 %0, %1, %2;" : "=r"(A[4 * i + 3]) : "r"(A[4 * i + 0]), "r"(zero));
}
template <bool GB> __device__ __forceinline__ void conv_dup(uint32_t* A) {
#pragma unroll
  for (int i = 0; i < grp_n<GB>(); i++) asm volatile("mov.b32 %0, %1;" : "=r"(A[4 * i + 3]) : "r"(A[4 * i + 0]));
}
template <bool GB, int I0, int I1> __device__ __forceinline__ void conv_mmas(float* acc, const uint32_t* A, uint64_t d) {
  if constexpr (I0 < I1) {
    constexpr int M = grp_m<GB>(I0);
    wgmma_rs<128 - 8 * (M / 2), 0>(acc, A + 4 * I0, d + (uint64_t)(4 * M), M != 0);
    conv_mmas<GB, I0 + 1, I1>(acc, A, d);
  }
}
struct SumAddr { uint32_t l0, l1, l2, se, so; };
__device__ __forceinline__ SumAddr conv_sum_addr(uint32_t sb, int c) {
  auto ua = [&](int j) { return sb + cv_u(0) + (127 - (j >> 3)) * 16 + (j & 7) * 2; };
  auto sa = [&](int hc) { const int ci = hc & ~1; return sb + cv_s(0) + ((ci >> 3) & 1) * 1024 + (ci >> 4) * 128 + (((ci ^ (ci >> 4)) & 7) << 4) + (hc & 1) * 8; };
  const int j0 = 4 * (c - 1);
  return {ua(j0 - 2), ua(j0), ua(j0 + 4), sa((c + 1) & 127), sa(c) + 2048};
}
__device__ __forceinline__ void sts64(uint32_t a, uint32_t x, uint32_t y) { asm volatile("st.shared.v2.b32 [%0], {%1,%2};" ::"r"(a), "r"(x), "r"(y) : "memory"); }
__device__ __forceinline__ void conv_sums(const SumAddr& sa, int lc, int c) {
  uint32_t e[4], o[4];
  {
    const float2 em = lds64f(sa.l1 + lc * 32768), om = lds64f(sa.l1 + lc * 32768 + CV_UH);
    e[0] = lds32(sa.l0 + lc * 32768); o[0] = lds32(sa.l0 + lc * 32768 + CV_UH);
    e[3] = lds32(sa.l2 + lc * 32768); o[3] = lds32(sa.l2 + lc * 32768 + CV_UH);
    e[1] = __float_as_uint(em.x); e[2] = __float_as_uint(em.y); o[1] = __float_as_uint(om.x); o[2] = __float_as_uint(om.y);
  }
  uint32_t s7e[2], s7o[2], s9e[2], s9o[2];
  uint32_t pw[4], sh[3];
#pragma unroll
  for (int k = 0; k < 4; k++) pw[k] = hadd2(e[k], o[k]);
#pragma unroll
  for (int k = 0; k < 3; k++) sh[k] = __byte_perm(pw[k], pw[k + 1], 0x5432);
#pragma unroll
  for (int k = 0; k < 2; k++) {
    const uint32_t t3 = hadd2(hadd2(sh[k], sh[k + 1]), pw[k + 1]);
    s7e[k] = hadd2(t3, o[k]); s7o[k] = hadd2(t3, e[k + 2]);
    s9e[k] = hadd2(s7o[k], pw[k]); s9o[k] = hadd2(s7e[k], pw[k + 2]);
  }
  if (c == 127) s9e[0] = s9e[1] = s9o[0] = s9o[1] = 0u;
  sts64(sa.se + lc * 32768, s9e[0], s9e[1]); sts64((sa.se ^ 16) + lc * 32768, s9o[0], s9o[1]);
  sts64(sa.so + lc * 32768, s7e[0], s7e[1]); sts64((sa.so ^ 16) + lc * 32768, s7o[0], s7o[1]);
}

__device__ __forceinline__ void conv_epi(uint32_t sb, int layer, int cta, int ch, int c0, uint4 x0, uint4 x1) {
  uint4 v[2][4];
  const uint4 xr[2] = {x0, x1};
  mbar_wait(sb + SM_BAR + 8 * (B_P + ch), layer);
#pragma unroll
  for (int u = 0; u < 2; u++) {
    const uint32_t pb = sb + cv_pb(ch) + u * (CV_PBW / 2) + c0 * 16;
#pragma unroll
    for (int k = 0; k < 4; k++) v[u][k] = lds128(pb + k * CV_PBW);
  }
#pragma unroll
  for (int u = 0; u < 2; u++) {
    uint4 o;
    o.x = hadd2(xr[u].x, hadd2(hadd2(v[u][0].x, v[u][1].x), hadd2(v[u][2].x, v[u][3].x)));
    o.y = hadd2(xr[u].y, hadd2(hadd2(v[u][0].y, v[u][1].y), hadd2(v[u][2].y, v[u][3].y)));
    o.z = hadd2(xr[u].z, hadd2(hadd2(v[u][0].z, v[u][1].z), hadd2(v[u][2].z, v[u][3].z)));
    o.w = hadd2(xr[u].w, hadd2(hadd2(v[u][0].w, v[u][1].w), hadd2(v[u][2].w, v[u][3].w)));
    if (layer == 0) sts128(sb + cv_s(ch) + (c0 + 128 * u) * 16, o);
    else st_tagged3((uint4*)(g_xT + (size_t)(3 * DM + cv_chan(cta, ch)) * LSEQ) + c0 + 128 * u, o.x, o.y, o.z, o.w);
  }
}
__device__ __forceinline__ void warp_release(uint32_t b) {
  fence_writer();
  __syncwarp();
  if (elect_one()) mbar_arrive(b);
}

__device__ __forceinline__ void conv_prep_load(uint32_t sb, int layer, int cta, int c, uint4 (&xr)[4], uint4 (&st)[4]) {
  mbar_wait(sb + SM_BAR + 8 * B_GB, layer);
  if (threadIdx.x == 0) TS(2 + layer * 20 + 11);
  xr[0] = ld_tagged((const uint4*)(g_xT + (size_t)(2 * layer * DM + cta) * LSEQ) + c);
#pragma unroll
  for (int i = 0; i < 4; i++) st[i] = ld_tagged((const uint4*)g_stats + (layer * 32 + (c >> 3)) * 32 + i * 8 + (c & 7));
}
template <bool HELPER>
__device__ __forceinline__ void conv_prep(uint32_t sb, int layer, int cta, int c, uint4 (&xr)[4], uint4 (&st)[4], const SumAddr& sa) {
  const uint32_t bar = sb + SM_BAR;
  const uint4* xin = (const uint4*)(g_xT + (size_t)(2 * layer * DM + cta) * LSEQ) + c;
  for (int it = 0;; it++) {
    const bool okx = __all_sync(~0u, xr[0].x != ~0u);
    const bool oks = __all_sync(~0u, (st[0].y & st[1].y & st[2].y & st[3].y & 1u) != 0);
    if (okx && oks) break;
    if (it > (1 << 22)) __trap();
    if (!okx) xr[0] = ld_tagged(xin);
    if (!oks) {
#pragma unroll
      for (int i = 0; i < 4; i++) st[i] = ld_tagged((const uint4*)g_stats + (layer * 32 + (c >> 3)) * 32 + i * 8 + (c & 7));
    }
  }
  if (threadIdx.x == 0) TS(2 + layer * 20 + 12);
  const int a = c & 127, h = c >> 7;
#pragma unroll
  for (int i = 0; i < 4; i++) {
    if (i == 1) {
#pragma unroll
      for (int j = 1; j < 4; j++) xr[j] = ld_tagged(xin + j * (128 * LSEQ / 8));
      if (HELPER) {
        mbar_wait(bar + 8 * B_U, layer);
        conv_sums(sa, 0, c);
        fence_async_smem();
        warp_release(bar + 8 * B_S);
        if (layer == 1 && c == 0) TS(46);
        mbar_wait(bar + 8 * B_GB, layer);
      }
      for (int it = 0; !__all_sync(~0u, xr[1].x != ~0u && xr[2].x != ~0u && xr[3].x != ~0u); it++) {
        if (it > (1 << 22)) __trap();
#pragma unroll
        for (int j = 1; j < 4; j++) xr[j] = ld_tagged(xin + j * (128 * LSEQ / 8));
      }
    }
    const uint32_t x[4] = {xr[i].x, xr[i].y, xr[i].z, xr[i].w};
    uint32_t u[4];
#pragma unroll
    for (int k = 0; k < 4; k++)
      u[k] = packbf(fmaf(bf_lo(x[k]), __uint_as_float(st[k].y), __uint_as_float(st[k].x)), fmaf(bf_hi(x[k]), __uint_as_float(st[k].w), __uint_as_float(st[k].z)));
    sts128(sb + cv_u(i) + h * CV_UH + (127 - a) * 16, make_uint4(u[0], u[1], u[2], u[3]));
    warp_release(bar + 8 * (B_U + i));
  }
}
__device__ __forceinline__ void conv_zero(uint32_t sb, int ht) {
  if (ht < 96) {
    const int ch = ht / 24, h2 = (ht / 12) & 1, qq = ht % 12;
    sts128(sb + cv_u(ch) + h2 * CV_UH + (128 + qq) * 16, make_uint4(0, 0, 0, 0));
  }
  if (ht >= 80) {
    const int i = ht - 80, ch = i / 12, q2 = i % 12;
    const int w2 = q2 < 2 ? 1 : q2 < 6 ? 2 : 3, cc = q2 < 2 ? q2 : q2 < 6 ? q2 - 2 : q2 - 6;
    sts128(sb + cv_pb(ch) + w2 * CV_PBW + (cc & 1) * (CV_PBW / 2) + (cc >> 1) * 16, make_uint4(0, 0, 0, 0));
  }
}

#define LD_AT 0
#define HANDOVER 12
template <int R>
__device__ __forceinline__ void conv_round(uint32_t sb, int layer, int wg, uint32_t* FA, uint32_t* FB, uint32_t pb, uint32_t pe2) {
  const uint32_t bar = sb + SM_BAR;
  const int ch = 2 * R + 1 - wg;
  float acc[64];
  const uint64_t d = mkdesc(sb + cv_u(ch), CV_UH, 128, 0);
  const bool leader = (opaque_tid() & 127) == 0;
  FTS(39);
  if (R == 0) {
    mbar_wait(bar + 8 * (B_U + ch), layer);
    fence_reader();
  }
  if (ch > 0) mbar_wait(bar + 8 * (B_T + ch - 1), layer);
  FTS(41);
  if (ch == 0 && threadIdx.x == 128) TS(2 + layer * 20 + 13);
  if (R == 1 && LD_AT == 0) conv_load<true>(FB, pe2);
  wg_fence();
  conv_mmas<false, 0, (HANDOVER < NA ? HANDOVER : NA)>(acc, FA, d);
  if (HANDOVER <= NA) mbar_arrive_if(bar + 8 * (B_T + ch), leader);
  conv_mmas<false, (HANDOVER < NA ? HANDOVER : NA), NA>(acc, FA, d);
  wg_commit();
  if (R == 1 && LD_AT == 1) conv_load<true>(FB, pe2);
  FTS(51);
  mbar_wait(bar + 8 * (B_S + ch), layer);
  if (R == 1) conv_dup<true>(FB);
  wg_fence();
  conv_mmas<true, 0, (HANDOVER > NA ? HANDOVER - NA : 0)>(acc, FB, d);
  if (HANDOVER > NA) mbar_arrive_if(bar + 8 * (B_T + ch), leader);
  conv_mmas<true, (HANDOVER > NA ? HANDOVER - NA : 0), 17 - NA>(acc, FB, d);
  wgmma_ss<64, 1, 1>(acc, mkdesc(sb + cv_s(ch), 1024, 1024, 1), mkdesc(sb + cv_ft(ch), 256, 16, 0), 1);
  wgmma_ss<64, 1, 1>(acc, mkdesc(sb + cv_s(ch) + 2048, 1024, 1024, 1), mkdesc(sb + cv_ft(ch) + 512, 256, 16, 0), 1);
  wg_commit();
  FTS(61);
  wg_wait<0>();
#pragma unroll
  for (int j = 0; j < 16; j += 2)
    stsm4t(pb + R * 65536 - j * 128, packbf(acc[4 * j], acc[4 * j + 1]), packbf(acc[4 * j + 2], acc[4 * j + 3]),
           packbf(acc[4 * j + 4], acc[4 * j + 5]), packbf(acc[4 * j + 6], acc[4 * j + 7]));
  __syncwarp();
  if (elect_one()) mbar_arrive(bar + 8 * (B_P + ch));
  if (threadIdx.x == 0) TS(2 + layer * 20 + 14 + R);
  FTS(57);
  if (R == 0) {
    mbar_wait(bar + 8 * (B_U + ch + 2), layer);
    if ((S_OWN & 2) && (!(S_OWN & 4) || layer == 0)) {
      const int c = opaque_tid() & 127;
      conv_sums(conv_sum_addr(sb + (ch + 2) * 32768, c), 0, c);
      fence_async_smem();
      warp_release(bar + 8 * (B_S + ch + 2));
    } else fence_reader();
  }
}
__device__ __forceinline__ void conv_phase(const Params& p, uint32_t sb, int layer, int cta) {
  const int tid = opaque_tid();
  const int wg = __shfl_sync(~0u, tid >> 7, 0), w = __shfl_sync(~0u, (tid >> 5) & 3, 0);
  const uint32_t bar = sb + SM_BAR;
  uint32_t FA0[4 * NA], FA1[4 * NA], FB[4 * (17 - NA)];
  const uint32_t pe = sb + cv_pe(1 - wg) + 4 * (16 + 16 * w + 2 * ((tid & 31) >> 2) - 4 * (tid & 3));
  mbar_wait(bar + 8 * B_PE, layer);
  conv_load<false>(FA0, pe); conv_load<true>(FB, pe);
  const uint32_t zero = tid >> 10;
  conv_dup_early<false>(FA0, zero); conv_dup_early<true>(FB, zero);
  if (wg == 0) {
    uint4 xr[4], st[4];
    conv_prep_load(sb, layer, cta, tid + 128, xr, st);
    conv_load<false>(FA1, pe + 65536);
    conv_dup_early<false>(FA1, zero);
    conv_prep<false>(sb, layer, cta, opaque_tid() + 128, xr, st, SumAddr());
    if ((S_OWN & 1) && (!(S_OWN & 4) || layer == 0)) {
      const int c = opaque_tid();
      const SumAddr sa = conv_sum_addr(sb, c);
      mbar_wait(bar + 8 * (B_U + 1), layer);
      conv_sums(sa, 1, c);
      fence_async_smem();
      warp_release(bar + 8 * (B_S + 1));
    }
  } else {
    conv_load<false>(FA1, pe + 65536);
    conv_dup_early<false>(FA1, zero);
  }
  uint32_t pb;
  {
    const int l2 = opaque_tid() & 31, mt = l2 >> 3;
    pb = sb + cv_pb(1 - wg) + w * CV_PBW + (mt & 1) * (CV_PBW / 2) + (127 - 8 * (mt >> 1) - (l2 & 7) + w) * 16;
  }
  conv_round<0>(sb, layer, wg, FA0, FB, pb, 0);
  conv_round<1>(sb, layer, wg, FA1, FB, pb, pe + 65536);
  if (G_WAIT == 0 && wg == 1 && layer == 0) mbar_wait(bar + 8 * (B_T + 3), layer);
  if (G_WAIT == 1 && layer == 0) mbar_wait(bar + 8 * (B_E + 3), layer);
  if (G_WAIT == 2 && layer == 0) mbar_wait(bar + 8 * (B_P + 3), layer);
}

__device__ __forceinline__ void final_phase(const Params& p, uint32_t sb, int cta, int wg, int w) {
  if (wg == 1 && w == 3) return;
  const int lane = opaque_tid() & 31, g = lane >> 2, t = lane & 3;
  const int lc = wg ? w : 3;
  const int pos0 = (cta & 31) * 64, ch0 = 128 * lc + (cta >> 5) * 32;
  const bf16* src = g_xT + (size_t)(3 * DM + ch0 + 8 * (g >> 1) + (g & 1)) * LSEQ + pos0;
  bf16* dst = p.out + (size_t)(2 * (pos0 & 1023) + (pos0 >> 10)) * DM + ch0 + 8 * t;
  constexpr int RS = 2 * DM;
  int it = 0;
  mbar_wait(sb + SM_BAR + 8 * (B_E + lc), 1);
  delay<D_FIN>();
  if (wg == 0) {
    uint2 v[4];
    do {
#pragma unroll
      for (int q = 0; q < 4; q++)
        asm volatile("ld.relaxed.gpu.global.v2.u32 {%0,%1}, [%2];" : "=r"(v[q].x), "=r"(v[q].y) : "l"(src + 2 * q * LSEQ + 16 * w + 4 * t) : "memory");
      if (++it > (1 << 22)) __trap();
    } while (!__all_sync(~0u, v[0].x != ~0u && v[1].x != ~0u && v[2].x != ~0u && v[3].x != ~0u));
    if (threadIdx.x == 0) TS(42);
    dst += (16 * w + 4 * (g >> 1) + (g & 1)) * RS;
    *(uint4*)dst = make_uint4(movm_t(v[0].x), movm_t(v[1].x), movm_t(v[2].x), movm_t(v[3].x));
    *(uint4*)(dst + 2 * RS) = make_uint4(movm_t(v[0].y), movm_t(v[1].y), movm_t(v[2].y), movm_t(v[3].y));
  } else {
    uint4 v[2][4];
    bool ok;
    do {
      ok = true;
#pragma unroll
      for (int h = 0; h < 2; h++)
#pragma unroll
        for (int q = 0; q < 4; q++) v[h][q] = ld_tagged((const uint4*)(src + 2 * q * LSEQ + 32 * h + 8 * t));
#pragma unroll
      for (int h = 0; h < 2; h++)
#pragma unroll
        for (int q = 0; q < 4; q++) ok = ok && v[h][q].x != ~0u;
      if (++it > (1 << 22)) __trap();
    } while (!__all_sync(~0u, ok));
    dst += (8 * (g >> 1) + (g & 1)) * RS;
#pragma unroll
    for (int h = 0; h < 2; h++) {
      *(uint4*)(dst + (32 * h + 0) * RS) = make_uint4(movm_t(v[h][0].x), movm_t(v[h][1].x), movm_t(v[h][2].x), movm_t(v[h][3].x));
      *(uint4*)(dst + (32 * h + 2) * RS) = make_uint4(movm_t(v[h][0].y), movm_t(v[h][1].y), movm_t(v[h][2].y), movm_t(v[h][3].y));
      *(uint4*)(dst + (32 * h + 4) * RS) = make_uint4(movm_t(v[h][0].z), movm_t(v[h][1].z), movm_t(v[h][2].z), movm_t(v[h][3].z));
      *(uint4*)(dst + (32 * h + 6) * RS) = make_uint4(movm_t(v[h][0].w), movm_t(v[h][1].w), movm_t(v[h][2].w), movm_t(v[h][3].w));
    }
  }
  if (threadIdx.x == 0) TS(43);
  if (threadIdx.x == 192) TS(63);
  if (threadIdx.x == 0) LTS(1);
}

struct cplx { float r, i; };
__device__ __forceinline__ cplx cmul(cplx a, cplx b) { return {fmaf(a.r, b.r, -a.i * b.i), fmaf(a.r, b.i, a.i * b.r)}; }
__device__ __forceinline__ cplx csqr(cplx a) { return {fmaf(a.r, a.r, -a.i * a.i), (a.r + a.r) * a.i}; }
__device__ __forceinline__ cplx cexp_l(float ar2, float ai, float l) {
  const float m = ex2(ar2 * l);
  const float x = ai * l;
  return {m * __cosf(x), m * __sinf(x)};
}

__device__ __forceinline__ void colsum_publish(uint32_t sb, int rb, int hg, int ht, uint32_t tag) {
  const int lane = ht & 31, q = lane & 15, h = lane >> 4;
  const uint32_t src = sb + SM_CW + (ht >> 5) * 4096 + h * 128 + (q & 1) * 8;
  float s[4] = {0.f, 0.f, 0.f, 0.f};
#pragma unroll 8
  for (int r = 0; r < 16; r++) {
    const float2 v = lds64f(src + r * 256 + (((q >> 1) ^ ((2 * r + h) & 7)) << 4));
    s[0] += bf_lo(__float_as_uint(v.x)); s[1] += bf_hi(__float_as_uint(v.x));
    s[2] += bf_lo(__float_as_uint(v.y)); s[3] += bf_hi(__float_as_uint(v.y));
  }
#pragma unroll
  for (int k = 0; k < 4; k++) s[k] += __shfl_xor_sync(~0u, s[k], 16);
  if (h == 0)
    st_tagged3(&g_colsum[(hg * 16 + rb) * 48 + (ht >> 5) * 16 + q], (__float_as_uint(s[0]) & ~7u) | tag, __float_as_uint(s[1]),
               __float_as_uint(s[2]), __float_as_uint(s[3]));
}
__device__ __forceinline__ void colsum_gather(uint32_t sb, int hg, int ht, uint32_t tag) {
  const int lane = ht & 31, rec = (ht >> 5) * 16 + (lane & 15);
  const uint4* src = &g_colsum[(hg * 16 + (lane >> 4) * 8) * 48 + rec];
  float s[4] = {0.f, 0.f, 0.f, 0.f};
#pragma unroll 1
  for (int h = 0; h < 2; h++, src += 4 * 48) {
    uint4 v[4];
    int it = 0;
    do {
#pragma unroll
      for (int i = 0; i < 4; i++) v[i] = ld_tagged(src + i * 48);
      if (++it > (1 << 22)) __trap();
    } while (!__all_sync(~0u, (v[0].x & 7u) == tag && (v[1].x & 7u) == tag && (v[2].x & 7u) == tag && (v[3].x & 7u) == tag));
#pragma unroll
    for (int i = 0; i < 4; i++) {
      s[0] += __uint_as_float(v[i].x & ~7u); s[1] += __uint_as_float(v[i].y); s[2] += __uint_as_float(v[i].z); s[3] += __uint_as_float(v[i].w);
    }
  }
#pragma unroll
  for (int k = 0; k < 4; k++) s[k] += __shfl_xor_sync(~0u, s[k], 16);
  if (lane < 16) sts128f(sb + SM_CS + rec * 16, s[0], s[1], s[2], s[3]);
}

__device__ __forceinline__ uint32_t packh(float lo, float hi) { uint32_t r; asm("cvt.rn.f16x2.f32 %0, %1, %2;" : "=r"(r) : "f"(hi), "f"(lo)); return r; }
__device__ __forceinline__ void mma_f16(float* d, uint32_t a0, uint32_t a1, uint32_t a2, uint32_t a3, uint32_t b0, uint32_t b1) {
  asm volatile("mma.sync.aligned.m16n8k16.row.col.f32.f16.f16.f32 {%0,%1,%2,%3}, {%4,%5,%6,%7}, {%8,%9}, {%0,%1,%2,%3};"
      : "+f"(d[0]), "+f"(d[1]), "+f"(d[2]), "+f"(d[3]) : "r"(a0), "r"(a1), "r"(a2), "r"(a3), "r"(b0), "r"(b1));
}
struct HSeed { uint32_t r, i; };
__device__ __forceinline__ HSeed hseed(cplx s) { return {packh(s.r, s.r), packh(s.i, s.i)}; }
__device__ __forceinline__ void hcmul(uint32_t& o_r, uint32_t& o_i, uint32_t br, uint32_t bi, HSeed s) {
  asm("{\n.reg .b32 t, u;\nmul.rn.f16x2 t, %3, %5;\nneg.f16x2 t, t;\nmul.rn.f16x2 u, %3, %4;\nfma.rn.f16x2 %0, %2, %4, t;\nfma.rn.f16x2 %1, %2, %5, u;\n}"
      : "=&r"(o_r), "=&r"(o_i) : "r"(br), "r"(bi), "r"(s.r), "r"(s.i));
}
struct HTile { uint32_t r[4], i[4]; };
__device__ __forceinline__ void tile_set(HTile& t, int k, cplx a, cplx b) { t.r[k] = packh(a.r, b.r); t.i[k] = packh(a.i, b.i); }
__device__ __forceinline__ void tile_upper(HTile& t, HSeed s) { hcmul(t.r[2], t.i[2], t.r[0], t.i[0], s); hcmul(t.r[3], t.i[3], t.r[1], t.i[1], s); }
__device__ __forceinline__ HTile tile_shift(const HTile& t, HSeed s) {
  HTile o;
#pragma unroll
  for (int k = 0; k < 4; k++) hcmul(o.r[k], o.i[k], t.r[k], t.i[k], s);
  return o;
}
__device__ __forceinline__ void tile_put(const HTile& t, uint32_t a) {
  sts128(a, make_uint4(t.r[0], t.r[1], t.r[2], t.r[3]));
  sts128(a + 512, make_uint4(t.i[0], t.i[1], t.i[2], t.i[3]));
}
__device__ __forceinline__ HTile tile_get(uint32_t a) { HTile o; ldsm4t(o.r, a); ldsm4t(o.i, a + 512); return o; }
__device__ __forceinline__ void tile_mma(float* T, const HTile& a0, const HTile& a1, const HTile& b) {
  mma_f16(T, a0.r[0], a0.r[1], a0.r[2], a0.r[3], b.r[0], b.r[1]);
  mma_f16(T, a0.i[0], a0.i[1], a0.i[2], a0.i[3], b.i[0], b.i[1]);
  mma_f16(T, a1.r[0], a1.r[1], a1.r[2], a1.r[3], b.r[2], b.r[3]);
  mma_f16(T, a1.i[0], a1.i[1], a1.i[2], a1.i[3], b.i[2], b.i[3]);
}
__device__ __forceinline__ void tile_mma2(float* T, float* U, const HTile& a0, const HTile& a1, const HTile& b, const HTile& c) {
  mma_f16(T, a0.r[0], a0.r[1], a0.r[2], a0.r[3], b.r[0], b.r[1]);
  mma_f16(U, a0.r[0], a0.r[1], a0.r[2], a0.r[3], c.r[0], c.r[1]);
  mma_f16(T, a0.i[0], a0.i[1], a0.i[2], a0.i[3], b.i[0], b.i[1]);
  mma_f16(U, a0.i[0], a0.i[1], a0.i[2], a0.i[3], c.i[0], c.i[1]);
  mma_f16(T, a1.r[0], a1.r[1], a1.r[2], a1.r[3], b.r[2], b.r[3]);
  mma_f16(U, a1.r[0], a1.r[1], a1.r[2], a1.r[3], c.r[2], c.r[3]);
  mma_f16(T, a1.i[0], a1.i[1], a1.i[2], a1.i[3], b.i[2], b.i[3]);
  mma_f16(U, a1.i[0], a1.i[1], a1.i[2], a1.i[3], c.i[2], c.i[3]);
}
__device__ __forceinline__ void kgen_unit(uint32_t tab, uint32_t taba, float ar2, float ai, cplx c, float (&T)[5][4]) {
  const cplx z1 = cexp_l(ar2, ai, 1.f), z16 = cexp_l(ar2, ai, 16.f), z256 = cexp_l(ar2, ai, 256.f);
  HTile a0, a1, b0, b1;
  {
    const cplx y1 = {z16.r, -z16.i}, y2 = csqr(y1), y3 = cmul(y2, y1), y4 = csqr(y2), y5 = cmul(y4, y1), y6 = csqr(y3), y7 = cmul(y4, y3);
    HTile t;
    tile_set(t, 0, {1.f, 0.f}, y1); tile_set(t, 1, y2, y3); tile_set(t, 2, y4, y5); tile_set(t, 3, y6, y7);
    const HTile u = tile_shift(t, hseed(csqr(y4)));
    __syncwarp();
    tile_put(t, tab); tile_put(u, tab + 1024);
    __syncwarp();
    a0 = tile_get(taba); a1 = tile_get(taba + 256);
  }
  const cplx z2 = csqr(z1), z4 = csqr(z2), z8 = csqr(z4);
  const HSeed h8 = hseed(z8);
  const cplx d = cmul(c, z256), e = cmul(d, z256);
  {
    const cplx z512 = csqr(z256), f = cmul(e, z512), f8 = cmul(f, z8), f16 = cmul(f, z16), e4 = cmul(e, z4);
    HTile t, u;
    tile_set(t, 0, e4, cmul(e, z8)); tile_set(t, 1, cmul(e4, z8), cmul(e, z16));
    tile_upper(t, hseed(z256));
    tile_set(u, 0, f8, f16); tile_set(u, 1, cmul(f8, z256), cmul(f16, z256));
    tile_upper(u, hseed(z512));
    __syncwarp();
    tile_put(t, tab); tile_put(u, tab + 1024);
    __syncwarp();
    b0 = tile_get(tab); b1 = tile_get(tab + 1024);
  }
  {
    const cplx d2 = cmul(d, z2), d4 = cmul(d, z4);
    HTile t;
    tile_set(t, 0, d2, d4); tile_set(t, 1, cmul(d2, z4), cmul(d, z8));
    tile_upper(t, h8);
    __syncwarp();
    tile_put(t, tab);
    __syncwarp();
    tile_mma2(T[3], T[4], a0, a1, b0, b1);
    b0 = tile_get(tab);
  }
  {
    const cplx c1 = cmul(c, z1), c2 = cmul(c, z2), c3 = cmul(c1, z2), c4 = cmul(c, z4);
    HTile t;
    tile_set(t, 0, c1, c2); tile_set(t, 1, c3, c4); tile_set(t, 2, cmul(c1, z4), cmul(c2, z4)); tile_set(t, 3, cmul(c3, z4), cmul(c4, z4));
    const HTile u = tile_shift(t, h8);
    __syncwarp();
    tile_put(t, tab); tile_put(u, tab + 1024);
    __syncwarp();
    tile_mma(T[2], a0, a1, b0);
    b0 = tile_get(tab); b1 = tile_get(tab + 1024);
    tile_mma2(T[0], T[1], a0, a1, b0, b1);
  }
}
struct ModeIn { uint2 ar, ai, br, bi, cr, ci; };
__device__ __forceinline__ ModeIn load_modes(const Params& p, int idx) {
  return {*(const uint2*)(p.a_re + idx), *(const uint2*)(p.a_im + idx), *(const uint2*)(p.b_re + idx),
          *(const uint2*)(p.b_im + idx), *(const uint2*)(p.c_re + idx), *(const uint2*)(p.c_im + idx)};
}
__device__ __forceinline__ float bf_el(uint2 v, int k) { const uint32_t x = (k & 2) ? v.y : v.x; return (k & 1) ? bf_hi(x) : bf_lo(x); }
struct KGen { float4 cur; float T[5][4]; };
__device__ __forceinline__ uint32_t kgen_slot(uint32_t sb, int ht, int u) {
  return sb + (u < 3 ? SM_KC + (ht >> 5) * (KC_STRIDE * 2) + (u - 1) * 512 + (ht & 31) * 16 + 16 : SM_HALO + 1024 + ht * 16);
}
__device__ __forceinline__ void kgen_setup(KGen& s, uint32_t sb, int cta, int ht, const ModeIn& in, bf16 logdt, bf16 dskip) {
  const float dt = __bfloat162float(__float2bfloat16_rn(expf(__bfloat162float(logdt))));
  float mx = 0.f, k0 = 0.f, ar2[4];
  cplx c[4];
#pragma unroll
  for (int k = 0; k < 4; k++) {
    ar2[k] = (dt * bf_el(in.ar, k)) * 1.4426950408889634f;
    c[k] = cmul({bf_el(in.cr, k), bf_el(in.ci, k)}, {dt * bf_el(in.br, k), dt * bf_el(in.bi, k)});
    k0 += c[k].r;
    mx = fmaxf(mx, fmaxf(fabsf(c[k].r), fabsf(c[k].i)) * ex2(fmaxf(ar2[k] * 2048.f, 0.f)));
  }
  const int ex = min(max(267 - (int)(__reduce_max_sync(~0u, __float_as_uint(mx)) >> 23), 1), 253);
  const float sc = __uint_as_float(ex << 23);
#pragma unroll
  for (int o = 16; o > 0; o >>= 1) k0 += __shfl_xor_sync(~0u, k0, o);
  if ((ht & 31) == 0) {
    const uint32_t kc = sb + SM_KC + (ht >> 5) * (KC_STRIDE * 2);
    sts16(kc, __bfloat16_as_ushort(__float2bfloat16_rn(k0 + __bfloat162float(dskip))));
    sts16(kc + 641 * 2, 0);
    sts32f(kc + 644 * 2, __uint_as_float((254 - ex) << 23));
  }
  s.cur = make_float4(ar2[0], dt * bf_el(in.ai, 0), c[0].r * sc, c[0].i * sc);
#pragma unroll
  for (int k = 1; k < 4; k++) sts128f(kgen_slot(sb, ht, k), ar2[k], dt * bf_el(in.ai, k), c[k].r * sc, c[k].i * sc);
#pragma unroll
  for (int i = 0; i < 5; i++) s.T[i][0] = s.T[i][1] = s.T[i][2] = s.T[i][3] = 0.f;
}
__device__ __forceinline__ void kgen_finish(KGen& s, uint32_t sb, int cta, int ht) {
  const int w = ht >> 5, lane = ht & 31, g = lane >> 2, t = lane & 3;
  const uint32_t kc = sb + SM_KC + w * KC_STRIDE * 2;
  __syncwarp();
  const float inv = __uint_as_float(lds32(kc + 644 * 2));
  auto put = [&](int idx, float v) {
    sts16(kc + idx * 2, __bfloat16_as_ushort(__float2bfloat16_rn(v)));
  };
#pragma unroll
  for (int hi = 0; hi < 2; hi++)
#pragma unroll
    for (int lo = 0; lo < 2; lo++) {
      const int i = g + 8 * hi, j = 2 * t + lo, e = 2 * hi + lo;
      put(16 * i + 1 + j, s.T[0][e] * inv);
      put(16 * i + 9 + j, s.T[1][e] * inv);
      put(257 + 8 * i + j, s.T[2][e] * inv);
      put(385 + 4 * i + (j & 3) + 64 * (j >> 2), s.T[3][e] * inv);
      put(513 + 2 * i + lo + 32 * t, s.T[4][e] * inv);
    }
}

__device__ __forceinline__ void expand_taps(uint32_t sb, int ht) {
  const int ch = ht >> 5, lane = ht & 31;
  const uint32_t kc = sb + SM_KC + ch * KC_STRIDE * 2;
  const uint32_t dst0 = sb + cv_pe(ch);
  auto put = [&](int G, uint32_t u0, uint32_t u1, uint32_t v0, uint32_t v1, uint32_t v2, uint32_t v3, uint32_t v4, uint32_t v5, uint32_t v6, uint32_t v7) {
    const uint32_t dst = dst0 + G * 32;
    sts128(dst, make_uint4(v0 | (u0 << 16), v1 | (u1 << 16), v2 | (v0 << 16), v3 | (v1 << 16)));
    sts128(dst + 16, make_uint4(v4 | (v2 << 16), v5 | (v3 << 16), v6 | (v4 << 16), v7 | (v5 << 16)));
  };
  {
    const uint4 q = lds128(kc + lane * 16);
    const uint32_t pv = lane ? lds32(kc + lane * 16 - 4) : 0u;
    const uint32_t dst = dst0 + (lane + 2) * 32;
    sts128(dst, make_uint4(__byte_perm(q.x, pv, 0x5410), __byte_perm(q.x, pv, 0x7632), __byte_perm(q.y, q.x, 0x5410), __byte_perm(q.y, q.x, 0x7632)));
    sts128(dst + 16, make_uint4(__byte_perm(q.z, q.y, 0x5410), __byte_perm(q.z, q.y, 0x7632), __byte_perm(q.w, q.z, 0x5410), __byte_perm(q.w, q.z, 0x7632)));
    if (lane < 4) sts128(dst0 + lane * 16, make_uint4(0, 0, 0, 0));
  }
  uint32_t a[5], b[2][3], fv[4];
  {
    const uint32_t s1 = kc + 2 * (256 + 4 * lane);
#pragma unroll
    for (int k = 0; k < 5; k++) a[k] = lds16(s1 + 2 * k);
#pragma unroll
    for (int u = 0; u < 2; u++) {
      const uint32_t s2 = kc + 2 * (384 + 2 * (lane + 32 * u));
#pragma unroll
      for (int k = 0; k < 3; k++) b[u][k] = lds16(s2 + 2 * k);
    }
#pragma unroll
    for (int k = 0; k < 4; k++) fv[k] = lds16(kc + 2 * (640 - 4 * lane - k));
  }
  const uint32_t am1 = lds16(kc + 2 * (lane ? 256 + 4 * lane : 255)), am2 = lds16(kc + 2 * (lane ? 255 + 4 * lane : 254));
  const uint32_t bm2 = lds16(kc + 2 * (lane ? 384 + 2 * lane : 383)), k1024 = lds16(kc + 2 * 512);
  put(34 + lane, am2, am1, a[0], a[0], a[1], a[2], a[2], a[2], a[3], a[4]);
#pragma unroll
  for (int u = 0; u < 2; u++) put(66 + lane + 32 * u, u ? b[u][0] : bm2, b[u][0], b[u][0], b[u][0], b[u][0], b[u][1], b[u][1], b[u][1], b[u][2], b[u][2]);
  if (lane < 10) {
    const uint32_t v = lane == 0 ? k1024 : 0u;
    put(130 + lane, v, v, v, v, v, v, v, 0u, 0u, 0u);
  }
  const uint32_t ft = sb + cv_ft(ch) + 4 * lane;
#pragma unroll
  for (int ty = 0; ty < 2; ty++) {
    const uint32_t v = fv[ty] | (fv[ty + 2] << 16);
    sts32f(ft + ty * 512, __uint_as_float(v));
    sts32f(ft + ty * 512 + 128, 0.f);
    sts32f(ft + ty * 512 + 256 + (lane < 2 ? 120 : -8), __uint_as_float(lane < 2 ? 0u : v));
    sts32f(ft + ty * 512 + 384, 0.f);
  }
}

__device__ __forceinline__ int role_id() { int v; asm volatile("mov.u32 %0, %%ctaid.x;" : "=r"(v)); return v; }
#define GMAP 8
__device__ __forceinline__ int role_rb(int cta) { return 4 * (cta >> 5) + (cta & 3); }
__device__ __forceinline__ int role_hg(int cta) { return 2 * (((cta >> 3) & 3) ^ (((cta >> 5) & 1) * 3)) + ((cta >> 2) & 1); }
__device__ __forceinline__ int role_rb2(int cta) { return cta >> 3; }
__device__ __forceinline__ int role_q2(int cta) { return cta & 7; }

__global__ void __launch_bounds__(NTHREADS, 1) fused_kernel(const __grid_constant__ Params p) {
  extern __shared__ __align__(1024) uint8_t smem[];
  const uint32_t sb = s32(smem);
  const int tid = threadIdx.x, lane = tid & 31;
  const int warp = __shfl_sync(~0u, tid >> 5, 0);
  const uint32_t bar = sb + SM_BAR;
  if (tid == 0) TS(0);
  const int cta0 = role_id();
  if (warp == 0 && elect_one()) {
    const int rb = role_rb(cta0), hg = role_hg(cta0);
#pragma unroll
    for (int c = 0; c < 2; c++) { mbar_init(bar + 8 * (B_XF + c), 1); mbar_init(bar + 8 * (B_KVF + c), 1); }
    fence_async_smem();
#pragma unroll
    for (int c = 0; c < 2; c++) {
      mbar_expect(bar + 8 * (B_XF + c), 16384);
      tma_ld(sb + SM_X + c * 16384, &p.mapX128, (rb >> 3) * DM + c * 64, (rb & 7) * 128, bar + 8 * (B_XF + c));
      mbar_expect(bar + 8 * (B_KVF + c), 24576);
      tma_ld3(sb + SM_W + c * 24576, &p.mapW3, hg * 64, c * 64, 0, bar + 8 * (B_KVF + c));
    }
  }
  if (warp == 1 && elect_one()) {
    const int rb = role_rb(cta0), hg = role_hg(cta0);
#pragma unroll
    for (int c = 2; c < 8; c++) mbar_init(bar + 8 * (B_XF + c), 1);
    mbar_init(bar + 8 * (B_KVF + 2), 1); mbar_init(bar + 8 * B_CW, 1);
    fence_async_smem();
    delay<D_START>();
    mbar_expect(bar + 8 * B_CW, 12288);
    tma_ld3(sb + SM_CW, &p.mapW3h, hg * 64, rb * 32, 0, bar + 8 * B_CW);
#pragma unroll
    for (int c = 2; c < 8; c++) {
      mbar_expect(bar + 8 * (B_XF + c), 16384);
      tma_ld(sb + SM_X + c * 16384, &p.mapX128, (rb >> 3) * DM + c * 64, (rb & 7) * 128, bar + 8 * (B_XF + c));
      if (c < 3) {
        mbar_expect(bar + 8 * (B_KVF + c), 24576);
        tma_ld3(sb + SM_W + c * 24576, &p.mapW3, hg * 64, c * 64, 0, bar + 8 * (B_KVF + c));
      }
    }
    TS(56);
  }
  if ((warp & 2) != 0 && warp < 15 && elect_one()) {
    const int grp = 1 + (warp & 1) + 2 * (warp >> 2), cnt = grp < 4 ? 1 : grp < 5 ? 2 : grp < 7 ? 4 : 8;
#pragma unroll
    for (int k = 0; k < 10; k++)
      if (k != 0 || grp > 3 || grp == 2) mbar_init(bar + 8 * (10 * grp + k), cnt);
    fence_async_smem();
  }

  if (warp < 8) {
    if (tid == 0) TS(1);
    asm volatile("setmaxnreg.inc.sync.aligned.u32 %0;" ::"n"(R_CONS));
    const int cta = role_id();
    auto warp_id = [] { return __shfl_sync(~0u, opaque_tid() >> 5, 0); };
    if (tid == 0) TS(54);
#pragma unroll 1
    for (int layer = 0; layer < 2; layer++) {
      { const int cw = warp_id(); attn_phase(p, sb, layer, role_rb(cta), role_hg(cta), cw >> 2, cw & 3); }
      if (p.stop == 1 + 3 * layer) return;
      { const int cw = warp_id(); proj_phase(p, sb, layer, role_rb2(cta), role_q2(cta), cw >> 2, cw & 3); }
      if (p.stop == 2 + 3 * layer) return;
      conv_phase(p, sb, layer, cta);
      if (p.stop == 3 + 3 * layer) return;
    }
    { const int cw = warp_id(); final_phase(p, sb, cta, cw >> 2, cw & 3); }
  } else if (warp < 12) {
    asm volatile("setmaxnreg.dec.sync.aligned.u32 %0;" ::"n"(R_HELP));
    const int ht = tid - 256;
    const int cta = role_id(), rb = role_rb(cta), hg = role_hg(cta);
    unsigned ep0 = 0;
    if (ht == 0) ep0 = ld_relaxed(&g_cnt[C_CS * 32]);
    bar_sync(0, NTHREADS);
    if (ht == 0) {
      asm volatile("st.shared.u32 [%0], %1;" ::"r"(sb + SM_EP), "r"(ep0 / NCTA) : "memory");
      mbar_arrive(bar + 8 * B_EP);
    }
    mbar_wait(bar + 8 * B_EP, 0);
    stats_publish(sb, 0, rb, hg, opaque_tid() - 256, part_tag(lds32(sb + SM_EP), 0));
    if (ht < 48) {
      const bf16* q = (&p.a_re)[ht >> 3];
      asm volatile("prefetch.global.L2 [%0];" ::"l"(q + cv_chan(cta, (ht >> 1) & 3) * 128 + (ht & 1) * 64));
    }
    {
      KGen kg;
      const uint32_t tab0 = sb + ((ht >> 5) < 2 ? SM_T : SM_T2 - 4096) + (ht >> 5) * 2048;
      const uint32_t tab = tab0 + (ht & 31) * 16, taba = tab0 + ((ht >> 3) & 1) * 1024 + (((ht >> 1) & 8) + (ht & 7)) * 16;
      delay<D_ST0>();
      stats_gather(sb, rb, opaque_tid() - 256, part_tag(lds32(sb + SM_EP), 0));
      if (ht == 0) TS(40);
      const int chn = cv_chan(cta, ht >> 5);
      const ModeIn modes = load_modes(p, chn * 128 + (ht & 31) * 4);
      const bf16 logdt = p.log_dt[chn], dskip = p.dskip[chn];
      if (!HALO_W14 && KG_START != 4) halo_receive(sb, 0, rb, hg, opaque_tid() - 256);
      if (KG_START == 1) mbar_wait(bar + 8 * B_HF, 0);
      kgen_setup(kg, sb, cta, ht, modes, logdt, dskip);
      if (!HALO_W14 && KG_START == 4) halo_receive(sb, 0, rb, hg, opaque_tid() - 256);
      if (KG_START == 2) mbar_wait(bar + 8 * B_HF, 0);
      if (KG_START == 3) mbar_wait(bar + 8 * B_QDONE, 0);
#pragma unroll 1
      for (int u = 0; u < 4; u++) {
        if (u == KG_PRE) {
          KTS(39);
          mbar_wait(bar + 8 * B_AD, 0);
          KTS(41);
        }
        kgen_unit(tab, taba, kg.cur.x, kg.cur.y, {kg.cur.z, kg.cur.w}, kg.T);
        kg.cur = lds128f(kgen_slot(sb, opaque_tid() - 256, u + 1));
      }
      kgen_finish(kg, sb, cta, opaque_tid() - 256);
    }
    KTS(51);
    bar_sync(4, 128);
#pragma unroll 1
    for (int layer = 0; layer < 2; layer++) {
      if (p.stop <= 1 + 3 * layer) return;
      mbar_wait(bar + 8 * (EXP_LATE ? B_PS : B_PDONE), layer);
      expand_taps(sb, opaque_tid() - 256);
      conv_zero(sb, opaque_tid() - 256);
      if (ht == 0) TS(52 + layer);
      warp_release(bar + 8 * B_PE);
      if (p.stop <= 2 + 3 * layer) return;
      {
        uint4 xr[4], st[4];
        const int c = opaque_tid() - 256;
        const SumAddr sa = conv_sum_addr(sb, c);
        conv_prep_load(sb, layer, cta, c, xr, st);
        conv_prep<true>(sb, layer, cta, c, xr, st, sa);
        if (layer == 1 && ht == 0) TS(62);
        const bf16* xup = g_xT + (size_t)(2 * layer * DM + cta) * LSEQ + (c + 128) * 8;
        st[0] = ldcg128(xup);
        mbar_wait(bar + 8 * (B_U + 3), layer);
#pragma unroll
        for (int lc = 0; lc < 4; lc++) {
          if (lc < 3) {
            if (!(S_OWN & (lc ? 2 : 1)) || ((S_OWN & 4) && layer == 1)) {
              conv_sums(sa, lc + 1, c);
              fence_async_smem();
              warp_release(bar + 8 * (B_S + lc + 1));
            }
            st[lc + 1] = ldcg128(xup + (lc + 1) * 128 * LSEQ);
          }
          conv_epi(sb, layer, cta, lc, c, xr[lc], st[lc]);
          warp_release(bar + 8 * (B_E + lc));
          if (layer == 1 && lc == 3 && ht == 0) TS(38);
        }
      }
      if (layer == 0 && p.stop > 3) {
        const int c1 = role_id();
        stats_publish(sb, 1, role_rb(c1), role_hg(c1), opaque_tid() - 256, part_tag(lds32(sb + SM_EP), 2));
        delay<D_ST>();
        stats_gather(sb, role_rb(c1), opaque_tid() - 256, part_tag(lds32(sb + SM_EP), 2));
        if (ht == 0) TS(25);
        if (!HALO_W14) halo_receive(sb, 1, role_rb(c1), role_hg(c1), opaque_tid() - 256);
      }
    }
  } else {
    asm volatile("setmaxnreg.dec.sync.aligned.u32 %0;" ::"n"(512 - 2 * R_CONS - R_HELP));
    const int cta = role_id(), rb = role_rb(cta), hg = role_hg(cta), rb2 = role_rb2(cta), q2 = role_q2(cta);
    bar_sync(0, NTHREADS);
    if (warp != 12) {
      mbar_wait(bar + 8 * B_EP, 0);
      const uint32_t tag = lds32(sb + SM_EP) % 7 + 1;
      mbar_wait(bar + 8 * B_CW, 0);
      colsum_publish(sb, rb, hg, tid - 416, tag);
      if (tid == 416) TS(50);
      delay<D_CS>();
      colsum_gather(sb, hg, tid - 416, tag);
      __syncwarp();
      if (tid == 416) TS(55);
    }
    if (elect_one()) mbar_arrive(bar + 8 * B_CSF);
    if (warp == 12) {
      if (elect_one()) {
        unsigned epoch = 0;
#pragma unroll 1
        for (int layer = 0; layer < 2; layer++) {
          auto ld_w = [&](int c, int slot) {
            const uint32_t b = bar + 8 * (B_KVF + c);
            mbar_expect(b, 24576);
            tma_ld3(sb + SM_W + slot * 24576, &p.mapW3, hg * 64, c * 64, 0, b);
          };
          if (layer == 0) {
            mbar_wait(bar + 8 * (B_KVF + 2), 0);
            if (rb2 < 4) tma_prefetch2(&p.mapWo128, q2 * 64, rb2 * 128);
            asm volatile("prefetch.tensormap [%0];" ::"l"(&p.mapO) : "memory");
            asm volatile("prefetch.tensormap [%0];" ::"l"(&p.mapO128) : "memory");
            asm volatile("prefetch.tensormap [%0];" ::"l"(&p.mapXT) : "memory");
            asm volatile("prefetch.tensormap [%0];" ::"l"(&p.mapXT3) : "memory");
            mbar_wait(bar + 8 * B_EP, 0);
            epoch = lds32(sb + SM_EP);
          } else {
            mbar_wait(bar + 8 * B_PDONE, 0);
            ld_w(0, 0); ld_w(1, 1);
            mbar_wait(bar + 8 * (W2_LATE ? B_U : B_RE), 0);
            ld_w(2, 2);
          }
          {
            int slot = 0;
#pragma unroll 1
            for (int c = 3; c < 8; c++) {
              mbar_wait(bar + 8 * (B_KVE + c - 3), layer);
              ld_w(c, slot);
              slot = slot == 2 ? 0 : slot + 1;
            }
          }
          if (p.stop <= 1 + 3 * layer) return;
          mbar_wait(bar + 8 * B_QDONE, layer);
          mbar_wait(bar + 8 * B_HF, layer);
#pragma unroll 1
          for (int c = 0; c < 4; c++) {
            const uint32_t b = bar + 8 * (B_WOF + c);
            mbar_expect(b, 16384);
            tma_ld(sb + SM_WO + c * 16384, &p.mapWo128, q2 * 64, c * 128, b);
          }
          {
            const uint32_t b = bar + 8 * B_RF;
            mbar_expect(b, 16384);
            if (layer == 0) tma_ld(sb + SM_R, &p.mapX128, (rb2 >> 3) * DM + q2 * 64, (rb2 & 7) * 128, b);
            else tma_ld3(sb + SM_R, &p.mapXT3, 0, DM + q2 * 64, rb2 * 2, b);
          }
          spin_until(&g_cnt[(C_O + rb2) * 32], (2 * epoch + layer + 1) * 16);
          fence_async_global();
#pragma unroll 1
          for (int c = 0; c < 8; c++) {
            const uint32_t b = bar + 8 * (B_OF + c);
            if (c == 4) { mbar_wait(bar + 8 * B_OST, layer); fence_async_smem(); }
            mbar_expect(b, 16384);
            tma_ld(sb + sm_o(c), &p.mapO128, c * 64, rb2 * 128, b);
          }
          if (p.stop <= 3 + 3 * layer) return;
        }
      }
    } else if (warp == 13) {
      if (elect_one() && p.stop > 3) {
        mbar_wait(bar + 8 * B_GB, 0);
        const unsigned target = (lds32(sb + SM_EP) + 1) * NCTA;
        auto ld_x = [&](int c) {
          mbar_expect(bar + 8 * (B_XF + c), 16384);
          tma_ld3(sb + SM_X + c * 16384, &p.mapXT3, 0, DM + c * 64, rb * 2, bar + 8 * (B_XF + c));
        };
        int done = 0, it = 0;
        while (done < 4) {
          const uint4 v = ld_tagged((const uint4*)&g_cnt[C_G1 * 32]);
          const int n = (int)(v.x - target) < 0 ? 0 : (int)(v.y - target) < 0 ? 1 : (int)(v.z - target) < 0 ? 2 : (int)(v.w - target) < 0 ? 3 : 4;
          if (++it > (1 << 23)) __trap();
          if (n == done) continue;
          if (n == 4) TS(44);
          fence_async_global();
          fence_async_smem();
          const int first = n == 4 && done > 1 ? 6 + (hg >> 2) : -1;
          if (first >= 0) ld_x(first);
#pragma unroll 1
          for (int c = 2 * done; c < 2 * n; c++)
            if (c != first) ld_x(c);
          done = n;
        }
      }
    } else if (warp == 15) {
      mbar_wait(bar + 8 * B_EP, 0);
      const unsigned epoch = lds32(sb + SM_EP);
#pragma unroll 1
      for (int layer = 0; layer < 2; layer++) {
#pragma unroll 1
        for (int i = 0; i < 6; i++) {
          mbar_wait(bar + 8 * (B_KVF + (FILL_AT + i < 7 ? FILL_AT + i : 7)), layer);
          uint4* dst = (uint4*)(g_xT + (size_t)(i < 4 ? 2 * layer * DM + cv_chan(cta, i) : 3 * DM + cv_chan(cta, 2 * layer + i - 4)) * LSEQ) + lane;
#pragma unroll
          for (int k = 0; k < 8; k++) dst[32 * k] = make_uint4(~0u, ~0u, ~0u, ~0u);
        }
        if (lane < 8) ((uint4*)g_stats)[layer * 1024 + cta * 8 + lane] = make_uint4(0, 0, 0, 0);
        __syncwarp();
        if (elect_one()) {
          red_release(&g_cnt[C_CS * 32 + layer]);
          spin_until(&g_cnt[C_CS * 32 + layer], (epoch + 1) * NCTA);
          mbar_arrive(bar + 8 * B_ZF);
          if (layer == 0 && p.stop > 2) {
#pragma unroll 1
            for (int lc = 0; lc < 4; lc++) {
              mbar_wait(bar + 8 * (B_E + lc), 0);
              fence_reader();
              bulk_st(g_xT + (size_t)(DM + cv_chan(cta, lc)) * LSEQ, sb + cv_s(lc), 4096);
              bulk_commit();
              bulk_wait_all();
              red_relaxed(&g_cnt[C_G1 * 32 + lc]);
              if (lc == 3) TS(18);
            }
          }
        }
        __syncwarp();
        if (p.stop <= 3) return;
      }
    } else if (warp == 14) {
      mbar_wait(bar + 8 * B_EP, 0);
      const unsigned epoch = lds32(sb + SM_EP);
#pragma unroll 1
      for (int layer = 0; layer < 2; layer++) {
        if (p.stop <= 3 * layer) return;
        if (HALO_W14) halo_receive1(sb, layer, rb, hg, lane, 2 * epoch + layer + 1);
        if (p.stop <= 1 + 3 * layer) return;
        mbar_wait(bar + 8 * B_ZF, layer);
        mbar_wait(bar + 8 * (EXP_LATE ? B_PS : B_PDONE), layer);
        delay<D_PST>();
        proj_stats(layer, rb2, q2, lane, part_tag(epoch, 2 * layer + 1));
        if (layer == 1 && lane == 0) TS(5);
        delay<D_PREP>();
        if (lane == 0) mbar_arrive(bar + 8 * B_GB);
      }
    }
  }
}

typedef CUresult (*EncodeFn)(CUtensorMap*, CUtensorMapDataType, cuuint32_t, void*, const cuuint64_t*, const cuuint64_t*,
                             const cuuint32_t*, const cuuint32_t*, CUtensorMapInterleave, CUtensorMapSwizzle,
                             CUtensorMapL2promotion, CUtensorMapFloatOOBfill);

static void make_map(EncodeFn enc, CUtensorMap* m, void* ptr, uint64_t cols, uint64_t rows, uint32_t box_rows) {
  cuuint64_t dims[2] = {cols, rows};
  cuuint64_t strides[1] = {cols * 2};
  cuuint32_t box[2] = {64, box_rows};
  cuuint32_t es[2] = {1, 1};
  enc(m, CU_TENSOR_MAP_DATA_TYPE_BFLOAT16, 2, ptr, dims, strides, box, es, CU_TENSOR_MAP_INTERLEAVE_NONE,
      CU_TENSOR_MAP_SWIZZLE_128B, CU_TENSOR_MAP_L2_PROMOTION_L2_128B, CU_TENSOR_MAP_FLOAT_OOB_FILL_NONE);
}
static void make_map3(EncodeFn enc, CUtensorMap* m, void* ptr, uint64_t d0, uint64_t cols, uint64_t rows, uint64_t blk_stride,
                      uint64_t nblocks, uint32_t nblk, uint32_t box_rows = 64) {
  cuuint64_t dims[3] = {d0, rows, nblocks};
  cuuint64_t strides[2] = {cols * 2, blk_stride * 2};
  cuuint32_t box[3] = {64, box_rows, nblk};
  cuuint32_t es[3] = {1, 1, 1};
  enc(m, CU_TENSOR_MAP_DATA_TYPE_BFLOAT16, 3, ptr, dims, strides, box, es, CU_TENSOR_MAP_INTERLEAVE_NONE,
      CU_TENSOR_MAP_SWIZZLE_128B, CU_TENSOR_MAP_L2_PROMOTION_L2_128B, CU_TENSOR_MAP_FLOAT_OOB_FILL_NONE);
}

extern "C" void kernel_launch(void* const* d_in, const int* in_sizes, int n_in, void* d_out, int out_size) {
  static Params prm;
  static void* cached[13] = {nullptr};
  static bool attr_done = false;
  bool same = attr_done && cached[12] == d_out;
  for (int i = 0; i < 12 && same; i++) same = cached[i] == d_in[i];
  if (!same) {
    void* fn = nullptr;
    cudaDriverEntryPointQueryResult qr;
    cudaGetDriverEntryPoint("cuTensorMapEncodeTiled", &fn, cudaEnableDefault, &qr);
    EncodeFn enc = (EncodeFn)fn;
    void *pO, *pXT;
    cudaGetSymbolAddress(&pO, g_O);
    cudaGetSymbolAddress(&pXT, g_xT);
    make_map(enc, &prm.mapO, pO, DM, LSEQ, 64);
    make_map(enc, &prm.mapXT, pXT, LSEQ, 4 * DM, 64);
    prm.out = (bf16*)d_out;
    make_map(enc, &prm.mapX128, d_in[0], 2 * DM, LSEQ / 2, 128);
    make_map(enc, &prm.mapWo128, d_in[2], DM, DM, 128);
    make_map(enc, &prm.mapO128, pO, DM, LSEQ, 128);
    make_map3(enc, &prm.mapW3, d_in[1], DM, 3 * DM, DM, DM, 3, 3);
    make_map3(enc, &prm.mapW3h, d_in[1], DM, 3 * DM, DM, DM, 3, 3, 32);
    make_map3(enc, &prm.mapXT3, pXT, 64, LSEQ, 4 * DM, 64, 32, 2);
    prm.a_re = (const bf16*)d_in[4]; prm.a_im = (const bf16*)d_in[5];
    prm.b_re = (const bf16*)d_in[6]; prm.b_im = (const bf16*)d_in[7];
    prm.c_re = (const bf16*)d_in[8]; prm.c_im = (const bf16*)d_in[9];
    prm.log_dt = (const bf16*)d_in[10]; prm.dskip = (const bf16*)d_in[11];
    cudaFuncSetAttribute(fused_kernel, cudaFuncAttributeMaxDynamicSharedMemorySize, SM_TOTAL);
    for (int i = 0; i < 12; i++) cached[i] = d_in[i];
    cached[12] = d_out;
    attr_done = true;
  }
  prm.stop = 100;
    fused_kernel<<<NCTA, NTHREADS, SM_TOTAL>>>(prm);
}
```

```cpp
#include <cuda_runtime.h>
#include <cuda_bf16.h>
#include <cuda.h>
#include <stdint.h>

typedef __nv_bfloat16 bf16;

constexpr int LSEQ = 2048;
constexpr int DM = 512;
constexpr int NCTA = 128;
constexpr int NTHREADS = 512;
#define RR 0
#define KG_PRE 2
#define W2_LATE 1
#define FILL_AT 5
#define EXP_LATE 1
#define RFENCE 1
#define D_FIN 550
#define FIN_LL 4
#define D_PREP 500
#define D_PST 0
#define D_HALO 500
#define STAG 2
#define D_ST 0
#define TLAYER 1
#define KG_PD 1
#define SUM_F32 0
#define CS_LATE0 1
#define D_HALO1 0
#define KG_START 0
#define S_AHEAD0 1
#define S_AHEAD1 2
#define PAUSE 0
#define PARK_FIRST 0
#define E_WAIT 0
#define G_WAIT 2
#define HALO_W14 1
#define D_START 200
#define D_CS 300
#define D_ST0 400
#define KG_LAST 0
#define X_JIT 0
#define KG_GATE 2
#define R_CONS 192
#define R_HELP 88

constexpr int SM_X = 0;
constexpr int SM_W = 131072;
constexpr int SM_KVX = SM_X;
constexpr int SM_OST = SM_X + 32768;
constexpr int SM_WO = SM_X + 65536;
__host__ __device__ constexpr int sm_o(int c) { return c < 4 ? SM_W + c * 16384 : SM_X + (c - 4) * 16384; }
constexpr int SM_R = 196608;
constexpr int SM_T = 212992;
constexpr int SM_KC = 217088;
constexpr int KC_STRIDE = 648;
constexpr int SM_CS = SM_KC + 4 * KC_STRIDE * 2;
constexpr int SM_CW = SM_R + 8192;
constexpr int SM_EP = SM_CS + 768;
constexpr int SM_BAR = SM_EP + 16;
constexpr int SM_T2 = SM_BAR + 896;
constexpr int SM_HALO = SM_T2 + 4096;
constexpr int SM_ST = SM_HALO + 3072;
constexpr int SM_TOTAL = SM_HALO + 4096;
static_assert(SM_TOTAL <= 232448, "shared memory");

constexpr int CV_UH = 140 * 16;
constexpr int CV_PECH = 1120 * 4;
constexpr int CV_PBW = 2112 * 2;
__host__ __device__ constexpr int cv_s(int lc) { return SM_X + lc * 32768; }
__host__ __device__ constexpr int cv_u(int lc) { return cv_s(lc) + 4096; }
__host__ __device__ constexpr int cv_pe(int lc) { return cv_u(lc) + 2 * CV_UH; }
__host__ __device__ constexpr int cv_pb(int lc) { return cv_pe(lc) + CV_PECH; }
__host__ __device__ constexpr int cv_ft(int lc) { return cv_pb(lc) + 4 * CV_PBW; }
static_assert(cv_ft(0) + 1024 <= 32768, "conv buffers");
__host__ __device__ constexpr int cv_chan(int cta, int lc) { return cta + 128 * lc; }

enum {
  B_XF = 0,
  B_KVF = 8,
  B_OF = 16,
  B_WOF = 24,
  B_T = 31,
  B_RF = 28,
  B_RE = 29,
  B_CW = 30,
  B_GB = 35,
  B_EP = 36,
  B_ZF = 37,
  B_XV = 39,
  B_SD = 38,
  B_KVE = 40,
  B_AD = 45,
  B_OST = 46,
  B_QDONE = 47,
  B_PDONE = 48,
  B_S = 50,
  B_E = 54,
  B_P = 58,
  B_PE = 62,
  B_STF = 63,
  B_CSF = 64,
  B_HF = 65,
  B_U = 70,
  B_PS = 74,
  B_COUNT = 80
};

enum {
  C_CS = 0,
  C_G1 = 2,
  C_O = 4,
  C_F = 20,
  C_COUNT = 24
};

__device__ __align__(128) unsigned g_cnt[C_COUNT * 32];
__device__ __align__(1024) bf16 g_O[LSEQ * DM];
__device__ __align__(1024) bf16 g_xT[4 * DM * LSEQ];
__device__ __align__(1024) float g_stats[2 * LSEQ * 2];
__device__ __align__(1024) uint4 g_colsum[8 * 16 * 48];
__device__ __align__(1024) uint4 g_halo[16 * 8 * 192];
__device__ __align__(1024) uint2 g_part[16 * 8 * 128];
#define TS(i) do { } while (0)

#define ATS(i, th) do { } while (0)
#define KTS(i) do { if (ht == 0) TS(i); } while (0)
#define FTS(i) do { } while (0)
#define LTS(i) do { } while (0)

#define STOP 100

struct Params {
  CUtensorMap mapO, mapXT, mapX128, mapWo128, mapO128, mapW3, mapW3h, mapXT3;
  const bf16 *a_re, *a_im, *b_re, *b_im, *c_re, *c_im, *log_dt, *dskip;
  bf16* out;
  int stop;
};

__device__ __forceinline__ uint32_t s32(const void* p) { return (uint32_t)__cvta_generic_to_shared(p); }
__device__ __forceinline__ void mbar_init(uint32_t b, int c) { asm volatile("mbarrier.init.shared::cta.b64 [%0], %1;" ::"r"(b), "r"(c) : "memory"); }
__device__ __forceinline__ void mbar_expect(uint32_t b, int bytes) { asm volatile("mbarrier.arrive.expect_tx.shared::cta.b64 _, [%0], %1;" ::"r"(b), "r"(bytes) : "memory"); }
__device__ __forceinline__ void mbar_arrive(uint32_t b) { asm volatile("mbarrier.arrive.shared::cta.b64 _, [%0];" ::"r"(b) : "memory"); }
__device__ __forceinline__ void mbar_arrive_if(uint32_t b, bool c) {
  asm volatile("{\n.reg .pred p;\nsetp.ne.u32 p, %1, 0;\n@p mbarrier.arrive.shared::cta.b64 _, [%0];\n}" ::"r"(b), "r"((uint32_t)c) : "memory");
}
__device__ __forceinline__ void mbar_wait(uint32_t b, int parity) {
  asm volatile("{\n.reg .pred p;\nWAIT_LOOP:\nmbarrier.try_wait.parity.shared::cta.b64 p, [%0], %1;\n@p bra WAIT_DONE;\nbra WAIT_LOOP;\nWAIT_DONE:\n}" ::"r"(b), "r"(parity) : "memory");
}
template <int N> __device__ __forceinline__ void delay() {
  if constexpr (N > 0) {
    uint32_t t0, t;
    asm volatile("mov.u32 %0, %%clock;" : "=r"(t0));
    do { asm volatile("mov.u32 %0, %%clock;" : "=r"(t)); } while (t - t0 < N);
  }
}
#define SF 3
template <int ID> __device__ __forceinline__ void sched_fence() {
  if constexpr ((SF >> ID) & 1)
    asm volatile("{\n.reg .pred p;\n.reg .u32 t;\nsetp.eq.u32 p, %0, 0;\n@p mov.u32 t, %%clock;\n@p st.shared.u32 [%0], t;\n}" ::"r"(gridDim.x) : "memory");
}
__device__ __forceinline__ int opaque_tid() { int v; asm volatile("mov.u32 %0, %%tid.x;" : "=r"(v)); return v; }
__device__ __forceinline__ bool elect_one() {
  uint32_t r;
  asm volatile("{\n.reg .pred p;\nelect.sync _|p, 0xffffffff;\nselp.u32 %0, 1, 0, p;\n}" : "=r"(r));
  return r != 0;
}
__device__ __forceinline__ void tma_ld(uint32_t dst, const CUtensorMap* m, int c0, int c1, uint32_t bar) {
  asm volatile("cp.async.bulk.tensor.2d.shared::cluster.global.mbarrier::complete_tx::bytes [%0], [%1, {%3, %4}], [%2];"
               ::"r"(dst), "l"(m), "r"(bar), "r"(c0), "r"(c1) : "memory");
}
__device__ __forceinline__ void tma_ld3(uint32_t dst, const CUtensorMap* m, int c0, int c1, int c2, uint32_t bar) {
  asm volatile("cp.async.bulk.tensor.3d.shared::cluster.global.mbarrier::complete_tx::bytes [%0], [%1, {%3, %4, %5}], [%2];"
               ::"r"(dst), "l"(m), "r"(bar), "r"(c0), "r"(c1), "r"(c2) : "memory");
}
__device__ __forceinline__ void tma_prefetch2(const CUtensorMap* m, int c0, int c1) {
  asm volatile("cp.async.bulk.prefetch.tensor.2d.L2.global.tile [%0, {%1, %2}];" ::"l"(m), "r"(c0), "r"(c1) : "memory");
}
__device__ __forceinline__ void tma_prefetch3(const CUtensorMap* m, int c0, int c1, int c2) {
  asm volatile("cp.async.bulk.prefetch.tensor.3d.L2.global.tile [%0, {%1, %2, %3}];" ::"l"(m), "r"(c0), "r"(c1), "r"(c2) : "memory");
}
__device__ __forceinline__ void tma_st(const CUtensorMap* m, int c0, int c1, uint32_t src) {
  asm volatile("cp.async.bulk.tensor.2d.global.shared::cta.bulk_group [%0, {%2, %3}], [%1];" ::"l"(m), "r"(src), "r"(c0), "r"(c1) : "memory");
}
__device__ __forceinline__ void bulk_ld(uint32_t dst, const void* src, int bytes, uint32_t bar) {
  asm volatile("cp.async.bulk.shared::cluster.global.mbarrier::complete_tx::bytes [%0], [%1], %2, [%3];" ::"r"(dst), "l"(src), "r"(bytes), "r"(bar) : "memory");
}
__device__ __forceinline__ void bulk_st(void* dst, uint32_t src, int bytes) {
  asm volatile("cp.async.bulk.global.shared::cta.bulk_group [%0], [%1], %2;" ::"l"(dst), "r"(src), "r"(bytes) : "memory");
}
__device__ __forceinline__ void bulk_red_add_f32(void* dst, uint32_t src, int bytes) {
  asm volatile("cp.reduce.async.bulk.global.shared::cta.bulk_group.add.f32 [%0], [%1], %2;" ::"l"(dst), "r"(src), "r"(bytes) : "memory");
}
__device__ __forceinline__ void bulk_commit() { asm volatile("cp.async.bulk.commit_group;" ::: "memory"); }
__device__ __forceinline__ void bulk_wait_all() { asm volatile("cp.async.bulk.wait_group 0;" ::: "memory"); }
__device__ __forceinline__ void fence_async_smem() { asm volatile("fence.proxy.async.shared::cta;" ::: "memory"); }
__device__ __forceinline__ void fence_writer() { if (!RFENCE) fence_async_smem(); }
__device__ __forceinline__ void fence_reader() { if (RFENCE) fence_async_smem(); }
__device__ __forceinline__ void fence_async_global() { asm volatile("fence.proxy.async.global;" ::: "memory"); }
__device__ __forceinline__ void bar_sync(int id, int n) { asm volatile("bar.sync %0, %1;" ::"r"(id), "r"(n) : "memory"); }
__device__ __forceinline__ void bar_arrive(int id, int n) { asm volatile("bar.arrive %0, %1;" ::"r"(id), "r"(n) : "memory"); }
__device__ __forceinline__ void wg_fence() { asm volatile("wgmma.fence.sync.aligned;" ::: "memory"); }
__device__ __forceinline__ void wg_commit() { asm volatile("wgmma.commit_group.sync.aligned;" ::: "memory"); }
template <int N> __device__ __forceinline__ void wg_wait() { asm volatile("wgmma.wait_group.sync.aligned %0;" ::"n"(N) : "memory"); }
__device__ __forceinline__ uint64_t mkdesc(uint32_t addr, uint32_t lbo, uint32_t sbo, int sw) {
  return (uint64_t)((addr & 0x3FFFF) >> 4) | ((uint64_t)(lbo >> 4) << 16) | ((uint64_t)(sbo >> 4) << 32) | ((uint64_t)sw << 62);
}
__device__ __forceinline__ void ldsm4(uint32_t* r, uint32_t a) {
  asm volatile("ldmatrix.sync.aligned.m8n8.x4.shared.b16 {%0,%1,%2,%3}, [%4];" : "=r"(r[0]), "=r"(r[1]), "=r"(r[2]), "=r"(r[3]) : "r"(a) : "memory");
}
__device__ __forceinline__ void ldsm4t(uint32_t* r, uint32_t a) {
  asm volatile("ldmatrix.sync.aligned.m8n8.x4.trans.shared.b16 {%0,%1,%2,%3}, [%4];" : "=r"(r[0]), "=r"(r[1]), "=r"(r[2]), "=r"(r[3]) : "r"(a) : "memory");
}
__device__ __forceinline__ void stsm4(uint32_t a, uint32_t r0, uint32_t r1, uint32_t r2, uint32_t r3) {
  asm volatile("stmatrix.sync.aligned.m8n8.x4.shared.b16 [%0], {%1,%2,%3,%4};" ::"r"(a), "r"(r0), "r"(r1), "r"(r2), "r"(r3) : "memory");
}
__device__ __forceinline__ void stsm4t(uint32_t a, uint32_t r0, uint32_t r1, uint32_t r2, uint32_t r3) {
  asm volatile("stmatrix.sync.aligned.m8n8.x4.trans.shared.b16 [%0], {%1,%2,%3,%4};" ::"r"(a), "r"(r0), "r"(r1), "r"(r2), "r"(r3) : "memory");
}
__device__ __forceinline__ uint32_t movm_t(uint32_t a) { uint32_t r; asm volatile("movmatrix.sync.aligned.m8n8.trans.b16 %0, %1;" : "=r"(r) : "r"(a)); return r; }
__device__ __forceinline__ uint32_t lds32(uint32_t a) { uint32_t v; asm volatile("ld.shared.b32 %0, [%1];" : "=r"(v) : "r"(a) : "memory"); return v; }
__device__ __forceinline__ float2 lds64f(uint32_t a) { float2 v; asm volatile("ld.shared.v2.f32 {%0,%1}, [%2];" : "=f"(v.x), "=f"(v.y) : "r"(a) : "memory"); return v; }
__device__ __forceinline__ float4 lds128f(uint32_t a) { float4 v; asm volatile("ld.shared.v4.f32 {%0,%1,%2,%3}, [%4];" : "=f"(v.x), "=f"(v.y), "=f"(v.z), "=f"(v.w) : "r"(a) : "memory"); return v; }
__device__ __forceinline__ uint4 lds128(uint32_t a) { uint4 v; asm volatile("ld.shared.v4.b32 {%0,%1,%2,%3}, [%4];" : "=r"(v.x), "=r"(v.y), "=r"(v.z), "=r"(v.w) : "r"(a) : "memory"); return v; }
__device__ __forceinline__ void sts128(uint32_t a, uint4 v) { asm volatile("st.shared.v4.b32 [%0], {%1,%2,%3,%4};" ::"r"(a), "r"(v.x), "r"(v.y), "r"(v.z), "r"(v.w) : "memory"); }
__device__ __forceinline__ void sts128f(uint32_t a, float x, float y, float z, float w) { asm volatile("st.shared.v4.f32 [%0], {%1,%2,%3,%4};" ::"r"(a), "f"(x), "f"(y), "f"(z), "f"(w) : "memory"); }
__device__ __forceinline__ void sts32f(uint32_t a, float v) { asm volatile("st.shared.f32 [%0], %1;" ::"r"(a), "f"(v) : "memory"); }
__device__ __forceinline__ void sts16(uint32_t a, uint16_t v) { asm volatile("st.shared.u16 [%0], %1;" ::"r"(a), "h"(v) : "memory"); }
__device__ __forceinline__ uint32_t lds16(uint32_t a) { uint16_t v; asm volatile("ld.shared.u16 %0, [%1];" : "=h"(v) : "r"(a) : "memory"); return v; }
__device__ __forceinline__ uint32_t packbf(float lo, float hi) { uint32_t r; asm("cvt.rn.bf16x2.f32 %0, %1, %2;" : "=r"(r) : "f"(hi), "f"(lo)); return r; }
__device__ __forceinline__ float bf_lo(uint32_t v) { return __uint_as_float(v << 16); }
__device__ __forceinline__ float bf_hi(uint32_t v) { return __uint_as_float(v & 0xffff0000u); }
__device__ __forceinline__ float ex2(float x) { float r; asm("ex2.approx.ftz.f32 %0, %1;" : "=f"(r) : "f"(x)); return r; }
__device__ __forceinline__ float rsqrt_approx(float x) { float r; asm("rsqrt.approx.ftz.f32 %0, %1;" : "=f"(r) : "f"(x)); return r; }
__device__ __forceinline__ float rcp_approx(float x) { float r; asm("rcp.approx.ftz.f32 %0, %1;" : "=f"(r) : "f"(x)); return r; }
__device__ __forceinline__ void mma_bf16(float* d, const uint32_t* a, uint32_t b0, uint32_t b1) {
  asm("mma.sync.aligned.m16n8k16.row.col.f32.bf16.bf16.f32 {%0,%1,%2,%3}, {%4,%5,%6,%7}, {%8,%9}, {%0,%1,%2,%3};"
               : "+f"(d[0]), "+f"(d[1]), "+f"(d[2]), "+f"(d[3]) : "r"(a[0]), "r"(a[1]), "r"(a[2]), "r"(a[3]), "r"(b0), "r"(b1));
}
__device__ __forceinline__ void mma_bf16_k8(float* d, uint32_t a0, uint32_t a1, uint32_t b) {
  asm("mma.sync.aligned.m16n8k8.row.col.f32.bf16.bf16.f32 {%0,%1,%2,%3}, {%4,%5}, {%6}, {%0,%1,%2,%3};"
      : "+f"(d[0]), "+f"(d[1]), "+f"(d[2]), "+f"(d[3]) : "r"(a0), "r"(a1), "r"(b));
}
__device__ __forceinline__ void red_release(unsigned* p) { asm volatile("red.release.gpu.global.add.u32 [%0], 1;" ::"l"(p) : "memory"); }
__device__ __forceinline__ void red_relaxed(unsigned* p) { asm volatile("red.relaxed.gpu.global.add.u32 [%0], 1;" ::"l"(p) : "memory"); }
__device__ __forceinline__ unsigned ld_relaxed(const unsigned* p) { unsigned v; asm volatile("ld.relaxed.gpu.global.u32 %0, [%1];" : "=r"(v) : "l"(p) : "memory"); return v; }
__device__ __forceinline__ void spin_until(const unsigned* p, unsigned target) {
  int it = 0;
  while ((int)(ld_relaxed(p) - target) < 0) {
    if (++it > (1 << 23)) __trap();
  }
}
__device__ __forceinline__ uint4 ldcg128(const void* p) { uint4 v; asm volatile("ld.global.cg.v4.b32 {%0,%1,%2,%3}, [%4];" : "=r"(v.x), "=r"(v.y), "=r"(v.z), "=r"(v.w) : "l"(p) : "memory"); return v; }
__device__ __forceinline__ uint4 ld_tagged(const uint4* p) { uint4 v; asm volatile("ld.relaxed.gpu.global.v4.u32 {%0,%1,%2,%3}, [%4];" : "=r"(v.x), "=r"(v.y), "=r"(v.z), "=r"(v.w) : "l"(p) : "memory"); return v; }
__device__ __forceinline__ uint2 ld_part(const uint2* p) { uint2 v; asm volatile("ld.relaxed.gpu.global.v2.u32 {%0,%1}, [%2];" : "=r"(v.x), "=r"(v.y) : "l"(p) : "memory"); return v; }
__device__ __forceinline__ void st_part(uint2* p, float s, float q, uint32_t tag) {
  asm volatile("st.relaxed.gpu.global.v2.u32 [%0], {%1,%2};" ::"l"(p), "r"(__float_as_uint(s)), "r"((__float_as_uint(q) & ~7u) | tag) : "memory");
}
__device__ __forceinline__ uint32_t part_tag(uint32_t epoch, int k) { return (4 * (epoch % 7) + k) % 7 + 1; }
__device__ __forceinline__ void st_tagged3(uint4* p, uint32_t a, uint32_t b, uint32_t c, uint32_t tag) { asm volatile("st.relaxed.gpu.global.v4.u32 [%0], {%1,%2,%3,%4};" ::"l"(p), "r"(a), "r"(b), "r"(c), "r"(tag) : "memory"); }
__device__ __forceinline__ uint32_t hadd2(uint32_t a, uint32_t b) { uint32_t r; asm("add.rn.bf16x2 %0, %1, %2;" : "=r"(r) : "r"(a), "r"(b)); return r; }
__device__ __forceinline__ uint32_t hmul2(uint32_t a, uint32_t b) { uint32_t r; asm("mul.rn.bf16x2 %0, %1, %2;" : "=r"(r) : "r"(a), "r"(b)); return r; }

template<int N,int TB> __device__ __forceinline__ void wgmma_rs(float* d, const uint32_t* a, uint64_t db, int sd);
template<int N,int TA,int TB> __device__ __forceinline__ void wgmma_ss(float* d, uint64_t da, uint64_t db, int sd);
template<> __device__ __forceinline__ void wgmma_rs<128,0>(float* d, const uint32_t* a, uint64_t db, int sd) {
  asm volatile("{\n.reg .pred p;\nsetp.ne.b32 p, %69, 0;\nwgmma.mma_async.sync.aligned.m64n128k16.f32.bf16.bf16 {%0,%1,%2,%3,%4,%5,%6,%7,%8,%9,%10,%11,%12,%13,%14,%15,%16,%17,%18,%19,%20,%21,%22,%23,%24,%25,%26,%27,%28,%29,%30,%31,%32,%33,%34,%35,%36,%37,%38,%39,%40,%41,%42,%43,%44,%45,%46,%47,%48,%49,%50,%51,%52,%53,%54,%55,%56,%57,%58,%59,%60,%61,%62,%63}, {%64,%65,%66,%67}, %68, p, 1, 1, 0;\n}\n"
   : "+f"(d[0]),"+f"(d[1]),"+f"(d[2]),"+f"(d[3]),"+f"(d[4]),"+f"(d[5]),"+f"(d[6]),"+f"(d[7]),"+f"(d[8]),"+f"(d[9]),"+f"(d[10]),"+f"(d[11]),"+f"(d[12]),"+f"(d[13]),"+f"(d[14]),"+f"(d[15]),"+f"(d[16]),"+f"(d[17]),"+f"(d[18]),"+f"(d[19]),"+f"(d[20]),"+f"(d[21]),"+f"(d[22]),"+f"(d[23]),"+f"(d[24]),"+f"(d[25]),"+f"(d[26]),"+f"(d[27]),"+f"(d[28]),"+f"(d[29]),"+f"(d[30]),"+f"(d[31]),"+f"(d[32]),"+f"(d[33]),"+f"(d[34]),"+f"(d[35]),"+f"(d[36]),"+f"(d[37]),"+f"(d[38]),"+f"(d[39]),"+f"(d[40]),"+f"(d[41]),"+f"(d[42]),"+f"(d[43]),"+f"(d[44]),"+f"(d[45]),"+f"(d[46]),"+f"(d[47]),"+f"(d[48]),"+f"(d[49]),"+f"(d[50]),"+f"(d[51]),"+f"(d[52]),"+f"(d[53]),"+f"(d[54]),"+f"(d[55]),"+f"(d[56]),"+f"(d[57]),"+f"(d[58]),"+f"(d[59]),"+f"(d[60]),"+f"(d[61]),"+f"(d[62]),"+f"(d[63])
   : "r"(a[0]), "r"(a[1]), "r"(a[2]), "r"(a[3]), "l"(db), "r"(sd));
}
template<> __device__ __forceinline__ void wgmma_rs<120,0>(float* d, const uint32_t* a, uint64_t db, int sd) {
  asm volatile("{\n.reg .pred p;\nsetp.ne.b32 p, %65, 0;\nwgmma.mma_async.sync.aligned.m64n120k16.f32.bf16.bf16 {%0,%1,%2,%3,%4,%5,%6,%7,%8,%9,%10,%11,%12,%13,%14,%15,%16,%17,%18,%19,%20,%21,%22,%23,%24,%25,%26,%27,%28,%29,%30,%31,%32,%33,%34,%35,%36,%37,%38,%39,%40,%41,%42,%43,%44,%45,%46,%47,%48,%49,%50,%51,%52,%53,%54,%55,%56,%57,%58,%59}, {%60,%61,%62,%63}, %64, p, 1, 1, 0;\n}\n"
   : "+f"(d[0]),"+f"(d[1]),"+f"(d[2]),"+f"(d[3]),"+f"(d[4]),"+f"(d[5]),"+f"(d[6]),"+f"(d[7]),"+f"(d[8]),"+f"(d[9]),"+f"(d[10]),"+f"(d[11]),"+f"(d[12]),"+f"(d[13]),"+f"(d[14]),"+f"(d[15]),"+f"(d[16]),"+f"(d[17]),"+f"(d[18]),"+f"(d[19]),"+f"(d[20]),"+f"(d[21]),"+f"(d[22]),"+f"(d[23]),"+f"(d[24]),"+f"(d[25]),"+f"(d[26]),"+f"(d[27]),"+f"(d[28]),"+f"(d[29]),"+f"(d[30]),"+f"(d[31]),"+f"(d[32]),"+f"(d[33]),"+f"(d[34]),"+f"(d[35]),"+f"(d[36]),"+f"(d[37]),"+f"(d[38]),"+f"(d[39]),"+f"(d[40]),"+f"(d[41]),"+f"(d[42]),"+f"(d[43]),"+f"(d[44]),"+f"(d[45]),"+f"(d[46]),"+f"(d[47]),"+f"(d[48]),"+f"(d[49]),"+f"(d[50]),"+f"(d[51]),"+f"(d[52]),"+f"(d[53]),"+f"(d[54]),"+f"(d[55]),"+f"(d[56]),"+f"(d[57]),"+f"(d[58]),"+f"(d[59])
   : "r"(a[0]), "r"(a[1]), "r"(a[2]), "r"(a[3]), "l"(db), "r"(sd));
}
template<> __device__ __forceinline__ void wgmma_rs<112,0>(float* d, const uint32_t* a, uint64_t db, int sd) {
  asm volatile("{\n.reg .pred p;\nsetp.ne.b32 p, %61, 0;\nwgmma.mma_async.sync.aligned.m64n112k16.f32.bf16.bf16 {%0,%1,%2,%3,%4,%5,%6,%7,%8,%9,%10,%11,%12,%13,%14,%15,%16,%17,%18,%19,%20,%21,%22,%23,%24,%25,%26,%27,%28,%29,%30,%31,%32,%33,%34,%35,%36,%37,%38,%39,%40,%41,%42,%43,%44,%45,%46,%47,%48,%49,%50,%51,%52,%53,%54,%55}, {%56,%57,%58,%59}, %60, p, 1, 1, 0;\n}\n"
   : "+f"(d[0]),"+f"(d[1]),"+f"(d[2]),"+f"(d[3]),"+f"(d[4]),"+f"(d[5]),"+f"(d[6]),"+f"(d[7]),"+f"(d[8]),"+f"(d[9]),"+f"(d[10]),"+f"(d[11]),"+f"(d[12]),"+f"(d[13]),"+f"(d[14]),"+f"(d[15]),"+f"(d[16]),"+f"(d[17]),"+f"(d[18]),"+f"(d[19]),"+f"(d[20]),"+f"(d[21]),"+f"(d[22]),"+f"(d[23]),"+f"(d[24]),"+f"(d[25]),"+f"(d[26]),"+f"(d[27]),"+f"(d[28]),"+f"(d[29]),"+f"(d[30]),"+f"(d[31]),"+f"(d[32]),"+f"(d[33]),"+f"(d[34]),"+f"(d[35]),"+f"(d[36]),"+f"(d[37]),"+f"(d[38]),"+f"(d[39]),"+f"(d[40]),"+f"(d[41]),"+f"(d[42]),"+f"(d[43]),"+f"(d[44]),"+f"(d[45]),"+f"(d[46]),"+f"(d[47]),"+f"(d[48]),"+f"(d[49]),"+f"(d[50]),"+f"(d[51]),"+f"(d[52]),"+f"(d[53]),"+f"(d[54]),"+f"(d[55])
   : "r"(a[0]), "r"(a[1]), "r"(a[2]), "r"(a[3]), "l"(db), "r"(sd));
}
template<> __device__ __forceinline__ void wgmma_rs<104,0>(float* d, const uint32_t* a, uint64_t db, int sd) {
  asm volatile("{\n.reg .pred p;\nsetp.ne.b32 p, %57, 0;\nwgmma.mma_async.sync.aligned.m64n104k16.f32.bf16.bf16 {%0,%1,%2,%3,%4,%5,%6,%7,%8,%9,%10,%11,%12,%13,%14,%15,%16,%17,%18,%19,%20,%21,%22,%23,%24,%25,%26,%27,%28,%29,%30,%31,%32,%33,%34,%35,%36,%37,%38,%39,%40,%41,%42,%43,%44,%45,%46,%47,%48,%49,%50,%51}, {%52,%53,%54,%55}, %56, p, 1, 1, 0;\n}\n"
   : "+f"(d[0]),"+f"(d[1]),"+f"(d[2]),"+f"(d[3]),"+f"(d[4]),"+f"(d[5]),"+f"(d[6]),"+f"(d[7]),"+f"(d[8]),"+f"(d[9]),"+f"(d[10]),"+f"(d[11]),"+f"(d[12]),"+f"(d[13]),"+f"(d[14]),"+f"(d[15]),"+f"(d[16]),"+f"(d[17]),"+f"(d[18]),"+f"(d[19]),"+f"(d[20]),"+f"(d[21]),"+f"(d[22]),"+f"(d[23]),"+f"(d[24]),"+f"(d[25]),"+f"(d[26]),"+f"(d[27]),"+f"(d[28]),"+f"(d[29]),"+f"(d[30]),"+f"(d[31]),"+f"(d[32]),"+f"(d[33]),"+f"(d[34]),"+f"(d[35]),"+f"(d[36]),"+f"(d[37]),"+f"(d[38]),"+f"(d[39]),"+f"(d[40]),"+f"(d[41]),"+f"(d[42]),"+f"(d[43]),"+f"(d[44]),"+f"(d[45]),"+f"(d[46]),"+f"(d[47]),"+f"(d[48]),"+f"(d[49]),"+f"(d[50]),"+f"(d[51])
   : "r"(a[0]), "r"(a[1]), "r"(a[2]), "r"(a[3]), "l"(db), "r"(sd));
}
template<> __device__ __forceinline__ void wgmma_rs<96,0>(float* d, const uint32_t* a, uint64_t db, int sd) {
  asm volatile("{\n.reg .pred p;\nsetp.ne.b32 p, %53, 0;\nwgmma.mma_async.sync.aligned.m64n96k16.f32.bf16.bf16 {%0,%1,%2,%3,%4,%5,%6,%7,%8,%9,%10,%11,%12,%13,%14,%15,%16,%17,%18,%19,%20,%21,%22,%23,%24,%25,%26,%27,%28,%29,%30,%31,%32,%33,%34,%35,%36,%37,%38,%39,%40,%41,%42,%43,%44,%45,%46,%47}, {%48,%49,%50,%51}, %52, p, 1, 1, 0;\n}\n"
   : "+f"(d[0]),"+f"(d[1]),"+f"(d[2]),"+f"(d[3]),"+f"(d[4]),"+f"(d[5]),"+f"(d[6]),"+f"(d[7]),"+f"(d[8]),"+f"(d[9]),"+f"(d[10]),"+f"(d[11]),"+f"(d[12]),"+f"(d[13]),"+f"(d[14]),"+f"(d[15]),"+f"(d[16]),"+f"(d[17]),"+f"(d[18]),"+f"(d[19]),"+f"(d[20]),"+f"(d[21]),"+f"(d[22]),"+f"(d[23]),"+f"(d[24]),"+f"(d[25]),"+f"(d[26]),"+f"(d[27]),"+f"(d[28]),"+f"(d[29]),"+f"(d[30]),"+f"(d[31]),"+f"(d[32]),"+f"(d[33]),"+f"(d[34]),"+f"(d[35]),"+f"(d[36]),"+f"(d[37]),"+f"(d[38]),"+f"(d[39]),"+f"(d[40]),"+f"(d[41]),"+f"(d[42]),"+f"(d[43]),"+f"(d[44]),"+f"(d[45]),"+f"(d[46]),"+f"(d[47])
   : "r"(a[0]), "r"(a[1]), "r"(a[2]), "r"(a[3]), "l"(db), "r"(sd));
}
template<> __device__ __forceinline__ void wgmma_rs<88,0>(float* d, const uint32_t* a, uint64_t db, int sd) {
  asm volatile("{\n.reg .pred p;\nsetp.ne.b32 p, %49, 0;\nwgmma.mma_async.sync.aligned.m64n88k16.f32.bf16.bf16 {%0,%1,%2,%3,%4,%5,%6,%7,%8,%9,%10,%11,%12,%13,%14,%15,%16,%17,%18,%19,%20,%21,%22,%23,%24,%25,%26,%27,%28,%29,%30,%31,%32,%33,%34,%35,%36,%37,%38,%39,%40,%41,%42,%43}, {%44,%45,%46,%47}, %48, p, 1, 1, 0;\n}\n"
   : "+f"(d[0]),"+f"(d[1]),"+f"(d[2]),"+f"(d[3]),"+f"(d[4]),"+f"(d[5]),"+f"(d[6]),"+f"(d[7]),"+f"(d[8]),"+f"(d[9]),"+f"(d[10]),"+f"(d[11]),"+f"(d[12]),"+f"(d[13]),"+f"(d[14]),"+f"(d[15]),"+f"(d[16]),"+f"(d[17]),"+f"(d[18]),"+f"(d[19]),"+f"(d[20]),"+f"(d[21]),"+f"(d[22]),"+f"(d[23]),"+f"(d[24]),"+f"(d[25]),"+f"(d[26]),"+f"(d[27]),"+f"(d[28]),"+f"(d[29]),"+f"(d[30]),"+f"(d[31]),"+f"(d[32]),"+f"(d[33]),"+f"(d[34]),"+f"(d[35]),"+f"(d[36]),"+f"(d[37]),"+f"(d[38]),"+f"(d[39]),"+f"(d[40]),"+f"(d[41]),"+f"(d[42]),"+f"(d[43])
   : "r"(a[0]), "r"(a[1]), "r"(a[2]), "r"(a[3]), "l"(db), "r"(sd));
}
template<> __device__ __forceinline__ void wgmma_rs<80,0>(float* d, const uint32_t* a, uint64_t db, int sd) {
  asm volatile("{\n.reg .pred p;\nsetp.ne.b32 p, %45, 0;\nwgmma.mma_async.sync.aligned.m64n80k16.f32.bf16.bf16 {%0,%1,%2,%3,%4,%5,%6,%7,%8,%9,%10,%11,%12,%13,%14,%15,%16,%17,%18,%19,%20,%21,%22,%23,%24,%25,%26,%27,%28,%29,%30,%31,%32,%33,%34,%35,%36,%37,%38,%39}, {%40,%41,%42,%43}, %44, p, 1, 1, 0;\n}\n"
   : "+f"(d[0]),"+f"(d[1]),"+f"(d[2]),"+f"(d[3]),"+f"(d[4]),"+f"(d[5]),"+f"(d[6]),"+f"(d[7]),"+f"(d[8]),"+f"(d[9]),"+f"(d[10]),"+f"(d[11]),"+f"(d[12]),"+f"(d[13]),"+f"(d[14]),"+f"(d[15]),"+f"(d[16]),"+f"(d[17]),"+f"(d[18]),"+f"(d[19]),"+f"(d[20]),"+f"(d[21]),"+f"(d[22]),"+f"(d[23]),"+f"(d[24]),"+f"(d[25]),"+f"(d[26]),"+f"(d[27]),"+f"(d[28]),"+f"(d[29]),"+f"(d[30]),"+f"(d[31]),"+f"(d[32]),"+f"(d[33]),"+f"(d[34]),"+f"(d[35]),"+f"(d[36]),"+f"(d[37]),"+f"(d[38]),"+f"(d[39])
   : "r"(a[0]), "r"(a[1]), "r"(a[2]), "r"(a[3]), "l"(db), "r"(sd));
}
template<> __device__ __forceinline__ void wgmma_rs<72,0>(float* d, const uint32_t* a, uint64_t db, int sd) {
  asm volatile("{\n.reg .pred p;\nsetp.ne.b32 p, %41, 0;\nwgmma.mma_async.sync.aligned.m64n72k16.f32.bf16.bf16 {%0,%1,%2,%3,%4,%5,%6,%7,%8,%9,%10,%11,%12,%13,%14,%15,%16,%17,%18,%19,%20,%21,%22,%23,%24,%25,%26,%27,%28,%29,%30,%31,%32,%33,%34,%35}, {%36,%37,%38,%39}, %40, p, 1, 1, 0;\n}\n"
   : "+f"(d[0]),"+f"(d[1]),"+f"(d[2]),"+f"(d[3]),"+f"(d[4]),"+f"(d[5]),"+f"(d[6]),"+f"(d[7]),"+f"(d[8]),"+f"(d[9]),"+f"(d[10]),"+f"(d[11]),"+f"(d[12]),"+f"(d[13]),"+f"(d[14]),"+f"(d[15]),"+f"(d[16]),"+f"(d[17]),"+f"(d[18]),"+f"(d[19]),"+f"(d[20]),"+f"(d[21]),"+f"(d[22]),"+f"(d[23]),"+f"(d[24]),"+f"(d[25]),"+f"(d[26]),"+f"(d[27]),"+f"(d[28]),"+f"(d[29]),"+f"(d[30]),"+f"(d[31]),"+f"(d[32]),"+f"(d[33]),"+f"(d[34]),"+f"(d[35])
   : "r"(a[0]), "r"(a[1]), "r"(a[2]), "r"(a[3]), "l"(db), "r"(sd));
}
template<> __device__ __forceinline__ void wgmma_rs<64,0>(float* d, const uint32_t* a, uint64_t db, int sd) {
  asm volatile("{\n.reg .pred p;\nsetp.ne.b32 p, %37, 0;\nwgmma.mma_async.sync.aligned.m64n64k16.f32.bf16.bf16 {%0,%1,%2,%3,%4,%5,%6,%7,%8,%9,%10,%11,%12,%13,%14,%15,%16,%17,%18,%19,%20,%21,%22,%23,%24,%25,%26,%27,%28,%29,%30,%31}, {%32,%33,%34,%35}, %36, p, 1, 1, 0;\n}\n"
   : "+f"(d[0]),"+f"(d[1]),"+f"(d[2]),"+f"(d[3]),"+f"(d[4]),"+f"(d[5]),"+f"(d[6]),"+f"(d[7]),"+f"(d[8]),"+f"(d[9]),"+f"(d[10]),"+f"(d[11]),"+f"(d[12]),"+f"(d[13]),"+f"(d[14]),"+f"(d[15]),"+f"(d[16]),"+f"(d[17]),"+f"(d[18]),"+f"(d[19]),"+f"(d[20]),"+f"(d[21]),"+f"(d[22]),"+f"(d[23]),"+f"(d[24]),"+f"(d[25]),"+f"(d[26]),"+f"(d[27]),"+f"(d[28]),"+f"(d[29]),"+f"(d[30]),"+f"(d[31])
   : "r"(a[0]), "r"(a[1]), "r"(a[2]), "r"(a[3]), "l"(db), "r"(sd));
}
template<> __device__ __forceinline__ void wgmma_ss<64,0,1>(float* d, uint64_t da, uint64_t db, int sd) {
  asm volatile("{\n.reg .pred p;\nsetp.ne.b32 p, %34, 0;\nwgmma.mma_async.sync.aligned.m64n64k16.f32.bf16.bf16 {%0,%1,%2,%3,%4,%5,%6,%7,%8,%9,%10,%11,%12,%13,%14,%15,%16,%17,%18,%19,%20,%21,%22,%23,%24,%25,%26,%27,%28,%29,%30,%31}, %32, %33, p, 1, 1, 0, 1;\n}\n"
   : "+f"(d[0]),"+f"(d[1]),"+f"(d[2]),"+f"(d[3]),"+f"(d[4]),"+f"(d[5]),"+f"(d[6]),"+f"(d[7]),"+f"(d[8]),"+f"(d[9]),"+f"(d[10]),"+f"(d[11]),"+f"(d[12]),"+f"(d[13]),"+f"(d[14]),"+f"(d[15]),"+f"(d[16]),"+f"(d[17]),"+f"(d[18]),"+f"(d[19]),"+f"(d[20]),"+f"(d[21]),"+f"(d[22]),"+f"(d[23]),"+f"(d[24]),"+f"(d[25]),"+f"(d[26]),"+f"(d[27]),"+f"(d[28]),"+f"(d[29]),"+f"(d[30]),"+f"(d[31])
   : "l"(da), "l"(db), "r"(sd));
}
template<> __device__ __forceinline__ void wgmma_ss<64,1,1>(float* d, uint64_t da, uint64_t db, int sd) {
  asm volatile("{\n.reg .pred p;\nsetp.ne.b32 p, %34, 0;\nwgmma.mma_async.sync.aligned.m64n64k16.f32.bf16.bf16 {%0,%1,%2,%3,%4,%5,%6,%7,%8,%9,%10,%11,%12,%13,%14,%15,%16,%17,%18,%19,%20,%21,%22,%23,%24,%25,%26,%27,%28,%29,%30,%31}, %32, %33, p, 1, 1, 1, 1;\n}\n"
   : "+f"(d[0]),"+f"(d[1]),"+f"(d[2]),"+f"(d[3]),"+f"(d[4]),"+f"(d[5]),"+f"(d[6]),"+f"(d[7]),"+f"(d[8]),"+f"(d[9]),"+f"(d[10]),"+f"(d[11]),"+f"(d[12]),"+f"(d[13]),"+f"(d[14]),"+f"(d[15]),"+f"(d[16]),"+f"(d[17]),"+f"(d[18]),"+f"(d[19]),"+f"(d[20]),"+f"(d[21]),"+f"(d[22]),"+f"(d[23]),"+f"(d[24]),"+f"(d[25]),"+f"(d[26]),"+f"(d[27]),"+f"(d[28]),"+f"(d[29]),"+f"(d[30]),"+f"(d[31])
   : "l"(da), "l"(db), "r"(sd));
}
template<> __device__ __forceinline__ void wgmma_ss<192,0,1>(float* d, uint64_t da, uint64_t db, int sd) {
  asm volatile("{\n.reg .pred p;\nsetp.ne.b32 p, %98, 0;\nwgmma.mma_async.sync.aligned.m64n192k16.f32.bf16.bf16 {%0,%1,%2,%3,%4,%5,%6,%7,%8,%9,%10,%11,%12,%13,%14,%15,%16,%17,%18,%19,%20,%21,%22,%23,%24,%25,%26,%27,%28,%29,%30,%31,%32,%33,%34,%35,%36,%37,%38,%39,%40,%41,%42,%43,%44,%45,%46,%47,%48,%49,%50,%51,%52,%53,%54,%55,%56,%57,%58,%59,%60,%61,%62,%63,%64,%65,%66,%67,%68,%69,%70,%71,%72,%73,%74,%75,%76,%77,%78,%79,%80,%81,%82,%83,%84,%85,%86,%87,%88,%89,%90,%91,%92,%93,%94,%95}, %96, %97, p, 1, 1, 0, 1;\n}\n"
   : "+f"(d[0]),"+f"(d[1]),"+f"(d[2]),"+f"(d[3]),"+f"(d[4]),"+f"(d[5]),"+f"(d[6]),"+f"(d[7]),"+f"(d[8]),"+f"(d[9]),"+f"(d[10]),"+f"(d[11]),"+f"(d[12]),"+f"(d[13]),"+f"(d[14]),"+f"(d[15]),"+f"(d[16]),"+f"(d[17]),"+f"(d[18]),"+f"(d[19]),"+f"(d[20]),"+f"(d[21]),"+f"(d[22]),"+f"(d[23]),"+f"(d[24]),"+f"(d[25]),"+f"(d[26]),"+f"(d[27]),"+f"(d[28]),"+f"(d[29]),"+f"(d[30]),"+f"(d[31]),"+f"(d[32]),"+f"(d[33]),"+f"(d[34]),"+f"(d[35]),"+f"(d[36]),"+f"(d[37]),"+f"(d[38]),"+f"(d[39]),"+f"(d[40]),"+f"(d[41]),"+f"(d[42]),"+f"(d[43]),"+f"(d[44]),"+f"(d[45]),"+f"(d[46]),"+f"(d[47]),"+f"(d[48]),"+f"(d[49]),"+f"(d[50]),"+f"(d[51]),"+f"(d[52]),"+f"(d[53]),"+f"(d[54]),"+f"(d[55]),"+f"(d[56]),"+f"(d[57]),"+f"(d[58]),"+f"(d[59]),"+f"(d[60]),"+f"(d[61]),"+f"(d[62]),"+f"(d[63]),"+f"(d[64]),"+f"(d[65]),"+f"(d[66]),"+f"(d[67]),"+f"(d[68]),"+f"(d[69]),"+f"(d[70]),"+f"(d[71]),"+f"(d[72]),"+f"(d[73]),"+f"(d[74]),"+f"(d[75]),"+f"(d[76]),"+f"(d[77]),"+f"(d[78]),"+f"(d[79]),"+f"(d[80]),"+f"(d[81]),"+f"(d[82]),"+f"(d[83]),"+f"(d[84]),"+f"(d[85]),"+f"(d[86]),"+f"(d[87]),"+f"(d[88]),"+f"(d[89]),"+f"(d[90]),"+f"(d[91]),"+f"(d[92]),"+f"(d[93]),"+f"(d[94]),"+f"(d[95])
   : "l"(da), "l"(db), "r"(sd));
}
template<> __device__ __forceinline__ void wgmma_ss<192,1,1>(float* d, uint64_t da, uint64_t db, int sd) {
  asm volatile("{\n.reg .pred p;\nsetp.ne.b32 p, %98, 0;\nwgmma.mma_async.sync.aligned.m64n192k16.f32.bf16.bf16 {%0,%1,%2,%3,%4,%5,%6,%7,%8,%9,%10,%11,%12,%13,%14,%15,%16,%17,%18,%19,%20,%21,%22,%23,%24,%25,%26,%27,%28,%29,%30,%31,%32,%33,%34,%35,%36,%37,%38,%39,%40,%41,%42,%43,%44,%45,%46,%47,%48,%49,%50,%51,%52,%53,%54,%55,%56,%57,%58,%59,%60,%61,%62,%63,%64,%65,%66,%67,%68,%69,%70,%71,%72,%73,%74,%75,%76,%77,%78,%79,%80,%81,%82,%83,%84,%85,%86,%87,%88,%89,%90,%91,%92,%93,%94,%95}, %96, %97, p, 1, 1, 1, 1;\n}\n"
   : "+f"(d[0]),"+f"(d[1]),"+f"(d[2]),"+f"(d[3]),"+f"(d[4]),"+f"(d[5]),"+f"(d[6]),"+f"(d[7]),"+f"(d[8]),"+f"(d[9]),"+f"(d[10]),"+f"(d[11]),"+f"(d[12]),"+f"(d[13]),"+f"(d[14]),"+f"(d[15]),"+f"(d[16]),"+f"(d[17]),"+f"(d[18]),"+f"(d[19]),"+f"(d[20]),"+f"(d[21]),"+f"(d[22]),"+f"(d[23]),"+f"(d[24]),"+f"(d[25]),"+f"(d[26]),"+f"(d[27]),"+f"(d[28]),"+f"(d[29]),"+f"(d[30]),"+f"(d[31]),"+f"(d[32]),"+f"(d[33]),"+f"(d[34]),"+f"(d[35]),"+f"(d[36]),"+f"(d[37]),"+f"(d[38]),"+f"(d[39]),"+f"(d[40]),"+f"(d[41]),"+f"(d[42]),"+f"(d[43]),"+f"(d[44]),"+f"(d[45]),"+f"(d[46]),"+f"(d[47]),"+f"(d[48]),"+f"(d[49]),"+f"(d[50]),"+f"(d[51]),"+f"(d[52]),"+f"(d[53]),"+f"(d[54]),"+f"(d[55]),"+f"(d[56]),"+f"(d[57]),"+f"(d[58]),"+f"(d[59]),"+f"(d[60]),"+f"(d[61]),"+f"(d[62]),"+f"(d[63]),"+f"(d[64]),"+f"(d[65]),"+f"(d[66]),"+f"(d[67]),"+f"(d[68]),"+f"(d[69]),"+f"(d[70]),"+f"(d[71]),"+f"(d[72]),"+f"(d[73]),"+f"(d[74]),"+f"(d[75]),"+f"(d[76]),"+f"(d[77]),"+f"(d[78]),"+f"(d[79]),"+f"(d[80]),"+f"(d[81]),"+f"(d[82]),"+f"(d[83]),"+f"(d[84]),"+f"(d[85]),"+f"(d[86]),"+f"(d[87]),"+f"(d[88]),"+f"(d[89]),"+f"(d[90]),"+f"(d[91]),"+f"(d[92]),"+f"(d[93]),"+f"(d[94]),"+f"(d[95])
   : "l"(da), "l"(db), "r"(sd));
}

__device__ __forceinline__ void stats_publish(uint32_t sb, int layer, int rb, int hg, int ht, uint32_t tag) {
  const int lane = ht & 31, w = ht >> 5, g = lane >> 2, t = lane & 3, ks = hg & 3;
  uint32_t xa;
  if (layer == 0) {
    const int row = 16 * w + (lane & 15), kc = 2 * ks + (lane >> 4);
    xa = row * 128 + ((kc ^ (row & 7)) << 4);
  } else {
    const int k = 16 * ks + (lane & 7) + 8 * (lane >> 4), pc = 2 * w + ((lane >> 3) & 1);
    xa = k * 128 + ((pc ^ (k & 7)) << 4);
  }
  float s[4] = {0.f, 0.f, 0.f, 0.f}, q[4] = {0.f, 0.f, 0.f, 0.f};
#pragma unroll 1
  for (int c = hg >> 2; c < 8; c += 2) {
    uint32_t A[2][4];
    mbar_wait(sb + SM_BAR + 8 * (B_XF + c), layer);
#pragma unroll
    for (int h = 0; h < 2; h++) {
      if (layer == 0) ldsm4(A[h], sb + SM_X + c * 16384 + h * 8192 + xa);
      else ldsm4t(A[h], sb + SM_X + c * 16384 + h * 8192 + xa);
    }
    if (c >= 6) ATS(48, 256);
    if (c < 2) ATS(51, 256);
#pragma unroll
    for (int r = 0; r < 4; r++)
#pragma unroll
      for (int i = 0; i < 2; i++) {
        const uint32_t v = A[r >> 1][2 * i + (r & 1)];
        const float a = bf_lo(v), b = bf_hi(v);
        s[r] += a + b; q[r] = fmaf(a, a, q[r]); q[r] = fmaf(b, b, q[r]);
      }
  }
#pragma unroll
  for (int r = 0; r < 2; r++) {
    s[r] = ((t & 2) ? s[r + 2] : s[r]) + __shfl_xor_sync(~0u, (t & 2) ? s[r] : s[r + 2], 2);
    q[r] = ((t & 2) ? q[r + 2] : q[r]) + __shfl_xor_sync(~0u, (t & 2) ? q[r] : q[r + 2], 2);
  }
  s[0] = ((t & 1) ? s[1] : s[0]) + __shfl_xor_sync(~0u, (t & 1) ? s[0] : s[1], 1);
  q[0] = ((t & 1) ? q[1] : q[0]) + __shfl_xor_sync(~0u, (t & 1) ? q[0] : q[1], 1);
  st_part(&g_part[(rb * 8 + hg) * 128 + 64 * (t >> 1) + 16 * w + 8 * (t & 1) + g], s[0], q[0], tag);
  ATS(49, 256);
}
__device__ __forceinline__ void stats_gather(uint32_t sb, int rb, int ht, uint32_t tag) {
  const uint2* src = &g_part[rb * 8 * 128 + ht];
  uint2 v[8];
  bool ok;
  int it = 0;
  do {
    ok = true;
#pragma unroll
    for (int i = 0; i < 8; i++) v[i] = ld_part(src + i * 128);
#pragma unroll
    for (int i = 0; i < 8; i++) ok = ok && (v[i].y & 7u) == tag;
    if (++it > (1 << 22)) __trap();
  } while (!__all_sync(~0u, ok));
  float s = 0.f, q = 0.f;
#pragma unroll
  for (int i = 0; i < 8; i++) { s += __uint_as_float(v[i].x); q += __uint_as_float(v[i].y); }
  const float mean = s * (1.f / DM);
  const float rstd = rsqrt_approx(fmaxf(q * (1.f / DM) - mean * mean, 0.f) + 1e-5f);
  asm volatile("st.shared.v2.f32 [%0], {%1,%2};" ::"r"(sb + SM_ST + ht * 8), "f"(mean), "f"(rstd) : "memory");
  __syncwarp();
  if (elect_one()) mbar_arrive(sb + SM_BAR + 8 * B_STF);
}
__device__ __forceinline__ void halo_receive(uint32_t sb, int layer, int rb, int hg, int ht) {
  const int lane = ht & 31, h = ht >> 5;
  uint4 kv = make_uint4(0, 0, 0, 0);
  mbar_wait(sb + SM_BAR + 8 * B_SD, layer);
  if (rb & 7) {
    const uint32_t tag = 2 * lds32(sb + SM_EP) + layer + 1;
    const uint4* src = &g_halo[((rb - 1) * 8 + hg) * 192 + h * 48];
    if (layer == 0) delay<D_HALO>(); else delay<D_HALO1>();
    uint4 a;
    uint2 b;
    int it = 0;
    do {
      a = ld_tagged(src + lane); b = ld_part((const uint2*)(src + 32) + lane);
      if (++it > (1 << 22)) __trap();
    } while (!__all_sync(~0u, a.w == tag && b.y == tag));
    kv = make_uint4(a.x, a.y, movm_t(a.z), movm_t(b.x));
  }
  sts128(sb + SM_KVX + h * 512 + lane * 16, kv);
  ATS(61, 256);
  bar_arrive(7, 160);
  if (elect_one()) mbar_arrive(sb + SM_BAR + 8 * B_HF);
}

__device__ __forceinline__ void halo_receive1(uint32_t sb, int layer, int rb, int hg, int lane, uint32_t tag) {
  uint4 a[4];
  uint2 b[4];
  mbar_wait(sb + SM_BAR + 8 * B_SD, layer);
  if (rb & 7) {
    const uint4* src = &g_halo[((rb - 1) * 8 + hg) * 192];
    if (layer == 0) delay<D_HALO>(); else delay<D_HALO1>();
    int it = 0;
    bool ok;
    do {
      ok = true;
#pragma unroll
      for (int h = 0; h < 4; h++) { a[h] = ld_tagged(src + h * 48 + lane); b[h] = ld_part((const uint2*)(src + h * 48 + 32) + lane); }
#pragma unroll
      for (int h = 0; h < 4; h++) ok = ok && a[h].w == tag && b[h].y == tag;
      if (++it > (1 << 22)) __trap();
    } while (!__all_sync(~0u, ok));
#pragma unroll
    for (int h = 0; h < 4; h++) { a[h].z = movm_t(a[h].z); a[h].w = movm_t(b[h].x); }
  } else {
#pragma unroll
    for (int h = 0; h < 4; h++) a[h] = make_uint4(0, 0, 0, 0);
  }
#pragma unroll
  for (int h = 0; h < 4; h++) sts128(sb + SM_KVX + h * 512 + lane * 16, a[h]);
  ATS(61, 448);
  bar_arrive(7, 64);
  if (lane < 4) mbar_arrive(sb + SM_BAR + 8 * B_HF);
}

template <bool TR>
__device__ __forceinline__ void gemm_section(float* acc, float2* cs, uint32_t sb, int layer, int wg, int w, int lane) {
  const uint32_t bar = sb + SM_BAR;
  const bool leader = (w == 0) && (lane == 0);
  auto issue = [&](int c, int slot) {
    mbar_wait(bar + 8 * (B_XF + c), layer);
    mbar_wait(bar + 8 * (B_KVF + c), layer);
    const uint64_t da = mkdesc(sb + SM_X + c * 16384 + wg * 8192, TR ? 8192 : 16, 1024, 1);
    const uint64_t db = mkdesc(sb + SM_W + slot * 24576, 8192, 1024, 1);
    wg_fence();
#pragma unroll
    for (int ks = 0; ks < 4; ks++) wgmma_ss<192, TR ? 1 : 0, 1>(acc, da + (TR ? ks * 128 : ks * 2), db + ks * 128, (c | ks) != 0);
    wg_commit();
  };
  auto step = [&](int c, int slot) {
    issue(c, slot);
    wg_wait<1>();
    if (leader) mbar_arrive(bar + 8 * (B_KVE + c - 1));
  };
  if (!TR) bar_sync(0, NTHREADS);
  issue(0, 0);
  if (threadIdx.x == 0) TS(2 + layer * 20 + 0);
  if (threadIdx.x == 128 && layer == 1) TS(60);
  step(1, 1); step(2, 2); step(3, 0); step(4, 1);
  auto ld_cs = [&](int j0) {
#pragma unroll
    for (int j = j0; j < j0 + 8; j++) cs[j] = lds64f(sb + SM_CS + 4 * (8 * j + 2 * (lane & 3)));
  };
  if (TR) ld_cs(8);
  step(5, 2);
  if (!TR && !CS_LATE0) { mbar_wait(bar + 8 * B_CSF, 0); ld_cs(8); }
  if (TR || !CS_LATE0) ld_cs(16);
  if (wg == 0) bar_sync(5, 256);
  issue(6, 0);
  issue(7, 1);
  if (wg == 1) bar_arrive(5, 256);
  if (!TR && CS_LATE0) { mbar_wait(bar + 8 * B_CSF, 0); ld_cs(8); ld_cs(16); }
}

__device__ __forceinline__ void attn_phase(const Params& p, uint32_t sb, int layer, int rb, int hg, int wg, int w) {
  const int lane = opaque_tid() & 31;
  const int g = lane >> 2, t = lane & 3;
  const uint32_t bar = sb + SM_BAR;
  const int row0 = 64 * wg + 16 * w;
  const bool leader = (w == 0) && (lane == 0);
  float acc[96];
  float2 cs[24];
  if (layer) gemm_section<true>(acc, cs, sb, layer, wg, w, lane);
  else gemm_section<false>(acc, cs, sb, layer, wg, w, lane);
  ATS(41, 224);
  mbar_wait(bar + 8 * B_STF, layer);
  const uint32_t tag = 2 * lds32(sb + SM_EP) + layer + 1;
  const float2 st0 = lds64f(sb + SM_ST + (row0 + g) * 8), st1 = lds64f(sb + SM_ST + (row0 + g + 8) * 8);
  const float mean0 = st0.x, rstd0 = st0.y, mean1 = st1.x, rstd1 = st1.y;
  wg_wait<0>();
  if (threadIdx.x == 0) TS(2 + layer * 20 + 1);
  ATS(39, 224);
  if (leader) mbar_arrive(bar + 8 * B_QDONE);

  uint32_t fp[4][4], fl[4][4], fh[4][4], qa[4][4];
  const int cw = 4 * wg + w;
  {
    const float nm0 = -mean0 * rstd0, nm1 = -mean1 * rstd1;
    const uint32_t kvx = sb + SM_KVX + cw * 2048 + lane * 16;
#pragma unroll
    for (int h = 0; h < 4; h++)
#pragma unroll
      for (int k = 0; k < 4; k++) {
        const int j = 8 + (k >> 1) * 8 + 2 * h + (k & 1);
        fh[h][k] = packbf(fmaf(acc[4 * j + 2], rstd1, nm1 * cs[j].x), fmaf(acc[4 * j + 3], rstd1, nm1 * cs[j].y));
      }
    if (cw == 7) {
      uint4* halo = &g_halo[(rb * 8 + hg) * 192];
#pragma unroll
      for (int h = 0; h < 4; h++) {
        st_tagged3(halo + h * 48 + lane, fh[h][0], fh[h][1], fh[h][2], tag);
        asm volatile("st.relaxed.gpu.global.v2.u32 [%0], {%1,%2};" ::"l"((uint2*)(halo + h * 48 + 32) + lane), "r"(fh[h][3]), "r"(tag) : "memory");
      }
      if (elect_one()) mbar_arrive(bar + 8 * B_SD);
      if (layer == TLAYER && threadIdx.x == 224) TS(47);
    }
#pragma unroll
    for (int h = 0; h < 4; h++) { fh[h][2] = movm_t(fh[h][2]); fh[h][3] = movm_t(fh[h][3]); }
    if (cw != 7) {
#pragma unroll
      for (int h = 0; h < 4; h++) sts128(kvx + 2048 + h * 512, make_uint4(fh[h][0], fh[h][1], fh[h][2], fh[h][3]));
      bar_arrive(8 + cw, 64);
    }
    sched_fence<6>();
    if (layer == TLAYER && threadIdx.x == 0) TS(45);
#pragma unroll
    for (int j = 0; j < 8; j++) cs[j] = lds64f(sb + SM_CS + 4 * (8 * j + 2 * t));
#pragma unroll
    for (int h = 0; h < 4; h++)
#pragma unroll
      for (int k = 0; k < 4; k++) {
        const int j = 8 + (k >> 1) * 8 + 2 * h + (k & 1);
        fl[h][k] = packbf(fmaf(acc[4 * j], rstd0, nm0 * cs[j].x), fmaf(acc[4 * j + 1], rstd0, nm0 * cs[j].y));
        if (k >= 2) fl[h][k] = movm_t(fl[h][k]);
      }
#pragma unroll
    for (int h = 0; h < 4; h++) {
#pragma unroll
      for (int dh = 0; dh < 2; dh++) {
        const int j = 2 * h + dh;
        const float2 c2 = cs[j];
        qa[h][2 * dh] = packbf(fmaf(-mean0, c2.x, acc[4 * j + 0]), fmaf(-mean0, c2.y, acc[4 * j + 1]));
        qa[h][2 * dh + 1] = packbf(fmaf(-mean1, c2.x, acc[4 * j + 2]), fmaf(-mean1, c2.y, acc[4 * j + 3]));
      }
    }
    if (threadIdx.x == 0) TS(2 + layer * 20 + 2);
    sched_fence<0>();
    bar_sync(7 + cw, cw == 0 && !HALO_W14 ? 160 : 64);
#pragma unroll
    for (int h = 0; h < 4; h++) {
      const uint4 v = lds128(kvx + h * 512);
      fp[h][0] = v.x; fp[h][1] = v.y; fp[h][2] = v.z; fp[h][3] = v.w;
    }
    if (threadIdx.x == 0) TS(2 + layer * 20 + 4);
  }

  const bool u0 = 2 * t > g, u1 = 2 * t + 1 > g;
  const uint32_t mU = (u0 ? 0x0000ffffu : 0u) | (u1 ? 0xffff0000u : 0u);
  const float cl2 = 0.25f * 1.4426950408889634f;
  const float sc0 = rstd0 * cl2, sc1 = rstd1 * cl2;
  const float cneg = ((rb & 7) == 0 && cw == 0) ? -INFINITY : 0.f;
  float v[4][4];
#pragma unroll
  for (int h = 0; h < 4; h++) {
    float T0[4] = {cneg, cneg, cneg, cneg}, T1[4] = {0.f, 0.f, 0.f, 0.f}, T2[4] = {0.f, 0.f, 0.f, 0.f};
    mma_bf16(T1, qa[h], fl[h][0], fl[h][1]);
    mma_bf16(T2, qa[h], fh[h][0], fh[h][1]);
    mma_bf16(T0, qa[h], fp[h][0], fp[h][1]);
    v[h][0] = u0 ? T0[0] : T1[0]; v[h][1] = u1 ? T0[1] : T1[1];
    v[h][2] = u0 ? T1[2] : T2[2]; v[h][3] = u1 ? T1[3] : T2[3];
  }
  float m0[4], m1[4];
#pragma unroll
  for (int h = 0; h < 4; h++) { m0[h] = fmaxf(v[h][0], v[h][1]); m1[h] = fmaxf(v[h][2], v[h][3]); }
#pragma unroll
  for (int o = 1; o <= 2; o <<= 1) {
#pragma unroll
    for (int h = 0; h < 4; h++) {
      m0[h] = fmaxf(m0[h], __shfl_xor_sync(~0u, m0[h], o));
      m1[h] = fmaxf(m1[h], __shfl_xor_sync(~0u, m1[h], o));
    }
  }
  float O0[4][4], O1[4][4], Z[4][4];
#pragma unroll
  for (int h = 0; h < 4; h++) {
    const float mm0 = -m0[h] * sc0, mm1 = -m1[h] * sc1;
    const uint32_t P0 = packbf(ex2(fmaf(v[h][0], sc0, mm0)), ex2(fmaf(v[h][1], sc0, mm0)));
    const uint32_t P1 = packbf(ex2(fmaf(v[h][2], sc1, mm1)), ex2(fmaf(v[h][3], sc1, mm1)));
#pragma unroll
    for (int k = 0; k < 4; k++) O0[h][k] = O1[h][k] = Z[h][k] = 0.f;
    mma_bf16_k8(Z[h], P0, P1, 0x3f803f80u);
    mma_bf16_k8(O0[h], P0 & ~mU, P1 & mU, fl[h][2]); mma_bf16_k8(O1[h], P0 & ~mU, P1 & mU, fl[h][3]);
    mma_bf16_k8(O0[h], P0 & mU, 0u, fp[h][2]); mma_bf16_k8(O1[h], P0 & mU, 0u, fp[h][3]);
    mma_bf16_k8(O0[h], 0u, P1 & ~mU, fh[h][2]); mma_bf16_k8(O1[h], 0u, P1 & ~mU, fh[h][3]);
  }
  const uint32_t ob = sb + SM_OST + wg * 8192;
  const int o_row = 16 * w + (lane & 7) + 8 * ((lane >> 3) & 1);
#pragma unroll
  for (int h = 0; h < 4; h++) {
    const float i0 = rcp_approx(Z[h][0]), i1 = rcp_approx(Z[h][2]);
    const int ch = 2 * h + (lane >> 4);
    stsm4(ob + o_row * 128 + ((ch ^ (o_row & 7)) << 4), packbf(O0[h][0] * i0, O0[h][1] * i0), packbf(O0[h][2] * i1, O0[h][3] * i1),
          packbf(O1[h][0] * i0, O1[h][1] * i0), packbf(O1[h][2] * i1, O1[h][3] * i1));
  }
  if (threadIdx.x == 0) TS(2 + layer * 20 + 5);
  ATS(57, 128); ATS(20, 96);
  bar_sync(2 + wg, 128);
  if (w == 0 && elect_one()) {
    fence_async_smem();
    tma_st(&p.mapO, hg * 64, rb * 128 + wg * 64, ob);
    bulk_commit();
    mbar_arrive(bar + 8 * B_AD);
    bulk_wait_all();
    red_relaxed(&g_cnt[(C_O + rb) * 32]);
    mbar_arrive(bar + 8 * B_OST);
    if (threadIdx.x == 0) TS(2 + layer * 20 + 6);
  }
  __syncwarp();
}

__device__ __forceinline__ void proj_phase(const Params& p, uint32_t sb, int layer, int rb, int q, int wg, int w) {
  const int lane = opaque_tid() & 31;
  const bool TR = layer != 0;
  const int t = lane & 3;
  const uint32_t bar = sb + SM_BAR;
  const uint32_t rbx = sb + SM_R + wg * 8192;
  uint32_t res[16];
  mbar_wait(bar + 8 * B_RF, layer);
  if (threadIdx.x == 0) TS(2 + layer * 20 + 7);
  if (!TR) {
#pragma unroll
    for (int j = 0; j < 8; j += 2) {
      const int mi = lane >> 3;
      const int row = 16 * w + (lane & 7) + 8 * (mi & 1), ch = j + (mi >> 1);
      ldsm4(&res[2 * j], rbx + row * 128 + ((ch ^ (row & 7)) << 4));
    }
  } else {
#pragma unroll
    for (int j = 0; j < 8; j += 2) {
      const int mi = lane >> 3;
      const int line = 8 * (j + (mi >> 1)) + (lane & 7), pc = 2 * w + (mi & 1);
      ldsm4t(&res[2 * j], rbx + line * 128 + ((pc ^ (line & 7)) << 4));
    }
  }
  bar_sync(2 + wg, 128);
  float acc[32];
#pragma unroll
  for (int i = 0; i < 16; i++) {
    asm volatile("shl.b32 %0, %1, 16;" : "=f"(acc[2 * i]) : "r"(res[i]));
    asm volatile("and.b32 %0, %1, 0xffff0000;" : "=f"(acc[2 * i + 1]) : "r"(res[i]));
  }
  const uint32_t tag = part_tag(lds32(sb + SM_EP), 2 * layer + 1);
  mbar_wait(bar + 8 * B_ZF, layer);
#pragma unroll 1
  for (int c = 0; c < 8; c++) {
    if ((c & 1) == 0) mbar_wait(bar + 8 * (B_WOF + (c >> 1)), layer);
    mbar_wait(bar + 8 * (B_OF + c), layer);
    if (c == 0 && threadIdx.x == 0) TS(2 + layer * 20 + 8);
    const uint64_t da = mkdesc(sb + sm_o(c) + wg * 8192, 16, 1024, 1);
    const uint64_t db = mkdesc(sb + SM_WO + c * 8192, 8192, 1024, 1);
    wg_fence();
#pragma unroll
    for (int ks = 0; ks < 4; ks++) wgmma_ss<64, 0, 1>(acc, da + ks * 2, db + ks * 128, 1);
    wg_commit();
  }
  wg_wait<0>();
#pragma unroll
  for (int i = 0; i < 32; i++) asm volatile("" : "+f"(acc[i]) :: "memory");
  if (threadIdx.x == 0) TS(2 + layer * 20 + 9);
  if (lane == 0 && w == 0) mbar_arrive(bar + 8 * B_PDONE);
  {
    float s[4], qq[4];
#pragma unroll
    for (int k = 0; k < 4; k++) { s[k] = acc[k]; qq[k] = acc[k] * acc[k]; }
#pragma unroll
    for (int j = 1; j < 8; j++)
#pragma unroll
      for (int k = 0; k < 4; k++) { s[k] += acc[4 * j + k]; qq[k] = fmaf(acc[4 * j + k], acc[4 * j + k], qq[k]); }
    const float s0 = s[0] + s[1], s1 = s[2] + s[3], q0 = qq[0] + qq[1], q1 = qq[2] + qq[3];
    float sr = ((t & 1) ? s1 : s0) + __shfl_xor_sync(~0u, (t & 1) ? s0 : s1, 1);
    float qr = ((t & 1) ? q1 : q0) + __shfl_xor_sync(~0u, (t & 1) ? q0 : q1, 1);
    sr += __shfl_xor_sync(~0u, sr, 2);
    qr += __shfl_xor_sync(~0u, qr, 2);
    if (t < 2) st_part(&g_part[(rb * 8 + q) * 128 + 64 * wg + 16 * w + (lane >> 2) + 8 * t], sr, qr, tag);
    __syncwarp();
    if (elect_one()) mbar_arrive(bar + 8 * B_PS);
    sched_fence<7>();
  }
#pragma unroll
  for (int j = 0; j < 8; j += 2) {
    const int mi = lane >> 3;
    const int line = 8 * (j + (mi >> 1)) + (lane & 7), pc = 2 * w + (mi & 1);
    stsm4t(rbx + line * 128 + ((pc ^ (line & 7)) << 4), packbf(acc[4 * j], acc[4 * j + 1]), packbf(acc[4 * j + 2], acc[4 * j + 3]),
           packbf(acc[4 * j + 4], acc[4 * j + 5]), packbf(acc[4 * j + 6], acc[4 * j + 7]));
  }
  fence_writer();
  bar_sync(2 + wg, 128);
  if (w == 0 && elect_one()) {
    fence_reader();
    fence_async_global();
    tma_st(&p.mapXT, rb * 128 + wg * 64, (2 * layer) * DM + q * 64, rbx);
    bulk_commit();
    if (threadIdx.x == 0) TS(2 + layer * 20 + 10);
    bulk_wait_all();
    red_relaxed(&g_cnt[C_CS * 32 + 2 + layer]);
    if (wg == 0) mbar_arrive(bar + 8 * B_RE);
  }
  __syncwarp();
}
__device__ __forceinline__ void proj_stats(int layer, int rb, int q, int lane, uint32_t tag) {
  const int r = 16 * q + (lane & 15);
  const uint2* src = &g_part[(rb * 8 + (lane >> 4) * 4) * 128 + r];
  uint2 v[4];
  bool ok;
  int it = 0;
  do {
    ok = true;
#pragma unroll
    for (int i = 0; i < 4; i++) v[i] = ld_part(src + i * 128);
#pragma unroll
    for (int i = 0; i < 4; i++) ok = ok && (v[i].y & 7u) == tag;
    if (++it > (1 << 22)) __trap();
  } while (!__all_sync(~0u, ok));
  float s = (__uint_as_float(v[0].x) + __uint_as_float(v[1].x)) + (__uint_as_float(v[2].x) + __uint_as_float(v[3].x));
  float qq = (__uint_as_float(v[0].y) + __uint_as_float(v[1].y)) + (__uint_as_float(v[2].y) + __uint_as_float(v[3].y));
  s += __shfl_xor_sync(~0u, s, 16);
  qq += __shfl_xor_sync(~0u, qq, 16);
  const float mean = s * (1.f / DM);
  const float rstd = rsqrt_approx(fmaxf(fmaf(qq, 1.f / DM, -mean * mean), 0.f) + 1e-5f), nm = -mean * rstd;
  const float nm1 = __shfl_xor_sync(~0u, nm, 1), rstd1 = __shfl_xor_sync(~0u, rstd, 1);
  if ((lane & 17) == 0)
    st_tagged3((uint4*)g_stats + (layer * 32 + rb * 2 + (r >> 6)) * 32 + ((r & 7) >> 1) * 8 + ((r >> 3) & 7),
               __float_as_uint(nm), __float_as_uint(rstd) | 1u, __float_as_uint(nm1), __float_as_uint(rstd1));
}

#define NA 14
#define NP 15
template <int M0, int M1> __device__ __forceinline__ void conv_load(uint32_t* A, uint32_t pe) {
#pragma unroll
  for (int m = M0; m < M1; m++) {
    asm volatile("ld.shared.v2.b32 {%0,%1}, [%2];" : "=r"(A[4 * m]), "=r"(A[4 * m + 1]) : "r"(pe + 256 * m) : "memory");
    A[4 * m + 2] = lds32(pe + 256 * m - 4);
  }
}
__device__ __forceinline__ uint32_t copy_reg(uint32_t v, uint32_t zero) { uint32_t r; asm volatile("or.b32 %0, %1, %2;" : "=r"(r) : "r"(v), "r"(zero)); return r; }
__device__ __forceinline__ uint32_t copy_reg2(uint32_t v, uint32_t zero) { uint32_t r; asm volatile("xor.b32 %0, %1, %2;" : "=r"(r) : "r"(v), "r"(zero)); return r; }
__device__ __forceinline__ void conv_park(uint32_t* P, uint32_t pe) {
#pragma unroll
  for (int m = 0; m < NP; m++)
#pragma unroll
    for (int k = 0; k < 3; k++) P[3 * m + k] = lds32(pe + 256 * m - 4 + 4 * k);
}
__device__ __forceinline__ void conv_unpark(uint32_t* A, const uint32_t* P, uint32_t zero) {
#pragma unroll
  for (int m = 0; m < NP; m++) {
    A[4 * m + 2] = copy_reg(P[3 * m], zero); A[4 * m] = copy_reg(P[3 * m + 1], zero);
    A[4 * m + 3] = copy_reg2(P[3 * m + 1], zero); A[4 * m + 1] = copy_reg(P[3 * m + 2], zero);
  }
}
template <int M0, int M1> __device__ __forceinline__ void conv_mmas(float* acc, const uint32_t* A, uint64_t d) {
  if constexpr (M0 < M1) {
    wgmma_rs<128 - 8 * (M0 / 2), 0>(acc, A + 4 * M0, d + (uint64_t)(4 * M0), M0 != 0);
    conv_mmas<M0 + 1, M1>(acc, A, d);
  }
}
struct SumAddr { uint32_t l0, l1, l2, se, so; };
__device__ __forceinline__ SumAddr conv_sum_addr(uint32_t sb, int c) {
  auto ua = [&](int j) { return sb + cv_u(0) + (127 - (j >> 3)) * 16 + (j & 7) * 2; };
  auto sa = [&](int hc) { const int ci = hc & ~1; return sb + cv_s(0) + ((ci >> 3) & 1) * 1024 + (ci >> 4) * 128 + (((ci ^ (ci >> 4)) & 7) << 4) + (hc & 1) * 8; };
  const int j0 = 4 * (c - 1);
  return {ua(j0 - 2), ua(j0), ua(j0 + 4), sa((c + 1) & 127), sa(c) + 2048};
}
__device__ __forceinline__ void sts64(uint32_t a, uint32_t x, uint32_t y) { asm volatile("st.shared.v2.b32 [%0], {%1,%2};" ::"r"(a), "r"(x), "r"(y) : "memory"); }
__device__ __forceinline__ void conv_sums(const SumAddr& sa, int lc, int c) {
  uint32_t e[4], o[4];
  {
    const float2 em = lds64f(sa.l1 + lc * 32768), om = lds64f(sa.l1 + lc * 32768 + CV_UH);
    e[0] = lds32(sa.l0 + lc * 32768); o[0] = lds32(sa.l0 + lc * 32768 + CV_UH);
    e[3] = lds32(sa.l2 + lc * 32768); o[3] = lds32(sa.l2 + lc * 32768 + CV_UH);
    e[1] = __float_as_uint(em.x); e[2] = __float_as_uint(em.y); o[1] = __float_as_uint(om.x); o[2] = __float_as_uint(om.y);
  }
  uint32_t s7e[2], s7o[2], s9e[2], s9o[2];
  uint32_t pw[4], sh[3];
#pragma unroll
  for (int k = 0; k < 4; k++) pw[k] = hadd2(e[k], o[k]);
#pragma unroll
  for (int k = 0; k < 3; k++) sh[k] = __byte_perm(pw[k], pw[k + 1], 0x5432);
#pragma unroll
  for (int k = 0; k < 2; k++) {
    const uint32_t t3 = hadd2(hadd2(sh[k], sh[k + 1]), pw[k + 1]);
    s7e[k] = hadd2(t3, o[k]); s7o[k] = hadd2(t3, e[k + 2]);
    s9e[k] = hadd2(s7o[k], pw[k]); s9o[k] = hadd2(s7e[k], pw[k + 2]);
  }
  if (c == 127) s9e[0] = s9e[1] = s9o[0] = s9o[1] = 0u;
  sts64(sa.se + lc * 32768, s9e[0], s9e[1]); sts64((sa.se ^ 16) + lc * 32768, s9o[0], s9o[1]);
  sts64(sa.so + lc * 32768, s7e[0], s7e[1]); sts64((sa.so ^ 16) + lc * 32768, s7o[0], s7o[1]);
}

__device__ __forceinline__ void conv_epi(uint32_t sb, int layer, int cta, int ch, int c0, uint4 x0, uint4 x1) {
  uint4 v[2][4];
  const uint4 xr[2] = {x0, x1};
  mbar_wait(sb + SM_BAR + 8 * (B_P + ch), layer);
#pragma unroll
  for (int u = 0; u < 2; u++) {
    const uint32_t pb = sb + cv_pb(ch) + u * (CV_PBW / 2) + c0 * 16;
#pragma unroll
    for (int k = 0; k < 4; k++) v[u][k] = lds128(pb + k * CV_PBW);
  }
#pragma unroll
  for (int u = 0; u < 2; u++) {
    uint4 o;
    o.x = hadd2(xr[u].x, hadd2(hadd2(v[u][0].x, v[u][1].x), hadd2(v[u][2].x, v[u][3].x)));
    o.y = hadd2(xr[u].y, hadd2(hadd2(v[u][0].y, v[u][1].y), hadd2(v[u][2].y, v[u][3].y)));
    o.z = hadd2(xr[u].z, hadd2(hadd2(v[u][0].z, v[u][1].z), hadd2(v[u][2].z, v[u][3].z)));
    o.w = hadd2(xr[u].w, hadd2(hadd2(v[u][0].w, v[u][1].w), hadd2(v[u][2].w, v[u][3].w)));
    if (layer == 0 || ch < 4 - FIN_LL) sts128(sb + cv_s(ch) + (c0 + 128 * u) * 16, o);
    else st_tagged3((uint4*)(g_xT + (size_t)(3 * DM + cv_chan(cta, ch)) * LSEQ) + c0 + 128 * u, o.x, o.y, o.z, o.w);
  }
}
__device__ __forceinline__ void warp_release(uint32_t b) {
  fence_writer();
  __syncwarp();
  if (elect_one()) mbar_arrive(b);
}

__device__ __forceinline__ void conv_prep_load(uint32_t sb, int layer, int cta, int c, uint4 (&xr)[4], uint4 (&st)[4]) {
  sched_fence<8>();
  mbar_wait(sb + SM_BAR + 8 * B_GB, layer);
  if (threadIdx.x == 0) TS(2 + layer * 20 + 11);
  xr[0] = ld_tagged((const uint4*)(g_xT + (size_t)(2 * layer * DM + cta) * LSEQ) + c);
#pragma unroll
  for (int i = 0; i < 4; i++) st[i] = ld_tagged((const uint4*)g_stats + (layer * 32 + (c >> 3)) * 32 + i * 8 + (c & 7));
}
template <bool HELPER>
__device__ __forceinline__ void conv_prep(uint32_t sb, int layer, int cta, int c, uint4 (&xr)[4], uint4 (&st)[4], const SumAddr& sa) {
  const uint32_t bar = sb + SM_BAR;
  const uint4* xin = (const uint4*)(g_xT + (size_t)(2 * layer * DM + cta) * LSEQ) + c;
  for (int it = 0;; it++) {
    uint32_t vs;
    asm("{\n.reg .b32 t;\nlop3.b32 t, %1, %2, %3, 0x80;\nlop3.b32 %0, t, %4, 1, 0x80;\n}" : "=r"(vs) : "r"(st[0].y), "r"(st[1].y), "r"(st[2].y), "r"(st[3].y));
    if (__all_sync(~0u, vs != 0 && xr[0].x != ~0u)) break;
    if (it > (1 << 22)) __trap();
    if (!__all_sync(~0u, xr[0].x != ~0u)) xr[0] = ld_tagged(xin);
    if (!__all_sync(~0u, vs != 0)) {
#pragma unroll
      for (int i = 0; i < 4; i++) st[i] = ld_tagged((const uint4*)g_stats + (layer * 32 + (c >> 3)) * 32 + i * 8 + (c & 7));
    }
  }
  if (threadIdx.x == 0) TS(2 + layer * 20 + 12);
  const int a = c & 127, h = c >> 7;
#pragma unroll
  for (int i = 0; i < 4; i++) {
    if (i == 1) {
      mbar_wait(bar + 8 * B_XV, layer);
#pragma unroll
      for (int j = 1; j < 4; j++) xr[j] = ld_tagged(xin + j * (128 * LSEQ / 8));
      if (HELPER) {
        mbar_wait(bar + 8 * B_U, layer);
        conv_sums(sa, 0, c);
        fence_async_smem();
        bar_arrive(7, 256);
        sched_fence<1>();
        if (layer == 1 && c == 0) TS(46);
      }
    }
    const uint32_t x[4] = {xr[i].x, xr[i].y, xr[i].z, xr[i].w};
    uint32_t u[4];
#pragma unroll
    for (int k = 0; k < 4; k++)
      u[k] = packbf(fmaf(bf_lo(x[k]), __uint_as_float(st[k].y), __uint_as_float(st[k].x)), fmaf(bf_hi(x[k]), __uint_as_float(st[k].w), __uint_as_float(st[k].z)));
    sts128(sb + cv_u(i) + h * CV_UH + (127 - a) * 16, make_uint4(u[0], u[1], u[2], u[3]));
    warp_release(bar + 8 * (B_U + i));
    sched_fence<2>();
  }
}
__device__ __forceinline__ void conv_zero(uint32_t sb, int ht) {
  if (ht < 96) {
    const int ch = ht / 24, h2 = (ht / 12) & 1, qq = ht % 12;
    sts128(sb + cv_u(ch) + h2 * CV_UH + (128 + qq) * 16, make_uint4(0, 0, 0, 0));
  }
  if (ht >= 80) {
    const int i = ht - 80, ch = i / 12, q2 = i % 12;
    const int w2 = q2 < 2 ? 1 : q2 < 6 ? 2 : 3, cc = q2 < 2 ? q2 : q2 < 6 ? q2 - 2 : q2 - 6;
    sts128(sb + cv_pb(ch) + w2 * CV_PBW + (cc & 1) * (CV_PBW / 2) + (cc >> 1) * 16, make_uint4(0, 0, 0, 0));
  }
}

#define HANDOVER 1
template <int R>
__device__ __forceinline__ void conv_round(uint32_t sb, int layer, int wg, uint32_t* A, const uint32_t* P, uint32_t pb, uint32_t pe2) {
  const uint32_t bar = sb + SM_BAR;
  const int ch = 2 * R + 1 - wg;
  float acc[64];
  const uint64_t d = mkdesc(sb + cv_u(ch), CV_UH, 128, 0);
  FTS(39);
  if (R == 0) {
    mbar_wait(bar + 8 * (B_U + ch), layer);
    fence_reader();
  }
  sched_fence<3>();
  if (R == 1 || wg == 0) bar_sync(10 + ch, 256);
  if (layer == 0 && ch > 0 && ((PAUSE >> (ch - 1)) & 1)) mbar_wait(bar + 8 * (B_E + ch - 1), 0);
  if (layer == 0 && ch > 0 && ((PAUSE >> (ch + 3)) & 1)) mbar_wait(bar + 8 * (B_P + ch - 1), 0);
  FTS(41);
  if (ch == 0 && threadIdx.x == 128) TS(2 + layer * 20 + 13);
  wg_fence();
  conv_mmas<0, 1>(acc, A, d); conv_mmas<2, NA + 1>(acc, A, d);
  wg_commit();
  FTS(51);
  if (HANDOVER == 0 && (R == 0 || wg == 1)) bar_arrive(11 + ch, 256);
  bar_sync(7 + ch, 256);
  wg_fence();
  conv_mmas<1, 2>(acc, A, d); conv_mmas<NA + 1, 17>(acc, A, d);
  wgmma_ss<64, 1, 1>(acc, mkdesc(sb + cv_s(ch), 1024, 1024, 1), mkdesc(sb + cv_ft(ch), 256, 16, 0), 1);
  wgmma_ss<64, 1, 1>(acc, mkdesc(sb + cv_s(ch) + 2048, 1024, 1024, 1), mkdesc(sb + cv_ft(ch) + 512, 256, 16, 0), 1);
  wg_commit();
  if (HANDOVER == 1 && (R == 0 || wg == 1)) bar_arrive(11 + ch, 256);
  FTS(61);
  wg_wait<0>();
#pragma unroll
  for (int j = 0; j < 16; j += 2)
    stsm4t(pb + R * 65536 - j * 128, packbf(acc[4 * j], acc[4 * j + 1]), packbf(acc[4 * j + 2], acc[4 * j + 3]),
           packbf(acc[4 * j + 4], acc[4 * j + 5]), packbf(acc[4 * j + 6], acc[4 * j + 7]));
  __syncwarp();
  if (elect_one()) mbar_arrive(bar + 8 * (B_P + ch));
  if (threadIdx.x == 0) TS(2 + layer * 20 + 14 + R);
  FTS(57);
  if (R == 0) {
    conv_unpark(A, P, opaque_tid() >> 10);
    mbar_wait(bar + 8 * (B_U + ch + 2), layer);
    fence_reader();
    conv_load<NP, 17>(A, pe2);
#pragma unroll
    for (int m = NP; m < 17; m++) A[4 * m + 3] = lds32(pe2 + 256 * m);
  }
}
__device__ __forceinline__ void conv_phase(const Params& p, uint32_t sb, int layer, int cta) {
  const int tid = opaque_tid();
  const int wg = __shfl_sync(~0u, tid >> 7, 0), w = __shfl_sync(~0u, (tid >> 5) & 3, 0);
  const uint32_t bar = sb + SM_BAR;
  uint32_t A[68], P[3 * NP];
  const uint32_t pe = sb + cv_pe(1 - wg) + 4 * (16 + 16 * w + 2 * ((tid & 31) >> 2) - 4 * (tid & 3));
  mbar_wait(bar + 8 * B_PE, layer);
  conv_load<0, 17>(A, pe);
#pragma unroll
  for (int m = 0; m < 17; m++) A[4 * m + 3] = copy_reg(A[4 * m], tid >> 10);
  if (wg == 0) {
    uint4 xr[4], st[4];
    if (PARK_FIRST) conv_park(P, pe + 65536);
    conv_prep_load(sb, layer, cta, tid + 128, xr, st);
    if (!PARK_FIRST) conv_park(P, pe + 65536);
    conv_prep<false>(sb, layer, cta, opaque_tid() + 128, xr, st, SumAddr());
  } else {
    conv_park(P, pe + 65536);
  }
  uint32_t pb;
  {
    const int l2 = opaque_tid() & 31, mt = l2 >> 3;
    pb = sb + cv_pb(1 - wg) + w * CV_PBW + (mt & 1) * (CV_PBW / 2) + (127 - 8 * (mt >> 1) - (l2 & 7) + w) * 16;
  }
  conv_round<0>(sb, layer, wg, A, P, pb, pe + 65536);
  conv_round<1>(sb, layer, wg, A, P, pb, 0);
  if (G_WAIT == 1 && layer == 0) mbar_wait(bar + 8 * (B_E + 3), layer);
  if (G_WAIT == 2 && layer == 0) mbar_wait(bar + 8 * (B_P + 3), layer);
}

__device__ __forceinline__ void final_phase(const Params& p, uint32_t sb, int cta, int wg, int w) {
  if (wg == 1 && w == 3) return;
  const int lane = opaque_tid() & 31, g = lane >> 2, t = lane & 3;
  const int lc = wg ? w : 3;
  const int pos0 = (cta & 31) * 64, ch0 = 128 * lc + (cta >> 5) * 32;
  const bf16* src = g_xT + (size_t)(3 * DM + ch0 + 8 * (g >> 1) + (g & 1)) * LSEQ + pos0;
  bf16* dst = p.out + (size_t)(2 * (pos0 & 1023) + (pos0 >> 10)) * DM + ch0 + 8 * t;
  constexpr int RS = 2 * DM;
  int it = 0;
  if (lc < 4 - FIN_LL) {
    spin_until(&g_cnt[(C_F + (cta >> 5)) * 32 + lc], (lds32(sb + SM_EP) + 1) * 32);
  } else {
    if (E_WAIT && lc < 2) {
      mbar_wait(sb + SM_BAR + 8 * (E_WAIT == 1 ? B_P + 3 : E_WAIT == 2 ? B_E + 2 : B_E + 3), 1);
    } else {
      mbar_wait(sb + SM_BAR + 8 * (B_E + lc), 1);
      delay<D_FIN>();
    }
  }
  if (wg == 0) {
    uint2 v[4];
    do {
#pragma unroll
      for (int q = 0; q < 4; q++) v[q] = ld_part((const uint2*)(src + 2 * q * LSEQ + 16 * w + 4 * t));
      if (++it > (1 << 22)) __trap();
    } while (!__all_sync(~0u, v[0].x != ~0u && v[1].x != ~0u && v[2].x != ~0u && v[3].x != ~0u));
    if (threadIdx.x == 0) TS(42);
    dst += (16 * w + 4 * (g >> 1) + (g & 1)) * RS;
    *(uint4*)dst = make_uint4(movm_t(v[0].x), movm_t(v[1].x), movm_t(v[2].x), movm_t(v[3].x));
    *(uint4*)(dst + 2 * RS) = make_uint4(movm_t(v[0].y), movm_t(v[1].y), movm_t(v[2].y), movm_t(v[3].y));
  } else {
    uint4 v[2][4];
    bool ok;
    do {
      ok = true;
#pragma unroll
      for (int h = 0; h < 2; h++)
#pragma unroll
        for (int q = 0; q < 4; q++) v[h][q] = ld_tagged((const uint4*)(src + 2 * q * LSEQ + 32 * h + 8 * t));
#pragma unroll
      for (int h = 0; h < 2; h++)
#pragma unroll
        for (int q = 0; q < 4; q++) ok = ok && v[h][q].x != ~0u;
      if (++it > (1 << 22)) __trap();
    } while (!__all_sync(~0u, ok));
    dst += (8 * (g >> 1) + (g & 1)) * RS;
#pragma unroll
    for (int h = 0; h < 2; h++) {
      *(uint4*)(dst + (32 * h + 0) * RS) = make_uint4(movm_t(v[h][0].x), movm_t(v[h][1].x), movm_t(v[h][2].x), movm_t(v[h][3].x));
      *(uint4*)(dst + (32 * h + 2) * RS) = make_uint4(movm_t(v[h][0].y), movm_t(v[h][1].y), movm_t(v[h][2].y), movm_t(v[h][3].y));
      *(uint4*)(dst + (32 * h + 4) * RS) = make_uint4(movm_t(v[h][0].z), movm_t(v[h][1].z), movm_t(v[h][2].z), movm_t(v[h][3].z));
      *(uint4*)(dst + (32 * h + 6) * RS) = make_uint4(movm_t(v[h][0].w), movm_t(v[h][1].w), movm_t(v[h][2].w), movm_t(v[h][3].w));
    }
  }
  if (threadIdx.x == 0) TS(43);
  if (threadIdx.x == 192) TS(63);
  if (threadIdx.x == 0) LTS(1);
}

struct cplx { float r, i; };
__device__ __forceinline__ cplx cmul(cplx a, cplx b) { return {fmaf(a.r, b.r, -a.i * b.i), fmaf(a.r, b.i, a.i * b.r)}; }
__device__ __forceinline__ cplx csqr(cplx a) { return {fmaf(a.r, a.r, -a.i * a.i), (a.r + a.r) * a.i}; }
__device__ __forceinline__ cplx cexp_l(float ar2, float ai, float l) {
  const float m = ex2(ar2 * l);
  const float x = ai * l;
  return {m * __cosf(x), m * __sinf(x)};
}

__device__ __forceinline__ void colsum_publish(uint32_t sb, int rb, int hg, int ht, uint32_t tag) {
  const int lane = ht & 31, q = lane & 15, h = lane >> 4;
  const uint32_t src = sb + SM_CW + (ht >> 5) * 4096 + h * 128 + (q & 1) * 8;
  float s[4] = {0.f, 0.f, 0.f, 0.f};
#pragma unroll 8
  for (int r = 0; r < 16; r++) {
    const float2 v = lds64f(src + r * 256 + (((q >> 1) ^ ((2 * r + h) & 7)) << 4));
    s[0] += bf_lo(__float_as_uint(v.x)); s[1] += bf_hi(__float_as_uint(v.x));
    s[2] += bf_lo(__float_as_uint(v.y)); s[3] += bf_hi(__float_as_uint(v.y));
  }
#pragma unroll
  for (int k = 0; k < 4; k++) s[k] += __shfl_xor_sync(~0u, s[k], 16);
  if (h == 0)
    st_tagged3(&g_colsum[(hg * 16 + rb) * 48 + (ht >> 5) * 16 + q], (__float_as_uint(s[0]) & ~7u) | tag, __float_as_uint(s[1]),
               __float_as_uint(s[2]), __float_as_uint(s[3]));
}
__device__ __forceinline__ void colsum_gather(uint32_t sb, int hg, int ht, uint32_t tag) {
  const int lane = ht & 31, rec = (ht >> 5) * 16 + (lane & 15);
  const uint4* src = &g_colsum[(hg * 16 + (lane >> 4) * 8) * 48 + rec];
  float s[4] = {0.f, 0.f, 0.f, 0.f};
#pragma unroll 1
  for (int h = 0; h < 2; h++, src += 4 * 48) {
    uint4 v[4];
    int it = 0;
    do {
#pragma unroll
      for (int i = 0; i < 4; i++) v[i] = ld_tagged(src + i * 48);
      if (++it > (1 << 22)) __trap();
    } while (!__all_sync(~0u, (v[0].x & 7u) == tag && (v[1].x & 7u) == tag && (v[2].x & 7u) == tag && (v[3].x & 7u) == tag));
#pragma unroll
    for (int i = 0; i < 4; i++) {
      s[0] += __uint_as_float(v[i].x & ~7u); s[1] += __uint_as_float(v[i].y); s[2] += __uint_as_float(v[i].z); s[3] += __uint_as_float(v[i].w);
    }
  }
#pragma unroll
  for (int k = 0; k < 4; k++) s[k] += __shfl_xor_sync(~0u, s[k], 16);
  if (lane < 16) sts128f(sb + SM_CS + rec * 16, s[0], s[1], s[2], s[3]);
}

__device__ __forceinline__ uint32_t packh(float lo, float hi) { uint32_t r; asm("cvt.rn.f16x2.f32 %0, %1, %2;" : "=r"(r) : "f"(hi), "f"(lo)); return r; }
__device__ __forceinline__ void mma_f16(float* d, uint32_t a0, uint32_t a1, uint32_t a2, uint32_t a3, uint32_t b0, uint32_t b1) {
  asm volatile("mma.sync.aligned.m16n8k16.row.col.f32.f16.f16.f32 {%0,%1,%2,%3}, {%4,%5,%6,%7}, {%8,%9}, {%0,%1,%2,%3};"
      : "+f"(d[0]), "+f"(d[1]), "+f"(d[2]), "+f"(d[3]) : "r"(a0), "r"(a1), "r"(a2), "r"(a3), "r"(b0), "r"(b1));
}
struct HSeed { uint32_t r, i; };
__device__ __forceinline__ HSeed hseed(cplx s) { return {packh(s.r, s.r), packh(s.i, s.i)}; }
__device__ __forceinline__ void hcmul(uint32_t& o_r, uint32_t& o_i, uint32_t br, uint32_t bi, HSeed s) {
  asm("{\n.reg .b32 t, u;\nmul.rn.f16x2 t, %3, %5;\nneg.f16x2 t, t;\nmul.rn.f16x2 u, %3, %4;\nfma.rn.f16x2 %0, %2, %4, t;\nfma.rn.f16x2 %1, %2, %5, u;\n}"
      : "=&r"(o_r), "=&r"(o_i) : "r"(br), "r"(bi), "r"(s.r), "r"(s.i));
}
struct HTile { uint32_t r[4], i[4]; };
__device__ __forceinline__ void tile_set(HTile& t, int k, cplx a, cplx b) { t.r[k] = packh(a.r, b.r); t.i[k] = packh(a.i, b.i); }
__device__ __forceinline__ void tile_upper(HTile& t, HSeed s) { hcmul(t.r[2], t.i[2], t.r[0], t.i[0], s); hcmul(t.r[3], t.i[3], t.r[1], t.i[1], s); }
__device__ __forceinline__ HTile tile_shift(const HTile& t, HSeed s) {
  HTile o;
#pragma unroll
  for (int k = 0; k < 4; k++) hcmul(o.r[k], o.i[k], t.r[k], t.i[k], s);
  return o;
}
__device__ __forceinline__ void tile_put(const HTile& t, uint32_t a) {
  sts128(a, make_uint4(t.r[0], t.r[1], t.r[2], t.r[3]));
  sts128(a + 512, make_uint4(t.i[0], t.i[1], t.i[2], t.i[3]));
}
__device__ __forceinline__ HTile tile_get(uint32_t a) { HTile o; ldsm4t(o.r, a); ldsm4t(o.i, a + 512); return o; }
__device__ __forceinline__ void tile_mma(float* T, const HTile& a0, const HTile& a1, const HTile& b) {
  mma_f16(T, a0.r[0], a0.r[1], a0.r[2], a0.r[3], b.r[0], b.r[1]);
  mma_f16(T, a0.i[0], a0.i[1], a0.i[2], a0.i[3], b.i[0], b.i[1]);
  mma_f16(T, a1.r[0], a1.r[1], a1.r[2], a1.r[3], b.r[2], b.r[3]);
  mma_f16(T, a1.i[0], a1.i[1], a1.i[2], a1.i[3], b.i[2], b.i[3]);
}
__device__ __forceinline__ void tile_mma2(float* T, float* U, const HTile& a0, const HTile& a1, const HTile& b, const HTile& c) {
  mma_f16(T, a0.r[0], a0.r[1], a0.r[2], a0.r[3], b.r[0], b.r[1]);
  mma_f16(U, a0.r[0], a0.r[1], a0.r[2], a0.r[3], c.r[0], c.r[1]);
  mma_f16(T, a0.i[0], a0.i[1], a0.i[2], a0.i[3], b.i[0], b.i[1]);
  mma_f16(U, a0.i[0], a0.i[1], a0.i[2], a0.i[3], c.i[0], c.i[1]);
  mma_f16(T, a1.r[0], a1.r[1], a1.r[2], a1.r[3], b.r[2], b.r[3]);
  mma_f16(U, a1.r[0], a1.r[1], a1.r[2], a1.r[3], c.r[2], c.r[3]);
  mma_f16(T, a1.i[0], a1.i[1], a1.i[2], a1.i[3], b.i[2], b.i[3]);
  mma_f16(U, a1.i[0], a1.i[1], a1.i[2], a1.i[3], c.i[2], c.i[3]);
}
__device__ __forceinline__ void kgen_unit(uint32_t tab, uint32_t taba, float ar2, float ai, cplx c, float (&T)[5][4]) {
  const cplx z1 = cexp_l(ar2, ai, 1.f), z16 = cexp_l(ar2, ai, 16.f), z256 = cexp_l(ar2, ai, 256.f);
  HTile a0, a1, b0, b1;
  {
    const cplx y1 = {z16.r, -z16.i}, y2 = csqr(y1), y3 = cmul(y2, y1), y4 = csqr(y2), y5 = cmul(y4, y1), y6 = csqr(y3), y7 = cmul(y4, y3);
    HTile t;
    tile_set(t, 0, {1.f, 0.f}, y1); tile_set(t, 1, y2, y3); tile_set(t, 2, y4, y5); tile_set(t, 3, y6, y7);
    const HTile u = tile_shift(t, hseed(csqr(y4)));
    __syncwarp();
    tile_put(t, tab); tile_put(u, tab + 1024);
    __syncwarp();
    a0 = tile_get(taba); a1 = tile_get(taba + 256);
  }
  const cplx z2 = csqr(z1), z4 = csqr(z2), z8 = csqr(z4);
  const HSeed h8 = hseed(z8);
  const cplx d = cmul(c, z256), e = cmul(d, z256);
  {
    const cplx z512 = csqr(z256), f = cmul(e, z512), f8 = cmul(f, z8), f16 = cmul(f, z16), e4 = cmul(e, z4);
    HTile t, u;
    tile_set(t, 0, e4, cmul(e, z8)); tile_set(t, 1, cmul(e4, z8), cmul(e, z16));
    tile_upper(t, hseed(z256));
    tile_set(u, 0, f8, f16); tile_set(u, 1, cmul(f8, z256), cmul(f16, z256));
    tile_upper(u, hseed(z512));
    __syncwarp();
    tile_put(t, tab); tile_put(u, tab + 1024);
    __syncwarp();
    b0 = tile_get(tab); b1 = tile_get(tab + 1024);
  }
  {
    const cplx d2 = cmul(d, z2), d4 = cmul(d, z4);
    HTile t;
    tile_set(t, 0, d2, d4); tile_set(t, 1, cmul(d2, z4), cmul(d, z8));
    tile_upper(t, h8);
    __syncwarp();
    tile_put(t, tab);
    __syncwarp();
    tile_mma2(T[3], T[4], a0, a1, b0, b1);
    b0 = tile_get(tab);
  }
  {
    const cplx c1 = cmul(c, z1), c2 = cmul(c, z2), c3 = cmul(c1, z2), c4 = cmul(c, z4);
    HTile t;
    tile_set(t, 0, c1, c2); tile_set(t, 1, c3, c4); tile_set(t, 2, cmul(c1, z4), cmul(c2, z4)); tile_set(t, 3, cmul(c3, z4), cmul(c4, z4));
    const HTile u = tile_shift(t, h8);
    __syncwarp();
    tile_put(t, tab); tile_put(u, tab + 1024);
    __syncwarp();
    tile_mma(T[2], a0, a1, b0);
    b0 = tile_get(tab); b1 = tile_get(tab + 1024);
    tile_mma2(T[0], T[1], a0, a1, b0, b1);
  }
}
struct ModeIn { uint2 ar, ai, br, bi, cr, ci; };
__device__ __forceinline__ ModeIn load_modes(const Params& p, int idx) {
  return {*(const uint2*)(p.a_re + idx), *(const uint2*)(p.a_im + idx), *(const uint2*)(p.b_re + idx),
          *(const uint2*)(p.b_im + idx), *(const uint2*)(p.c_re + idx), *(const uint2*)(p.c_im + idx)};
}
__device__ __forceinline__ float bf_el(uint2 v, int k) { const uint32_t x = (k & 2) ? v.y : v.x; return (k & 1) ? bf_hi(x) : bf_lo(x); }
struct KGen { float4 cur; float T[5][4]; };
__device__ __forceinline__ uint32_t kgen_slot(uint32_t sb, int ht, int u) {
  return sb + (u < 3 ? SM_KC + (ht >> 5) * (KC_STRIDE * 2) + (u - 1) * 512 + (ht & 31) * 16 + 16 : SM_HALO + 1024 + ht * 16);
}
__device__ __forceinline__ void kgen_setup(KGen& s, uint32_t sb, int cta, int ht, const ModeIn& in, bf16 logdt, bf16 dskip) {
  const float dt = __bfloat162float(__float2bfloat16_rn(expf(__bfloat162float(logdt))));
  float mx = 0.f, k0 = 0.f, ar2[4];
  cplx c[4];
#pragma unroll
  for (int k = 0; k < 4; k++) {
    ar2[k] = (dt * bf_el(in.ar, k)) * 1.4426950408889634f;
    c[k] = cmul({bf_el(in.cr, k), bf_el(in.ci, k)}, {dt * bf_el(in.br, k), dt * bf_el(in.bi, k)});
    k0 += c[k].r;
    mx = fmaxf(mx, fmaxf(fabsf(c[k].r), fabsf(c[k].i)) * ex2(fmaxf(ar2[k] * 2048.f, 0.f)));
  }
  const int ex = min(max(267 - (int)(__reduce_max_sync(~0u, __float_as_uint(mx)) >> 23), 1), 253);
  const float sc = __uint_as_float(ex << 23);
#pragma unroll
  for (int o = 16; o > 0; o >>= 1) k0 += __shfl_xor_sync(~0u, k0, o);
  if ((ht & 31) == 0) {
    const uint32_t kc = sb + SM_KC + (ht >> 5) * (KC_STRIDE * 2);
    sts16(kc, __bfloat16_as_ushort(__float2bfloat16_rn(k0 + __bfloat162float(dskip))));
    sts16(kc + 641 * 2, 0);
    sts32f(kc + 644 * 2, __uint_as_float((254 - ex) << 23));
  }
  s.cur = make_float4(ar2[0], dt * bf_el(in.ai, 0), c[0].r * sc, c[0].i * sc);
#pragma unroll
  for (int k = 1; k < 4; k++) sts128f(kgen_slot(sb, ht, k), ar2[k], dt * bf_el(in.ai, k), c[k].r * sc, c[k].i * sc);
#pragma unroll
  for (int i = 0; i < 5; i++) s.T[i][0] = s.T[i][1] = s.T[i][2] = s.T[i][3] = 0.f;
}
__device__ __forceinline__ void kgen_finish(KGen& s, uint32_t sb, int cta, int ht) {
  const int w = ht >> 5, lane = ht & 31, g = lane >> 2, t = lane & 3;
  const uint32_t kc = sb + SM_KC + w * KC_STRIDE * 2;
  __syncwarp();
  const float inv = __uint_as_float(lds32(kc + 644 * 2));
  auto put = [&](int idx, float v) {
    sts16(kc + idx * 2, __bfloat16_as_ushort(__float2bfloat16_rn(v)));
  };
#pragma unroll
  for (int hi = 0; hi < 2; hi++)
#pragma unroll
    for (int lo = 0; lo < 2; lo++) {
      const int i = g + 8 * hi, j = 2 * t + lo, e = 2 * hi + lo;
      put(16 * i + 1 + j, s.T[0][e] * inv);
      put(16 * i + 9 + j, s.T[1][e] * inv);
      put(257 + 8 * i + j, s.T[2][e] * inv);
      put(385 + 4 * i + (j & 3) + 64 * (j >> 2), s.T[3][e] * inv);
      put(513 + 2 * i + lo + 32 * t, s.T[4][e] * inv);
    }
}

__device__ __forceinline__ void expand_taps(uint32_t sb, int ht) {
  const int ch = ht >> 5, lane = ht & 31;
  const uint32_t kc = sb + SM_KC + ch * KC_STRIDE * 2;
  const uint32_t dst0 = sb + cv_pe(ch);
  auto put = [&](int G, uint32_t u0, uint32_t u1, uint32_t v0, uint32_t v1, uint32_t v2, uint32_t v3, uint32_t v4, uint32_t v5, uint32_t v6, uint32_t v7) {
    const uint32_t dst = dst0 + G * 32;
    sts128(dst, make_uint4(v0 | (u0 << 16), v1 | (u1 << 16), v2 | (v0 << 16), v3 | (v1 << 16)));
    sts128(dst + 16, make_uint4(v4 | (v2 << 16), v5 | (v3 << 16), v6 | (v4 << 16), v7 | (v5 << 16)));
  };
  {
    const uint4 q = lds128(kc + lane * 16);
    const uint32_t pv = lane ? lds32(kc + lane * 16 - 4) : 0u;
    const uint32_t dst = dst0 + (lane + 2) * 32;
    sts128(dst, make_uint4(__byte_perm(q.x, pv, 0x5410), __byte_perm(q.x, pv, 0x7632), __byte_perm(q.y, q.x, 0x5410), __byte_perm(q.y, q.x, 0x7632)));
    sts128(dst + 16, make_uint4(__byte_perm(q.z, q.y, 0x5410), __byte_perm(q.z, q.y, 0x7632), __byte_perm(q.w, q.z, 0x5410), __byte_perm(q.w, q.z, 0x7632)));
    if (lane < 4) sts128(dst0 + lane * 16, make_uint4(0, 0, 0, 0));
  }
  uint32_t a[5], b[2][3], fv[4];
  {
    const uint32_t s1 = kc + 2 * (256 + 4 * lane);
#pragma unroll
    for (int k = 0; k < 5; k++) a[k] = lds16(s1 + 2 * k);
#pragma unroll
    for (int u = 0; u < 2; u++) {
      const uint32_t s2 = kc + 2 * (384 + 2 * (lane + 32 * u));
#pragma unroll
      for (int k = 0; k < 3; k++) b[u][k] = lds16(s2 + 2 * k);
    }
#pragma unroll
    for (int k = 0; k < 4; k++) fv[k] = lds16(kc + 2 * (640 - 4 * lane - k));
  }
  const uint32_t am1 = lds16(kc + 2 * (lane ? 256 + 4 * lane : 255)), am2 = lds16(kc + 2 * (lane ? 255 + 4 * lane : 254));
  const uint32_t bm2 = lds16(kc + 2 * (lane ? 384 + 2 * lane : 383)), k1024 = lds16(kc + 2 * 512);
  put(34 + lane, am2, am1, a[0], a[0], a[1], a[2], a[2], a[2], a[3], a[4]);
#pragma unroll
  for (int u = 0; u < 2; u++) put(66 + lane + 32 * u, u ? b[u][0] : bm2, b[u][0], b[u][0], b[u][0], b[u][0], b[u][1], b[u][1], b[u][1], b[u][2], b[u][2]);
  if (lane < 10) {
    const uint32_t v = lane == 0 ? k1024 : 0u;
    put(130 + lane, v, v, v, v, v, v, v, 0u, 0u, 0u);
  }
  const uint32_t ft = sb + cv_ft(ch) + 4 * lane;
#pragma unroll
  for (int ty = 0; ty < 2; ty++) {
    const uint32_t v = fv[ty] | (fv[ty + 2] << 16);
    sts32f(ft + ty * 512, __uint_as_float(v));
    sts32f(ft + ty * 512 + 128, 0.f);
    sts32f(ft + ty * 512 + 256 + (lane < 2 ? 120 : -8), __uint_as_float(lane < 2 ? 0u : v));
    sts32f(ft + ty * 512 + 384, 0.f);
  }
}

__device__ __forceinline__ int role_id() { int v; asm volatile("mov.u32 %0, %%ctaid.x;" : "=r"(v)); return v; }
#define GMAP 8
__device__ __forceinline__ int role_rb(int cta) { return 4 * (cta >> 5) + (cta & 3); }
__device__ __forceinline__ int role_hg(int cta) { return 2 * (((cta >> 3) & 3) ^ (((cta >> 5) & 1) * 3)) + ((cta >> 2) & 1); }
__device__ __forceinline__ int role_rb2(int cta) { return cta >> 3; }
__device__ __forceinline__ int role_q2(int cta) { return cta & 7; }

__global__ void __launch_bounds__(NTHREADS, 1) fused_kernel(const __grid_constant__ Params p) {
  extern __shared__ __align__(1024) uint8_t smem[];
  const uint32_t sb = s32(smem);
  const int tid = threadIdx.x, lane = tid & 31;
  const int warp = __shfl_sync(~0u, tid >> 5, 0);
  const uint32_t bar = sb + SM_BAR;
  if (tid == 0) TS(0);
  const int cta0 = role_id();
  if (warp == 0 && elect_one()) {
    const int rb = role_rb(cta0), hg = role_hg(cta0);
#pragma unroll
    for (int c = 0; c < 2; c++) { mbar_init(bar + 8 * (B_XF + c), 1); mbar_init(bar + 8 * (B_KVF + c), 1); }
    fence_async_smem();
#pragma unroll
    for (int c = 0; c < 2; c++) {
      mbar_expect(bar + 8 * (B_XF + c), 16384);
      tma_ld(sb + SM_X + c * 16384, &p.mapX128, (rb >> 3) * DM + c * 64, (rb & 7) * 128, bar + 8 * (B_XF + c));
      mbar_expect(bar + 8 * (B_KVF + c), 24576);
      tma_ld3(sb + SM_W + c * 24576, &p.mapW3, hg * 64, c * 64, 0, bar + 8 * (B_KVF + c));
    }
  }
  if (warp == 1 && elect_one()) {
    const int rb = role_rb(cta0), hg = role_hg(cta0);
#pragma unroll
    for (int c = 2; c < 8; c++) mbar_init(bar + 8 * (B_XF + c), 1);
    mbar_init(bar + 8 * (B_KVF + 2), 1); mbar_init(bar + 8 * B_CW, 1);
    fence_async_smem();
    delay<D_START>();
    mbar_expect(bar + 8 * B_CW, 12288);
    tma_ld3(sb + SM_CW, &p.mapW3h, hg * 64, rb * 32, 0, bar + 8 * B_CW);
#pragma unroll
    for (int c = 2; c < 8; c++) {
      mbar_expect(bar + 8 * (B_XF + c), 16384);
      tma_ld(sb + SM_X + c * 16384, &p.mapX128, (rb >> 3) * DM + c * 64, (rb & 7) * 128, bar + 8 * (B_XF + c));
      if (c < 3) {
        mbar_expect(bar + 8 * (B_KVF + c), 24576);
        tma_ld3(sb + SM_W + c * 24576, &p.mapW3, hg * 64, c * 64, 0, bar + 8 * (B_KVF + c));
      }
    }
    TS(56);
  }
  if ((warp & 2) != 0 && warp < 15 && elect_one()) {
    const int grp = 1 + (warp & 1) + 2 * (warp >> 2), cnt = grp < 4 ? 1 : grp < 5 ? 2 : grp < 7 ? 4 : 8;
#pragma unroll
    for (int k = 0; k < 10; k++)
      if (k != 0 || grp > 3 || grp == 2) mbar_init(bar + 8 * (10 * grp + k), cnt);
    fence_async_smem();
  }

  if (warp < 8) {
    if (tid == 0) TS(1);
    asm volatile("setmaxnreg.inc.sync.aligned.u32 %0;" ::"n"(R_CONS));
    const int cta = role_id();
    auto warp_id = [] { return __shfl_sync(~0u, opaque_tid() >> 5, 0); };
    if (tid == 0) TS(54);
#pragma unroll 1
    for (int layer = 0; layer < 2; layer++) {
      { const int cw = warp_id(); attn_phase(p, sb, layer, role_rb(cta), role_hg(cta), cw >> 2, cw & 3); }
      if (STOP == 1 + 3 * layer) return;
      { const int cw = warp_id(); proj_phase(p, sb, layer, role_rb2(cta), role_q2(cta), cw >> 2, cw & 3); }
      if (STOP == 2 + 3 * layer) return;
      conv_phase(p, sb, layer, cta);
      if (STOP == 3 + 3 * layer) return;
    }
    { const int cw = warp_id(); final_phase(p, sb, cta, cw >> 2, cw & 3); }
  } else if (warp < 12) {
    asm volatile("setmaxnreg.dec.sync.aligned.u32 %0;" ::"n"(R_HELP));
    const int ht = tid - 256;
    const int cta = role_id(), rb = role_rb(cta), hg = role_hg(cta);
    unsigned ep0 = 0;
    if (ht == 0) ep0 = ld_relaxed(&g_cnt[C_CS * 32]);
    bar_sync(0, NTHREADS);
    if (ht == 0) {
      asm volatile("st.shared.u32 [%0], %1;" ::"r"(sb + SM_EP), "r"(ep0 / NCTA) : "memory");
      mbar_arrive(bar + 8 * B_EP);
    }
    mbar_wait(bar + 8 * B_EP, 0);
    stats_publish(sb, 0, rb, hg, opaque_tid() - 256, part_tag(lds32(sb + SM_EP), 0));
    if (ht < 48) {
      const bf16* q = (&p.a_re)[ht >> 3];
      asm volatile("prefetch.global.L2 [%0];" ::"l"(q + cv_chan(cta, (ht >> 1) & 3) * 128 + (ht & 1) * 64));
    }
    {
      KGen kg;
      const uint32_t tab0 = sb + ((ht >> 5) < 2 ? SM_T : SM_T2 - 4096) + (ht >> 5) * 2048;
      const uint32_t tab = tab0 + (ht & 31) * 16, taba = tab0 + ((ht >> 3) & 1) * 1024 + (((ht >> 1) & 8) + (ht & 7)) * 16;
      delay<D_ST0>();
      stats_gather(sb, rb, opaque_tid() - 256, part_tag(lds32(sb + SM_EP), 0));
      if (ht == 0) TS(40);
      const int chn = cv_chan(cta, ht >> 5);
      const ModeIn modes = load_modes(p, chn * 128 + (ht & 31) * 4);
      const bf16 logdt = p.log_dt[chn], dskip = p.dskip[chn];
      if (!HALO_W14 && KG_START != 4) halo_receive(sb, 0, rb, hg, opaque_tid() - 256);
      if (KG_START == 1) mbar_wait(bar + 8 * B_HF, 0);
      kgen_setup(kg, sb, cta, ht, modes, logdt, dskip);
      if (!HALO_W14 && KG_START == 4) halo_receive(sb, 0, rb, hg, opaque_tid() - 256);
      if (KG_START == 2) mbar_wait(bar + 8 * B_HF, 0);
      if (KG_START == 3) mbar_wait(bar + 8 * B_QDONE, 0);
#pragma unroll 1
      for (int u = 0; u < 4; u++) {
        if (u == KG_PRE) {
          KTS(39);
          mbar_wait(bar + 8 * B_AD, 0);
          KTS(41);
        }
        kgen_unit(tab, taba, kg.cur.x, kg.cur.y, {kg.cur.z, kg.cur.w}, kg.T);
        kg.cur = lds128f(kgen_slot(sb, opaque_tid() - 256, u + 1));
      }
      kgen_finish(kg, sb, cta, opaque_tid() - 256);
    }
    KTS(51);
    bar_sync(4, 128);
#pragma unroll 1
    for (int layer = 0; layer < 2; layer++) {
      if (STOP <= 1 + 3 * layer) return;
      mbar_wait(bar + 8 * (EXP_LATE ? B_PS : B_PDONE), layer);
      expand_taps(sb, opaque_tid() - 256);
      conv_zero(sb, opaque_tid() - 256);
      if (ht == 0) TS(52 + layer);
      warp_release(bar + 8 * B_PE);
      if (STOP <= 2 + 3 * layer) return;
      {
        uint4 xr[4], st[4];
        const int c = opaque_tid() - 256;
        const SumAddr sa = conv_sum_addr(sb, c);
        conv_prep_load(sb, layer, cta, c, xr, st);
        conv_prep<true>(sb, layer, cta, c, xr, st, sa);
        if (layer == 1 && ht == 0) TS(62);
        const bf16* xup = g_xT + (size_t)(2 * layer * DM + cta) * LSEQ + (c + 128) * 8;
        const int ahead = layer ? S_AHEAD1 : S_AHEAD0;
        mbar_wait(bar + 8 * (B_U + 3), layer);
        if (ahead == 2) {
          conv_sums(sa, 1, c);
          fence_async_smem();
          bar_arrive(8, 256);
        }
        st[0] = ldcg128(xup);
#pragma unroll
        for (int lc = 0; lc < 4; lc++) {
          if (lc < 3 && lc + ahead < 4) {
            conv_sums(sa, lc + ahead, c);
            fence_async_smem();
            bar_arrive(7 + lc + ahead, 256);
            sched_fence<4>();
          }
          if (lc < 3) st[lc + 1] = ldcg128(xup + (lc + 1) * 128 * LSEQ);
          conv_epi(sb, layer, cta, lc, c, xr[lc], st[lc]);
          warp_release(bar + 8 * (B_E + lc));
          sched_fence<5>();
          if (layer == 1 && lc == 3 && ht == 0) TS(38);
        }
      }
      if (layer == 0 && STOP > 3) {
        const int c1 = role_id();
        stats_publish(sb, 1, role_rb(c1), role_hg(c1), opaque_tid() - 256, part_tag(lds32(sb + SM_EP), 2));
        delay<D_ST>();
        stats_gather(sb, role_rb(c1), opaque_tid() - 256, part_tag(lds32(sb + SM_EP), 2));
        if (ht == 0) TS(25);
        if (!HALO_W14) halo_receive(sb, 1, role_rb(c1), role_hg(c1), opaque_tid() - 256);
      }
    }
  } else {
    asm volatile("setmaxnreg.dec.sync.aligned.u32 %0;" ::"n"(512 - 2 * R_CONS - R_HELP));
    const int cta = role_id(), rb = role_rb(cta), hg = role_hg(cta), rb2 = role_rb2(cta), q2 = role_q2(cta);
    bar_sync(0, NTHREADS);
    if (warp != 12) {
      mbar_wait(bar + 8 * B_EP, 0);
      const uint32_t tag = lds32(sb + SM_EP) % 7 + 1;
      mbar_wait(bar + 8 * B_CW, 0);
      colsum_publish(sb, rb, hg, tid - 416, tag);
      if (tid == 416) TS(50);
      delay<D_CS>();
      colsum_gather(sb, hg, tid - 416, tag);
      __syncwarp();
      if (tid == 416) TS(55);
    }
    if (elect_one()) mbar_arrive(bar + 8 * B_CSF);
    if (warp == 12) {
      if (elect_one()) {
        unsigned epoch = 0;
#pragma unroll 1
        for (int layer = 0; layer < 2; layer++) {
          auto ld_w = [&](int c, int slot) {
            const uint32_t b = bar + 8 * (B_KVF + c);
            mbar_expect(b, 24576);
            tma_ld3(sb + SM_W + slot * 24576, &p.mapW3, hg * 64, c * 64, 0, b);
          };
          if (layer == 0) {
            mbar_wait(bar + 8 * (B_KVF + 2), 0);
            if (rb2 < 4) tma_prefetch2(&p.mapWo128, q2 * 64, rb2 * 128);
            asm volatile("prefetch.tensormap [%0];" ::"l"(&p.mapO) : "memory");
            asm volatile("prefetch.tensormap [%0];" ::"l"(&p.mapO128) : "memory");
            asm volatile("prefetch.tensormap [%0];" ::"l"(&p.mapXT) : "memory");
            asm volatile("prefetch.tensormap [%0];" ::"l"(&p.mapXT3) : "memory");
            mbar_wait(bar + 8 * B_EP, 0);
            epoch = lds32(sb + SM_EP);
          } else {
            mbar_wait(bar + 8 * B_PDONE, 0);
            ld_w(0, 0); ld_w(1, 1);
            mbar_wait(bar + 8 * (W2_LATE ? B_U : B_RE), 0);
            ld_w(2, 2);
          }
          {
            int slot = 0;
#pragma unroll 1
            for (int c = 3; c < 8; c++) {
              mbar_wait(bar + 8 * (B_KVE + c - 3), layer);
              ld_w(c, slot);
              slot = slot == 2 ? 0 : slot + 1;
            }
          }
          if (STOP <= 1 + 3 * layer) return;
          mbar_wait(bar + 8 * B_QDONE, layer);
          mbar_wait(bar + 8 * B_HF, layer);
#pragma unroll 1
          for (int c = 0; c < 4; c++) {
            const uint32_t b = bar + 8 * (B_WOF + c);
            mbar_expect(b, 16384);
            tma_ld(sb + SM_WO + c * 16384, &p.mapWo128, q2 * 64, c * 128, b);
          }
          {
            const uint32_t b = bar + 8 * B_RF;
            mbar_expect(b, 16384);
            if (layer == 0) tma_ld(sb + SM_R, &p.mapX128, (rb2 >> 3) * DM + q2 * 64, (rb2 & 7) * 128, b);
            else tma_ld3(sb + SM_R, &p.mapXT3, 0, DM + q2 * 64, rb2 * 2, b);
          }
          spin_until(&g_cnt[(C_O + rb2) * 32], (2 * epoch + layer + 1) * 16);
          fence_async_global();
#pragma unroll 1
          for (int c = 0; c < 8; c++) {
            const uint32_t b = bar + 8 * (B_OF + c);
            if (c == 4) { mbar_wait(bar + 8 * B_OST, layer); fence_async_smem(); }
            mbar_expect(b, 16384);
            tma_ld(sb + sm_o(c), &p.mapO128, c * 64, rb2 * 128, b);
          }
          if (STOP <= 3 + 3 * layer) return;
        }
      }
    } else if (warp == 13) {
      if (elect_one() && STOP > 1) {
        const unsigned target = (lds32(sb + SM_EP) + 1) * NCTA;
        mbar_wait(bar + 8 * B_RE, 0);
        spin_until(&g_cnt[C_CS * 32 + 2], 2 * target);
        mbar_arrive(bar + 8 * B_XV);
        if (STOP <= 3) return;
        auto ld_x = [&](int c) {
          mbar_expect(bar + 8 * (B_XF + c), 16384);
          tma_ld3(sb + SM_X + c * 16384, &p.mapXT3, 0, DM + c * 64, rb * 2, bar + 8 * (B_XF + c));
        };
        int done = 0, it = 0;
        while (done < 4) {
          const uint4 v = ld_tagged((const uint4*)&g_cnt[C_G1 * 32]);
          const int n = (int)(v.x - target) < 0 ? 0 : (int)(v.y - target) < 0 ? 1 : (int)(v.z - target) < 0 ? 2 : (int)(v.w - target) < 0 ? 3 : 4;
          if (++it > (1 << 23)) __trap();
          if (n == done) continue;
          if (n == 4) TS(44);
          fence_async_global();
          fence_async_smem();
          const int first = n == 4 && done > 1 ? 6 + (hg >> 2) : -1;
          if (first >= 0) ld_x(first);
#pragma unroll 1
          for (int c = 2 * done; c < 2 * n; c++)
            if (c != first) ld_x(c);
          done = n;
        }
        if (STOP <= 4) return;
        mbar_wait(bar + 8 * B_RE, 1);
        spin_until(&g_cnt[C_CS * 32 + 3], 2 * target);
        mbar_arrive(bar + 8 * B_XV);
      }
    } else if (warp == 15) {
      mbar_wait(bar + 8 * B_EP, 0);
      const unsigned epoch = lds32(sb + SM_EP);
#pragma unroll 1
      for (int layer = 0; layer < 2; layer++) {
        mbar_wait(bar + 8 * (B_KVF + FILL_AT), layer);
#pragma unroll
        for (int k = 0; k < 8; k++) ((uint4*)(g_xT + (size_t)(2 * layer * DM + cta) * LSEQ))[32 * k + lane] = make_uint4(~0u, ~0u, ~0u, ~0u);
        mbar_wait(bar + 8 * (B_KVF + FILL_AT + 1), layer);
#pragma unroll
        for (int k = 0; k < 4 * FIN_LL; k++)
          ((uint4*)(g_xT + (size_t)(3 * DM + cv_chan(cta, 3 - (k >> 2))) * LSEQ))[128 * layer + 32 * (k & 3) + lane] = make_uint4(~0u, ~0u, ~0u, ~0u);
        if (lane < 8) ((uint4*)g_stats)[layer * 1024 + cta * 8 + lane] = make_uint4(0, 0, 0, 0);
        __syncwarp();
        if (elect_one()) {
          red_release(&g_cnt[C_CS * 32 + layer]);
          spin_until(&g_cnt[C_CS * 32 + layer], (epoch + 1) * NCTA);
          mbar_arrive(bar + 8 * B_ZF);
          if (STOP > 2 + 3 * layer) {
#pragma unroll 1
            for (int lc = 0; lc < 4 - FIN_LL * layer; lc++) {
              mbar_wait(bar + 8 * (B_E + lc), layer);
              fence_reader();
              bulk_st(g_xT + (size_t)((2 * layer + 1) * DM + cv_chan(cta, lc)) * LSEQ, sb + cv_s(lc), 4096);
              bulk_commit();
              bulk_wait_all();
              red_relaxed(&g_cnt[(layer ? C_F + (cta >> 5) : C_G1) * 32 + lc]);
              if (lc == 3) TS(18);
            }
          }
        }
        __syncwarp();
        if (STOP <= 3) return;
      }
    } else if (warp == 14) {
      mbar_wait(bar + 8 * B_EP, 0);
      const unsigned epoch = lds32(sb + SM_EP);
#pragma unroll 1
      for (int layer = 0; layer < 2; layer++) {
        if (STOP <= 3 * layer) return;
        if (HALO_W14) halo_receive1(sb, layer, rb, hg, lane, 2 * epoch + layer + 1);
        if (STOP <= 1 + 3 * layer) return;
        mbar_wait(bar + 8 * B_ZF, layer);
        mbar_wait(bar + 8 * (EXP_LATE ? B_PS : B_PDONE), layer);
        delay<D_PST>();
        proj_stats(layer, rb2, q2, lane, part_tag(epoch, 2 * layer + 1));
        if (layer == 1 && lane == 0) TS(5);
        delay<D_PREP>();
        if (lane == 0) mbar_arrive(bar + 8 * B_GB);
      }
    }
  }
}

typedef CUresult (*EncodeFn)(CUtensorMap*, CUtensorMapDataType, cuuint32_t, void*, const cuuint64_t*, const cuuint64_t*,
                             const cuuint32_t*, const cuuint32_t*, CUtensorMapInterleave, CUtensorMapSwizzle,
                             CUtensorMapL2promotion, CUtensorMapFloatOOBfill);

static void make_map(EncodeFn enc, CUtensorMap* m, void* ptr, uint64_t cols, uint64_t rows, uint32_t box_rows) {
  cuuint64_t dims[2] = {cols, rows};
  cuuint64_t strides[1] = {cols * 2};
  cuuint32_t box[2] = {64, box_rows};
  cuuint32_t es[2] = {1, 1};
  enc(m, CU_TENSOR_MAP_DATA_TYPE_BFLOAT16, 2, ptr, dims, strides, box, es, CU_TENSOR_MAP_INTERLEAVE_NONE,
      CU_TENSOR_MAP_SWIZZLE_128B, CU_TENSOR_MAP_L2_PROMOTION_L2_128B, CU_TENSOR_MAP_FLOAT_OOB_FILL_NONE);
}
static void make_map3(EncodeFn enc, CUtensorMap* m, void* ptr, uint64_t d0, uint64_t cols, uint64_t rows, uint64_t blk_stride,
                      uint64_t nblocks, uint32_t nblk, uint32_t box_rows = 64) {
  cuuint64_t dims[3] = {d0, rows, nblocks};
  cuuint64_t strides[2] = {cols * 2, blk_stride * 2};
  cuuint32_t box[3] = {64, box_rows, nblk};
  cuuint32_t es[3] = {1, 1, 1};
  enc(m, CU_TENSOR_MAP_DATA_TYPE_BFLOAT16, 3, ptr, dims, strides, box, es, CU_TENSOR_MAP_INTERLEAVE_NONE,
      CU_TENSOR_MAP_SWIZZLE_128B, CU_TENSOR_MAP_L2_PROMOTION_L2_128B, CU_TENSOR_MAP_FLOAT_OOB_FILL_NONE);
}

extern "C" void kernel_launch(void* const* d_in, const int* in_sizes, int n_in, void* d_out, int out_size) {
  static Params prm;
  static void* cached[13] = {nullptr};
  static bool attr_done = false;
  bool same = attr_done && cached[12] == d_out;
  for (int i = 0; i < 12 && same; i++) same = cached[i] == d_in[i];
  if (!same) {
    void* fn = nullptr;
    cudaDriverEntryPointQueryResult qr;
    cudaGetDriverEntryPoint("cuTensorMapEncodeTiled", &fn, cudaEnableDefault, &qr);
    EncodeFn enc = (EncodeFn)fn;
    void *pO, *pXT;
    cudaGetSymbolAddress(&pO, g_O);
    cudaGetSymbolAddress(&pXT, g_xT);
    make_map(enc, &prm.mapO, pO, DM, LSEQ, 64);
    make_map(enc, &prm.mapXT, pXT, LSEQ, 4 * DM, 64);
    prm.out = (bf16*)d_out;
    make_map(enc, &prm.mapX128, d_in[0], 2 * DM, LSEQ / 2, 128);
    make_map(enc, &prm.mapWo128, d_in[2], DM, DM, 128);
    make_map(enc, &prm.mapO128, pO, DM, LSEQ, 128);
    make_map3(enc, &prm.mapW3, d_in[1], DM, 3 * DM, DM, DM, 3, 3);
    make_map3(enc, &prm.mapW3h, d_in[1], DM, 3 * DM, DM, DM, 3, 3, 32);
    make_map3(enc, &prm.mapXT3, pXT, 64, LSEQ, 4 * DM, 64, 32, 2);
    prm.a_re = (const bf16*)d_in[4]; prm.a_im = (const bf16*)d_in[5];
    prm.b_re = (const bf16*)d_in[6]; prm.b_im = (const bf16*)d_in[7];
    prm.c_re = (const bf16*)d_in[8]; prm.c_im = (const bf16*)d_in[9];
    prm.log_dt = (const bf16*)d_in[10]; prm.dskip = (const bf16*)d_in[11];
    cudaFuncSetAttribute(fused_kernel, cudaFuncAttributeMaxDynamicSharedMemorySize, SM_TOTAL);
    for (int i = 0; i < 12; i++) cached[i] = d_in[i];
    cached[12] = d_out;
    attr_done = true;
  }
  prm.stop = 100;
    fused_kernel<<<NCTA, NTHREADS, SM_TOTAL>>>(prm);
}
```

```cpp
#include <cuda_runtime.h>
#include <cuda_bf16.h>
#include <cuda.h>
#include <stdint.h>

typedef __nv_bfloat16 bf16;

constexpr int LSEQ = 2048;
constexpr int DM = 512;
constexpr int NCTA = 128;
constexpr int NTHREADS = 512;
#define RR 0
#define KG_PRE 2
#define W2_LATE 1
#define FILL_AT 5
#define EXP_LATE 1
#define RFENCE 1
#define D_FIN 550
#define FIN_LL 4
#define D_PREP 500
#define D_PST 0
#define D_HALO 500
#define STAG 2
#define D_ST 0
#define TLAYER 1
#define KG_PD 1
#define SUM_F32 0
#define CS_LATE0 1
#define D_HALO1 0
#define KG_START 0
#define S_AHEAD0 1
#define S_AHEAD1 2
#define PAUSE 0
#define PARK_FIRST 0
#define E_WAIT 0
#define G_WAIT 2
#define HALO_W14 1
#define D_START 200
#define D_CS 300
#define D_ST0 400
#define KG_LAST 0
#define X_JIT 0
#define KG_GATE 2
#define R_CONS 192
#define R_HELP 88

constexpr int SM_X = 0;
constexpr int SM_W = 131072;
constexpr int SM_KVX = SM_X;
constexpr int SM_OST = SM_X + 32768;
constexpr int SM_WO = SM_X + 65536;
__host__ __device__ constexpr int sm_o(int c) { return c < 4 ? SM_W + c * 16384 : SM_X + (c - 4) * 16384; }
constexpr int SM_R = 196608;
constexpr int SM_T = 212992;
constexpr int SM_KC = 217088;
constexpr int KC_STRIDE = 648;
constexpr int SM_CS = SM_KC + 4 * KC_STRIDE * 2;
constexpr int SM_CW = SM_R + 8192;
constexpr int SM_EP = SM_CS + 768;
constexpr int SM_BAR = SM_EP + 16;
constexpr int SM_T2 = SM_BAR + 896;
constexpr int SM_HALO = SM_T2 + 4096;
constexpr int SM_ST = SM_HALO + 3072;
constexpr int SM_TOTAL = SM_HALO + 4096;
static_assert(SM_TOTAL <= 232448, "shared memory");

constexpr int CV_UH = 140 * 16;
constexpr int CV_PECH = 1120 * 4;
constexpr int CV_PBW = 2112 * 2;
__host__ __device__ constexpr int cv_s(int lc) { return SM_X + lc * 32768; }
__host__ __device__ constexpr int cv_u(int lc) { return cv_s(lc) + 4096; }
__host__ __device__ constexpr int cv_pe(int lc) { return cv_u(lc) + 2 * CV_UH; }
__host__ __device__ constexpr int cv_pb(int lc) { return cv_pe(lc) + CV_PECH; }
__host__ __device__ constexpr int cv_ft(int lc) { return cv_pb(lc) + 4 * CV_PBW; }
static_assert(cv_ft(0) + 1024 <= 32768, "conv buffers");
__host__ __device__ constexpr int cv_chan(int cta, int lc) { return cta + 128 * lc; }

enum {
  B_XF = 0,
  B_KVF = 8,
  B_OF = 16,
  B_WOF = 24,
  B_T = 31,
  B_RF = 28,
  B_RE = 29,
  B_CW = 30,
  B_GB = 35,
  B_EP = 36,
  B_ZF = 37,
  B_XV = 39,
  B_SD = 38,
  B_KVE = 40,
  B_AD = 45,
  B_OST = 46,
  B_QDONE = 47,
  B_PDONE = 48,
  B_S = 50,
  B_E = 54,
  B_P = 58,
  B_PE = 62,
  B_STF = 63,
  B_CSF = 64,
  B_HF = 65,
  B_U = 70,
  B_PS = 74,
  B_COUNT = 80
};

enum {
  C_CS = 0,
  C_G1 = 2,
  C_O = 4,
  C_F = 20,
  C_COUNT = 24
};

__device__ __align__(128) unsigned g_cnt[C_COUNT * 32];
__device__ __align__(1024) bf16 g_O[LSEQ * DM];
__device__ __align__(1024) bf16 g_xT[4 * DM * LSEQ];
__device__ __align__(1024) float g_stats[2 * LSEQ * 2];
__device__ __align__(1024) uint4 g_colsum[8 * 16 * 48];
__device__ __align__(1024) uint4 g_halo[16 * 8 * 192];
__device__ __align__(1024) uint2 g_part[16 * 8 * 128];
#define TS(i) do { } while (0)

#define ATS(i, th) do { } while (0)
#define KTS(i) do { if (ht == 0) TS(i); } while (0)
#define FTS(i) do { } while (0)
#define LTS(i) do { } while (0)

#define STOP 100

struct Params {
  CUtensorMap mapO, mapXT, mapX128, mapWo128, mapO128, mapW3, mapW3h, mapXT3;
  const bf16 *a_re, *a_im, *b_re, *b_im, *c_re, *c_im, *log_dt, *dskip;
  bf16* out;
  int stop;
};

__device__ __forceinline__ uint32_t s32(const void* p) { return (uint32_t)__cvta_generic_to_shared(p); }
__device__ __forceinline__ void mbar_init(uint32_t b, int c) { asm volatile("mbarrier.init.shared::cta.b64 [%0], %1;" ::"r"(b), "r"(c) : "memory"); }
__device__ __forceinline__ void mbar_expect(uint32_t b, int bytes) { asm volatile("mbarrier.arrive.expect_tx.shared::cta.b64 _, [%0], %1;" ::"r"(b), "r"(bytes) : "memory"); }
__device__ __forceinline__ void mbar_arrive(uint32_t b) { asm volatile("mbarrier.arrive.shared::cta.b64 _, [%0];" ::"r"(b) : "memory"); }
__device__ __forceinline__ void mbar_arrive_if(uint32_t b, bool c) {
  asm volatile("{\n.reg .pred p;\nsetp.ne.u32 p, %1, 0;\n@p mbarrier.arrive.shared::cta.b64 _, [%0];\n}" ::"r"(b), "r"((uint32_t)c) : "memory");
}
__device__ __forceinline__ void mbar_wait(uint32_t b, int parity) {
  asm volatile("{\n.reg .pred p;\nWAIT_LOOP:\nmbarrier.try_wait.parity.shared::cta.b64 p, [%0], %1;\n@p bra WAIT_DONE;\nbra WAIT_LOOP;\nWAIT_DONE:\n}" ::"r"(b), "r"(parity) : "memory");
}
template <int N> __device__ __forceinline__ void delay() {
  if constexpr (N > 0) {
    uint32_t t0, t;
    asm volatile("mov.u32 %0, %%clock;" : "=r"(t0));
    do { asm volatile("mov.u32 %0, %%clock;" : "=r"(t)); } while (t - t0 < N);
  }
}
#define SF 3
template <int ID> __device__ __forceinline__ void sched_fence() {
  if constexpr ((SF >> ID) & 1)
    asm volatile("{\n.reg .pred p;\n.reg .u32 t;\nsetp.eq.u32 p, %0, 0;\n@p mov.u32 t, %%clock;\n@p st.shared.u32 [%0], t;\n}" ::"r"(gridDim.x) : "memory");
}
__device__ __forceinline__ int opaque_tid() { int v; asm volatile("mov.u32 %0, %%tid.x;" : "=r"(v)); return v; }
__device__ __forceinline__ bool elect_one() {
  uint32_t r;
  asm volatile("{\n.reg .pred p;\nelect.sync _|p, 0xffffffff;\nselp.u32 %0, 1, 0, p;\n}" : "=r"(r));
  return r != 0;
}
__device__ __forceinline__ void tma_ld(uint32_t dst, const CUtensorMap* m, int c0, int c1, uint32_t bar) {
  asm volatile("cp.async.bulk.tensor.2d.shared::cluster.global.mbarrier::complete_tx::bytes [%0], [%1, {%3, %4}], [%2];"
               ::"r"(dst), "l"(m), "r"(bar), "r"(c0), "r"(c1) : "memory");
}
__device__ __forceinline__ void tma_ld3(uint32_t dst, const CUtensorMap* m, int c0, int c1, int c2, uint32_t bar) {
  asm volatile("cp.async.bulk.tensor.3d.shared::cluster.global.mbarrier::complete_tx::bytes [%0], [%1, {%3, %4, %5}], [%2];"
               ::"r"(dst), "l"(m), "r"(bar), "r"(c0), "r"(c1), "r"(c2) : "memory");
}
__device__ __forceinline__ void tma_prefetch2(const CUtensorMap* m, int c0, int c1) {
  asm volatile("cp.async.bulk.prefetch.tensor.2d.L2.global.tile [%0, {%1, %2}];" ::"l"(m), "r"(c0), "r"(c1) : "memory");
}
__device__ __forceinline__ void tma_prefetch3(const CUtensorMap* m, int c0, int c1, int c2) {
  asm volatile("cp.async.bulk.prefetch.tensor.3d.L2.global.tile [%0, {%1, %2, %3}];" ::"l"(m), "r"(c0), "r"(c1), "r"(c2) : "memory");
}
__device__ __forceinline__ void tma_st(const CUtensorMap* m, int c0, int c1, uint32_t src) {
  asm volatile("cp.async.bulk.tensor.2d.global.shared::cta.bulk_group [%0, {%2, %3}], [%1];" ::"l"(m), "r"(src), "r"(c0), "r"(c1) : "memory");
}
__device__ __forceinline__ void bulk_ld(uint32_t dst, const void* src, int bytes, uint32_t bar) {
  asm volatile("cp.async.bulk.shared::cluster.global.mbarrier::complete_tx::bytes [%0], [%1], %2, [%3];" ::"r"(dst), "l"(src), "r"(bytes), "r"(bar) : "memory");
}
__device__ __forceinline__ void bulk_st(void* dst, uint32_t src, int bytes) {
  asm volatile("cp.async.bulk.global.shared::cta.bulk_group [%0], [%1], %2;" ::"l"(dst), "r"(src), "r"(bytes) : "memory");
}
__device__ __forceinline__ void bulk_red_add_f32(void* dst, uint32_t src, int bytes) {
  asm volatile("cp.reduce.async.bulk.global.shared::cta.bulk_group.add.f32 [%0], [%1], %2;" ::"l"(dst), "r"(src), "r"(bytes) : "memory");
}
__device__ __forceinline__ void bulk_commit() { asm volatile("cp.async.bulk.commit_group;" ::: "memory"); }
__device__ __forceinline__ void bulk_wait_all() { asm volatile("cp.async.bulk.wait_group 0;" ::: "memory"); }
__device__ __forceinline__ void fence_async_smem() { asm volatile("fence.proxy.async.shared::cta;" ::: "memory"); }
__device__ __forceinline__ void fence_writer() { if (!RFENCE) fence_async_smem(); }
__device__ __forceinline__ void fence_reader() { if (RFENCE) fence_async_smem(); }
__device__ __forceinline__ void fence_async_global() { asm volatile("fence.proxy.async.global;" ::: "memory"); }
__device__ __forceinline__ void bar_sync(int id, int n) { asm volatile("bar.sync %0, %1;" ::"r"(id), "r"(n) : "memory"); }
__device__ __forceinline__ void bar_arrive(int id, int n) { asm volatile("bar.arrive %0, %1;" ::"r"(id), "r"(n) : "memory"); }
__device__ __forceinline__ void wg_fence() { asm volatile("wgmma.fence.sync.aligned;" ::: "memory"); }
__device__ __forceinline__ void wg_commit() { asm volatile("wgmma.commit_group.sync.aligned;" ::: "memory"); }
template <int N> __device__ __forceinline__ void wg_wait() { asm volatile("wgmma.wait_group.sync.aligned %0;" ::"n"(N) : "memory"); }
__device__ __forceinline__ uint64_t mkdesc(uint32_t addr, uint32_t lbo, uint32_t sbo, int sw) {
  return (uint64_t)((addr & 0x3FFFF) >> 4) | ((uint64_t)(lbo >> 4) << 16) | ((uint64_t)(sbo >> 4) << 32) | ((uint64_t)sw << 62);
}
__device__ __forceinline__ void ldsm4(uint32_t* r, uint32_t a) {
  asm volatile("ldmatrix.sync.aligned.m8n8.x4.shared.b16 {%0,%1,%2,%3}, [%4];" : "=r"(r[0]), "=r"(r[1]), "=r"(r[2]), "=r"(r[3]) : "r"(a) : "memory");
}
__device__ __forceinline__ void ldsm4t(uint32_t* r, uint32_t a) {
  asm volatile("ldmatrix.sync.aligned.m8n8.x4.trans.shared.b16 {%0,%1,%2,%3}, [%4];" : "=r"(r[0]), "=r"(r[1]), "=r"(r[2]), "=r"(r[3]) : "r"(a) : "memory");
}
__device__ __forceinline__ void stsm4(uint32_t a, uint32_t r0, uint32_t r1, uint32_t r2, uint32_t r3) {
  asm volatile("stmatrix.sync.aligned.m8n8.x4.shared.b16 [%0], {%1,%2,%3,%4};" ::"r"(a), "r"(r0), "r"(r1), "r"(r2), "r"(r3) : "memory");
}
__device__ __forceinline__ void stsm4t(uint32_t a, uint32_t r0, uint32_t r1, uint32_t r2, uint32_t r3) {
  asm volatile("stmatrix.sync.aligned.m8n8.x4.trans.shared.b16 [%0], {%1,%2,%3,%4};" ::"r"(a), "r"(r0), "r"(r1), "r"(r2), "r"(r3) : "memory");
}
__device__ __forceinline__ uint32_t movm_t(uint32_t a) { uint32_t r; asm volatile("movmatrix.sync.aligned.m8n8.trans.b16 %0, %1;" : "=r"(r) : "r"(a)); return r; }
__device__ __forceinline__ uint32_t lds32(uint32_t a) { uint32_t v; asm volatile("ld.shared.b32 %0, [%1];" : "=r"(v) : "r"(a) : "memory"); return v; }
__device__ __forceinline__ float2 lds64f(uint32_t a) { float2 v; asm volatile("ld.shared.v2.f32 {%0,%1}, [%2];" : "=f"(v.x), "=f"(v.y) : "r"(a) : "memory"); return v; }
__device__ __forceinline__ float4 lds128f(uint32_t a) { float4 v; asm volatile("ld.shared.v4.f32 {%0,%1,%2,%3}, [%4];" : "=f"(v.x), "=f"(v.y), "=f"(v.z), "=f"(v.w) : "r"(a) : "memory"); return v; }
__device__ __forceinline__ uint4 lds128(uint32_t a) { uint4 v; asm volatile("ld.shared.v4.b32 {%0,%1,%2,%3}, [%4];" : "=r"(v.x), "=r"(v.y), "=r"(v.z), "=r"(v.w) : "r"(a) : "memory"); return v; }
__device__ __forceinline__ void sts128(uint32_t a, uint4 v) { asm volatile("st.shared.v4.b32 [%0], {%1,%2,%3,%4};" ::"r"(a), "r"(v.x), "r"(v.y), "r"(v.z), "r"(v.w) : "memory"); }
__device__ __forceinline__ void sts128f(uint32_t a, float x, float y, float z, float w) { asm volatile("st.shared.v4.f32 [%0], {%1,%2,%3,%4};" ::"r"(a), "f"(x), "f"(y), "f"(z), "f"(w) : "memory"); }
__device__ __forceinline__ void sts32f(uint32_t a, float v) { asm volatile("st.shared.f32 [%0], %1;" ::"r"(a), "f"(v) : "memory"); }
__device__ __forceinline__ void sts16(uint32_t a, uint16_t v) { asm volatile("st.shared.u16 [%0], %1;" ::"r"(a), "h"(v) : "memory"); }
__device__ __forceinline__ uint32_t lds16(uint32_t a) { uint16_t v; asm volatile("ld.shared.u16 %0, [%1];" : "=h"(v) : "r"(a) : "memory"); return v; }
__device__ __forceinline__ uint32_t packbf(float lo, float hi) { uint32_t r; asm("cvt.rn.bf16x2.f32 %0, %1, %2;" : "=r"(r) : "f"(hi), "f"(lo)); return r; }
__device__ __forceinline__ float bf_lo(uint32_t v) { return __uint_as_float(v << 16); }
__device__ __forceinline__ float bf_hi(uint32_t v) { return __uint_as_float(v & 0xffff0000u); }
__device__ __forceinline__ float ex2(float x) { float r; asm("ex2.approx.ftz.f32 %0, %1;" : "=f"(r) : "f"(x)); return r; }
__device__ __forceinline__ float rsqrt_approx(float x) { float r; asm("rsqrt.approx.ftz.f32 %0, %1;" : "=f"(r) : "f"(x)); return r; }
__device__ __forceinline__ float rcp_approx(float x) { float r; asm("rcp.approx.ftz.f32 %0, %1;" : "=f"(r) : "f"(x)); return r; }
__device__ __forceinline__ void mma_bf16(float* d, const uint32_t* a, uint32_t b0, uint32_t b1) {
  asm("mma.sync.aligned.m16n8k16.row.col.f32.bf16.bf16.f32 {%0,%1,%2,%3}, {%4,%5,%6,%7}, {%8,%9}, {%0,%1,%2,%3};"
               : "+f"(d[0]), "+f"(d[1]), "+f"(d[2]), "+f"(d[3]) : "r"(a[0]), "r"(a[1]), "r"(a[2]), "r"(a[3]), "r"(b0), "r"(b1));
}
__device__ __forceinline__ void mma_bf16_k8(float* d, uint32_t a0, uint32_t a1, uint32_t b) {
  asm("mma.sync.aligned.m16n8k8.row.col.f32.bf16.bf16.f32 {%0,%1,%2,%3}, {%4,%5}, {%6}, {%0,%1,%2,%3};"
      : "+f"(d[0]), "+f"(d[1]), "+f"(d[2]), "+f"(d[3]) : "r"(a0), "r"(a1), "r"(b));
}
__device__ __forceinline__ void red_release(unsigned* p) { asm volatile("red.release.gpu.global.add.u32 [%0], 1;" ::"l"(p) : "memory"); }
__device__ __forceinline__ void red_relaxed(unsigned* p) { asm volatile("red.relaxed.gpu.global.add.u32 [%0], 1;" ::"l"(p) : "memory"); }
__device__ __forceinline__ unsigned ld_relaxed(const unsigned* p) { unsigned v; asm volatile("ld.relaxed.gpu.global.u32 %0, [%1];" : "=r"(v) : "l"(p) : "memory"); return v; }
__device__ __forceinline__ void spin_until(const unsigned* p, unsigned target) {
  int it = 0;
  while ((int)(ld_relaxed(p) - target) < 0) {
    if (++it > (1 << 23)) __trap();
  }
}
__device__ __forceinline__ uint4 ldcg128(const void* p) { uint4 v; asm volatile("ld.global.cg.v4.b32 {%0,%1,%2,%3}, [%4];" : "=r"(v.x), "=r"(v.y), "=r"(v.z), "=r"(v.w) : "l"(p) : "memory"); return v; }
__device__ __forceinline__ uint4 ld_tagged(const uint4* p) { uint4 v; asm volatile("ld.relaxed.gpu.global.v4.u32 {%0,%1,%2,%3}, [%4];" : "=r"(v.x), "=r"(v.y), "=r"(v.z), "=r"(v.w) : "l"(p) : "memory"); return v; }
__device__ __forceinline__ uint2 ld_part(const uint2* p) { uint2 v; asm volatile("ld.relaxed.gpu.global.v2.u32 {%0,%1}, [%2];" : "=r"(v.x), "=r"(v.y) : "l"(p) : "memory"); return v; }
__device__ __forceinline__ void st_part(uint2* p, float s, float q, uint32_t tag) {
  asm volatile("st.relaxed.gpu.global.v2.u32 [%0], {%1,%2};" ::"l"(p), "r"(__float_as_uint(s)), "r"((__float_as_uint(q) & ~7u) | tag) : "memory");
}
__device__ __forceinline__ uint32_t part_tag(uint32_t epoch, int k) { return (4 * (epoch % 7) + k) % 7 + 1; }
__device__ __forceinline__ void st_tagged3(uint4* p, uint32_t a, uint32_t b, uint32_t c, uint32_t tag) { asm volatile("st.relaxed.gpu.global.v4.u32 [%0], {%1,%2,%3,%4};" ::"l"(p), "r"(a), "r"(b), "r"(c), "r"(tag) : "memory"); }
__device__ __forceinline__ uint32_t hadd2(uint32_t a, uint32_t b) { uint32_t r; asm("add.rn.bf16x2 %0, %1, %2;" : "=r"(r) : "r"(a), "r"(b)); return r; }
__device__ __forceinline__ uint32_t hmul2(uint32_t a, uint32_t b) { uint32_t r; asm("mul.rn.bf16x2 %0, %1, %2;" : "=r"(r) : "r"(a), "r"(b)); return r; }

template<int N,int TB> __device__ __forceinline__ void wgmma_rs(float* d, const uint32_t* a, uint64_t db, int sd);
template<int N,int TA,int TB> __device__ __forceinline__ void wgmma_ss(float* d, uint64_t da, uint64_t db, int sd);
template<> __device__ __forceinline__ void wgmma_rs<128,0>(float* d, const uint32_t* a, uint64_t db, int sd) {
  asm volatile("{\n.reg .pred p;\nsetp.ne.b32 p, %69, 0;\nwgmma.mma_async.sync.aligned.m64n128k16.f32.bf16.bf16 {%0,%1,%2,%3,%4,%5,%6,%7,%8,%9,%10,%11,%12,%13,%14,%15,%16,%17,%18,%19,%20,%21,%22,%23,%24,%25,%26,%27,%28,%29,%30,%31,%32,%33,%34,%35,%36,%37,%38,%39,%40,%41,%42,%43,%44,%45,%46,%47,%48,%49,%50,%51,%52,%53,%54,%55,%56,%57,%58,%59,%60,%61,%62,%63}, {%64,%65,%66,%67}, %68, p, 1, 1, 0;\n}\n"
   : "+f"(d[0]),"+f"(d[1]),"+f"(d[2]),"+f"(d[3]),"+f"(d[4]),"+f"(d[5]),"+f"(d[6]),"+f"(d[7]),"+f"(d[8]),"+f"(d[9]),"+f"(d[10]),"+f"(d[11]),"+f"(d[12]),"+f"(d[13]),"+f"(d[14]),"+f"(d[15]),"+f"(d[16]),"+f"(d[17]),"+f"(d[18]),"+f"(d[19]),"+f"(d[20]),"+f"(d[21]),"+f"(d[22]),"+f"(d[23]),"+f"(d[24]),"+f"(d[25]),"+f"(d[26]),"+f"(d[27]),"+f"(d[28]),"+f"(d[29]),"+f"(d[30]),"+f"(d[31]),"+f"(d[32]),"+f"(d[33]),"+f"(d[34]),"+f"(d[35]),"+f"(d[36]),"+f"(d[37]),"+f"(d[38]),"+f"(d[39]),"+f"(d[40]),"+f"(d[41]),"+f"(d[42]),"+f"(d[43]),"+f"(d[44]),"+f"(d[45]),"+f"(d[46]),"+f"(d[47]),"+f"(d[48]),"+f"(d[49]),"+f"(d[50]),"+f"(d[51]),"+f"(d[52]),"+f"(d[53]),"+f"(d[54]),"+f"(d[55]),"+f"(d[56]),"+f"(d[57]),"+f"(d[58]),"+f"(d[59]),"+f"(d[60]),"+f"(d[61]),"+f"(d[62]),"+f"(d[63])
   : "r"(a[0]), "r"(a[1]), "r"(a[2]), "r"(a[3]), "l"(db), "r"(sd));
}
template<> __device__ __forceinline__ void wgmma_rs<120,0>(float* d, const uint32_t* a, uint64_t db, int sd) {
  asm volatile("{\n.reg .pred p;\nsetp.ne.b32 p, %65, 0;\nwgmma.mma_async.sync.aligned.m64n120k16.f32.bf16.bf16 {%0,%1,%2,%3,%4,%5,%6,%7,%8,%9,%10,%11,%12,%13,%14,%15,%16,%17,%18,%19,%20,%21,%22,%23,%24,%25,%26,%27,%28,%29,%30,%31,%32,%33,%34,%35,%36,%37,%38,%39,%40,%41,%42,%43,%44,%45,%46,%47,%48,%49,%50,%51,%52,%53,%54,%55,%56,%57,%58,%59}, {%60,%61,%62,%63}, %64, p, 1, 1, 0;\n}\n"
   : "+f"(d[0]),"+f"(d[1]),"+f"(d[2]),"+f"(d[3]),"+f"(d[4]),"+f"(d[5]),"+f"(d[6]),"+f"(d[7]),"+f"(d[8]),"+f"(d[9]),"+f"(d[10]),"+f"(d[11]),"+f"(d[12]),"+f"(d[13]),"+f"(d[14]),"+f"(d[15]),"+f"(d[16]),"+f"(d[17]),"+f"(d[18]),"+f"(d[19]),"+f"(d[20]),"+f"(d[21]),"+f"(d[22]),"+f"(d[23]),"+f"(d[24]),"+f"(d[25]),"+f"(d[26]),"+f"(d[27]),"+f"(d[28]),"+f"(d[29]),"+f"(d[30]),"+f"(d[31]),"+f"(d[32]),"+f"(d[33]),"+f"(d[34]),"+f"(d[35]),"+f"(d[36]),"+f"(d[37]),"+f"(d[38]),"+f"(d[39]),"+f"(d[40]),"+f"(d[41]),"+f"(d[42]),"+f"(d[43]),"+f"(d[44]),"+f"(d[45]),"+f"(d[46]),"+f"(d[47]),"+f"(d[48]),"+f"(d[49]),"+f"(d[50]),"+f"(d[51]),"+f"(d[52]),"+f"(d[53]),"+f"(d[54]),"+f"(d[55]),"+f"(d[56]),"+f"(d[57]),"+f"(d[58]),"+f"(d[59])
   : "r"(a[0]), "r"(a[1]), "r"(a[2]), "r"(a[3]), "l"(db), "r"(sd));
}
template<> __device__ __forceinline__ void wgmma_rs<112,0>(float* d, const uint32_t* a, uint64_t db, int sd) {
  asm volatile("{\n.reg .pred p;\nsetp.ne.b32 p, %61, 0;\nwgmma.mma_async.sync.aligned.m64n112k16.f32.bf16.bf16 {%0,%1,%2,%3,%4,%5,%6,%7,%8,%9,%10,%11,%12,%13,%14,%15,%16,%17,%18,%19,%20,%21,%22,%23,%24,%25,%26,%27,%28,%29,%30,%31,%32,%33,%34,%35,%36,%37,%38,%39,%40,%41,%42,%43,%44,%45,%46,%47,%48,%49,%50,%51,%52,%53,%54,%55}, {%56,%57,%58,%59}, %60, p, 1, 1, 0;\n}\n"
   : "+f"(d[0]),"+f"(d[1]),"+f"(d[2]),"+f"(d[3]),"+f"(d[4]),"+f"(d[5]),"+f"(d[6]),"+f"(d[7]),"+f"(d[8]),"+f"(d[9]),"+f"(d[10]),"+f"(d[11]),"+f"(d[12]),"+f"(d[13]),"+f"(d[14]),"+f"(d[15]),"+f"(d[16]),"+f"(d[17]),"+f"(d[18]),"+f"(d[19]),"+f"(d[20]),"+f"(d[21]),"+f"(d[22]),"+f"(d[23]),"+f"(d[24]),"+f"(d[25]),"+f"(d[26]),"+f"(d[27]),"+f"(d[28]),"+f"(d[29]),"+f"(d[30]),"+f"(d[31]),"+f"(d[32]),"+f"(d[33]),"+f"(d[34]),"+f"(d[35]),"+f"(d[36]),"+f"(d[37]),"+f"(d[38]),"+f"(d[39]),"+f"(d[40]),"+f"(d[41]),"+f"(d[42]),"+f"(d[43]),"+f"(d[44]),"+f"(d[45]),"+f"(d[46]),"+f"(d[47]),"+f"(d[48]),"+f"(d[49]),"+f"(d[50]),"+f"(d[51]),"+f"(d[52]),"+f"(d[53]),"+f"(d[54]),"+f"(d[55])
   : "r"(a[0]), "r"(a[1]), "r"(a[2]), "r"(a[3]), "l"(db), "r"(sd));
}
template<> __device__ __forceinline__ void wgmma_rs<104,0>(float* d, const uint32_t* a, uint64_t db, int sd) {
  asm volatile("{\n.reg .pred p;\nsetp.ne.b32 p, %57, 0;\nwgmma.mma_async.sync.aligned.m64n104k16.f32.bf16.bf16 {%0,%1,%2,%3,%4,%5,%6,%7,%8,%9,%10,%11,%12,%13,%14,%15,%16,%17,%18,%19,%20,%21,%22,%23,%24,%25,%26,%27,%28,%29,%30,%31,%32,%33,%34,%35,%36,%37,%38,%39,%40,%41,%42,%43,%44,%45,%46,%47,%48,%49,%50,%51}, {%52,%53,%54,%55}, %56, p, 1, 1, 0;\n}\n"
   : "+f"(d[0]),"+f"(d[1]),"+f"(d[2]),"+f"(d[3]),"+f"(d[4]),"+f"(d[5]),"+f"(d[6]),"+f"(d[7]),"+f"(d[8]),"+f"(d[9]),"+f"(d[10]),"+f"(d[11]),"+f"(d[12]),"+f"(d[13]),"+f"(d[14]),"+f"(d[15]),"+f"(d[16]),"+f"(d[17]),"+f"(d[18]),"+f"(d[19]),"+f"(d[20]),"+f"(d[21]),"+f"(d[22]),"+f"(d[23]),"+f"(d[24]),"+f"(d[25]),"+f"(d[26]),"+f"(d[27]),"+f"(d[28]),"+f"(d[29]),"+f"(d[30]),"+f"(d[31]),"+f"(d[32]),"+f"(d[33]),"+f"(d[34]),"+f"(d[35]),"+f"(d[36]),"+f"(d[37]),"+f"(d[38]),"+f"(d[39]),"+f"(d[40]),"+f"(d[41]),"+f"(d[42]),"+f"(d[43]),"+f"(d[44]),"+f"(d[45]),"+f"(d[46]),"+f"(d[47]),"+f"(d[48]),"+f"(d[49]),"+f"(d[50]),"+f"(d[51])
   : "r"(a[0]), "r"(a[1]), "r"(a[2]), "r"(a[3]), "l"(db), "r"(sd));
}
template<> __device__ __forceinline__ void wgmma_rs<96,0>(float* d, const uint32_t* a, uint64_t db, int sd) {
  asm volatile("{\n.reg .pred p;\nsetp.ne.b32 p, %53, 0;\nwgmma.mma_async.sync.aligned.m64n96k16.f32.bf16.bf16 {%0,%1,%2,%3,%4,%5,%6,%7,%8,%9,%10,%11,%12,%13,%14,%15,%16,%17,%18,%19,%20,%21,%22,%23,%24,%25,%26,%27,%28,%29,%30,%31,%32,%33,%34,%35,%36,%37,%38,%39,%40,%41,%42,%43,%44,%45,%46,%47}, {%48,%49,%50,%51}, %52, p, 1, 1, 0;\n}\n"
   : "+f"(d[0]),"+f"(d[1]),"+f"(d[2]),"+f"(d[3]),"+f"(d[4]),"+f"(d[5]),"+f"(d[6]),"+f"(d[7]),"+f"(d[8]),"+f"(d[9]),"+f"(d[10]),"+f"(d[11]),"+f"(d[12]),"+f"(d[13]),"+f"(d[14]),"+f"(d[15]),"+f"(d[16]),"+f"(d[17]),"+f"(d[18]),"+f"(d[19]),"+f"(d[20]),"+f"(d[21]),"+f"(d[22]),"+f"(d[23]),"+f"(d[24]),"+f"(d[25]),"+f"(d[26]),"+f"(d[27]),"+f"(d[28]),"+f"(d[29]),"+f"(d[30]),"+f"(d[31]),"+f"(d[32]),"+f"(d[33]),"+f"(d[34]),"+f"(d[35]),"+f"(d[36]),"+f"(d[37]),"+f"(d[38]),"+f"(d[39]),"+f"(d[40]),"+f"(d[41]),"+f"(d[42]),"+f"(d[43]),"+f"(d[44]),"+f"(d[45]),"+f"(d[46]),"+f"(d[47])
   : "r"(a[0]), "r"(a[1]), "r"(a[2]), "r"(a[3]), "l"(db), "r"(sd));
}
template<> __device__ __forceinline__ void wgmma_rs<88,0>(float* d, const uint32_t* a, uint64_t db, int sd) {
  asm volatile("{\n.reg .pred p;\nsetp.ne.b32 p, %49, 0;\nwgmma.mma_async.sync.aligned.m64n88k16.f32.bf16.bf16 {%0,%1,%2,%3,%4,%5,%6,%7,%8,%9,%10,%11,%12,%13,%14,%15,%16,%17,%18,%19,%20,%21,%22,%23,%24,%25,%26,%27,%28,%29,%30,%31,%32,%33,%34,%35,%36,%37,%38,%39,%40,%41,%42,%43}, {%44,%45,%46,%47}, %48, p, 1, 1, 0;\n}\n"
   : "+f"(d[0]),"+f"(d[1]),"+f"(d[2]),"+f"(d[3]),"+f"(d[4]),"+f"(d[5]),"+f"(d[6]),"+f"(d[7]),"+f"(d[8]),"+f"(d[9]),"+f"(d[10]),"+f"(d[11]),"+f"(d[12]),"+f"(d[13]),"+f"(d[14]),"+f"(d[15]),"+f"(d[16]),"+f"(d[17]),"+f"(d[18]),"+f"(d[19]),"+f"(d[20]),"+f"(d[21]),"+f"(d[22]),"+f"(d[23]),"+f"(d[24]),"+f"(d[25]),"+f"(d[26]),"+f"(d[27]),"+f"(d[28]),"+f"(d[29]),"+f"(d[30]),"+f"(d[31]),"+f"(d[32]),"+f"(d[33]),"+f"(d[34]),"+f"(d[35]),"+f"(d[36]),"+f"(d[37]),"+f"(d[38]),"+f"(d[39]),"+f"(d[40]),"+f"(d[41]),"+f"(d[42]),"+f"(d[43])
   : "r"(a[0]), "r"(a[1]), "r"(a[2]), "r"(a[3]), "l"(db), "r"(sd));
}
template<> __device__ __forceinline__ void wgmma_rs<80,0>(float* d, const uint32_t* a, uint64_t db, int sd) {
  asm volatile("{\n.reg .pred p;\nsetp.ne.b32 p, %45, 0;\nwgmma.mma_async.sync.aligned.m64n80k16.f32.bf16.bf16 {%0,%1,%2,%3,%4,%5,%6,%7,%8,%9,%10,%11,%12,%13,%14,%15,%16,%17,%18,%19,%20,%21,%22,%23,%24,%25,%26,%27,%28,%29,%30,%31,%32,%33,%34,%35,%36,%37,%38,%39}, {%40,%41,%42,%43}, %44, p, 1, 1, 0;\n}\n"
   : "+f"(d[0]),"+f"(d[1]),"+f"(d[2]),"+f"(d[3]),"+f"(d[4]),"+f"(d[5]),"+f"(d[6]),"+f"(d[7]),"+f"(d[8]),"+f"(d[9]),"+f"(d[10]),"+f"(d[11]),"+f"(d[12]),"+f"(d[13]),"+f"(d[14]),"+f"(d[15]),"+f"(d[16]),"+f"(d[17]),"+f"(d[18]),"+f"(d[19]),"+f"(d[20]),"+f"(d[21]),"+f"(d[22]),"+f"(d[23]),"+f"(d[24]),"+f"(d[25]),"+f"(d[26]),"+f"(d[27]),"+f"(d[28]),"+f"(d[29]),"+f"(d[30]),"+f"(d[31]),"+f"(d[32]),"+f"(d[33]),"+f"(d[34]),"+f"(d[35]),"+f"(d[36]),"+f"(d[37]),"+f"(d[38]),"+f"(d[39])
   : "r"(a[0]), "r"(a[1]), "r"(a[2]), "r"(a[3]), "l"(db), "r"(sd));
}
template<> __device__ __forceinline__ void wgmma_rs<72,0>(float* d, const uint32_t* a, uint64_t db, int sd) {
  asm volatile("{\n.reg .pred p;\nsetp.ne.b32 p, %41, 0;\nwgmma.mma_async.sync.aligned.m64n72k16.f32.bf16.bf16 {%0,%1,%2,%3,%4,%5,%6,%7,%8,%9,%10,%11,%12,%13,%14,%15,%16,%17,%18,%19,%20,%21,%22,%23,%24,%25,%26,%27,%28,%29,%30,%31,%32,%33,%34,%35}, {%36,%37,%38,%39}, %40, p, 1, 1, 0;\n}\n"
   : "+f"(d[0]),"+f"(d[1]),"+f"(d[2]),"+f"(d[3]),"+f"(d[4]),"+f"(d[5]),"+f"(d[6]),"+f"(d[7]),"+f"(d[8]),"+f"(d[9]),"+f"(d[10]),"+f"(d[11]),"+f"(d[12]),"+f"(d[13]),"+f"(d[14]),"+f"(d[15]),"+f"(d[16]),"+f"(d[17]),"+f"(d[18]),"+f"(d[19]),"+f"(d[20]),"+f"(d[21]),"+f"(d[22]),"+f"(d[23]),"+f"(d[24]),"+f"(d[25]),"+f"(d[26]),"+f"(d[27]),"+f"(d[28]),"+f"(d[29]),"+f"(d[30]),"+f"(d[31]),"+f"(d[32]),"+f"(d[33]),"+f"(d[34]),"+f"(d[35])
   : "r"(a[0]), "r"(a[1]), "r"(a[2]), "r"(a[3]), "l"(db), "r"(sd));
}
template<> __device__ __forceinline__ void wgmma_rs<64,0>(float* d, const uint32_t* a, uint64_t db, int sd) {
  asm volatile("{\n.reg .pred p;\nsetp.ne.b32 p, %37, 0;\nwgmma.mma_async.sync.aligned.m64n64k16.f32.bf16.bf16 {%0,%1,%2,%3,%4,%5,%6,%7,%8,%9,%10,%11,%12,%13,%14,%15,%16,%17,%18,%19,%20,%21,%22,%23,%24,%25,%26,%27,%28,%29,%30,%31}, {%32,%33,%34,%35}, %36, p, 1, 1, 0;\n}\n"
   : "+f"(d[0]),"+f"(d[1]),"+f"(d[2]),"+f"(d[3]),"+f"(d[4]),"+f"(d[5]),"+f"(d[6]),"+f"(d[7]),"+f"(d[8]),"+f"(d[9]),"+f"(d[10]),"+f"(d[11]),"+f"(d[12]),"+f"(d[13]),"+f"(d[14]),"+f"(d[15]),"+f"(d[16]),"+f"(d[17]),"+f"(d[18]),"+f"(d[19]),"+f"(d[20]),"+f"(d[21]),"+f"(d[22]),"+f"(d[23]),"+f"(d[24]),"+f"(d[25]),"+f"(d[26]),"+f"(d[27]),"+f"(d[28]),"+f"(d[29]),"+f"(d[30]),"+f"(d[31])
   : "r"(a[0]), "r"(a[1]), "r"(a[2]), "r"(a[3]), "l"(db), "r"(sd));
}
template<> __device__ __forceinline__ void wgmma_ss<64,0,1>(float* d, uint64_t da, uint64_t db, int sd) {
  asm volatile("{\n.reg .pred p;\nsetp.ne.b32 p, %34, 0;\nwgmma.mma_async.sync.aligned.m64n64k16.f32.bf16.bf16 {%0,%1,%2,%3,%4,%5,%6,%7,%8,%9,%10,%11,%12,%13,%14,%15,%16,%17,%18,%19,%20,%21,%22,%23,%24,%25,%26,%27,%28,%29,%30,%31}, %32, %33, p, 1, 1, 0, 1;\n}\n"
   : "+f"(d[0]),"+f"(d[1]),"+f"(d[2]),"+f"(d[3]),"+f"(d[4]),"+f"(d[5]),"+f"(d[6]),"+f"(d[7]),"+f"(d[8]),"+f"(d[9]),"+f"(d[10]),"+f"(d[11]),"+f"(d[12]),"+f"(d[13]),"+f"(d[14]),"+f"(d[15]),"+f"(d[16]),"+f"(d[17]),"+f"(d[18]),"+f"(d[19]),"+f"(d[20]),"+f"(d[21]),"+f"(d[22]),"+f"(d[23]),"+f"(d[24]),"+f"(d[25]),"+f"(d[26]),"+f"(d[27]),"+f"(d[28]),"+f"(d[29]),"+f"(d[30]),"+f"(d[31])
   : "l"(da), "l"(db), "r"(sd));
}
template<> __device__ __forceinline__ void wgmma_ss<64,1,1>(float* d, uint64_t da, uint64_t db, int sd) {
  asm volatile("{\n.reg .pred p;\nsetp.ne.b32 p, %34, 0;\nwgmma.mma_async.sync.aligned.m64n64k16.f32.bf16.bf16 {%0,%1,%2,%3,%4,%5,%6,%7,%8,%9,%10,%11,%12,%13,%14,%15,%16,%17,%18,%19,%20,%21,%22,%23,%24,%25,%26,%27,%28,%29,%30,%31}, %32, %33, p, 1, 1, 1, 1;\n}\n"
   : "+f"(d[0]),"+f"(d[1]),"+f"(d[2]),"+f"(d[3]),"+f"(d[4]),"+f"(d[5]),"+f"(d[6]),"+f"(d[7]),"+f"(d[8]),"+f"(d[9]),"+f"(d[10]),"+f"(d[11]),"+f"(d[12]),"+f"(d[13]),"+f"(d[14]),"+f"(d[15]),"+f"(d[16]),"+f"(d[17]),"+f"(d[18]),"+f"(d[19]),"+f"(d[20]),"+f"(d[21]),"+f"(d[22]),"+f"(d[23]),"+f"(d[24]),"+f"(d[25]),"+f"(d[26]),"+f"(d[27]),"+f"(d[28]),"+f"(d[29]),"+f"(d[30]),"+f"(d[31])
   : "l"(da), "l"(db), "r"(sd));
}
template<> __device__ __forceinline__ void wgmma_ss<192,0,1>(float* d, uint64_t da, uint64_t db, int sd) {
  asm volatile("{\n.reg .pred p;\nsetp.ne.b32 p, %98, 0;\nwgmma.mma_async.sync.aligned.m64n192k16.f32.bf16.bf16 {%0,%1,%2,%3,%4,%5,%6,%7,%8,%9,%10,%11,%12,%13,%14,%15,%16,%17,%18,%19,%20,%21,%22,%23,%24,%25,%26,%27,%28,%29,%30,%31,%32,%33,%34,%35,%36,%37,%38,%39,%40,%41,%42,%43,%44,%45,%46,%47,%48,%49,%50,%51,%52,%53,%54,%55,%56,%57,%58,%59,%60,%61,%62,%63,%64,%65,%66,%67,%68,%69,%70,%71,%72,%73,%74,%75,%76,%77,%78,%79,%80,%81,%82,%83,%84,%85,%86,%87,%88,%89,%90,%91,%92,%93,%94,%95}, %96, %97, p, 1, 1, 0, 1;\n}\n"
   : "+f"(d[0]),"+f"(d[1]),"+f"(d[2]),"+f"(d[3]),"+f"(d[4]),"+f"(d[5]),"+f"(d[6]),"+f"(d[7]),"+f"(d[8]),"+f"(d[9]),"+f"(d[10]),"+f"(d[11]),"+f"(d[12]),"+f"(d[13]),"+f"(d[14]),"+f"(d[15]),"+f"(d[16]),"+f"(d[17]),"+f"(d[18]),"+f"(d[19]),"+f"(d[20]),"+f"(d[21]),"+f"(d[22]),"+f"(d[23]),"+f"(d[24]),"+f"(d[25]),"+f"(d[26]),"+f"(d[27]),"+f"(d[28]),"+f"(d[29]),"+f"(d[30]),"+f"(d[31]),"+f"(d[32]),"+f"(d[33]),"+f"(d[34]),"+f"(d[35]),"+f"(d[36]),"+f"(d[37]),"+f"(d[38]),"+f"(d[39]),"+f"(d[40]),"+f"(d[41]),"+f"(d[42]),"+f"(d[43]),"+f"(d[44]),"+f"(d[45]),"+f"(d[46]),"+f"(d[47]),"+f"(d[48]),"+f"(d[49]),"+f"(d[50]),"+f"(d[51]),"+f"(d[52]),"+f"(d[53]),"+f"(d[54]),"+f"(d[55]),"+f"(d[56]),"+f"(d[57]),"+f"(d[58]),"+f"(d[59]),"+f"(d[60]),"+f"(d[61]),"+f"(d[62]),"+f"(d[63]),"+f"(d[64]),"+f"(d[65]),"+f"(d[66]),"+f"(d[67]),"+f"(d[68]),"+f"(d[69]),"+f"(d[70]),"+f"(d[71]),"+f"(d[72]),"+f"(d[73]),"+f"(d[74]),"+f"(d[75]),"+f"(d[76]),"+f"(d[77]),"+f"(d[78]),"+f"(d[79]),"+f"(d[80]),"+f"(d[81]),"+f"(d[82]),"+f"(d[83]),"+f"(d[84]),"+f"(d[85]),"+f"(d[86]),"+f"(d[87]),"+f"(d[88]),"+f"(d[89]),"+f"(d[90]),"+f"(d[91]),"+f"(d[92]),"+f"(d[93]),"+f"(d[94]),"+f"(d[95])
   : "l"(da), "l"(db), "r"(sd));
}
template<> __device__ __forceinline__ void wgmma_ss<192,1,1>(float* d, uint64_t da, uint64_t db, int sd) {
  asm volatile("{\n.reg .pred p;\nsetp.ne.b32 p, %98, 0;\nwgmma.mma_async.sync.aligned.m64n192k16.f32.bf16.bf16 {%0,%1,%2,%3,%4,%5,%6,%7,%8,%9,%10,%11,%12,%13,%14,%15,%16,%17,%18,%19,%20,%21,%22,%23,%24,%25,%26,%27,%28,%29,%30,%31,%32,%33,%34,%35,%36,%37,%38,%39,%40,%41,%42,%43,%44,%45,%46,%47,%48,%49,%50,%51,%52,%53,%54,%55,%56,%57,%58,%59,%60,%61,%62,%63,%64,%65,%66,%67,%68,%69,%70,%71,%72,%73,%74,%75,%76,%77,%78,%79,%80,%81,%82,%83,%84,%85,%86,%87,%88,%89,%90,%91,%92,%93,%94,%95}, %96, %97, p, 1, 1, 1, 1;\n}\n"
   : "+f"(d[0]),"+f"(d[1]),"+f"(d[2]),"+f"(d[3]),"+f"(d[4]),"+f"(d[5]),"+f"(d[6]),"+f"(d[7]),"+f"(d[8]),"+f"(d[9]),"+f"(d[10]),"+f"(d[11]),"+f"(d[12]),"+f"(d[13]),"+f"(d[14]),"+f"(d[15]),"+f"(d[16]),"+f"(d[17]),"+f"(d[18]),"+f"(d[19]),"+f"(d[20]),"+f"(d[21]),"+f"(d[22]),"+f"(d[23]),"+f"(d[24]),"+f"(d[25]),"+f"(d[26]),"+f"(d[27]),"+f"(d[28]),"+f"(d[29]),"+f"(d[30]),"+f"(d[31]),"+f"(d[32]),"+f"(d[33]),"+f"(d[34]),"+f"(d[35]),"+f"(d[36]),"+f"(d[37]),"+f"(d[38]),"+f"(d[39]),"+f"(d[40]),"+f"(d[41]),"+f"(d[42]),"+f"(d[43]),"+f"(d[44]),"+f"(d[45]),"+f"(d[46]),"+f"(d[47]),"+f"(d[48]),"+f"(d[49]),"+f"(d[50]),"+f"(d[51]),"+f"(d[52]),"+f"(d[53]),"+f"(d[54]),"+f"(d[55]),"+f"(d[56]),"+f"(d[57]),"+f"(d[58]),"+f"(d[59]),"+f"(d[60]),"+f"(d[61]),"+f"(d[62]),"+f"(d[63]),"+f"(d[64]),"+f"(d[65]),"+f"(d[66]),"+f"(d[67]),"+f"(d[68]),"+f"(d[69]),"+f"(d[70]),"+f"(d[71]),"+f"(d[72]),"+f"(d[73]),"+f"(d[74]),"+f"(d[75]),"+f"(d[76]),"+f"(d[77]),"+f"(d[78]),"+f"(d[79]),"+f"(d[80]),"+f"(d[81]),"+f"(d[82]),"+f"(d[83]),"+f"(d[84]),"+f"(d[85]),"+f"(d[86]),"+f"(d[87]),"+f"(d[88]),"+f"(d[89]),"+f"(d[90]),"+f"(d[91]),"+f"(d[92]),"+f"(d[93]),"+f"(d[94]),"+f"(d[95])
   : "l"(da), "l"(db), "r"(sd));
}

__device__ __forceinline__ void stats_publish(uint32_t sb, int layer, int rb, int hg, int ht, uint32_t tag) {
  const int lane = ht & 31, w = ht >> 5, g = lane >> 2, t = lane & 3, ks = hg & 3;
  uint32_t xa;
  if (layer == 0) {
    const int row = 16 * w + (lane & 15), kc = 2 * ks + (lane >> 4);
    xa = row * 128 + ((kc ^ (row & 7)) << 4);
  } else {
    const int k = 16 * ks + (lane & 7) + 8 * (lane >> 4), pc = 2 * w + ((lane >> 3) & 1);
    xa = k * 128 + ((pc ^ (k & 7)) << 4);
  }
  float s[4] = {0.f, 0.f, 0.f, 0.f}, q[4] = {0.f, 0.f, 0.f, 0.f};
#pragma unroll 1
  for (int c = hg >> 2; c < 8; c += 2) {
    uint32_t A[2][4];
    mbar_wait(sb + SM_BAR + 8 * (B_XF + c), layer);
#pragma unroll
    for (int h = 0; h < 2; h++) {
      if (layer == 0) ldsm4(A[h], sb + SM_X + c * 16384 + h * 8192 + xa);
      else ldsm4t(A[h], sb + SM_X + c * 16384 + h * 8192 + xa);
    }
    if (c >= 6) ATS(48, 256);
    if (c < 2) ATS(51, 256);
#pragma unroll
    for (int r = 0; r < 4; r++)
#pragma unroll
      for (int i = 0; i < 2; i++) {
        const uint32_t v = A[r >> 1][2 * i + (r & 1)];
        const float a = bf_lo(v), b = bf_hi(v);
        s[r] += a + b; q[r] = fmaf(a, a, q[r]); q[r] = fmaf(b, b, q[r]);
      }
  }
#pragma unroll
  for (int r = 0; r < 2; r++) {
    s[r] = ((t & 2) ? s[r + 2] : s[r]) + __shfl_xor_sync(~0u, (t & 2) ? s[r] : s[r + 2], 2);
    q[r] = ((t & 2) ? q[r + 2] : q[r]) + __shfl_xor_sync(~0u, (t & 2) ? q[r] : q[r + 2], 2);
  }
  s[0] = ((t & 1) ? s[1] : s[0]) + __shfl_xor_sync(~0u, (t & 1) ? s[0] : s[1], 1);
  q[0] = ((t & 1) ? q[1] : q[0]) + __shfl_xor_sync(~0u, (t & 1) ? q[0] : q[1], 1);
  st_part(&g_part[(rb * 8 + hg) * 128 + 64 * (t >> 1) + 16 * w + 8 * (t & 1) + g], s[0], q[0], tag);
  ATS(49, 256);
}
__device__ __forceinline__ void stats_gather(uint32_t sb, int rb, int ht, uint32_t tag) {
  const uint2* src = &g_part[rb * 8 * 128 + ht];
  uint2 v[8];
  for (int it = 0;; it++) {
    uint32_t bad = 0;
#pragma unroll
    for (int i = 0; i < 8; i++) v[i] = ld_part(src + i * 128);
#pragma unroll
    for (int i = 0; i < 8; i++) bad |= v[i].y ^ tag;
    if (__all_sync(~0u, (bad & 7u) == 0)) break;
    if (it > (1 << 22)) __trap();
  }
  float s = 0.f, q = 0.f;
#pragma unroll
  for (int i = 0; i < 8; i++) { s += __uint_as_float(v[i].x); q += __uint_as_float(v[i].y); }
  const float mean = s * (1.f / DM);
  const float rstd = rsqrt_approx(fmaxf(q * (1.f / DM) - mean * mean, 0.f) + 1e-5f);
  asm volatile("st.shared.v2.f32 [%0], {%1,%2};" ::"r"(sb + SM_ST + ht * 8), "f"(mean), "f"(rstd) : "memory");
  __syncwarp();
  if (elect_one()) mbar_arrive(sb + SM_BAR + 8 * B_STF);
}
__device__ __forceinline__ void halo_receive(uint32_t sb, int layer, int rb, int hg, int ht) {
  const int lane = ht & 31, h = ht >> 5;
  uint4 kv = make_uint4(0, 0, 0, 0);
  mbar_wait(sb + SM_BAR + 8 * B_SD, layer);
  if (rb & 7) {
    const uint32_t tag = 2 * lds32(sb + SM_EP) + layer + 1;
    const uint4* src = &g_halo[((rb - 1) * 8 + hg) * 192 + h * 48];
    if (layer == 0) delay<D_HALO>(); else delay<D_HALO1>();
    uint4 a;
    uint2 b;
    int it = 0;
    do {
      a = ld_tagged(src + lane); b = ld_part((const uint2*)(src + 32) + lane);
      if (++it > (1 << 22)) __trap();
    } while (!__all_sync(~0u, a.w == tag && b.y == tag));
    kv = make_uint4(a.x, a.y, movm_t(a.z), movm_t(b.x));
  }
  sts128(sb + SM_KVX + h * 512 + lane * 16, kv);
  ATS(61, 256);
  bar_arrive(7, 160);
  if (elect_one()) mbar_arrive(sb + SM_BAR + 8 * B_HF);
}

__device__ __forceinline__ void halo_receive1(uint32_t sb, int layer, int rb, int hg, int lane, uint32_t tag) {
  uint4 a[4];
  uint2 b[4];
  mbar_wait(sb + SM_BAR + 8 * B_SD, layer);
  if (rb & 7) {
    const uint4* src = &g_halo[((rb - 1) * 8 + hg) * 192];
    if (layer == 0) delay<D_HALO>(); else delay<D_HALO1>();
    for (int it = 0;; it++) {
      uint32_t bad = 0;
#pragma unroll
      for (int h = 0; h < 4; h++) { a[h] = ld_tagged(src + h * 48 + lane); b[h] = ld_part((const uint2*)(src + h * 48 + 32) + lane); }
#pragma unroll
      for (int h = 0; h < 4; h++) {
        bad |= (a[h].w ^ tag) | (b[h].y ^ tag);
        a[h].z = movm_t(a[h].z); a[h].w = movm_t(b[h].x);
      }
      if (__all_sync(~0u, bad == 0)) break;
      if (it > (1 << 22)) __trap();
    }
  } else {
#pragma unroll
    for (int h = 0; h < 4; h++) a[h] = make_uint4(0, 0, 0, 0);
  }
#pragma unroll
  for (int h = 0; h < 4; h++) sts128(sb + SM_KVX + h * 512 + lane * 16, a[h]);
  ATS(61, 448);
  bar_arrive(7, 64);
  if (lane < 4) mbar_arrive(sb + SM_BAR + 8 * B_HF);
}

template <bool TR>
__device__ __forceinline__ void gemm_section(float* acc, float2* cs, uint32_t sb, int layer, int wg, int w, int lane) {
  const uint32_t bar = sb + SM_BAR;
  const bool leader = (w == 0) && (lane == 0);
  auto issue = [&](int c, int slot) {
    mbar_wait(bar + 8 * (B_XF + c), layer);
    mbar_wait(bar + 8 * (B_KVF + c), layer);
    const uint64_t da = mkdesc(sb + SM_X + c * 16384 + wg * 8192, TR ? 8192 : 16, 1024, 1);
    const uint64_t db = mkdesc(sb + SM_W + slot * 24576, 8192, 1024, 1);
    wg_fence();
#pragma unroll
    for (int ks = 0; ks < 4; ks++) wgmma_ss<192, TR ? 1 : 0, 1>(acc, da + (TR ? ks * 128 : ks * 2), db + ks * 128, (c | ks) != 0);
    wg_commit();
  };
  auto step = [&](int c, int slot) {
    issue(c, slot);
    wg_wait<1>();
    if (leader) mbar_arrive(bar + 8 * (B_KVE + c - 1));
  };
  if (!TR) bar_sync(0, NTHREADS);
  issue(0, 0);
  if (threadIdx.x == 0) TS(2 + layer * 20 + 0);
  if (threadIdx.x == 128 && layer == 1) TS(60);
  step(1, 1); step(2, 2); step(3, 0); step(4, 1);
  auto ld_cs = [&](int j0) {
#pragma unroll
    for (int j = j0; j < j0 + 8; j++) cs[j] = lds64f(sb + SM_CS + 4 * (8 * j + 2 * (lane & 3)));
  };
  if (TR) ld_cs(8);
  step(5, 2);
  if (!TR && !CS_LATE0) { mbar_wait(bar + 8 * B_CSF, 0); ld_cs(8); }
  if (TR || !CS_LATE0) ld_cs(16);
  if (wg == 0) bar_sync(5, 256);
  issue(6, 0);
  issue(7, 1);
  if (wg == 1) bar_arrive(5, 256);
  if (!TR && CS_LATE0) { mbar_wait(bar + 8 * B_CSF, 0); ld_cs(8); ld_cs(16); }
}

__device__ __forceinline__ void attn_phase(const Params& p, uint32_t sb, int layer, int rb, int hg, int wg, int w) {
  const int lane = opaque_tid() & 31;
  const int g = lane >> 2, t = lane & 3;
  const uint32_t bar = sb + SM_BAR;
  const int row0 = 64 * wg + 16 * w;
  const bool leader = (w == 0) && (lane == 0);
  float acc[96];
  float2 cs[24];
  if (layer) gemm_section<true>(acc, cs, sb, layer, wg, w, lane);
  else gemm_section<false>(acc, cs, sb, layer, wg, w, lane);
  ATS(41, 224);
  mbar_wait(bar + 8 * B_STF, layer);
  const uint32_t tag = 2 * lds32(sb + SM_EP) + layer + 1;
  const float2 st0 = lds64f(sb + SM_ST + (row0 + g) * 8), st1 = lds64f(sb + SM_ST + (row0 + g + 8) * 8);
  const float mean0 = st0.x, rstd0 = st0.y, mean1 = st1.x, rstd1 = st1.y;
  wg_wait<0>();
  if (threadIdx.x == 0) TS(2 + layer * 20 + 1);
  ATS(39, 224);
  if (leader) mbar_arrive(bar + 8 * B_QDONE);

  uint32_t fp[4][4], fl[4][4], fh[4][4], qa[4][4];
  const int cw = 4 * wg + w;
  {
    const float nm0 = -mean0 * rstd0, nm1 = -mean1 * rstd1;
    const uint32_t kvx = sb + SM_KVX + cw * 2048 + lane * 16;
#pragma unroll
    for (int h = 0; h < 4; h++)
#pragma unroll
      for (int k = 0; k < 4; k++) {
        const int j = 8 + (k >> 1) * 8 + 2 * h + (k & 1);
        fh[h][k] = packbf(fmaf(acc[4 * j + 2], rstd1, nm1 * cs[j].x), fmaf(acc[4 * j + 3], rstd1, nm1 * cs[j].y));
      }
    if (cw == 7) {
      uint4* halo = &g_halo[(rb * 8 + hg) * 192];
#pragma unroll
      for (int h = 0; h < 4; h++) {
        st_tagged3(halo + h * 48 + lane, fh[h][0], fh[h][1], fh[h][2], tag);
        asm volatile("st.relaxed.gpu.global.v2.u32 [%0], {%1,%2};" ::"l"((uint2*)(halo + h * 48 + 32) + lane), "r"(fh[h][3]), "r"(tag) : "memory");
      }
      if (elect_one()) mbar_arrive(bar + 8 * B_SD);
      if (layer == TLAYER && threadIdx.x == 224) TS(47);
    }
#pragma unroll
    for (int h = 0; h < 4; h++) { fh[h][2] = movm_t(fh[h][2]); fh[h][3] = movm_t(fh[h][3]); }
    if (cw != 7) {
#pragma unroll
      for (int h = 0; h < 4; h++) sts128(kvx + 2048 + h * 512, make_uint4(fh[h][0], fh[h][1], fh[h][2], fh[h][3]));
      bar_arrive(8 + cw, 64);
    }
    sched_fence<6>();
    if (layer == TLAYER && threadIdx.x == 0) TS(45);
#pragma unroll
    for (int j = 0; j < 8; j++) cs[j] = lds64f(sb + SM_CS + 4 * (8 * j + 2 * t));
#pragma unroll
    for (int h = 0; h < 4; h++)
#pragma unroll
      for (int k = 0; k < 4; k++) {
        const int j = 8 + (k >> 1) * 8 + 2 * h + (k & 1);
        fl[h][k] = packbf(fmaf(acc[4 * j], rstd0, nm0 * cs[j].x), fmaf(acc[4 * j + 1], rstd0, nm0 * cs[j].y));
        if (k >= 2) fl[h][k] = movm_t(fl[h][k]);
      }
#pragma unroll
    for (int h = 0; h < 4; h++) {
#pragma unroll
      for (int dh = 0; dh < 2; dh++) {
        const int j = 2 * h + dh;
        const float2 c2 = cs[j];
        qa[h][2 * dh] = packbf(fmaf(-mean0, c2.x, acc[4 * j + 0]), fmaf(-mean0, c2.y, acc[4 * j + 1]));
        qa[h][2 * dh + 1] = packbf(fmaf(-mean1, c2.x, acc[4 * j + 2]), fmaf(-mean1, c2.y, acc[4 * j + 3]));
      }
    }
    if (threadIdx.x == 0) TS(2 + layer * 20 + 2);
    sched_fence<0>();
    bar_sync(7 + cw, cw == 0 && !HALO_W14 ? 160 : 64);
#pragma unroll
    for (int h = 0; h < 4; h++) {
      const uint4 v = lds128(kvx + h * 512);
      fp[h][0] = v.x; fp[h][1] = v.y; fp[h][2] = v.z; fp[h][3] = v.w;
    }
    if (threadIdx.x == 0) TS(2 + layer * 20 + 4);
  }

  const bool u0 = 2 * t > g, u1 = 2 * t + 1 > g;
  const uint32_t mU = (u0 ? 0x0000ffffu : 0u) | (u1 ? 0xffff0000u : 0u);
  const float cl2 = 0.25f * 1.4426950408889634f;
  const float sc0 = rstd0 * cl2, sc1 = rstd1 * cl2;
  const float cneg = ((rb & 7) == 0 && cw == 0) ? -INFINITY : 0.f;
  float v[4][4];
#pragma unroll
  for (int h = 0; h < 4; h++) {
    float T0[4] = {cneg, cneg, cneg, cneg}, T1[4] = {0.f, 0.f, 0.f, 0.f}, T2[4] = {0.f, 0.f, 0.f, 0.f};
    mma_bf16(T1, qa[h], fl[h][0], fl[h][1]);
    mma_bf16(T2, qa[h], fh[h][0], fh[h][1]);
    mma_bf16(T0, qa[h], fp[h][0], fp[h][1]);
    v[h][0] = u0 ? T0[0] : T1[0]; v[h][1] = u1 ? T0[1] : T1[1];
    v[h][2] = u0 ? T1[2] : T2[2]; v[h][3] = u1 ? T1[3] : T2[3];
  }
  float m0[4], m1[4];
#pragma unroll
  for (int h = 0; h < 4; h++) { m0[h] = fmaxf(v[h][0], v[h][1]); m1[h] = fmaxf(v[h][2], v[h][3]); }
#pragma unroll
  for (int o = 1; o <= 2; o <<= 1) {
#pragma unroll
    for (int h = 0; h < 4; h++) {
      m0[h] = fmaxf(m0[h], __shfl_xor_sync(~0u, m0[h], o));
      m1[h] = fmaxf(m1[h], __shfl_xor_sync(~0u, m1[h], o));
    }
  }
  float O0[4][4], O1[4][4], Z[4][4];
#pragma unroll
  for (int h = 0; h < 4; h++) {
    const float mm0 = -m0[h] * sc0, mm1 = -m1[h] * sc1;
    const uint32_t P0 = packbf(ex2(fmaf(v[h][0], sc0, mm0)), ex2(fmaf(v[h][1], sc0, mm0)));
    const uint32_t P1 = packbf(ex2(fmaf(v[h][2], sc1, mm1)), ex2(fmaf(v[h][3], sc1, mm1)));
#pragma unroll
    for (int k = 0; k < 4; k++) O0[h][k] = O1[h][k] = Z[h][k] = 0.f;
    mma_bf16_k8(Z[h], P0, P1, 0x3f803f80u);
    mma_bf16_k8(O0[h], P0 & ~mU, P1 & mU, fl[h][2]); mma_bf16_k8(O1[h], P0 & ~mU, P1 & mU, fl[h][3]);
    mma_bf16_k8(O0[h], P0 & mU, 0u, fp[h][2]); mma_bf16_k8(O1[h], P0 & mU, 0u, fp[h][3]);
    mma_bf16_k8(O0[h], 0u, P1 & ~mU, fh[h][2]); mma_bf16_k8(O1[h], 0u, P1 & ~mU, fh[h][3]);
  }
  const uint32_t ob = sb + SM_OST + wg * 8192;
  const int o_row = 16 * w + (lane & 7) + 8 * ((lane >> 3) & 1);
#pragma unroll
  for (int h = 0; h < 4; h++) {
    const float i0 = rcp_approx(Z[h][0]), i1 = rcp_approx(Z[h][2]);
    const int ch = 2 * h + (lane >> 4);
    stsm4(ob + o_row * 128 + ((ch ^ (o_row & 7)) << 4), packbf(O0[h][0] * i0, O0[h][1] * i0), packbf(O0[h][2] * i1, O0[h][3] * i1),
          packbf(O1[h][0] * i0, O1[h][1] * i0), packbf(O1[h][2] * i1, O1[h][3] * i1));
  }
  if (threadIdx.x == 0) TS(2 + layer * 20 + 5);
  ATS(57, 128); ATS(20, 96);
  bar_sync(2 + wg, 128);
  if (w == 0 && elect_one()) {
    fence_async_smem();
    tma_st(&p.mapO, hg * 64, rb * 128 + wg * 64, ob);
    bulk_commit();
    mbar_arrive(bar + 8 * B_AD);
    bulk_wait_all();
    red_relaxed(&g_cnt[(C_O + rb) * 32]);
    mbar_arrive(bar + 8 * B_OST);
    if (threadIdx.x == 0) TS(2 + layer * 20 + 6);
  }
  __syncwarp();
}

__device__ __forceinline__ void proj_phase(const Params& p, uint32_t sb, int layer, int rb, int q, int wg, int w) {
  const int lane = opaque_tid() & 31;
  const bool TR = layer != 0;
  const int t = lane & 3;
  const uint32_t bar = sb + SM_BAR;
  const uint32_t rbx = sb + SM_R + wg * 8192;
  uint32_t res[16];
  mbar_wait(bar + 8 * B_RF, layer);
  if (threadIdx.x == 0) TS(2 + layer * 20 + 7);
  if (!TR) {
#pragma unroll
    for (int j = 0; j < 8; j += 2) {
      const int mi = lane >> 3;
      const int row = 16 * w + (lane & 7) + 8 * (mi & 1), ch = j + (mi >> 1);
      ldsm4(&res[2 * j], rbx + row * 128 + ((ch ^ (row & 7)) << 4));
    }
  } else {
#pragma unroll
    for (int j = 0; j < 8; j += 2) {
      const int mi = lane >> 3;
      const int line = 8 * (j + (mi >> 1)) + (lane & 7), pc = 2 * w + (mi & 1);
      ldsm4t(&res[2 * j], rbx + line * 128 + ((pc ^ (line & 7)) << 4));
    }
  }
  bar_sync(2 + wg, 128);
  float acc[32];
#pragma unroll
  for (int i = 0; i < 16; i++) {
    asm volatile("shl.b32 %0, %1, 16;" : "=f"(acc[2 * i]) : "r"(res[i]));
    asm volatile("and.b32 %0, %1, 0xffff0000;" : "=f"(acc[2 * i + 1]) : "r"(res[i]));
  }
  const uint32_t tag = part_tag(lds32(sb + SM_EP), 2 * layer + 1);
  mbar_wait(bar + 8 * B_ZF, layer);
#pragma unroll 1
  for (int c = 0; c < 8; c++) {
    if ((c & 1) == 0) mbar_wait(bar + 8 * (B_WOF + (c >> 1)), layer);
    mbar_wait(bar + 8 * (B_OF + c), layer);
    if (c == 0 && threadIdx.x == 0) TS(2 + layer * 20 + 8);
    const uint64_t da = mkdesc(sb + sm_o(c) + wg * 8192, 16, 1024, 1);
    const uint64_t db = mkdesc(sb + SM_WO + c * 8192, 8192, 1024, 1);
    wg_fence();
#pragma unroll
    for (int ks = 0; ks < 4; ks++) wgmma_ss<64, 0, 1>(acc, da + ks * 2, db + ks * 128, 1);
    wg_commit();
  }
  wg_wait<0>();
#pragma unroll
  for (int i = 0; i < 32; i++) asm volatile("" : "+f"(acc[i]) :: "memory");
  if (threadIdx.x == 0) TS(2 + layer * 20 + 9);
  if (lane == 0 && w == 0) mbar_arrive(bar + 8 * B_PDONE);
  {
    float s[4], qq[4];
#pragma unroll
    for (int k = 0; k < 4; k++) { s[k] = acc[k]; qq[k] = acc[k] * acc[k]; }
#pragma unroll
    for (int j = 1; j < 8; j++)
#pragma unroll
      for (int k = 0; k < 4; k++) { s[k] += acc[4 * j + k]; qq[k] = fmaf(acc[4 * j + k], acc[4 * j + k], qq[k]); }
    const float s0 = s[0] + s[1], s1 = s[2] + s[3], q0 = qq[0] + qq[1], q1 = qq[2] + qq[3];
    float sr = ((t & 1) ? s1 : s0) + __shfl_xor_sync(~0u, (t & 1) ? s0 : s1, 1);
    float qr = ((t & 1) ? q1 : q0) + __shfl_xor_sync(~0u, (t & 1) ? q0 : q1, 1);
    sr += __shfl_xor_sync(~0u, sr, 2);
    qr += __shfl_xor_sync(~0u, qr, 2);
    if (t < 2) st_part(&g_part[(rb * 8 + q) * 128 + 64 * wg + 16 * w + (lane >> 2) + 8 * t], sr, qr, tag);
    __syncwarp();
    if (elect_one()) mbar_arrive(bar + 8 * B_PS);
    sched_fence<7>();
  }
#pragma unroll
  for (int j = 0; j < 8; j += 2) {
    const int mi = lane >> 3;
    const int line = 8 * (j + (mi >> 1)) + (lane & 7), pc = 2 * w + (mi & 1);
    stsm4t(rbx + line * 128 + ((pc ^ (line & 7)) << 4), packbf(acc[4 * j], acc[4 * j + 1]), packbf(acc[4 * j + 2], acc[4 * j + 3]),
           packbf(acc[4 * j + 4], acc[4 * j + 5]), packbf(acc[4 * j + 6], acc[4 * j + 7]));
  }
  fence_writer();
  bar_sync(2 + wg, 128);
  if (w == 0 && elect_one()) {
    fence_reader();
    fence_async_global();
    tma_st(&p.mapXT, rb * 128 + wg * 64, (2 * layer) * DM + q * 64, rbx);
    bulk_commit();
    if (threadIdx.x == 0) TS(2 + layer * 20 + 10);
    bulk_wait_all();
    red_relaxed(&g_cnt[C_CS * 32 + 2 + layer]);
    if (wg == 0) mbar_arrive(bar + 8 * B_RE);
  }
  __syncwarp();
}
__device__ __forceinline__ void proj_stats(uint32_t sb, int layer, int rb, int q, int lane, uint32_t tag) {
  const int r = 16 * q + (lane & 15);
  const uint2* src = &g_part[rb * 8 * 128 + r];
  uint2* dst = (uint2*)g_stats + ((layer * 32 + rb * 2 + (r >> 6)) * 32 + ((r & 7) >> 1) * 8 + ((r >> 3) & 7)) * 2 + (r & 1);
  mbar_wait(sb + SM_BAR + 8 * B_PS, layer);
  delay<D_PST>();
  for (int it = 0;; it++) {
    uint2 v[8];
#pragma unroll
    for (int i = 0; i < 8; i++) v[i] = ld_part(src + i * 128);
    float s[4], qq[4];
    uint32_t bad = 0;
#pragma unroll
    for (int i = 0; i < 4; i++) {
      s[i] = __uint_as_float(v[i].x) + __uint_as_float(v[i + 4].x);
      qq[i] = __uint_as_float(v[i].y) + __uint_as_float(v[i + 4].y);
      bad |= (v[i].y ^ tag) | (v[i + 4].y ^ tag);
    }
    const float mean = ((s[0] + s[1]) + (s[2] + s[3])) * (1.f / DM);
    const float rstd = rsqrt_approx(fmaxf(fmaf((qq[0] + qq[1]) + (qq[2] + qq[3]), 1.f / DM, -mean * mean), 0.f) + 1e-5f);
    const bool ok = __all_sync(~0u, (bad & 7u) == 0);
    if (ok && lane < 16)
      asm volatile("st.relaxed.gpu.global.v2.u32 [%0], {%1,%2};" ::"l"(dst), "r"(__float_as_uint(-mean * rstd)), "r"(__float_as_uint(rstd) | 1u) : "memory");
    if (ok) break;
    if (it > (1 << 22)) __trap();
  }
}

#define NA 14
#define NP 15
template <int M0, int M1> __device__ __forceinline__ void conv_load(uint32_t* A, uint32_t pe) {
#pragma unroll
  for (int m = M0; m < M1; m++) {
    asm volatile("ld.shared.v2.b32 {%0,%1}, [%2];" : "=r"(A[4 * m]), "=r"(A[4 * m + 1]) : "r"(pe + 256 * m) : "memory");
    A[4 * m + 2] = lds32(pe + 256 * m - 4);
  }
}
__device__ __forceinline__ uint32_t copy_reg(uint32_t v, uint32_t zero) { uint32_t r; asm volatile("or.b32 %0, %1, %2;" : "=r"(r) : "r"(v), "r"(zero)); return r; }
__device__ __forceinline__ uint32_t copy_reg2(uint32_t v, uint32_t zero) { uint32_t r; asm volatile("xor.b32 %0, %1, %2;" : "=r"(r) : "r"(v), "r"(zero)); return r; }
__device__ __forceinline__ void conv_park(uint32_t* P, uint32_t pe) {
#pragma unroll
  for (int m = 0; m < NP; m++)
#pragma unroll
    for (int k = 0; k < 3; k++) P[3 * m + k] = lds32(pe + 256 * m - 4 + 4 * k);
}
__device__ __forceinline__ void conv_unpark(uint32_t* A, const uint32_t* P, uint32_t zero) {
#pragma unroll
  for (int m = 0; m < NP; m++) {
    A[4 * m + 2] = copy_reg(P[3 * m], zero); A[4 * m] = copy_reg(P[3 * m + 1], zero);
    A[4 * m + 3] = copy_reg2(P[3 * m + 1], zero); A[4 * m + 1] = copy_reg(P[3 * m + 2], zero);
  }
}
template <int M0, int M1> __device__ __forceinline__ void conv_mmas(float* acc, const uint32_t* A, uint64_t d) {
  if constexpr (M0 < M1) {
    wgmma_rs<128 - 8 * (M0 / 2), 0>(acc, A + 4 * M0, d + (uint64_t)(4 * M0), M0 != 0);
    conv_mmas<M0 + 1, M1>(acc, A, d);
  }
}
struct SumAddr { uint32_t l0, l1, l2, se, so; };
__device__ __forceinline__ SumAddr conv_sum_addr(uint32_t sb, int c) {
  auto ua = [&](int j) { return sb + cv_u(0) + (127 - (j >> 3)) * 16 + (j & 7) * 2; };
  auto sa = [&](int hc) { const int ci = hc & ~1; return sb + cv_s(0) + ((ci >> 3) & 1) * 1024 + (ci >> 4) * 128 + (((ci ^ (ci >> 4)) & 7) << 4) + (hc & 1) * 8; };
  const int j0 = 4 * (c - 1);
  return {ua(j0 - 2), ua(j0), ua(j0 + 4), sa((c + 1) & 127), sa(c) + 2048};
}
__device__ __forceinline__ void sts64(uint32_t a, uint32_t x, uint32_t y) { asm volatile("st.shared.v2.b32 [%0], {%1,%2};" ::"r"(a), "r"(x), "r"(y) : "memory"); }
__device__ __forceinline__ void conv_sums(const SumAddr& sa, int lc, int c) {
  uint32_t e[4], o[4];
  {
    const float2 em = lds64f(sa.l1 + lc * 32768), om = lds64f(sa.l1 + lc * 32768 + CV_UH);
    e[0] = lds32(sa.l0 + lc * 32768); o[0] = lds32(sa.l0 + lc * 32768 + CV_UH);
    e[3] = lds32(sa.l2 + lc * 32768); o[3] = lds32(sa.l2 + lc * 32768 + CV_UH);
    e[1] = __float_as_uint(em.x); e[2] = __float_as_uint(em.y); o[1] = __float_as_uint(om.x); o[2] = __float_as_uint(om.y);
  }
  uint32_t s7e[2], s7o[2], s9e[2], s9o[2];
  uint32_t pw[4], sh[3];
#pragma unroll
  for (int k = 0; k < 4; k++) pw[k] = hadd2(e[k], o[k]);
#pragma unroll
  for (int k = 0; k < 3; k++) sh[k] = __byte_perm(pw[k], pw[k + 1], 0x5432);
#pragma unroll
  for (int k = 0; k < 2; k++) {
    const uint32_t t3 = hadd2(hadd2(sh[k], sh[k + 1]), pw[k + 1]);
    s7e[k] = hadd2(t3, o[k]); s7o[k] = hadd2(t3, e[k + 2]);
    s9e[k] = hadd2(s7o[k], pw[k]); s9o[k] = hadd2(s7e[k], pw[k + 2]);
  }
  if (c == 127) s9e[0] = s9e[1] = s9o[0] = s9o[1] = 0u;
  sts64(sa.se + lc * 32768, s9e[0], s9e[1]); sts64((sa.se ^ 16) + lc * 32768, s9o[0], s9o[1]);
  sts64(sa.so + lc * 32768, s7e[0], s7e[1]); sts64((sa.so ^ 16) + lc * 32768, s7o[0], s7o[1]);
}

__device__ __forceinline__ void conv_epi(uint32_t sb, int layer, int cta, int ch, int c0, uint4 x0, uint4 x1) {
  uint4 v[2][4];
  const uint4 xr[2] = {x0, x1};
  mbar_wait(sb + SM_BAR + 8 * (B_P + ch), layer);
#pragma unroll
  for (int u = 0; u < 2; u++) {
    const uint32_t pb = sb + cv_pb(ch) + u * (CV_PBW / 2) + c0 * 16;
#pragma unroll
    for (int k = 0; k < 4; k++) v[u][k] = lds128(pb + k * CV_PBW);
  }
#pragma unroll
  for (int u = 0; u < 2; u++) {
    uint4 o;
    o.x = hadd2(xr[u].x, hadd2(hadd2(v[u][0].x, v[u][1].x), hadd2(v[u][2].x, v[u][3].x)));
    o.y = hadd2(xr[u].y, hadd2(hadd2(v[u][0].y, v[u][1].y), hadd2(v[u][2].y, v[u][3].y)));
    o.z = hadd2(xr[u].z, hadd2(hadd2(v[u][0].z, v[u][1].z), hadd2(v[u][2].z, v[u][3].z)));
    o.w = hadd2(xr[u].w, hadd2(hadd2(v[u][0].w, v[u][1].w), hadd2(v[u][2].w, v[u][3].w)));
    if (layer == 0 || ch < 4 - FIN_LL) sts128(sb + cv_s(ch) + (c0 + 128 * u) * 16, o);
    else st_tagged3((uint4*)(g_xT + (size_t)(3 * DM + cv_chan(cta, ch)) * LSEQ) + c0 + 128 * u, o.x, o.y, o.z, o.w);
  }
}
__device__ __forceinline__ void warp_release(uint32_t b) {
  fence_writer();
  __syncwarp();
  if (elect_one()) mbar_arrive(b);
}

__device__ __forceinline__ void conv_prep_load(uint32_t sb, int layer, int cta, int c, uint4 (&xr)[4], uint4 (&st)[4]) {
  sched_fence<8>();
  mbar_wait(sb + SM_BAR + 8 * B_GB, layer);
  if (threadIdx.x == 0) TS(2 + layer * 20 + 11);
  xr[0] = ld_tagged((const uint4*)(g_xT + (size_t)(2 * layer * DM + cta) * LSEQ) + c);
#pragma unroll
  for (int i = 0; i < 4; i++) st[i] = ld_tagged((const uint4*)g_stats + (layer * 32 + (c >> 3)) * 32 + i * 8 + (c & 7));
}
template <bool HELPER>
__device__ __forceinline__ void conv_prep(uint32_t sb, int layer, int cta, int c, uint4 (&xr)[4], uint4 (&st)[4], const SumAddr& sa) {
  const uint32_t bar = sb + SM_BAR;
  const uint4* xin = (const uint4*)(g_xT + (size_t)(2 * layer * DM + cta) * LSEQ) + c;
  for (int it = 0;; it++) {
    uint32_t vs;
    asm("{\n.reg .b32 t, u, v;\nlop3.b32 t, %1, %2, %3, 0x80;\nlop3.b32 u, %4, %5, %6, 0x80;\nlop3.b32 v, %7, %8, 1, 0x80;\nlop3.b32 %0, t, u, v, 0x80;\n}"
        : "=r"(vs) : "r"(st[0].y), "r"(st[0].w), "r"(st[1].y), "r"(st[1].w), "r"(st[2].y), "r"(st[2].w), "r"(st[3].y), "r"(st[3].w));
    if (__all_sync(~0u, vs != 0 && xr[0].x != ~0u)) break;
    if (it > (1 << 22)) __trap();
    if (!__all_sync(~0u, xr[0].x != ~0u)) xr[0] = ld_tagged(xin);
    if (!__all_sync(~0u, vs != 0)) {
#pragma unroll
      for (int i = 0; i < 4; i++) st[i] = ld_tagged((const uint4*)g_stats + (layer * 32 + (c >> 3)) * 32 + i * 8 + (c & 7));
    }
  }
  if (threadIdx.x == 0) TS(2 + layer * 20 + 12);
  const int a = c & 127, h = c >> 7;
#pragma unroll
  for (int i = 0; i < 4; i++) {
    if (i == 1) {
      mbar_wait(bar + 8 * B_XV, layer);
#pragma unroll
      for (int j = 1; j < 4; j++) xr[j] = ld_tagged(xin + j * (128 * LSEQ / 8));
      if (HELPER) {
        mbar_wait(bar + 8 * B_U, layer);
        conv_sums(sa, 0, c);
        fence_async_smem();
        bar_arrive(7, 256);
        sched_fence<1>();
        if (layer == 1 && c == 0) TS(46);
      }
    }
    const uint32_t x[4] = {xr[i].x, xr[i].y, xr[i].z, xr[i].w};
    uint32_t u[4];
#pragma unroll
    for (int k = 0; k < 4; k++)
      u[k] = packbf(fmaf(bf_lo(x[k]), __uint_as_float(st[k].y), __uint_as_float(st[k].x)), fmaf(bf_hi(x[k]), __uint_as_float(st[k].w), __uint_as_float(st[k].z)));
    sts128(sb + cv_u(i) + h * CV_UH + (127 - a) * 16, make_uint4(u[0], u[1], u[2], u[3]));
    warp_release(bar + 8 * (B_U + i));
    sched_fence<2>();
  }
}
__device__ __forceinline__ void conv_zero(uint32_t sb, int ht) {
  if (ht < 96) {
    const int ch = ht / 24, h2 = (ht / 12) & 1, qq = ht % 12;
    sts128(sb + cv_u(ch) + h2 * CV_UH + (128 + qq) * 16, make_uint4(0, 0, 0, 0));
  }
  if (ht >= 80) {
    const int i = ht - 80, ch = i / 12, q2 = i % 12;
    const int w2 = q2 < 2 ? 1 : q2 < 6 ? 2 : 3, cc = q2 < 2 ? q2 : q2 < 6 ? q2 - 2 : q2 - 6;
    sts128(sb + cv_pb(ch) + w2 * CV_PBW + (cc & 1) * (CV_PBW / 2) + (cc >> 1) * 16, make_uint4(0, 0, 0, 0));
  }
}

#define HANDOVER 1
template <int R>
__device__ __forceinline__ void conv_round(uint32_t sb, int layer, int wg, uint32_t* A, const uint32_t* P, uint32_t pb, uint32_t pe2) {
  const uint32_t bar = sb + SM_BAR;
  const int ch = 2 * R + 1 - wg;
  float acc[64];
  const uint64_t d = mkdesc(sb + cv_u(ch), CV_UH, 128, 0);
  FTS(39);
  if (R == 0) {
    mbar_wait(bar + 8 * (B_U + ch), layer);
    fence_reader();
  }
  sched_fence<3>();
  if (R == 1 || wg == 0) bar_sync(10 + ch, 256);
  if (layer == 0 && ch > 0 && ((PAUSE >> (ch - 1)) & 1)) mbar_wait(bar + 8 * (B_E + ch - 1), 0);
  if (layer == 0 && ch > 0 && ((PAUSE >> (ch + 3)) & 1)) mbar_wait(bar + 8 * (B_P + ch - 1), 0);
  FTS(41);
  if (ch == 0 && threadIdx.x == 128) TS(2 + layer * 20 + 13);
  wg_fence();
  conv_mmas<0, 1>(acc, A, d); conv_mmas<2, NA + 1>(acc, A, d);
  wg_commit();
  FTS(51);
  if (HANDOVER == 0 && (R == 0 || wg == 1)) bar_arrive(11 + ch, 256);
  bar_sync(7 + ch, 256);
  wg_fence();
  conv_mmas<1, 2>(acc, A, d); conv_mmas<NA + 1, 17>(acc, A, d);
  wgmma_ss<64, 1, 1>(acc, mkdesc(sb + cv_s(ch), 1024, 1024, 1), mkdesc(sb + cv_ft(ch), 256, 16, 0), 1);
  wgmma_ss<64, 1, 1>(acc, mkdesc(sb + cv_s(ch) + 2048, 1024, 1024, 1), mkdesc(sb + cv_ft(ch) + 512, 256, 16, 0), 1);
  wg_commit();
  if (HANDOVER == 1 && (R == 0 || wg == 1)) bar_arrive(11 + ch, 256);
  FTS(61);
  wg_wait<0>();
#pragma unroll
  for (int j = 0; j < 16; j += 2)
    stsm4t(pb + R * 65536 - j * 128, packbf(acc[4 * j], acc[4 * j + 1]), packbf(acc[4 * j + 2], acc[4 * j + 3]),
           packbf(acc[4 * j + 4], acc[4 * j + 5]), packbf(acc[4 * j + 6], acc[4 * j + 7]));
  __syncwarp();
  if (elect_one()) mbar_arrive(bar + 8 * (B_P + ch));
  if (threadIdx.x == 0) TS(2 + layer * 20 + 14 + R);
  FTS(57);
  if (R == 0) {
    conv_unpark(A, P, opaque_tid() >> 10);
    mbar_wait(bar + 8 * (B_U + ch + 2), layer);
    fence_reader();
    conv_load<NP, 17>(A, pe2);
#pragma unroll
    for (int m = NP; m < 17; m++) A[4 * m + 3] = lds32(pe2 + 256 * m);
  }
}
__device__ __forceinline__ void conv_phase(const Params& p, uint32_t sb, int layer, int cta) {
  const int tid = opaque_tid();
  const int wg = __shfl_sync(~0u, tid >> 7, 0), w = __shfl_sync(~0u, (tid >> 5) & 3, 0);
  const uint32_t bar = sb + SM_BAR;
  uint32_t A[68], P[3 * NP];
  const uint32_t pe = sb + cv_pe(1 - wg) + 4 * (16 + 16 * w + 2 * ((tid & 31) >> 2) - 4 * (tid & 3));
  mbar_wait(bar + 8 * B_PE, layer);
  conv_load<0, 17>(A, pe);
#pragma unroll
  for (int m = 0; m < 17; m++) A[4 * m + 3] = copy_reg(A[4 * m], tid >> 10);
  if (wg == 0) {
    uint4 xr[4], st[4];
    if (PARK_FIRST) conv_park(P, pe + 65536);
    conv_prep_load(sb, layer, cta, tid + 128, xr, st);
    if (!PARK_FIRST) conv_park(P, pe + 65536);
    conv_prep<false>(sb, layer, cta, opaque_tid() + 128, xr, st, SumAddr());
  } else {
    conv_park(P, pe + 65536);
  }
  uint32_t pb;
  {
    const int l2 = opaque_tid() & 31, mt = l2 >> 3;
    pb = sb + cv_pb(1 - wg) + w * CV_PBW + (mt & 1) * (CV_PBW / 2) + (127 - 8 * (mt >> 1) - (l2 & 7) + w) * 16;
  }
  conv_round<0>(sb, layer, wg, A, P, pb, pe + 65536);
  conv_round<1>(sb, layer, wg, A, P, pb, 0);
  if (G_WAIT == 1 && layer == 0) mbar_wait(bar + 8 * (B_E + 3), layer);
  if (G_WAIT == 2 && layer == 0) mbar_wait(bar + 8 * (B_P + 3), layer);
}

__device__ __forceinline__ void final_phase(const Params& p, uint32_t sb, int cta, int wg, int w) {
  if (wg == 1 && w == 3) return;
  const int lane = opaque_tid() & 31, g = lane >> 2, t = lane & 3;
  const int lc = wg ? w : 3;
  const int pos0 = (cta & 31) * 64, ch0 = 128 * lc + (cta >> 5) * 32;
  const bf16* src = g_xT + (size_t)(3 * DM + ch0 + 8 * (g >> 1) + (g & 1)) * LSEQ + pos0;
  bf16* dst = p.out + (size_t)(2 * (pos0 & 1023) + (pos0 >> 10)) * DM + ch0 + 8 * t;
  constexpr int RS = 2 * DM;
  int it = 0;
  if (lc < 4 - FIN_LL) {
    spin_until(&g_cnt[(C_F + (cta >> 5)) * 32 + lc], (lds32(sb + SM_EP) + 1) * 32);
  } else {
    if (E_WAIT && lc < 2) {
      mbar_wait(sb + SM_BAR + 8 * (E_WAIT == 1 ? B_P + 3 : E_WAIT == 2 ? B_E + 2 : B_E + 3), 1);
    } else {
      mbar_wait(sb + SM_BAR + 8 * (B_E + lc), 1);
      delay<D_FIN>();
    }
  }
  if (wg == 0) {
    uint2 v[4];
    for (;;) {
#pragma unroll
      for (int q = 0; q < 4; q++) v[q] = ld_part((const uint2*)(src + 2 * q * LSEQ + 16 * w + 4 * t));
      if (__all_sync(~0u, max(max(v[0].x, v[1].x), max(v[2].x, v[3].x)) != ~0u)) break;
      if (++it > (1 << 22)) __trap();
    }
    if (threadIdx.x == 0) TS(42);
    dst += (16 * w + 4 * (g >> 1) + (g & 1)) * RS;
    *(uint4*)dst = make_uint4(movm_t(v[0].x), movm_t(v[1].x), movm_t(v[2].x), movm_t(v[3].x));
    *(uint4*)(dst + 2 * RS) = make_uint4(movm_t(v[0].y), movm_t(v[1].y), movm_t(v[2].y), movm_t(v[3].y));
  } else {
    uint4 v[2][4];
    bool ok;
    do {
      ok = true;
#pragma unroll
      for (int h = 0; h < 2; h++)
#pragma unroll
        for (int q = 0; q < 4; q++) v[h][q] = ld_tagged((const uint4*)(src + 2 * q * LSEQ + 32 * h + 8 * t));
#pragma unroll
      for (int h = 0; h < 2; h++)
#pragma unroll
        for (int q = 0; q < 4; q++) ok = ok && v[h][q].x != ~0u;
      if (++it > (1 << 22)) __trap();
    } while (!__all_sync(~0u, ok));
    dst += (8 * (g >> 1) + (g & 1)) * RS;
#pragma unroll
    for (int h = 0; h < 2; h++) {
      *(uint4*)(dst + (32 * h + 0) * RS) = make_uint4(movm_t(v[h][0].x), movm_t(v[h][1].x), movm_t(v[h][2].x), movm_t(v[h][3].x));
      *(uint4*)(dst + (32 * h + 2) * RS) = make_uint4(movm_t(v[h][0].y), movm_t(v[h][1].y), movm_t(v[h][2].y), movm_t(v[h][3].y));
      *(uint4*)(dst + (32 * h + 4) * RS) = make_uint4(movm_t(v[h][0].z), movm_t(v[h][1].z), movm_t(v[h][2].z), movm_t(v[h][3].z));
      *(uint4*)(dst + (32 * h + 6) * RS) = make_uint4(movm_t(v[h][0].w), movm_t(v[h][1].w), movm_t(v[h][2].w), movm_t(v[h][3].w));
    }
  }
  if (threadIdx.x == 0) TS(43);
  if (threadIdx.x == 192) TS(63);
  if (threadIdx.x == 0) LTS(1);
}

struct cplx { float r, i; };
__device__ __forceinline__ cplx cmul(cplx a, cplx b) { return {fmaf(a.r, b.r, -a.i * b.i), fmaf(a.r, b.i, a.i * b.r)}; }
__device__ __forceinline__ cplx csqr(cplx a) { return {fmaf(a.r, a.r, -a.i * a.i), (a.r + a.r) * a.i}; }
__device__ __forceinline__ cplx cexp_l(float ar2, float ai, float l) {
  const float m = ex2(ar2 * l);
  const float x = ai * l;
  return {m * __cosf(x), m * __sinf(x)};
}

__device__ __forceinline__ void colsum_publish(uint32_t sb, int rb, int hg, int ht, uint32_t tag) {
  const int lane = ht & 31, q = lane & 15, h = lane >> 4;
  const uint32_t src = sb + SM_CW + (ht >> 5) * 4096 + h * 128 + (q & 1) * 8;
  float s[4] = {0.f, 0.f, 0.f, 0.f};
#pragma unroll 8
  for (int r = 0; r < 16; r++) {
    const float2 v = lds64f(src + r * 256 + (((q >> 1) ^ ((2 * r + h) & 7)) << 4));
    s[0] += bf_lo(__float_as_uint(v.x)); s[1] += bf_hi(__float_as_uint(v.x));
    s[2] += bf_lo(__float_as_uint(v.y)); s[3] += bf_hi(__float_as_uint(v.y));
  }
#pragma unroll
  for (int k = 0; k < 4; k++) s[k] += __shfl_xor_sync(~0u, s[k], 16);
  if (h == 0)
    st_tagged3(&g_colsum[(hg * 16 + rb) * 48 + (ht >> 5) * 16 + q], (__float_as_uint(s[0]) & ~7u) | tag, __float_as_uint(s[1]),
               __float_as_uint(s[2]), __float_as_uint(s[3]));
}
__device__ __forceinline__ void colsum_gather(uint32_t sb, int hg, int ht, uint32_t tag) {
  const int lane = ht & 31, rec = (ht >> 5) * 16 + (lane & 15);
  const uint4* src = &g_colsum[(hg * 16 + (lane >> 4) * 8) * 48 + rec];
  float s[4] = {0.f, 0.f, 0.f, 0.f};
#pragma unroll 1
  for (int h = 0; h < 2; h++, src += 4 * 48) {
    uint4 v[4];
    int it = 0;
    do {
#pragma unroll
      for (int i = 0; i < 4; i++) v[i] = ld_tagged(src + i * 48);
      if (++it > (1 << 22)) __trap();
    } while (!__all_sync(~0u, (v[0].x & 7u) == tag && (v[1].x & 7u) == tag && (v[2].x & 7u) == tag && (v[3].x & 7u) == tag));
#pragma unroll
    for (int i = 0; i < 4; i++) {
      s[0] += __uint_as_float(v[i].x & ~7u); s[1] += __uint_as_float(v[i].y); s[2] += __uint_as_float(v[i].z); s[3] += __uint_as_float(v[i].w);
    }
  }
#pragma unroll
  for (int k = 0; k < 4; k++) s[k] += __shfl_xor_sync(~0u, s[k], 16);
  if (lane < 16) sts128f(sb + SM_CS + rec * 16, s[0], s[1], s[2], s[3]);
}

__device__ __forceinline__ uint32_t packh(float lo, float hi) { uint32_t r; asm("cvt.rn.f16x2.f32 %0, %1, %2;" : "=r"(r) : "f"(hi), "f"(lo)); return r; }
__device__ __forceinline__ void mma_f16(float* d, uint32_t a0, uint32_t a1, uint32_t a2, uint32_t a3, uint32_t b0, uint32_t b1) {
  asm volatile("mma.sync.aligned.m16n8k16.row.col.f32.f16.f16.f32 {%0,%1,%2,%3}, {%4,%5,%6,%7}, {%8,%9}, {%0,%1,%2,%3};"
      : "+f"(d[0]), "+f"(d[1]), "+f"(d[2]), "+f"(d[3]) : "r"(a0), "r"(a1), "r"(a2), "r"(a3), "r"(b0), "r"(b1));
}
struct HSeed { uint32_t r, i; };
__device__ __forceinline__ HSeed hseed(cplx s) { return {packh(s.r, s.r), packh(s.i, s.i)}; }
__device__ __forceinline__ void hcmul(uint32_t& o_r, uint32_t& o_i, uint32_t br, uint32_t bi, HSeed s) {
  asm("{\n.reg .b32 t, u;\nmul.rn.f16x2 t, %3, %5;\nneg.f16x2 t, t;\nmul.rn.f16x2 u, %3, %4;\nfma.rn.f16x2 %0, %2, %4, t;\nfma.rn.f16x2 %1, %2, %5, u;\n}"
      : "=&r"(o_r), "=&r"(o_i) : "r"(br), "r"(bi), "r"(s.r), "r"(s.i));
}
struct HTile { uint32_t r[4], i[4]; };
__device__ __forceinline__ void tile_set(HTile& t, int k, cplx a, cplx b) { t.r[k] = packh(a.r, b.r); t.i[k] = packh(a.i, b.i); }
__device__ __forceinline__ void tile_upper(HTile& t, HSeed s) { hcmul(t.r[2], t.i[2], t.r[0], t.i[0], s); hcmul(t.r[3], t.i[3], t.r[1], t.i[1], s); }
__device__ __forceinline__ HTile tile_shift(const HTile& t, HSeed s) {
  HTile o;
#pragma unroll
  for (int k = 0; k < 4; k++) hcmul(o.r[k], o.i[k], t.r[k], t.i[k], s);
  return o;
}
__device__ __forceinline__ void tile_put(const HTile& t, uint32_t a) {
  sts128(a, make_uint4(t.r[0], t.r[1], t.r[2], t.r[3]));
  sts128(a + 512, make_uint4(t.i[0], t.i[1], t.i[2], t.i[3]));
}
__device__ __forceinline__ HTile tile_get(uint32_t a) { HTile o; ldsm4t(o.r, a); ldsm4t(o.i, a + 512); return o; }
__device__ __forceinline__ void tile_mma(float* T, const HTile& a0, const HTile& a1, const HTile& b) {
  mma_f16(T, a0.r[0], a0.r[1], a0.r[2], a0.r[3], b.r[0], b.r[1]);
  mma_f16(T, a0.i[0], a0.i[1], a0.i[2], a0.i[3], b.i[0], b.i[1]);
  mma_f16(T, a1.r[0], a1.r[1], a1.r[2], a1.r[3], b.r[2], b.r[3]);
  mma_f16(T, a1.i[0], a1.i[1], a1.i[2], a1.i[3], b.i[2], b.i[3]);
}
__device__ __forceinline__ void tile_mma2(float* T, float* U, const HTile& a0, const HTile& a1, const HTile& b, const HTile& c) {
  mma_f16(T, a0.r[0], a0.r[1], a0.r[2], a0.r[3], b.r[0], b.r[1]);
  mma_f16(U, a0.r[0], a0.r[1], a0.r[2], a0.r[3], c.r[0], c.r[1]);
  mma_f16(T, a0.i[0], a0.i[1], a0.i[2], a0.i[3], b.i[0], b.i[1]);
  mma_f16(U, a0.i[0], a0.i[1], a0.i[2], a0.i[3], c.i[0], c.i[1]);
  mma_f16(T, a1.r[0], a1.r[1], a1.r[2], a1.r[3], b.r[2], b.r[3]);
  mma_f16(U, a1.r[0], a1.r[1], a1.r[2], a1.r[3], c.r[2], c.r[3]);
  mma_f16(T, a1.i[0], a1.i[1], a1.i[2], a1.i[3], b.i[2], b.i[3]);
  mma_f16(U, a1.i[0], a1.i[1], a1.i[2], a1.i[3], c.i[2], c.i[3]);
}
__device__ __forceinline__ void kgen_unit(uint32_t tab, uint32_t taba, float ar2, float ai, cplx c, float (&T)[5][4]) {
  const cplx z1 = cexp_l(ar2, ai, 1.f), z16 = cexp_l(ar2, ai, 16.f), z256 = cexp_l(ar2, ai, 256.f);
  HTile a0, a1, b0, b1;
  {
    const cplx y1 = {z16.r, -z16.i}, y2 = csqr(y1), y3 = cmul(y2, y1), y4 = csqr(y2), y5 = cmul(y4, y1), y6 = csqr(y3), y7 = cmul(y4, y3);
    HTile t;
    tile_set(t, 0, {1.f, 0.f}, y1); tile_set(t, 1, y2, y3); tile_set(t, 2, y4, y5); tile_set(t, 3, y6, y7);
    const HTile u = tile_shift(t, hseed(csqr(y4)));
    __syncwarp();
    tile_put(t, tab); tile_put(u, tab + 1024);
    __syncwarp();
    a0 = tile_get(taba); a1 = tile_get(taba + 256);
  }
  const cplx z2 = csqr(z1), z4 = csqr(z2), z8 = csqr(z4);
  const HSeed h8 = hseed(z8);
  const cplx d = cmul(c, z256), e = cmul(d, z256);
  {
    const cplx z512 = csqr(z256), f = cmul(e, z512), f8 = cmul(f, z8), f16 = cmul(f, z16), e4 = cmul(e, z4);
    HTile t, u;
    tile_set(t, 0, e4, cmul(e, z8)); tile_set(t, 1, cmul(e4, z8), cmul(e, z16));
    tile_upper(t, hseed(z256));
    tile_set(u, 0, f8, f16); tile_set(u, 1, cmul(f8, z256), cmul(f16, z256));
    tile_upper(u, hseed(z512));
    __syncwarp();
    tile_put(t, tab); tile_put(u, tab + 1024);
    __syncwarp();
    b0 = tile_get(tab); b1 = tile_get(tab + 1024);
  }
  {
    const cplx d2 = cmul(d, z2), d4 = cmul(d, z4);
    HTile t;
    tile_set(t, 0, d2, d4); tile_set(t, 1, cmul(d2, z4), cmul(d, z8));
    tile_upper(t, h8);
    __syncwarp();
    tile_put(t, tab);
    __syncwarp();
    tile_mma2(T[3], T[4], a0, a1, b0, b1);
    b0 = tile_get(tab);
  }
  {
    const cplx c1 = cmul(c, z1), c2 = cmul(c, z2), c3 = cmul(c1, z2), c4 = cmul(c, z4);
    HTile t;
    tile_set(t, 0, c1, c2); tile_set(t, 1, c3, c4); tile_set(t, 2, cmul(c1, z4), cmul(c2, z4)); tile_set(t, 3, cmul(c3, z4), cmul(c4, z4));
    const HTile u = tile_shift(t, h8);
    __syncwarp();
    tile_put(t, tab); tile_put(u, tab + 1024);
    __syncwarp();
    tile_mma(T[2], a0, a1, b0);
    b0 = tile_get(tab); b1 = tile_get(tab + 1024);
    tile_mma2(T[0], T[1], a0, a1, b0, b1);
  }
}
struct ModeIn { uint2 ar, ai, br, bi, cr, ci; };
__device__ __forceinline__ ModeIn load_modes(const Params& p, int idx) {
  return {*(const uint2*)(p.a_re + idx), *(const uint2*)(p.a_im + idx), *(const uint2*)(p.b_re + idx),
          *(const uint2*)(p.b_im + idx), *(const uint2*)(p.c_re + idx), *(const uint2*)(p.c_im + idx)};
}
__device__ __forceinline__ float bf_el(uint2 v, int k) { const uint32_t x = (k & 2) ? v.y : v.x; return (k & 1) ? bf_hi(x) : bf_lo(x); }
struct KGen { float4 cur; float T[5][4]; };
__device__ __forceinline__ uint32_t kgen_slot(uint32_t sb, int ht, int u) {
  return sb + (u < 3 ? SM_KC + (ht >> 5) * (KC_STRIDE * 2) + (u - 1) * 512 + (ht & 31) * 16 + 16 : SM_HALO + 1024 + ht * 16);
}
__device__ __forceinline__ void kgen_setup(KGen& s, uint32_t sb, int cta, int ht, const ModeIn& in, bf16 logdt, bf16 dskip) {
  const float dt = __bfloat162float(__float2bfloat16_rn(expf(__bfloat162float(logdt))));
  float mx = 0.f, k0 = 0.f, ar2[4];
  cplx c[4];
#pragma unroll
  for (int k = 0; k < 4; k++) {
    ar2[k] = (dt * bf_el(in.ar, k)) * 1.4426950408889634f;
    c[k] = cmul({bf_el(in.cr, k), bf_el(in.ci, k)}, {dt * bf_el(in.br, k), dt * bf_el(in.bi, k)});
    k0 += c[k].r;
    mx = fmaxf(mx, fmaxf(fabsf(c[k].r), fabsf(c[k].i)) * ex2(fmaxf(ar2[k] * 2048.f, 0.f)));
  }
  const int ex = min(max(267 - (int)(__reduce_max_sync(~0u, __float_as_uint(mx)) >> 23), 1), 253);
  const float sc = __uint_as_float(ex << 23);
#pragma unroll
  for (int o = 16; o > 0; o >>= 1) k0 += __shfl_xor_sync(~0u, k0, o);
  if ((ht & 31) == 0) {
    const uint32_t kc = sb + SM_KC + (ht >> 5) * (KC_STRIDE * 2);
    sts16(kc, __bfloat16_as_ushort(__float2bfloat16_rn(k0 + __bfloat162float(dskip))));
    sts16(kc + 641 * 2, 0);
    sts32f(kc + 644 * 2, __uint_as_float((254 - ex) << 23));
  }
  s.cur = make_float4(ar2[0], dt * bf_el(in.ai, 0), c[0].r * sc, c[0].i * sc);
#pragma unroll
  for (int k = 1; k < 4; k++) sts128f(kgen_slot(sb, ht, k), ar2[k], dt * bf_el(in.ai, k), c[k].r * sc, c[k].i * sc);
#pragma unroll
  for (int i = 0; i < 5; i++) s.T[i][0] = s.T[i][1] = s.T[i][2] = s.T[i][3] = 0.f;
}
__device__ __forceinline__ void kgen_finish(KGen& s, uint32_t sb, int cta, int ht) {
  const int w = ht >> 5, lane = ht & 31, g = lane >> 2, t = lane & 3;
  const uint32_t kc = sb + SM_KC + w * KC_STRIDE * 2;
  __syncwarp();
  const float inv = __uint_as_float(lds32(kc + 644 * 2));
  auto put = [&](int idx, float v) {
    sts16(kc + idx * 2, __bfloat16_as_ushort(__float2bfloat16_rn(v)));
  };
#pragma unroll
  for (int hi = 0; hi < 2; hi++)
#pragma unroll
    for (int lo = 0; lo < 2; lo++) {
      const int i = g + 8 * hi, j = 2 * t + lo, e = 2 * hi + lo;
      put(16 * i + 1 + j, s.T[0][e] * inv);
      put(16 * i + 9 + j, s.T[1][e] * inv);
      put(257 + 8 * i + j, s.T[2][e] * inv);
      put(385 + 4 * i + (j & 3) + 64 * (j >> 2), s.T[3][e] * inv);
      put(513 + 2 * i + lo + 32 * t, s.T[4][e] * inv);
    }
}

__device__ __forceinline__ void expand_taps(uint32_t sb, int ht) {
  const int ch = ht >> 5, lane = ht & 31;
  const uint32_t kc = sb + SM_KC + ch * KC_STRIDE * 2;
  const uint32_t dst0 = sb + cv_pe(ch);
  auto put = [&](int G, uint32_t u0, uint32_t u1, uint32_t v0, uint32_t v1, uint32_t v2, uint32_t v3, uint32_t v4, uint32_t v5, uint32_t v6, uint32_t v7) {
    const uint32_t dst = dst0 + G * 32;
    sts128(dst, make_uint4(v0 | (u0 << 16), v1 | (u1 << 16), v2 | (v0 << 16), v3 | (v1 << 16)));
    sts128(dst + 16, make_uint4(v4 | (v2 << 16), v5 | (v3 << 16), v6 | (v4 << 16), v7 | (v5 << 16)));
  };
  {
    const uint4 q = lds128(kc + lane * 16);
    const uint32_t pv = lane ? lds32(kc + lane * 16 - 4) : 0u;
    const uint32_t dst = dst0 + (lane + 2) * 32;
    sts128(dst, make_uint4(__byte_perm(q.x, pv, 0x5410), __byte_perm(q.x, pv, 0x7632), __byte_perm(q.y, q.x, 0x5410), __byte_perm(q.y, q.x, 0x7632)));
    sts128(dst + 16, make_uint4(__byte_perm(q.z, q.y, 0x5410), __byte_perm(q.z, q.y, 0x7632), __byte_perm(q.w, q.z, 0x5410), __byte_perm(q.w, q.z, 0x7632)));
    if (lane < 4) sts128(dst0 + lane * 16, make_uint4(0, 0, 0, 0));
  }
  uint32_t a[5], b[2][3], fv[4];
  {
    const uint32_t s1 = kc + 2 * (256 + 4 * lane);
#pragma unroll
    for (int k = 0; k < 5; k++) a[k] = lds16(s1 + 2 * k);
#pragma unroll
    for (int u = 0; u < 2; u++) {
      const uint32_t s2 = kc + 2 * (384 + 2 * (lane + 32 * u));
#pragma unroll
      for (int k = 0; k < 3; k++) b[u][k] = lds16(s2 + 2 * k);
    }
#pragma unroll
    for (int k = 0; k < 4; k++) fv[k] = lds16(kc + 2 * (640 - 4 * lane - k));
  }
  const uint32_t am1 = lds16(kc + 2 * (lane ? 256 + 4 * lane : 255)), am2 = lds16(kc + 2 * (lane ? 255 + 4 * lane : 254));
  const uint32_t bm2 = lds16(kc + 2 * (lane ? 384 + 2 * lane : 383)), k1024 = lds16(kc + 2 * 512);
  put(34 + lane, am2, am1, a[0], a[0], a[1], a[2], a[2], a[2], a[3], a[4]);
#pragma unroll
  for (int u = 0; u < 2; u++) put(66 + lane + 32 * u, u ? b[u][0] : bm2, b[u][0], b[u][0], b[u][0], b[u][0], b[u][1], b[u][1], b[u][1], b[u][2], b[u][2]);
  if (lane < 10) {
    const uint32_t v = lane == 0 ? k1024 : 0u;
    put(130 + lane, v, v, v, v, v, v, v, 0u, 0u, 0u);
  }
  const uint32_t ft = sb + cv_ft(ch) + 4 * lane;
#pragma unroll
  for (int ty = 0; ty < 2; ty++) {
    const uint32_t v = fv[ty] | (fv[ty + 2] << 16);
    sts32f(ft + ty * 512, __uint_as_float(v));
    sts32f(ft + ty * 512 + 128, 0.f);
    sts32f(ft + ty * 512 + 256 + (lane < 2 ? 120 : -8), __uint_as_float(lane < 2 ? 0u : v));
    sts32f(ft + ty * 512 + 384, 0.f);
  }
}

__device__ __forceinline__ int role_id() { int v; asm volatile("mov.u32 %0, %%ctaid.x;" : "=r"(v)); return v; }
#define GMAP 8
__device__ __forceinline__ int role_rb(int cta) { return 4 * (cta >> 5) + (cta & 3); }
__device__ __forceinline__ int role_hg(int cta) { return 2 * (((cta >> 3) & 3) ^ (((cta >> 5) & 1) * 3)) + ((cta >> 2) & 1); }
__device__ __forceinline__ int role_rb2(int cta) { return cta >> 3; }
__device__ __forceinline__ int role_q2(int cta) { return cta & 7; }

__global__ void __launch_bounds__(NTHREADS, 1) fused_kernel(const __grid_constant__ Params p) {
  extern __shared__ __align__(1024) uint8_t smem[];
  const uint32_t sb = s32(smem);
  const int tid = threadIdx.x, lane = tid & 31;
  const int warp = __shfl_sync(~0u, tid >> 5, 0);
  const uint32_t bar = sb + SM_BAR;
  if (tid == 0) TS(0);
  const int cta0 = role_id();
  if (warp == 0 && elect_one()) {
    const int rb = role_rb(cta0), hg = role_hg(cta0);
#pragma unroll
    for (int c = 0; c < 2; c++) { mbar_init(bar + 8 * (B_XF + c), 1); mbar_init(bar + 8 * (B_KVF + c), 1); }
    fence_async_smem();
#pragma unroll
    for (int c = 0; c < 2; c++) {
      mbar_expect(bar + 8 * (B_XF + c), 16384);
      tma_ld(sb + SM_X + c * 16384, &p.mapX128, (rb >> 3) * DM + c * 64, (rb & 7) * 128, bar + 8 * (B_XF + c));
      mbar_expect(bar + 8 * (B_KVF + c), 24576);
      tma_ld3(sb + SM_W + c * 24576, &p.mapW3, hg * 64, c * 64, 0, bar + 8 * (B_KVF + c));
    }
  }
  if (warp == 1 && elect_one()) {
    const int rb = role_rb(cta0), hg = role_hg(cta0);
#pragma unroll
    for (int c = 2; c < 8; c++) mbar_init(bar + 8 * (B_XF + c), 1);
    mbar_init(bar + 8 * (B_KVF + 2), 1); mbar_init(bar + 8 * B_CW, 1);
    fence_async_smem();
    delay<D_START>();
    mbar_expect(bar + 8 * B_CW, 12288);
    tma_ld3(sb + SM_CW, &p.mapW3h, hg * 64, rb * 32, 0, bar + 8 * B_CW);
#pragma unroll
    for (int c = 2; c < 8; c++) {
      mbar_expect(bar + 8 * (B_XF + c), 16384);
      tma_ld(sb + SM_X + c * 16384, &p.mapX128, (rb >> 3) * DM + c * 64, (rb & 7) * 128, bar + 8 * (B_XF + c));
      if (c < 3) {
        mbar_expect(bar + 8 * (B_KVF + c), 24576);
        tma_ld3(sb + SM_W + c * 24576, &p.mapW3, hg * 64, c * 64, 0, bar + 8 * (B_KVF + c));
      }
    }
    TS(56);
  }
  if ((warp & 2) != 0 && warp < 15 && elect_one()) {
    const int grp = 1 + (warp & 1) + 2 * (warp >> 2), cnt = grp < 4 ? 1 : grp < 5 ? 2 : grp < 7 ? 4 : 8;
#pragma unroll
    for (int k = 0; k < 10; k++)
      if (k != 0 || grp > 3 || grp == 2) mbar_init(bar + 8 * (10 * grp + k), cnt);
    fence_async_smem();
  }

  if (warp < 8) {
    if (tid == 0) TS(1);
    asm volatile("setmaxnreg.inc.sync.aligned.u32 %0;" ::"n"(R_CONS));
    const int cta = role_id();
    auto warp_id = [] { return __shfl_sync(~0u, opaque_tid() >> 5, 0); };
    if (tid == 0) TS(54);
#pragma unroll 1
    for (int layer = 0; layer < 2; layer++) {
      { const int cw = warp_id(); attn_phase(p, sb, layer, role_rb(cta), role_hg(cta), cw >> 2, cw & 3); }
      if (STOP == 1 + 3 * layer) return;
      { const int cw = warp_id(); proj_phase(p, sb, layer, role_rb2(cta), role_q2(cta), cw >> 2, cw & 3); }
      if (STOP == 2 + 3 * layer) return;
      conv_phase(p, sb, layer, cta);
      if (STOP == 3 + 3 * layer) return;
    }
    { const int cw = warp_id(); final_phase(p, sb, cta, cw >> 2, cw & 3); }
  } else if (warp < 12) {
    asm volatile("setmaxnreg.dec.sync.aligned.u32 %0;" ::"n"(R_HELP));
    const int ht = tid - 256;
    const int cta = role_id(), rb = role_rb(cta), hg = role_hg(cta);
    unsigned ep0 = 0;
    if (ht == 0) ep0 = ld_relaxed(&g_cnt[C_CS * 32]);
    bar_sync(0, NTHREADS);
    if (ht == 0) {
      asm volatile("st.shared.u32 [%0], %1;" ::"r"(sb + SM_EP), "r"(ep0 / NCTA) : "memory");
      mbar_arrive(bar + 8 * B_EP);
    }
    mbar_wait(bar + 8 * B_EP, 0);
    stats_publish(sb, 0, rb, hg, opaque_tid() - 256, part_tag(lds32(sb + SM_EP), 0));
    if (ht < 48) {
      const bf16* q = (&p.a_re)[ht >> 3];
      asm volatile("prefetch.global.L2 [%0];" ::"l"(q + cv_chan(cta, (ht >> 1) & 3) * 128 + (ht & 1) * 64));
    }
    {
      KGen kg;
      const uint32_t tab0 = sb + ((ht >> 5) < 2 ? SM_T : SM_T2 - 4096) + (ht >> 5) * 2048;
      const uint32_t tab = tab0 + (ht & 31) * 16, taba = tab0 + ((ht >> 3) & 1) * 1024 + (((ht >> 1) & 8) + (ht & 7)) * 16;
      delay<D_ST0>();
      stats_gather(sb, rb, opaque_tid() - 256, part_tag(lds32(sb + SM_EP), 0));
      if (ht == 0) TS(40);
      const int chn = cv_chan(cta, ht >> 5);
      const ModeIn modes = load_modes(p, chn * 128 + (ht & 31) * 4);
      const bf16 logdt = p.log_dt[chn], dskip = p.dskip[chn];
      if (!HALO_W14 && KG_START != 4) halo_receive(sb, 0, rb, hg, opaque_tid() - 256);
      if (KG_START == 1) mbar_wait(bar + 8 * B_HF, 0);
      kgen_setup(kg, sb, cta, ht, modes, logdt, dskip);
      if (!HALO_W14 && KG_START == 4) halo_receive(sb, 0, rb, hg, opaque_tid() - 256);
      if (KG_START == 2) mbar_wait(bar + 8 * B_HF, 0);
      if (KG_START == 3) mbar_wait(bar + 8 * B_QDONE, 0);
#pragma unroll 1
      for (int u = 0; u < 4; u++) {
        if (u == KG_PRE) {
          KTS(39);
          mbar_wait(bar + 8 * B_AD, 0);
          KTS(41);
        }
        kgen_unit(tab, taba, kg.cur.x, kg.cur.y, {kg.cur.z, kg.cur.w}, kg.T);
        kg.cur = lds128f(kgen_slot(sb, opaque_tid() - 256, u + 1));
      }
      kgen_finish(kg, sb, cta, opaque_tid() - 256);
    }
    KTS(51);
    bar_sync(4, 128);
#pragma unroll 1
    for (int layer = 0; layer < 2; layer++) {
      if (STOP <= 1 + 3 * layer) return;
      mbar_wait(bar + 8 * (EXP_LATE ? B_PS : B_PDONE), layer);
      expand_taps(sb, opaque_tid() - 256);
      conv_zero(sb, opaque_tid() - 256);
      if (ht == 0) TS(52 + layer);
      warp_release(bar + 8 * B_PE);
      if (STOP <= 2 + 3 * layer) return;
      {
        uint4 xr[4], st[4];
        const int c = opaque_tid() - 256;
        const SumAddr sa = conv_sum_addr(sb, c);
        conv_prep_load(sb, layer, cta, c, xr, st);
        conv_prep<true>(sb, layer, cta, c, xr, st, sa);
        if (layer == 1 && ht == 0) TS(62);
        const bf16* xup = g_xT + (size_t)(2 * layer * DM + cta) * LSEQ + (c + 128) * 8;
        const int ahead = layer ? S_AHEAD1 : S_AHEAD0;
        mbar_wait(bar + 8 * (B_U + 3), layer);
        if (ahead == 2) {
          conv_sums(sa, 1, c);
          fence_async_smem();
          bar_arrive(8, 256);
        }
        st[0] = ldcg128(xup);
#pragma unroll
        for (int lc = 0; lc < 4; lc++) {
          if (lc < 3 && lc + ahead < 4) {
            conv_sums(sa, lc + ahead, c);
            fence_async_smem();
            bar_arrive(7 + lc + ahead, 256);
            sched_fence<4>();
          }
          if (lc < 3) st[lc + 1] = ldcg128(xup + (lc + 1) * 128 * LSEQ);
          conv_epi(sb, layer, cta, lc, c, xr[lc], st[lc]);
          warp_release(bar + 8 * (B_E + lc));
          sched_fence<5>();
          if (layer == 1 && lc == 3 && ht == 0) TS(38);
        }
      }
      if (layer == 0 && STOP > 3) {
        const int c1 = role_id();
        stats_publish(sb, 1, role_rb(c1), role_hg(c1), opaque_tid() - 256, part_tag(lds32(sb + SM_EP), 2));
        delay<D_ST>();
        stats_gather(sb, role_rb(c1), opaque_tid() - 256, part_tag(lds32(sb + SM_EP), 2));
        if (ht == 0) TS(25);
        if (!HALO_W14) halo_receive(sb, 1, role_rb(c1), role_hg(c1), opaque_tid() - 256);
      }
    }
  } else {
    asm volatile("setmaxnreg.dec.sync.aligned.u32 %0;" ::"n"(512 - 2 * R_CONS - R_HELP));
    const int cta = role_id(), rb = role_rb(cta), hg = role_hg(cta), rb2 = role_rb2(cta), q2 = role_q2(cta);
    bar_sync(0, NTHREADS);
    if (warp != 12) {
      mbar_wait(bar + 8 * B_EP, 0);
      const uint32_t tag = lds32(sb + SM_EP) % 7 + 1;
      mbar_wait(bar + 8 * B_CW, 0);
      colsum_publish(sb, rb, hg, tid - 416, tag);
      if (tid == 416) TS(50);
      delay<D_CS>();
      colsum_gather(sb, hg, tid - 416, tag);
      __syncwarp();
      if (tid == 416) TS(55);
    }
    if (elect_one()) mbar_arrive(bar + 8 * B_CSF);
    if (warp == 12) {
      if (elect_one()) {
        unsigned epoch = 0;
#pragma unroll 1
        for (int layer = 0; layer < 2; layer++) {
          auto ld_w = [&](int c, int slot) {
            const uint32_t b = bar + 8 * (B_KVF + c);
            mbar_expect(b, 24576);
            tma_ld3(sb + SM_W + slot * 24576, &p.mapW3, hg * 64, c * 64, 0, b);
          };
          if (layer == 0) {
            mbar_wait(bar + 8 * (B_KVF + 2), 0);
            if (rb2 < 4) tma_prefetch2(&p.mapWo128, q2 * 64, rb2 * 128);
            asm volatile("prefetch.tensormap [%0];" ::"l"(&p.mapO) : "memory");
            asm volatile("prefetch.tensormap [%0];" ::"l"(&p.mapO128) : "memory");
            asm volatile("prefetch.tensormap [%0];" ::"l"(&p.mapXT) : "memory");
            asm volatile("prefetch.tensormap [%0];" ::"l"(&p.mapXT3) : "memory");
            mbar_wait(bar + 8 * B_EP, 0);
            epoch = lds32(sb + SM_EP);
          } else {
            mbar_wait(bar + 8 * B_PDONE, 0);
            ld_w(0, 0); ld_w(1, 1);
            mbar_wait(bar + 8 * (W2_LATE ? B_U : B_RE), 0);
            ld_w(2, 2);
          }
          {
            int slot = 0;
#pragma unroll 1
            for (int c = 3; c < 8; c++) {
              mbar_wait(bar + 8 * (B_KVE + c - 3), layer);
              ld_w(c, slot);
              slot = slot == 2 ? 0 : slot + 1;
            }
          }
          if (STOP <= 1 + 3 * layer) return;
          mbar_wait(bar + 8 * B_QDONE, layer);
          mbar_wait(bar + 8 * B_HF, layer);
#pragma unroll 1
          for (int c = 0; c < 4; c++) {
            const uint32_t b = bar + 8 * (B_WOF + c);
            mbar_expect(b, 16384);
            tma_ld(sb + SM_WO + c * 16384, &p.mapWo128, q2 * 64, c * 128, b);
          }
          {
            const uint32_t b = bar + 8 * B_RF;
            mbar_expect(b, 16384);
            if (layer == 0) tma_ld(sb + SM_R, &p.mapX128, (rb2 >> 3) * DM + q2 * 64, (rb2 & 7) * 128, b);
            else tma_ld3(sb + SM_R, &p.mapXT3, 0, DM + q2 * 64, rb2 * 2, b);
          }
#pragma unroll
          for (int c = 0; c < 8; c++) mbar_expect(bar + 8 * (B_OF + c), 16384);
          spin_until(&g_cnt[(C_O + rb2) * 32], (2 * epoch + layer + 1) * 16);
          fence_async_global();
#pragma unroll
          for (int c = 0; c < 8; c++) {
            if (c == 4) { mbar_wait(bar + 8 * B_OST, layer); fence_async_smem(); }
            tma_ld(sb + sm_o(c), &p.mapO128, c * 64, rb2 * 128, bar + 8 * (B_OF + c));
          }
          if (STOP <= 3 + 3 * layer) return;
        }
      }
    } else if (warp == 13) {
      if (elect_one() && STOP > 1) {
        const unsigned target = (lds32(sb + SM_EP) + 1) * NCTA;
        mbar_wait(bar + 8 * B_RE, 0);
        spin_until(&g_cnt[C_CS * 32 + 2], 2 * target);
        mbar_arrive(bar + 8 * B_XV);
        if (STOP <= 3) return;
        auto ld_x = [&](int c) { tma_ld3(sb + SM_X + c * 16384, &p.mapXT3, 0, DM + c * 64, rb * 2, bar + 8 * (B_XF + c)); };
#pragma unroll
        for (int c = 0; c < 8; c++) mbar_expect(bar + 8 * (B_XF + c), 16384);
        spin_until(&g_cnt[C_G1 * 32], target);
        fence_async_global();
        fence_async_smem();
        ld_x(0); ld_x(1);
        int done = 1, it = 0;
        while (done < 4) {
          const uint4 v = ld_tagged((const uint4*)&g_cnt[C_G1 * 32]);
          const int n = 4 + ((int)(v.y - target) >> 31) + ((int)(v.z - target) >> 31) + ((int)(v.w - target) >> 31);
          if (n == done) { if (++it > (1 << 23)) __trap(); continue; }
          if (n == 4) TS(44);
          fence_async_global();
          fence_async_smem();
          const int first = n == 4 && done > 1 ? 6 + (hg >> 2) : -1;
          if (first >= 0) ld_x(first);
#pragma unroll 1
          for (int c = 2 * done; c < 2 * n; c++)
            if (c != first) ld_x(c);
          done = n;
        }
        if (STOP <= 4) return;
        mbar_wait(bar + 8 * B_RE, 1);
        spin_until(&g_cnt[C_CS * 32 + 3], 2 * target);
        mbar_arrive(bar + 8 * B_XV);
      }
    } else if (warp == 15) {
      mbar_wait(bar + 8 * B_EP, 0);
      const unsigned epoch = lds32(sb + SM_EP);
#pragma unroll 1
      for (int layer = 0; layer < 2; layer++) {
        mbar_wait(bar + 8 * (B_KVF + FILL_AT), layer);
#pragma unroll
        for (int k = 0; k < 8; k++) ((uint4*)(g_xT + (size_t)(2 * layer * DM + cta) * LSEQ))[32 * k + lane] = make_uint4(~0u, ~0u, ~0u, ~0u);
        mbar_wait(bar + 8 * (B_KVF + FILL_AT + 1), layer);
#pragma unroll
        for (int k = 0; k < 4 * FIN_LL; k++)
          ((uint4*)(g_xT + (size_t)(3 * DM + cv_chan(cta, 3 - (k >> 2))) * LSEQ))[128 * layer + 32 * (k & 3) + lane] = make_uint4(~0u, ~0u, ~0u, ~0u);
        if (lane < 8) ((uint4*)g_stats)[layer * 1024 + cta * 8 + lane] = make_uint4(0, 0, 0, 0);
        __syncwarp();
        if (elect_one()) {
          red_release(&g_cnt[C_CS * 32 + layer]);
          spin_until(&g_cnt[C_CS * 32 + layer], (epoch + 1) * NCTA);
          mbar_arrive(bar + 8 * B_ZF);
          if (STOP > 2 + 3 * layer) {
#pragma unroll 1
            for (int lc = 0; lc < 4 - FIN_LL * layer; lc++) {
              mbar_wait(bar + 8 * (B_E + lc), layer);
              fence_reader();
              bulk_st(g_xT + (size_t)((2 * layer + 1) * DM + cv_chan(cta, lc)) * LSEQ, sb + cv_s(lc), 4096);
              bulk_commit();
              bulk_wait_all();
              red_relaxed(&g_cnt[(layer ? C_F + (cta >> 5) : C_G1) * 32 + lc]);
              if (lc == 3) TS(18);
            }
          }
        }
        __syncwarp();
        if (STOP <= 3) return;
      }
    } else if (warp == 14) {
      mbar_wait(bar + 8 * B_EP, 0);
      const unsigned epoch = lds32(sb + SM_EP);
#pragma unroll 1
      for (int layer = 0; layer < 2; layer++) {
        if (STOP <= 3 * layer) return;
        if (HALO_W14) halo_receive1(sb, layer, rb, hg, opaque_tid() & 31, 2 * epoch + layer + 1);
        if (STOP <= 1 + 3 * layer) return;
        mbar_wait(bar + 8 * B_ZF, layer);
        proj_stats(sb, layer, rb2, q2, opaque_tid() & 31, part_tag(epoch, 2 * layer + 1));
        if (layer == 1 && lane == 0) TS(5);
        delay<D_PREP>();
        if (lane == 0) mbar_arrive(bar + 8 * B_GB);
      }
    }
  }
}

typedef CUresult (*EncodeFn)(CUtensorMap*, CUtensorMapDataType, cuuint32_t, void*, const cuuint64_t*, const cuuint64_t*,
                             const cuuint32_t*, const cuuint32_t*, CUtensorMapInterleave, CUtensorMapSwizzle,
                             CUtensorMapL2promotion, CUtensorMapFloatOOBfill);

static void make_map(EncodeFn enc, CUtensorMap* m, void* ptr, uint64_t cols, uint64_t rows, uint32_t box_rows) {
  cuuint64_t dims[2] = {cols, rows};
  cuuint64_t strides[1] = {cols * 2};
  cuuint32_t box[2] = {64, box_rows};
  cuuint32_t es[2] = {1, 1};
  enc(m, CU_TENSOR_MAP_DATA_TYPE_BFLOAT16, 2, ptr, dims, strides, box, es, CU_TENSOR_MAP_INTERLEAVE_NONE,
      CU_TENSOR_MAP_SWIZZLE_128B, CU_TENSOR_MAP_L2_PROMOTION_L2_128B, CU_TENSOR_MAP_FLOAT_OOB_FILL_NONE);
}
static void make_map3(EncodeFn enc, CUtensorMap* m, void* ptr, uint64_t d0, uint64_t cols, uint64_t rows, uint64_t blk_stride,
                      uint64_t nblocks, uint32_t nblk, uint32_t box_rows = 64) {
  cuuint64_t dims[3] = {d0, rows, nblocks};
  cuuint64_t strides[2] = {cols * 2, blk_stride * 2};
  cuuint32_t box[3] = {64, box_rows, nblk};
  cuuint32_t es[3] = {1, 1, 1};
  enc(m, CU_TENSOR_MAP_DATA_TYPE_BFLOAT16, 3, ptr, dims, strides, box, es, CU_TENSOR_MAP_INTERLEAVE_NONE,
      CU_TENSOR_MAP_SWIZZLE_128B, CU_TENSOR_MAP_L2_PROMOTION_L2_128B, CU_TENSOR_MAP_FLOAT_OOB_FILL_NONE);
}

extern "C" void kernel_launch(void* const* d_in, const int* in_sizes, int n_in, void* d_out, int out_size) {
  static Params prm;
  static void* cached[13] = {nullptr};
  static bool attr_done = false;
  bool same = attr_done && cached[12] == d_out;
  for (int i = 0; i < 12 && same; i++) same = cached[i] == d_in[i];
  if (!same) {
    void* fn = nullptr;
    cudaDriverEntryPointQueryResult qr;
    cudaGetDriverEntryPoint("cuTensorMapEncodeTiled", &fn, cudaEnableDefault, &qr);
    EncodeFn enc = (EncodeFn)fn;
    void *pO, *pXT;
    cudaGetSymbolAddress(&pO, g_O);
    cudaGetSymbolAddress(&pXT, g_xT);
    make_map(enc, &prm.mapO, pO, DM, LSEQ, 64);
    make_map(enc, &prm.mapXT, pXT, LSEQ, 4 * DM, 64);
    prm.out = (bf16*)d_out;
    make_map(enc, &prm.mapX128, d_in[0], 2 * DM, LSEQ / 2, 128);
    make_map(enc, &prm.mapWo128, d_in[2], DM, DM, 128);
    make_map(enc, &prm.mapO128, pO, DM, LSEQ, 128);
    make_map3(enc, &prm.mapW3, d_in[1], DM, 3 * DM, DM, DM, 3, 3);
    make_map3(enc, &prm.mapW3h, d_in[1], DM, 3 * DM, DM, DM, 3, 3, 32);
    make_map3(enc, &prm.mapXT3, pXT, 64, LSEQ, 4 * DM, 64, 32, 2);
    prm.a_re = (const bf16*)d_in[4]; prm.a_im = (const bf16*)d_in[5];
    prm.b_re = (const bf16*)d_in[6]; prm.b_im = (const bf16*)d_in[7];
    prm.c_re = (const bf16*)d_in[8]; prm.c_im = (const bf16*)d_in[9];
    prm.log_dt = (const bf16*)d_in[10]; prm.dskip = (const bf16*)d_in[11];
    cudaFuncSetAttribute(fused_kernel, cudaFuncAttributeMaxDynamicSharedMemorySize, SM_TOTAL);
    for (int i = 0; i < 12; i++) cached[i] = d_in[i];
    cached[12] = d_out;
    attr_done = true;
  }
  prm.stop = 100;
    fused_kernel<<<NCTA, NTHREADS, SM_TOTAL>>>(prm);
}
```

```cpp
#include <cuda_runtime.h>
#include <cuda_bf16.h>
#include <cuda.h>
#include <stdint.h>

typedef __nv_bfloat16 bf16;

constexpr int LSEQ = 2048;
constexpr int DM = 512;
constexpr int NCTA = 128;
constexpr int NTHREADS = 512;
#define RR 0
#define KG_PRE 2
#define W2_LATE 1
#define FILL_AT 5
#define EXP_LATE 1
#define RFENCE 1
#define D_FIN 550
#define D_PREP 500
#define D_PST 0
#define D_HALO 500
#define STAG 2
#define D_ST 0
#define TLAYER 1
#define KG_PD 1
#define SUM_F32 0
#define CS_LATE0 1
#define D_HALO1 0
#define KG_START 0
#define S_AHEAD0 1
#define S_AHEAD1 2
#define PAUSE 0
#define PARK_FIRST 0
#define P_UNROLL_N 1
constexpr int P_UNROLL = P_UNROLL_N;
#define G_WAIT 2
#define HALO_W14 1
#define D_START 200
#define D_CS 300
#define D_ST0 400
#define KG_LAST 0
#define X_JIT 0
#define KG_GATE 2
#define R_CONS 192
#define R_HELP 88

constexpr int SM_X = 0;
constexpr int SM_W = 131072;
constexpr int SM_KVX = SM_X;
constexpr int SM_OST = SM_X + 32768;
constexpr int SM_WO = SM_X + 65536;
__host__ __device__ constexpr int sm_o(int c) { return c < 4 ? SM_W + c * 16384 : SM_X + (c - 4) * 16384; }
constexpr int SM_R = 196608;
constexpr int SM_T = 212992;
constexpr int SM_KC = 217088;
constexpr int KC_STRIDE = 648;
constexpr int SM_CS = SM_KC + 4 * KC_STRIDE * 2;
constexpr int SM_CW = SM_R + 8192;
constexpr int SM_EP = SM_CS + 768;
constexpr int SM_BAR = SM_EP + 16;
constexpr int SM_T2 = SM_BAR + 896;
constexpr int SM_HALO = SM_T2 + 4096;
constexpr int SM_ST = SM_HALO + 3072;
constexpr int SM_TOTAL = SM_HALO + 4096;
static_assert(SM_TOTAL <= 232448, "shared memory");

constexpr int CV_UH = 140 * 16;
constexpr int CV_PECH = 1120 * 4;
constexpr int CV_PBW = 2112 * 2;
__host__ __device__ constexpr int cv_s(int lc) { return SM_X + lc * 32768; }
__host__ __device__ constexpr int cv_u(int lc) { return cv_s(lc) + 4096; }
__host__ __device__ constexpr int cv_pe(int lc) { return cv_u(lc) + 2 * CV_UH; }
__host__ __device__ constexpr int cv_pb(int lc) { return cv_pe(lc) + CV_PECH; }
__host__ __device__ constexpr int cv_ft(int lc) { return cv_pb(lc) + 4 * CV_PBW; }
static_assert(cv_ft(0) + 1024 <= 32768, "conv buffers");
__host__ __device__ constexpr int cv_chan(int cta, int lc) { return cta + 128 * lc; }

enum {
  B_XF = 0,
  B_KVF = 8,
  B_OF = 16,
  B_WOF = 24,
  B_T = 31,
  B_RF = 28,
  B_RE = 29,
  B_CW = 30,
  B_GB = 35,
  B_EP = 36,
  B_ZF = 37,
  B_XV = 39,
  B_SD = 38,
  B_KVE = 40,
  B_AD = 45,
  B_OST = 46,
  B_QDONE = 47,
  B_PDONE = 48,
  B_S = 50,
  B_E = 54,
  B_P = 58,
  B_PE = 62,
  B_STF = 63,
  B_CSF = 64,
  B_HF = 65,
  B_U = 70,
  B_PS = 74,
  B_COUNT = 80
};

enum {
  C_CS = 0,
  C_G1 = 2,
  C_O = 4,
  C_COUNT = 20
};

__device__ __align__(128) unsigned g_cnt[C_COUNT * 32];
__device__ __align__(1024) bf16 g_O[LSEQ * DM];
__device__ __align__(1024) bf16 g_xT[4 * DM * LSEQ];
__device__ __align__(1024) float g_stats[2 * LSEQ * 2];
__device__ __align__(1024) uint4 g_colsum[8 * 16 * 48];
__device__ __align__(1024) uint4 g_halo[16 * 8 * 192];
__device__ __align__(1024) uint2 g_part[16 * 8 * 128];
#define TS(i) do { } while (0)

#define ATS(i, th) do { } while (0)
#define KTS(i) do { if (ht == 0) TS(i); } while (0)
#define FTS(i) do { } while (0)
#define LTS(i) do { } while (0)

#define STOP 100

struct Params {
  CUtensorMap mapO, mapXT, mapX128, mapWo128, mapO128, mapW3, mapW3h, mapXT3;
  const bf16 *a_re, *a_im, *b_re, *b_im, *c_re, *c_im, *log_dt, *dskip;
  bf16* out;
  int stop;
};

__device__ __forceinline__ uint32_t s32(const void* p) { return (uint32_t)__cvta_generic_to_shared(p); }
__device__ __forceinline__ void mbar_init(uint32_t b, int c) { asm volatile("mbarrier.init.shared::cta.b64 [%0], %1;" ::"r"(b), "r"(c) : "memory"); }
__device__ __forceinline__ void mbar_expect(uint32_t b, int bytes) { asm volatile("mbarrier.arrive.expect_tx.shared::cta.b64 _, [%0], %1;" ::"r"(b), "r"(bytes) : "memory"); }
__device__ __forceinline__ void mbar_arrive(uint32_t b) { asm volatile("mbarrier.arrive.shared::cta.b64 _, [%0];" ::"r"(b) : "memory"); }
__device__ __forceinline__ void mbar_arrive_if(uint32_t b, bool c) {
  asm volatile("{\n.reg .pred p;\nsetp.ne.u32 p, %1, 0;\n@p mbarrier.arrive.shared::cta.b64 _, [%0];\n}" ::"r"(b), "r"((uint32_t)c) : "memory");
}
__device__ __forceinline__ void mbar_wait(uint32_t b, int parity) {
  asm volatile("{\n.reg .pred p;\nWAIT_LOOP:\nmbarrier.try_wait.parity.shared::cta.b64 p, [%0], %1;\n@p bra WAIT_DONE;\nbra WAIT_LOOP;\nWAIT_DONE:\n}" ::"r"(b), "r"(parity) : "memory");
}
template <int N> __device__ __forceinline__ void delay() {
  if constexpr (N > 0) {
    uint32_t t0, t;
    asm volatile("mov.u32 %0, %%clock;" : "=r"(t0));
    do { asm volatile("mov.u32 %0, %%clock;" : "=r"(t)); } while (t - t0 < N);
  }
}
#define SF 3
template <int ID> __device__ __forceinline__ void sched_fence() {
  if constexpr ((SF >> ID) & 1)
    asm volatile("{\n.reg .pred p;\n.reg .u32 t;\nsetp.eq.u32 p, %0, 0;\n@p mov.u32 t, %%clock;\n@p st.shared.u32 [%0], t;\n}" ::"r"(gridDim.x) : "memory");
}
__device__ __forceinline__ int opaque_tid() { int v; asm volatile("mov.u32 %0, %%tid.x;" : "=r"(v)); return v; }
__device__ __forceinline__ bool elect_one() {
  uint32_t r;
  asm volatile("{\n.reg .pred p;\nelect.sync _|p, 0xffffffff;\nselp.u32 %0, 1, 0, p;\n}" : "=r"(r));
  return r != 0;
}
__device__ __forceinline__ void tma_ld(uint32_t dst, const CUtensorMap* m, int c0, int c1, uint32_t bar) {
  asm volatile("cp.async.bulk.tensor.2d.shared::cluster.global.mbarrier::complete_tx::bytes [%0], [%1, {%3, %4}], [%2];"
               ::"r"(dst), "l"(m), "r"(bar), "r"(c0), "r"(c1) : "memory");
}
__device__ __forceinline__ void tma_ld3(uint32_t dst, const CUtensorMap* m, int c0, int c1, int c2, uint32_t bar) {
  asm volatile("cp.async.bulk.tensor.3d.shared::cluster.global.mbarrier::complete_tx::bytes [%0], [%1, {%3, %4, %5}], [%2];"
               ::"r"(dst), "l"(m), "r"(bar), "r"(c0), "r"(c1), "r"(c2) : "memory");
}
__device__ __forceinline__ void tma_prefetch2(const CUtensorMap* m, int c0, int c1) {
  asm volatile("cp.async.bulk.prefetch.tensor.2d.L2.global.tile [%0, {%1, %2}];" ::"l"(m), "r"(c0), "r"(c1) : "memory");
}
__device__ __forceinline__ void tma_prefetch3(const CUtensorMap* m, int c0, int c1, int c2) {
  asm volatile("cp.async.bulk.prefetch.tensor.3d.L2.global.tile [%0, {%1, %2, %3}];" ::"l"(m), "r"(c0), "r"(c1), "r"(c2) : "memory");
}
__device__ __forceinline__ void tma_st(const CUtensorMap* m, int c0, int c1, uint32_t src) {
  asm volatile("cp.async.bulk.tensor.2d.global.shared::cta.bulk_group [%0, {%2, %3}], [%1];" ::"l"(m), "r"(src), "r"(c0), "r"(c1) : "memory");
}
__device__ __forceinline__ void bulk_ld(uint32_t dst, const void* src, int bytes, uint32_t bar) {
  asm volatile("cp.async.bulk.shared::cluster.global.mbarrier::complete_tx::bytes [%0], [%1], %2, [%3];" ::"r"(dst), "l"(src), "r"(bytes), "r"(bar) : "memory");
}
__device__ __forceinline__ void bulk_st(void* dst, uint32_t src, int bytes) {
  asm volatile("cp.async.bulk.global.shared::cta.bulk_group [%0], [%1], %2;" ::"l"(dst), "r"(src), "r"(bytes) : "memory");
}
__device__ __forceinline__ void bulk_red_add_f32(void* dst, uint32_t src, int bytes) {
  asm volatile("cp.reduce.async.bulk.global.shared::cta.bulk_group.add.f32 [%0], [%1], %2;" ::"l"(dst), "r"(src), "r"(bytes) : "memory");
}
__device__ __forceinline__ void bulk_commit() { asm volatile("cp.async.bulk.commit_group;" ::: "memory"); }
__device__ __forceinline__ void bulk_wait_all() { asm volatile("cp.async.bulk.wait_group 0;" ::: "memory"); }
__device__ __forceinline__ void fence_async_smem() { asm volatile("fence.proxy.async.shared::cta;" ::: "memory"); }
__device__ __forceinline__ void fence_writer() { if (!RFENCE) fence_async_smem(); }
__device__ __forceinline__ void fence_reader() { if (RFENCE) fence_async_smem(); }
__device__ __forceinline__ void fence_async_global() { asm volatile("fence.proxy.async.global;" ::: "memory"); }
__device__ __forceinline__ void bar_sync(int id, int n) { asm volatile("bar.sync %0, %1;" ::"r"(id), "r"(n) : "memory"); }
__device__ __forceinline__ void bar_arrive(int id, int n) { asm volatile("bar.arrive %0, %1;" ::"r"(id), "r"(n) : "memory"); }
__device__ __forceinline__ void wg_fence() { asm volatile("wgmma.fence.sync.aligned;" ::: "memory"); }
__device__ __forceinline__ void wg_commit() { asm volatile("wgmma.commit_group.sync.aligned;" ::: "memory"); }
template <int N> __device__ __forceinline__ void wg_wait() { asm volatile("wgmma.wait_group.sync.aligned %0;" ::"n"(N) : "memory"); }
__device__ __forceinline__ uint64_t mkdesc(uint32_t addr, uint32_t lbo, uint32_t sbo, int sw) {
  return (uint64_t)((addr & 0x3FFFF) >> 4) | ((uint64_t)(lbo >> 4) << 16) | ((uint64_t)(sbo >> 4) << 32) | ((uint64_t)sw << 62);
}
__device__ __forceinline__ void ldsm4(uint32_t* r, uint32_t a) {
  asm volatile("ldmatrix.sync.aligned.m8n8.x4.shared.b16 {%0,%1,%2,%3}, [%4];" : "=r"(r[0]), "=r"(r[1]), "=r"(r[2]), "=r"(r[3]) : "r"(a) : "memory");
}
__device__ __forceinline__ void ldsm4t(uint32_t* r, uint32_t a) {
  asm volatile("ldmatrix.sync.aligned.m8n8.x4.trans.shared.b16 {%0,%1,%2,%3}, [%4];" : "=r"(r[0]), "=r"(r[1]), "=r"(r[2]), "=r"(r[3]) : "r"(a) : "memory");
}
__device__ __forceinline__ void stsm4(uint32_t a, uint32_t r0, uint32_t r1, uint32_t r2, uint32_t r3) {
  asm volatile("stmatrix.sync.aligned.m8n8.x4.shared.b16 [%0], {%1,%2,%3,%4};" ::"r"(a), "r"(r0), "r"(r1), "r"(r2), "r"(r3) : "memory");
}
__device__ __forceinline__ void stsm4t(uint32_t a, uint32_t r0, uint32_t r1, uint32_t r2, uint32_t r3) {
  asm volatile("stmatrix.sync.aligned.m8n8.x4.trans.shared.b16 [%0], {%1,%2,%3,%4};" ::"r"(a), "r"(r0), "r"(r1), "r"(r2), "r"(r3) : "memory");
}
__device__ __forceinline__ uint32_t movm_t(uint32_t a) { uint32_t r; asm volatile("movmatrix.sync.aligned.m8n8.trans.b16 %0, %1;" : "=r"(r) : "r"(a)); return r; }
__device__ __forceinline__ uint32_t lds32(uint32_t a) { uint32_t v; asm volatile("ld.shared.b32 %0, [%1];" : "=r"(v) : "r"(a) : "memory"); return v; }
__device__ __forceinline__ float2 lds64f(uint32_t a) { float2 v; asm volatile("ld.shared.v2.f32 {%0,%1}, [%2];" : "=f"(v.x), "=f"(v.y) : "r"(a) : "memory"); return v; }
__device__ __forceinline__ float4 lds128f(uint32_t a) { float4 v; asm volatile("ld.shared.v4.f32 {%0,%1,%2,%3}, [%4];" : "=f"(v.x), "=f"(v.y), "=f"(v.z), "=f"(v.w) : "r"(a) : "memory"); return v; }
__device__ __forceinline__ uint4 lds128(uint32_t a) { uint4 v; asm volatile("ld.shared.v4.b32 {%0,%1,%2,%3}, [%4];" : "=r"(v.x), "=r"(v.y), "=r"(v.z), "=r"(v.w) : "r"(a) : "memory"); return v; }
__device__ __forceinline__ void sts128(uint32_t a, uint4 v) { asm volatile("st.shared.v4.b32 [%0], {%1,%2,%3,%4};" ::"r"(a), "r"(v.x), "r"(v.y), "r"(v.z), "r"(v.w) : "memory"); }
__device__ __forceinline__ void sts128f(uint32_t a, float x, float y, float z, float w) { asm volatile("st.shared.v4.f32 [%0], {%1,%2,%3,%4};" ::"r"(a), "f"(x), "f"(y), "f"(z), "f"(w) : "memory"); }
__device__ __forceinline__ void sts32f(uint32_t a, float v) { asm volatile("st.shared.f32 [%0], %1;" ::"r"(a), "f"(v) : "memory"); }
__device__ __forceinline__ void sts16(uint32_t a, uint16_t v) { asm volatile("st.shared.u16 [%0], %1;" ::"r"(a), "h"(v) : "memory"); }
__device__ __forceinline__ uint32_t lds16(uint32_t a) { uint16_t v; asm volatile("ld.shared.u16 %0, [%1];" : "=h"(v) : "r"(a) : "memory"); return v; }
__device__ __forceinline__ uint32_t packbf(float lo, float hi) { uint32_t r; asm("cvt.rn.bf16x2.f32 %0, %1, %2;" : "=r"(r) : "f"(hi), "f"(lo)); return r; }
__device__ __forceinline__ float bf_lo(uint32_t v) { return __uint_as_float(v << 16); }
__device__ __forceinline__ float bf_hi(uint32_t v) { return __uint_as_float(v & 0xffff0000u); }
__device__ __forceinline__ float ex2(float x) { float r; asm("ex2.approx.ftz.f32 %0, %1;" : "=f"(r) : "f"(x)); return r; }
__device__ __forceinline__ float rsqrt_approx(float x) { float r; asm("rsqrt.approx.ftz.f32 %0, %1;" : "=f"(r) : "f"(x)); return r; }
__device__ __forceinline__ float rcp_approx(float x) { float r; asm("rcp.approx.ftz.f32 %0, %1;" : "=f"(r) : "f"(x)); return r; }
__device__ __forceinline__ void mma_bf16(float* d, const uint32_t* a, uint32_t b0, uint32_t b1) {
  asm("mma.sync.aligned.m16n8k16.row.col.f32.bf16.bf16.f32 {%0,%1,%2,%3}, {%4,%5,%6,%7}, {%8,%9}, {%0,%1,%2,%3};"
               : "+f"(d[0]), "+f"(d[1]), "+f"(d[2]), "+f"(d[3]) : "r"(a[0]), "r"(a[1]), "r"(a[2]), "r"(a[3]), "r"(b0), "r"(b1));
}
__device__ __forceinline__ void mma_bf16_k8(float* d, uint32_t a0, uint32_t a1, uint32_t b) {
  asm("mma.sync.aligned.m16n8k8.row.col.f32.bf16.bf16.f32 {%0,%1,%2,%3}, {%4,%5}, {%6}, {%0,%1,%2,%3};"
      : "+f"(d[0]), "+f"(d[1]), "+f"(d[2]), "+f"(d[3]) : "r"(a0), "r"(a1), "r"(b));
}
__device__ __forceinline__ void red_release(unsigned* p) { asm volatile("red.release.gpu.global.add.u32 [%0], 1;" ::"l"(p) : "memory"); }
__device__ __forceinline__ void red_relaxed(unsigned* p) { asm volatile("red.relaxed.gpu.global.add.u32 [%0], 1;" ::"l"(p) : "memory"); }
__device__ __forceinline__ unsigned ld_relaxed(const unsigned* p) { unsigned v; asm volatile("ld.relaxed.gpu.global.u32 %0, [%1];" : "=r"(v) : "l"(p) : "memory"); return v; }
__device__ __forceinline__ void spin_until(const unsigned* p, unsigned target) {
  int it = 0;
  while ((int)(ld_relaxed(p) - target) < 0) {
    if (++it > (1 << 23)) __trap();
  }
}
__device__ __forceinline__ uint4 ldcg128(const void* p) { uint4 v; asm volatile("ld.global.cg.v4.b32 {%0,%1,%2,%3}, [%4];" : "=r"(v.x), "=r"(v.y), "=r"(v.z), "=r"(v.w) : "l"(p) : "memory"); return v; }
__device__ __forceinline__ uint4 ld_tagged(const uint4* p) { uint4 v; asm volatile("ld.relaxed.gpu.global.v4.u32 {%0,%1,%2,%3}, [%4];" : "=r"(v.x), "=r"(v.y), "=r"(v.z), "=r"(v.w) : "l"(p) : "memory"); return v; }
__device__ __forceinline__ uint2 ld_part(const uint2* p) { uint2 v; asm volatile("ld.relaxed.gpu.global.v2.u32 {%0,%1}, [%2];" : "=r"(v.x), "=r"(v.y) : "l"(p) : "memory"); return v; }
__device__ __forceinline__ void st_part(uint2* p, float s, float q, uint32_t tag) {
  asm volatile("st.relaxed.gpu.global.v2.u32 [%0], {%1,%2};" ::"l"(p), "r"(__float_as_uint(s)), "r"((__float_as_uint(q) & ~7u) | tag) : "memory");
}
__device__ __forceinline__ uint32_t part_tag(uint32_t epoch, int k) { return (4 * (epoch % 7) + k) % 7 + 1; }
__device__ __forceinline__ void st_tagged3(uint4* p, uint32_t a, uint32_t b, uint32_t c, uint32_t tag) { asm volatile("st.relaxed.gpu.global.v4.u32 [%0], {%1,%2,%3,%4};" ::"l"(p), "r"(a), "r"(b), "r"(c), "r"(tag) : "memory"); }
__device__ __forceinline__ uint32_t hadd2(uint32_t a, uint32_t b) { uint32_t r; asm("add.rn.bf16x2 %0, %1, %2;" : "=r"(r) : "r"(a), "r"(b)); return r; }
__device__ __forceinline__ uint32_t hmul2(uint32_t a, uint32_t b) { uint32_t r; asm("mul.rn.bf16x2 %0, %1, %2;" : "=r"(r) : "r"(a), "r"(b)); return r; }

template<int N,int TB> __device__ __forceinline__ void wgmma_rs(float* d, const uint32_t* a, uint64_t db, int sd);
template<int N,int TA,int TB> __device__ __forceinline__ void wgmma_ss(float* d, uint64_t da, uint64_t db, int sd);
template<> __device__ __forceinline__ void wgmma_rs<128,0>(float* d, const uint32_t* a, uint64_t db, int sd) {
  asm volatile("{\n.reg .pred p;\nsetp.ne.b32 p, %69, 0;\nwgmma.mma_async.sync.aligned.m64n128k16.f32.bf16.bf16 {%0,%1,%2,%3,%4,%5,%6,%7,%8,%9,%10,%11,%12,%13,%14,%15,%16,%17,%18,%19,%20,%21,%22,%23,%24,%25,%26,%27,%28,%29,%30,%31,%32,%33,%34,%35,%36,%37,%38,%39,%40,%41,%42,%43,%44,%45,%46,%47,%48,%49,%50,%51,%52,%53,%54,%55,%56,%57,%58,%59,%60,%61,%62,%63}, {%64,%65,%66,%67}, %68, p, 1, 1, 0;\n}\n"
   : "+f"(d[0]),"+f"(d[1]),"+f"(d[2]),"+f"(d[3]),"+f"(d[4]),"+f"(d[5]),"+f"(d[6]),"+f"(d[7]),"+f"(d[8]),"+f"(d[9]),"+f"(d[10]),"+f"(d[11]),"+f"(d[12]),"+f"(d[13]),"+f"(d[14]),"+f"(d[15]),"+f"(d[16]),"+f"(d[17]),"+f"(d[18]),"+f"(d[19]),"+f"(d[20]),"+f"(d[21]),"+f"(d[22]),"+f"(d[23]),"+f"(d[24]),"+f"(d[25]),"+f"(d[26]),"+f"(d[27]),"+f"(d[28]),"+f"(d[29]),"+f"(d[30]),"+f"(d[31]),"+f"(d[32]),"+f"(d[33]),"+f"(d[34]),"+f"(d[35]),"+f"(d[36]),"+f"(d[37]),"+f"(d[38]),"+f"(d[39]),"+f"(d[40]),"+f"(d[41]),"+f"(d[42]),"+f"(d[43]),"+f"(d[44]),"+f"(d[45]),"+f"(d[46]),"+f"(d[47]),"+f"(d[48]),"+f"(d[49]),"+f"(d[50]),"+f"(d[51]),"+f"(d[52]),"+f"(d[53]),"+f"(d[54]),"+f"(d[55]),"+f"(d[56]),"+f"(d[57]),"+f"(d[58]),"+f"(d[59]),"+f"(d[60]),"+f"(d[61]),"+f"(d[62]),"+f"(d[63])
   : "r"(a[0]), "r"(a[1]), "r"(a[2]), "r"(a[3]), "l"(db), "r"(sd));
}
template<> __device__ __forceinline__ void wgmma_rs<120,0>(float* d, const uint32_t* a, uint64_t db, int sd) {
  asm volatile("{\n.reg .pred p;\nsetp.ne.b32 p, %65, 0;\nwgmma.mma_async.sync.aligned.m64n120k16.f32.bf16.bf16 {%0,%1,%2,%3,%4,%5,%6,%7,%8,%9,%10,%11,%12,%13,%14,%15,%16,%17,%18,%19,%20,%21,%22,%23,%24,%25,%26,%27,%28,%29,%30,%31,%32,%33,%34,%35,%36,%37,%38,%39,%40,%41,%42,%43,%44,%45,%46,%47,%48,%49,%50,%51,%52,%53,%54,%55,%56,%57,%58,%59}, {%60,%61,%62,%63}, %64, p, 1, 1, 0;\n}\n"
   : "+f"(d[0]),"+f"(d[1]),"+f"(d[2]),"+f"(d[3]),"+f"(d[4]),"+f"(d[5]),"+f"(d[6]),"+f"(d[7]),"+f"(d[8]),"+f"(d[9]),"+f"(d[10]),"+f"(d[11]),"+f"(d[12]),"+f"(d[13]),"+f"(d[14]),"+f"(d[15]),"+f"(d[16]),"+f"(d[17]),"+f"(d[18]),"+f"(d[19]),"+f"(d[20]),"+f"(d[21]),"+f"(d[22]),"+f"(d[23]),"+f"(d[24]),"+f"(d[25]),"+f"(d[26]),"+f"(d[27]),"+f"(d[28]),"+f"(d[29]),"+f"(d[30]),"+f"(d[31]),"+f"(d[32]),"+f"(d[33]),"+f"(d[34]),"+f"(d[35]),"+f"(d[36]),"+f"(d[37]),"+f"(d[38]),"+f"(d[39]),"+f"(d[40]),"+f"(d[41]),"+f"(d[42]),"+f"(d[43]),"+f"(d[44]),"+f"(d[45]),"+f"(d[46]),"+f"(d[47]),"+f"(d[48]),"+f"(d[49]),"+f"(d[50]),"+f"(d[51]),"+f"(d[52]),"+f"(d[53]),"+f"(d[54]),"+f"(d[55]),"+f"(d[56]),"+f"(d[57]),"+f"(d[58]),"+f"(d[59])
   : "r"(a[0]), "r"(a[1]), "r"(a[2]), "r"(a[3]), "l"(db), "r"(sd));
}
template<> __device__ __forceinline__ void wgmma_rs<112,0>(float* d, const uint32_t* a, uint64_t db, int sd) {
  asm volatile("{\n.reg .pred p;\nsetp.ne.b32 p, %61, 0;\nwgmma.mma_async.sync.aligned.m64n112k16.f32.bf16.bf16 {%0,%1,%2,%3,%4,%5,%6,%7,%8,%9,%10,%11,%12,%13,%14,%15,%16,%17,%18,%19,%20,%21,%22,%23,%24,%25,%26,%27,%28,%29,%30,%31,%32,%33,%34,%35,%36,%37,%38,%39,%40,%41,%42,%43,%44,%45,%46,%47,%48,%49,%50,%51,%52,%53,%54,%55}, {%56,%57,%58,%59}, %60, p, 1, 1, 0;\n}\n"
   : "+f"(d[0]),"+f"(d[1]),"+f"(d[2]),"+f"(d[3]),"+f"(d[4]),"+f"(d[5]),"+f"(d[6]),"+f"(d[7]),"+f"(d[8]),"+f"(d[9]),"+f"(d[10]),"+f"(d[11]),"+f"(d[12]),"+f"(d[13]),"+f"(d[14]),"+f"(d[15]),"+f"(d[16]),"+f"(d[17]),"+f"(d[18]),"+f"(d[19]),"+f"(d[20]),"+f"(d[21]),"+f"(d[22]),"+f"(d[23]),"+f"(d[24]),"+f"(d[25]),"+f"(d[26]),"+f"(d[27]),"+f"(d[28]),"+f"(d[29]),"+f"(d[30]),"+f"(d[31]),"+f"(d[32]),"+f"(d[33]),"+f"(d[34]),"+f"(d[35]),"+f"(d[36]),"+f"(d[37]),"+f"(d[38]),"+f"(d[39]),"+f"(d[40]),"+f"(d[41]),"+f"(d[42]),"+f"(d[43]),"+f"(d[44]),"+f"(d[45]),"+f"(d[46]),"+f"(d[47]),"+f"(d[48]),"+f"(d[49]),"+f"(d[50]),"+f"(d[51]),"+f"(d[52]),"+f"(d[53]),"+f"(d[54]),"+f"(d[55])
   : "r"(a[0]), "r"(a[1]), "r"(a[2]), "r"(a[3]), "l"(db), "r"(sd));
}
template<> __device__ __forceinline__ void wgmma_rs<104,0>(float* d, const uint32_t* a, uint64_t db, int sd) {
  asm volatile("{\n.reg .pred p;\nsetp.ne.b32 p, %57, 0;\nwgmma.mma_async.sync.aligned.m64n104k16.f32.bf16.bf16 {%0,%1,%2,%3,%4,%5,%6,%7,%8,%9,%10,%11,%12,%13,%14,%15,%16,%17,%18,%19,%20,%21,%22,%23,%24,%25,%26,%27,%28,%29,%30,%31,%32,%33,%34,%35,%36,%37,%38,%39,%40,%41,%42,%43,%44,%45,%46,%47,%48,%49,%50,%51}, {%52,%53,%54,%55}, %56, p, 1, 1, 0;\n}\n"
   : "+f"(d[0]),"+f"(d[1]),"+f"(d[2]),"+f"(d[3]),"+f"(d[4]),"+f"(d[5]),"+f"(d[6]),"+f"(d[7]),"+f"(d[8]),"+f"(d[9]),"+f"(d[10]),"+f"(d[11]),"+f"(d[12]),"+f"(d[13]),"+f"(d[14]),"+f"(d[15]),"+f"(d[16]),"+f"(d[17]),"+f"(d[18]),"+f"(d[19]),"+f"(d[20]),"+f"(d[21]),"+f"(d[22]),"+f"(d[23]),"+f"(d[24]),"+f"(d[25]),"+f"(d[26]),"+f"(d[27]),"+f"(d[28]),"+f"(d[29]),"+f"(d[30]),"+f"(d[31]),"+f"(d[32]),"+f"(d[33]),"+f"(d[34]),"+f"(d[35]),"+f"(d[36]),"+f"(d[37]),"+f"(d[38]),"+f"(d[39]),"+f"(d[40]),"+f"(d[41]),"+f"(d[42]),"+f"(d[43]),"+f"(d[44]),"+f"(d[45]),"+f"(d[46]),"+f"(d[47]),"+f"(d[48]),"+f"(d[49]),"+f"(d[50]),"+f"(d[51])
   : "r"(a[0]), "r"(a[1]), "r"(a[2]), "r"(a[3]), "l"(db), "r"(sd));
}
template<> __device__ __forceinline__ void wgmma_rs<96,0>(float* d, const uint32_t* a, uint64_t db, int sd) {
  asm volatile("{\n.reg .pred p;\nsetp.ne.b32 p, %53, 0;\nwgmma.mma_async.sync.aligned.m64n96k16.f32.bf16.bf16 {%0,%1,%2,%3,%4,%5,%6,%7,%8,%9,%10,%11,%12,%13,%14,%15,%16,%17,%18,%19,%20,%21,%22,%23,%24,%25,%26,%27,%28,%29,%30,%31,%32,%33,%34,%35,%36,%37,%38,%39,%40,%41,%42,%43,%44,%45,%46,%47}, {%48,%49,%50,%51}, %52, p, 1, 1, 0;\n}\n"
   : "+f"(d[0]),"+f"(d[1]),"+f"(d[2]),"+f"(d[3]),"+f"(d[4]),"+f"(d[5]),"+f"(d[6]),"+f"(d[7]),"+f"(d[8]),"+f"(d[9]),"+f"(d[10]),"+f"(d[11]),"+f"(d[12]),"+f"(d[13]),"+f"(d[14]),"+f"(d[15]),"+f"(d[16]),"+f"(d[17]),"+f"(d[18]),"+f"(d[19]),"+f"(d[20]),"+f"(d[21]),"+f"(d[22]),"+f"(d[23]),"+f"(d[24]),"+f"(d[25]),"+f"(d[26]),"+f"(d[27]),"+f"(d[28]),"+f"(d[29]),"+f"(d[30]),"+f"(d[31]),"+f"(d[32]),"+f"(d[33]),"+f"(d[34]),"+f"(d[35]),"+f"(d[36]),"+f"(d[37]),"+f"(d[38]),"+f"(d[39]),"+f"(d[40]),"+f"(d[41]),"+f"(d[42]),"+f"(d[43]),"+f"(d[44]),"+f"(d[45]),"+f"(d[46]),"+f"(d[47])
   : "r"(a[0]), "r"(a[1]), "r"(a[2]), "r"(a[3]), "l"(db), "r"(sd));
}
template<> __device__ __forceinline__ void wgmma_rs<88,0>(float* d, const uint32_t* a, uint64_t db, int sd) {
  asm volatile("{\n.reg .pred p;\nsetp.ne.b32 p, %49, 0;\nwgmma.mma_async.sync.aligned.m64n88k16.f32.bf16.bf16 {%0,%1,%2,%3,%4,%5,%6,%7,%8,%9,%10,%11,%12,%13,%14,%15,%16,%17,%18,%19,%20,%21,%22,%23,%24,%25,%26,%27,%28,%29,%30,%31,%32,%33,%34,%35,%36,%37,%38,%39,%40,%41,%42,%43}, {%44,%45,%46,%47}, %48, p, 1, 1, 0;\n}\n"
   : "+f"(d[0]),"+f"(d[1]),"+f"(d[2]),"+f"(d[3]),"+f"(d[4]),"+f"(d[5]),"+f"(d[6]),"+f"(d[7]),"+f"(d[8]),"+f"(d[9]),"+f"(d[10]),"+f"(d[11]),"+f"(d[12]),"+f"(d[13]),"+f"(d[14]),"+f"(d[15]),"+f"(d[16]),"+f"(d[17]),"+f"(d[18]),"+f"(d[19]),"+f"(d[20]),"+f"(d[21]),"+f"(d[22]),"+f"(d[23]),"+f"(d[24]),"+f"(d[25]),"+f"(d[26]),"+f"(d[27]),"+f"(d[28]),"+f"(d[29]),"+f"(d[30]),"+f"(d[31]),"+f"(d[32]),"+f"(d[33]),"+f"(d[34]),"+f"(d[35]),"+f"(d[36]),"+f"(d[37]),"+f"(d[38]),"+f"(d[39]),"+f"(d[40]),"+f"(d[41]),"+f"(d[42]),"+f"(d[43])
   : "r"(a[0]), "r"(a[1]), "r"(a[2]), "r"(a[3]), "l"(db), "r"(sd));
}
template<> __device__ __forceinline__ void wgmma_rs<80,0>(float* d, const uint32_t* a, uint64_t db, int sd) {
  asm volatile("{\n.reg .pred p;\nsetp.ne.b32 p, %45, 0;\nwgmma.mma_async.sync.aligned.m64n80k16.f32.bf16.bf16 {%0,%1,%2,%3,%4,%5,%6,%7,%8,%9,%10,%11,%12,%13,%14,%15,%16,%17,%18,%19,%20,%21,%22,%23,%24,%25,%26,%27,%28,%29,%30,%31,%32,%33,%34,%35,%36,%37,%38,%39}, {%40,%41,%42,%43}, %44, p, 1, 1, 0;\n}\n"
   : "+f"(d[0]),"+f"(d[1]),"+f"(d[2]),"+f"(d[3]),"+f"(d[4]),"+f"(d[5]),"+f"(d[6]),"+f"(d[7]),"+f"(d[8]),"+f"(d[9]),"+f"(d[10]),"+f"(d[11]),"+f"(d[12]),"+f"(d[13]),"+f"(d[14]),"+f"(d[15]),"+f"(d[16]),"+f"(d[17]),"+f"(d[18]),"+f"(d[19]),"+f"(d[20]),"+f"(d[21]),"+f"(d[22]),"+f"(d[23]),"+f"(d[24]),"+f"(d[25]),"+f"(d[26]),"+f"(d[27]),"+f"(d[28]),"+f"(d[29]),"+f"(d[30]),"+f"(d[31]),"+f"(d[32]),"+f"(d[33]),"+f"(d[34]),"+f"(d[35]),"+f"(d[36]),"+f"(d[37]),"+f"(d[38]),"+f"(d[39])
   : "r"(a[0]), "r"(a[1]), "r"(a[2]), "r"(a[3]), "l"(db), "r"(sd));
}
template<> __device__ __forceinline__ void wgmma_rs<72,0>(float* d, const uint32_t* a, uint64_t db, int sd) {
  asm volatile("{\n.reg .pred p;\nsetp.ne.b32 p, %41, 0;\nwgmma.mma_async.sync.aligned.m64n72k16.f32.bf16.bf16 {%0,%1,%2,%3,%4,%5,%6,%7,%8,%9,%10,%11,%12,%13,%14,%15,%16,%17,%18,%19,%20,%21,%22,%23,%24,%25,%26,%27,%28,%29,%30,%31,%32,%33,%34,%35}, {%36,%37,%38,%39}, %40, p, 1, 1, 0;\n}\n"
   : "+f"(d[0]),"+f"(d[1]),"+f"(d[2]),"+f"(d[3]),"+f"(d[4]),"+f"(d[5]),"+f"(d[6]),"+f"(d[7]),"+f"(d[8]),"+f"(d[9]),"+f"(d[10]),"+f"(d[11]),"+f"(d[12]),"+f"(d[13]),"+f"(d[14]),"+f"(d[15]),"+f"(d[16]),"+f"(d[17]),"+f"(d[18]),"+f"(d[19]),"+f"(d[20]),"+f"(d[21]),"+f"(d[22]),"+f"(d[23]),"+f"(d[24]),"+f"(d[25]),"+f"(d[26]),"+f"(d[27]),"+f"(d[28]),"+f"(d[29]),"+f"(d[30]),"+f"(d[31]),"+f"(d[32]),"+f"(d[33]),"+f"(d[34]),"+f"(d[35])
   : "r"(a[0]), "r"(a[1]), "r"(a[2]), "r"(a[3]), "l"(db), "r"(sd));
}
template<> __device__ __forceinline__ void wgmma_rs<64,0>(float* d, const uint32_t* a, uint64_t db, int sd) {
  asm volatile("{\n.reg .pred p;\nsetp.ne.b32 p, %37, 0;\nwgmma.mma_async.sync.aligned.m64n64k16.f32.bf16.bf16 {%0,%1,%2,%3,%4,%5,%6,%7,%8,%9,%10,%11,%12,%13,%14,%15,%16,%17,%18,%19,%20,%21,%22,%23,%24,%25,%26,%27,%28,%29,%30,%31}, {%32,%33,%34,%35}, %36, p, 1, 1, 0;\n}\n"
   : "+f"(d[0]),"+f"(d[1]),"+f"(d[2]),"+f"(d[3]),"+f"(d[4]),"+f"(d[5]),"+f"(d[6]),"+f"(d[7]),"+f"(d[8]),"+f"(d[9]),"+f"(d[10]),"+f"(d[11]),"+f"(d[12]),"+f"(d[13]),"+f"(d[14]),"+f"(d[15]),"+f"(d[16]),"+f"(d[17]),"+f"(d[18]),"+f"(d[19]),"+f"(d[20]),"+f"(d[21]),"+f"(d[22]),"+f"(d[23]),"+f"(d[24]),"+f"(d[25]),"+f"(d[26]),"+f"(d[27]),"+f"(d[28]),"+f"(d[29]),"+f"(d[30]),"+f"(d[31])
   : "r"(a[0]), "r"(a[1]), "r"(a[2]), "r"(a[3]), "l"(db), "r"(sd));
}
template<> __device__ __forceinline__ void wgmma_ss<64,0,1>(float* d, uint64_t da, uint64_t db, int sd) {
  asm volatile("{\n.reg .pred p;\nsetp.ne.b32 p, %34, 0;\nwgmma.mma_async.sync.aligned.m64n64k16.f32.bf16.bf16 {%0,%1,%2,%3,%4,%5,%6,%7,%8,%9,%10,%11,%12,%13,%14,%15,%16,%17,%18,%19,%20,%21,%22,%23,%24,%25,%26,%27,%28,%29,%30,%31}, %32, %33, p, 1, 1, 0, 1;\n}\n"
   : "+f"(d[0]),"+f"(d[1]),"+f"(d[2]),"+f"(d[3]),"+f"(d[4]),"+f"(d[5]),"+f"(d[6]),"+f"(d[7]),"+f"(d[8]),"+f"(d[9]),"+f"(d[10]),"+f"(d[11]),"+f"(d[12]),"+f"(d[13]),"+f"(d[14]),"+f"(d[15]),"+f"(d[16]),"+f"(d[17]),"+f"(d[18]),"+f"(d[19]),"+f"(d[20]),"+f"(d[21]),"+f"(d[22]),"+f"(d[23]),"+f"(d[24]),"+f"(d[25]),"+f"(d[26]),"+f"(d[27]),"+f"(d[28]),"+f"(d[29]),"+f"(d[30]),"+f"(d[31])
   : "l"(da), "l"(db), "r"(sd));
}
template<> __device__ __forceinline__ void wgmma_ss<64,1,1>(float* d, uint64_t da, uint64_t db, int sd) {
  asm volatile("{\n.reg .pred p;\nsetp.ne.b32 p, %34, 0;\nwgmma.mma_async.sync.aligned.m64n64k16.f32.bf16.bf16 {%0,%1,%2,%3,%4,%5,%6,%7,%8,%9,%10,%11,%12,%13,%14,%15,%16,%17,%18,%19,%20,%21,%22,%23,%24,%25,%26,%27,%28,%29,%30,%31}, %32, %33, p, 1, 1, 1, 1;\n}\n"
   : "+f"(d[0]),"+f"(d[1]),"+f"(d[2]),"+f"(d[3]),"+f"(d[4]),"+f"(d[5]),"+f"(d[6]),"+f"(d[7]),"+f"(d[8]),"+f"(d[9]),"+f"(d[10]),"+f"(d[11]),"+f"(d[12]),"+f"(d[13]),"+f"(d[14]),"+f"(d[15]),"+f"(d[16]),"+f"(d[17]),"+f"(d[18]),"+f"(d[19]),"+f"(d[20]),"+f"(d[21]),"+f"(d[22]),"+f"(d[23]),"+f"(d[24]),"+f"(d[25]),"+f"(d[26]),"+f"(d[27]),"+f"(d[28]),"+f"(d[29]),"+f"(d[30]),"+f"(d[31])
   : "l"(da), "l"(db), "r"(sd));
}
template<> __device__ __forceinline__ void wgmma_ss<192,0,1>(float* d, uint64_t da, uint64_t db, int sd) {
  asm volatile("{\n.reg .pred p;\nsetp.ne.b32 p, %98, 0;\nwgmma.mma_async.sync.aligned.m64n192k16.f32.bf16.bf16 {%0,%1,%2,%3,%4,%5,%6,%7,%8,%9,%10,%11,%12,%13,%14,%15,%16,%17,%18,%19,%20,%21,%22,%23,%24,%25,%26,%27,%28,%29,%30,%31,%32,%33,%34,%35,%36,%37,%38,%39,%40,%41,%42,%43,%44,%45,%46,%47,%48,%49,%50,%51,%52,%53,%54,%55,%56,%57,%58,%59,%60,%61,%62,%63,%64,%65,%66,%67,%68,%69,%70,%71,%72,%73,%74,%75,%76,%77,%78,%79,%80,%81,%82,%83,%84,%85,%86,%87,%88,%89,%90,%91,%92,%93,%94,%95}, %96, %97, p, 1, 1, 0, 1;\n}\n"
   : "+f"(d[0]),"+f"(d[1]),"+f"(d[2]),"+f"(d[3]),"+f"(d[4]),"+f"(d[5]),"+f"(d[6]),"+f"(d[7]),"+f"(d[8]),"+f"(d[9]),"+f"(d[10]),"+f"(d[11]),"+f"(d[12]),"+f"(d[13]),"+f"(d[14]),"+f"(d[15]),"+f"(d[16]),"+f"(d[17]),"+f"(d[18]),"+f"(d[19]),"+f"(d[20]),"+f"(d[21]),"+f"(d[22]),"+f"(d[23]),"+f"(d[24]),"+f"(d[25]),"+f"(d[26]),"+f"(d[27]),"+f"(d[28]),"+f"(d[29]),"+f"(d[30]),"+f"(d[31]),"+f"(d[32]),"+f"(d[33]),"+f"(d[34]),"+f"(d[35]),"+f"(d[36]),"+f"(d[37]),"+f"(d[38]),"+f"(d[39]),"+f"(d[40]),"+f"(d[41]),"+f"(d[42]),"+f"(d[43]),"+f"(d[44]),"+f"(d[45]),"+f"(d[46]),"+f"(d[47]),"+f"(d[48]),"+f"(d[49]),"+f"(d[50]),"+f"(d[51]),"+f"(d[52]),"+f"(d[53]),"+f"(d[54]),"+f"(d[55]),"+f"(d[56]),"+f"(d[57]),"+f"(d[58]),"+f"(d[59]),"+f"(d[60]),"+f"(d[61]),"+f"(d[62]),"+f"(d[63]),"+f"(d[64]),"+f"(d[65]),"+f"(d[66]),"+f"(d[67]),"+f"(d[68]),"+f"(d[69]),"+f"(d[70]),"+f"(d[71]),"+f"(d[72]),"+f"(d[73]),"+f"(d[74]),"+f"(d[75]),"+f"(d[76]),"+f"(d[77]),"+f"(d[78]),"+f"(d[79]),"+f"(d[80]),"+f"(d[81]),"+f"(d[82]),"+f"(d[83]),"+f"(d[84]),"+f"(d[85]),"+f"(d[86]),"+f"(d[87]),"+f"(d[88]),"+f"(d[89]),"+f"(d[90]),"+f"(d[91]),"+f"(d[92]),"+f"(d[93]),"+f"(d[94]),"+f"(d[95])
   : "l"(da), "l"(db), "r"(sd));
}
template<> __device__ __forceinline__ void wgmma_ss<192,1,1>(float* d, uint64_t da, uint64_t db, int sd) {
  asm volatile("{\n.reg .pred p;\nsetp.ne.b32 p, %98, 0;\nwgmma.mma_async.sync.aligned.m64n192k16.f32.bf16.bf16 {%0,%1,%2,%3,%4,%5,%6,%7,%8,%9,%10,%11,%12,%13,%14,%15,%16,%17,%18,%19,%20,%21,%22,%23,%24,%25,%26,%27,%28,%29,%30,%31,%32,%33,%34,%35,%36,%37,%38,%39,%40,%41,%42,%43,%44,%45,%46,%47,%48,%49,%50,%51,%52,%53,%54,%55,%56,%57,%58,%59,%60,%61,%62,%63,%64,%65,%66,%67,%68,%69,%70,%71,%72,%73,%74,%75,%76,%77,%78,%79,%80,%81,%82,%83,%84,%85,%86,%87,%88,%89,%90,%91,%92,%93,%94,%95}, %96, %97, p, 1, 1, 1, 1;\n}\n"
   : "+f"(d[0]),"+f"(d[1]),"+f"(d[2]),"+f"(d[3]),"+f"(d[4]),"+f"(d[5]),"+f"(d[6]),"+f"(d[7]),"+f"(d[8]),"+f"(d[9]),"+f"(d[10]),"+f"(d[11]),"+f"(d[12]),"+f"(d[13]),"+f"(d[14]),"+f"(d[15]),"+f"(d[16]),"+f"(d[17]),"+f"(d[18]),"+f"(d[19]),"+f"(d[20]),"+f"(d[21]),"+f"(d[22]),"+f"(d[23]),"+f"(d[24]),"+f"(d[25]),"+f"(d[26]),"+f"(d[27]),"+f"(d[28]),"+f"(d[29]),"+f"(d[30]),"+f"(d[31]),"+f"(d[32]),"+f"(d[33]),"+f"(d[34]),"+f"(d[35]),"+f"(d[36]),"+f"(d[37]),"+f"(d[38]),"+f"(d[39]),"+f"(d[40]),"+f"(d[41]),"+f"(d[42]),"+f"(d[43]),"+f"(d[44]),"+f"(d[45]),"+f"(d[46]),"+f"(d[47]),"+f"(d[48]),"+f"(d[49]),"+f"(d[50]),"+f"(d[51]),"+f"(d[52]),"+f"(d[53]),"+f"(d[54]),"+f"(d[55]),"+f"(d[56]),"+f"(d[57]),"+f"(d[58]),"+f"(d[59]),"+f"(d[60]),"+f"(d[61]),"+f"(d[62]),"+f"(d[63]),"+f"(d[64]),"+f"(d[65]),"+f"(d[66]),"+f"(d[67]),"+f"(d[68]),"+f"(d[69]),"+f"(d[70]),"+f"(d[71]),"+f"(d[72]),"+f"(d[73]),"+f"(d[74]),"+f"(d[75]),"+f"(d[76]),"+f"(d[77]),"+f"(d[78]),"+f"(d[79]),"+f"(d[80]),"+f"(d[81]),"+f"(d[82]),"+f"(d[83]),"+f"(d[84]),"+f"(d[85]),"+f"(d[86]),"+f"(d[87]),"+f"(d[88]),"+f"(d[89]),"+f"(d[90]),"+f"(d[91]),"+f"(d[92]),"+f"(d[93]),"+f"(d[94]),"+f"(d[95])
   : "l"(da), "l"(db), "r"(sd));
}

__device__ __forceinline__ void stats_publish(uint32_t sb, int layer, int rb, int hg, int ht, uint32_t tag) {
  const int lane = ht & 31, w = ht >> 5, g = lane >> 2, t = lane & 3, ks = hg & 3;
  uint32_t xa;
  if (layer == 0) {
    const int row = 16 * w + (lane & 15), kc = 2 * ks + (lane >> 4);
    xa = row * 128 + ((kc ^ (row & 7)) << 4);
  } else {
    const int k = 16 * ks + (lane & 7) + 8 * (lane >> 4), pc = 2 * w + ((lane >> 3) & 1);
    xa = k * 128 + ((pc ^ (k & 7)) << 4);
  }
  float s[4] = {0.f, 0.f, 0.f, 0.f}, q[4] = {0.f, 0.f, 0.f, 0.f};
#pragma unroll 1
  for (int c = hg >> 2; c < 8; c += 2) {
    uint32_t A[2][4];
    mbar_wait(sb + SM_BAR + 8 * (B_XF + c), layer);
#pragma unroll
    for (int h = 0; h < 2; h++) {
      if (layer == 0) ldsm4(A[h], sb + SM_X + c * 16384 + h * 8192 + xa);
      else ldsm4t(A[h], sb + SM_X + c * 16384 + h * 8192 + xa);
    }
    if (c >= 6) ATS(48, 256);
    if (c < 2) ATS(51, 256);
#pragma unroll
    for (int r = 0; r < 4; r++)
#pragma unroll
      for (int i = 0; i < 2; i++) {
        const uint32_t v = A[r >> 1][2 * i + (r & 1)];
        const float a = bf_lo(v), b = bf_hi(v);
        s[r] += a + b; q[r] = fmaf(a, a, q[r]); q[r] = fmaf(b, b, q[r]);
      }
  }
#pragma unroll
  for (int r = 0; r < 2; r++) {
    s[r] = ((t & 2) ? s[r + 2] : s[r]) + __shfl_xor_sync(~0u, (t & 2) ? s[r] : s[r + 2], 2);
    q[r] = ((t & 2) ? q[r + 2] : q[r]) + __shfl_xor_sync(~0u, (t & 2) ? q[r] : q[r + 2], 2);
  }
  s[0] = ((t & 1) ? s[1] : s[0]) + __shfl_xor_sync(~0u, (t & 1) ? s[0] : s[1], 1);
  q[0] = ((t & 1) ? q[1] : q[0]) + __shfl_xor_sync(~0u, (t & 1) ? q[0] : q[1], 1);
  st_part(&g_part[(rb * 8 + hg) * 128 + 64 * (t >> 1) + 16 * w + 8 * (t & 1) + g], s[0], q[0], tag);
  ATS(49, 256);
}
__device__ __forceinline__ void stats_gather(uint32_t sb, int rb, int ht, uint32_t tag) {
  const uint2* src = &g_part[rb * 8 * 128 + ht];
  uint2 v[8];
  for (int it = 0;; it++) {
    uint32_t bad = 0;
#pragma unroll
    for (int i = 0; i < 8; i++) v[i] = ld_part(src + i * 128);
#pragma unroll
    for (int i = 0; i < 8; i++) bad |= v[i].y ^ tag;
    if (__all_sync(~0u, (bad & 7u) == 0)) break;
    if (it > (1 << 22)) __trap();
  }
  float s = 0.f, q = 0.f;
#pragma unroll
  for (int i = 0; i < 8; i++) { s += __uint_as_float(v[i].x); q += __uint_as_float(v[i].y); }
  const float mean = s * (1.f / DM);
  const float rstd = rsqrt_approx(fmaxf(q * (1.f / DM) - mean * mean, 0.f) + 1e-5f);
  asm volatile("st.shared.v2.f32 [%0], {%1,%2};" ::"r"(sb + SM_ST + ht * 8), "f"(mean), "f"(rstd) : "memory");
  __syncwarp();
  if (elect_one()) mbar_arrive(sb + SM_BAR + 8 * B_STF);
}
__device__ __forceinline__ void halo_receive(uint32_t sb, int layer, int rb, int hg, int ht) {
  const int lane = ht & 31, h = ht >> 5;
  uint4 kv = make_uint4(0, 0, 0, 0);
  mbar_wait(sb + SM_BAR + 8 * B_SD, layer);
  if (rb & 7) {
    const uint32_t tag = 2 * lds32(sb + SM_EP) + layer + 1;
    const uint4* src = &g_halo[((rb - 1) * 8 + hg) * 192 + h * 48];
    if (layer == 0) delay<D_HALO>(); else delay<D_HALO1>();
    uint4 a;
    uint2 b;
    int it = 0;
    do {
      a = ld_tagged(src + lane); b = ld_part((const uint2*)(src + 32) + lane);
      if (++it > (1 << 22)) __trap();
    } while (!__all_sync(~0u, a.w == tag && b.y == tag));
    kv = make_uint4(a.x, a.y, movm_t(a.z), movm_t(b.x));
  }
  sts128(sb + SM_KVX + h * 512 + lane * 16, kv);
  ATS(61, 256);
  bar_arrive(7, 160);
  if (elect_one()) mbar_arrive(sb + SM_BAR + 8 * B_HF);
}

__device__ __forceinline__ void halo_receive1(uint32_t sb, int layer, int rb, int hg, int lane, uint32_t tag) {
  uint4 a[4];
  uint2 b[4];
  mbar_wait(sb + SM_BAR + 8 * B_SD, layer);
  if (rb & 7) {
    const uint4* src = &g_halo[((rb - 1) * 8 + hg) * 192];
    if (layer == 0) delay<D_HALO>(); else delay<D_HALO1>();
    for (int it = 0;; it++) {
      uint32_t bad = 0;
#pragma unroll
      for (int h = 0; h < 4; h++) { a[h] = ld_tagged(src + h * 48 + lane); b[h] = ld_part((const uint2*)(src + h * 48 + 32) + lane); }
#pragma unroll
      for (int h = 0; h < 4; h++) {
        bad |= (a[h].w ^ tag) | (b[h].y ^ tag);
        a[h].z = movm_t(a[h].z); a[h].w = movm_t(b[h].x);
      }
      if (__all_sync(~0u, bad == 0)) break;
      if (it > (1 << 22)) __trap();
    }
  } else {
#pragma unroll
    for (int h = 0; h < 4; h++) a[h] = make_uint4(0, 0, 0, 0);
  }
#pragma unroll
  for (int h = 0; h < 4; h++) sts128(sb + SM_KVX + h * 512 + lane * 16, a[h]);
  ATS(61, 448);
  bar_arrive(7, 64);
  if (lane < 4) mbar_arrive(sb + SM_BAR + 8 * B_HF);
}

template <bool TR>
__device__ __forceinline__ void gemm_section(float* acc, float2* cs, uint32_t sb, int layer, int wg, int w, int lane) {
  const uint32_t bar = sb + SM_BAR;
  const bool leader = (w == 0) && (lane == 0);
  auto issue = [&](int c, int slot) {
    mbar_wait(bar + 8 * (B_XF + c), layer);
    mbar_wait(bar + 8 * (B_KVF + c), layer);
    const uint64_t da = mkdesc(sb + SM_X + c * 16384 + wg * 8192, TR ? 8192 : 16, 1024, 1);
    const uint64_t db = mkdesc(sb + SM_W + slot * 24576, 8192, 1024, 1);
    wg_fence();
#pragma unroll
    for (int ks = 0; ks < 4; ks++) wgmma_ss<192, TR ? 1 : 0, 1>(acc, da + (TR ? ks * 128 : ks * 2), db + ks * 128, (c | ks) != 0);
    wg_commit();
  };
  auto step = [&](int c, int slot) {
    issue(c, slot);
    wg_wait<1>();
    if (leader) mbar_arrive(bar + 8 * (B_KVE + c - 1));
  };
  if (!TR) bar_sync(0, NTHREADS);
  issue(0, 0);
  if (threadIdx.x == 0) TS(2 + layer * 20 + 0);
  if (threadIdx.x == 128 && layer == 1) TS(60);
  step(1, 1); step(2, 2); step(3, 0); step(4, 1);
  auto ld_cs = [&](int j0) {
#pragma unroll
    for (int j = j0; j < j0 + 8; j++) cs[j] = lds64f(sb + SM_CS + 4 * (8 * j + 2 * (lane & 3)));
  };
  if (TR) ld_cs(8);
  step(5, 2);
  if (!TR && !CS_LATE0) { mbar_wait(bar + 8 * B_CSF, 0); ld_cs(8); }
  if (TR || !CS_LATE0) ld_cs(16);
  if (wg == 0) bar_sync(5, 256);
  issue(6, 0);
  issue(7, 1);
  if (wg == 1) bar_arrive(5, 256);
  if (!TR && CS_LATE0) { mbar_wait(bar + 8 * B_CSF, 0); ld_cs(8); ld_cs(16); }
}

__device__ __forceinline__ void attn_phase(const Params& p, uint32_t sb, int layer, int rb, int hg, int wg, int w) {
  const int lane = opaque_tid() & 31;
  const int g = lane >> 2, t = lane & 3;
  const uint32_t bar = sb + SM_BAR;
  const int row0 = 64 * wg + 16 * w;
  const bool leader = (w == 0) && (lane == 0);
  float acc[96];
  float2 cs[24];
  if (layer) gemm_section<true>(acc, cs, sb, layer, wg, w, lane);
  else gemm_section<false>(acc, cs, sb, layer, wg, w, lane);
  ATS(41, 224);
  mbar_wait(bar + 8 * B_STF, layer);
  const uint32_t tag = 2 * lds32(sb + SM_EP) + layer + 1;
  const float2 st0 = lds64f(sb + SM_ST + (row0 + g) * 8), st1 = lds64f(sb + SM_ST + (row0 + g + 8) * 8);
  const float mean0 = st0.x, rstd0 = st0.y, mean1 = st1.x, rstd1 = st1.y;
  wg_wait<0>();
  if (threadIdx.x == 0) TS(2 + layer * 20 + 1);
  ATS(39, 224);
  if (leader) mbar_arrive(bar + 8 * B_QDONE);

  uint32_t fp[4][4], fl[4][4], fh[4][4], qa[4][4];
  const int cw = 4 * wg + w;
  {
    const float nm0 = -mean0 * rstd0, nm1 = -mean1 * rstd1;
    const uint32_t kvx = sb + SM_KVX + cw * 2048 + lane * 16;
#pragma unroll
    for (int h = 0; h < 4; h++)
#pragma unroll
      for (int k = 0; k < 4; k++) {
        const int j = 8 + (k >> 1) * 8 + 2 * h + (k & 1);
        fh[h][k] = packbf(fmaf(acc[4 * j + 2], rstd1, nm1 * cs[j].x), fmaf(acc[4 * j + 3], rstd1, nm1 * cs[j].y));
      }
    if (cw == 7) {
      uint4* halo = &g_halo[(rb * 8 + hg) * 192];
#pragma unroll
      for (int h = 0; h < 4; h++) {
        st_tagged3(halo + h * 48 + lane, fh[h][0], fh[h][1], fh[h][2], tag);
        asm volatile("st.relaxed.gpu.global.v2.u32 [%0], {%1,%2};" ::"l"((uint2*)(halo + h * 48 + 32) + lane), "r"(fh[h][3]), "r"(tag) : "memory");
      }
      if (elect_one()) mbar_arrive(bar + 8 * B_SD);
      if (layer == TLAYER && threadIdx.x == 224) TS(47);
    }
#pragma unroll
    for (int h = 0; h < 4; h++) { fh[h][2] = movm_t(fh[h][2]); fh[h][3] = movm_t(fh[h][3]); }
    if (cw != 7) {
#pragma unroll
      for (int h = 0; h < 4; h++) sts128(kvx + 2048 + h * 512, make_uint4(fh[h][0], fh[h][1], fh[h][2], fh[h][3]));
      bar_arrive(8 + cw, 64);
    }
    sched_fence<6>();
    if (layer == TLAYER && threadIdx.x == 0) TS(45);
#pragma unroll
    for (int j = 0; j < 8; j++) cs[j] = lds64f(sb + SM_CS + 4 * (8 * j + 2 * t));
#pragma unroll
    for (int h = 0; h < 4; h++)
#pragma unroll
      for (int k = 0; k < 4; k++) {
        const int j = 8 + (k >> 1) * 8 + 2 * h + (k & 1);
        fl[h][k] = packbf(fmaf(acc[4 * j], rstd0, nm0 * cs[j].x), fmaf(acc[4 * j + 1], rstd0, nm0 * cs[j].y));
        if (k >= 2) fl[h][k] = movm_t(fl[h][k]);
      }
#pragma unroll
    for (int h = 0; h < 4; h++) {
#pragma unroll
      for (int dh = 0; dh < 2; dh++) {
        const int j = 2 * h + dh;
        const float2 c2 = cs[j];
        qa[h][2 * dh] = packbf(fmaf(-mean0, c2.x, acc[4 * j + 0]), fmaf(-mean0, c2.y, acc[4 * j + 1]));
        qa[h][2 * dh + 1] = packbf(fmaf(-mean1, c2.x, acc[4 * j + 2]), fmaf(-mean1, c2.y, acc[4 * j + 3]));
      }
    }
    if (threadIdx.x == 0) TS(2 + layer * 20 + 2);
    sched_fence<0>();
    bar_sync(7 + cw, cw == 0 && !HALO_W14 ? 160 : 64);
#pragma unroll
    for (int h = 0; h < 4; h++) {
      const uint4 v = lds128(kvx + h * 512);
      fp[h][0] = v.x; fp[h][1] = v.y; fp[h][2] = v.z; fp[h][3] = v.w;
    }
    if (threadIdx.x == 0) TS(2 + layer * 20 + 4);
  }

  const bool u0 = 2 * t > g, u1 = 2 * t + 1 > g;
  const uint32_t mU = (u0 ? 0x0000ffffu : 0u) | (u1 ? 0xffff0000u : 0u);
  const float cl2 = 0.25f * 1.4426950408889634f;
  const float sc0 = rstd0 * cl2, sc1 = rstd1 * cl2;
  const float cneg = ((rb & 7) == 0 && cw == 0) ? -INFINITY : 0.f;
  float v[4][4];
#pragma unroll
  for (int h = 0; h < 4; h++) {
    float T0[4] = {cneg, cneg, cneg, cneg}, T1[4] = {0.f, 0.f, 0.f, 0.f}, T2[4] = {0.f, 0.f, 0.f, 0.f};
    mma_bf16(T1, qa[h], fl[h][0], fl[h][1]);
    mma_bf16(T2, qa[h], fh[h][0], fh[h][1]);
    mma_bf16(T0, qa[h], fp[h][0], fp[h][1]);
    v[h][0] = u0 ? T0[0] : T1[0]; v[h][1] = u1 ? T0[1] : T1[1];
    v[h][2] = u0 ? T1[2] : T2[2]; v[h][3] = u1 ? T1[3] : T2[3];
  }
  float m0[4], m1[4];
#pragma unroll
  for (int h = 0; h < 4; h++) { m0[h] = fmaxf(v[h][0], v[h][1]); m1[h] = fmaxf(v[h][2], v[h][3]); }
#pragma unroll
  for (int o = 1; o <= 2; o <<= 1) {
#pragma unroll
    for (int h = 0; h < 4; h++) {
      m0[h] = fmaxf(m0[h], __shfl_xor_sync(~0u, m0[h], o));
      m1[h] = fmaxf(m1[h], __shfl_xor_sync(~0u, m1[h], o));
    }
  }
  float O0[4][4], O1[4][4], Z[4][4];
#pragma unroll
  for (int h = 0; h < 4; h++) {
    const float mm0 = -m0[h] * sc0, mm1 = -m1[h] * sc1;
    const uint32_t P0 = packbf(ex2(fmaf(v[h][0], sc0, mm0)), ex2(fmaf(v[h][1], sc0, mm0)));
    const uint32_t P1 = packbf(ex2(fmaf(v[h][2], sc1, mm1)), ex2(fmaf(v[h][3], sc1, mm1)));
#pragma unroll
    for (int k = 0; k < 4; k++) O0[h][k] = O1[h][k] = Z[h][k] = 0.f;
    mma_bf16_k8(Z[h], P0, P1, 0x3f803f80u);
    mma_bf16_k8(O0[h], P0 & ~mU, P1 & mU, fl[h][2]); mma_bf16_k8(O1[h], P0 & ~mU, P1 & mU, fl[h][3]);
    mma_bf16_k8(O0[h], P0 & mU, 0u, fp[h][2]); mma_bf16_k8(O1[h], P0 & mU, 0u, fp[h][3]);
    mma_bf16_k8(O0[h], 0u, P1 & ~mU, fh[h][2]); mma_bf16_k8(O1[h], 0u, P1 & ~mU, fh[h][3]);
  }
  const uint32_t ob = sb + SM_OST + wg * 8192;
  const int o_row = 16 * w + (lane & 7) + 8 * ((lane >> 3) & 1);
#pragma unroll
  for (int h = 0; h < 4; h++) {
    const float i0 = rcp_approx(Z[h][0]), i1 = rcp_approx(Z[h][2]);
    const int ch = 2 * h + (lane >> 4);
    stsm4(ob + o_row * 128 + ((ch ^ (o_row & 7)) << 4), packbf(O0[h][0] * i0, O0[h][1] * i0), packbf(O0[h][2] * i1, O0[h][3] * i1),
          packbf(O1[h][0] * i0, O1[h][1] * i0), packbf(O1[h][2] * i1, O1[h][3] * i1));
  }
  if (threadIdx.x == 0) TS(2 + layer * 20 + 5);
  ATS(57, 128); ATS(20, 96);
  bar_sync(2 + wg, 128);
  if (w == 0 && elect_one()) {
    fence_async_smem();
    tma_st(&p.mapO, hg * 64, rb * 128 + wg * 64, ob);
    bulk_commit();
    mbar_arrive(bar + 8 * B_AD);
    bulk_wait_all();
    red_relaxed(&g_cnt[(C_O + rb) * 32]);
    mbar_arrive(bar + 8 * B_OST);
    if (threadIdx.x == 0) TS(2 + layer * 20 + 6);
  }
  __syncwarp();
}

__device__ __forceinline__ void proj_phase(const Params& p, uint32_t sb, int layer, int rb, int q, int wg, int w) {
  const int lane = opaque_tid() & 31;
  const bool TR = layer != 0;
  const int t = lane & 3;
  const uint32_t bar = sb + SM_BAR;
  const uint32_t rbx = sb + SM_R + wg * 8192;
  uint32_t res[16];
  mbar_wait(bar + 8 * B_RF, layer);
  if (threadIdx.x == 0) TS(2 + layer * 20 + 7);
  if (!TR) {
#pragma unroll
    for (int j = 0; j < 8; j += 2) {
      const int mi = lane >> 3;
      const int row = 16 * w + (lane & 7) + 8 * (mi & 1), ch = j + (mi >> 1);
      ldsm4(&res[2 * j], rbx + row * 128 + ((ch ^ (row & 7)) << 4));
    }
  } else {
#pragma unroll
    for (int j = 0; j < 8; j += 2) {
      const int mi = lane >> 3;
      const int line = 8 * (j + (mi >> 1)) + (lane & 7), pc = 2 * w + (mi & 1);
      ldsm4t(&res[2 * j], rbx + line * 128 + ((pc ^ (line & 7)) << 4));
    }
  }
  bar_sync(2 + wg, 128);
  float acc[32];
#pragma unroll
  for (int i = 0; i < 16; i++) {
    asm volatile("shl.b32 %0, %1, 16;" : "=f"(acc[2 * i]) : "r"(res[i]));
    asm volatile("and.b32 %0, %1, 0xffff0000;" : "=f"(acc[2 * i + 1]) : "r"(res[i]));
  }
  const uint32_t tag = part_tag(lds32(sb + SM_EP), 2 * layer + 1);
  mbar_wait(bar + 8 * B_ZF, layer);
  mbar_wait(bar + 8 * B_WOF, layer);
#pragma unroll P_UNROLL
  for (int c = 0; c < 8; c++) {
    mbar_wait(bar + 8 * (B_OF + c), layer);
    if (c == 0 && threadIdx.x == 0) TS(2 + layer * 20 + 8);
    const uint64_t da = mkdesc(sb + sm_o(c) + wg * 8192, 16, 1024, 1);
    const uint64_t db = mkdesc(sb + SM_WO + c * 8192, 8192, 1024, 1);
    wg_fence();
#pragma unroll
    for (int ks = 0; ks < 4; ks++) wgmma_ss<64, 0, 1>(acc, da + ks * 2, db + ks * 128, 1);
    wg_commit();
  }
  wg_wait<0>();
#pragma unroll
  for (int i = 0; i < 32; i++) asm volatile("" : "+f"(acc[i]) :: "memory");
  if (threadIdx.x == 0) TS(2 + layer * 20 + 9);
  if (lane == 0 && w == 0) mbar_arrive(bar + 8 * B_PDONE);
  {
    float s[4], qq[4];
#pragma unroll
    for (int k = 0; k < 4; k++) { s[k] = acc[k]; qq[k] = acc[k] * acc[k]; }
#pragma unroll
    for (int j = 1; j < 8; j++)
#pragma unroll
      for (int k = 0; k < 4; k++) { s[k] += acc[4 * j + k]; qq[k] = fmaf(acc[4 * j + k], acc[4 * j + k], qq[k]); }
    const float s0 = s[0] + s[1], s1 = s[2] + s[3], q0 = qq[0] + qq[1], q1 = qq[2] + qq[3];
    float sr = ((t & 1) ? s1 : s0) + __shfl_xor_sync(~0u, (t & 1) ? s0 : s1, 1);
    float qr = ((t & 1) ? q1 : q0) + __shfl_xor_sync(~0u, (t & 1) ? q0 : q1, 1);
    sr += __shfl_xor_sync(~0u, sr, 2);
    qr += __shfl_xor_sync(~0u, qr, 2);
    if (t < 2) st_part(&g_part[(rb * 8 + q) * 128 + 64 * wg + 16 * w + (lane >> 2) + 8 * t], sr, qr, tag);
    __syncwarp();
    if (elect_one()) mbar_arrive(bar + 8 * B_PS);
    sched_fence<7>();
  }
#pragma unroll
  for (int j = 0; j < 8; j += 2) {
    const int mi = lane >> 3;
    const int line = 8 * (j + (mi >> 1)) + (lane & 7), pc = 2 * w + (mi & 1);
    stsm4t(rbx + line * 128 + ((pc ^ (line & 7)) << 4), packbf(acc[4 * j], acc[4 * j + 1]), packbf(acc[4 * j + 2], acc[4 * j + 3]),
           packbf(acc[4 * j + 4], acc[4 * j + 5]), packbf(acc[4 * j + 6], acc[4 * j + 7]));
  }
  fence_writer();
  bar_sync(2 + wg, 128);
  if (w == 0 && elect_one()) {
    fence_reader();
    fence_async_global();
    tma_st(&p.mapXT, rb * 128 + wg * 64, (2 * layer) * DM + q * 64, rbx);
    bulk_commit();
    if (threadIdx.x == 0) TS(2 + layer * 20 + 10);
    bulk_wait_all();
    red_relaxed(&g_cnt[C_CS * 32 + 2 + layer]);
    if (wg == 0) mbar_arrive(bar + 8 * B_RE);
  }
  __syncwarp();
}
__device__ __forceinline__ void proj_stats(uint32_t sb, int layer, int rb, int q, int lane, uint32_t tag) {
  const int r = 16 * q + (lane & 15);
  const uint2* src = &g_part[rb * 8 * 128 + r];
  uint2* dst = (uint2*)g_stats + ((layer * 32 + rb * 2 + (r >> 6)) * 32 + ((r & 7) >> 1) * 8 + ((r >> 3) & 7)) * 2 + (r & 1);
  mbar_wait(sb + SM_BAR + 8 * B_PS, layer);
  delay<D_PST>();
  for (int it = 0;; it++) {
    uint2 v[8];
#pragma unroll
    for (int i = 0; i < 8; i++) v[i] = ld_part(src + i * 128);
    float s[4], qq[4];
    uint32_t bad = 0;
#pragma unroll
    for (int i = 0; i < 4; i++) {
      s[i] = __uint_as_float(v[i].x) + __uint_as_float(v[i + 4].x);
      qq[i] = __uint_as_float(v[i].y) + __uint_as_float(v[i + 4].y);
      bad |= (v[i].y ^ tag) | (v[i + 4].y ^ tag);
    }
    const float mean = ((s[0] + s[1]) + (s[2] + s[3])) * (1.f / DM);
    const float rstd = rsqrt_approx(fmaxf(fmaf((qq[0] + qq[1]) + (qq[2] + qq[3]), 1.f / DM, -mean * mean), 0.f) + 1e-5f);
    const bool ok = __all_sync(~0u, (bad & 7u) == 0);
    if (ok && lane < 16)
      asm volatile("st.relaxed.gpu.global.v2.u32 [%0], {%1,%2};" ::"l"(dst), "r"(__float_as_uint(-mean * rstd)), "r"(__float_as_uint(rstd) | 1u) : "memory");
    if (ok) break;
    if (it > (1 << 22)) __trap();
  }
}

#define NA 14
#define NP 15
template <int M0, int M1> __device__ __forceinline__ void conv_load(uint32_t* A, uint32_t pe) {
#pragma unroll
  for (int m = M0; m < M1; m++) {
    asm volatile("ld.shared.v2.b32 {%0,%1}, [%2];" : "=r"(A[4 * m]), "=r"(A[4 * m + 1]) : "r"(pe + 256 * m) : "memory");
    A[4 * m + 2] = lds32(pe + 256 * m - 4);
  }
}
__device__ __forceinline__ uint32_t copy_reg(uint32_t v, uint32_t zero) { uint32_t r; asm volatile("or.b32 %0, %1, %2;" : "=r"(r) : "r"(v), "r"(zero)); return r; }
__device__ __forceinline__ uint32_t copy_reg2(uint32_t v, uint32_t zero) { uint32_t r; asm volatile("xor.b32 %0, %1, %2;" : "=r"(r) : "r"(v), "r"(zero)); return r; }
__device__ __forceinline__ void conv_park(uint32_t* P, uint32_t pe) {
#pragma unroll
  for (int m = 0; m < NP; m++)
#pragma unroll
    for (int k = 0; k < 3; k++) P[3 * m + k] = lds32(pe + 256 * m - 4 + 4 * k);
}
__device__ __forceinline__ void conv_unpark(uint32_t* A, const uint32_t* P, uint32_t zero) {
#pragma unroll
  for (int m = 0; m < NP; m++) {
    A[4 * m + 2] = copy_reg(P[3 * m], zero); A[4 * m] = copy_reg(P[3 * m + 1], zero);
    A[4 * m + 3] = copy_reg2(P[3 * m + 1], zero); A[4 * m + 1] = copy_reg(P[3 * m + 2], zero);
  }
}
template <int M0, int M1> __device__ __forceinline__ void conv_mmas(float* acc, const uint32_t* A, uint64_t d) {
  if constexpr (M0 < M1) {
    wgmma_rs<128 - 8 * (M0 / 2), 0>(acc, A + 4 * M0, d + (uint64_t)(4 * M0), M0 != 0);
    conv_mmas<M0 + 1, M1>(acc, A, d);
  }
}
struct SumAddr { uint32_t l0, l1, l2, se, so; };
__device__ __forceinline__ SumAddr conv_sum_addr(uint32_t sb, int c) {
  auto ua = [&](int j) { return sb + cv_u(0) + (127 - (j >> 3)) * 16 + (j & 7) * 2; };
  auto sa = [&](int hc) { const int ci = hc & ~1; return sb + cv_s(0) + ((ci >> 3) & 1) * 1024 + (ci >> 4) * 128 + (((ci ^ (ci >> 4)) & 7) << 4) + (hc & 1) * 8; };
  const int j0 = 4 * (c - 1);
  return {ua(j0 - 2), ua(j0), ua(j0 + 4), sa((c + 1) & 127), sa(c) + 2048};
}
__device__ __forceinline__ void sts64(uint32_t a, uint32_t x, uint32_t y) { asm volatile("st.shared.v2.b32 [%0], {%1,%2};" ::"r"(a), "r"(x), "r"(y) : "memory"); }
__device__ __forceinline__ void conv_sums(const SumAddr& sa, int lc, int c) {
  uint32_t e[4], o[4];
  {
    const float2 em = lds64f(sa.l1 + lc * 32768), om = lds64f(sa.l1 + lc * 32768 + CV_UH);
    e[0] = lds32(sa.l0 + lc * 32768); o[0] = lds32(sa.l0 + lc * 32768 + CV_UH);
    e[3] = lds32(sa.l2 + lc * 32768); o[3] = lds32(sa.l2 + lc * 32768 + CV_UH);
    e[1] = __float_as_uint(em.x); e[2] = __float_as_uint(em.y); o[1] = __float_as_uint(om.x); o[2] = __float_as_uint(om.y);
  }
  uint32_t s7e[2], s7o[2], s9e[2], s9o[2];
  uint32_t pw[4], sh[3];
#pragma unroll
  for (int k = 0; k < 4; k++) pw[k] = hadd2(e[k], o[k]);
#pragma unroll
  for (int k = 0; k < 3; k++) sh[k] = __byte_perm(pw[k], pw[k + 1], 0x5432);
#pragma unroll
  for (int k = 0; k < 2; k++) {
    const uint32_t t3 = hadd2(hadd2(sh[k], sh[k + 1]), pw[k + 1]);
    s7e[k] = hadd2(t3, o[k]); s7o[k] = hadd2(t3, e[k + 2]);
    s9e[k] = hadd2(s7o[k], pw[k]); s9o[k] = hadd2(s7e[k], pw[k + 2]);
  }
  if (c == 127) s9e[0] = s9e[1] = s9o[0] = s9o[1] = 0u;
  sts64(sa.se + lc * 32768, s9e[0], s9e[1]); sts64((sa.se ^ 16) + lc * 32768, s9o[0], s9o[1]);
  sts64(sa.so + lc * 32768, s7e[0], s7e[1]); sts64((sa.so ^ 16) + lc * 32768, s7o[0], s7o[1]);
}

__device__ __forceinline__ void conv_epi(uint32_t sb, int layer, int cta, int ch, int c0, uint4 x0, uint4 x1) {
  uint4 v[2][4];
  const uint4 xr[2] = {x0, x1};
  mbar_wait(sb + SM_BAR + 8 * (B_P + ch), layer);
#pragma unroll
  for (int u = 0; u < 2; u++) {
    const uint32_t pb = sb + cv_pb(ch) + u * (CV_PBW / 2) + c0 * 16;
#pragma unroll
    for (int k = 0; k < 4; k++) v[u][k] = lds128(pb + k * CV_PBW);
  }
#pragma unroll
  for (int u = 0; u < 2; u++) {
    uint4 o;
    o.x = hadd2(xr[u].x, hadd2(hadd2(v[u][0].x, v[u][1].x), hadd2(v[u][2].x, v[u][3].x)));
    o.y = hadd2(xr[u].y, hadd2(hadd2(v[u][0].y, v[u][1].y), hadd2(v[u][2].y, v[u][3].y)));
    o.z = hadd2(xr[u].z, hadd2(hadd2(v[u][0].z, v[u][1].z), hadd2(v[u][2].z, v[u][3].z)));
    o.w = hadd2(xr[u].w, hadd2(hadd2(v[u][0].w, v[u][1].w), hadd2(v[u][2].w, v[u][3].w)));
    if (layer == 0) sts128(sb + cv_s(ch) + (c0 + 128 * u) * 16, o);
    else st_tagged3((uint4*)(g_xT + (size_t)(3 * DM + cv_chan(cta, ch)) * LSEQ) + c0 + 128 * u, o.x, o.y, o.z, o.w);
  }
}
__device__ __forceinline__ void warp_release(uint32_t b) {
  fence_writer();
  __syncwarp();
  if (elect_one()) mbar_arrive(b);
}

__device__ __forceinline__ void conv_prep_load(uint32_t sb, int layer, int cta, int c, uint4 (&xr)[4], uint4 (&st)[4]) {
  sched_fence<8>();
  mbar_wait(sb + SM_BAR + 8 * B_GB, layer);
  if (threadIdx.x == 0) TS(2 + layer * 20 + 11);
  xr[0] = ld_tagged((const uint4*)(g_xT + (size_t)(2 * layer * DM + cta) * LSEQ) + c);
#pragma unroll
  for (int i = 0; i < 4; i++) st[i] = ld_tagged((const uint4*)g_stats + (layer * 32 + (c >> 3)) * 32 + i * 8 + (c & 7));
}
template <bool HELPER>
__device__ __forceinline__ void conv_prep(uint32_t sb, int layer, int cta, int c, uint4 (&xr)[4], uint4 (&st)[4], const SumAddr& sa) {
  const uint32_t bar = sb + SM_BAR;
  const uint4* xin = (const uint4*)(g_xT + (size_t)(2 * layer * DM + cta) * LSEQ) + c;
  for (int it = 0;; it++) {
    uint32_t vs;
    asm("{\n.reg .b32 t, u, v;\nlop3.b32 t, %1, %2, %3, 0x80;\nlop3.b32 u, %4, %5, %6, 0x80;\nlop3.b32 v, %7, %8, 1, 0x80;\nlop3.b32 %0, t, u, v, 0x80;\n}"
        : "=r"(vs) : "r"(st[0].y), "r"(st[0].w), "r"(st[1].y), "r"(st[1].w), "r"(st[2].y), "r"(st[2].w), "r"(st[3].y), "r"(st[3].w));
    if (__all_sync(~0u, vs != 0 && xr[0].x != ~0u)) break;
    if (it > (1 << 22)) __trap();
    if (!__all_sync(~0u, xr[0].x != ~0u)) xr[0] = ld_tagged(xin);
    if (!__all_sync(~0u, vs != 0)) {
#pragma unroll
      for (int i = 0; i < 4; i++) st[i] = ld_tagged((const uint4*)g_stats + (layer * 32 + (c >> 3)) * 32 + i * 8 + (c & 7));
    }
  }
  if (threadIdx.x == 0) TS(2 + layer * 20 + 12);
  const int a = c & 127, h = c >> 7;
#pragma unroll
  for (int i = 0; i < 4; i++) {
    if (i == 1) {
      mbar_wait(bar + 8 * B_XV, layer);
#pragma unroll
      for (int j = 1; j < 4; j++) xr[j] = ld_tagged(xin + j * (128 * LSEQ / 8));
      if (HELPER) {
        mbar_wait(bar + 8 * B_U, layer);
        conv_sums(sa, 0, c);
        fence_async_smem();
        bar_arrive(7, 256);
        sched_fence<1>();
        if (layer == 1 && c == 0) TS(46);
      }
    }
    const uint32_t x[4] = {xr[i].x, xr[i].y, xr[i].z, xr[i].w};
    uint32_t u[4];
#pragma unroll
    for (int k = 0; k < 4; k++)
      u[k] = packbf(fmaf(bf_lo(x[k]), __uint_as_float(st[k].y), __uint_as_float(st[k].x)), fmaf(bf_hi(x[k]), __uint_as_float(st[k].w), __uint_as_float(st[k].z)));
    sts128(sb + cv_u(i) + h * CV_UH + (127 - a) * 16, make_uint4(u[0], u[1], u[2], u[3]));
    warp_release(bar + 8 * (B_U + i));
    sched_fence<2>();
  }
}
__device__ __forceinline__ void conv_zero(uint32_t sb, int ht) {
  if (ht < 96) {
    const int ch = ht / 24, h2 = (ht / 12) & 1, qq = ht % 12;
    sts128(sb + cv_u(ch) + h2 * CV_UH + (128 + qq) * 16, make_uint4(0, 0, 0, 0));
  }
  if (ht >= 80) {
    const int i = ht - 80, ch = i / 12, q2 = i % 12;
    const int w2 = q2 < 2 ? 1 : q2 < 6 ? 2 : 3, cc = q2 < 2 ? q2 : q2 < 6 ? q2 - 2 : q2 - 6;
    sts128(sb + cv_pb(ch) + w2 * CV_PBW + (cc & 1) * (CV_PBW / 2) + (cc >> 1) * 16, make_uint4(0, 0, 0, 0));
  }
}

#define HANDOVER 1
template <int R>
__device__ __forceinline__ void conv_round(uint32_t sb, int layer, int wg, uint32_t* A, const uint32_t* P, uint32_t pb, uint32_t pe2) {
  const uint32_t bar = sb + SM_BAR;
  const int ch = 2 * R + 1 - wg;
  float acc[64];
  const uint64_t d = mkdesc(sb + cv_u(ch), CV_UH, 128, 0);
  FTS(39);
  if (R == 0) {
    mbar_wait(bar + 8 * (B_U + ch), layer);
    fence_reader();
  }
  sched_fence<3>();
  if (R == 1 || wg == 0) bar_sync(10 + ch, 256);
  if (layer == 0 && ch > 0 && ((PAUSE >> (ch - 1)) & 1)) mbar_wait(bar + 8 * (B_E + ch - 1), 0);
  if (layer == 0 && ch > 0 && ((PAUSE >> (ch + 3)) & 1)) mbar_wait(bar + 8 * (B_P + ch - 1), 0);
  FTS(41);
  if (ch == 0 && threadIdx.x == 128) TS(2 + layer * 20 + 13);
  wg_fence();
  conv_mmas<0, 1>(acc, A, d); conv_mmas<2, NA + 1>(acc, A, d);
  wg_commit();
  FTS(51);
  if (HANDOVER == 0 && (R == 0 || wg == 1)) bar_arrive(11 + ch, 256);
  bar_sync(7 + ch, 256);
  wg_fence();
  conv_mmas<1, 2>(acc, A, d); conv_mmas<NA + 1, 17>(acc, A, d);
  wgmma_ss<64, 1, 1>(acc, mkdesc(sb + cv_s(ch), 1024, 1024, 1), mkdesc(sb + cv_ft(ch), 256, 16, 0), 1);
  wgmma_ss<64, 1, 1>(acc, mkdesc(sb + cv_s(ch) + 2048, 1024, 1024, 1), mkdesc(sb + cv_ft(ch) + 512, 256, 16, 0), 1);
  wg_commit();
  if (HANDOVER == 1 && (R == 0 || wg == 1)) bar_arrive(11 + ch, 256);
  FTS(61);
  wg_wait<0>();
#pragma unroll
  for (int j = 0; j < 16; j += 2)
    stsm4t(pb + R * 65536 - j * 128, packbf(acc[4 * j], acc[4 * j + 1]), packbf(acc[4 * j + 2], acc[4 * j + 3]),
           packbf(acc[4 * j + 4], acc[4 * j + 5]), packbf(acc[4 * j + 6], acc[4 * j + 7]));
  __syncwarp();
  if (elect_one()) mbar_arrive(bar + 8 * (B_P + ch));
  if (threadIdx.x == 0) TS(2 + layer * 20 + 14 + R);
  FTS(57);
  if (R == 0) {
    conv_unpark(A, P, opaque_tid() >> 10);
    mbar_wait(bar + 8 * (B_U + ch + 2), layer);
    fence_reader();
    conv_load<NP, 17>(A, pe2);
#pragma unroll
    for (int m = NP; m < 17; m++) A[4 * m + 3] = lds32(pe2 + 256 * m);
  }
}
__device__ __forceinline__ void conv_phase(const Params& p, uint32_t sb, int layer, int cta) {
  const int tid = opaque_tid();
  const int wg = __shfl_sync(~0u, tid >> 7, 0), w = __shfl_sync(~0u, (tid >> 5) & 3, 0);
  const uint32_t bar = sb + SM_BAR;
  uint32_t A[68], P[3 * NP];
  const uint32_t pe = sb + cv_pe(1 - wg) + 4 * (16 + 16 * w + 2 * ((tid & 31) >> 2) - 4 * (tid & 3));
  mbar_wait(bar + 8 * B_PE, layer);
  conv_load<0, 17>(A, pe);
#pragma unroll
  for (int m = 0; m < 17; m++) A[4 * m + 3] = copy_reg(A[4 * m], tid >> 10);
  if (wg == 0) {
    uint4 xr[4], st[4];
    if (PARK_FIRST) conv_park(P, pe + 65536);
    conv_prep_load(sb, layer, cta, tid + 128, xr, st);
    if (!PARK_FIRST) conv_park(P, pe + 65536);
    conv_prep<false>(sb, layer, cta, opaque_tid() + 128, xr, st, SumAddr());
  } else {
    conv_park(P, pe + 65536);
  }
  uint32_t pb;
  {
    const int l2 = opaque_tid() & 31, mt = l2 >> 3;
    pb = sb + cv_pb(1 - wg) + w * CV_PBW + (mt & 1) * (CV_PBW / 2) + (127 - 8 * (mt >> 1) - (l2 & 7) + w) * 16;
  }
  conv_round<0>(sb, layer, wg, A, P, pb, pe + 65536);
  conv_round<1>(sb, layer, wg, A, P, pb, 0);
  if (G_WAIT == 1 && layer == 0) mbar_wait(bar + 8 * (B_E + 3), layer);
  if (G_WAIT == 2 && layer == 0) mbar_wait(bar + 8 * (B_P + 3), layer);
}

__device__ __forceinline__ void final_phase(const Params& p, uint32_t sb, int cta, int wg, int w) {
  if (wg == 1 && w == 3) return;
  const int lane = opaque_tid() & 31, g = lane >> 2, t = lane & 3;
  const int lc = wg ? w : 3;
  const int pos0 = (cta & 31) * 64, ch0 = 128 * lc + (cta >> 5) * 32;
  const bf16* src = g_xT + (size_t)(3 * DM + ch0 + 8 * (g >> 1) + (g & 1)) * LSEQ + pos0;
  bf16* dst = p.out + (size_t)(2 * (pos0 & 1023) + (pos0 >> 10)) * DM + ch0 + 8 * t;
  constexpr int RS = 2 * DM;
  int it = 0;
  mbar_wait(sb + SM_BAR + 8 * (B_E + lc), 1);
  delay<D_FIN>();
  if (wg == 0) {
    uint2 v[4];
    for (;;) {
#pragma unroll
      for (int q = 0; q < 4; q++) v[q] = ld_part((const uint2*)(src + 2 * q * LSEQ + 16 * w + 4 * t));
      if (__all_sync(~0u, max(max(v[0].x, v[1].x), max(v[2].x, v[3].x)) != ~0u)) break;
      if (++it > (1 << 22)) __trap();
    }
    if (threadIdx.x == 0) TS(42);
    dst += (16 * w + 4 * (g >> 1) + (g & 1)) * RS;
    *(uint4*)dst = make_uint4(movm_t(v[0].x), movm_t(v[1].x), movm_t(v[2].x), movm_t(v[3].x));
    *(uint4*)(dst + 2 * RS) = make_uint4(movm_t(v[0].y), movm_t(v[1].y), movm_t(v[2].y), movm_t(v[3].y));
  } else {
    uint4 v[2][4];
    bool ok;
    do {
      ok = true;
#pragma unroll
      for (int h = 0; h < 2; h++)
#pragma unroll
        for (int q = 0; q < 4; q++) v[h][q] = ld_tagged((const uint4*)(src + 2 * q * LSEQ + 32 * h + 8 * t));
#pragma unroll
      for (int h = 0; h < 2; h++)
#pragma unroll
        for (int q = 0; q < 4; q++) ok = ok && v[h][q].x != ~0u;
      if (++it > (1 << 22)) __trap();
    } while (!__all_sync(~0u, ok));
    dst += (8 * (g >> 1) + (g & 1)) * RS;
#pragma unroll
    for (int h = 0; h < 2; h++) {
      *(uint4*)(dst + (32 * h + 0) * RS) = make_uint4(movm_t(v[h][0].x), movm_t(v[h][1].x), movm_t(v[h][2].x), movm_t(v[h][3].x));
      *(uint4*)(dst + (32 * h + 2) * RS) = make_uint4(movm_t(v[h][0].y), movm_t(v[h][1].y), movm_t(v[h][2].y), movm_t(v[h][3].y));
      *(uint4*)(dst + (32 * h + 4) * RS) = make_uint4(movm_t(v[h][0].z), movm_t(v[h][1].z), movm_t(v[h][2].z), movm_t(v[h][3].z));
      *(uint4*)(dst + (32 * h + 6) * RS) = make_uint4(movm_t(v[h][0].w), movm_t(v[h][1].w), movm_t(v[h][2].w), movm_t(v[h][3].w));
    }
  }
  if (threadIdx.x == 0) TS(43);
  if (threadIdx.x == 192) TS(63);
  if (threadIdx.x == 0) LTS(1);
}

struct cplx { float r, i; };
__device__ __forceinline__ cplx cmul(cplx a, cplx b) { return {fmaf(a.r, b.r, -a.i * b.i), fmaf(a.r, b.i, a.i * b.r)}; }
__device__ __forceinline__ cplx csqr(cplx a) { return {fmaf(a.r, a.r, -a.i * a.i), (a.r + a.r) * a.i}; }
__device__ __forceinline__ cplx cexp_l(float ar2, float ai, float l) {
  const float m = ex2(ar2 * l);
  const float x = ai * l;
  return {m * __cosf(x), m * __sinf(x)};
}

__device__ __forceinline__ void colsum_publish(uint32_t sb, int rb, int hg, int ht, uint32_t tag) {
  const int lane = ht & 31, q = lane & 15, h = lane >> 4;
  const uint32_t src = sb + SM_CW + (ht >> 5) * 4096 + h * 128 + (q & 1) * 8;
  float s[4] = {0.f, 0.f, 0.f, 0.f};
#pragma unroll 8
  for (int r = 0; r < 16; r++) {
    const float2 v = lds64f(src + r * 256 + (((q >> 1) ^ ((2 * r + h) & 7)) << 4));
    s[0] += bf_lo(__float_as_uint(v.x)); s[1] += bf_hi(__float_as_uint(v.x));
    s[2] += bf_lo(__float_as_uint(v.y)); s[3] += bf_hi(__float_as_uint(v.y));
  }
#pragma unroll
  for (int k = 0; k < 4; k++) s[k] += __shfl_xor_sync(~0u, s[k], 16);
  if (h == 0)
    st_tagged3(&g_colsum[(hg * 16 + rb) * 48 + (ht >> 5) * 16 + q], (__float_as_uint(s[0]) & ~7u) | tag, __float_as_uint(s[1]),
               __float_as_uint(s[2]), __float_as_uint(s[3]));
}
__device__ __forceinline__ void colsum_gather(uint32_t sb, int hg, int ht, uint32_t tag) {
  const int lane = ht & 31, rec = (ht >> 5) * 16 + (lane & 15);
  const uint4* src = &g_colsum[(hg * 16 + (lane >> 4) * 8) * 48 + rec];
  float s[4] = {0.f, 0.f, 0.f, 0.f};
#pragma unroll 1
  for (int h = 0; h < 2; h++, src += 4 * 48) {
    uint4 v[4];
    int it = 0;
    do {
#pragma unroll
      for (int i = 0; i < 4; i++) v[i] = ld_tagged(src + i * 48);
      if (++it > (1 << 22)) __trap();
    } while (!__all_sync(~0u, (v[0].x & 7u) == tag && (v[1].x & 7u) == tag && (v[2].x & 7u) == tag && (v[3].x & 7u) == tag));
#pragma unroll
    for (int i = 0; i < 4; i++) {
      s[0] += __uint_as_float(v[i].x & ~7u); s[1] += __uint_as_float(v[i].y); s[2] += __uint_as_float(v[i].z); s[3] += __uint_as_float(v[i].w);
    }
  }
#pragma unroll
  for (int k = 0; k < 4; k++) s[k] += __shfl_xor_sync(~0u, s[k], 16);
  if (lane < 16) sts128f(sb + SM_CS + rec * 16, s[0], s[1], s[2], s[3]);
}

__device__ __forceinline__ uint32_t packh(float lo, float hi) { uint32_t r; asm("cvt.rn.f16x2.f32 %0, %1, %2;" : "=r"(r) : "f"(hi), "f"(lo)); return r; }
__device__ __forceinline__ void mma_f16(float* d, uint32_t a0, uint32_t a1, uint32_t a2, uint32_t a3, uint32_t b0, uint32_t b1) {
  asm volatile("mma.sync.aligned.m16n8k16.row.col.f32.f16.f16.f32 {%0,%1,%2,%3}, {%4,%5,%6,%7}, {%8,%9}, {%0,%1,%2,%3};"
      : "+f"(d[0]), "+f"(d[1]), "+f"(d[2]), "+f"(d[3]) : "r"(a0), "r"(a1), "r"(a2), "r"(a3), "r"(b0), "r"(b1));
}
struct HSeed { uint32_t r, i; };
__device__ __forceinline__ HSeed hseed(cplx s) { return {packh(s.r, s.r), packh(s.i, s.i)}; }
__device__ __forceinline__ void hcmul(uint32_t& o_r, uint32_t& o_i, uint32_t br, uint32_t bi, HSeed s) {
  asm("{\n.reg .b32 t, u;\nmul.rn.f16x2 t, %3, %5;\nneg.f16x2 t, t;\nmul.rn.f16x2 u, %3, %4;\nfma.rn.f16x2 %0, %2, %4, t;\nfma.rn.f16x2 %1, %2, %5, u;\n}"
      : "=&r"(o_r), "=&r"(o_i) : "r"(br), "r"(bi), "r"(s.r), "r"(s.i));
}
struct HTile { uint32_t r[4], i[4]; };
__device__ __forceinline__ void tile_set(HTile& t, int k, cplx a, cplx b) { t.r[k] = packh(a.r, b.r); t.i[k] = packh(a.i, b.i); }
__device__ __forceinline__ void tile_upper(HTile& t, HSeed s) { hcmul(t.r[2], t.i[2], t.r[0], t.i[0], s); hcmul(t.r[3], t.i[3], t.r[1], t.i[1], s); }
__device__ __forceinline__ HTile tile_shift(const HTile& t, HSeed s) {
  HTile o;
#pragma unroll
  for (int k = 0; k < 4; k++) hcmul(o.r[k], o.i[k], t.r[k], t.i[k], s);
  return o;
}
__device__ __forceinline__ void tile_put(const HTile& t, uint32_t a) {
  sts128(a, make_uint4(t.r[0], t.r[1], t.r[2], t.r[3]));
  sts128(a + 512, make_uint4(t.i[0], t.i[1], t.i[2], t.i[3]));
}
__device__ __forceinline__ HTile tile_get(uint32_t a) { HTile o; ldsm4t(o.r, a); ldsm4t(o.i, a + 512); return o; }
__device__ __forceinline__ void tile_mma(float* T, const HTile& a0, const HTile& a1, const HTile& b) {
  mma_f16(T, a0.r[0], a0.r[1], a0.r[2], a0.r[3], b.r[0], b.r[1]);
  mma_f16(T, a0.i[0], a0.i[1], a0.i[2], a0.i[3], b.i[0], b.i[1]);
  mma_f16(T, a1.r[0], a1.r[1], a1.r[2], a1.r[3], b.r[2], b.r[3]);
  mma_f16(T, a1.i[0], a1.i[1], a1.i[2], a1.i[3], b.i[2], b.i[3]);
}
__device__ __forceinline__ void tile_mma2(float* T, float* U, const HTile& a0, const HTile& a1, const HTile& b, const HTile& c) {
  mma_f16(T, a0.r[0], a0.r[1], a0.r[2], a0.r[3], b.r[0], b.r[1]);
  mma_f16(U, a0.r[0], a0.r[1], a0.r[2], a0.r[3], c.r[0], c.r[1]);
  mma_f16(T, a0.i[0], a0.i[1], a0.i[2], a0.i[3], b.i[0], b.i[1]);
  mma_f16(U, a0.i[0], a0.i[1], a0.i[2], a0.i[3], c.i[0], c.i[1]);
  mma_f16(T, a1.r[0], a1.r[1], a1.r[2], a1.r[3], b.r[2], b.r[3]);
  mma_f16(U, a1.r[0], a1.r[1], a1.r[2], a1.r[3], c.r[2], c.r[3]);
  mma_f16(T, a1.i[0], a1.i[1], a1.i[2], a1.i[3], b.i[2], b.i[3]);
  mma_f16(U, a1.i[0], a1.i[1], a1.i[2], a1.i[3], c.i[2], c.i[3]);
}
__device__ __forceinline__ void kgen_unit(uint32_t tab, uint32_t taba, float ar2, float ai, cplx c, float (&T)[5][4]) {
  const cplx z1 = cexp_l(ar2, ai, 1.f), z16 = cexp_l(ar2, ai, 16.f), z256 = cexp_l(ar2, ai, 256.f);
  HTile a0, a1, b0, b1;
  {
    const cplx y1 = {z16.r, -z16.i}, y2 = csqr(y1), y3 = cmul(y2, y1), y4 = csqr(y2), y5 = cmul(y4, y1), y6 = csqr(y3), y7 = cmul(y4, y3);
    HTile t;
    tile_set(t, 0, {1.f, 0.f}, y1); tile_set(t, 1, y2, y3); tile_set(t, 2, y4, y5); tile_set(t, 3, y6, y7);
    const HTile u = tile_shift(t, hseed(csqr(y4)));
    __syncwarp();
    tile_put(t, tab); tile_put(u, tab + 1024);
    __syncwarp();
    a0 = tile_get(taba); a1 = tile_get(taba + 256);
  }
  const cplx z2 = csqr(z1), z4 = csqr(z2), z8 = csqr(z4);
  const HSeed h8 = hseed(z8);
  const cplx d = cmul(c, z256), e = cmul(d, z256);
  {
    const cplx z512 = csqr(z256), f = cmul(e, z512), f8 = cmul(f, z8), f16 = cmul(f, z16), e4 = cmul(e, z4);
    HTile t, u;
    tile_set(t, 0, e4, cmul(e, z8)); tile_set(t, 1, cmul(e4, z8), cmul(e, z16));
    tile_upper(t, hseed(z256));
    tile_set(u, 0, f8, f16); tile_set(u, 1, cmul(f8, z256), cmul(f16, z256));
    tile_upper(u, hseed(z512));
    __syncwarp();
    tile_put(t, tab); tile_put(u, tab + 1024);
    __syncwarp();
    b0 = tile_get(tab); b1 = tile_get(tab + 1024);
  }
  {
    const cplx d2 = cmul(d, z2), d4 = cmul(d, z4);
    HTile t;
    tile_set(t, 0, d2, d4); tile_set(t, 1, cmul(d2, z4), cmul(d, z8));
    tile_upper(t, h8);
    __syncwarp();
    tile_put(t, tab);
    __syncwarp();
    tile_mma2(T[3], T[4], a0, a1, b0, b1);
    b0 = tile_get(tab);
  }
  {
    const cplx c1 = cmul(c, z1), c2 = cmul(c, z2), c3 = cmul(c1, z2), c4 = cmul(c, z4);
    HTile t;
    tile_set(t, 0, c1, c2); tile_set(t, 1, c3, c4); tile_set(t, 2, cmul(c1, z4), cmul(c2, z4)); tile_set(t, 3, cmul(c3, z4), cmul(c4, z4));
    const HTile u = tile_shift(t, h8);
    __syncwarp();
    tile_put(t, tab); tile_put(u, tab + 1024);
    __syncwarp();
    tile_mma(T[2], a0, a1, b0);
    b0 = tile_get(tab); b1 = tile_get(tab + 1024);
    tile_mma2(T[0], T[1], a0, a1, b0, b1);
  }
}
struct ModeIn { uint2 ar, ai, br, bi, cr, ci; };
__device__ __forceinline__ ModeIn load_modes(const Params& p, int idx) {
  return {*(const uint2*)(p.a_re + idx), *(const uint2*)(p.a_im + idx), *(const uint2*)(p.b_re + idx),
          *(const uint2*)(p.b_im + idx), *(const uint2*)(p.c_re + idx), *(const uint2*)(p.c_im + idx)};
}
__device__ __forceinline__ float bf_el(uint2 v, int k) { const uint32_t x = (k & 2) ? v.y : v.x; return (k & 1) ? bf_hi(x) : bf_lo(x); }
struct KGen { float4 cur; float T[5][4]; };
__device__ __forceinline__ uint32_t kgen_slot(uint32_t sb, int ht, int u) {
  return sb + (u < 3 ? SM_KC + (ht >> 5) * (KC_STRIDE * 2) + (u - 1) * 512 + (ht & 31) * 16 + 16 : SM_HALO + 1024 + ht * 16);
}
__device__ __forceinline__ void kgen_setup(KGen& s, uint32_t sb, int cta, int ht, const ModeIn& in, bf16 logdt, bf16 dskip) {
  const float dt = __bfloat162float(__float2bfloat16_rn(expf(__bfloat162float(logdt))));
  float mx = 0.f, k0 = 0.f, ar2[4];
  cplx c[4];
#pragma unroll
  for (int k = 0; k < 4; k++) {
    ar2[k] = (dt * bf_el(in.ar, k)) * 1.4426950408889634f;
    c[k] = cmul({bf_el(in.cr, k), bf_el(in.ci, k)}, {dt * bf_el(in.br, k), dt * bf_el(in.bi, k)});
    k0 += c[k].r;
    mx = fmaxf(mx, fmaxf(fabsf(c[k].r), fabsf(c[k].i)) * ex2(fmaxf(ar2[k] * 2048.f, 0.f)));
  }
  const int ex = min(max(267 - (int)(__reduce_max_sync(~0u, __float_as_uint(mx)) >> 23), 1), 253);
  const float sc = __uint_as_float(ex << 23);
#pragma unroll
  for (int o = 16; o > 0; o >>= 1) k0 += __shfl_xor_sync(~0u, k0, o);
  if ((ht & 31) == 0) {
    const uint32_t kc = sb + SM_KC + (ht >> 5) * (KC_STRIDE * 2);
    sts16(kc, __bfloat16_as_ushort(__float2bfloat16_rn(k0 + __bfloat162float(dskip))));
    sts16(kc + 641 * 2, 0);
    sts32f(kc + 644 * 2, __uint_as_float((254 - ex) << 23));
  }
  s.cur = make_float4(ar2[0], dt * bf_el(in.ai, 0), c[0].r * sc, c[0].i * sc);
#pragma unroll
  for (int k = 1; k < 4; k++) sts128f(kgen_slot(sb, ht, k), ar2[k], dt * bf_el(in.ai, k), c[k].r * sc, c[k].i * sc);
#pragma unroll
  for (int i = 0; i < 5; i++) s.T[i][0] = s.T[i][1] = s.T[i][2] = s.T[i][3] = 0.f;
}
__device__ __forceinline__ void kgen_finish(KGen& s, uint32_t sb, int cta, int ht) {
  const int w = ht >> 5, lane = ht & 31, g = lane >> 2, t = lane & 3;
  const uint32_t kc = sb + SM_KC + w * KC_STRIDE * 2;
  __syncwarp();
  const float inv = __uint_as_float(lds32(kc + 644 * 2));
  auto put = [&](int idx, float v) {
    sts16(kc + idx * 2, __bfloat16_as_ushort(__float2bfloat16_rn(v)));
  };
#pragma unroll
  for (int hi = 0; hi < 2; hi++)
#pragma unroll
    for (int lo = 0; lo < 2; lo++) {
      const int i = g + 8 * hi, j = 2 * t + lo, e = 2 * hi + lo;
      put(16 * i + 1 + j, s.T[0][e] * inv);
      put(16 * i + 9 + j, s.T[1][e] * inv);
      put(257 + 8 * i + j, s.T[2][e] * inv);
      put(385 + 4 * i + (j & 3) + 64 * (j >> 2), s.T[3][e] * inv);
      put(513 + 2 * i + lo + 32 * t, s.T[4][e] * inv);
    }
}

__device__ __forceinline__ void expand_taps(uint32_t sb, int ht) {
  const int ch = ht >> 5, lane = ht & 31;
  const uint32_t kc = sb + SM_KC + ch * KC_STRIDE * 2;
  const uint32_t dst0 = sb + cv_pe(ch);
  auto put = [&](int G, uint32_t u0, uint32_t u1, uint32_t v0, uint32_t v1, uint32_t v2, uint32_t v3, uint32_t v4, uint32_t v5, uint32_t v6, uint32_t v7) {
    const uint32_t dst = dst0 + G * 32;
    sts128(dst, make_uint4(v0 | (u0 << 16), v1 | (u1 << 16), v2 | (v0 << 16), v3 | (v1 << 16)));
    sts128(dst + 16, make_uint4(v4 | (v2 << 16), v5 | (v3 << 16), v6 | (v4 << 16), v7 | (v5 << 16)));
  };
  {
    const uint4 q = lds128(kc + lane * 16);
    const uint32_t pv = lane ? lds32(kc + lane * 16 - 4) : 0u;
    const uint32_t dst = dst0 + (lane + 2) * 32;
    sts128(dst, make_uint4(__byte_perm(q.x, pv, 0x5410), __byte_perm(q.x, pv, 0x7632), __byte_perm(q.y, q.x, 0x5410), __byte_perm(q.y, q.x, 0x7632)));
    sts128(dst + 16, make_uint4(__byte_perm(q.z, q.y, 0x5410), __byte_perm(q.z, q.y, 0x7632), __byte_perm(q.w, q.z, 0x5410), __byte_perm(q.w, q.z, 0x7632)));
    if (lane < 4) sts128(dst0 + lane * 16, make_uint4(0, 0, 0, 0));
  }
  uint32_t a[5], b[2][3], fv[4];
  {
    const uint32_t s1 = kc + 2 * (256 + 4 * lane);
#pragma unroll
    for (int k = 0; k < 5; k++) a[k] = lds16(s1 + 2 * k);
#pragma unroll
    for (int u = 0; u < 2; u++) {
      const uint32_t s2 = kc + 2 * (384 + 2 * (lane + 32 * u));
#pragma unroll
      for (int k = 0; k < 3; k++) b[u][k] = lds16(s2 + 2 * k);
    }
#pragma unroll
    for (int k = 0; k < 4; k++) fv[k] = lds16(kc + 2 * (640 - 4 * lane - k));
  }
  const uint32_t am1 = lds16(kc + 2 * (lane ? 256 + 4 * lane : 255)), am2 = lds16(kc + 2 * (lane ? 255 + 4 * lane : 254));
  const uint32_t bm2 = lds16(kc + 2 * (lane ? 384 + 2 * lane : 383)), k1024 = lds16(kc + 2 * 512);
  put(34 + lane, am2, am1, a[0], a[0], a[1], a[2], a[2], a[2], a[3], a[4]);
#pragma unroll
  for (int u = 0; u < 2; u++) put(66 + lane + 32 * u, u ? b[u][0] : bm2, b[u][0], b[u][0], b[u][0], b[u][0], b[u][1], b[u][1], b[u][1], b[u][2], b[u][2]);
  if (lane < 10) {
    const uint32_t v = lane == 0 ? k1024 : 0u;
    put(130 + lane, v, v, v, v, v, v, v, 0u, 0u, 0u);
  }
  const uint32_t ft = sb + cv_ft(ch) + 4 * lane;
#pragma unroll
  for (int ty = 0; ty < 2; ty++) {
    const uint32_t v = fv[ty] | (fv[ty + 2] << 16);
    sts32f(ft + ty * 512, __uint_as_float(v));
    sts32f(ft + ty * 512 + 128, 0.f);
    sts32f(ft + ty * 512 + 256 + (lane < 2 ? 120 : -8), __uint_as_float(lane < 2 ? 0u : v));
    sts32f(ft + ty * 512 + 384, 0.f);
  }
}

__device__ __forceinline__ int role_id() { int v; asm volatile("mov.u32 %0, %%ctaid.x;" : "=r"(v)); return v; }
#define GMAP 8
__device__ __forceinline__ int role_rb(int cta) { return 4 * (cta >> 5) + (cta & 3); }
__device__ __forceinline__ int role_hg(int cta) { return 2 * (((cta >> 3) & 3) ^ (((cta >> 5) & 1) * 3)) + ((cta >> 2) & 1); }
__device__ __forceinline__ int role_rb2(int cta) { return cta >> 3; }
__device__ __forceinline__ int role_q2(int cta) { return cta & 7; }

__global__ void __launch_bounds__(NTHREADS, 1) fused_kernel(const __grid_constant__ Params p) {
  extern __shared__ __align__(1024) uint8_t smem[];
  const uint32_t sb = s32(smem);
  const int tid = threadIdx.x, lane = tid & 31;
  const int warp = __shfl_sync(~0u, tid >> 5, 0);
  const uint32_t bar = sb + SM_BAR;
  if (tid == 0) TS(0);
  const int cta0 = role_id();
  if (warp == 0 && elect_one()) {
    const int rb = role_rb(cta0), hg = role_hg(cta0);
#pragma unroll
    for (int c = 0; c < 2; c++) { mbar_init(bar + 8 * (B_XF + c), 1); mbar_init(bar + 8 * (B_KVF + c), 1); }
    fence_async_smem();
#pragma unroll
    for (int c = 0; c < 2; c++) {
      mbar_expect(bar + 8 * (B_XF + c), 16384);
      tma_ld(sb + SM_X + c * 16384, &p.mapX128, (rb >> 3) * DM + c * 64, (rb & 7) * 128, bar + 8 * (B_XF + c));
      mbar_expect(bar + 8 * (B_KVF + c), 24576);
      tma_ld3(sb + SM_W + c * 24576, &p.mapW3, hg * 64, c * 64, 0, bar + 8 * (B_KVF + c));
    }
  }
  if (warp == 1 && elect_one()) {
    const int rb = role_rb(cta0), hg = role_hg(cta0);
#pragma unroll
    for (int c = 2; c < 8; c++) mbar_init(bar + 8 * (B_XF + c), 1);
    mbar_init(bar + 8 * (B_KVF + 2), 1); mbar_init(bar + 8 * B_CW, 1);
    fence_async_smem();
    delay<D_START>();
    mbar_expect(bar + 8 * B_CW, 12288);
    tma_ld3(sb + SM_CW, &p.mapW3h, hg * 64, rb * 32, 0, bar + 8 * B_CW);
#pragma unroll
    for (int c = 2; c < 8; c++) {
      mbar_expect(bar + 8 * (B_XF + c), 16384);
      tma_ld(sb + SM_X + c * 16384, &p.mapX128, (rb >> 3) * DM + c * 64, (rb & 7) * 128, bar + 8 * (B_XF + c));
      if (c < 3) {
        mbar_expect(bar + 8 * (B_KVF + c), 24576);
        tma_ld3(sb + SM_W + c * 24576, &p.mapW3, hg * 64, c * 64, 0, bar + 8 * (B_KVF + c));
      }
    }
    TS(56);
  }
  if ((warp & 2) != 0 && warp < 15 && elect_one()) {
    const int grp = 1 + (warp & 1) + 2 * (warp >> 2), cnt = grp < 4 ? 1 : grp < 5 ? 2 : grp < 7 ? 4 : 8;
#pragma unroll
    for (int k = 0; k < 10; k++)
      if (k != 0 || grp > 3 || grp == 2) mbar_init(bar + 8 * (10 * grp + k), cnt);
    fence_async_smem();
  }

  if (warp < 8) {
    if (tid == 0) TS(1);
    asm volatile("setmaxnreg.inc.sync.aligned.u32 %0;" ::"n"(R_CONS));
    const int cta = role_id();
    auto warp_id = [] { return __shfl_sync(~0u, opaque_tid() >> 5, 0); };
    if (tid == 0) TS(54);
#pragma unroll 1
    for (int layer = 0; layer < 2; layer++) {
      { const int cw = warp_id(); attn_phase(p, sb, layer, role_rb(cta), role_hg(cta), cw >> 2, cw & 3); }
      if (STOP == 1 + 3 * layer) return;
      { const int cw = warp_id(); proj_phase(p, sb, layer, role_rb2(cta), role_q2(cta), cw >> 2, cw & 3); }
      if (STOP == 2 + 3 * layer) return;
      conv_phase(p, sb, layer, cta);
      if (STOP == 3 + 3 * layer) return;
    }
    { const int cw = warp_id(); final_phase(p, sb, cta, cw >> 2, cw & 3); }
  } else if (warp < 12) {
    asm volatile("setmaxnreg.dec.sync.aligned.u32 %0;" ::"n"(R_HELP));
    const int ht = tid - 256;
    const int cta = role_id(), rb = role_rb(cta), hg = role_hg(cta);
    unsigned ep0 = 0;
    if (ht == 0) ep0 = ld_relaxed(&g_cnt[C_CS * 32]);
    bar_sync(0, NTHREADS);
    if (ht == 0) {
      asm volatile("st.shared.u32 [%0], %1;" ::"r"(sb + SM_EP), "r"(ep0 / NCTA) : "memory");
      mbar_arrive(bar + 8 * B_EP);
    }
    mbar_wait(bar + 8 * B_EP, 0);
    stats_publish(sb, 0, rb, hg, opaque_tid() - 256, part_tag(lds32(sb + SM_EP), 0));
    if (ht < 48) {
      const bf16* q = (&p.a_re)[ht >> 3];
      asm volatile("prefetch.global.L2 [%0];" ::"l"(q + cv_chan(cta, (ht >> 1) & 3) * 128 + (ht & 1) * 64));
    }
    {
      KGen kg;
      const uint32_t tab0 = sb + ((ht >> 5) < 2 ? SM_T : SM_T2 - 4096) + (ht >> 5) * 2048;
      const uint32_t tab = tab0 + (ht & 31) * 16, taba = tab0 + ((ht >> 3) & 1) * 1024 + (((ht >> 1) & 8) + (ht & 7)) * 16;
      delay<D_ST0>();
      stats_gather(sb, rb, opaque_tid() - 256, part_tag(lds32(sb + SM_EP), 0));
      if (ht == 0) TS(40);
      const int chn = cv_chan(cta, ht >> 5);
      const ModeIn modes = load_modes(p, chn * 128 + (ht & 31) * 4);
      const bf16 logdt = p.log_dt[chn], dskip = p.dskip[chn];
      if (!HALO_W14 && KG_START != 4) halo_receive(sb, 0, rb, hg, opaque_tid() - 256);
      if (KG_START == 1) mbar_wait(bar + 8 * B_HF, 0);
      kgen_setup(kg, sb, cta, ht, modes, logdt, dskip);
      if (!HALO_W14 && KG_START == 4) halo_receive(sb, 0, rb, hg, opaque_tid() - 256);
      if (KG_START == 2) mbar_wait(bar + 8 * B_HF, 0);
      if (KG_START == 3) mbar_wait(bar + 8 * B_QDONE, 0);
#pragma unroll 1
      for (int u = 0; u < 4; u++) {
        if (u == KG_PRE) {
          KTS(39);
          mbar_wait(bar + 8 * B_AD, 0);
          KTS(41);
        }
        kgen_unit(tab, taba, kg.cur.x, kg.cur.y, {kg.cur.z, kg.cur.w}, kg.T);
        kg.cur = lds128f(kgen_slot(sb, opaque_tid() - 256, u + 1));
      }
      kgen_finish(kg, sb, cta, opaque_tid() - 256);
    }
    KTS(51);
    bar_sync(4, 128);
#pragma unroll 1
    for (int layer = 0; layer < 2; layer++) {
      if (STOP <= 1 + 3 * layer) return;
      mbar_wait(bar + 8 * (EXP_LATE ? B_PS : B_PDONE), layer);
      expand_taps(sb, opaque_tid() - 256);
      conv_zero(sb, opaque_tid() - 256);
      if (ht == 0) TS(52 + layer);
      warp_release(bar + 8 * B_PE);
      if (STOP <= 2 + 3 * layer) return;
      {
        uint4 xr[4], st[4];
        const int c = opaque_tid() - 256;
        const SumAddr sa = conv_sum_addr(sb, c);
        conv_prep_load(sb, layer, cta, c, xr, st);
        conv_prep<true>(sb, layer, cta, c, xr, st, sa);
        if (layer == 1 && ht == 0) TS(62);
        const bf16* xup = g_xT + (size_t)(2 * layer * DM + cta) * LSEQ + (c + 128) * 8;
        const int ahead = layer ? S_AHEAD1 : S_AHEAD0;
        mbar_wait(bar + 8 * (B_U + 3), layer);
        if (ahead == 2) {
          conv_sums(sa, 1, c);
          fence_async_smem();
          bar_arrive(8, 256);
        }
        st[0] = ldcg128(xup);
#pragma unroll
        for (int lc = 0; lc < 4; lc++) {
          if (lc < 3 && lc + ahead < 4) {
            conv_sums(sa, lc + ahead, c);
            fence_async_smem();
            bar_arrive(7 + lc + ahead, 256);
            sched_fence<4>();
          }
          if (lc < 3) st[lc + 1] = ldcg128(xup + (lc + 1) * 128 * LSEQ);
          conv_epi(sb, layer, cta, lc, c, xr[lc], st[lc]);
          warp_release(bar + 8 * (B_E + lc));
          sched_fence<5>();
          if (layer == 1 && lc == 3 && ht == 0) TS(38);
        }
      }
      if (layer == 0 && STOP > 3) {
        const int c1 = role_id();
        stats_publish(sb, 1, role_rb(c1), role_hg(c1), opaque_tid() - 256, part_tag(lds32(sb + SM_EP), 2));
        delay<D_ST>();
        stats_gather(sb, role_rb(c1), opaque_tid() - 256, part_tag(lds32(sb + SM_EP), 2));
        if (ht == 0) TS(25);
        if (!HALO_W14) halo_receive(sb, 1, role_rb(c1), role_hg(c1), opaque_tid() - 256);
      }
    }
  } else {
    asm volatile("setmaxnreg.dec.sync.aligned.u32 %0;" ::"n"(512 - 2 * R_CONS - R_HELP));
    const int cta = role_id(), rb = role_rb(cta), hg = role_hg(cta), rb2 = role_rb2(cta), q2 = role_q2(cta);
    bar_sync(0, NTHREADS);
    if (warp != 12) {
      mbar_wait(bar + 8 * B_EP, 0);
      const uint32_t tag = lds32(sb + SM_EP) % 7 + 1;
      mbar_wait(bar + 8 * B_CW, 0);
      colsum_publish(sb, rb, hg, tid - 416, tag);
      if (tid == 416) TS(50);
      delay<D_CS>();
      colsum_gather(sb, hg, tid - 416, tag);
      __syncwarp();
      if (tid == 416) TS(55);
    }
    if (elect_one()) mbar_arrive(bar + 8 * B_CSF);
    if (warp == 12) {
      if (elect_one()) {
        unsigned epoch = 0;
#pragma unroll 1
        for (int layer = 0; layer < 2; layer++) {
          auto ld_w = [&](int c, int slot) {
            const uint32_t b = bar + 8 * (B_KVF + c);
            mbar_expect(b, 24576);
            tma_ld3(sb + SM_W + slot * 24576, &p.mapW3, hg * 64, c * 64, 0, b);
          };
          if (layer == 0) {
            mbar_wait(bar + 8 * (B_KVF + 2), 0);
            if (rb2 < 4) tma_prefetch2(&p.mapWo128, q2 * 64, rb2 * 128);
            asm volatile("prefetch.tensormap [%0];" ::"l"(&p.mapO) : "memory");
            asm volatile("prefetch.tensormap [%0];" ::"l"(&p.mapO128) : "memory");
            asm volatile("prefetch.tensormap [%0];" ::"l"(&p.mapXT) : "memory");
            asm volatile("prefetch.tensormap [%0];" ::"l"(&p.mapXT3) : "memory");
            mbar_wait(bar + 8 * B_EP, 0);
            epoch = lds32(sb + SM_EP);
          } else {
            mbar_wait(bar + 8 * B_PDONE, 0);
            ld_w(0, 0); ld_w(1, 1);
            mbar_wait(bar + 8 * (W2_LATE ? B_U : B_RE), 0);
            ld_w(2, 2);
          }
          {
            int slot = 0;
#pragma unroll 1
            for (int c = 3; c < 8; c++) {
              mbar_wait(bar + 8 * (B_KVE + c - 3), layer);
              ld_w(c, slot);
              slot = slot == 2 ? 0 : slot + 1;
            }
          }
          if (STOP <= 1 + 3 * layer) return;
          mbar_wait(bar + 8 * B_QDONE, layer);
          mbar_wait(bar + 8 * B_HF, layer);
          mbar_expect(bar + 8 * B_WOF, 65536);
#pragma unroll
          for (int c = 0; c < 4; c++) tma_ld(sb + SM_WO + c * 16384, &p.mapWo128, q2 * 64, c * 128, bar + 8 * B_WOF);
          {
            const uint32_t b = bar + 8 * B_RF;
            mbar_expect(b, 16384);
            if (layer == 0) tma_ld(sb + SM_R, &p.mapX128, (rb2 >> 3) * DM + q2 * 64, (rb2 & 7) * 128, b);
            else tma_ld3(sb + SM_R, &p.mapXT3, 0, DM + q2 * 64, rb2 * 2, b);
          }
#pragma unroll
          for (int c = 0; c < 8; c++) mbar_expect(bar + 8 * (B_OF + c), 16384);
          spin_until(&g_cnt[(C_O + rb2) * 32], (2 * epoch + layer + 1) * 16);
          fence_async_global();
#pragma unroll
          for (int c = 0; c < 8; c++) {
            if (c == 4) { mbar_wait(bar + 8 * B_OST, layer); fence_async_smem(); }
            tma_ld(sb + sm_o(c), &p.mapO128, c * 64, rb2 * 128, bar + 8 * (B_OF + c));
          }
          if (STOP <= 3 + 3 * layer) return;
        }
      }
    } else if (warp == 13) {
      if (elect_one() && STOP > 1) {
        const unsigned target = (lds32(sb + SM_EP) + 1) * NCTA;
        mbar_wait(bar + 8 * B_RE, 0);
        spin_until(&g_cnt[C_CS * 32 + 2], 2 * target);
        mbar_arrive(bar + 8 * B_XV);
        if (STOP <= 3) return;
        auto ld_x = [&](int c) { tma_ld3(sb + SM_X + c * 16384, &p.mapXT3, 0, DM + c * 64, rb * 2, bar + 8 * (B_XF + c)); };
#pragma unroll
        for (int c = 0; c < 8; c++) mbar_expect(bar + 8 * (B_XF + c), 16384);
        spin_until(&g_cnt[C_G1 * 32], target);
        fence_async_global();
        fence_async_smem();
        ld_x(0); ld_x(1);
        int done = 1, it = 0;
        while (done < 4) {
          const uint4 v = ld_tagged((const uint4*)&g_cnt[C_G1 * 32]);
          const int n = 4 + ((int)(v.y - target) >> 31) + ((int)(v.z - target) >> 31) + ((int)(v.w - target) >> 31);
          if (n == done) { if (++it > (1 << 23)) __trap(); continue; }
          if (n == 4) TS(44);
          fence_async_global();
          fence_async_smem();
          const int first = n == 4 && done > 1 ? 6 + (hg >> 2) : -1;
          if (first >= 0) ld_x(first);
#pragma unroll 1
          for (int c = 2 * done; c < 2 * n; c++)
            if (c != first) ld_x(c);
          done = n;
        }
        if (STOP <= 4) return;
        mbar_wait(bar + 8 * B_RE, 1);
        spin_until(&g_cnt[C_CS * 32 + 3], 2 * target);
        mbar_arrive(bar + 8 * B_XV);
      }
    } else if (warp == 15) {
      mbar_wait(bar + 8 * B_EP, 0);
      const unsigned epoch = lds32(sb + SM_EP);
#pragma unroll 1
      for (int layer = 0; layer < 2; layer++) {
        mbar_wait(bar + 8 * (B_KVF + FILL_AT), layer);
#pragma unroll
        for (int k = 0; k < 8; k++) ((uint4*)(g_xT + (size_t)(2 * layer * DM + cta) * LSEQ))[32 * k + lane] = make_uint4(~0u, ~0u, ~0u, ~0u);
        mbar_wait(bar + 8 * (B_KVF + FILL_AT + 1), layer);
#pragma unroll
        for (int k = 0; k < 16; k++)
          ((uint4*)(g_xT + (size_t)(3 * DM + cv_chan(cta, 3 - (k >> 2))) * LSEQ))[128 * layer + 32 * (k & 3) + lane] = make_uint4(~0u, ~0u, ~0u, ~0u);
        if (lane < 8) ((uint4*)g_stats)[layer * 1024 + cta * 8 + lane] = make_uint4(0, 0, 0, 0);
        __syncwarp();
        if (elect_one()) {
          red_release(&g_cnt[C_CS * 32 + layer]);
          spin_until(&g_cnt[C_CS * 32 + layer], (epoch + 1) * NCTA);
          mbar_arrive(bar + 8 * B_ZF);
          if (layer == 0 && STOP > 2) {
#pragma unroll
            for (int lc = 0; lc < 4; lc++) {
              mbar_wait(bar + 8 * (B_E + lc), 0);
              fence_reader();
              bulk_st(g_xT + (size_t)(DM + cv_chan(cta, lc)) * LSEQ, sb + cv_s(lc), 4096);
              bulk_commit();
              bulk_wait_all();
              red_relaxed(&g_cnt[C_G1 * 32 + lc]);
              if (lc == 3) TS(18);
            }
          }
        }
        __syncwarp();
        if (STOP <= 3) return;
      }
    } else if (warp == 14) {
      mbar_wait(bar + 8 * B_EP, 0);
      const unsigned epoch = lds32(sb + SM_EP);
#pragma unroll 1
      for (int layer = 0; layer < 2; layer++) {
        if (STOP <= 3 * layer) return;
        if (HALO_W14) halo_receive1(sb, layer, rb, hg, opaque_tid() & 31, 2 * epoch + layer + 1);
        if (STOP <= 1 + 3 * layer) return;
        mbar_wait(bar + 8 * B_ZF, layer);
        proj_stats(sb, layer, rb2, q2, opaque_tid() & 31, part_tag(epoch, 2 * layer + 1));
        if (layer == 1 && lane == 0) TS(5);
        delay<D_PREP>();
        if (lane == 0) mbar_arrive(bar + 8 * B_GB);
      }
    }
  }
}

typedef CUresult (*EncodeFn)(CUtensorMap*, CUtensorMapDataType, cuuint32_t, void*, const cuuint64_t*, const cuuint64_t*,
                             const cuuint32_t*, const cuuint32_t*, CUtensorMapInterleave, CUtensorMapSwizzle,
                             CUtensorMapL2promotion, CUtensorMapFloatOOBfill);

static void make_map(EncodeFn enc, CUtensorMap* m, void* ptr, uint64_t cols, uint64_t rows, uint32_t box_rows) {
  cuuint64_t dims[2] = {cols, rows};
  cuuint64_t strides[1] = {cols * 2};
  cuuint32_t box[2] = {64, box_rows};
  cuuint32_t es[2] = {1, 1};
  enc(m, CU_TENSOR_MAP_DATA_TYPE_BFLOAT16, 2, ptr, dims, strides, box, es, CU_TENSOR_MAP_INTERLEAVE_NONE,
      CU_TENSOR_MAP_SWIZZLE_128B, CU_TENSOR_MAP_L2_PROMOTION_L2_128B, CU_TENSOR_MAP_FLOAT_OOB_FILL_NONE);
}
static void make_map3(EncodeFn enc, CUtensorMap* m, void* ptr, uint64_t d0, uint64_t cols, uint64_t rows, uint64_t blk_stride,
                      uint64_t nblocks, uint32_t nblk, uint32_t box_rows = 64) {
  cuuint64_t dims[3] = {d0, rows, nblocks};
  cuuint64_t strides[2] = {cols * 2, blk_stride * 2};
  cuuint32_t box[3] = {64, box_rows, nblk};
  cuuint32_t es[3] = {1, 1, 1};
  enc(m, CU_TENSOR_MAP_DATA_TYPE_BFLOAT16, 3, ptr, dims, strides, box, es, CU_TENSOR_MAP_INTERLEAVE_NONE,
      CU_TENSOR_MAP_SWIZZLE_128B, CU_TENSOR_MAP_L2_PROMOTION_L2_128B, CU_TENSOR_MAP_FLOAT_OOB_FILL_NONE);
}

extern "C" void kernel_launch(void* const* d_in, const int* in_sizes, int n_in, void* d_out, int out_size) {
  static Params prm;
  static void* cached[13] = {nullptr};
  static bool attr_done = false;
  bool same = attr_done && cached[12] == d_out;
  for (int i = 0; i < 12 && same; i++) same = cached[i] == d_in[i];
  if (!same) {
    void* fn = nullptr;
    cudaDriverEntryPointQueryResult qr;
    cudaGetDriverEntryPoint("cuTensorMapEncodeTiled", &fn, cudaEnableDefault, &qr);
    EncodeFn enc = (EncodeFn)fn;
    void *pO, *pXT;
    cudaGetSymbolAddress(&pO, g_O);
    cudaGetSymbolAddress(&pXT, g_xT);
    make_map(enc, &prm.mapO, pO, DM, LSEQ, 64);
    make_map(enc, &prm.mapXT, pXT, LSEQ, 4 * DM, 64);
    prm.out = (bf16*)d_out;
    make_map(enc, &prm.mapX128, d_in[0], 2 * DM, LSEQ / 2, 128);
    make_map(enc, &prm.mapWo128, d_in[2], DM, DM, 128);
    make_map(enc, &prm.mapO128, pO, DM, LSEQ, 128);
    make_map3(enc, &prm.mapW3, d_in[1], DM, 3 * DM, DM, DM, 3, 3);
    make_map3(enc, &prm.mapW3h, d_in[1], DM, 3 * DM, DM, DM, 3, 3, 32);
    make_map3(enc, &prm.mapXT3, pXT, 64, LSEQ, 4 * DM, 64, 32, 2);
    prm.a_re = (const bf16*)d_in[4]; prm.a_im = (const bf16*)d_in[5];
    prm.b_re = (const bf16*)d_in[6]; prm.b_im = (const bf16*)d_in[7];
    prm.c_re = (const bf16*)d_in[8]; prm.c_im = (const bf16*)d_in[9];
    prm.log_dt = (const bf16*)d_in[10]; prm.dskip = (const bf16*)d_in[11];
    cudaFuncSetAttribute(fused_kernel, cudaFuncAttributeMaxDynamicSharedMemorySize, SM_TOTAL);
    for (int i = 0; i < 12; i++) cached[i] = d_in[i];
    cached[12] = d_out;
    attr_done = true;
  }
  prm.stop = 100;
    fused_kernel<<<NCTA, NTHREADS, SM_TOTAL>>>(prm);
}
```

```cpp
#include <cuda_runtime.h>
#include <cuda_bf16.h>
#include <cuda.h>
#include <stdint.h>

typedef __nv_bfloat16 bf16;

constexpr int LSEQ = 2048;
constexpr int DM = 512;
constexpr int NCTA = 128;
constexpr int NTHREADS = 512;
#define RR 0
#define KG_PRE 2
#define W2_LATE 1
#define FILL_AT 5
#define EXP_LATE 1
#define RFENCE 1
#define D_FIN 550
#define D_PREP 500
#define D_PST 0
#define D_HALO 500
#define STAG 2
#define D_ST 0
#define TLAYER 1
#define KG_PD 1
#define SUM_F32 0
#define CS_LATE0 1
#define D_HALO1 0
#define KG_START 0
#define S_AHEAD0 1
#define S_AHEAD1 2
#define PAUSE 0
#define PARK_FIRST 0
#define P_UNROLL_N 1
constexpr int P_UNROLL = P_UNROLL_N;
#define NORM_FMA 0
#define G_WAIT 2
#define HALO_W14 1
#define D_START 200
#define D_CS 300
#define D_ST0 400
#define KG_LAST 0
#define X_JIT 0
#define KG_GATE 2
#define R_CONS 192
#define R_HELP 88

constexpr int SM_X = 0;
constexpr int SM_W = 131072;
constexpr int SM_KVX = SM_X;
constexpr int SM_OST = SM_X + 32768;
constexpr int SM_WO = SM_X + 65536;
__host__ __device__ constexpr int sm_o(int c) { return c < 4 ? SM_W + c * 16384 : SM_X + (c - 4) * 16384; }
constexpr int SM_R = 196608;
constexpr int SM_T = 212992;
constexpr int SM_KC = 217088;
constexpr int KC_STRIDE = 648;
constexpr int SM_CS = SM_KC + 4 * KC_STRIDE * 2;
constexpr int SM_CW = SM_R + 8192;
constexpr int SM_EP = SM_CS + 768;
constexpr int SM_BAR = SM_EP + 16;
constexpr int SM_T2 = SM_BAR + 896;
constexpr int SM_HALO = SM_T2 + 4096;
constexpr int SM_ST = SM_HALO + 3072;
constexpr int SM_TOTAL = SM_HALO + 4096;
static_assert(SM_TOTAL <= 232448, "shared memory");

constexpr int CV_UH = 140 * 16;
constexpr int CV_PECH = 1120 * 4;
constexpr int CV_PBW = 2112 * 2;
__host__ __device__ constexpr int cv_s(int lc) { return SM_X + lc * 32768; }
__host__ __device__ constexpr int cv_u(int lc) { return cv_s(lc) + 4096; }
__host__ __device__ constexpr int cv_pe(int lc) { return cv_u(lc) + 2 * CV_UH; }
__host__ __device__ constexpr int cv_pb(int lc) { return cv_pe(lc) + CV_PECH; }
__host__ __device__ constexpr int cv_ft(int lc) { return cv_pb(lc) + 4 * CV_PBW; }
static_assert(cv_ft(0) + 1024 <= 32768, "conv buffers");
__host__ __device__ constexpr int cv_chan(int cta, int lc) { return cta + 128 * lc; }

enum {
  B_XF = 0,
  B_KVF = 8,
  B_OF = 16,
  B_WOF = 24,
  B_T = 31,
  B_RF = 28,
  B_RE = 29,
  B_CW = 30,
  B_GB = 35,
  B_EP = 36,
  B_ZF = 37,
  B_XV = 39,
  B_SD = 38,
  B_KVE = 40,
  B_AD = 45,
  B_OST = 46,
  B_QDONE = 47,
  B_PDONE = 48,
  B_S = 50,
  B_E = 54,
  B_P = 58,
  B_PE = 62,
  B_STF = 63,
  B_CSF = 64,
  B_HF = 65,
  B_U = 70,
  B_PS = 74,
  B_COUNT = 80
};

enum {
  C_CS = 0,
  C_G1 = 2,
  C_O = 4,
  C_COUNT = 20
};

__device__ __align__(128) unsigned g_cnt[C_COUNT * 32];
__device__ __align__(1024) bf16 g_O[LSEQ * DM];
__device__ __align__(1024) bf16 g_xT[4 * DM * LSEQ];
__device__ __align__(1024) uint32_t g_stats[2 * LSEQ];
__device__ __align__(1024) uint4 g_colsum[8 * 16 * 48];
__device__ __align__(1024) uint4 g_halo[16 * 8 * 192];
__device__ __align__(1024) uint2 g_part[16 * 8 * 128];
#define TS(i) do { } while (0)

#define ATS(i, th) do { } while (0)
#define KTS(i) do { if (ht == 0) TS(i); } while (0)
#define FTS(i) do { } while (0)
#define LTS(i) do { } while (0)

#define STOP 100

struct Params {
  CUtensorMap mapO, mapXT, mapX128, mapWo128, mapO128, mapW3, mapW3h, mapXT3;
  const bf16 *a_re, *a_im, *b_re, *b_im, *c_re, *c_im, *log_dt, *dskip;
  bf16* out;
  int stop;
};

__device__ __forceinline__ uint32_t s32(const void* p) { return (uint32_t)__cvta_generic_to_shared(p); }
__device__ __forceinline__ void mbar_init(uint32_t b, int c) { asm volatile("mbarrier.init.shared::cta.b64 [%0], %1;" ::"r"(b), "r"(c) : "memory"); }
__device__ __forceinline__ void mbar_expect(uint32_t b, int bytes) { asm volatile("mbarrier.arrive.expect_tx.shared::cta.b64 _, [%0], %1;" ::"r"(b), "r"(bytes) : "memory"); }
__device__ __forceinline__ void mbar_arrive(uint32_t b) { asm volatile("mbarrier.arrive.shared::cta.b64 _, [%0];" ::"r"(b) : "memory"); }
__device__ __forceinline__ void mbar_arrive_if(uint32_t b, bool c) {
  asm volatile("{\n.reg .pred p;\nsetp.ne.u32 p, %1, 0;\n@p mbarrier.arrive.shared::cta.b64 _, [%0];\n}" ::"r"(b), "r"((uint32_t)c) : "memory");
}
__device__ __forceinline__ void mbar_wait(uint32_t b, int parity) {
  asm volatile("{\n.reg .pred p;\nWAIT_LOOP:\nmbarrier.try_wait.parity.shared::cta.b64 p, [%0], %1;\n@p bra WAIT_DONE;\nbra WAIT_LOOP;\nWAIT_DONE:\n}" ::"r"(b), "r"(parity) : "memory");
}
template <int N> __device__ __forceinline__ void delay() {
  if constexpr (N > 0) {
    uint32_t t0, t;
    asm volatile("mov.u32 %0, %%clock;" : "=r"(t0));
    do { asm volatile("mov.u32 %0, %%clock;" : "=r"(t)); } while (t - t0 < N);
  }
}
#define SF 3
template <int ID> __device__ __forceinline__ void sched_fence() {
  if constexpr ((SF >> ID) & 1)
    asm volatile("{\n.reg .pred p;\n.reg .u32 t;\nsetp.eq.u32 p, %0, 0;\n@p mov.u32 t, %%clock;\n@p st.shared.u32 [%0], t;\n}" ::"r"(gridDim.x) : "memory");
}
__device__ __forceinline__ int opaque_tid() { int v; asm volatile("mov.u32 %0, %%tid.x;" : "=r"(v)); return v; }
__device__ __forceinline__ bool elect_one() {
  uint32_t r;
  asm volatile("{\n.reg .pred p;\nelect.sync _|p, 0xffffffff;\nselp.u32 %0, 1, 0, p;\n}" : "=r"(r));
  return r != 0;
}
__device__ __forceinline__ void tma_ld(uint32_t dst, const CUtensorMap* m, int c0, int c1, uint32_t bar) {
  asm volatile("cp.async.bulk.tensor.2d.shared::cluster.global.mbarrier::complete_tx::bytes [%0], [%1, {%3, %4}], [%2];"
               ::"r"(dst), "l"(m), "r"(bar), "r"(c0), "r"(c1) : "memory");
}
__device__ __forceinline__ void tma_ld3(uint32_t dst, const CUtensorMap* m, int c0, int c1, int c2, uint32_t bar) {
  asm volatile("cp.async.bulk.tensor.3d.shared::cluster.global.mbarrier::complete_tx::bytes [%0], [%1, {%3, %4, %5}], [%2];"
               ::"r"(dst), "l"(m), "r"(bar), "r"(c0), "r"(c1), "r"(c2) : "memory");
}
__device__ __forceinline__ void tma_prefetch2(const CUtensorMap* m, int c0, int c1) {
  asm volatile("cp.async.bulk.prefetch.tensor.2d.L2.global.tile [%0, {%1, %2}];" ::"l"(m), "r"(c0), "r"(c1) : "memory");
}
__device__ __forceinline__ void tma_prefetch3(const CUtensorMap* m, int c0, int c1, int c2) {
  asm volatile("cp.async.bulk.prefetch.tensor.3d.L2.global.tile [%0, {%1, %2, %3}];" ::"l"(m), "r"(c0), "r"(c1), "r"(c2) : "memory");
}
__device__ __forceinline__ void tma_st(const CUtensorMap* m, int c0, int c1, uint32_t src) {
  asm volatile("cp.async.bulk.tensor.2d.global.shared::cta.bulk_group [%0, {%2, %3}], [%1];" ::"l"(m), "r"(src), "r"(c0), "r"(c1) : "memory");
}
__device__ __forceinline__ void bulk_ld(uint32_t dst, const void* src, int bytes, uint32_t bar) {
  asm volatile("cp.async.bulk.shared::cluster.global.mbarrier::complete_tx::bytes [%0], [%1], %2, [%3];" ::"r"(dst), "l"(src), "r"(bytes), "r"(bar) : "memory");
}
__device__ __forceinline__ void bulk_st(void* dst, uint32_t src, int bytes) {
  asm volatile("cp.async.bulk.global.shared::cta.bulk_group [%0], [%1], %2;" ::"l"(dst), "r"(src), "r"(bytes) : "memory");
}
__device__ __forceinline__ void bulk_red_add_f32(void* dst, uint32_t src, int bytes) {
  asm volatile("cp.reduce.async.bulk.global.shared::cta.bulk_group.add.f32 [%0], [%1], %2;" ::"l"(dst), "r"(src), "r"(bytes) : "memory");
}
__device__ __forceinline__ void bulk_commit() { asm volatile("cp.async.bulk.commit_group;" ::: "memory"); }
__device__ __forceinline__ void bulk_wait_all() { asm volatile("cp.async.bulk.wait_group 0;" ::: "memory"); }
__device__ __forceinline__ void fence_async_smem() { asm volatile("fence.proxy.async.shared::cta;" ::: "memory"); }
__device__ __forceinline__ void fence_writer() { if (!RFENCE) fence_async_smem(); }
__device__ __forceinline__ void fence_reader() { if (RFENCE) fence_async_smem(); }
__device__ __forceinline__ void fence_async_global() { asm volatile("fence.proxy.async.global;" ::: "memory"); }
__device__ __forceinline__ void bar_sync(int id, int n) { asm volatile("bar.sync %0, %1;" ::"r"(id), "r"(n) : "memory"); }
__device__ __forceinline__ void bar_arrive(int id, int n) { asm volatile("bar.arrive %0, %1;" ::"r"(id), "r"(n) : "memory"); }
__device__ __forceinline__ void wg_fence() { asm volatile("wgmma.fence.sync.aligned;" ::: "memory"); }
__device__ __forceinline__ void wg_commit() { asm volatile("wgmma.commit_group.sync.aligned;" ::: "memory"); }
template <int N> __device__ __forceinline__ void wg_wait() { asm volatile("wgmma.wait_group.sync.aligned %0;" ::"n"(N) : "memory"); }
__device__ __forceinline__ uint64_t mkdesc(uint32_t addr, uint32_t lbo, uint32_t sbo, int sw) {
  return (uint64_t)((addr & 0x3FFFF) >> 4) | ((uint64_t)(lbo >> 4) << 16) | ((uint64_t)(sbo >> 4) << 32) | ((uint64_t)sw << 62);
}
__device__ __forceinline__ void ldsm4(uint32_t* r, uint32_t a) {
  asm volatile("ldmatrix.sync.aligned.m8n8.x4.shared.b16 {%0,%1,%2,%3}, [%4];" : "=r"(r[0]), "=r"(r[1]), "=r"(r[2]), "=r"(r[3]) : "r"(a) : "memory");
}
__device__ __forceinline__ void ldsm4t(uint32_t* r, uint32_t a) {
  asm volatile("ldmatrix.sync.aligned.m8n8.x4.trans.shared.b16 {%0,%1,%2,%3}, [%4];" : "=r"(r[0]), "=r"(r[1]), "=r"(r[2]), "=r"(r[3]) : "r"(a) : "memory");
}
__device__ __forceinline__ void stsm4(uint32_t a, uint32_t r0, uint32_t r1, uint32_t r2, uint32_t r3) {
  asm volatile("stmatrix.sync.aligned.m8n8.x4.shared.b16 [%0], {%1,%2,%3,%4};" ::"r"(a), "r"(r0), "r"(r1), "r"(r2), "r"(r3) : "memory");
}
__device__ __forceinline__ void stsm4t(uint32_t a, uint32_t r0, uint32_t r1, uint32_t r2, uint32_t r3) {
  asm volatile("stmatrix.sync.aligned.m8n8.x4.trans.shared.b16 [%0], {%1,%2,%3,%4};" ::"r"(a), "r"(r0), "r"(r1), "r"(r2), "r"(r3) : "memory");
}
__device__ __forceinline__ uint32_t movm_t(uint32_t a) { uint32_t r; asm volatile("movmatrix.sync.aligned.m8n8.trans.b16 %0, %1;" : "=r"(r) : "r"(a)); return r; }
__device__ __forceinline__ uint32_t lds32(uint32_t a) { uint32_t v; asm volatile("ld.shared.b32 %0, [%1];" : "=r"(v) : "r"(a) : "memory"); return v; }
__device__ __forceinline__ float2 lds64f(uint32_t a) { float2 v; asm volatile("ld.shared.v2.f32 {%0,%1}, [%2];" : "=f"(v.x), "=f"(v.y) : "r"(a) : "memory"); return v; }
__device__ __forceinline__ float4 lds128f(uint32_t a) { float4 v; asm volatile("ld.shared.v4.f32 {%0,%1,%2,%3}, [%4];" : "=f"(v.x), "=f"(v.y), "=f"(v.z), "=f"(v.w) : "r"(a) : "memory"); return v; }
__device__ __forceinline__ uint4 lds128(uint32_t a) { uint4 v; asm volatile("ld.shared.v4.b32 {%0,%1,%2,%3}, [%4];" : "=r"(v.x), "=r"(v.y), "=r"(v.z), "=r"(v.w) : "r"(a) : "memory"); return v; }
__device__ __forceinline__ void sts128(uint32_t a, uint4 v) { asm volatile("st.shared.v4.b32 [%0], {%1,%2,%3,%4};" ::"r"(a), "r"(v.x), "r"(v.y), "r"(v.z), "r"(v.w) : "memory"); }
__device__ __forceinline__ void sts128f(uint32_t a, float x, float y, float z, float w) { asm volatile("st.shared.v4.f32 [%0], {%1,%2,%3,%4};" ::"r"(a), "f"(x), "f"(y), "f"(z), "f"(w) : "memory"); }
__device__ __forceinline__ void sts32f(uint32_t a, float v) { asm volatile("st.shared.f32 [%0], %1;" ::"r"(a), "f"(v) : "memory"); }
__device__ __forceinline__ void sts16(uint32_t a, uint16_t v) { asm volatile("st.shared.u16 [%0], %1;" ::"r"(a), "h"(v) : "memory"); }
__device__ __forceinline__ uint32_t lds16(uint32_t a) { uint16_t v; asm volatile("ld.shared.u16 %0, [%1];" : "=h"(v) : "r"(a) : "memory"); return v; }
__device__ __forceinline__ uint32_t packbf(float lo, float hi) { uint32_t r; asm("cvt.rn.bf16x2.f32 %0, %1, %2;" : "=r"(r) : "f"(hi), "f"(lo)); return r; }
__device__ __forceinline__ float bf_lo(uint32_t v) { return __uint_as_float(v << 16); }
__device__ __forceinline__ float bf_hi(uint32_t v) { return __uint_as_float(v & 0xffff0000u); }
__device__ __forceinline__ float ex2(float x) { float r; asm("ex2.approx.ftz.f32 %0, %1;" : "=f"(r) : "f"(x)); return r; }
__device__ __forceinline__ float rsqrt_approx(float x) { float r; asm("rsqrt.approx.ftz.f32 %0, %1;" : "=f"(r) : "f"(x)); return r; }
__device__ __forceinline__ float rcp_approx(float x) { float r; asm("rcp.approx.ftz.f32 %0, %1;" : "=f"(r) : "f"(x)); return r; }
__device__ __forceinline__ void mma_bf16(float* d, const uint32_t* a, uint32_t b0, uint32_t b1) {
  asm("mma.sync.aligned.m16n8k16.row.col.f32.bf16.bf16.f32 {%0,%1,%2,%3}, {%4,%5,%6,%7}, {%8,%9}, {%0,%1,%2,%3};"
               : "+f"(d[0]), "+f"(d[1]), "+f"(d[2]), "+f"(d[3]) : "r"(a[0]), "r"(a[1]), "r"(a[2]), "r"(a[3]), "r"(b0), "r"(b1));
}
__device__ __forceinline__ void mma_bf16_k8(float* d, uint32_t a0, uint32_t a1, uint32_t b) {
  asm("mma.sync.aligned.m16n8k8.row.col.f32.bf16.bf16.f32 {%0,%1,%2,%3}, {%4,%5}, {%6}, {%0,%1,%2,%3};"
      : "+f"(d[0]), "+f"(d[1]), "+f"(d[2]), "+f"(d[3]) : "r"(a0), "r"(a1), "r"(b));
}
__device__ __forceinline__ void red_release(unsigned* p) { asm volatile("red.release.gpu.global.add.u32 [%0], 1;" ::"l"(p) : "memory"); }
__device__ __forceinline__ void red_relaxed(unsigned* p) { asm volatile("red.relaxed.gpu.global.add.u32 [%0], 1;" ::"l"(p) : "memory"); }
__device__ __forceinline__ unsigned ld_relaxed(const unsigned* p) { unsigned v; asm volatile("ld.relaxed.gpu.global.u32 %0, [%1];" : "=r"(v) : "l"(p) : "memory"); return v; }
__device__ __forceinline__ void spin_until(const unsigned* p, unsigned target) {
  int it = 0;
  while ((int)(ld_relaxed(p) - target) < 0) {
    if (++it > (1 << 23)) __trap();
  }
}
__device__ __forceinline__ uint4 ldcg128(const void* p) { uint4 v; asm volatile("ld.global.cg.v4.b32 {%0,%1,%2,%3}, [%4];" : "=r"(v.x), "=r"(v.y), "=r"(v.z), "=r"(v.w) : "l"(p) : "memory"); return v; }
__device__ __forceinline__ uint4 ld_tagged(const uint4* p) { uint4 v; asm volatile("ld.relaxed.gpu.global.v4.u32 {%0,%1,%2,%3}, [%4];" : "=r"(v.x), "=r"(v.y), "=r"(v.z), "=r"(v.w) : "l"(p) : "memory"); return v; }
__device__ __forceinline__ uint2 ld_part(const uint2* p) { uint2 v; asm volatile("ld.relaxed.gpu.global.v2.u32 {%0,%1}, [%2];" : "=r"(v.x), "=r"(v.y) : "l"(p) : "memory"); return v; }
__device__ __forceinline__ void st_part(uint2* p, float s, float q, uint32_t tag) {
  asm volatile("st.relaxed.gpu.global.v2.u32 [%0], {%1,%2};" ::"l"(p), "r"(__float_as_uint(s)), "r"((__float_as_uint(q) & ~7u) | tag) : "memory");
}
__device__ __forceinline__ uint32_t part_tag(uint32_t epoch, int k) { return (4 * (epoch % 7) + k) % 7 + 1; }
__device__ __forceinline__ void st_tagged3(uint4* p, uint32_t a, uint32_t b, uint32_t c, uint32_t tag) { asm volatile("st.relaxed.gpu.global.v4.u32 [%0], {%1,%2,%3,%4};" ::"l"(p), "r"(a), "r"(b), "r"(c), "r"(tag) : "memory"); }
__device__ __forceinline__ uint32_t hadd2(uint32_t a, uint32_t b) { uint32_t r; asm("add.rn.bf16x2 %0, %1, %2;" : "=r"(r) : "r"(a), "r"(b)); return r; }
__device__ __forceinline__ uint32_t hfma2(uint32_t a, uint32_t b, uint32_t c) { uint32_t r; asm("fma.rn.bf16x2 %0, %1, %2, %3;" : "=r"(r) : "r"(a), "r"(b), "r"(c)); return r; }
__device__ __forceinline__ uint32_t hmul2(uint32_t a, uint32_t b) { uint32_t r; asm("mul.rn.bf16x2 %0, %1, %2;" : "=r"(r) : "r"(a), "r"(b)); return r; }

template<int N,int TB> __device__ __forceinline__ void wgmma_rs(float* d, const uint32_t* a, uint64_t db, int sd);
template<int N,int TA,int TB> __device__ __forceinline__ void wgmma_ss(float* d, uint64_t da, uint64_t db, int sd);
template<> __device__ __forceinline__ void wgmma_rs<128,0>(float* d, const uint32_t* a, uint64_t db, int sd) {
  asm volatile("{\n.reg .pred p;\nsetp.ne.b32 p, %69, 0;\nwgmma.mma_async.sync.aligned.m64n128k16.f32.bf16.bf16 {%0,%1,%2,%3,%4,%5,%6,%7,%8,%9,%10,%11,%12,%13,%14,%15,%16,%17,%18,%19,%20,%21,%22,%23,%24,%25,%26,%27,%28,%29,%30,%31,%32,%33,%34,%35,%36,%37,%38,%39,%40,%41,%42,%43,%44,%45,%46,%47,%48,%49,%50,%51,%52,%53,%54,%55,%56,%57,%58,%59,%60,%61,%62,%63}, {%64,%65,%66,%67}, %68, p, 1, 1, 0;\n}\n"
   : "+f"(d[0]),"+f"(d[1]),"+f"(d[2]),"+f"(d[3]),"+f"(d[4]),"+f"(d[5]),"+f"(d[6]),"+f"(d[7]),"+f"(d[8]),"+f"(d[9]),"+f"(d[10]),"+f"(d[11]),"+f"(d[12]),"+f"(d[13]),"+f"(d[14]),"+f"(d[15]),"+f"(d[16]),"+f"(d[17]),"+f"(d[18]),"+f"(d[19]),"+f"(d[20]),"+f"(d[21]),"+f"(d[22]),"+f"(d[23]),"+f"(d[24]),"+f"(d[25]),"+f"(d[26]),"+f"(d[27]),"+f"(d[28]),"+f"(d[29]),"+f"(d[30]),"+f"(d[31]),"+f"(d[32]),"+f"(d[33]),"+f"(d[34]),"+f"(d[35]),"+f"(d[36]),"+f"(d[37]),"+f"(d[38]),"+f"(d[39]),"+f"(d[40]),"+f"(d[41]),"+f"(d[42]),"+f"(d[43]),"+f"(d[44]),"+f"(d[45]),"+f"(d[46]),"+f"(d[47]),"+f"(d[48]),"+f"(d[49]),"+f"(d[50]),"+f"(d[51]),"+f"(d[52]),"+f"(d[53]),"+f"(d[54]),"+f"(d[55]),"+f"(d[56]),"+f"(d[57]),"+f"(d[58]),"+f"(d[59]),"+f"(d[60]),"+f"(d[61]),"+f"(d[62]),"+f"(d[63])
   : "r"(a[0]), "r"(a[1]), "r"(a[2]), "r"(a[3]), "l"(db), "r"(sd));
}
template<> __device__ __forceinline__ void wgmma_rs<120,0>(float* d, const uint32_t* a, uint64_t db, int sd) {
  asm volatile("{\n.reg .pred p;\nsetp.ne.b32 p, %65, 0;\nwgmma.mma_async.sync.aligned.m64n120k16.f32.bf16.bf16 {%0,%1,%2,%3,%4,%5,%6,%7,%8,%9,%10,%11,%12,%13,%14,%15,%16,%17,%18,%19,%20,%21,%22,%23,%24,%25,%26,%27,%28,%29,%30,%31,%32,%33,%34,%35,%36,%37,%38,%39,%40,%41,%42,%43,%44,%45,%46,%47,%48,%49,%50,%51,%52,%53,%54,%55,%56,%57,%58,%59}, {%60,%61,%62,%63}, %64, p, 1, 1, 0;\n}\n"
   : "+f"(d[0]),"+f"(d[1]),"+f"(d[2]),"+f"(d[3]),"+f"(d[4]),"+f"(d[5]),"+f"(d[6]),"+f"(d[7]),"+f"(d[8]),"+f"(d[9]),"+f"(d[10]),"+f"(d[11]),"+f"(d[12]),"+f"(d[13]),"+f"(d[14]),"+f"(d[15]),"+f"(d[16]),"+f"(d[17]),"+f"(d[18]),"+f"(d[19]),"+f"(d[20]),"+f"(d[21]),"+f"(d[22]),"+f"(d[23]),"+f"(d[24]),"+f"(d[25]),"+f"(d[26]),"+f"(d[27]),"+f"(d[28]),"+f"(d[29]),"+f"(d[30]),"+f"(d[31]),"+f"(d[32]),"+f"(d[33]),"+f"(d[34]),"+f"(d[35]),"+f"(d[36]),"+f"(d[37]),"+f"(d[38]),"+f"(d[39]),"+f"(d[40]),"+f"(d[41]),"+f"(d[42]),"+f"(d[43]),"+f"(d[44]),"+f"(d[45]),"+f"(d[46]),"+f"(d[47]),"+f"(d[48]),"+f"(d[49]),"+f"(d[50]),"+f"(d[51]),"+f"(d[52]),"+f"(d[53]),"+f"(d[54]),"+f"(d[55]),"+f"(d[56]),"+f"(d[57]),"+f"(d[58]),"+f"(d[59])
   : "r"(a[0]), "r"(a[1]), "r"(a[2]), "r"(a[3]), "l"(db), "r"(sd));
}
template<> __device__ __forceinline__ void wgmma_rs<112,0>(float* d, const uint32_t* a, uint64_t db, int sd) {
  asm volatile("{\n.reg .pred p;\nsetp.ne.b32 p, %61, 0;\nwgmma.mma_async.sync.aligned.m64n112k16.f32.bf16.bf16 {%0,%1,%2,%3,%4,%5,%6,%7,%8,%9,%10,%11,%12,%13,%14,%15,%16,%17,%18,%19,%20,%21,%22,%23,%24,%25,%26,%27,%28,%29,%30,%31,%32,%33,%34,%35,%36,%37,%38,%39,%40,%41,%42,%43,%44,%45,%46,%47,%48,%49,%50,%51,%52,%53,%54,%55}, {%56,%57,%58,%59}, %60, p, 1, 1, 0;\n}\n"
   : "+f"(d[0]),"+f"(d[1]),"+f"(d[2]),"+f"(d[3]),"+f"(d[4]),"+f"(d[5]),"+f"(d[6]),"+f"(d[7]),"+f"(d[8]),"+f"(d[9]),"+f"(d[10]),"+f"(d[11]),"+f"(d[12]),"+f"(d[13]),"+f"(d[14]),"+f"(d[15]),"+f"(d[16]),"+f"(d[17]),"+f"(d[18]),"+f"(d[19]),"+f"(d[20]),"+f"(d[21]),"+f"(d[22]),"+f"(d[23]),"+f"(d[24]),"+f"(d[25]),"+f"(d[26]),"+f"(d[27]),"+f"(d[28]),"+f"(d[29]),"+f"(d[30]),"+f"(d[31]),"+f"(d[32]),"+f"(d[33]),"+f"(d[34]),"+f"(d[35]),"+f"(d[36]),"+f"(d[37]),"+f"(d[38]),"+f"(d[39]),"+f"(d[40]),"+f"(d[41]),"+f"(d[42]),"+f"(d[43]),"+f"(d[44]),"+f"(d[45]),"+f"(d[46]),"+f"(d[47]),"+f"(d[48]),"+f"(d[49]),"+f"(d[50]),"+f"(d[51]),"+f"(d[52]),"+f"(d[53]),"+f"(d[54]),"+f"(d[55])
   : "r"(a[0]), "r"(a[1]), "r"(a[2]), "r"(a[3]), "l"(db), "r"(sd));
}
template<> __device__ __forceinline__ void wgmma_rs<104,0>(float* d, const uint32_t* a, uint64_t db, int sd) {
  asm volatile("{\n.reg .pred p;\nsetp.ne.b32 p, %57, 0;\nwgmma.mma_async.sync.aligned.m64n104k16.f32.bf16.bf16 {%0,%1,%2,%3,%4,%5,%6,%7,%8,%9,%10,%11,%12,%13,%14,%15,%16,%17,%18,%19,%20,%21,%22,%23,%24,%25,%26,%27,%28,%29,%30,%31,%32,%33,%34,%35,%36,%37,%38,%39,%40,%41,%42,%43,%44,%45,%46,%47,%48,%49,%50,%51}, {%52,%53,%54,%55}, %56, p, 1, 1, 0;\n}\n"
   : "+f"(d[0]),"+f"(d[1]),"+f"(d[2]),"+f"(d[3]),"+f"(d[4]),"+f"(d[5]),"+f"(d[6]),"+f"(d[7]),"+f"(d[8]),"+f"(d[9]),"+f"(d[10]),"+f"(d[11]),"+f"(d[12]),"+f"(d[13]),"+f"(d[14]),"+f"(d[15]),"+f"(d[16]),"+f"(d[17]),"+f"(d[18]),"+f"(d[19]),"+f"(d[20]),"+f"(d[21]),"+f"(d[22]),"+f"(d[23]),"+f"(d[24]),"+f"(d[25]),"+f"(d[26]),"+f"(d[27]),"+f"(d[28]),"+f"(d[29]),"+f"(d[30]),"+f"(d[31]),"+f"(d[32]),"+f"(d[33]),"+f"(d[34]),"+f"(d[35]),"+f"(d[36]),"+f"(d[37]),"+f"(d[38]),"+f"(d[39]),"+f"(d[40]),"+f"(d[41]),"+f"(d[42]),"+f"(d[43]),"+f"(d[44]),"+f"(d[45]),"+f"(d[46]),"+f"(d[47]),"+f"(d[48]),"+f"(d[49]),"+f"(d[50]),"+f"(d[51])
   : "r"(a[0]), "r"(a[1]), "r"(a[2]), "r"(a[3]), "l"(db), "r"(sd));
}
template<> __device__ __forceinline__ void wgmma_rs<96,0>(float* d, const uint32_t* a, uint64_t db, int sd) {
  asm volatile("{\n.reg .pred p;\nsetp.ne.b32 p, %53, 0;\nwgmma.mma_async.sync.aligned.m64n96k16.f32.bf16.bf16 {%0,%1,%2,%3,%4,%5,%6,%7,%8,%9,%10,%11,%12,%13,%14,%15,%16,%17,%18,%19,%20,%21,%22,%23,%24,%25,%26,%27,%28,%29,%30,%31,%32,%33,%34,%35,%36,%37,%38,%39,%40,%41,%42,%43,%44,%45,%46,%47}, {%48,%49,%50,%51}, %52, p, 1, 1, 0;\n}\n"
   : "+f"(d[0]),"+f"(d[1]),"+f"(d[2]),"+f"(d[3]),"+f"(d[4]),"+f"(d[5]),"+f"(d[6]),"+f"(d[7]),"+f"(d[8]),"+f"(d[9]),"+f"(d[10]),"+f"(d[11]),"+f"(d[12]),"+f"(d[13]),"+f"(d[14]),"+f"(d[15]),"+f"(d[16]),"+f"(d[17]),"+f"(d[18]),"+f"(d[19]),"+f"(d[20]),"+f"(d[21]),"+f"(d[22]),"+f"(d[23]),"+f"(d[24]),"+f"(d[25]),"+f"(d[26]),"+f"(d[27]),"+f"(d[28]),"+f"(d[29]),"+f"(d[30]),"+f"(d[31]),"+f"(d[32]),"+f"(d[33]),"+f"(d[34]),"+f"(d[35]),"+f"(d[36]),"+f"(d[37]),"+f"(d[38]),"+f"(d[39]),"+f"(d[40]),"+f"(d[41]),"+f"(d[42]),"+f"(d[43]),"+f"(d[44]),"+f"(d[45]),"+f"(d[46]),"+f"(d[47])
   : "r"(a[0]), "r"(a[1]), "r"(a[2]), "r"(a[3]), "l"(db), "r"(sd));
}
template<> __device__ __forceinline__ void wgmma_rs<88,0>(float* d, const uint32_t* a, uint64_t db, int sd) {
  asm volatile("{\n.reg .pred p;\nsetp.ne.b32 p, %49, 0;\nwgmma.mma_async.sync.aligned.m64n88k16.f32.bf16.bf16 {%0,%1,%2,%3,%4,%5,%6,%7,%8,%9,%10,%11,%12,%13,%14,%15,%16,%17,%18,%19,%20,%21,%22,%23,%24,%25,%26,%27,%28,%29,%30,%31,%32,%33,%34,%35,%36,%37,%38,%39,%40,%41,%42,%43}, {%44,%45,%46,%47}, %48, p, 1, 1, 0;\n}\n"
   : "+f"(d[0]),"+f"(d[1]),"+f"(d[2]),"+f"(d[3]),"+f"(d[4]),"+f"(d[5]),"+f"(d[6]),"+f"(d[7]),"+f"(d[8]),"+f"(d[9]),"+f"(d[10]),"+f"(d[11]),"+f"(d[12]),"+f"(d[13]),"+f"(d[14]),"+f"(d[15]),"+f"(d[16]),"+f"(d[17]),"+f"(d[18]),"+f"(d[19]),"+f"(d[20]),"+f"(d[21]),"+f"(d[22]),"+f"(d[23]),"+f"(d[24]),"+f"(d[25]),"+f"(d[26]),"+f"(d[27]),"+f"(d[28]),"+f"(d[29]),"+f"(d[30]),"+f"(d[31]),"+f"(d[32]),"+f"(d[33]),"+f"(d[34]),"+f"(d[35]),"+f"(d[36]),"+f"(d[37]),"+f"(d[38]),"+f"(d[39]),"+f"(d[40]),"+f"(d[41]),"+f"(d[42]),"+f"(d[43])
   : "r"(a[0]), "r"(a[1]), "r"(a[2]), "r"(a[3]), "l"(db), "r"(sd));
}
template<> __device__ __forceinline__ void wgmma_rs<80,0>(float* d, const uint32_t* a, uint64_t db, int sd) {
  asm volatile("{\n.reg .pred p;\nsetp.ne.b32 p, %45, 0;\nwgmma.mma_async.sync.aligned.m64n80k16.f32.bf16.bf16 {%0,%1,%2,%3,%4,%5,%6,%7,%8,%9,%10,%11,%12,%13,%14,%15,%16,%17,%18,%19,%20,%21,%22,%23,%24,%25,%26,%27,%28,%29,%30,%31,%32,%33,%34,%35,%36,%37,%38,%39}, {%40,%41,%42,%43}, %44, p, 1, 1, 0;\n}\n"
   : "+f"(d[0]),"+f"(d[1]),"+f"(d[2]),"+f"(d[3]),"+f"(d[4]),"+f"(d[5]),"+f"(d[6]),"+f"(d[7]),"+f"(d[8]),"+f"(d[9]),"+f"(d[10]),"+f"(d[11]),"+f"(d[12]),"+f"(d[13]),"+f"(d[14]),"+f"(d[15]),"+f"(d[16]),"+f"(d[17]),"+f"(d[18]),"+f"(d[19]),"+f"(d[20]),"+f"(d[21]),"+f"(d[22]),"+f"(d[23]),"+f"(d[24]),"+f"(d[25]),"+f"(d[26]),"+f"(d[27]),"+f"(d[28]),"+f"(d[29]),"+f"(d[30]),"+f"(d[31]),"+f"(d[32]),"+f"(d[33]),"+f"(d[34]),"+f"(d[35]),"+f"(d[36]),"+f"(d[37]),"+f"(d[38]),"+f"(d[39])
   : "r"(a[0]), "r"(a[1]), "r"(a[2]), "r"(a[3]), "l"(db), "r"(sd));
}
template<> __device__ __forceinline__ void wgmma_rs<72,0>(float* d, const uint32_t* a, uint64_t db, int sd) {
  asm volatile("{\n.reg .pred p;\nsetp.ne.b32 p, %41, 0;\nwgmma.mma_async.sync.aligned.m64n72k16.f32.bf16.bf16 {%0,%1,%2,%3,%4,%5,%6,%7,%8,%9,%10,%11,%12,%13,%14,%15,%16,%17,%18,%19,%20,%21,%22,%23,%24,%25,%26,%27,%28,%29,%30,%31,%32,%33,%34,%35}, {%36,%37,%38,%39}, %40, p, 1, 1, 0;\n}\n"
   : "+f"(d[0]),"+f"(d[1]),"+f"(d[2]),"+f"(d[3]),"+f"(d[4]),"+f"(d[5]),"+f"(d[6]),"+f"(d[7]),"+f"(d[8]),"+f"(d[9]),"+f"(d[10]),"+f"(d[11]),"+f"(d[12]),"+f"(d[13]),"+f"(d[14]),"+f"(d[15]),"+f"(d[16]),"+f"(d[17]),"+f"(d[18]),"+f"(d[19]),"+f"(d[20]),"+f"(d[21]),"+f"(d[22]),"+f"(d[23]),"+f"(d[24]),"+f"(d[25]),"+f"(d[26]),"+f"(d[27]),"+f"(d[28]),"+f"(d[29]),"+f"(d[30]),"+f"(d[31]),"+f"(d[32]),"+f"(d[33]),"+f"(d[34]),"+f"(d[35])
   : "r"(a[0]), "r"(a[1]), "r"(a[2]), "r"(a[3]), "l"(db), "r"(sd));
}
template<> __device__ __forceinline__ void wgmma_rs<64,0>(float* d, const uint32_t* a, uint64_t db, int sd) {
  asm volatile("{\n.reg .pred p;\nsetp.ne.b32 p, %37, 0;\nwgmma.mma_async.sync.aligned.m64n64k16.f32.bf16.bf16 {%0,%1,%2,%3,%4,%5,%6,%7,%8,%9,%10,%11,%12,%13,%14,%15,%16,%17,%18,%19,%20,%21,%22,%23,%24,%25,%26,%27,%28,%29,%30,%31}, {%32,%33,%34,%35}, %36, p, 1, 1, 0;\n}\n"
   : "+f"(d[0]),"+f"(d[1]),"+f"(d[2]),"+f"(d[3]),"+f"(d[4]),"+f"(d[5]),"+f"(d[6]),"+f"(d[7]),"+f"(d[8]),"+f"(d[9]),"+f"(d[10]),"+f"(d[11]),"+f"(d[12]),"+f"(d[13]),"+f"(d[14]),"+f"(d[15]),"+f"(d[16]),"+f"(d[17]),"+f"(d[18]),"+f"(d[19]),"+f"(d[20]),"+f"(d[21]),"+f"(d[22]),"+f"(d[23]),"+f"(d[24]),"+f"(d[25]),"+f"(d[26]),"+f"(d[27]),"+f"(d[28]),"+f"(d[29]),"+f"(d[30]),"+f"(d[31])
   : "r"(a[0]), "r"(a[1]), "r"(a[2]), "r"(a[3]), "l"(db), "r"(sd));
}
template<> __device__ __forceinline__ void wgmma_ss<64,0,1>(float* d, uint64_t da, uint64_t db, int sd) {
  asm volatile("{\n.reg .pred p;\nsetp.ne.b32 p, %34, 0;\nwgmma.mma_async.sync.aligned.m64n64k16.f32.bf16.bf16 {%0,%1,%2,%3,%4,%5,%6,%7,%8,%9,%10,%11,%12,%13,%14,%15,%16,%17,%18,%19,%20,%21,%22,%23,%24,%25,%26,%27,%28,%29,%30,%31}, %32, %33, p, 1, 1, 0, 1;\n}\n"
   : "+f"(d[0]),"+f"(d[1]),"+f"(d[2]),"+f"(d[3]),"+f"(d[4]),"+f"(d[5]),"+f"(d[6]),"+f"(d[7]),"+f"(d[8]),"+f"(d[9]),"+f"(d[10]),"+f"(d[11]),"+f"(d[12]),"+f"(d[13]),"+f"(d[14]),"+f"(d[15]),"+f"(d[16]),"+f"(d[17]),"+f"(d[18]),"+f"(d[19]),"+f"(d[20]),"+f"(d[21]),"+f"(d[22]),"+f"(d[23]),"+f"(d[24]),"+f"(d[25]),"+f"(d[26]),"+f"(d[27]),"+f"(d[28]),"+f"(d[29]),"+f"(d[30]),"+f"(d[31])
   : "l"(da), "l"(db), "r"(sd));
}
template<> __device__ __forceinline__ void wgmma_ss<64,1,1>(float* d, uint64_t da, uint64_t db, int sd) {
  asm volatile("{\n.reg .pred p;\nsetp.ne.b32 p, %34, 0;\nwgmma.mma_async.sync.aligned.m64n64k16.f32.bf16.bf16 {%0,%1,%2,%3,%4,%5,%6,%7,%8,%9,%10,%11,%12,%13,%14,%15,%16,%17,%18,%19,%20,%21,%22,%23,%24,%25,%26,%27,%28,%29,%30,%31}, %32, %33, p, 1, 1, 1, 1;\n}\n"
   : "+f"(d[0]),"+f"(d[1]),"+f"(d[2]),"+f"(d[3]),"+f"(d[4]),"+f"(d[5]),"+f"(d[6]),"+f"(d[7]),"+f"(d[8]),"+f"(d[9]),"+f"(d[10]),"+f"(d[11]),"+f"(d[12]),"+f"(d[13]),"+f"(d[14]),"+f"(d[15]),"+f"(d[16]),"+f"(d[17]),"+f"(d[18]),"+f"(d[19]),"+f"(d[20]),"+f"(d[21]),"+f"(d[22]),"+f"(d[23]),"+f"(d[24]),"+f"(d[25]),"+f"(d[26]),"+f"(d[27]),"+f"(d[28]),"+f"(d[29]),"+f"(d[30]),"+f"(d[31])
   : "l"(da), "l"(db), "r"(sd));
}
template<> __device__ __forceinline__ void wgmma_ss<192,0,1>(float* d, uint64_t da, uint64_t db, int sd) {
  asm volatile("{\n.reg .pred p;\nsetp.ne.b32 p, %98, 0;\nwgmma.mma_async.sync.aligned.m64n192k16.f32.bf16.bf16 {%0,%1,%2,%3,%4,%5,%6,%7,%8,%9,%10,%11,%12,%13,%14,%15,%16,%17,%18,%19,%20,%21,%22,%23,%24,%25,%26,%27,%28,%29,%30,%31,%32,%33,%34,%35,%36,%37,%38,%39,%40,%41,%42,%43,%44,%45,%46,%47,%48,%49,%50,%51,%52,%53,%54,%55,%56,%57,%58,%59,%60,%61,%62,%63,%64,%65,%66,%67,%68,%69,%70,%71,%72,%73,%74,%75,%76,%77,%78,%79,%80,%81,%82,%83,%84,%85,%86,%87,%88,%89,%90,%91,%92,%93,%94,%95}, %96, %97, p, 1, 1, 0, 1;\n}\n"
   : "+f"(d[0]),"+f"(d[1]),"+f"(d[2]),"+f"(d[3]),"+f"(d[4]),"+f"(d[5]),"+f"(d[6]),"+f"(d[7]),"+f"(d[8]),"+f"(d[9]),"+f"(d[10]),"+f"(d[11]),"+f"(d[12]),"+f"(d[13]),"+f"(d[14]),"+f"(d[15]),"+f"(d[16]),"+f"(d[17]),"+f"(d[18]),"+f"(d[19]),"+f"(d[20]),"+f"(d[21]),"+f"(d[22]),"+f"(d[23]),"+f"(d[24]),"+f"(d[25]),"+f"(d[26]),"+f"(d[27]),"+f"(d[28]),"+f"(d[29]),"+f"(d[30]),"+f"(d[31]),"+f"(d[32]),"+f"(d[33]),"+f"(d[34]),"+f"(d[35]),"+f"(d[36]),"+f"(d[37]),"+f"(d[38]),"+f"(d[39]),"+f"(d[40]),"+f"(d[41]),"+f"(d[42]),"+f"(d[43]),"+f"(d[44]),"+f"(d[45]),"+f"(d[46]),"+f"(d[47]),"+f"(d[48]),"+f"(d[49]),"+f"(d[50]),"+f"(d[51]),"+f"(d[52]),"+f"(d[53]),"+f"(d[54]),"+f"(d[55]),"+f"(d[56]),"+f"(d[57]),"+f"(d[58]),"+f"(d[59]),"+f"(d[60]),"+f"(d[61]),"+f"(d[62]),"+f"(d[63]),"+f"(d[64]),"+f"(d[65]),"+f"(d[66]),"+f"(d[67]),"+f"(d[68]),"+f"(d[69]),"+f"(d[70]),"+f"(d[71]),"+f"(d[72]),"+f"(d[73]),"+f"(d[74]),"+f"(d[75]),"+f"(d[76]),"+f"(d[77]),"+f"(d[78]),"+f"(d[79]),"+f"(d[80]),"+f"(d[81]),"+f"(d[82]),"+f"(d[83]),"+f"(d[84]),"+f"(d[85]),"+f"(d[86]),"+f"(d[87]),"+f"(d[88]),"+f"(d[89]),"+f"(d[90]),"+f"(d[91]),"+f"(d[92]),"+f"(d[93]),"+f"(d[94]),"+f"(d[95])
   : "l"(da), "l"(db), "r"(sd));
}
template<> __device__ __forceinline__ void wgmma_ss<192,1,1>(float* d, uint64_t da, uint64_t db, int sd) {
  asm volatile("{\n.reg .pred p;\nsetp.ne.b32 p, %98, 0;\nwgmma.mma_async.sync.aligned.m64n192k16.f32.bf16.bf16 {%0,%1,%2,%3,%4,%5,%6,%7,%8,%9,%10,%11,%12,%13,%14,%15,%16,%17,%18,%19,%20,%21,%22,%23,%24,%25,%26,%27,%28,%29,%30,%31,%32,%33,%34,%35,%36,%37,%38,%39,%40,%41,%42,%43,%44,%45,%46,%47,%48,%49,%50,%51,%52,%53,%54,%55,%56,%57,%58,%59,%60,%61,%62,%63,%64,%65,%66,%67,%68,%69,%70,%71,%72,%73,%74,%75,%76,%77,%78,%79,%80,%81,%82,%83,%84,%85,%86,%87,%88,%89,%90,%91,%92,%93,%94,%95}, %96, %97, p, 1, 1, 1, 1;\n}\n"
   : "+f"(d[0]),"+f"(d[1]),"+f"(d[2]),"+f"(d[3]),"+f"(d[4]),"+f"(d[5]),"+f"(d[6]),"+f"(d[7]),"+f"(d[8]),"+f"(d[9]),"+f"(d[10]),"+f"(d[11]),"+f"(d[12]),"+f"(d[13]),"+f"(d[14]),"+f"(d[15]),"+f"(d[16]),"+f"(d[17]),"+f"(d[18]),"+f"(d[19]),"+f"(d[20]),"+f"(d[21]),"+f"(d[22]),"+f"(d[23]),"+f"(d[24]),"+f"(d[25]),"+f"(d[26]),"+f"(d[27]),"+f"(d[28]),"+f"(d[29]),"+f"(d[30]),"+f"(d[31]),"+f"(d[32]),"+f"(d[33]),"+f"(d[34]),"+f"(d[35]),"+f"(d[36]),"+f"(d[37]),"+f"(d[38]),"+f"(d[39]),"+f"(d[40]),"+f"(d[41]),"+f"(d[42]),"+f"(d[43]),"+f"(d[44]),"+f"(d[45]),"+f"(d[46]),"+f"(d[47]),"+f"(d[48]),"+f"(d[49]),"+f"(d[50]),"+f"(d[51]),"+f"(d[52]),"+f"(d[53]),"+f"(d[54]),"+f"(d[55]),"+f"(d[56]),"+f"(d[57]),"+f"(d[58]),"+f"(d[59]),"+f"(d[60]),"+f"(d[61]),"+f"(d[62]),"+f"(d[63]),"+f"(d[64]),"+f"(d[65]),"+f"(d[66]),"+f"(d[67]),"+f"(d[68]),"+f"(d[69]),"+f"(d[70]),"+f"(d[71]),"+f"(d[72]),"+f"(d[73]),"+f"(d[74]),"+f"(d[75]),"+f"(d[76]),"+f"(d[77]),"+f"(d[78]),"+f"(d[79]),"+f"(d[80]),"+f"(d[81]),"+f"(d[82]),"+f"(d[83]),"+f"(d[84]),"+f"(d[85]),"+f"(d[86]),"+f"(d[87]),"+f"(d[88]),"+f"(d[89]),"+f"(d[90]),"+f"(d[91]),"+f"(d[92]),"+f"(d[93]),"+f"(d[94]),"+f"(d[95])
   : "l"(da), "l"(db), "r"(sd));
}

__device__ __forceinline__ void stats_publish(uint32_t sb, int layer, int rb, int hg, int ht, uint32_t tag) {
  const int lane = ht & 31, w = ht >> 5, g = lane >> 2, t = lane & 3, ks = hg & 3;
  uint32_t xa;
  if (layer == 0) {
    const int row = 16 * w + (lane & 15), kc = 2 * ks + (lane >> 4);
    xa = row * 128 + ((kc ^ (row & 7)) << 4);
  } else {
    const int k = 16 * ks + (lane & 7) + 8 * (lane >> 4), pc = 2 * w + ((lane >> 3) & 1);
    xa = k * 128 + ((pc ^ (k & 7)) << 4);
  }
  float s[4] = {0.f, 0.f, 0.f, 0.f}, q[4] = {0.f, 0.f, 0.f, 0.f};
#pragma unroll 1
  for (int c = hg >> 2; c < 8; c += 2) {
    uint32_t A[2][4];
    mbar_wait(sb + SM_BAR + 8 * (B_XF + c), layer);
#pragma unroll
    for (int h = 0; h < 2; h++) {
      if (layer == 0) ldsm4(A[h], sb + SM_X + c * 16384 + h * 8192 + xa);
      else ldsm4t(A[h], sb + SM_X + c * 16384 + h * 8192 + xa);
    }
    if (c >= 6) ATS(48, 256);
    if (c < 2) ATS(51, 256);
#pragma unroll
    for (int r = 0; r < 4; r++)
#pragma unroll
      for (int i = 0; i < 2; i++) {
        const uint32_t v = A[r >> 1][2 * i + (r & 1)];
        const float a = bf_lo(v), b = bf_hi(v);
        s[r] += a + b; q[r] = fmaf(a, a, q[r]); q[r] = fmaf(b, b, q[r]);
      }
  }
#pragma unroll
  for (int r = 0; r < 2; r++) {
    s[r] = ((t & 2) ? s[r + 2] : s[r]) + __shfl_xor_sync(~0u, (t & 2) ? s[r] : s[r + 2], 2);
    q[r] = ((t & 2) ? q[r + 2] : q[r]) + __shfl_xor_sync(~0u, (t & 2) ? q[r] : q[r + 2], 2);
  }
  s[0] = ((t & 1) ? s[1] : s[0]) + __shfl_xor_sync(~0u, (t & 1) ? s[0] : s[1], 1);
  q[0] = ((t & 1) ? q[1] : q[0]) + __shfl_xor_sync(~0u, (t & 1) ? q[0] : q[1], 1);
  st_part(&g_part[(rb * 8 + hg) * 128 + 64 * (t >> 1) + 16 * w + 8 * (t & 1) + g], s[0], q[0], tag);
  ATS(49, 256);
}
__device__ __forceinline__ void stats_gather(uint32_t sb, int rb, int ht, uint32_t tag) {
  const uint2* src = &g_part[rb * 8 * 128 + ht];
  uint2 v[8];
  for (int it = 0;; it++) {
    uint32_t bad = 0;
#pragma unroll
    for (int i = 0; i < 8; i++) v[i] = ld_part(src + i * 128);
#pragma unroll
    for (int i = 0; i < 8; i++) bad |= v[i].y ^ tag;
    if (__all_sync(~0u, (bad & 7u) == 0)) break;
    if (it > (1 << 22)) __trap();
  }
  float s = 0.f, q = 0.f;
#pragma unroll
  for (int i = 0; i < 8; i++) { s += __uint_as_float(v[i].x); q += __uint_as_float(v[i].y); }
  const float mean = s * (1.f / DM);
  const float rstd = rsqrt_approx(fmaxf(q * (1.f / DM) - mean * mean, 0.f) + 1e-5f);
  asm volatile("st.shared.v2.f32 [%0], {%1,%2};" ::"r"(sb + SM_ST + ht * 8), "f"(mean), "f"(rstd) : "memory");
  __syncwarp();
  if (elect_one()) mbar_arrive(sb + SM_BAR + 8 * B_STF);
}
__device__ __forceinline__ void halo_receive(uint32_t sb, int layer, int rb, int hg, int ht) {
  const int lane = ht & 31, h = ht >> 5;
  uint4 kv = make_uint4(0, 0, 0, 0);
  mbar_wait(sb + SM_BAR + 8 * B_SD, layer);
  if (rb & 7) {
    const uint32_t tag = 2 * lds32(sb + SM_EP) + layer + 1;
    const uint4* src = &g_halo[((rb - 1) * 8 + hg) * 192 + h * 48];
    if (layer == 0) delay<D_HALO>(); else delay<D_HALO1>();
    uint4 a;
    uint2 b;
    int it = 0;
    do {
      a = ld_tagged(src + lane); b = ld_part((const uint2*)(src + 32) + lane);
      if (++it > (1 << 22)) __trap();
    } while (!__all_sync(~0u, a.w == tag && b.y == tag));
    kv = make_uint4(a.x, a.y, movm_t(a.z), movm_t(b.x));
  }
  sts128(sb + SM_KVX + h * 512 + lane * 16, kv);
  ATS(61, 256);
  bar_arrive(7, 160);
  if (elect_one()) mbar_arrive(sb + SM_BAR + 8 * B_HF);
}

__device__ __forceinline__ void halo_receive1(uint32_t sb, int layer, int rb, int hg, int lane, uint32_t tag) {
  uint4 a[4];
  uint2 b[4];
  mbar_wait(sb + SM_BAR + 8 * B_SD, layer);
  if (rb & 7) {
    const uint4* src = &g_halo[((rb - 1) * 8 + hg) * 192];
    if (layer == 0) delay<D_HALO>(); else delay<D_HALO1>();
    for (int it = 0;; it++) {
      uint32_t bad = 0;
#pragma unroll
      for (int h = 0; h < 4; h++) { a[h] = ld_tagged(src + h * 48 + lane); b[h] = ld_part((const uint2*)(src + h * 48 + 32) + lane); }
#pragma unroll
      for (int h = 0; h < 4; h++) {
        bad |= (a[h].w ^ tag) | (b[h].y ^ tag);
        a[h].z = movm_t(a[h].z); a[h].w = movm_t(b[h].x);
      }
      if (__all_sync(~0u, bad == 0)) break;
      if (it > (1 << 22)) __trap();
    }
  } else {
#pragma unroll
    for (int h = 0; h < 4; h++) a[h] = make_uint4(0, 0, 0, 0);
  }
#pragma unroll
  for (int h = 0; h < 4; h++) sts128(sb + SM_KVX + h * 512 + lane * 16, a[h]);
  ATS(61, 448);
  bar_arrive(7, 64);
  if (lane < 4) mbar_arrive(sb + SM_BAR + 8 * B_HF);
}

template <bool TR>
__device__ __forceinline__ void gemm_section(float* acc, float2* cs, uint32_t sb, int layer, int wg, int w, int lane) {
  const uint32_t bar = sb + SM_BAR;
  const bool leader = (w == 0) && (lane == 0);
  auto issue = [&](int c, int slot) {
    mbar_wait(bar + 8 * (B_XF + c), layer);
    mbar_wait(bar + 8 * (B_KVF + c), layer);
    const uint64_t da = mkdesc(sb + SM_X + c * 16384 + wg * 8192, TR ? 8192 : 16, 1024, 1);
    const uint64_t db = mkdesc(sb + SM_W + slot * 24576, 8192, 1024, 1);
    wg_fence();
#pragma unroll
    for (int ks = 0; ks < 4; ks++) wgmma_ss<192, TR ? 1 : 0, 1>(acc, da + (TR ? ks * 128 : ks * 2), db + ks * 128, (c | ks) != 0);
    wg_commit();
  };
  auto step = [&](int c, int slot) {
    issue(c, slot);
    wg_wait<1>();
    if (leader) mbar_arrive(bar + 8 * (B_KVE + c - 1));
  };
  if (!TR) bar_sync(0, NTHREADS);
  issue(0, 0);
  if (threadIdx.x == 0) TS(2 + layer * 20 + 0);
  if (threadIdx.x == 128 && layer == 1) TS(60);
  step(1, 1); step(2, 2); step(3, 0); step(4, 1);
  auto ld_cs = [&](int j0) {
#pragma unroll
    for (int j = j0; j < j0 + 8; j++) cs[j] = lds64f(sb + SM_CS + 4 * (8 * j + 2 * (lane & 3)));
  };
  if (TR) ld_cs(8);
  step(5, 2);
  if (!TR && !CS_LATE0) { mbar_wait(bar + 8 * B_CSF, 0); ld_cs(8); }
  if (TR || !CS_LATE0) ld_cs(16);
  if (wg == 0) bar_sync(5, 256);
  issue(6, 0);
  issue(7, 1);
  if (wg == 1) bar_arrive(5, 256);
  if (!TR && CS_LATE0) { mbar_wait(bar + 8 * B_CSF, 0); ld_cs(8); ld_cs(16); }
}

__device__ __forceinline__ void attn_phase(const Params& p, uint32_t sb, int layer, int rb, int hg, int wg, int w) {
  const int lane = opaque_tid() & 31;
  const int g = lane >> 2, t = lane & 3;
  const uint32_t bar = sb + SM_BAR;
  const int row0 = 64 * wg + 16 * w;
  const bool leader = (w == 0) && (lane == 0);
  float acc[96];
  float2 cs[24];
  if (layer) gemm_section<true>(acc, cs, sb, layer, wg, w, lane);
  else gemm_section<false>(acc, cs, sb, layer, wg, w, lane);
  ATS(41, 224);
  mbar_wait(bar + 8 * B_STF, layer);
  const uint32_t tag = 2 * lds32(sb + SM_EP) + layer + 1;
  const float2 st0 = lds64f(sb + SM_ST + (row0 + g) * 8), st1 = lds64f(sb + SM_ST + (row0 + g + 8) * 8);
  const float mean0 = st0.x, rstd0 = st0.y, mean1 = st1.x, rstd1 = st1.y;
  wg_wait<0>();
  if (threadIdx.x == 0) TS(2 + layer * 20 + 1);
  ATS(39, 224);
  if (leader) mbar_arrive(bar + 8 * B_QDONE);

  uint32_t fp[4][4], fl[4][4], fh[4][4], qa[4][4];
  const int cw = 4 * wg + w;
  {
    const float nm0 = -mean0 * rstd0, nm1 = -mean1 * rstd1;
    const uint32_t kvx = sb + SM_KVX + cw * 2048 + lane * 16;
#pragma unroll
    for (int h = 0; h < 4; h++)
#pragma unroll
      for (int k = 0; k < 4; k++) {
        const int j = 8 + (k >> 1) * 8 + 2 * h + (k & 1);
        fh[h][k] = packbf(fmaf(acc[4 * j + 2], rstd1, nm1 * cs[j].x), fmaf(acc[4 * j + 3], rstd1, nm1 * cs[j].y));
      }
    if (cw == 7) {
      uint4* halo = &g_halo[(rb * 8 + hg) * 192];
#pragma unroll
      for (int h = 0; h < 4; h++) {
        st_tagged3(halo + h * 48 + lane, fh[h][0], fh[h][1], fh[h][2], tag);
        asm volatile("st.relaxed.gpu.global.v2.u32 [%0], {%1,%2};" ::"l"((uint2*)(halo + h * 48 + 32) + lane), "r"(fh[h][3]), "r"(tag) : "memory");
      }
      if (elect_one()) mbar_arrive(bar + 8 * B_SD);
      if (layer == TLAYER && threadIdx.x == 224) TS(47);
    }
#pragma unroll
    for (int h = 0; h < 4; h++) { fh[h][2] = movm_t(fh[h][2]); fh[h][3] = movm_t(fh[h][3]); }
    if (cw != 7) {
#pragma unroll
      for (int h = 0; h < 4; h++) sts128(kvx + 2048 + h * 512, make_uint4(fh[h][0], fh[h][1], fh[h][2], fh[h][3]));
      bar_arrive(8 + cw, 64);
    }
    sched_fence<6>();
    if (layer == TLAYER && threadIdx.x == 0) TS(45);
#pragma unroll
    for (int j = 0; j < 8; j++) cs[j] = lds64f(sb + SM_CS + 4 * (8 * j + 2 * t));
#pragma unroll
    for (int h = 0; h < 4; h++)
#pragma unroll
      for (int k = 0; k < 4; k++) {
        const int j = 8 + (k >> 1) * 8 + 2 * h + (k & 1);
        fl[h][k] = packbf(fmaf(acc[4 * j], rstd0, nm0 * cs[j].x), fmaf(acc[4 * j + 1], rstd0, nm0 * cs[j].y));
        if (k >= 2) fl[h][k] = movm_t(fl[h][k]);
      }
#pragma unroll
    for (int h = 0; h < 4; h++) {
#pragma unroll
      for (int dh = 0; dh < 2; dh++) {
        const int j = 2 * h + dh;
        const float2 c2 = cs[j];
        qa[h][2 * dh] = packbf(fmaf(-mean0, c2.x, acc[4 * j + 0]), fmaf(-mean0, c2.y, acc[4 * j + 1]));
        qa[h][2 * dh + 1] = packbf(fmaf(-mean1, c2.x, acc[4 * j + 2]), fmaf(-mean1, c2.y, acc[4 * j + 3]));
      }
    }
    if (threadIdx.x == 0) TS(2 + layer * 20 + 2);
    sched_fence<0>();
    bar_sync(7 + cw, cw == 0 && !HALO_W14 ? 160 : 64);
#pragma unroll
    for (int h = 0; h < 4; h++) {
      const uint4 v = lds128(kvx + h * 512);
      fp[h][0] = v.x; fp[h][1] = v.y; fp[h][2] = v.z; fp[h][3] = v.w;
    }
    if (threadIdx.x == 0) TS(2 + layer * 20 + 4);
  }

  const bool u0 = 2 * t > g, u1 = 2 * t + 1 > g;
  const uint32_t mU = (u0 ? 0x0000ffffu : 0u) | (u1 ? 0xffff0000u : 0u);
  const float cl2 = 0.25f * 1.4426950408889634f;
  const float sc0 = rstd0 * cl2, sc1 = rstd1 * cl2;
  const float cneg = ((rb & 7) == 0 && cw == 0) ? -INFINITY : 0.f;
  float v[4][4];
#pragma unroll
  for (int h = 0; h < 4; h++) {
    float T0[4] = {cneg, cneg, cneg, cneg}, T1[4] = {0.f, 0.f, 0.f, 0.f}, T2[4] = {0.f, 0.f, 0.f, 0.f};
    mma_bf16(T1, qa[h], fl[h][0], fl[h][1]);
    mma_bf16(T2, qa[h], fh[h][0], fh[h][1]);
    mma_bf16(T0, qa[h], fp[h][0], fp[h][1]);
    v[h][0] = u0 ? T0[0] : T1[0]; v[h][1] = u1 ? T0[1] : T1[1];
    v[h][2] = u0 ? T1[2] : T2[2]; v[h][3] = u1 ? T1[3] : T2[3];
  }
  float m0[4], m1[4];
#pragma unroll
  for (int h = 0; h < 4; h++) { m0[h] = fmaxf(v[h][0], v[h][1]); m1[h] = fmaxf(v[h][2], v[h][3]); }
#pragma unroll
  for (int o = 1; o <= 2; o <<= 1) {
#pragma unroll
    for (int h = 0; h < 4; h++) {
      m0[h] = fmaxf(m0[h], __shfl_xor_sync(~0u, m0[h], o));
      m1[h] = fmaxf(m1[h], __shfl_xor_sync(~0u, m1[h], o));
    }
  }
  float O0[4][4], O1[4][4], Z[4][4];
#pragma unroll
  for (int h = 0; h < 4; h++) {
    const float mm0 = -m0[h] * sc0, mm1 = -m1[h] * sc1;
    const uint32_t P0 = packbf(ex2(fmaf(v[h][0], sc0, mm0)), ex2(fmaf(v[h][1], sc0, mm0)));
    const uint32_t P1 = packbf(ex2(fmaf(v[h][2], sc1, mm1)), ex2(fmaf(v[h][3], sc1, mm1)));
#pragma unroll
    for (int k = 0; k < 4; k++) O0[h][k] = O1[h][k] = Z[h][k] = 0.f;
    mma_bf16_k8(Z[h], P0, P1, 0x3f803f80u);
    mma_bf16_k8(O0[h], P0 & ~mU, P1 & mU, fl[h][2]); mma_bf16_k8(O1[h], P0 & ~mU, P1 & mU, fl[h][3]);
    mma_bf16_k8(O0[h], P0 & mU, 0u, fp[h][2]); mma_bf16_k8(O1[h], P0 & mU, 0u, fp[h][3]);
    mma_bf16_k8(O0[h], 0u, P1 & ~mU, fh[h][2]); mma_bf16_k8(O1[h], 0u, P1 & ~mU, fh[h][3]);
  }
  const uint32_t ob = sb + SM_OST + wg * 8192;
  const int o_row = 16 * w + (lane & 7) + 8 * ((lane >> 3) & 1);
#pragma unroll
  for (int h = 0; h < 4; h++) {
    const float i0 = rcp_approx(Z[h][0]), i1 = rcp_approx(Z[h][2]);
    const int ch = 2 * h + (lane >> 4);
    stsm4(ob + o_row * 128 + ((ch ^ (o_row & 7)) << 4), packbf(O0[h][0] * i0, O0[h][1] * i0), packbf(O0[h][2] * i1, O0[h][3] * i1),
          packbf(O1[h][0] * i0, O1[h][1] * i0), packbf(O1[h][2] * i1, O1[h][3] * i1));
  }
  if (threadIdx.x == 0) TS(2 + layer * 20 + 5);
  ATS(57, 128); ATS(20, 96);
  bar_sync(2 + wg, 128);
  if (w == 0 && elect_one()) {
    fence_async_smem();
    tma_st(&p.mapO, hg * 64, rb * 128 + wg * 64, ob);
    bulk_commit();
    mbar_arrive(bar + 8 * B_AD);
    bulk_wait_all();
    red_relaxed(&g_cnt[(C_O + rb) * 32]);
    mbar_arrive(bar + 8 * B_OST);
    if (threadIdx.x == 0) TS(2 + layer * 20 + 6);
  }
  __syncwarp();
}

__device__ __forceinline__ void proj_phase(const Params& p, uint32_t sb, int layer, int rb, int q, int wg, int w) {
  const int lane = opaque_tid() & 31;
  const bool TR = layer != 0;
  const int t = lane & 3;
  const uint32_t bar = sb + SM_BAR;
  const uint32_t rbx = sb + SM_R + wg * 8192;
  uint32_t res[16];
  mbar_wait(bar + 8 * B_RF, layer);
  if (threadIdx.x == 0) TS(2 + layer * 20 + 7);
  if (!TR) {
#pragma unroll
    for (int j = 0; j < 8; j += 2) {
      const int mi = lane >> 3;
      const int row = 16 * w + (lane & 7) + 8 * (mi & 1), ch = j + (mi >> 1);
      ldsm4(&res[2 * j], rbx + row * 128 + ((ch ^ (row & 7)) << 4));
    }
  } else {
#pragma unroll
    for (int j = 0; j < 8; j += 2) {
      const int mi = lane >> 3;
      const int line = 8 * (j + (mi >> 1)) + (lane & 7), pc = 2 * w + (mi & 1);
      ldsm4t(&res[2 * j], rbx + line * 128 + ((pc ^ (line & 7)) << 4));
    }
  }
  bar_sync(2 + wg, 128);
  float acc[32];
#pragma unroll
  for (int i = 0; i < 16; i++) {
    asm volatile("shl.b32 %0, %1, 16;" : "=f"(acc[2 * i]) : "r"(res[i]));
    asm volatile("and.b32 %0, %1, 0xffff0000;" : "=f"(acc[2 * i + 1]) : "r"(res[i]));
  }
  const uint32_t tag = part_tag(lds32(sb + SM_EP), 2 * layer + 1);
  mbar_wait(bar + 8 * B_ZF, layer);
  mbar_wait(bar + 8 * B_WOF, layer);
#pragma unroll P_UNROLL
  for (int c = 0; c < 8; c++) {
    mbar_wait(bar + 8 * (B_OF + c), layer);
    if (c == 0 && threadIdx.x == 0) TS(2 + layer * 20 + 8);
    const uint64_t da = mkdesc(sb + sm_o(c) + wg * 8192, 16, 1024, 1);
    const uint64_t db = mkdesc(sb + SM_WO + c * 8192, 8192, 1024, 1);
    wg_fence();
#pragma unroll
    for (int ks = 0; ks < 4; ks++) wgmma_ss<64, 0, 1>(acc, da + ks * 2, db + ks * 128, 1);
    wg_commit();
  }
  wg_wait<0>();
#pragma unroll
  for (int i = 0; i < 32; i++) asm volatile("" : "+f"(acc[i]) :: "memory");
  if (threadIdx.x == 0) TS(2 + layer * 20 + 9);
  if (lane == 0 && w == 0) mbar_arrive(bar + 8 * B_PDONE);
  {
    float s[4], qq[4];
#pragma unroll
    for (int k = 0; k < 4; k++) { s[k] = acc[k]; qq[k] = acc[k] * acc[k]; }
#pragma unroll
    for (int j = 1; j < 8; j++)
#pragma unroll
      for (int k = 0; k < 4; k++) { s[k] += acc[4 * j + k]; qq[k] = fmaf(acc[4 * j + k], acc[4 * j + k], qq[k]); }
    const float s0 = s[0] + s[1], s1 = s[2] + s[3], q0 = qq[0] + qq[1], q1 = qq[2] + qq[3];
    float sr = ((t & 1) ? s1 : s0) + __shfl_xor_sync(~0u, (t & 1) ? s0 : s1, 1);
    float qr = ((t & 1) ? q1 : q0) + __shfl_xor_sync(~0u, (t & 1) ? q0 : q1, 1);
    sr += __shfl_xor_sync(~0u, sr, 2);
    qr += __shfl_xor_sync(~0u, qr, 2);
    if (t < 2) st_part(&g_part[(rb * 8 + q) * 128 + 64 * wg + 16 * w + (lane >> 2) + 8 * t], sr, qr, tag);
    __syncwarp();
    if (elect_one()) mbar_arrive(bar + 8 * B_PS);
    sched_fence<7>();
  }
#pragma unroll
  for (int j = 0; j < 8; j += 2) {
    const int mi = lane >> 3;
    const int line = 8 * (j + (mi >> 1)) + (lane & 7), pc = 2 * w + (mi & 1);
    stsm4t(rbx + line * 128 + ((pc ^ (line & 7)) << 4), packbf(acc[4 * j], acc[4 * j + 1]), packbf(acc[4 * j + 2], acc[4 * j + 3]),
           packbf(acc[4 * j + 4], acc[4 * j + 5]), packbf(acc[4 * j + 6], acc[4 * j + 7]));
  }
  fence_writer();
  bar_sync(2 + wg, 128);
  if (w == 0 && elect_one()) {
    fence_reader();
    fence_async_global();
    tma_st(&p.mapXT, rb * 128 + wg * 64, (2 * layer) * DM + q * 64, rbx);
    bulk_commit();
    if (threadIdx.x == 0) TS(2 + layer * 20 + 10);
    bulk_wait_all();
    red_relaxed(&g_cnt[C_CS * 32 + 2 + layer]);
    if (wg == 0) mbar_arrive(bar + 8 * B_RE);
  }
  __syncwarp();
}
__device__ __forceinline__ void proj_stats(uint32_t sb, int layer, int rb, int q, int lane, uint32_t tag) {
  const int r = 16 * q + (lane & 15);
  const uint2* src = &g_part[rb * 8 * 128 + r];
  uint32_t* dst = g_stats + layer * LSEQ + (rb >> 1) * 256 + ((r >> 2) & 1) * 128 + ((rb & 1) * 16 + (r >> 3)) * 4 + (r & 3);
  mbar_wait(sb + SM_BAR + 8 * B_PS, layer);
  delay<D_PST>();
  for (int it = 0;; it++) {
    uint2 v[8];
#pragma unroll
    for (int i = 0; i < 8; i++) v[i] = ld_part(src + i * 128);
    float s[4], qq[4];
    uint32_t bad = 0;
#pragma unroll
    for (int i = 0; i < 4; i++) {
      s[i] = __uint_as_float(v[i].x) + __uint_as_float(v[i + 4].x);
      qq[i] = __uint_as_float(v[i].y) + __uint_as_float(v[i + 4].y);
      bad |= (v[i].y ^ tag) | (v[i + 4].y ^ tag);
    }
    const float mean = ((s[0] + s[1]) + (s[2] + s[3])) * (1.f / DM);
    const float rstd = rsqrt_approx(fmaxf(fmaf((qq[0] + qq[1]) + (qq[2] + qq[3]), 1.f / DM, -mean * mean), 0.f) + 1e-5f);
    const bool ok = __all_sync(~0u, (bad & 7u) == 0);
    if (ok && lane < 16)
      asm volatile("st.relaxed.gpu.global.u32 [%0], %1;" ::"l"(dst), "r"(max(packbf(NORM_FMA ? -mean * rstd : -mean, rstd), 1u)) : "memory");
    if (ok) break;
    if (it > (1 << 22)) __trap();
  }
}

#define NA 14
#define NP 15
template <int M0, int M1> __device__ __forceinline__ void conv_load(uint32_t* A, uint32_t pe) {
#pragma unroll
  for (int m = M0; m < M1; m++) {
    asm volatile("ld.shared.v2.b32 {%0,%1}, [%2];" : "=r"(A[4 * m]), "=r"(A[4 * m + 1]) : "r"(pe + 256 * m) : "memory");
    A[4 * m + 2] = lds32(pe + 256 * m - 4);
  }
}
__device__ __forceinline__ uint32_t copy_reg(uint32_t v, uint32_t zero) { uint32_t r; asm volatile("or.b32 %0, %1, %2;" : "=r"(r) : "r"(v), "r"(zero)); return r; }
__device__ __forceinline__ uint32_t copy_reg2(uint32_t v, uint32_t zero) { uint32_t r; asm volatile("xor.b32 %0, %1, %2;" : "=r"(r) : "r"(v), "r"(zero)); return r; }
__device__ __forceinline__ void conv_park(uint32_t* P, uint32_t pe) {
#pragma unroll
  for (int m = 0; m < NP; m++)
#pragma unroll
    for (int k = 0; k < 3; k++) P[3 * m + k] = lds32(pe + 256 * m - 4 + 4 * k);
}
__device__ __forceinline__ void conv_unpark(uint32_t* A, const uint32_t* P, uint32_t zero) {
#pragma unroll
  for (int m = 0; m < NP; m++) {
    A[4 * m + 2] = copy_reg(P[3 * m], zero); A[4 * m] = copy_reg(P[3 * m + 1], zero);
    A[4 * m + 3] = copy_reg2(P[3 * m + 1], zero); A[4 * m + 1] = copy_reg(P[3 * m + 2], zero);
  }
}
template <int M0, int M1> __device__ __forceinline__ void conv_mmas(float* acc, const uint32_t* A, uint64_t d) {
  if constexpr (M0 < M1) {
    wgmma_rs<128 - 8 * (M0 / 2), 0>(acc, A + 4 * M0, d + (uint64_t)(4 * M0), M0 != 0);
    conv_mmas<M0 + 1, M1>(acc, A, d);
  }
}
struct SumAddr { uint32_t l0, l1, l2, se, so; };
__device__ __forceinline__ SumAddr conv_sum_addr(uint32_t sb, int c) {
  auto ua = [&](int j) { return sb + cv_u(0) + (127 - (j >> 3)) * 16 + (j & 7) * 2; };
  auto sa = [&](int hc) { const int ci = hc & ~1; return sb + cv_s(0) + ((ci >> 3) & 1) * 1024 + (ci >> 4) * 128 + (((ci ^ (ci >> 4)) & 7) << 4) + (hc & 1) * 8; };
  const int j0 = 4 * (c - 1);
  return {ua(j0 - 2), ua(j0), ua(j0 + 4), sa((c + 1) & 127), sa(c) + 2048};
}
__device__ __forceinline__ void sts64(uint32_t a, uint32_t x, uint32_t y) { asm volatile("st.shared.v2.b32 [%0], {%1,%2};" ::"r"(a), "r"(x), "r"(y) : "memory"); }
__device__ __forceinline__ void conv_sums(const SumAddr& sa, int lc, int c) {
  uint32_t e[4], o[4];
  {
    const float2 em = lds64f(sa.l1 + lc * 32768), om = lds64f(sa.l1 + lc * 32768 + CV_UH);
    e[0] = lds32(sa.l0 + lc * 32768); o[0] = lds32(sa.l0 + lc * 32768 + CV_UH);
    e[3] = lds32(sa.l2 + lc * 32768); o[3] = lds32(sa.l2 + lc * 32768 + CV_UH);
    e[1] = __float_as_uint(em.x); e[2] = __float_as_uint(em.y); o[1] = __float_as_uint(om.x); o[2] = __float_as_uint(om.y);
  }
  uint32_t s7e[2], s7o[2], s9e[2], s9o[2];
  uint32_t pw[4], sh[3];
#pragma unroll
  for (int k = 0; k < 4; k++) pw[k] = hadd2(e[k], o[k]);
#pragma unroll
  for (int k = 0; k < 3; k++) sh[k] = __byte_perm(pw[k], pw[k + 1], 0x5432);
#pragma unroll
  for (int k = 0; k < 2; k++) {
    const uint32_t t3 = hadd2(hadd2(sh[k], sh[k + 1]), pw[k + 1]);
    s7e[k] = hadd2(t3, o[k]); s7o[k] = hadd2(t3, e[k + 2]);
    s9e[k] = hadd2(s7o[k], pw[k]); s9o[k] = hadd2(s7e[k], pw[k + 2]);
  }
  if (c == 127) s9e[0] = s9e[1] = s9o[0] = s9o[1] = 0u;
  sts64(sa.se + lc * 32768, s9e[0], s9e[1]); sts64((sa.se ^ 16) + lc * 32768, s9o[0], s9o[1]);
  sts64(sa.so + lc * 32768, s7e[0], s7e[1]); sts64((sa.so ^ 16) + lc * 32768, s7o[0], s7o[1]);
}

__device__ __forceinline__ void conv_epi(uint32_t sb, int layer, int cta, int ch, int c0, uint4 x0, uint4 x1) {
  uint4 v[2][4];
  const uint4 xr[2] = {x0, x1};
  mbar_wait(sb + SM_BAR + 8 * (B_P + ch), layer);
#pragma unroll
  for (int u = 0; u < 2; u++) {
    const uint32_t pb = sb + cv_pb(ch) + u * (CV_PBW / 2) + c0 * 16;
#pragma unroll
    for (int k = 0; k < 4; k++) v[u][k] = lds128(pb + k * CV_PBW);
  }
#pragma unroll
  for (int u = 0; u < 2; u++) {
    uint4 o;
    o.x = hadd2(xr[u].x, hadd2(hadd2(v[u][0].x, v[u][1].x), hadd2(v[u][2].x, v[u][3].x)));
    o.y = hadd2(xr[u].y, hadd2(hadd2(v[u][0].y, v[u][1].y), hadd2(v[u][2].y, v[u][3].y)));
    o.z = hadd2(xr[u].z, hadd2(hadd2(v[u][0].z, v[u][1].z), hadd2(v[u][2].z, v[u][3].z)));
    o.w = hadd2(xr[u].w, hadd2(hadd2(v[u][0].w, v[u][1].w), hadd2(v[u][2].w, v[u][3].w)));
    if (layer == 0) sts128(sb + cv_s(ch) + (c0 + 128 * u) * 16, o);
    else st_tagged3((uint4*)(g_xT + (size_t)(3 * DM + cv_chan(cta, ch)) * LSEQ) + c0 + 128 * u, o.x, o.y, o.z, o.w);
  }
}
__device__ __forceinline__ void warp_release(uint32_t b) {
  fence_writer();
  __syncwarp();
  if (elect_one()) mbar_arrive(b);
}

__device__ __forceinline__ void conv_prep_load(uint32_t sb, int layer, int cta, int c, uint4 (&xr)[4], uint4 (&st)[4]) {
  sched_fence<8>();
  mbar_wait(sb + SM_BAR + 8 * B_GB, layer);
  if (threadIdx.x == 0) TS(2 + layer * 20 + 11);
  xr[0] = ld_tagged((const uint4*)(g_xT + (size_t)(2 * layer * DM + cta) * LSEQ) + c);
#pragma unroll
  for (int i = 0; i < 2; i++) st[i] = ld_tagged((const uint4*)g_stats + layer * 512 + (c >> 5) * 64 + i * 32 + (c & 31));
}
template <bool HELPER>
__device__ __forceinline__ void conv_prep(uint32_t sb, int layer, int cta, int c, uint4 (&xr)[4], uint4 (&st)[4], const SumAddr& sa) {
  const uint32_t bar = sb + SM_BAR;
  const uint4* xin = (const uint4*)(g_xT + (size_t)(2 * layer * DM + cta) * LSEQ) + c;
  for (int it = 0;; it++) {
    const uint32_t vs = min(min(min(st[0].x, st[0].y), min(st[0].z, st[0].w)), min(min(st[1].x, st[1].y), min(st[1].z, st[1].w)));
    if (__all_sync(~0u, vs != 0 && xr[0].x != ~0u)) break;
    if (it > (1 << 22)) __trap();
    if (!__all_sync(~0u, xr[0].x != ~0u)) xr[0] = ld_tagged(xin);
    if (!__all_sync(~0u, vs != 0)) {
#pragma unroll
      for (int i = 0; i < 2; i++) st[i] = ld_tagged((const uint4*)g_stats + layer * 512 + (c >> 5) * 64 + i * 32 + (c & 31));
    }
  }
  const uint32_t nm[4] = {__byte_perm(st[0].x, st[0].y, 0x5410), __byte_perm(st[0].z, st[0].w, 0x5410), __byte_perm(st[1].x, st[1].y, 0x5410), __byte_perm(st[1].z, st[1].w, 0x5410)};
  const uint32_t rs[4] = {__byte_perm(st[0].x, st[0].y, 0x7632), __byte_perm(st[0].z, st[0].w, 0x7632), __byte_perm(st[1].x, st[1].y, 0x7632), __byte_perm(st[1].z, st[1].w, 0x7632)};
  if (threadIdx.x == 0) TS(2 + layer * 20 + 12);
  const int a = c & 127, h = c >> 7;
#pragma unroll
  for (int i = 0; i < 4; i++) {
    if (i == 1) {
      mbar_wait(bar + 8 * B_XV, layer);
#pragma unroll
      for (int j = 1; j < 4; j++) xr[j] = ld_tagged(xin + j * (128 * LSEQ / 8));
      if (HELPER) {
        mbar_wait(bar + 8 * B_U, layer);
        conv_sums(sa, 0, c);
        fence_async_smem();
        bar_arrive(7, 256);
        sched_fence<1>();
        if (layer == 1 && c == 0) TS(46);
      }
    }
    const uint32_t x[4] = {xr[i].x, xr[i].y, xr[i].z, xr[i].w};
    uint32_t u[4];
#pragma unroll
    for (int k = 0; k < 4; k++)
      u[k] = NORM_FMA ? hfma2(x[k], rs[k], nm[k]) : hmul2(hadd2(x[k], nm[k]), rs[k]);
    sts128(sb + cv_u(i) + h * CV_UH + (127 - a) * 16, make_uint4(u[0], u[1], u[2], u[3]));
    warp_release(bar + 8 * (B_U + i));
    sched_fence<2>();
  }
}
__device__ __forceinline__ void conv_zero(uint32_t sb, int ht) {
  if (ht < 96) {
    const int ch = ht / 24, h2 = (ht / 12) & 1, qq = ht % 12;
    sts128(sb + cv_u(ch) + h2 * CV_UH + (128 + qq) * 16, make_uint4(0, 0, 0, 0));
  }
  if (ht >= 80) {
    const int i = ht - 80, ch = i / 12, q2 = i % 12;
    const int w2 = q2 < 2 ? 1 : q2 < 6 ? 2 : 3, cc = q2 < 2 ? q2 : q2 < 6 ? q2 - 2 : q2 - 6;
    sts128(sb + cv_pb(ch) + w2 * CV_PBW + (cc & 1) * (CV_PBW / 2) + (cc >> 1) * 16, make_uint4(0, 0, 0, 0));
  }
}

#define HANDOVER 1
template <int R>
__device__ __forceinline__ void conv_round(uint32_t sb, int layer, int wg, uint32_t* A, const uint32_t* P, uint32_t pb, uint32_t pe2) {
  const uint32_t bar = sb + SM_BAR;
  const int ch = 2 * R + 1 - wg;
  float acc[64];
  const uint64_t d = mkdesc(sb + cv_u(ch), CV_UH, 128, 0);
  FTS(39);
  if (R == 0) {
    mbar_wait(bar + 8 * (B_U + ch), layer);
    fence_reader();
  }
  sched_fence<3>();
  if (R == 1 || wg == 0) bar_sync(10 + ch, 256);
  if (layer == 0 && ch > 0 && ((PAUSE >> (ch - 1)) & 1)) mbar_wait(bar + 8 * (B_E + ch - 1), 0);
  if (layer == 0 && ch > 0 && ((PAUSE >> (ch + 3)) & 1)) mbar_wait(bar + 8 * (B_P + ch - 1), 0);
  FTS(41);
  if (ch == 0 && threadIdx.x == 128) TS(2 + layer * 20 + 13);
  wg_fence();
  conv_mmas<0, 1>(acc, A, d); conv_mmas<2, NA + 1>(acc, A, d);
  wg_commit();
  FTS(51);
  if (HANDOVER == 0 && (R == 0 || wg == 1)) bar_arrive(11 + ch, 256);
  bar_sync(7 + ch, 256);
  wg_fence();
  conv_mmas<1, 2>(acc, A, d); conv_mmas<NA + 1, 17>(acc, A, d);
  wgmma_ss<64, 1, 1>(acc, mkdesc(sb + cv_s(ch), 1024, 1024, 1), mkdesc(sb + cv_ft(ch), 256, 16, 0), 1);
  wgmma_ss<64, 1, 1>(acc, mkdesc(sb + cv_s(ch) + 2048, 1024, 1024, 1), mkdesc(sb + cv_ft(ch) + 512, 256, 16, 0), 1);
  wg_commit();
  if (HANDOVER == 1 && (R == 0 || wg == 1)) bar_arrive(11 + ch, 256);
  FTS(61);
  wg_wait<0>();
#pragma unroll
  for (int j = 0; j < 16; j += 2)
    stsm4t(pb + R * 65536 - j * 128, packbf(acc[4 * j], acc[4 * j + 1]), packbf(acc[4 * j + 2], acc[4 * j + 3]),
           packbf(acc[4 * j + 4], acc[4 * j + 5]), packbf(acc[4 * j + 6], acc[4 * j + 7]));
  __syncwarp();
  if (elect_one()) mbar_arrive(bar + 8 * (B_P + ch));
  if (threadIdx.x == 0) TS(2 + layer * 20 + 14 + R);
  FTS(57);
  if (R == 0) {
    conv_unpark(A, P, opaque_tid() >> 10);
    mbar_wait(bar + 8 * (B_U + ch + 2), layer);
    fence_reader();
    conv_load<NP, 17>(A, pe2);
#pragma unroll
    for (int m = NP; m < 17; m++) A[4 * m + 3] = lds32(pe2 + 256 * m);
  }
}
__device__ __forceinline__ void conv_phase(const Params& p, uint32_t sb, int layer, int cta) {
  const int tid = opaque_tid();
  const int wg = __shfl_sync(~0u, tid >> 7, 0), w = __shfl_sync(~0u, (tid >> 5) & 3, 0);
  const uint32_t bar = sb + SM_BAR;
  uint32_t A[68], P[3 * NP];
  const uint32_t pe = sb + cv_pe(1 - wg) + 4 * (16 + 16 * w + 2 * ((tid & 31) >> 2) - 4 * (tid & 3));
  mbar_wait(bar + 8 * B_PE, layer);
  conv_load<0, 17>(A, pe);
#pragma unroll
  for (int m = 0; m < 17; m++) A[4 * m + 3] = copy_reg(A[4 * m], tid >> 10);
  if (wg == 0) {
    uint4 xr[4], st[4];
    if (PARK_FIRST) conv_park(P, pe + 65536);
    conv_prep_load(sb, layer, cta, tid + 128, xr, st);
    if (!PARK_FIRST) conv_park(P, pe + 65536);
    conv_prep<false>(sb, layer, cta, opaque_tid() + 128, xr, st, SumAddr());
  } else {
    conv_park(P, pe + 65536);
  }
  uint32_t pb;
  {
    const int l2 = opaque_tid() & 31, mt = l2 >> 3;
    pb = sb + cv_pb(1 - wg) + w * CV_PBW + (mt & 1) * (CV_PBW / 2) + (127 - 8 * (mt >> 1) - (l2 & 7) + w) * 16;
  }
  conv_round<0>(sb, layer, wg, A, P, pb, pe + 65536);
  conv_round<1>(sb, layer, wg, A, P, pb, 0);
  if (G_WAIT == 1 && layer == 0) mbar_wait(bar + 8 * (B_E + 3), layer);
  if (G_WAIT == 2 && layer == 0) mbar_wait(bar + 8 * (B_P + 3), layer);
}

__device__ __forceinline__ void final_phase(const Params& p, uint32_t sb, int cta, int wg, int w) {
  if (wg == 1 && w == 3) return;
  const int lane = opaque_tid() & 31, g = lane >> 2, t = lane & 3;
  const int lc = wg ? w : 3;
  const int pos0 = (cta & 31) * 64, ch0 = 128 * lc + (cta >> 5) * 32;
  const bf16* src = g_xT + (size_t)(3 * DM + ch0 + 8 * (g >> 1) + (g & 1)) * LSEQ + pos0;
  bf16* dst = p.out + (size_t)(2 * (pos0 & 1023) + (pos0 >> 10)) * DM + ch0 + 8 * t;
  constexpr int RS = 2 * DM;
  int it = 0;
  mbar_wait(sb + SM_BAR + 8 * (B_E + lc), 1);
  delay<D_FIN>();
  if (wg == 0) {
    uint2 v[4];
    for (;;) {
#pragma unroll
      for (int q = 0; q < 4; q++) v[q] = ld_part((const uint2*)(src + 2 * q * LSEQ + 16 * w + 4 * t));
      if (__all_sync(~0u, max(max(v[0].x, v[1].x), max(v[2].x, v[3].x)) != ~0u)) break;
      if (++it > (1 << 22)) __trap();
    }
    if (threadIdx.x == 0) TS(42);
    dst += (16 * w + 4 * (g >> 1) + (g & 1)) * RS;
    *(uint4*)dst = make_uint4(movm_t(v[0].x), movm_t(v[1].x), movm_t(v[2].x), movm_t(v[3].x));
    *(uint4*)(dst + 2 * RS) = make_uint4(movm_t(v[0].y), movm_t(v[1].y), movm_t(v[2].y), movm_t(v[3].y));
  } else {
    uint4 v[2][4];
    bool ok;
    do {
      ok = true;
#pragma unroll
      for (int h = 0; h < 2; h++)
#pragma unroll
        for (int q = 0; q < 4; q++) v[h][q] = ld_tagged((const uint4*)(src + 2 * q * LSEQ + 32 * h + 8 * t));
#pragma unroll
      for (int h = 0; h < 2; h++)
#pragma unroll
        for (int q = 0; q < 4; q++) ok = ok && v[h][q].x != ~0u;
      if (++it > (1 << 22)) __trap();
    } while (!__all_sync(~0u, ok));
    dst += (8 * (g >> 1) + (g & 1)) * RS;
#pragma unroll
    for (int h = 0; h < 2; h++) {
      *(uint4*)(dst + (32 * h + 0) * RS) = make_uint4(movm_t(v[h][0].x), movm_t(v[h][1].x), movm_t(v[h][2].x), movm_t(v[h][3].x));
      *(uint4*)(dst + (32 * h + 2) * RS) = make_uint4(movm_t(v[h][0].y), movm_t(v[h][1].y), movm_t(v[h][2].y), movm_t(v[h][3].y));
      *(uint4*)(dst + (32 * h + 4) * RS) = make_uint4(movm_t(v[h][0].z), movm_t(v[h][1].z), movm_t(v[h][2].z), movm_t(v[h][3].z));
      *(uint4*)(dst + (32 * h + 6) * RS) = make_uint4(movm_t(v[h][0].w), movm_t(v[h][1].w), movm_t(v[h][2].w), movm_t(v[h][3].w));
    }
  }
  if (threadIdx.x == 0) TS(43);
  if (threadIdx.x == 192) TS(63);
  if (threadIdx.x == 0) LTS(1);
}

struct cplx { float r, i; };
__device__ __forceinline__ cplx cmul(cplx a, cplx b) { return {fmaf(a.r, b.r, -a.i * b.i), fmaf(a.r, b.i, a.i * b.r)}; }
__device__ __forceinline__ cplx csqr(cplx a) { return {fmaf(a.r, a.r, -a.i * a.i), (a.r + a.r) * a.i}; }
__device__ __forceinline__ cplx cexp_l(float ar2, float ai, float l) {
  const float m = ex2(ar2 * l);
  const float x = ai * l;
  return {m * __cosf(x), m * __sinf(x)};
}

__device__ __forceinline__ void colsum_publish(uint32_t sb, int rb, int hg, int ht, uint32_t tag) {
  const int lane = ht & 31, q = lane & 15, h = lane >> 4;
  const uint32_t src = sb + SM_CW + (ht >> 5) * 4096 + h * 128 + (q & 1) * 8;
  float s[4] = {0.f, 0.f, 0.f, 0.f};
#pragma unroll 8
  for (int r = 0; r < 16; r++) {
    const float2 v = lds64f(src + r * 256 + (((q >> 1) ^ ((2 * r + h) & 7)) << 4));
    s[0] += bf_lo(__float_as_uint(v.x)); s[1] += bf_hi(__float_as_uint(v.x));
    s[2] += bf_lo(__float_as_uint(v.y)); s[3] += bf_hi(__float_as_uint(v.y));
  }
#pragma unroll
  for (int k = 0; k < 4; k++) s[k] += __shfl_xor_sync(~0u, s[k], 16);
  if (h == 0)
    st_tagged3(&g_colsum[(hg * 16 + rb) * 48 + (ht >> 5) * 16 + q], (__float_as_uint(s[0]) & ~7u) | tag, __float_as_uint(s[1]),
               __float_as_uint(s[2]), __float_as_uint(s[3]));
}
__device__ __forceinline__ void colsum_gather(uint32_t sb, int hg, int ht, uint32_t tag) {
  const int lane = ht & 31, rec = (ht >> 5) * 16 + (lane & 15);
  const uint4* src = &g_colsum[(hg * 16 + (lane >> 4) * 8) * 48 + rec];
  float s[4] = {0.f, 0.f, 0.f, 0.f};
#pragma unroll 1
  for (int h = 0; h < 2; h++, src += 4 * 48) {
    uint4 v[4];
    int it = 0;
    do {
#pragma unroll
      for (int i = 0; i < 4; i++) v[i] = ld_tagged(src + i * 48);
      if (++it > (1 << 22)) __trap();
    } while (!__all_sync(~0u, (v[0].x & 7u) == tag && (v[1].x & 7u) == tag && (v[2].x & 7u) == tag && (v[3].x & 7u) == tag));
#pragma unroll
    for (int i = 0; i < 4; i++) {
      s[0] += __uint_as_float(v[i].x & ~7u); s[1] += __uint_as_float(v[i].y); s[2] += __uint_as_float(v[i].z); s[3] += __uint_as_float(v[i].w);
    }
  }
#pragma unroll
  for (int k = 0; k < 4; k++) s[k] += __shfl_xor_sync(~0u, s[k], 16);
  if (lane < 16) sts128f(sb + SM_CS + rec * 16, s[0], s[1], s[2], s[3]);
}

__device__ __forceinline__ uint32_t packh(float lo, float hi) { uint32_t r; asm("cvt.rn.f16x2.f32 %0, %1, %2;" : "=r"(r) : "f"(hi), "f"(lo)); return r; }
__device__ __forceinline__ void mma_f16(float* d, uint32_t a0, uint32_t a1, uint32_t a2, uint32_t a3, uint32_t b0, uint32_t b1) {
  asm volatile("mma.sync.aligned.m16n8k16.row.col.f32.f16.f16.f32 {%0,%1,%2,%3}, {%4,%5,%6,%7}, {%8,%9}, {%0,%1,%2,%3};"
      : "+f"(d[0]), "+f"(d[1]), "+f"(d[2]), "+f"(d[3]) : "r"(a0), "r"(a1), "r"(a2), "r"(a3), "r"(b0), "r"(b1));
}
struct HSeed { uint32_t r, i; };
__device__ __forceinline__ HSeed hseed(cplx s) { return {packh(s.r, s.r), packh(s.i, s.i)}; }
__device__ __forceinline__ void hcmul(uint32_t& o_r, uint32_t& o_i, uint32_t br, uint32_t bi, HSeed s) {
  asm("{\n.reg .b32 t, u;\nmul.rn.f16x2 t, %3, %5;\nneg.f16x2 t, t;\nmul.rn.f16x2 u, %3, %4;\nfma.rn.f16x2 %0, %2, %4, t;\nfma.rn.f16x2 %1, %2, %5, u;\n}"
      : "=&r"(o_r), "=&r"(o_i) : "r"(br), "r"(bi), "r"(s.r), "r"(s.i));
}
struct HTile { uint32_t r[4], i[4]; };
__device__ __forceinline__ void tile_set(HTile& t, int k, cplx a, cplx b) { t.r[k] = packh(a.r, b.r); t.i[k] = packh(a.i, b.i); }
__device__ __forceinline__ void tile_upper(HTile& t, HSeed s) { hcmul(t.r[2], t.i[2], t.r[0], t.i[0], s); hcmul(t.r[3], t.i[3], t.r[1], t.i[1], s); }
__device__ __forceinline__ HTile tile_shift(const HTile& t, HSeed s) {
  HTile o;
#pragma unroll
  for (int k = 0; k < 4; k++) hcmul(o.r[k], o.i[k], t.r[k], t.i[k], s);
  return o;
}
__device__ __forceinline__ void tile_put(const HTile& t, uint32_t a) {
  sts128(a, make_uint4(t.r[0], t.r[1], t.r[2], t.r[3]));
  sts128(a + 512, make_uint4(t.i[0], t.i[1], t.i[2], t.i[3]));
}
__device__ __forceinline__ HTile tile_get(uint32_t a) { HTile o; ldsm4t(o.r, a); ldsm4t(o.i, a + 512); return o; }
__device__ __forceinline__ void tile_mma(float* T, const HTile& a0, const HTile& a1, const HTile& b) {
  mma_f16(T, a0.r[0], a0.r[1], a0.r[2], a0.r[3], b.r[0], b.r[1]);
  mma_f16(T, a0.i[0], a0.i[1], a0.i[2], a0.i[3], b.i[0], b.i[1]);
  mma_f16(T, a1.r[0], a1.r[1], a1.r[2], a1.r[3], b.r[2], b.r[3]);
  mma_f16(T, a1.i[0], a1.i[1], a1.i[2], a1.i[3], b.i[2], b.i[3]);
}
__device__ __forceinline__ void tile_mma2(float* T, float* U, const HTile& a0, const HTile& a1, const HTile& b, const HTile& c) {
  mma_f16(T, a0.r[0], a0.r[1], a0.r[2], a0.r[3], b.r[0], b.r[1]);
  mma_f16(U, a0.r[0], a0.r[1], a0.r[2], a0.r[3], c.r[0], c.r[1]);
  mma_f16(T, a0.i[0], a0.i[1], a0.i[2], a0.i[3], b.i[0], b.i[1]);
  mma_f16(U, a0.i[0], a0.i[1], a0.i[2], a0.i[3], c.i[0], c.i[1]);
  mma_f16(T, a1.r[0], a1.r[1], a1.r[2], a1.r[3], b.r[2], b.r[3]);
  mma_f16(U, a1.r[0], a1.r[1], a1.r[2], a1.r[3], c.r[2], c.r[3]);
  mma_f16(T, a1.i[0], a1.i[1], a1.i[2], a1.i[3], b.i[2], b.i[3]);
  mma_f16(U, a1.i[0], a1.i[1], a1.i[2], a1.i[3], c.i[2], c.i[3]);
}
__device__ __forceinline__ void kgen_unit(uint32_t tab, uint32_t taba, float ar2, float ai, cplx c, float (&T)[5][4]) {
  const cplx z1 = cexp_l(ar2, ai, 1.f), z16 = cexp_l(ar2, ai, 16.f), z256 = cexp_l(ar2, ai, 256.f);
  HTile a0, a1, b0, b1;
  {
    const cplx y1 = {z16.r, -z16.i}, y2 = csqr(y1), y3 = cmul(y2, y1), y4 = csqr(y2), y5 = cmul(y4, y1), y6 = csqr(y3), y7 = cmul(y4, y3);
    HTile t;
    tile_set(t, 0, {1.f, 0.f}, y1); tile_set(t, 1, y2, y3); tile_set(t, 2, y4, y5); tile_set(t, 3, y6, y7);
    const HTile u = tile_shift(t, hseed(csqr(y4)));
    __syncwarp();
    tile_put(t, tab); tile_put(u, tab + 1024);
    __syncwarp();
    a0 = tile_get(taba); a1 = tile_get(taba + 256);
  }
  const cplx z2 = csqr(z1), z4 = csqr(z2), z8 = csqr(z4);
  const HSeed h8 = hseed(z8);
  const cplx d = cmul(c, z256), e = cmul(d, z256);
  {
    const cplx z512 = csqr(z256), f = cmul(e, z512), f8 = cmul(f, z8), f16 = cmul(f, z16), e4 = cmul(e, z4);
    HTile t, u;
    tile_set(t, 0, e4, cmul(e, z8)); tile_set(t, 1, cmul(e4, z8), cmul(e, z16));
    tile_upper(t, hseed(z256));
    tile_set(u, 0, f8, f16); tile_set(u, 1, cmul(f8, z256), cmul(f16, z256));
    tile_upper(u, hseed(z512));
    __syncwarp();
    tile_put(t, tab); tile_put(u, tab + 1024);
    __syncwarp();
    b0 = tile_get(tab); b1 = tile_get(tab + 1024);
  }
  {
    const cplx d2 = cmul(d, z2), d4 = cmul(d, z4);
    HTile t;
    tile_set(t, 0, d2, d4); tile_set(t, 1, cmul(d2, z4), cmul(d, z8));
    tile_upper(t, h8);
    __syncwarp();
    tile_put(t, tab);
    __syncwarp();
    tile_mma2(T[3], T[4], a0, a1, b0, b1);
    b0 = tile_get(tab);
  }
  {
    const cplx c1 = cmul(c, z1), c2 = cmul(c, z2), c3 = cmul(c1, z2), c4 = cmul(c, z4);
    HTile t;
    tile_set(t, 0, c1, c2); tile_set(t, 1, c3, c4); tile_set(t, 2, cmul(c1, z4), cmul(c2, z4)); tile_set(t, 3, cmul(c3, z4), cmul(c4, z4));
    const HTile u = tile_shift(t, h8);
    __syncwarp();
    tile_put(t, tab); tile_put(u, tab + 1024);
    __syncwarp();
    tile_mma(T[2], a0, a1, b0);
    b0 = tile_get(tab); b1 = tile_get(tab + 1024);
    tile_mma2(T[0], T[1], a0, a1, b0, b1);
  }
}
struct ModeIn { uint2 ar, ai, br, bi, cr, ci; };
__device__ __forceinline__ ModeIn load_modes(const Params& p, int idx) {
  return {*(const uint2*)(p.a_re + idx), *(const uint2*)(p.a_im + idx), *(const uint2*)(p.b_re + idx),
          *(const uint2*)(p.b_im + idx), *(const uint2*)(p.c_re + idx), *(const uint2*)(p.c_im + idx)};
}
__device__ __forceinline__ float bf_el(uint2 v, int k) { const uint32_t x = (k & 2) ? v.y : v.x; return (k & 1) ? bf_hi(x) : bf_lo(x); }
struct KGen { float4 cur; float T[5][4]; };
__device__ __forceinline__ uint32_t kgen_slot(uint32_t sb, int ht, int u) {
  return sb + (u < 3 ? SM_KC + (ht >> 5) * (KC_STRIDE * 2) + (u - 1) * 512 + (ht & 31) * 16 + 16 : SM_HALO + 1024 + ht * 16);
}
__device__ __forceinline__ void kgen_setup(KGen& s, uint32_t sb, int cta, int ht, const ModeIn& in, bf16 logdt, bf16 dskip) {
  const float dt = __bfloat162float(__float2bfloat16_rn(expf(__bfloat162float(logdt))));
  float mx = 0.f, k0 = 0.f, ar2[4];
  cplx c[4];
#pragma unroll
  for (int k = 0; k < 4; k++) {
    ar2[k] = (dt * bf_el(in.ar, k)) * 1.4426950408889634f;
    c[k] = cmul({bf_el(in.cr, k), bf_el(in.ci, k)}, {dt * bf_el(in.br, k), dt * bf_el(in.bi, k)});
    k0 += c[k].r;
    mx = fmaxf(mx, fmaxf(fabsf(c[k].r), fabsf(c[k].i)) * ex2(fmaxf(ar2[k] * 2048.f, 0.f)));
  }
  const int ex = min(max(267 - (int)(__reduce_max_sync(~0u, __float_as_uint(mx)) >> 23), 1), 253);
  const float sc = __uint_as_float(ex << 23);
#pragma unroll
  for (int o = 16; o > 0; o >>= 1) k0 += __shfl_xor_sync(~0u, k0, o);
  if ((ht & 31) == 0) {
    const uint32_t kc = sb + SM_KC + (ht >> 5) * (KC_STRIDE * 2);
    sts16(kc, __bfloat16_as_ushort(__float2bfloat16_rn(k0 + __bfloat162float(dskip))));
    sts16(kc + 641 * 2, 0);
    sts32f(kc + 644 * 2, __uint_as_float((254 - ex) << 23));
  }
  s.cur = make_float4(ar2[0], dt * bf_el(in.ai, 0), c[0].r * sc, c[0].i * sc);
#pragma unroll
  for (int k = 1; k < 4; k++) sts128f(kgen_slot(sb, ht, k), ar2[k], dt * bf_el(in.ai, k), c[k].r * sc, c[k].i * sc);
#pragma unroll
  for (int i = 0; i < 5; i++) s.T[i][0] = s.T[i][1] = s.T[i][2] = s.T[i][3] = 0.f;
}
__device__ __forceinline__ void kgen_finish(KGen& s, uint32_t sb, int cta, int ht) {
  const int w = ht >> 5, lane = ht & 31, g = lane >> 2, t = lane & 3;
  const uint32_t kc = sb + SM_KC + w * KC_STRIDE * 2;
  __syncwarp();
  const float inv = __uint_as_float(lds32(kc + 644 * 2));
  auto put = [&](int idx, float v) {
    sts16(kc + idx * 2, __bfloat16_as_ushort(__float2bfloat16_rn(v)));
  };
#pragma unroll
  for (int hi = 0; hi < 2; hi++)
#pragma unroll
    for (int lo = 0; lo < 2; lo++) {
      const int i = g + 8 * hi, j = 2 * t + lo, e = 2 * hi + lo;
      put(16 * i + 1 + j, s.T[0][e] * inv);
      put(16 * i + 9 + j, s.T[1][e] * inv);
      put(257 + 8 * i + j, s.T[2][e] * inv);
      put(385 + 4 * i + (j & 3) + 64 * (j >> 2), s.T[3][e] * inv);
      put(513 + 2 * i + lo + 32 * t, s.T[4][e] * inv);
    }
}

__device__ __forceinline__ void expand_taps(uint32_t sb, int ht) {
  const int ch = ht >> 5, lane = ht & 31;
  const uint32_t kc = sb + SM_KC + ch * KC_STRIDE * 2;
  const uint32_t dst0 = sb + cv_pe(ch);
  auto put = [&](int G, uint32_t u0, uint32_t u1, uint32_t v0, uint32_t v1, uint32_t v2, uint32_t v3, uint32_t v4, uint32_t v5, uint32_t v6, uint32_t v7) {
    const uint32_t dst = dst0 + G * 32;
    sts128(dst, make_uint4(v0 | (u0 << 16), v1 | (u1 << 16), v2 | (v0 << 16), v3 | (v1 << 16)));
    sts128(dst + 16, make_uint4(v4 | (v2 << 16), v5 | (v3 << 16), v6 | (v4 << 16), v7 | (v5 << 16)));
  };
  {
    const uint4 q = lds128(kc + lane * 16);
    const uint32_t pv = lane ? lds32(kc + lane * 16 - 4) : 0u;
    const uint32_t dst = dst0 + (lane + 2) * 32;
    sts128(dst, make_uint4(__byte_perm(q.x, pv, 0x5410), __byte_perm(q.x, pv, 0x7632), __byte_perm(q.y, q.x, 0x5410), __byte_perm(q.y, q.x, 0x7632)));
    sts128(dst + 16, make_uint4(__byte_perm(q.z, q.y, 0x5410), __byte_perm(q.z, q.y, 0x7632), __byte_perm(q.w, q.z, 0x5410), __byte_perm(q.w, q.z, 0x7632)));
    if (lane < 4) sts128(dst0 + lane * 16, make_uint4(0, 0, 0, 0));
  }
  uint32_t a[5], b[2][3], fv[4];
  {
    const uint32_t s1 = kc + 2 * (256 + 4 * lane);
#pragma unroll
    for (int k = 0; k < 5; k++) a[k] = lds16(s1 + 2 * k);
#pragma unroll
    for (int u = 0; u < 2; u++) {
      const uint32_t s2 = kc + 2 * (384 + 2 * (lane + 32 * u));
#pragma unroll
      for (int k = 0; k < 3; k++) b[u][k] = lds16(s2 + 2 * k);
    }
#pragma unroll
    for (int k = 0; k < 4; k++) fv[k] = lds16(kc + 2 * (640 - 4 * lane - k));
  }
  const uint32_t am1 = lds16(kc + 2 * (lane ? 256 + 4 * lane : 255)), am2 = lds16(kc + 2 * (lane ? 255 + 4 * lane : 254));
  const uint32_t bm2 = lds16(kc + 2 * (lane ? 384 + 2 * lane : 383)), k1024 = lds16(kc + 2 * 512);
  put(34 + lane, am2, am1, a[0], a[0], a[1], a[2], a[2], a[2], a[3], a[4]);
#pragma unroll
  for (int u = 0; u < 2; u++) put(66 + lane + 32 * u, u ? b[u][0] : bm2, b[u][0], b[u][0], b[u][0], b[u][0], b[u][1], b[u][1], b[u][1], b[u][2], b[u][2]);
  if (lane < 10) {
    const uint32_t v = lane == 0 ? k1024 : 0u;
    put(130 + lane, v, v, v, v, v, v, v, 0u, 0u, 0u);
  }
  const uint32_t ft = sb + cv_ft(ch) + 4 * lane;
#pragma unroll
  for (int ty = 0; ty < 2; ty++) {
    const uint32_t v = fv[ty] | (fv[ty + 2] << 16);
    sts32f(ft + ty * 512, __uint_as_float(v));
    sts32f(ft + ty * 512 + 128, 0.f);
    sts32f(ft + ty * 512 + 256 + (lane < 2 ? 120 : -8), __uint_as_float(lane < 2 ? 0u : v));
    sts32f(ft + ty * 512 + 384, 0.f);
  }
}

__device__ __forceinline__ int role_id() { int v; asm volatile("mov.u32 %0, %%ctaid.x;" : "=r"(v)); return v; }
#define GMAP 8
__device__ __forceinline__ int role_rb(int cta) { return 4 * (cta >> 5) + (cta & 3); }
__device__ __forceinline__ int role_hg(int cta) { return 2 * (((cta >> 3) & 3) ^ (((cta >> 5) & 1) * 3)) + ((cta >> 2) & 1); }
__device__ __forceinline__ int role_rb2(int cta) { return cta >> 3; }
__device__ __forceinline__ int role_q2(int cta) { return cta & 7; }

__global__ void __launch_bounds__(NTHREADS, 1) fused_kernel(const __grid_constant__ Params p) {
  extern __shared__ __align__(1024) uint8_t smem[];
  const uint32_t sb = s32(smem);
  const int tid = threadIdx.x, lane = tid & 31;
  const int warp = __shfl_sync(~0u, tid >> 5, 0);
  const uint32_t bar = sb + SM_BAR;
  if (tid == 0) TS(0);
  const int cta0 = role_id();
  if (warp == 0 && elect_one()) {
    const int rb = role_rb(cta0), hg = role_hg(cta0);
#pragma unroll
    for (int c = 0; c < 2; c++) { mbar_init(bar + 8 * (B_XF + c), 1); mbar_init(bar + 8 * (B_KVF + c), 1); }
    fence_async_smem();
#pragma unroll
    for (int c = 0; c < 2; c++) {
      mbar_expect(bar + 8 * (B_XF + c), 16384);
      tma_ld(sb + SM_X + c * 16384, &p.mapX128, (rb >> 3) * DM + c * 64, (rb & 7) * 128, bar + 8 * (B_XF + c));
      mbar_expect(bar + 8 * (B_KVF + c), 24576);
      tma_ld3(sb + SM_W + c * 24576, &p.mapW3, hg * 64, c * 64, 0, bar + 8 * (B_KVF + c));
    }
  }
  if (warp == 1 && elect_one()) {
    const int rb = role_rb(cta0), hg = role_hg(cta0);
#pragma unroll
    for (int c = 2; c < 8; c++) mbar_init(bar + 8 * (B_XF + c), 1);
    mbar_init(bar + 8 * (B_KVF + 2), 1); mbar_init(bar + 8 * B_CW, 1);
    fence_async_smem();
    delay<D_START>();
    mbar_expect(bar + 8 * B_CW, 12288);
    tma_ld3(sb + SM_CW, &p.mapW3h, hg * 64, rb * 32, 0, bar + 8 * B_CW);
#pragma unroll
    for (int c = 2; c < 8; c++) {
      mbar_expect(bar + 8 * (B_XF + c), 16384);
      tma_ld(sb + SM_X + c * 16384, &p.mapX128, (rb >> 3) * DM + c * 64, (rb & 7) * 128, bar + 8 * (B_XF + c));
      if (c < 3) {
        mbar_expect(bar + 8 * (B_KVF + c), 24576);
        tma_ld3(sb + SM_W + c * 24576, &p.mapW3, hg * 64, c * 64, 0, bar + 8 * (B_KVF + c));
      }
    }
    TS(56);
  }
  if ((warp & 2) != 0 && warp < 15 && elect_one()) {
    const int grp = 1 + (warp & 1) + 2 * (warp >> 2), cnt = grp < 4 ? 1 : grp < 5 ? 2 : grp < 7 ? 4 : 8;
#pragma unroll
    for (int k = 0; k < 10; k++)
      if (k != 0 || grp > 3 || grp == 2) mbar_init(bar + 8 * (10 * grp + k), cnt);
    fence_async_smem();
  }

  if (warp < 8) {
    if (tid == 0) TS(1);
    asm volatile("setmaxnreg.inc.sync.aligned.u32 %0;" ::"n"(R_CONS));
    const int cta = role_id();
    auto warp_id = [] { return __shfl_sync(~0u, opaque_tid() >> 5, 0); };
    if (tid == 0) TS(54);
#pragma unroll 1
    for (int layer = 0; layer < 2; layer++) {
      { const int cw = warp_id(); attn_phase(p, sb, layer, role_rb(cta), role_hg(cta), cw >> 2, cw & 3); }
      if (STOP == 1 + 3 * layer) return;
      { const int cw = warp_id(); proj_phase(p, sb, layer, role_rb2(cta), role_q2(cta), cw >> 2, cw & 3); }
      if (STOP == 2 + 3 * layer) return;
      conv_phase(p, sb, layer, cta);
      if (STOP == 3 + 3 * layer) return;
    }
    { const int cw = warp_id(); final_phase(p, sb, cta, cw >> 2, cw & 3); }
  } else if (warp < 12) {
    asm volatile("setmaxnreg.dec.sync.aligned.u32 %0;" ::"n"(R_HELP));
    const int ht = tid - 256;
    const int cta = role_id(), rb = role_rb(cta), hg = role_hg(cta);
    unsigned ep0 = 0;
    if (ht == 0) ep0 = ld_relaxed(&g_cnt[C_CS * 32]);
    bar_sync(0, NTHREADS);
    if (ht == 0) {
      asm volatile("st.shared.u32 [%0], %1;" ::"r"(sb + SM_EP), "r"(ep0 / NCTA) : "memory");
      mbar_arrive(bar + 8 * B_EP);
    }
    mbar_wait(bar + 8 * B_EP, 0);
    stats_publish(sb, 0, rb, hg, opaque_tid() - 256, part_tag(lds32(sb + SM_EP), 0));
    if (ht < 48) {
      const bf16* q = (&p.a_re)[ht >> 3];
      asm volatile("prefetch.global.L2 [%0];" ::"l"(q + cv_chan(cta, (ht >> 1) & 3) * 128 + (ht & 1) * 64));
    }
    {
      KGen kg;
      const uint32_t tab0 = sb + ((ht >> 5) < 2 ? SM_T : SM_T2 - 4096) + (ht >> 5) * 2048;
      const uint32_t tab = tab0 + (ht & 31) * 16, taba = tab0 + ((ht >> 3) & 1) * 1024 + (((ht >> 1) & 8) + (ht & 7)) * 16;
      delay<D_ST0>();
      stats_gather(sb, rb, opaque_tid() - 256, part_tag(lds32(sb + SM_EP), 0));
      if (ht == 0) TS(40);
      const int chn = cv_chan(cta, ht >> 5);
      const ModeIn modes = load_modes(p, chn * 128 + (ht & 31) * 4);
      const bf16 logdt = p.log_dt[chn], dskip = p.dskip[chn];
      if (!HALO_W14 && KG_START != 4) halo_receive(sb, 0, rb, hg, opaque_tid() - 256);
      if (KG_START == 1) mbar_wait(bar + 8 * B_HF, 0);
      kgen_setup(kg, sb, cta, ht, modes, logdt, dskip);
      if (!HALO_W14 && KG_START == 4) halo_receive(sb, 0, rb, hg, opaque_tid() - 256);
      if (KG_START == 2) mbar_wait(bar + 8 * B_HF, 0);
      if (KG_START == 3) mbar_wait(bar + 8 * B_QDONE, 0);
#pragma unroll 1
      for (int u = 0; u < 4; u++) {
        if (u == KG_PRE) {
          KTS(39);
          mbar_wait(bar + 8 * B_AD, 0);
          KTS(41);
        }
        kgen_unit(tab, taba, kg.cur.x, kg.cur.y, {kg.cur.z, kg.cur.w}, kg.T);
        kg.cur = lds128f(kgen_slot(sb, opaque_tid() - 256, u + 1));
      }
      kgen_finish(kg, sb, cta, opaque_tid() - 256);
    }
    KTS(51);
    bar_sync(4, 128);
#pragma unroll 1
    for (int layer = 0; layer < 2; layer++) {
      if (STOP <= 1 + 3 * layer) return;
      mbar_wait(bar + 8 * (EXP_LATE ? B_PS : B_PDONE), layer);
      expand_taps(sb, opaque_tid() - 256);
      conv_zero(sb, opaque_tid() - 256);
      if (ht == 0) TS(52 + layer);
      warp_release(bar + 8 * B_PE);
      if (STOP <= 2 + 3 * layer) return;
      {
        uint4 xr[4], st[4];
        const int c = opaque_tid() - 256;
        const SumAddr sa = conv_sum_addr(sb, c);
        conv_prep_load(sb, layer, cta, c, xr, st);
        conv_prep<true>(sb, layer, cta, c, xr, st, sa);
        if (layer == 1 && ht == 0) TS(62);
        const bf16* xup = g_xT + (size_t)(2 * layer * DM + cta) * LSEQ + (c + 128) * 8;
        const int ahead = layer ? S_AHEAD1 : S_AHEAD0;
        mbar_wait(bar + 8 * (B_U + 3), layer);
        if (ahead == 2) {
          conv_sums(sa, 1, c);
          fence_async_smem();
          bar_arrive(8, 256);
        }
        st[0] = ldcg128(xup);
#pragma unroll
        for (int lc = 0; lc < 4; lc++) {
          if (lc < 3 && lc + ahead < 4) {
            conv_sums(sa, lc + ahead, c);
            fence_async_smem();
            bar_arrive(7 + lc + ahead, 256);
            sched_fence<4>();
          }
          if (lc < 3) st[lc + 1] = ldcg128(xup + (lc + 1) * 128 * LSEQ);
          conv_epi(sb, layer, cta, lc, c, xr[lc], st[lc]);
          warp_release(bar + 8 * (B_E + lc));
          sched_fence<5>();
          if (layer == 1 && lc == 3 && ht == 0) TS(38);
        }
      }
      if (layer == 0 && STOP > 3) {
        const int c1 = role_id();
        stats_publish(sb, 1, role_rb(c1), role_hg(c1), opaque_tid() - 256, part_tag(lds32(sb + SM_EP), 2));
        delay<D_ST>();
        stats_gather(sb, role_rb(c1), opaque_tid() - 256, part_tag(lds32(sb + SM_EP), 2));
        if (ht == 0) TS(25);
        if (!HALO_W14) halo_receive(sb, 1, role_rb(c1), role_hg(c1), opaque_tid() - 256);
      }
    }
  } else {
    asm volatile("setmaxnreg.dec.sync.aligned.u32 %0;" ::"n"(512 - 2 * R_CONS - R_HELP));
    const int cta = role_id(), rb = role_rb(cta), hg = role_hg(cta), rb2 = role_rb2(cta), q2 = role_q2(cta);
    bar_sync(0, NTHREADS);
    if (warp != 12) {
      mbar_wait(bar + 8 * B_EP, 0);
      const uint32_t tag = lds32(sb + SM_EP) % 7 + 1;
      mbar_wait(bar + 8 * B_CW, 0);
      colsum_publish(sb, rb, hg, tid - 416, tag);
      if (tid == 416) TS(50);
      delay<D_CS>();
      colsum_gather(sb, hg, tid - 416, tag);
      __syncwarp();
      if (tid == 416) TS(55);
    }
    if (elect_one()) mbar_arrive(bar + 8 * B_CSF);
    if (warp == 12) {
      if (elect_one()) {
        unsigned epoch = 0;
#pragma unroll 1
        for (int layer = 0; layer < 2; layer++) {
          auto ld_w = [&](int c, int slot) {
            const uint32_t b = bar + 8 * (B_KVF + c);
            mbar_expect(b, 24576);
            tma_ld3(sb + SM_W + slot * 24576, &p.mapW3, hg * 64, c * 64, 0, b);
          };
          if (layer == 0) {
            mbar_wait(bar + 8 * (B_KVF + 2), 0);
            if (rb2 < 4) tma_prefetch2(&p.mapWo128, q2 * 64, rb2 * 128);
            asm volatile("prefetch.tensormap [%0];" ::"l"(&p.mapO) : "memory");
            asm volatile("prefetch.tensormap [%0];" ::"l"(&p.mapO128) : "memory");
            asm volatile("prefetch.tensormap [%0];" ::"l"(&p.mapXT) : "memory");
            asm volatile("prefetch.tensormap [%0];" ::"l"(&p.mapXT3) : "memory");
            mbar_wait(bar + 8 * B_EP, 0);
            epoch = lds32(sb + SM_EP);
          } else {
            mbar_wait(bar + 8 * B_PDONE, 0);
            ld_w(0, 0); ld_w(1, 1);
            mbar_wait(bar + 8 * (W2_LATE ? B_U : B_RE), 0);
            ld_w(2, 2);
          }
          {
            int slot = 0;
#pragma unroll 1
            for (int c = 3; c < 8; c++) {
              mbar_wait(bar + 8 * (B_KVE + c - 3), layer);
              ld_w(c, slot);
              slot = slot == 2 ? 0 : slot + 1;
            }
          }
          if (STOP <= 1 + 3 * layer) return;
          mbar_wait(bar + 8 * B_QDONE, layer);
          mbar_wait(bar + 8 * B_HF, layer);
          mbar_expect(bar + 8 * B_WOF, 65536);
#pragma unroll
          for (int c = 0; c < 4; c++) tma_ld(sb + SM_WO + c * 16384, &p.mapWo128, q2 * 64, c * 128, bar + 8 * B_WOF);
          {
            const uint32_t b = bar + 8 * B_RF;
            mbar_expect(b, 16384);
            if (layer == 0) tma_ld(sb + SM_R, &p.mapX128, (rb2 >> 3) * DM + q2 * 64, (rb2 & 7) * 128, b);
            else tma_ld3(sb + SM_R, &p.mapXT3, 0, DM + q2 * 64, rb2 * 2, b);
          }
#pragma unroll
          for (int c = 0; c < 8; c++) mbar_expect(bar + 8 * (B_OF + c), 16384);
          spin_until(&g_cnt[(C_O + rb2) * 32], (2 * epoch + layer + 1) * 16);
          fence_async_global();
#pragma unroll
          for (int c = 0; c < 8; c++) {
            if (c == 4) { mbar_wait(bar + 8 * B_OST, layer); fence_async_smem(); }
            tma_ld(sb + sm_o(c), &p.mapO128, c * 64, rb2 * 128, bar + 8 * (B_OF + c));
          }
          if (STOP <= 3 + 3 * layer) return;
        }
      }
    } else if (warp == 13) {
      if (elect_one() && STOP > 1) {
        const unsigned target = (lds32(sb + SM_EP) + 1) * NCTA;
        mbar_wait(bar + 8 * B_RE, 0);
        spin_until(&g_cnt[C_CS * 32 + 2], 2 * target);
        mbar_arrive(bar + 8 * B_XV);
        if (STOP <= 3) return;
        auto ld_x = [&](int c) { tma_ld3(sb + SM_X + c * 16384, &p.mapXT3, 0, DM + c * 64, rb * 2, bar + 8 * (B_XF + c)); };
#pragma unroll
        for (int c = 0; c < 8; c++) mbar_expect(bar + 8 * (B_XF + c), 16384);
        spin_until(&g_cnt[C_G1 * 32], target);
        fence_async_global();
        fence_async_smem();
        ld_x(0); ld_x(1);
        int done = 1, it = 0;
        while (done < 4) {
          const uint4 v = ld_tagged((const uint4*)&g_cnt[C_G1 * 32]);
          const int n = 4 + ((int)(v.y - target) >> 31) + ((int)(v.z - target) >> 31) + ((int)(v.w - target) >> 31);
          if (n == done) { if (++it > (1 << 23)) __trap(); continue; }
          if (n == 4) TS(44);
          fence_async_global();
          fence_async_smem();
          const int first = n == 4 && done > 1 ? 6 + (hg >> 2) : -1;
          if (first >= 0) ld_x(first);
#pragma unroll 1
          for (int c = 2 * done; c < 2 * n; c++)
            if (c != first) ld_x(c);
          done = n;
        }
        if (STOP <= 4) return;
        mbar_wait(bar + 8 * B_RE, 1);
        spin_until(&g_cnt[C_CS * 32 + 3], 2 * target);
        mbar_arrive(bar + 8 * B_XV);
      }
    } else if (warp == 15) {
      mbar_wait(bar + 8 * B_EP, 0);
      const unsigned epoch = lds32(sb + SM_EP);
#pragma unroll 1
      for (int layer = 0; layer < 2; layer++) {
        mbar_wait(bar + 8 * (B_KVF + FILL_AT), layer);
#pragma unroll
        for (int k = 0; k < 8; k++) ((uint4*)(g_xT + (size_t)(2 * layer * DM + cta) * LSEQ))[32 * k + lane] = make_uint4(~0u, ~0u, ~0u, ~0u);
        mbar_wait(bar + 8 * (B_KVF + FILL_AT + 1), layer);
#pragma unroll
        for (int k = 0; k < 16; k++)
          ((uint4*)(g_xT + (size_t)(3 * DM + cv_chan(cta, 3 - (k >> 2))) * LSEQ))[128 * layer + 32 * (k & 3) + lane] = make_uint4(~0u, ~0u, ~0u, ~0u);
        if (lane < 4) ((uint4*)g_stats)[layer * 512 + cta * 4 + lane] = make_uint4(0, 0, 0, 0);
        __syncwarp();
        if (elect_one()) {
          red_release(&g_cnt[C_CS * 32 + layer]);
          spin_until(&g_cnt[C_CS * 32 + layer], (epoch + 1) * NCTA);
          mbar_arrive(bar + 8 * B_ZF);
          if (layer == 0 && STOP > 2) {
#pragma unroll
            for (int lc = 0; lc < 4; lc++) {
              mbar_wait(bar + 8 * (B_E + lc), 0);
              fence_reader();
              bulk_st(g_xT + (size_t)(DM + cv_chan(cta, lc)) * LSEQ, sb + cv_s(lc), 4096);
              bulk_commit();
              bulk_wait_all();
              red_relaxed(&g_cnt[C_G1 * 32 + lc]);
              if (lc == 3) TS(18);
            }
          }
        }
        __syncwarp();
        if (STOP <= 3) return;
      }
    } else if (warp == 14) {
      mbar_wait(bar + 8 * B_EP, 0);
      const unsigned epoch = lds32(sb + SM_EP);
#pragma unroll 1
      for (int layer = 0; layer < 2; layer++) {
        if (STOP <= 3 * layer) return;
        if (HALO_W14) halo_receive1(sb, layer, rb, hg, opaque_tid() & 31, 2 * epoch + layer + 1);
        if (STOP <= 1 + 3 * layer) return;
        mbar_wait(bar + 8 * B_ZF, layer);
        proj_stats(sb, layer, rb2, q2, opaque_tid() & 31, part_tag(epoch, 2 * layer + 1));
        if (layer == 1 && lane == 0) TS(5);
        delay<D_PREP>();
        if (lane == 0) mbar_arrive(bar + 8 * B_GB);
      }
    }
  }
}

typedef CUresult (*EncodeFn)(CUtensorMap*, CUtensorMapDataType, cuuint32_t, void*, const cuuint64_t*, const cuuint64_t*,
                             const cuuint32_t*, const cuuint32_t*, CUtensorMapInterleave, CUtensorMapSwizzle,
                             CUtensorMapL2promotion, CUtensorMapFloatOOBfill);

static void make_map(EncodeFn enc, CUtensorMap* m, void* ptr, uint64_t cols, uint64_t rows, uint32_t box_rows) {
  cuuint64_t dims[2] = {cols, rows};
  cuuint64_t strides[1] = {cols * 2};
  cuuint32_t box[2] = {64, box_rows};
  cuuint32_t es[2] = {1, 1};
  enc(m, CU_TENSOR_MAP_DATA_TYPE_BFLOAT16, 2, ptr, dims, strides, box, es, CU_TENSOR_MAP_INTERLEAVE_NONE,
      CU_TENSOR_MAP_SWIZZLE_128B, CU_TENSOR_MAP_L2_PROMOTION_L2_128B, CU_TENSOR_MAP_FLOAT_OOB_FILL_NONE);
}
static void make_map3(EncodeFn enc, CUtensorMap* m, void* ptr, uint64_t d0, uint64_t cols, uint64_t rows, uint64_t blk_stride,
                      uint64_t nblocks, uint32_t nblk, uint32_t box_rows = 64) {
  cuuint64_t dims[3] = {d0, rows, nblocks};
  cuuint64_t strides[2] = {cols * 2, blk_stride * 2};
  cuuint32_t box[3] = {64, box_rows, nblk};
  cuuint32_t es[3] = {1, 1, 1};
  enc(m, CU_TENSOR_MAP_DATA_TYPE_BFLOAT16, 3, ptr, dims, strides, box, es, CU_TENSOR_MAP_INTERLEAVE_NONE,
      CU_TENSOR_MAP_SWIZZLE_128B, CU_TENSOR_MAP_L2_PROMOTION_L2_128B, CU_TENSOR_MAP_FLOAT_OOB_FILL_NONE);
}

extern "C" void kernel_launch(void* const* d_in, const int* in_sizes, int n_in, void* d_out, int out_size) {
  static Params prm;
  static void* cached[13] = {nullptr};
  static bool attr_done = false;
  bool same = attr_done && cached[12] == d_out;
  for (int i = 0; i < 12 && same; i++) same = cached[i] == d_in[i];
  if (!same) {
    void* fn = nullptr;
    cudaDriverEntryPointQueryResult qr;
    cudaGetDriverEntryPoint("cuTensorMapEncodeTiled", &fn, cudaEnableDefault, &qr);
    EncodeFn enc = (EncodeFn)fn;
    void *pO, *pXT;
    cudaGetSymbolAddress(&pO, g_O);
    cudaGetSymbolAddress(&pXT, g_xT);
    make_map(enc, &prm.mapO, pO, DM, LSEQ, 64);
    make_map(enc, &prm.mapXT, pXT, LSEQ, 4 * DM, 64);
    prm.out = (bf16*)d_out;
    make_map(enc, &prm.mapX128, d_in[0], 2 * DM, LSEQ / 2, 128);
    make_map(enc, &prm.mapWo128, d_in[2], DM, DM, 128);
    make_map(enc, &prm.mapO128, pO, DM, LSEQ, 128);
    make_map3(enc, &prm.mapW3, d_in[1], DM, 3 * DM, DM, DM, 3, 3);
    make_map3(enc, &prm.mapW3h, d_in[1], DM, 3 * DM, DM, DM, 3, 3, 32);
    make_map3(enc, &prm.mapXT3, pXT, 64, LSEQ, 4 * DM, 64, 32, 2);
    prm.a_re = (const bf16*)d_in[4]; prm.a_im = (const bf16*)d_in[5];
    prm.b_re = (const bf16*)d_in[6]; prm.b_im = (const bf16*)d_in[7];
    prm.c_re = (const bf16*)d_in[8]; prm.c_im = (const bf16*)d_in[9];
    prm.log_dt = (const bf16*)d_in[10]; prm.dskip = (const bf16*)d_in[11];
    cudaFuncSetAttribute(fused_kernel, cudaFuncAttributeMaxDynamicSharedMemorySize, SM_TOTAL);
    for (int i = 0; i < 12; i++) cached[i] = d_in[i];
    cached[12] = d_out;
    attr_done = true;
  }
  prm.stop = 100;
    fused_kernel<<<NCTA, NTHREADS, SM_TOTAL>>>(prm);
}
```

```cpp
#include <cuda_runtime.h>
#include <cuda_bf16.h>
#include <cuda.h>
#include <stdint.h>

typedef __nv_bfloat16 bf16;

constexpr int LSEQ = 2048;
constexpr int DM = 512;
constexpr int NCTA = 128;
constexpr int NTHREADS = 512;
#define RR 0
#define KG_PRE 2
#define W2_LATE 1
#define FILL_AT 6
#define EXP_LATE 1
#define RFENCE 1
#define D_FIN 500
#define D_PREP 500
#define D_PST 0
#define D_HALO 500
#define STAG 2
#define D_ST 500
#define TLAYER 1
#define KG_PD 1
#define SUM_F32 0
#define CS_LATE0 1
#define D_HALO1 0
#define KG_START 0
#define S_AHEAD0 1
#define S_AHEAD1 2
#define PAUSE 2
#define PARK_FIRST 0
#define P_UNROLL_N 1
constexpr int P_UNROLL = P_UNROLL_N;
#define NORM_FMA 0
#define X_ORDER 1
#define G_WAIT 2
#define HALO_W14 1
#define D_START 200
#define D_CS 300
#define D_ST0 400
#define KG_LAST 0
#define X_JIT 0
#define KG_GATE 2
#define R_CONS 192
#define R_HELP 88

constexpr int SM_X = 0;
constexpr int SM_W = 131072;
constexpr int SM_KVX = SM_X;
constexpr int SM_OST = SM_X + 32768;
constexpr int SM_WO = SM_X + 65536;
__host__ __device__ constexpr int sm_o(int c) { return c < 4 ? SM_W + c * 16384 : SM_X + (c - 4) * 16384; }
constexpr int SM_R = 196608;
constexpr int SM_T = 212992;
constexpr int SM_KC = 217088;
constexpr int KC_STRIDE = 648;
constexpr int SM_CS = SM_KC + 4 * KC_STRIDE * 2;
constexpr int SM_CW = SM_R + 8192;
constexpr int SM_EP = SM_CS + 768;
constexpr int SM_BAR = SM_EP + 16;
constexpr int SM_T2 = SM_BAR + 896;
constexpr int SM_HALO = SM_T2 + 4096;
constexpr int SM_ST = SM_HALO + 3072;
constexpr int SM_TOTAL = SM_HALO + 4096;
static_assert(SM_TOTAL <= 232448, "shared memory");

constexpr int CV_UH = 140 * 16;
constexpr int CV_PECH = 1120 * 4;
constexpr int CV_PBW = 2112 * 2;
__host__ __device__ constexpr int cv_s(int lc) { return SM_X + lc * 32768; }
__host__ __device__ constexpr int cv_u(int lc) { return cv_s(lc) + 4096; }
__host__ __device__ constexpr int cv_pe(int lc) { return cv_u(lc) + 2 * CV_UH; }
__host__ __device__ constexpr int cv_pb(int lc) { return cv_pe(lc) + CV_PECH; }
__host__ __device__ constexpr int cv_ft(int lc) { return cv_pb(lc) + 4 * CV_PBW; }
static_assert(cv_ft(0) + 1024 <= 32768, "conv buffers");
__host__ __device__ constexpr int cv_chan(int cta, int lc) { return cta + 128 * lc; }

enum {
  B_XF = 0,
  B_KVF = 8,
  B_OF = 16,
  B_WOF = 24,
  B_T = 31,
  B_RF = 28,
  B_RE = 29,
  B_CW = 30,
  B_GB = 35,
  B_EP = 36,
  B_ZF = 37,
  B_XV = 39,
  B_SD = 38,
  B_KVE = 40,
  B_AD = 45,
  B_OST = 46,
  B_QDONE = 47,
  B_PDONE = 48,
  B_S = 50,
  B_E = 54,
  B_P = 58,
  B_PE = 62,
  B_STF = 63,
  B_CSF = 64,
  B_HF = 65,
  B_U = 70,
  B_PS = 74,
  B_COUNT = 80
};

enum {
  C_CS = 0,
  C_G1 = 2,
  C_O = 4,
  C_COUNT = 20
};

__device__ __align__(128) unsigned g_cnt[C_COUNT * 32];
__device__ __align__(1024) bf16 g_O[LSEQ * DM];
__device__ __align__(1024) bf16 g_xT[4 * DM * LSEQ];
__device__ __align__(1024) uint32_t g_stats[2 * LSEQ];
__device__ __align__(1024) uint4 g_colsum[8 * 16 * 48];
__device__ __align__(1024) uint4 g_halo[16 * 8 * 192];
__device__ __align__(1024) uint2 g_part[16 * 8 * 128];
#define TS(i) do { } while (0)

#define ATS(i, th) do { } while (0)
#define KTS(i) do { if (ht == 0) TS(i); } while (0)
#define FTS(i) do { } while (0)
#define LTS(i) do { } while (0)

#define STOP 100

struct Params {
  CUtensorMap mapO, mapXT, mapX128, mapWo128, mapO128, mapW3, mapW3h, mapXT3;
  const bf16 *a_re, *a_im, *b_re, *b_im, *c_re, *c_im, *log_dt, *dskip;
  bf16* out;
  int stop;
};

__device__ __forceinline__ uint32_t s32(const void* p) { return (uint32_t)__cvta_generic_to_shared(p); }
__device__ __forceinline__ void mbar_init(uint32_t b, int c) { asm volatile("mbarrier.init.shared::cta.b64 [%0], %1;" ::"r"(b), "r"(c) : "memory"); }
__device__ __forceinline__ void mbar_expect(uint32_t b, int bytes) { asm volatile("mbarrier.arrive.expect_tx.shared::cta.b64 _, [%0], %1;" ::"r"(b), "r"(bytes) : "memory"); }
__device__ __forceinline__ void mbar_arrive(uint32_t b) { asm volatile("mbarrier.arrive.shared::cta.b64 _, [%0];" ::"r"(b) : "memory"); }
__device__ __forceinline__ void mbar_arrive_if(uint32_t b, bool c) {
  asm volatile("{\n.reg .pred p;\nsetp.ne.u32 p, %1, 0;\n@p mbarrier.arrive.shared::cta.b64 _, [%0];\n}" ::"r"(b), "r"((uint32_t)c) : "memory");
}
__device__ __forceinline__ void mbar_wait(uint32_t b, int parity) {
  asm volatile("{\n.reg .pred p;\nWAIT_LOOP:\nmbarrier.try_wait.parity.shared::cta.b64 p, [%0], %1;\n@p bra WAIT_DONE;\nbra WAIT_LOOP;\nWAIT_DONE:\n}" ::"r"(b), "r"(parity) : "memory");
}
template <int N> __device__ __forceinline__ void delay() {
  if constexpr (N > 0) {
    uint32_t t0, t;
    asm volatile("mov.u32 %0, %%clock;" : "=r"(t0));
    do { asm volatile("mov.u32 %0, %%clock;" : "=r"(t)); } while (t - t0 < N);
  }
}
#define SF 3
template <int ID> __device__ __forceinline__ void sched_fence() {
  if constexpr ((SF >> ID) & 1)
    asm volatile("{\n.reg .pred p;\n.reg .u32 t;\nsetp.eq.u32 p, %0, 0;\n@p mov.u32 t, %%clock;\n@p st.shared.u32 [%0], t;\n}" ::"r"(gridDim.x) : "memory");
}
__device__ __forceinline__ int opaque_tid() { int v; asm volatile("mov.u32 %0, %%tid.x;" : "=r"(v)); return v; }
__device__ __forceinline__ bool elect_one() {
  uint32_t r;
  asm volatile("{\n.reg .pred p;\nelect.sync _|p, 0xffffffff;\nselp.u32 %0, 1, 0, p;\n}" : "=r"(r));
  return r != 0;
}
__device__ __forceinline__ void tma_ld(uint32_t dst, const CUtensorMap* m, int c0, int c1, uint32_t bar) {
  asm volatile("cp.async.bulk.tensor.2d.shared::cluster.global.mbarrier::complete_tx::bytes [%0], [%1, {%3, %4}], [%2];"
               ::"r"(dst), "l"(m), "r"(bar), "r"(c0), "r"(c1) : "memory");
}
__device__ __forceinline__ void tma_ld3(uint32_t dst, const CUtensorMap* m, int c0, int c1, int c2, uint32_t bar) {
  asm volatile("cp.async.bulk.tensor.3d.shared::cluster.global.mbarrier::complete_tx::bytes [%0], [%1, {%3, %4, %5}], [%2];"
               ::"r"(dst), "l"(m), "r"(bar), "r"(c0), "r"(c1), "r"(c2) : "memory");
}
__device__ __forceinline__ void tma_prefetch2(const CUtensorMap* m, int c0, int c1) {
  asm volatile("cp.async.bulk.prefetch.tensor.2d.L2.global.tile [%0, {%1, %2}];" ::"l"(m), "r"(c0), "r"(c1) : "memory");
}
__device__ __forceinline__ void tma_prefetch3(const CUtensorMap* m, int c0, int c1, int c2) {
  asm volatile("cp.async.bulk.prefetch.tensor.3d.L2.global.tile [%0, {%1, %2, %3}];" ::"l"(m), "r"(c0), "r"(c1), "r"(c2) : "memory");
}
__device__ __forceinline__ void tma_st(const CUtensorMap* m, int c0, int c1, uint32_t src) {
  asm volatile("cp.async.bulk.tensor.2d.global.shared::cta.bulk_group [%0, {%2, %3}], [%1];" ::"l"(m), "r"(src), "r"(c0), "r"(c1) : "memory");
}
__device__ __forceinline__ void bulk_ld(uint32_t dst, const void* src, int bytes, uint32_t bar) {
  asm volatile("cp.async.bulk.shared::cluster.global.mbarrier::complete_tx::bytes [%0], [%1], %2, [%3];" ::"r"(dst), "l"(src), "r"(bytes), "r"(bar) : "memory");
}
__device__ __forceinline__ void bulk_st(void* dst, uint32_t src, int bytes) {
  asm volatile("cp.async.bulk.global.shared::cta.bulk_group [%0], [%1], %2;" ::"l"(dst), "r"(src), "r"(bytes) : "memory");
}
__device__ __forceinline__ void bulk_red_add_f32(void* dst, uint32_t src, int bytes) {
  asm volatile("cp.reduce.async.bulk.global.shared::cta.bulk_group.add.f32 [%0], [%1], %2;" ::"l"(dst), "r"(src), "r"(bytes) : "memory");
}
__device__ __forceinline__ void bulk_commit() { asm volatile("cp.async.bulk.commit_group;" ::: "memory"); }
__device__ __forceinline__ void bulk_wait_all() { asm volatile("cp.async.bulk.wait_group 0;" ::: "memory"); }
__device__ __forceinline__ void fence_async_smem() { asm volatile("fence.proxy.async.shared::cta;" ::: "memory"); }
__device__ __forceinline__ void fence_writer() { if (!RFENCE) fence_async_smem(); }
__device__ __forceinline__ void fence_reader() { if (RFENCE) fence_async_smem(); }
__device__ __forceinline__ void fence_async_global() { asm volatile("fence.proxy.async.global;" ::: "memory"); }
__device__ __forceinline__ void bar_sync(int id, int n) { asm volatile("bar.sync %0, %1;" ::"r"(id), "r"(n) : "memory"); }
__device__ __forceinline__ void bar_arrive(int id, int n) { asm volatile("bar.arrive %0, %1;" ::"r"(id), "r"(n) : "memory"); }
__device__ __forceinline__ void wg_fence() { asm volatile("wgmma.fence.sync.aligned;" ::: "memory"); }
__device__ __forceinline__ void wg_commit() { asm volatile("wgmma.commit_group.sync.aligned;" ::: "memory"); }
template <int N> __device__ __forceinline__ void wg_wait() { asm volatile("wgmma.wait_group.sync.aligned %0;" ::"n"(N) : "memory"); }
__device__ __forceinline__ uint64_t mkdesc(uint32_t addr, uint32_t lbo, uint32_t sbo, int sw) {
  return (uint64_t)((addr & 0x3FFFF) >> 4) | ((uint64_t)(lbo >> 4) << 16) | ((uint64_t)(sbo >> 4) << 32) | ((uint64_t)sw << 62);
}
__device__ __forceinline__ void ldsm4(uint32_t* r, uint32_t a) {
  asm volatile("ldmatrix.sync.aligned.m8n8.x4.shared.b16 {%0,%1,%2,%3}, [%4];" : "=r"(r[0]), "=r"(r[1]), "=r"(r[2]), "=r"(r[3]) : "r"(a) : "memory");
}
__device__ __forceinline__ void ldsm4t(uint32_t* r, uint32_t a) {
  asm volatile("ldmatrix.sync.aligned.m8n8.x4.trans.shared.b16 {%0,%1,%2,%3}, [%4];" : "=r"(r[0]), "=r"(r[1]), "=r"(r[2]), "=r"(r[3]) : "r"(a) : "memory");
}
__device__ __forceinline__ void stsm4(uint32_t a, uint32_t r0, uint32_t r1, uint32_t r2, uint32_t r3) {
  asm volatile("stmatrix.sync.aligned.m8n8.x4.shared.b16 [%0], {%1,%2,%3,%4};" ::"r"(a), "r"(r0), "r"(r1), "r"(r2), "r"(r3) : "memory");
}
__device__ __forceinline__ void stsm4t(uint32_t a, uint32_t r0, uint32_t r1, uint32_t r2, uint32_t r3) {
  asm volatile("stmatrix.sync.aligned.m8n8.x4.trans.shared.b16 [%0], {%1,%2,%3,%4};" ::"r"(a), "r"(r0), "r"(r1), "r"(r2), "r"(r3) : "memory");
}
__device__ __forceinline__ uint32_t movm_t(uint32_t a) { uint32_t r; asm volatile("movmatrix.sync.aligned.m8n8.trans.b16 %0, %1;" : "=r"(r) : "r"(a)); return r; }
__device__ __forceinline__ uint32_t lds32(uint32_t a) { uint32_t v; asm volatile("ld.shared.b32 %0, [%1];" : "=r"(v) : "r"(a) : "memory"); return v; }
__device__ __forceinline__ float2 lds64f(uint32_t a) { float2 v; asm volatile("ld.shared.v2.f32 {%0,%1}, [%2];" : "=f"(v.x), "=f"(v.y) : "r"(a) : "memory"); return v; }
__device__ __forceinline__ float4 lds128f(uint32_t a) { float4 v; asm volatile("ld.shared.v4.f32 {%0,%1,%2,%3}, [%4];" : "=f"(v.x), "=f"(v.y), "=f"(v.z), "=f"(v.w) : "r"(a) : "memory"); return v; }
__device__ __forceinline__ uint4 lds128(uint32_t a) { uint4 v; asm volatile("ld.shared.v4.b32 {%0,%1,%2,%3}, [%4];" : "=r"(v.x), "=r"(v.y), "=r"(v.z), "=r"(v.w) : "r"(a) : "memory"); return v; }
__device__ __forceinline__ void sts128(uint32_t a, uint4 v) { asm volatile("st.shared.v4.b32 [%0], {%1,%2,%3,%4};" ::"r"(a), "r"(v.x), "r"(v.y), "r"(v.z), "r"(v.w) : "memory"); }
__device__ __forceinline__ void sts128f(uint32_t a, float x, float y, float z, float w) { asm volatile("st.shared.v4.f32 [%0], {%1,%2,%3,%4};" ::"r"(a), "f"(x), "f"(y), "f"(z), "f"(w) : "memory"); }
__device__ __forceinline__ void sts32f(uint32_t a, float v) { asm volatile("st.shared.f32 [%0], %1;" ::"r"(a), "f"(v) : "memory"); }
__device__ __forceinline__ void sts16(uint32_t a, uint16_t v) { asm volatile("st.shared.u16 [%0], %1;" ::"r"(a), "h"(v) : "memory"); }
__device__ __forceinline__ uint32_t lds16(uint32_t a) { uint16_t v; asm volatile("ld.shared.u16 %0, [%1];" : "=h"(v) : "r"(a) : "memory"); return v; }
__device__ __forceinline__ uint32_t packbf(float lo, float hi) { uint32_t r; asm("cvt.rn.bf16x2.f32 %0, %1, %2;" : "=r"(r) : "f"(hi), "f"(lo)); return r; }
__device__ __forceinline__ float bf_lo(uint32_t v) { return __uint_as_float(v << 16); }
__device__ __forceinline__ float bf_hi(uint32_t v) { return __uint_as_float(v & 0xffff0000u); }
__device__ __forceinline__ float ex2(float x) { float r; asm("ex2.approx.ftz.f32 %0, %1;" : "=f"(r) : "f"(x)); return r; }
__device__ __forceinline__ float rsqrt_approx(float x) { float r; asm("rsqrt.approx.ftz.f32 %0, %1;" : "=f"(r) : "f"(x)); return r; }
__device__ __forceinline__ float rcp_approx(float x) { float r; asm("rcp.approx.ftz.f32 %0, %1;" : "=f"(r) : "f"(x)); return r; }
__device__ __forceinline__ void mma_bf16(float* d, const uint32_t* a, uint32_t b0, uint32_t b1) {
  asm("mma.sync.aligned.m16n8k16.row.col.f32.bf16.bf16.f32 {%0,%1,%2,%3}, {%4,%5,%6,%7}, {%8,%9}, {%0,%1,%2,%3};"
               : "+f"(d[0]), "+f"(d[1]), "+f"(d[2]), "+f"(d[3]) : "r"(a[0]), "r"(a[1]), "r"(a[2]), "r"(a[3]), "r"(b0), "r"(b1));
}
__device__ __forceinline__ void mma_bf16_k8(float* d, uint32_t a0, uint32_t a1, uint32_t b) {
  asm("mma.sync.aligned.m16n8k8.row.col.f32.bf16.bf16.f32 {%0,%1,%2,%3}, {%4,%5}, {%6}, {%0,%1,%2,%3};"
      : "+f"(d[0]), "+f"(d[1]), "+f"(d[2]), "+f"(d[3]) : "r"(a0), "r"(a1), "r"(b));
}
__device__ __forceinline__ void red_release(unsigned* p) { asm volatile("red.release.gpu.global.add.u32 [%0], 1;" ::"l"(p) : "memory"); }
__device__ __forceinline__ void red_relaxed(unsigned* p) { asm volatile("red.relaxed.gpu.global.add.u32 [%0], 1;" ::"l"(p) : "memory"); }
__device__ __forceinline__ unsigned ld_relaxed(const unsigned* p) { unsigned v; asm volatile("ld.relaxed.gpu.global.u32 %0, [%1];" : "=r"(v) : "l"(p) : "memory"); return v; }
__device__ __forceinline__ void spin_until(const unsigned* p, unsigned target) {
  int it = 0;
  while ((int)(ld_relaxed(p) - target) < 0) {
    if (++it > (1 << 23)) __trap();
  }
}
__device__ __forceinline__ uint4 ldcg128(const void* p) { uint4 v; asm volatile("ld.global.cg.v4.b32 {%0,%1,%2,%3}, [%4];" : "=r"(v.x), "=r"(v.y), "=r"(v.z), "=r"(v.w) : "l"(p) : "memory"); return v; }
__device__ __forceinline__ uint4 ld_tagged(const uint4* p) { uint4 v; asm volatile("ld.relaxed.gpu.global.v4.u32 {%0,%1,%2,%3}, [%4];" : "=r"(v.x), "=r"(v.y), "=r"(v.z), "=r"(v.w) : "l"(p) : "memory"); return v; }
__device__ __forceinline__ uint2 ld_part(const uint2* p) { uint2 v; asm volatile("ld.relaxed.gpu.global.v2.u32 {%0,%1}, [%2];" : "=r"(v.x), "=r"(v.y) : "l"(p) : "memory"); return v; }
__device__ __forceinline__ void st_part(uint2* p, float s, float q, uint32_t tag) {
  asm volatile("st.relaxed.gpu.global.v2.u32 [%0], {%1,%2};" ::"l"(p), "r"(__float_as_uint(s)), "r"((__float_as_uint(q) & ~7u) | tag) : "memory");
}
__device__ __forceinline__ uint32_t part_tag(uint32_t epoch, int k) { return (4 * (epoch % 7) + k) % 7 + 1; }
__device__ __forceinline__ void st_tagged3(uint4* p, uint32_t a, uint32_t b, uint32_t c, uint32_t tag) { asm volatile("st.relaxed.gpu.global.v4.u32 [%0], {%1,%2,%3,%4};" ::"l"(p), "r"(a), "r"(b), "r"(c), "r"(tag) : "memory"); }
__device__ __forceinline__ uint32_t hadd2(uint32_t a, uint32_t b) { uint32_t r; asm("add.rn.bf16x2 %0, %1, %2;" : "=r"(r) : "r"(a), "r"(b)); return r; }
__device__ __forceinline__ uint32_t hfma2(uint32_t a, uint32_t b, uint32_t c) { uint32_t r; asm("fma.rn.bf16x2 %0, %1, %2, %3;" : "=r"(r) : "r"(a), "r"(b), "r"(c)); return r; }
__device__ __forceinline__ uint32_t hmul2(uint32_t a, uint32_t b) { uint32_t r; asm("mul.rn.bf16x2 %0, %1, %2;" : "=r"(r) : "r"(a), "r"(b)); return r; }

template<int N,int TB> __device__ __forceinline__ void wgmma_rs(float* d, const uint32_t* a, uint64_t db, int sd);
template<int N,int TA,int TB> __device__ __forceinline__ void wgmma_ss(float* d, uint64_t da, uint64_t db, int sd);
template<> __device__ __forceinline__ void wgmma_rs<128,0>(float* d, const uint32_t* a, uint64_t db, int sd) {
  asm volatile("{\n.reg .pred p;\nsetp.ne.b32 p, %69, 0;\nwgmma.mma_async.sync.aligned.m64n128k16.f32.bf16.bf16 {%0,%1,%2,%3,%4,%5,%6,%7,%8,%9,%10,%11,%12,%13,%14,%15,%16,%17,%18,%19,%20,%21,%22,%23,%24,%25,%26,%27,%28,%29,%30,%31,%32,%33,%34,%35,%36,%37,%38,%39,%40,%41,%42,%43,%44,%45,%46,%47,%48,%49,%50,%51,%52,%53,%54,%55,%56,%57,%58,%59,%60,%61,%62,%63}, {%64,%65,%66,%67}, %68, p, 1, 1, 0;\n}\n"
   : "+f"(d[0]),"+f"(d[1]),"+f"(d[2]),"+f"(d[3]),"+f"(d[4]),"+f"(d[5]),"+f"(d[6]),"+f"(d[7]),"+f"(d[8]),"+f"(d[9]),"+f"(d[10]),"+f"(d[11]),"+f"(d[12]),"+f"(d[13]),"+f"(d[14]),"+f"(d[15]),"+f"(d[16]),"+f"(d[17]),"+f"(d[18]),"+f"(d[19]),"+f"(d[20]),"+f"(d[21]),"+f"(d[22]),"+f"(d[23]),"+f"(d[24]),"+f"(d[25]),"+f"(d[26]),"+f"(d[27]),"+f"(d[28]),"+f"(d[29]),"+f"(d[30]),"+f"(d[31]),"+f"(d[32]),"+f"(d[33]),"+f"(d[34]),"+f"(d[35]),"+f"(d[36]),"+f"(d[37]),"+f"(d[38]),"+f"(d[39]),"+f"(d[40]),"+f"(d[41]),"+f"(d[42]),"+f"(d[43]),"+f"(d[44]),"+f"(d[45]),"+f"(d[46]),"+f"(d[47]),"+f"(d[48]),"+f"(d[49]),"+f"(d[50]),"+f"(d[51]),"+f"(d[52]),"+f"(d[53]),"+f"(d[54]),"+f"(d[55]),"+f"(d[56]),"+f"(d[57]),"+f"(d[58]),"+f"(d[59]),"+f"(d[60]),"+f"(d[61]),"+f"(d[62]),"+f"(d[63])
   : "r"(a[0]), "r"(a[1]), "r"(a[2]), "r"(a[3]), "l"(db), "r"(sd));
}
template<> __device__ __forceinline__ void wgmma_rs<120,0>(float* d, const uint32_t* a, uint64_t db, int sd) {
  asm volatile("{\n.reg .pred p;\nsetp.ne.b32 p, %65, 0;\nwgmma.mma_async.sync.aligned.m64n120k16.f32.bf16.bf16 {%0,%1,%2,%3,%4,%5,%6,%7,%8,%9,%10,%11,%12,%13,%14,%15,%16,%17,%18,%19,%20,%21,%22,%23,%24,%25,%26,%27,%28,%29,%30,%31,%32,%33,%34,%35,%36,%37,%38,%39,%40,%41,%42,%43,%44,%45,%46,%47,%48,%49,%50,%51,%52,%53,%54,%55,%56,%57,%58,%59}, {%60,%61,%62,%63}, %64, p, 1, 1, 0;\n}\n"
   : "+f"(d[0]),"+f"(d[1]),"+f"(d[2]),"+f"(d[3]),"+f"(d[4]),"+f"(d[5]),"+f"(d[6]),"+f"(d[7]),"+f"(d[8]),"+f"(d[9]),"+f"(d[10]),"+f"(d[11]),"+f"(d[12]),"+f"(d[13]),"+f"(d[14]),"+f"(d[15]),"+f"(d[16]),"+f"(d[17]),"+f"(d[18]),"+f"(d[19]),"+f"(d[20]),"+f"(d[21]),"+f"(d[22]),"+f"(d[23]),"+f"(d[24]),"+f"(d[25]),"+f"(d[26]),"+f"(d[27]),"+f"(d[28]),"+f"(d[29]),"+f"(d[30]),"+f"(d[31]),"+f"(d[32]),"+f"(d[33]),"+f"(d[34]),"+f"(d[35]),"+f"(d[36]),"+f"(d[37]),"+f"(d[38]),"+f"(d[39]),"+f"(d[40]),"+f"(d[41]),"+f"(d[42]),"+f"(d[43]),"+f"(d[44]),"+f"(d[45]),"+f"(d[46]),"+f"(d[47]),"+f"(d[48]),"+f"(d[49]),"+f"(d[50]),"+f"(d[51]),"+f"(d[52]),"+f"(d[53]),"+f"(d[54]),"+f"(d[55]),"+f"(d[56]),"+f"(d[57]),"+f"(d[58]),"+f"(d[59])
   : "r"(a[0]), "r"(a[1]), "r"(a[2]), "r"(a[3]), "l"(db), "r"(sd));
}
template<> __device__ __forceinline__ void wgmma_rs<112,0>(float* d, const uint32_t* a, uint64_t db, int sd) {
  asm volatile("{\n.reg .pred p;\nsetp.ne.b32 p, %61, 0;\nwgmma.mma_async.sync.aligned.m64n112k16.f32.bf16.bf16 {%0,%1,%2,%3,%4,%5,%6,%7,%8,%9,%10,%11,%12,%13,%14,%15,%16,%17,%18,%19,%20,%21,%22,%23,%24,%25,%26,%27,%28,%29,%30,%31,%32,%33,%34,%35,%36,%37,%38,%39,%40,%41,%42,%43,%44,%45,%46,%47,%48,%49,%50,%51,%52,%53,%54,%55}, {%56,%57,%58,%59}, %60, p, 1, 1, 0;\n}\n"
   : "+f"(d[0]),"+f"(d[1]),"+f"(d[2]),"+f"(d[3]),"+f"(d[4]),"+f"(d[5]),"+f"(d[6]),"+f"(d[7]),"+f"(d[8]),"+f"(d[9]),"+f"(d[10]),"+f"(d[11]),"+f"(d[12]),"+f"(d[13]),"+f"(d[14]),"+f"(d[15]),"+f"(d[16]),"+f"(d[17]),"+f"(d[18]),"+f"(d[19]),"+f"(d[20]),"+f"(d[21]),"+f"(d[22]),"+f"(d[23]),"+f"(d[24]),"+f"(d[25]),"+f"(d[26]),"+f"(d[27]),"+f"(d[28]),"+f"(d[29]),"+f"(d[30]),"+f"(d[31]),"+f"(d[32]),"+f"(d[33]),"+f"(d[34]),"+f"(d[35]),"+f"(d[36]),"+f"(d[37]),"+f"(d[38]),"+f"(d[39]),"+f"(d[40]),"+f"(d[41]),"+f"(d[42]),"+f"(d[43]),"+f"(d[44]),"+f"(d[45]),"+f"(d[46]),"+f"(d[47]),"+f"(d[48]),"+f"(d[49]),"+f"(d[50]),"+f"(d[51]),"+f"(d[52]),"+f"(d[53]),"+f"(d[54]),"+f"(d[55])
   : "r"(a[0]), "r"(a[1]), "r"(a[2]), "r"(a[3]), "l"(db), "r"(sd));
}
template<> __device__ __forceinline__ void wgmma_rs<104,0>(float* d, const uint32_t* a, uint64_t db, int sd) {
  asm volatile("{\n.reg .pred p;\nsetp.ne.b32 p, %57, 0;\nwgmma.mma_async.sync.aligned.m64n104k16.f32.bf16.bf16 {%0,%1,%2,%3,%4,%5,%6,%7,%8,%9,%10,%11,%12,%13,%14,%15,%16,%17,%18,%19,%20,%21,%22,%23,%24,%25,%26,%27,%28,%29,%30,%31,%32,%33,%34,%35,%36,%37,%38,%39,%40,%41,%42,%43,%44,%45,%46,%47,%48,%49,%50,%51}, {%52,%53,%54,%55}, %56, p, 1, 1, 0;\n}\n"
   : "+f"(d[0]),"+f"(d[1]),"+f"(d[2]),"+f"(d[3]),"+f"(d[4]),"+f"(d[5]),"+f"(d[6]),"+f"(d[7]),"+f"(d[8]),"+f"(d[9]),"+f"(d[10]),"+f"(d[11]),"+f"(d[12]),"+f"(d[13]),"+f"(d[14]),"+f"(d[15]),"+f"(d[16]),"+f"(d[17]),"+f"(d[18]),"+f"(d[19]),"+f"(d[20]),"+f"(d[21]),"+f"(d[22]),"+f"(d[23]),"+f"(d[24]),"+f"(d[25]),"+f"(d[26]),"+f"(d[27]),"+f"(d[28]),"+f"(d[29]),"+f"(d[30]),"+f"(d[31]),"+f"(d[32]),"+f"(d[33]),"+f"(d[34]),"+f"(d[35]),"+f"(d[36]),"+f"(d[37]),"+f"(d[38]),"+f"(d[39]),"+f"(d[40]),"+f"(d[41]),"+f"(d[42]),"+f"(d[43]),"+f"(d[44]),"+f"(d[45]),"+f"(d[46]),"+f"(d[47]),"+f"(d[48]),"+f"(d[49]),"+f"(d[50]),"+f"(d[51])
   : "r"(a[0]), "r"(a[1]), "r"(a[2]), "r"(a[3]), "l"(db), "r"(sd));
}
template<> __device__ __forceinline__ void wgmma_rs<96,0>(float* d, const uint32_t* a, uint64_t db, int sd) {
  asm volatile("{\n.reg .pred p;\nsetp.ne.b32 p, %53, 0;\nwgmma.mma_async.sync.aligned.m64n96k16.f32.bf16.bf16 {%0,%1,%2,%3,%4,%5,%6,%7,%8,%9,%10,%11,%12,%13,%14,%15,%16,%17,%18,%19,%20,%21,%22,%23,%24,%25,%26,%27,%28,%29,%30,%31,%32,%33,%34,%35,%36,%37,%38,%39,%40,%41,%42,%43,%44,%45,%46,%47}, {%48,%49,%50,%51}, %52, p, 1, 1, 0;\n}\n"
   : "+f"(d[0]),"+f"(d[1]),"+f"(d[2]),"+f"(d[3]),"+f"(d[4]),"+f"(d[5]),"+f"(d[6]),"+f"(d[7]),"+f"(d[8]),"+f"(d[9]),"+f"(d[10]),"+f"(d[11]),"+f"(d[12]),"+f"(d[13]),"+f"(d[14]),"+f"(d[15]),"+f"(d[16]),"+f"(d[17]),"+f"(d[18]),"+f"(d[19]),"+f"(d[20]),"+f"(d[21]),"+f"(d[22]),"+f"(d[23]),"+f"(d[24]),"+f"(d[25]),"+f"(d[26]),"+f"(d[27]),"+f"(d[28]),"+f"(d[29]),"+f"(d[30]),"+f"(d[31]),"+f"(d[32]),"+f"(d[33]),"+f"(d[34]),"+f"(d[35]),"+f"(d[36]),"+f"(d[37]),"+f"(d[38]),"+f"(d[39]),"+f"(d[40]),"+f"(d[41]),"+f"(d[42]),"+f"(d[43]),"+f"(d[44]),"+f"(d[45]),"+f"(d[46]),"+f"(d[47])
   : "r"(a[0]), "r"(a[1]), "r"(a[2]), "r"(a[3]), "l"(db), "r"(sd));
}
template<> __device__ __forceinline__ void wgmma_rs<88,0>(float* d, const uint32_t* a, uint64_t db, int sd) {
  asm volatile("{\n.reg .pred p;\nsetp.ne.b32 p, %49, 0;\nwgmma.mma_async.sync.aligned.m64n88k16.f32.bf16.bf16 {%0,%1,%2,%3,%4,%5,%6,%7,%8,%9,%10,%11,%12,%13,%14,%15,%16,%17,%18,%19,%20,%21,%22,%23,%24,%25,%26,%27,%28,%29,%30,%31,%32,%33,%34,%35,%36,%37,%38,%39,%40,%41,%42,%43}, {%44,%45,%46,%47}, %48, p, 1, 1, 0;\n}\n"
   : "+f"(d[0]),"+f"(d[1]),"+f"(d[2]),"+f"(d[3]),"+f"(d[4]),"+f"(d[5]),"+f"(d[6]),"+f"(d[7]),"+f"(d[8]),"+f"(d[9]),"+f"(d[10]),"+f"(d[11]),"+f"(d[12]),"+f"(d[13]),"+f"(d[14]),"+f"(d[15]),"+f"(d[16]),"+f"(d[17]),"+f"(d[18]),"+f"(d[19]),"+f"(d[20]),"+f"(d[21]),"+f"(d[22]),"+f"(d[23]),"+f"(d[24]),"+f"(d[25]),"+f"(d[26]),"+f"(d[27]),"+f"(d[28]),"+f"(d[29]),"+f"(d[30]),"+f"(d[31]),"+f"(d[32]),"+f"(d[33]),"+f"(d[34]),"+f"(d[35]),"+f"(d[36]),"+f"(d[37]),"+f"(d[38]),"+f"(d[39]),"+f"(d[40]),"+f"(d[41]),"+f"(d[42]),"+f"(d[43])
   : "r"(a[0]), "r"(a[1]), "r"(a[2]), "r"(a[3]), "l"(db), "r"(sd));
}
template<> __device__ __forceinline__ void wgmma_rs<80,0>(float* d, const uint32_t* a, uint64_t db, int sd) {
  asm volatile("{\n.reg .pred p;\nsetp.ne.b32 p, %45, 0;\nwgmma.mma_async.sync.aligned.m64n80k16.f32.bf16.bf16 {%0,%1,%2,%3,%4,%5,%6,%7,%8,%9,%10,%11,%12,%13,%14,%15,%16,%17,%18,%19,%20,%21,%22,%23,%24,%25,%26,%27,%28,%29,%30,%31,%32,%33,%34,%35,%36,%37,%38,%39}, {%40,%41,%42,%43}, %44, p, 1, 1, 0;\n}\n"
   : "+f"(d[0]),"+f"(d[1]),"+f"(d[2]),"+f"(d[3]),"+f"(d[4]),"+f"(d[5]),"+f"(d[6]),"+f"(d[7]),"+f"(d[8]),"+f"(d[9]),"+f"(d[10]),"+f"(d[11]),"+f"(d[12]),"+f"(d[13]),"+f"(d[14]),"+f"(d[15]),"+f"(d[16]),"+f"(d[17]),"+f"(d[18]),"+f"(d[19]),"+f"(d[20]),"+f"(d[21]),"+f"(d[22]),"+f"(d[23]),"+f"(d[24]),"+f"(d[25]),"+f"(d[26]),"+f"(d[27]),"+f"(d[28]),"+f"(d[29]),"+f"(d[30]),"+f"(d[31]),"+f"(d[32]),"+f"(d[33]),"+f"(d[34]),"+f"(d[35]),"+f"(d[36]),"+f"(d[37]),"+f"(d[38]),"+f"(d[39])
   : "r"(a[0]), "r"(a[1]), "r"(a[2]), "r"(a[3]), "l"(db), "r"(sd));
}
template<> __device__ __forceinline__ void wgmma_rs<72,0>(float* d, const uint32_t* a, uint64_t db, int sd) {
  asm volatile("{\n.reg .pred p;\nsetp.ne.b32 p, %41, 0;\nwgmma.mma_async.sync.aligned.m64n72k16.f32.bf16.bf16 {%0,%1,%2,%3,%4,%5,%6,%7,%8,%9,%10,%11,%12,%13,%14,%15,%16,%17,%18,%19,%20,%21,%22,%23,%24,%25,%26,%27,%28,%29,%30,%31,%32,%33,%34,%35}, {%36,%37,%38,%39}, %40, p, 1, 1, 0;\n}\n"
   : "+f"(d[0]),"+f"(d[1]),"+f"(d[2]),"+f"(d[3]),"+f"(d[4]),"+f"(d[5]),"+f"(d[6]),"+f"(d[7]),"+f"(d[8]),"+f"(d[9]),"+f"(d[10]),"+f"(d[11]),"+f"(d[12]),"+f"(d[13]),"+f"(d[14]),"+f"(d[15]),"+f"(d[16]),"+f"(d[17]),"+f"(d[18]),"+f"(d[19]),"+f"(d[20]),"+f"(d[21]),"+f"(d[22]),"+f"(d[23]),"+f"(d[24]),"+f"(d[25]),"+f"(d[26]),"+f"(d[27]),"+f"(d[28]),"+f"(d[29]),"+f"(d[30]),"+f"(d[31]),"+f"(d[32]),"+f"(d[33]),"+f"(d[34]),"+f"(d[35])
   : "r"(a[0]), "r"(a[1]), "r"(a[2]), "r"(a[3]), "l"(db), "r"(sd));
}
template<> __device__ __forceinline__ void wgmma_rs<64,0>(float* d, const uint32_t* a, uint64_t db, int sd) {
  asm volatile("{\n.reg .pred p;\nsetp.ne.b32 p, %37, 0;\nwgmma.mma_async.sync.aligned.m64n64k16.f32.bf16.bf16 {%0,%1,%2,%3,%4,%5,%6,%7,%8,%9,%10,%11,%12,%13,%14,%15,%16,%17,%18,%19,%20,%21,%22,%23,%24,%25,%26,%27,%28,%29,%30,%31}, {%32,%33,%34,%35}, %36, p, 1, 1, 0;\n}\n"
   : "+f"(d[0]),"+f"(d[1]),"+f"(d[2]),"+f"(d[3]),"+f"(d[4]),"+f"(d[5]),"+f"(d[6]),"+f"(d[7]),"+f"(d[8]),"+f"(d[9]),"+f"(d[10]),"+f"(d[11]),"+f"(d[12]),"+f"(d[13]),"+f"(d[14]),"+f"(d[15]),"+f"(d[16]),"+f"(d[17]),"+f"(d[18]),"+f"(d[19]),"+f"(d[20]),"+f"(d[21]),"+f"(d[22]),"+f"(d[23]),"+f"(d[24]),"+f"(d[25]),"+f"(d[26]),"+f"(d[27]),"+f"(d[28]),"+f"(d[29]),"+f"(d[30]),"+f"(d[31])
   : "r"(a[0]), "r"(a[1]), "r"(a[2]), "r"(a[3]), "l"(db), "r"(sd));
}
template<> __device__ __forceinline__ void wgmma_ss<64,0,1>(float* d, uint64_t da, uint64_t db, int sd) {
  asm volatile("{\n.reg .pred p;\nsetp.ne.b32 p, %34, 0;\nwgmma.mma_async.sync.aligned.m64n64k16.f32.bf16.bf16 {%0,%1,%2,%3,%4,%5,%6,%7,%8,%9,%10,%11,%12,%13,%14,%15,%16,%17,%18,%19,%20,%21,%22,%23,%24,%25,%26,%27,%28,%29,%30,%31}, %32, %33, p, 1, 1, 0, 1;\n}\n"
   : "+f"(d[0]),"+f"(d[1]),"+f"(d[2]),"+f"(d[3]),"+f"(d[4]),"+f"(d[5]),"+f"(d[6]),"+f"(d[7]),"+f"(d[8]),"+f"(d[9]),"+f"(d[10]),"+f"(d[11]),"+f"(d[12]),"+f"(d[13]),"+f"(d[14]),"+f"(d[15]),"+f"(d[16]),"+f"(d[17]),"+f"(d[18]),"+f"(d[19]),"+f"(d[20]),"+f"(d[21]),"+f"(d[22]),"+f"(d[23]),"+f"(d[24]),"+f"(d[25]),"+f"(d[26]),"+f"(d[27]),"+f"(d[28]),"+f"(d[29]),"+f"(d[30]),"+f"(d[31])
   : "l"(da), "l"(db), "r"(sd));
}
template<> __device__ __forceinline__ void wgmma_ss<64,1,1>(float* d, uint64_t da, uint64_t db, int sd) {
  asm volatile("{\n.reg .pred p;\nsetp.ne.b32 p, %34, 0;\nwgmma.mma_async.sync.aligned.m64n64k16.f32.bf16.bf16 {%0,%1,%2,%3,%4,%5,%6,%7,%8,%9,%10,%11,%12,%13,%14,%15,%16,%17,%18,%19,%20,%21,%22,%23,%24,%25,%26,%27,%28,%29,%30,%31}, %32, %33, p, 1, 1, 1, 1;\n}\n"
   : "+f"(d[0]),"+f"(d[1]),"+f"(d[2]),"+f"(d[3]),"+f"(d[4]),"+f"(d[5]),"+f"(d[6]),"+f"(d[7]),"+f"(d[8]),"+f"(d[9]),"+f"(d[10]),"+f"(d[11]),"+f"(d[12]),"+f"(d[13]),"+f"(d[14]),"+f"(d[15]),"+f"(d[16]),"+f"(d[17]),"+f"(d[18]),"+f"(d[19]),"+f"(d[20]),"+f"(d[21]),"+f"(d[22]),"+f"(d[23]),"+f"(d[24]),"+f"(d[25]),"+f"(d[26]),"+f"(d[27]),"+f"(d[28]),"+f"(d[29]),"+f"(d[30]),"+f"(d[31])
   : "l"(da), "l"(db), "r"(sd));
}
template<> __device__ __forceinline__ void wgmma_ss<192,0,1>(float* d, uint64_t da, uint64_t db, int sd) {
  asm volatile("{\n.reg .pred p;\nsetp.ne.b32 p, %98, 0;\nwgmma.mma_async.sync.aligned.m64n192k16.f32.bf16.bf16 {%0,%1,%2,%3,%4,%5,%6,%7,%8,%9,%10,%11,%12,%13,%14,%15,%16,%17,%18,%19,%20,%21,%22,%23,%24,%25,%26,%27,%28,%29,%30,%31,%32,%33,%34,%35,%36,%37,%38,%39,%40,%41,%42,%43,%44,%45,%46,%47,%48,%49,%50,%51,%52,%53,%54,%55,%56,%57,%58,%59,%60,%61,%62,%63,%64,%65,%66,%67,%68,%69,%70,%71,%72,%73,%74,%75,%76,%77,%78,%79,%80,%81,%82,%83,%84,%85,%86,%87,%88,%89,%90,%91,%92,%93,%94,%95}, %96, %97, p, 1, 1, 0, 1;\n}\n"
   : "+f"(d[0]),"+f"(d[1]),"+f"(d[2]),"+f"(d[3]),"+f"(d[4]),"+f"(d[5]),"+f"(d[6]),"+f"(d[7]),"+f"(d[8]),"+f"(d[9]),"+f"(d[10]),"+f"(d[11]),"+f"(d[12]),"+f"(d[13]),"+f"(d[14]),"+f"(d[15]),"+f"(d[16]),"+f"(d[17]),"+f"(d[18]),"+f"(d[19]),"+f"(d[20]),"+f"(d[21]),"+f"(d[22]),"+f"(d[23]),"+f"(d[24]),"+f"(d[25]),"+f"(d[26]),"+f"(d[27]),"+f"(d[28]),"+f"(d[29]),"+f"(d[30]),"+f"(d[31]),"+f"(d[32]),"+f"(d[33]),"+f"(d[34]),"+f"(d[35]),"+f"(d[36]),"+f"(d[37]),"+f"(d[38]),"+f"(d[39]),"+f"(d[40]),"+f"(d[41]),"+f"(d[42]),"+f"(d[43]),"+f"(d[44]),"+f"(d[45]),"+f"(d[46]),"+f"(d[47]),"+f"(d[48]),"+f"(d[49]),"+f"(d[50]),"+f"(d[51]),"+f"(d[52]),"+f"(d[53]),"+f"(d[54]),"+f"(d[55]),"+f"(d[56]),"+f"(d[57]),"+f"(d[58]),"+f"(d[59]),"+f"(d[60]),"+f"(d[61]),"+f"(d[62]),"+f"(d[63]),"+f"(d[64]),"+f"(d[65]),"+f"(d[66]),"+f"(d[67]),"+f"(d[68]),"+f"(d[69]),"+f"(d[70]),"+f"(d[71]),"+f"(d[72]),"+f"(d[73]),"+f"(d[74]),"+f"(d[75]),"+f"(d[76]),"+f"(d[77]),"+f"(d[78]),"+f"(d[79]),"+f"(d[80]),"+f"(d[81]),"+f"(d[82]),"+f"(d[83]),"+f"(d[84]),"+f"(d[85]),"+f"(d[86]),"+f"(d[87]),"+f"(d[88]),"+f"(d[89]),"+f"(d[90]),"+f"(d[91]),"+f"(d[92]),"+f"(d[93]),"+f"(d[94]),"+f"(d[95])
   : "l"(da), "l"(db), "r"(sd));
}
template<> __device__ __forceinline__ void wgmma_ss<192,1,1>(float* d, uint64_t da, uint64_t db, int sd) {
  asm volatile("{\n.reg .pred p;\nsetp.ne.b32 p, %98, 0;\nwgmma.mma_async.sync.aligned.m64n192k16.f32.bf16.bf16 {%0,%1,%2,%3,%4,%5,%6,%7,%8,%9,%10,%11,%12,%13,%14,%15,%16,%17,%18,%19,%20,%21,%22,%23,%24,%25,%26,%27,%28,%29,%30,%31,%32,%33,%34,%35,%36,%37,%38,%39,%40,%41,%42,%43,%44,%45,%46,%47,%48,%49,%50,%51,%52,%53,%54,%55,%56,%57,%58,%59,%60,%61,%62,%63,%64,%65,%66,%67,%68,%69,%70,%71,%72,%73,%74,%75,%76,%77,%78,%79,%80,%81,%82,%83,%84,%85,%86,%87,%88,%89,%90,%91,%92,%93,%94,%95}, %96, %97, p, 1, 1, 1, 1;\n}\n"
   : "+f"(d[0]),"+f"(d[1]),"+f"(d[2]),"+f"(d[3]),"+f"(d[4]),"+f"(d[5]),"+f"(d[6]),"+f"(d[7]),"+f"(d[8]),"+f"(d[9]),"+f"(d[10]),"+f"(d[11]),"+f"(d[12]),"+f"(d[13]),"+f"(d[14]),"+f"(d[15]),"+f"(d[16]),"+f"(d[17]),"+f"(d[18]),"+f"(d[19]),"+f"(d[20]),"+f"(d[21]),"+f"(d[22]),"+f"(d[23]),"+f"(d[24]),"+f"(d[25]),"+f"(d[26]),"+f"(d[27]),"+f"(d[28]),"+f"(d[29]),"+f"(d[30]),"+f"(d[31]),"+f"(d[32]),"+f"(d[33]),"+f"(d[34]),"+f"(d[35]),"+f"(d[36]),"+f"(d[37]),"+f"(d[38]),"+f"(d[39]),"+f"(d[40]),"+f"(d[41]),"+f"(d[42]),"+f"(d[43]),"+f"(d[44]),"+f"(d[45]),"+f"(d[46]),"+f"(d[47]),"+f"(d[48]),"+f"(d[49]),"+f"(d[50]),"+f"(d[51]),"+f"(d[52]),"+f"(d[53]),"+f"(d[54]),"+f"(d[55]),"+f"(d[56]),"+f"(d[57]),"+f"(d[58]),"+f"(d[59]),"+f"(d[60]),"+f"(d[61]),"+f"(d[62]),"+f"(d[63]),"+f"(d[64]),"+f"(d[65]),"+f"(d[66]),"+f"(d[67]),"+f"(d[68]),"+f"(d[69]),"+f"(d[70]),"+f"(d[71]),"+f"(d[72]),"+f"(d[73]),"+f"(d[74]),"+f"(d[75]),"+f"(d[76]),"+f"(d[77]),"+f"(d[78]),"+f"(d[79]),"+f"(d[80]),"+f"(d[81]),"+f"(d[82]),"+f"(d[83]),"+f"(d[84]),"+f"(d[85]),"+f"(d[86]),"+f"(d[87]),"+f"(d[88]),"+f"(d[89]),"+f"(d[90]),"+f"(d[91]),"+f"(d[92]),"+f"(d[93]),"+f"(d[94]),"+f"(d[95])
   : "l"(da), "l"(db), "r"(sd));
}

__device__ __forceinline__ void stats_publish(uint32_t sb, int layer, int rb, int hg, int ht, uint32_t tag) {
  const int lane = ht & 31, w = ht >> 5, g = lane >> 2, t = lane & 3, ks = hg & 3;
  uint32_t xa;
  if (layer == 0) {
    const int row = 16 * w + (lane & 15), kc = 2 * ks + (lane >> 4);
    xa = row * 128 + ((kc ^ (row & 7)) << 4);
  } else {
    const int k = 16 * ks + (lane & 7) + 8 * (lane >> 4), pc = 2 * w + ((lane >> 3) & 1);
    xa = k * 128 + ((pc ^ (k & 7)) << 4);
  }
  float s[4] = {0.f, 0.f, 0.f, 0.f}, q[4] = {0.f, 0.f, 0.f, 0.f};
#pragma unroll 1
  for (int c = hg >> 2; c < 8; c += 2) {
    uint32_t A[2][4];
    mbar_wait(sb + SM_BAR + 8 * (B_XF + c), layer);
#pragma unroll
    for (int h = 0; h < 2; h++) {
      if (layer == 0) ldsm4(A[h], sb + SM_X + c * 16384 + h * 8192 + xa);
      else ldsm4t(A[h], sb + SM_X + c * 16384 + h * 8192 + xa);
    }
    if (c >= 6) ATS(48, 256);
    if (c < 2) ATS(51, 256);
#pragma unroll
    for (int r = 0; r < 4; r++)
#pragma unroll
      for (int i = 0; i < 2; i++) {
        const uint32_t v = A[r >> 1][2 * i + (r & 1)];
        const float a = bf_lo(v), b = bf_hi(v);
        s[r] += a + b; q[r] = fmaf(a, a, q[r]); q[r] = fmaf(b, b, q[r]);
      }
  }
#pragma unroll
  for (int r = 0; r < 2; r++) {
    s[r] = ((t & 2) ? s[r + 2] : s[r]) + __shfl_xor_sync(~0u, (t & 2) ? s[r] : s[r + 2], 2);
    q[r] = ((t & 2) ? q[r + 2] : q[r]) + __shfl_xor_sync(~0u, (t & 2) ? q[r] : q[r + 2], 2);
  }
  s[0] = ((t & 1) ? s[1] : s[0]) + __shfl_xor_sync(~0u, (t & 1) ? s[0] : s[1], 1);
  q[0] = ((t & 1) ? q[1] : q[0]) + __shfl_xor_sync(~0u, (t & 1) ? q[0] : q[1], 1);
  st_part(&g_part[(rb * 8 + hg) * 128 + 64 * (t >> 1) + 16 * w + 8 * (t & 1) + g], s[0], q[0], tag);
  ATS(49, 256);
}
__device__ __forceinline__ void stats_gather(uint32_t sb, int rb, int ht, uint32_t tag) {
  const uint2* src = &g_part[rb * 8 * 128 + ht];
  uint2 v[8];
  for (int it = 0;; it++) {
    uint32_t bad = 0;
#pragma unroll
    for (int i = 0; i < 8; i++) v[i] = ld_part(src + i * 128);
#pragma unroll
    for (int i = 0; i < 8; i++) bad |= v[i].y ^ tag;
    if (__all_sync(~0u, (bad & 7u) == 0)) break;
    if (it > (1 << 22)) __trap();
  }
  float s = 0.f, q = 0.f;
#pragma unroll
  for (int i = 0; i < 8; i++) { s += __uint_as_float(v[i].x); q += __uint_as_float(v[i].y); }
  const float mean = s * (1.f / DM);
  const float rstd = rsqrt_approx(fmaxf(q * (1.f / DM) - mean * mean, 0.f) + 1e-5f);
  asm volatile("st.shared.v2.f32 [%0], {%1,%2};" ::"r"(sb + SM_ST + ht * 8), "f"(mean), "f"(rstd) : "memory");
  __syncwarp();
  if (elect_one()) mbar_arrive(sb + SM_BAR + 8 * B_STF);
}
__device__ __forceinline__ void halo_receive(uint32_t sb, int layer, int rb, int hg, int ht) {
  const int lane = ht & 31, h = ht >> 5;
  uint4 kv = make_uint4(0, 0, 0, 0);
  mbar_wait(sb + SM_BAR + 8 * B_SD, layer);
  if (rb & 7) {
    const uint32_t tag = 2 * lds32(sb + SM_EP) + layer + 1;
    const uint4* src = &g_halo[((rb - 1) * 8 + hg) * 192 + h * 48];
    if (layer == 0) delay<D_HALO>(); else delay<D_HALO1>();
    uint4 a;
    uint2 b;
    int it = 0;
    do {
      a = ld_tagged(src + lane); b = ld_part((const uint2*)(src + 32) + lane);
      if (++it > (1 << 22)) __trap();
    } while (!__all_sync(~0u, a.w == tag && b.y == tag));
    kv = make_uint4(a.x, a.y, movm_t(a.z), movm_t(b.x));
  }
  sts128(sb + SM_KVX + h * 512 + lane * 16, kv);
  ATS(61, 256);
  bar_arrive(7, 160);
  if (elect_one()) mbar_arrive(sb + SM_BAR + 8 * B_HF);
}

__device__ __forceinline__ void halo_receive1(uint32_t sb, int layer, int rb, int hg, int lane, uint32_t tag) {
  uint4 a[4];
  uint2 b[4];
  mbar_wait(sb + SM_BAR + 8 * B_SD, layer);
  if (rb & 7) {
    const uint4* src = &g_halo[((rb - 1) * 8 + hg) * 192];
    if (layer == 0) delay<D_HALO>(); else delay<D_HALO1>();
    for (int it = 0;; it++) {
      uint32_t bad = 0;
#pragma unroll
      for (int h = 0; h < 4; h++) { a[h] = ld_tagged(src + h * 48 + lane); b[h] = ld_part((const uint2*)(src + h * 48 + 32) + lane); }
#pragma unroll
      for (int h = 0; h < 4; h++) {
        bad |= (a[h].w ^ tag) | (b[h].y ^ tag);
        a[h].z = movm_t(a[h].z); a[h].w = movm_t(b[h].x);
      }
      if (__all_sync(~0u, bad == 0)) break;
      if (it > (1 << 22)) __trap();
    }
  } else {
#pragma unroll
    for (int h = 0; h < 4; h++) a[h] = make_uint4(0, 0, 0, 0);
  }
#pragma unroll
  for (int h = 0; h < 4; h++) sts128(sb + SM_KVX + h * 512 + lane * 16, a[h]);
  ATS(61, 448);
  bar_arrive(7, 64);
  if (lane < 4) mbar_arrive(sb + SM_BAR + 8 * B_HF);
}

template <bool TR>
__device__ __forceinline__ void gemm_section(float* acc, float2* cs, uint32_t sb, int layer, int wg, int w, int lane) {
  const uint32_t bar = sb + SM_BAR;
  const bool leader = (w == 0) && (lane == 0);
  auto issue = [&](int c, int slot) {
    mbar_wait(bar + 8 * (B_XF + c), layer);
    mbar_wait(bar + 8 * (B_KVF + c), layer);
    const uint64_t da = mkdesc(sb + SM_X + c * 16384 + wg * 8192, TR ? 8192 : 16, 1024, 1);
    const uint64_t db = mkdesc(sb + SM_W + slot * 24576, 8192, 1024, 1);
    wg_fence();
#pragma unroll
    for (int ks = 0; ks < 4; ks++) wgmma_ss<192, TR ? 1 : 0, 1>(acc, da + (TR ? ks * 128 : ks * 2), db + ks * 128, (c | ks) != 0);
    wg_commit();
  };
  auto step = [&](int c, int slot) {
    issue(c, slot);
    wg_wait<1>();
    if (leader) mbar_arrive(bar + 8 * (B_KVE + c - 1));
  };
  if (!TR) bar_sync(0, NTHREADS);
  if (TR && G_WAIT == 3 && wg == 1) bar_sync(14, 256);
  if (TR && G_WAIT == 4 && wg == 1) mbar_wait(bar + 8 * (B_P + 3), 0);
  issue(0, 0);
  if (threadIdx.x == 0) TS(2 + layer * 20 + 0);
  if (threadIdx.x == 128 && layer == 1) TS(60);
  step(1, 1); step(2, 2); step(3, 0); step(4, 1);
  auto ld_cs = [&](int j0) {
#pragma unroll
    for (int j = j0; j < j0 + 8; j++) cs[j] = lds64f(sb + SM_CS + 4 * (8 * j + 2 * (lane & 3)));
  };
  if (TR) ld_cs(8);
  step(5, 2);
  if (!TR && !CS_LATE0) { mbar_wait(bar + 8 * B_CSF, 0); ld_cs(8); }
  if (TR || !CS_LATE0) ld_cs(16);
  if (wg == 0) bar_sync(5, 256);
  issue(6, 0);
  issue(7, 1);
  if (wg == 1) bar_arrive(5, 256);
  if (!TR && CS_LATE0) { mbar_wait(bar + 8 * B_CSF, 0); ld_cs(8); ld_cs(16); }
}

__device__ __forceinline__ void attn_phase(const Params& p, uint32_t sb, int layer, int rb, int hg, int wg, int w) {
  const int lane = opaque_tid() & 31;
  const int g = lane >> 2, t = lane & 3;
  const uint32_t bar = sb + SM_BAR;
  const int row0 = 64 * wg + 16 * w;
  const bool leader = (w == 0) && (lane == 0);
  float acc[96];
  float2 cs[24];
  if (layer) gemm_section<true>(acc, cs, sb, layer, wg, w, lane);
  else gemm_section<false>(acc, cs, sb, layer, wg, w, lane);
  ATS(41, 224);
  mbar_wait(bar + 8 * B_STF, layer);
  const uint32_t tag = 2 * lds32(sb + SM_EP) + layer + 1;
  const float2 st0 = lds64f(sb + SM_ST + (row0 + g) * 8), st1 = lds64f(sb + SM_ST + (row0 + g + 8) * 8);
  const float mean0 = st0.x, rstd0 = st0.y, mean1 = st1.x, rstd1 = st1.y;
  wg_wait<0>();
  if (threadIdx.x == 0) TS(2 + layer * 20 + 1);
  ATS(39, 224);
  if (leader) mbar_arrive(bar + 8 * B_QDONE);

  uint32_t fp[4][4], fl[4][4], fh[4][4], qa[4][4];
  const int cw = 4 * wg + w;
  {
    const float nm0 = -mean0 * rstd0, nm1 = -mean1 * rstd1;
    const uint32_t kvx = sb + SM_KVX + cw * 2048 + lane * 16;
#pragma unroll
    for (int h = 0; h < 4; h++)
#pragma unroll
      for (int k = 0; k < 4; k++) {
        const int j = 8 + (k >> 1) * 8 + 2 * h + (k & 1);
        fh[h][k] = packbf(fmaf(acc[4 * j + 2], rstd1, nm1 * cs[j].x), fmaf(acc[4 * j + 3], rstd1, nm1 * cs[j].y));
      }
    if (cw == 7) {
      uint4* halo = &g_halo[(rb * 8 + hg) * 192];
#pragma unroll
      for (int h = 0; h < 4; h++) {
        st_tagged3(halo + h * 48 + lane, fh[h][0], fh[h][1], fh[h][2], tag);
        asm volatile("st.relaxed.gpu.global.v2.u32 [%0], {%1,%2};" ::"l"((uint2*)(halo + h * 48 + 32) + lane), "r"(fh[h][3]), "r"(tag) : "memory");
      }
      if (elect_one()) mbar_arrive(bar + 8 * B_SD);
      if (layer == TLAYER && threadIdx.x == 224) TS(47);
    }
#pragma unroll
    for (int h = 0; h < 4; h++) { fh[h][2] = movm_t(fh[h][2]); fh[h][3] = movm_t(fh[h][3]); }
    if (cw != 7) {
#pragma unroll
      for (int h = 0; h < 4; h++) sts128(kvx + 2048 + h * 512, make_uint4(fh[h][0], fh[h][1], fh[h][2], fh[h][3]));
      bar_arrive(8 + cw, 64);
    }
    sched_fence<6>();
    if (layer == TLAYER && threadIdx.x == 0) TS(45);
#pragma unroll
    for (int j = 0; j < 8; j++) cs[j] = lds64f(sb + SM_CS + 4 * (8 * j + 2 * t));
#pragma unroll
    for (int h = 0; h < 4; h++)
#pragma unroll
      for (int k = 0; k < 4; k++) {
        const int j = 8 + (k >> 1) * 8 + 2 * h + (k & 1);
        fl[h][k] = packbf(fmaf(acc[4 * j], rstd0, nm0 * cs[j].x), fmaf(acc[4 * j + 1], rstd0, nm0 * cs[j].y));
        if (k >= 2) fl[h][k] = movm_t(fl[h][k]);
      }
#pragma unroll
    for (int h = 0; h < 4; h++) {
#pragma unroll
      for (int dh = 0; dh < 2; dh++) {
        const int j = 2 * h + dh;
        const float2 c2 = cs[j];
        qa[h][2 * dh] = packbf(fmaf(-mean0, c2.x, acc[4 * j + 0]), fmaf(-mean0, c2.y, acc[4 * j + 1]));
        qa[h][2 * dh + 1] = packbf(fmaf(-mean1, c2.x, acc[4 * j + 2]), fmaf(-mean1, c2.y, acc[4 * j + 3]));
      }
    }
    if (threadIdx.x == 0) TS(2 + layer * 20 + 2);
    sched_fence<0>();
    bar_sync(7 + cw, cw == 0 && !HALO_W14 ? 160 : 64);
#pragma unroll
    for (int h = 0; h < 4; h++) {
      const uint4 v = lds128(kvx + h * 512);
      fp[h][0] = v.x; fp[h][1] = v.y; fp[h][2] = v.z; fp[h][3] = v.w;
    }
    if (threadIdx.x == 0) TS(2 + layer * 20 + 4);
  }

  const bool u0 = 2 * t > g, u1 = 2 * t + 1 > g;
  const uint32_t mU = (u0 ? 0x0000ffffu : 0u) | (u1 ? 0xffff0000u : 0u);
  const float cl2 = 0.25f * 1.4426950408889634f;
  const float sc0 = rstd0 * cl2, sc1 = rstd1 * cl2;
  const float cneg = ((rb & 7) == 0 && cw == 0) ? -INFINITY : 0.f;
  float v[4][4];
#pragma unroll
  for (int h = 0; h < 4; h++) {
    float T0[4] = {cneg, cneg, cneg, cneg}, T1[4] = {0.f, 0.f, 0.f, 0.f}, T2[4] = {0.f, 0.f, 0.f, 0.f};
    mma_bf16(T1, qa[h], fl[h][0], fl[h][1]);
    mma_bf16(T2, qa[h], fh[h][0], fh[h][1]);
    mma_bf16(T0, qa[h], fp[h][0], fp[h][1]);
    v[h][0] = u0 ? T0[0] : T1[0]; v[h][1] = u1 ? T0[1] : T1[1];
    v[h][2] = u0 ? T1[2] : T2[2]; v[h][3] = u1 ? T1[3] : T2[3];
  }
  float m0[4], m1[4];
#pragma unroll
  for (int h = 0; h < 4; h++) { m0[h] = fmaxf(v[h][0], v[h][1]); m1[h] = fmaxf(v[h][2], v[h][3]); }
#pragma unroll
  for (int o = 1; o <= 2; o <<= 1) {
#pragma unroll
    for (int h = 0; h < 4; h++) {
      m0[h] = fmaxf(m0[h], __shfl_xor_sync(~0u, m0[h], o));
      m1[h] = fmaxf(m1[h], __shfl_xor_sync(~0u, m1[h], o));
    }
  }
  float O0[4][4], O1[4][4], Z[4][4];
#pragma unroll
  for (int h = 0; h < 4; h++) {
    const float mm0 = -m0[h] * sc0, mm1 = -m1[h] * sc1;
    const uint32_t P0 = packbf(ex2(fmaf(v[h][0], sc0, mm0)), ex2(fmaf(v[h][1], sc0, mm0)));
    const uint32_t P1 = packbf(ex2(fmaf(v[h][2], sc1, mm1)), ex2(fmaf(v[h][3], sc1, mm1)));
#pragma unroll
    for (int k = 0; k < 4; k++) O0[h][k] = O1[h][k] = Z[h][k] = 0.f;
    mma_bf16_k8(Z[h], P0, P1, 0x3f803f80u);
    mma_bf16_k8(O0[h], P0 & ~mU, P1 & mU, fl[h][2]); mma_bf16_k8(O1[h], P0 & ~mU, P1 & mU, fl[h][3]);
    mma_bf16_k8(O0[h], P0 & mU, 0u, fp[h][2]); mma_bf16_k8(O1[h], P0 & mU, 0u, fp[h][3]);
    mma_bf16_k8(O0[h], 0u, P1 & ~mU, fh[h][2]); mma_bf16_k8(O1[h], 0u, P1 & ~mU, fh[h][3]);
  }
  const uint32_t ob = sb + SM_OST + wg * 8192;
  const int o_row = 16 * w + (lane & 7) + 8 * ((lane >> 3) & 1);
#pragma unroll
  for (int h = 0; h < 4; h++) {
    const float i0 = rcp_approx(Z[h][0]), i1 = rcp_approx(Z[h][2]);
    const int ch = 2 * h + (lane >> 4);
    stsm4(ob + o_row * 128 + ((ch ^ (o_row & 7)) << 4), packbf(O0[h][0] * i0, O0[h][1] * i0), packbf(O0[h][2] * i1, O0[h][3] * i1),
          packbf(O1[h][0] * i0, O1[h][1] * i0), packbf(O1[h][2] * i1, O1[h][3] * i1));
  }
  if (threadIdx.x == 0) TS(2 + layer * 20 + 5);
  ATS(57, 128); ATS(20, 96);
  bar_sync(2 + wg, 128);
  if (w == 0 && elect_one()) {
    fence_async_smem();
    tma_st(&p.mapO, hg * 64, rb * 128 + wg * 64, ob);
    bulk_commit();
    mbar_arrive(bar + 8 * B_AD);
    bulk_wait_all();
    red_relaxed(&g_cnt[(C_O + rb) * 32]);
    mbar_arrive(bar + 8 * B_OST);
    if (threadIdx.x == 0) TS(2 + layer * 20 + 6);
  }
  __syncwarp();
}

__device__ __forceinline__ void proj_phase(const Params& p, uint32_t sb, int layer, int rb, int q, int wg, int w) {
  const int lane = opaque_tid() & 31;
  const bool TR = layer != 0;
  const int t = lane & 3;
  const uint32_t bar = sb + SM_BAR;
  const uint32_t rbx = sb + SM_R + wg * 8192;
  uint32_t res[16];
  mbar_wait(bar + 8 * B_RF, layer);
  if (threadIdx.x == 0) TS(2 + layer * 20 + 7);
  if (!TR) {
#pragma unroll
    for (int j = 0; j < 8; j += 2) {
      const int mi = lane >> 3;
      const int row = 16 * w + (lane & 7) + 8 * (mi & 1), ch = j + (mi >> 1);
      ldsm4(&res[2 * j], rbx + row * 128 + ((ch ^ (row & 7)) << 4));
    }
  } else {
#pragma unroll
    for (int j = 0; j < 8; j += 2) {
      const int mi = lane >> 3;
      const int line = 8 * (j + (mi >> 1)) + (lane & 7), pc = 2 * w + (mi & 1);
      ldsm4t(&res[2 * j], rbx + line * 128 + ((pc ^ (line & 7)) << 4));
    }
  }
  bar_sync(2 + wg, 128);
  float acc[32];
#pragma unroll
  for (int i = 0; i < 16; i++) {
    asm volatile("shl.b32 %0, %1, 16;" : "=f"(acc[2 * i]) : "r"(res[i]));
    asm volatile("and.b32 %0, %1, 0xffff0000;" : "=f"(acc[2 * i + 1]) : "r"(res[i]));
  }
  const uint32_t tag = part_tag(lds32(sb + SM_EP), 2 * layer + 1);
  mbar_wait(bar + 8 * B_ZF, layer);
  mbar_wait(bar + 8 * B_WOF, layer);
#pragma unroll P_UNROLL
  for (int c = 0; c < 8; c++) {
    mbar_wait(bar + 8 * (B_OF + c), layer);
    if (c == 0 && threadIdx.x == 0) TS(2 + layer * 20 + 8);
    const uint64_t da = mkdesc(sb + sm_o(c) + wg * 8192, 16, 1024, 1);
    const uint64_t db = mkdesc(sb + SM_WO + c * 8192, 8192, 1024, 1);
    wg_fence();
#pragma unroll
    for (int ks = 0; ks < 4; ks++) wgmma_ss<64, 0, 1>(acc, da + ks * 2, db + ks * 128, 1);
    wg_commit();
  }
  wg_wait<0>();
#pragma unroll
  for (int i = 0; i < 32; i++) asm volatile("" : "+f"(acc[i]) :: "memory");
  if (threadIdx.x == 0) TS(2 + layer * 20 + 9);
  if (lane == 0 && w == 0) mbar_arrive(bar + 8 * B_PDONE);
  {
    float s[4], qq[4];
#pragma unroll
    for (int k = 0; k < 4; k++) { s[k] = acc[k]; qq[k] = acc[k] * acc[k]; }
#pragma unroll
    for (int j = 1; j < 8; j++)
#pragma unroll
      for (int k = 0; k < 4; k++) { s[k] += acc[4 * j + k]; qq[k] = fmaf(acc[4 * j + k], acc[4 * j + k], qq[k]); }
    const float s0 = s[0] + s[1], s1 = s[2] + s[3], q0 = qq[0] + qq[1], q1 = qq[2] + qq[3];
    float sr = ((t & 1) ? s1 : s0) + __shfl_xor_sync(~0u, (t & 1) ? s0 : s1, 1);
    float qr = ((t & 1) ? q1 : q0) + __shfl_xor_sync(~0u, (t & 1) ? q0 : q1, 1);
    sr += __shfl_xor_sync(~0u, sr, 2);
    qr += __shfl_xor_sync(~0u, qr, 2);
    if (t < 2) st_part(&g_part[(rb * 8 + q) * 128 + 64 * wg + 16 * w + (lane >> 2) + 8 * t], sr, qr, tag);
    __syncwarp();
    if (elect_one()) mbar_arrive(bar + 8 * B_PS);
    sched_fence<7>();
  }
#pragma unroll
  for (int j = 0; j < 8; j += 2) {
    const int mi = lane >> 3;
    const int line = 8 * (j + (mi >> 1)) + (lane & 7), pc = 2 * w + (mi & 1);
    stsm4t(rbx + line * 128 + ((pc ^ (line & 7)) << 4), packbf(acc[4 * j], acc[4 * j + 1]), packbf(acc[4 * j + 2], acc[4 * j + 3]),
           packbf(acc[4 * j + 4], acc[4 * j + 5]), packbf(acc[4 * j + 6], acc[4 * j + 7]));
  }
  fence_writer();
  bar_sync(2 + wg, 128);
  if (w == 0 && elect_one()) {
    fence_reader();
    fence_async_global();
    tma_st(&p.mapXT, rb * 128 + wg * 64, (2 * layer) * DM + q * 64, rbx);
    bulk_commit();
    if (threadIdx.x == 0) TS(2 + layer * 20 + 10);
    bulk_wait_all();
    red_relaxed(&g_cnt[C_CS * 32 + 2 + layer]);
    if (wg == 0) mbar_arrive(bar + 8 * B_RE);
  }
  __syncwarp();
}
__device__ __forceinline__ void proj_stats(uint32_t sb, int layer, int rb, int q, int lane, uint32_t tag) {
  const int r = 16 * q + (lane & 15);
  const uint2* src = &g_part[rb * 8 * 128 + r];
  uint32_t* dst = g_stats + layer * LSEQ + (rb >> 1) * 256 + ((r >> 2) & 1) * 128 + ((rb & 1) * 16 + (r >> 3)) * 4 + (r & 3);
  mbar_wait(sb + SM_BAR + 8 * B_PS, layer);
  delay<D_PST>();
  for (int it = 0;; it++) {
    uint2 v[8];
#pragma unroll
    for (int i = 0; i < 8; i++) v[i] = ld_part(src + i * 128);
    float s[4], qq[4];
    uint32_t bad = 0;
#pragma unroll
    for (int i = 0; i < 4; i++) {
      s[i] = __uint_as_float(v[i].x) + __uint_as_float(v[i + 4].x);
      qq[i] = __uint_as_float(v[i].y) + __uint_as_float(v[i + 4].y);
      bad |= (v[i].y ^ tag) | (v[i + 4].y ^ tag);
    }
    const float mean = ((s[0] + s[1]) + (s[2] + s[3])) * (1.f / DM);
    const float rstd = rsqrt_approx(fmaxf(fmaf((qq[0] + qq[1]) + (qq[2] + qq[3]), 1.f / DM, -mean * mean), 0.f) + 1e-5f);
    const bool ok = __all_sync(~0u, (bad & 7u) == 0);
    if (ok && lane < 16)
      asm volatile("st.relaxed.gpu.global.u32 [%0], %1;" ::"l"(dst), "r"(max(packbf(NORM_FMA ? -mean * rstd : -mean, rstd), 1u)) : "memory");
    if (ok) break;
    if (it > (1 << 22)) __trap();
  }
}

#define NA 14
#define NP 15
template <int M0, int M1> __device__ __forceinline__ void conv_load(uint32_t* A, uint32_t pe) {
#pragma unroll
  for (int m = M0; m < M1; m++) {
    asm volatile("ld.shared.v2.b32 {%0,%1}, [%2];" : "=r"(A[4 * m]), "=r"(A[4 * m + 1]) : "r"(pe + 256 * m) : "memory");
    A[4 * m + 2] = lds32(pe + 256 * m - 4);
  }
}
__device__ __forceinline__ uint32_t copy_reg(uint32_t v, uint32_t zero) { uint32_t r; asm volatile("or.b32 %0, %1, %2;" : "=r"(r) : "r"(v), "r"(zero)); return r; }
__device__ __forceinline__ uint32_t copy_reg2(uint32_t v, uint32_t zero) { uint32_t r; asm volatile("xor.b32 %0, %1, %2;" : "=r"(r) : "r"(v), "r"(zero)); return r; }
__device__ __forceinline__ void conv_park(uint32_t* P, uint32_t pe) {
#pragma unroll
  for (int m = 0; m < NP; m++)
#pragma unroll
    for (int k = 0; k < 3; k++) P[3 * m + k] = lds32(pe + 256 * m - 4 + 4 * k);
}
__device__ __forceinline__ void conv_unpark(uint32_t* A, const uint32_t* P, uint32_t zero) {
#pragma unroll
  for (int m = 0; m < NP; m++) {
    A[4 * m + 2] = copy_reg(P[3 * m], zero); A[4 * m] = copy_reg(P[3 * m + 1], zero);
    A[4 * m + 3] = copy_reg2(P[3 * m + 1], zero); A[4 * m + 1] = copy_reg(P[3 * m + 2], zero);
  }
}
template <int M0, int M1> __device__ __forceinline__ void conv_mmas(float* acc, const uint32_t* A, uint64_t d) {
  if constexpr (M0 < M1) {
    wgmma_rs<128 - 8 * (M0 / 2), 0>(acc, A + 4 * M0, d + (uint64_t)(4 * M0), M0 != 0);
    conv_mmas<M0 + 1, M1>(acc, A, d);
  }
}
struct SumAddr { uint32_t l0, l1, l2, se, so; };
__device__ __forceinline__ SumAddr conv_sum_addr(uint32_t sb, int c) {
  auto ua = [&](int j) { return sb + cv_u(0) + (127 - (j >> 3)) * 16 + (j & 7) * 2; };
  auto sa = [&](int hc) { const int ci = hc & ~1; return sb + cv_s(0) + ((ci >> 3) & 1) * 1024 + (ci >> 4) * 128 + (((ci ^ (ci >> 4)) & 7) << 4) + (hc & 1) * 8; };
  const int j0 = 4 * (c - 1);
  return {ua(j0 - 2), ua(j0), ua(j0 + 4), sa((c + 1) & 127), sa(c) + 2048};
}
__device__ __forceinline__ void sts64(uint32_t a, uint32_t x, uint32_t y) { asm volatile("st.shared.v2.b32 [%0], {%1,%2};" ::"r"(a), "r"(x), "r"(y) : "memory"); }
__device__ __forceinline__ void conv_sums(const SumAddr& sa, int lc, int c) {
  uint32_t e[4], o[4];
  {
    const float2 em = lds64f(sa.l1 + lc * 32768), om = lds64f(sa.l1 + lc * 32768 + CV_UH);
    e[0] = lds32(sa.l0 + lc * 32768); o[0] = lds32(sa.l0 + lc * 32768 + CV_UH);
    e[3] = lds32(sa.l2 + lc * 32768); o[3] = lds32(sa.l2 + lc * 32768 + CV_UH);
    e[1] = __float_as_uint(em.x); e[2] = __float_as_uint(em.y); o[1] = __float_as_uint(om.x); o[2] = __float_as_uint(om.y);
  }
  uint32_t s7e[2], s7o[2], s9e[2], s9o[2];
  uint32_t pw[4], sh[3];
#pragma unroll
  for (int k = 0; k < 4; k++) pw[k] = hadd2(e[k], o[k]);
#pragma unroll
  for (int k = 0; k < 3; k++) sh[k] = __byte_perm(pw[k], pw[k + 1], 0x5432);
#pragma unroll
  for (int k = 0; k < 2; k++) {
    const uint32_t t3 = hadd2(hadd2(sh[k], sh[k + 1]), pw[k + 1]);
    s7e[k] = hadd2(t3, o[k]); s7o[k] = hadd2(t3, e[k + 2]);
    s9e[k] = hadd2(s7o[k], pw[k]); s9o[k] = hadd2(s7e[k], pw[k + 2]);
  }
  if (c == 127) s9e[0] = s9e[1] = s9o[0] = s9o[1] = 0u;
  sts64(sa.se + lc * 32768, s9e[0], s9e[1]); sts64((sa.se ^ 16) + lc * 32768, s9o[0], s9o[1]);
  sts64(sa.so + lc * 32768, s7e[0], s7e[1]); sts64((sa.so ^ 16) + lc * 32768, s7o[0], s7o[1]);
}

__device__ __forceinline__ void conv_epi(uint32_t sb, int layer, int cta, int ch, int c0, uint4 x0, uint4 x1) {
  uint4 v[2][4];
  const uint4 xr[2] = {x0, x1};
  mbar_wait(sb + SM_BAR + 8 * (B_P + ch), layer);
#pragma unroll
  for (int u = 0; u < 2; u++) {
    const uint32_t pb = sb + cv_pb(ch) + u * (CV_PBW / 2) + c0 * 16;
#pragma unroll
    for (int k = 0; k < 4; k++) v[u][k] = lds128(pb + k * CV_PBW);
  }
#pragma unroll
  for (int u = 0; u < 2; u++) {
    uint4 o;
    o.x = hadd2(xr[u].x, hadd2(hadd2(v[u][0].x, v[u][1].x), hadd2(v[u][2].x, v[u][3].x)));
    o.y = hadd2(xr[u].y, hadd2(hadd2(v[u][0].y, v[u][1].y), hadd2(v[u][2].y, v[u][3].y)));
    o.z = hadd2(xr[u].z, hadd2(hadd2(v[u][0].z, v[u][1].z), hadd2(v[u][2].z, v[u][3].z)));
    o.w = hadd2(xr[u].w, hadd2(hadd2(v[u][0].w, v[u][1].w), hadd2(v[u][2].w, v[u][3].w)));
    if (layer == 0) sts128(sb + cv_s(ch) + (c0 + 128 * u) * 16, o);
    else st_tagged3((uint4*)(g_xT + (size_t)(3 * DM + cv_chan(cta, ch)) * LSEQ) + c0 + 128 * u, o.x, o.y, o.z, o.w);
  }
}
__device__ __forceinline__ void warp_release(uint32_t b) {
  fence_writer();
  __syncwarp();
  if (elect_one()) mbar_arrive(b);
}

__device__ __forceinline__ void conv_prep_load(uint32_t sb, int layer, int cta, int c, uint4 (&xr)[4], uint4 (&st)[4]) {
  sched_fence<8>();
  mbar_wait(sb + SM_BAR + 8 * B_GB, layer);
  if (threadIdx.x == 0) TS(2 + layer * 20 + 11);
  xr[0] = ld_tagged((const uint4*)(g_xT + (size_t)(2 * layer * DM + cta) * LSEQ) + c);
#pragma unroll
  for (int i = 0; i < 2; i++) st[i] = ld_tagged((const uint4*)g_stats + layer * 512 + (c >> 5) * 64 + i * 32 + (c & 31));
}
template <bool HELPER>
__device__ __forceinline__ void conv_prep(uint32_t sb, int layer, int cta, int c, uint4 (&xr)[4], uint4 (&st)[4], const SumAddr& sa) {
  const uint32_t bar = sb + SM_BAR;
  const uint4* xin = (const uint4*)(g_xT + (size_t)(2 * layer * DM + cta) * LSEQ) + c;
  for (int it = 0;; it++) {
    const uint32_t vs = min(min(min(st[0].x, st[0].y), min(st[0].z, st[0].w)), min(min(st[1].x, st[1].y), min(st[1].z, st[1].w)));
    if (__all_sync(~0u, vs != 0 && xr[0].x != ~0u)) break;
    if (it > (1 << 22)) __trap();
    if (!__all_sync(~0u, xr[0].x != ~0u)) xr[0] = ld_tagged(xin);
    if (!__all_sync(~0u, vs != 0)) {
#pragma unroll
      for (int i = 0; i < 2; i++) st[i] = ld_tagged((const uint4*)g_stats + layer * 512 + (c >> 5) * 64 + i * 32 + (c & 31));
    }
  }
  const uint32_t nm[4] = {__byte_perm(st[0].x, st[0].y, 0x5410), __byte_perm(st[0].z, st[0].w, 0x5410), __byte_perm(st[1].x, st[1].y, 0x5410), __byte_perm(st[1].z, st[1].w, 0x5410)};
  const uint32_t rs[4] = {__byte_perm(st[0].x, st[0].y, 0x7632), __byte_perm(st[0].z, st[0].w, 0x7632), __byte_perm(st[1].x, st[1].y, 0x7632), __byte_perm(st[1].z, st[1].w, 0x7632)};
  if (threadIdx.x == 0) TS(2 + layer * 20 + 12);
  const int a = c & 127, h = c >> 7;
#pragma unroll
  for (int i = 0; i < 4; i++) {
    if (i == 1) {
      mbar_wait(bar + 8 * B_XV, layer);
#pragma unroll
      for (int j = 1; j < 4; j++) xr[j] = ld_tagged(xin + j * (128 * LSEQ / 8));
      if (HELPER) {
        mbar_wait(bar + 8 * B_U, layer);
        conv_sums(sa, 0, c);
        fence_async_smem();
        bar_arrive(7, 256);
        sched_fence<1>();
        if (layer == 1 && c == 0) TS(46);
      }
    }
    const uint32_t x[4] = {xr[i].x, xr[i].y, xr[i].z, xr[i].w};
    uint32_t u[4];
#pragma unroll
    for (int k = 0; k < 4; k++)
      u[k] = NORM_FMA ? hfma2(x[k], rs[k], nm[k]) : hmul2(hadd2(x[k], nm[k]), rs[k]);
    sts128(sb + cv_u(i) + h * CV_UH + (127 - a) * 16, make_uint4(u[0], u[1], u[2], u[3]));
    warp_release(bar + 8 * (B_U + i));
    sched_fence<2>();
  }
}
__device__ __forceinline__ void conv_zero(uint32_t sb, int ht) {
  if (ht < 96) {
    const int ch = ht / 24, h2 = (ht / 12) & 1, qq = ht % 12;
    sts128(sb + cv_u(ch) + h2 * CV_UH + (128 + qq) * 16, make_uint4(0, 0, 0, 0));
  }
  if (ht >= 80) {
    const int i = ht - 80, ch = i / 12, q2 = i % 12;
    const int w2 = q2 < 2 ? 1 : q2 < 6 ? 2 : 3, cc = q2 < 2 ? q2 : q2 < 6 ? q2 - 2 : q2 - 6;
    sts128(sb + cv_pb(ch) + w2 * CV_PBW + (cc & 1) * (CV_PBW / 2) + (cc >> 1) * 16, make_uint4(0, 0, 0, 0));
  }
}

#define HANDOVER 1
template <int R>
__device__ __forceinline__ void conv_round(uint32_t sb, int layer, int wg, uint32_t* A, const uint32_t* P, uint32_t pb, uint32_t pe2) {
  const uint32_t bar = sb + SM_BAR;
  const int ch = 2 * R + 1 - wg;
  float acc[64];
  const uint64_t d = mkdesc(sb + cv_u(ch), CV_UH, 128, 0);
  FTS(39);
  if (R == 0) {
    mbar_wait(bar + 8 * (B_U + ch), layer);
    fence_reader();
  }
  sched_fence<3>();
  if (R == 1 || wg == 0) bar_sync(10 + ch, 256);
  if (layer == 0 && ch > 0 && ((PAUSE >> (ch - 1)) & 1)) mbar_wait(bar + 8 * (B_E + ch - 1), 0);
  if (layer == 0 && ch > 0 && ((PAUSE >> (ch + 3)) & 1)) mbar_wait(bar + 8 * (B_P + ch - 1), 0);
  FTS(41);
  if (ch == 0 && threadIdx.x == 128) TS(2 + layer * 20 + 13);
  wg_fence();
  conv_mmas<0, 1>(acc, A, d); conv_mmas<2, NA + 1>(acc, A, d);
  wg_commit();
  FTS(51);
  if (HANDOVER == 0 && (R == 0 || wg == 1)) bar_arrive(11 + ch, 256);
  bar_sync(7 + ch, 256);
  wg_fence();
  conv_mmas<1, 2>(acc, A, d); conv_mmas<NA + 1, 17>(acc, A, d);
  wgmma_ss<64, 1, 1>(acc, mkdesc(sb + cv_s(ch), 1024, 1024, 1), mkdesc(sb + cv_ft(ch), 256, 16, 0), 1);
  wgmma_ss<64, 1, 1>(acc, mkdesc(sb + cv_s(ch) + 2048, 1024, 1024, 1), mkdesc(sb + cv_ft(ch) + 512, 256, 16, 0), 1);
  wg_commit();
  if (HANDOVER == 1 && (R == 0 || wg == 1 || (G_WAIT == 3 && layer == 0))) bar_arrive(11 + ch, 256);
  FTS(61);
  wg_wait<0>();
#pragma unroll
  for (int j = 0; j < 16; j += 2)
    stsm4t(pb + R * 65536 - j * 128, packbf(acc[4 * j], acc[4 * j + 1]), packbf(acc[4 * j + 2], acc[4 * j + 3]),
           packbf(acc[4 * j + 4], acc[4 * j + 5]), packbf(acc[4 * j + 6], acc[4 * j + 7]));
  __syncwarp();
  if (elect_one()) mbar_arrive(bar + 8 * (B_P + ch));
  if (threadIdx.x == 0) TS(2 + layer * 20 + 14 + R);
  FTS(57);
  if (R == 0) {
    conv_unpark(A, P, opaque_tid() >> 10);
    mbar_wait(bar + 8 * (B_U + ch + 2), layer);
    fence_reader();
    conv_load<NP, 17>(A, pe2);
#pragma unroll
    for (int m = NP; m < 17; m++) A[4 * m + 3] = lds32(pe2 + 256 * m);
  }
}
__device__ __forceinline__ void conv_phase(const Params& p, uint32_t sb, int layer, int cta) {
  const int tid = opaque_tid();
  const int wg = __shfl_sync(~0u, tid >> 7, 0), w = __shfl_sync(~0u, (tid >> 5) & 3, 0);
  const uint32_t bar = sb + SM_BAR;
  uint32_t A[68], P[3 * NP];
  const uint32_t pe = sb + cv_pe(1 - wg) + 4 * (16 + 16 * w + 2 * ((tid & 31) >> 2) - 4 * (tid & 3));
  mbar_wait(bar + 8 * B_PE, layer);
  conv_load<0, 17>(A, pe);
#pragma unroll
  for (int m = 0; m < 17; m++) A[4 * m + 3] = copy_reg(A[4 * m], tid >> 10);
  if (wg == 0) {
    uint4 xr[4], st[4];
    if (PARK_FIRST) conv_park(P, pe + 65536);
    conv_prep_load(sb, layer, cta, tid + 128, xr, st);
    if (!PARK_FIRST) conv_park(P, pe + 65536);
    conv_prep<false>(sb, layer, cta, opaque_tid() + 128, xr, st, SumAddr());
  } else {
    conv_park(P, pe + 65536);
  }
  uint32_t pb;
  {
    const int l2 = opaque_tid() & 31, mt = l2 >> 3;
    pb = sb + cv_pb(1 - wg) + w * CV_PBW + (mt & 1) * (CV_PBW / 2) + (127 - 8 * (mt >> 1) - (l2 & 7) + w) * 16;
  }
  conv_round<0>(sb, layer, wg, A, P, pb, pe + 65536);
  conv_round<1>(sb, layer, wg, A, P, pb, 0);
  if (G_WAIT == 1 && layer == 0) mbar_wait(bar + 8 * (B_E + 3), layer);
  if (G_WAIT == 2 && layer == 0) mbar_wait(bar + 8 * (B_P + 3), layer);
}

__device__ __forceinline__ void final_phase(const Params& p, uint32_t sb, int cta, int wg, int w) {
  if (wg == 1 && w == 3) return;
  const int lane = opaque_tid() & 31, g = lane >> 2, t = lane & 3;
  const int lc = wg ? w : 3;
  const int pos0 = (cta & 31) * 64, ch0 = 128 * lc + (cta >> 5) * 32;
  const bf16* src = g_xT + (size_t)(3 * DM + ch0 + 8 * (g >> 1) + (g & 1)) * LSEQ + pos0;
  bf16* dst = p.out + (size_t)(2 * (pos0 & 1023) + (pos0 >> 10)) * DM + ch0 + 8 * t;
  constexpr int RS = 2 * DM;
  int it = 0;
  mbar_wait(sb + SM_BAR + 8 * (B_E + lc), 1);
  delay<D_FIN>();
  if (wg == 0) {
    uint2 v[4];
    for (;;) {
#pragma unroll
      for (int q = 0; q < 4; q++) v[q] = ld_part((const uint2*)(src + 2 * q * LSEQ + 16 * w + 4 * t));
      if (__all_sync(~0u, max(max(v[0].x, v[1].x), max(v[2].x, v[3].x)) != ~0u)) break;
      if (++it > (1 << 22)) __trap();
    }
    if (threadIdx.x == 0) TS(42);
    dst += (16 * w + 4 * (g >> 1) + (g & 1)) * RS;
    *(uint4*)dst = make_uint4(movm_t(v[0].x), movm_t(v[1].x), movm_t(v[2].x), movm_t(v[3].x));
    *(uint4*)(dst + 2 * RS) = make_uint4(movm_t(v[0].y), movm_t(v[1].y), movm_t(v[2].y), movm_t(v[3].y));
  } else {
    uint4 v[2][4];
    bool ok;
    do {
      ok = true;
#pragma unroll
      for (int h = 0; h < 2; h++)
#pragma unroll
        for (int q = 0; q < 4; q++) v[h][q] = ld_tagged((const uint4*)(src + 2 * q * LSEQ + 32 * h + 8 * t));
#pragma unroll
      for (int h = 0; h < 2; h++)
#pragma unroll
        for (int q = 0; q < 4; q++) ok = ok && v[h][q].x != ~0u;
      if (++it > (1 << 22)) __trap();
    } while (!__all_sync(~0u, ok));
    dst += (8 * (g >> 1) + (g & 1)) * RS;
#pragma unroll
    for (int h = 0; h < 2; h++) {
      *(uint4*)(dst + (32 * h + 0) * RS) = make_uint4(movm_t(v[h][0].x), movm_t(v[h][1].x), movm_t(v[h][2].x), movm_t(v[h][3].x));
      *(uint4*)(dst + (32 * h + 2) * RS) = make_uint4(movm_t(v[h][0].y), movm_t(v[h][1].y), movm_t(v[h][2].y), movm_t(v[h][3].y));
      *(uint4*)(dst + (32 * h + 4) * RS) = make_uint4(movm_t(v[h][0].z), movm_t(v[h][1].z), movm_t(v[h][2].z), movm_t(v[h][3].z));
      *(uint4*)(dst + (32 * h + 6) * RS) = make_uint4(movm_t(v[h][0].w), movm_t(v[h][1].w), movm_t(v[h][2].w), movm_t(v[h][3].w));
    }
  }
  if (threadIdx.x == 0) TS(43);
  if (threadIdx.x == 192) TS(63);
  if (threadIdx.x == 0) LTS(1);
}

struct cplx { float r, i; };
__device__ __forceinline__ cplx cmul(cplx a, cplx b) { return {fmaf(a.r, b.r, -a.i * b.i), fmaf(a.r, b.i, a.i * b.r)}; }
__device__ __forceinline__ cplx csqr(cplx a) { return {fmaf(a.r, a.r, -a.i * a.i), (a.r + a.r) * a.i}; }
__device__ __forceinline__ cplx cexp_l(float ar2, float ai, float l) {
  const float m = ex2(ar2 * l);
  const float x = ai * l;
  return {m * __cosf(x), m * __sinf(x)};
}

__device__ __forceinline__ void colsum_publish(uint32_t sb, int rb, int hg, int ht, uint32_t tag) {
  const int lane = ht & 31, q = lane & 15, h = lane >> 4;
  const uint32_t src = sb + SM_CW + (ht >> 5) * 4096 + h * 128 + (q & 1) * 8;
  float s[4] = {0.f, 0.f, 0.f, 0.f};
#pragma unroll 8
  for (int r = 0; r < 16; r++) {
    const float2 v = lds64f(src + r * 256 + (((q >> 1) ^ ((2 * r + h) & 7)) << 4));
    s[0] += bf_lo(__float_as_uint(v.x)); s[1] += bf_hi(__float_as_uint(v.x));
    s[2] += bf_lo(__float_as_uint(v.y)); s[3] += bf_hi(__float_as_uint(v.y));
  }
#pragma unroll
  for (int k = 0; k < 4; k++) s[k] += __shfl_xor_sync(~0u, s[k], 16);
  if (h == 0)
    st_tagged3(&g_colsum[(hg * 16 + rb) * 48 + (ht >> 5) * 16 + q], (__float_as_uint(s[0]) & ~7u) | tag, __float_as_uint(s[1]),
               __float_as_uint(s[2]), __float_as_uint(s[3]));
}
__device__ __forceinline__ void colsum_gather(uint32_t sb, int hg, int ht, uint32_t tag) {
  const int lane = ht & 31, rec = (ht >> 5) * 16 + (lane & 15);
  const uint4* src = &g_colsum[(hg * 16 + (lane >> 4) * 8) * 48 + rec];
  float s[4] = {0.f, 0.f, 0.f, 0.f};
#pragma unroll 1
  for (int h = 0; h < 2; h++, src += 4 * 48) {
    uint4 v[4];
    int it = 0;
    do {
#pragma unroll
      for (int i = 0; i < 4; i++) v[i] = ld_tagged(src + i * 48);
      if (++it > (1 << 22)) __trap();
    } while (!__all_sync(~0u, (v[0].x & 7u) == tag && (v[1].x & 7u) == tag && (v[2].x & 7u) == tag && (v[3].x & 7u) == tag));
#pragma unroll
    for (int i = 0; i < 4; i++) {
      s[0] += __uint_as_float(v[i].x & ~7u); s[1] += __uint_as_float(v[i].y); s[2] += __uint_as_float(v[i].z); s[3] += __uint_as_float(v[i].w);
    }
  }
#pragma unroll
  for (int k = 0; k < 4; k++) s[k] += __shfl_xor_sync(~0u, s[k], 16);
  if (lane < 16) sts128f(sb + SM_CS + rec * 16, s[0], s[1], s[2], s[3]);
}

__device__ __forceinline__ uint32_t packh(float lo, float hi) { uint32_t r; asm("cvt.rn.f16x2.f32 %0, %1, %2;" : "=r"(r) : "f"(hi), "f"(lo)); return r; }
__device__ __forceinline__ void mma_f16(float* d, uint32_t a0, uint32_t a1, uint32_t a2, uint32_t a3, uint32_t b0, uint32_t b1) {
  asm volatile("mma.sync.aligned.m16n8k16.row.col.f32.f16.f16.f32 {%0,%1,%2,%3}, {%4,%5,%6,%7}, {%8,%9}, {%0,%1,%2,%3};"
      : "+f"(d[0]), "+f"(d[1]), "+f"(d[2]), "+f"(d[3]) : "r"(a0), "r"(a1), "r"(a2), "r"(a3), "r"(b0), "r"(b1));
}
struct HSeed { uint32_t r, i; };
__device__ __forceinline__ HSeed hseed(cplx s) { return {packh(s.r, s.r), packh(s.i, s.i)}; }
__device__ __forceinline__ void hcmul(uint32_t& o_r, uint32_t& o_i, uint32_t br, uint32_t bi, HSeed s) {
  asm("{\n.reg .b32 t, u;\nmul.rn.f16x2 t, %3, %5;\nneg.f16x2 t, t;\nmul.rn.f16x2 u, %3, %4;\nfma.rn.f16x2 %0, %2, %4, t;\nfma.rn.f16x2 %1, %2, %5, u;\n}"
      : "=&r"(o_r), "=&r"(o_i) : "r"(br), "r"(bi), "r"(s.r), "r"(s.i));
}
struct HTile { uint32_t r[4], i[4]; };
__device__ __forceinline__ void tile_set(HTile& t, int k, cplx a, cplx b) { t.r[k] = packh(a.r, b.r); t.i[k] = packh(a.i, b.i); }
__device__ __forceinline__ void tile_upper(HTile& t, HSeed s) { hcmul(t.r[2], t.i[2], t.r[0], t.i[0], s); hcmul(t.r[3], t.i[3], t.r[1], t.i[1], s); }
__device__ __forceinline__ HTile tile_shift(const HTile& t, HSeed s) {
  HTile o;
#pragma unroll
  for (int k = 0; k < 4; k++) hcmul(o.r[k], o.i[k], t.r[k], t.i[k], s);
  return o;
}
__device__ __forceinline__ void tile_put(const HTile& t, uint32_t a) {
  sts128(a, make_uint4(t.r[0], t.r[1], t.r[2], t.r[3]));
  sts128(a + 512, make_uint4(t.i[0], t.i[1], t.i[2], t.i[3]));
}
__device__ __forceinline__ HTile tile_get(uint32_t a) { HTile o; ldsm4t(o.r, a); ldsm4t(o.i, a + 512); return o; }
__device__ __forceinline__ void tile_mma(float* T, const HTile& a0, const HTile& a1, const HTile& b) {
  mma_f16(T, a0.r[0], a0.r[1], a0.r[2], a0.r[3], b.r[0], b.r[1]);
  mma_f16(T, a0.i[0], a0.i[1], a0.i[2], a0.i[3], b.i[0], b.i[1]);
  mma_f16(T, a1.r[0], a1.r[1], a1.r[2], a1.r[3], b.r[2], b.r[3]);
  mma_f16(T, a1.i[0], a1.i[1], a1.i[2], a1.i[3], b.i[2], b.i[3]);
}
__device__ __forceinline__ void tile_mma2(float* T, float* U, const HTile& a0, const HTile& a1, const HTile& b, const HTile& c) {
  mma_f16(T, a0.r[0], a0.r[1], a0.r[2], a0.r[3], b.r[0], b.r[1]);
  mma_f16(U, a0.r[0], a0.r[1], a0.r[2], a0.r[3], c.r[0], c.r[1]);
  mma_f16(T, a0.i[0], a0.i[1], a0.i[2], a0.i[3], b.i[0], b.i[1]);
  mma_f16(U, a0.i[0], a0.i[1], a0.i[2], a0.i[3], c.i[0], c.i[1]);
  mma_f16(T, a1.r[0], a1.r[1], a1.r[2], a1.r[3], b.r[2], b.r[3]);
  mma_f16(U, a1.r[0], a1.r[1], a1.r[2], a1.r[3], c.r[2], c.r[3]);
  mma_f16(T, a1.i[0], a1.i[1], a1.i[2], a1.i[3], b.i[2], b.i[3]);
  mma_f16(U, a1.i[0], a1.i[1], a1.i[2], a1.i[3], c.i[2], c.i[3]);
}
__device__ __forceinline__ void kgen_unit(uint32_t tab, uint32_t taba, float ar2, float ai, cplx c, float (&T)[5][4]) {
  const cplx z1 = cexp_l(ar2, ai, 1.f), z16 = cexp_l(ar2, ai, 16.f), z256 = cexp_l(ar2, ai, 256.f);
  HTile a0, a1, b0, b1;
  {
    const cplx y1 = {z16.r, -z16.i}, y2 = csqr(y1), y3 = cmul(y2, y1), y4 = csqr(y2), y5 = cmul(y4, y1), y6 = csqr(y3), y7 = cmul(y4, y3);
    HTile t;
    tile_set(t, 0, {1.f, 0.f}, y1); tile_set(t, 1, y2, y3); tile_set(t, 2, y4, y5); tile_set(t, 3, y6, y7);
    const HTile u = tile_shift(t, hseed(csqr(y4)));
    __syncwarp();
    tile_put(t, tab); tile_put(u, tab + 1024);
    __syncwarp();
    a0 = tile_get(taba); a1 = tile_get(taba + 256);
  }
  const cplx z2 = csqr(z1), z4 = csqr(z2), z8 = csqr(z4);
  const HSeed h8 = hseed(z8);
  const cplx d = cmul(c, z256), e = cmul(d, z256);
  {
    const cplx z512 = csqr(z256), f = cmul(e, z512), f8 = cmul(f, z8), f16 = cmul(f, z16), e4 = cmul(e, z4);
    HTile t, u;
    tile_set(t, 0, e4, cmul(e, z8)); tile_set(t, 1, cmul(e4, z8), cmul(e, z16));
    tile_upper(t, hseed(z256));
    tile_set(u, 0, f8, f16); tile_set(u, 1, cmul(f8, z256), cmul(f16, z256));
    tile_upper(u, hseed(z512));
    __syncwarp();
    tile_put(t, tab); tile_put(u, tab + 1024);
    __syncwarp();
    b0 = tile_get(tab); b1 = tile_get(tab + 1024);
  }
  {
    const cplx d2 = cmul(d, z2), d4 = cmul(d, z4);
    HTile t;
    tile_set(t, 0, d2, d4); tile_set(t, 1, cmul(d2, z4), cmul(d, z8));
    tile_upper(t, h8);
    __syncwarp();
    tile_put(t, tab);
    __syncwarp();
    tile_mma2(T[3], T[4], a0, a1, b0, b1);
    b0 = tile_get(tab);
  }
  {
    const cplx c1 = cmul(c, z1), c2 = cmul(c, z2), c3 = cmul(c1, z2), c4 = cmul(c, z4);
    HTile t;
    tile_set(t, 0, c1, c2); tile_set(t, 1, c3, c4); tile_set(t, 2, cmul(c1, z4), cmul(c2, z4)); tile_set(t, 3, cmul(c3, z4), cmul(c4, z4));
    const HTile u = tile_shift(t, h8);
    __syncwarp();
    tile_put(t, tab); tile_put(u, tab + 1024);
    __syncwarp();
    tile_mma(T[2], a0, a1, b0);
    b0 = tile_get(tab); b1 = tile_get(tab + 1024);
    tile_mma2(T[0], T[1], a0, a1, b0, b1);
  }
}
struct ModeIn { uint2 ar, ai, br, bi, cr, ci; };
__device__ __forceinline__ ModeIn load_modes(const Params& p, int idx) {
  return {*(const uint2*)(p.a_re + idx), *(const uint2*)(p.a_im + idx), *(const uint2*)(p.b_re + idx),
          *(const uint2*)(p.b_im + idx), *(const uint2*)(p.c_re + idx), *(const uint2*)(p.c_im + idx)};
}
__device__ __forceinline__ float bf_el(uint2 v, int k) { const uint32_t x = (k & 2) ? v.y : v.x; return (k & 1) ? bf_hi(x) : bf_lo(x); }
struct KGen { float4 cur; float T[5][4]; };
__device__ __forceinline__ uint32_t kgen_slot(uint32_t sb, int ht, int u) {
  return sb + (u < 3 ? SM_KC + (ht >> 5) * (KC_STRIDE * 2) + (u - 1) * 512 + (ht & 31) * 16 + 16 : SM_HALO + 1024 + ht * 16);
}
__device__ __forceinline__ void kgen_setup(KGen& s, uint32_t sb, int cta, int ht, const ModeIn& in, bf16 logdt, bf16 dskip) {
  const float dt = __bfloat162float(__float2bfloat16_rn(expf(__bfloat162float(logdt))));
  float mx = 0.f, k0 = 0.f, ar2[4];
  cplx c[4];
#pragma unroll
  for (int k = 0; k < 4; k++) {
    ar2[k] = (dt * bf_el(in.ar, k)) * 1.4426950408889634f;
    c[k] = cmul({bf_el(in.cr, k), bf_el(in.ci, k)}, {dt * bf_el(in.br, k), dt * bf_el(in.bi, k)});
    k0 += c[k].r;
    mx = fmaxf(mx, fmaxf(fabsf(c[k].r), fabsf(c[k].i)) * ex2(fmaxf(ar2[k] * 2048.f, 0.f)));
  }
  const int ex = min(max(267 - (int)(__reduce_max_sync(~0u, __float_as_uint(mx)) >> 23), 1), 253);
  const float sc = __uint_as_float(ex << 23);
#pragma unroll
  for (int o = 16; o > 0; o >>= 1) k0 += __shfl_xor_sync(~0u, k0, o);
  if ((ht & 31) == 0) {
    const uint32_t kc = sb + SM_KC + (ht >> 5) * (KC_STRIDE * 2);
    sts16(kc, __bfloat16_as_ushort(__float2bfloat16_rn(k0 + __bfloat162float(dskip))));
    sts16(kc + 641 * 2, 0);
    sts32f(kc + 644 * 2, __uint_as_float((254 - ex) << 23));
  }
  s.cur = make_float4(ar2[0], dt * bf_el(in.ai, 0), c[0].r * sc, c[0].i * sc);
#pragma unroll
  for (int k = 1; k < 4; k++) sts128f(kgen_slot(sb, ht, k), ar2[k], dt * bf_el(in.ai, k), c[k].r * sc, c[k].i * sc);
#pragma unroll
  for (int i = 0; i < 5; i++) s.T[i][0] = s.T[i][1] = s.T[i][2] = s.T[i][3] = 0.f;
}
__device__ __forceinline__ void kgen_finish(KGen& s, uint32_t sb, int cta, int ht) {
  const int w = ht >> 5, lane = ht & 31, g = lane >> 2, t = lane & 3;
  const uint32_t kc = sb + SM_KC + w * KC_STRIDE * 2;
  __syncwarp();
  const float inv = __uint_as_float(lds32(kc + 644 * 2));
  auto put = [&](int idx, float v) {
    sts16(kc + idx * 2, __bfloat16_as_ushort(__float2bfloat16_rn(v)));
  };
#pragma unroll
  for (int hi = 0; hi < 2; hi++)
#pragma unroll
    for (int lo = 0; lo < 2; lo++) {
      const int i = g + 8 * hi, j = 2 * t + lo, e = 2 * hi + lo;
      put(16 * i + 1 + j, s.T[0][e] * inv);
      put(16 * i + 9 + j, s.T[1][e] * inv);
      put(257 + 8 * i + j, s.T[2][e] * inv);
      put(385 + 4 * i + (j & 3) + 64 * (j >> 2), s.T[3][e] * inv);
      put(513 + 2 * i + lo + 32 * t, s.T[4][e] * inv);
    }
}

__device__ __forceinline__ void expand_taps(uint32_t sb, int ht) {
  const int ch = ht >> 5, lane = ht & 31;
  const uint32_t kc = sb + SM_KC + ch * KC_STRIDE * 2;
  const uint32_t dst0 = sb + cv_pe(ch);
  auto put = [&](int G, uint32_t u0, uint32_t u1, uint32_t v0, uint32_t v1, uint32_t v2, uint32_t v3, uint32_t v4, uint32_t v5, uint32_t v6, uint32_t v7) {
    const uint32_t dst = dst0 + G * 32;
    sts128(dst, make_uint4(v0 | (u0 << 16), v1 | (u1 << 16), v2 | (v0 << 16), v3 | (v1 << 16)));
    sts128(dst + 16, make_uint4(v4 | (v2 << 16), v5 | (v3 << 16), v6 | (v4 << 16), v7 | (v5 << 16)));
  };
  {
    const uint4 q = lds128(kc + lane * 16);
    const uint32_t pv = lane ? lds32(kc + lane * 16 - 4) : 0u;
    const uint32_t dst = dst0 + (lane + 2) * 32;
    sts128(dst, make_uint4(__byte_perm(q.x, pv, 0x5410), __byte_perm(q.x, pv, 0x7632), __byte_perm(q.y, q.x, 0x5410), __byte_perm(q.y, q.x, 0x7632)));
    sts128(dst + 16, make_uint4(__byte_perm(q.z, q.y, 0x5410), __byte_perm(q.z, q.y, 0x7632), __byte_perm(q.w, q.z, 0x5410), __byte_perm(q.w, q.z, 0x7632)));
    if (lane < 4) sts128(dst0 + lane * 16, make_uint4(0, 0, 0, 0));
  }
  uint32_t a[5], b[2][3], fv[4];
  {
    const uint32_t s1 = kc + 2 * (256 + 4 * lane);
#pragma unroll
    for (int k = 0; k < 5; k++) a[k] = lds16(s1 + 2 * k);
#pragma unroll
    for (int u = 0; u < 2; u++) {
      const uint32_t s2 = kc + 2 * (384 + 2 * (lane + 32 * u));
#pragma unroll
      for (int k = 0; k < 3; k++) b[u][k] = lds16(s2 + 2 * k);
    }
#pragma unroll
    for (int k = 0; k < 4; k++) fv[k] = lds16(kc + 2 * (640 - 4 * lane - k));
  }
  const uint32_t am1 = lds16(kc + 2 * (lane ? 256 + 4 * lane : 255)), am2 = lds16(kc + 2 * (lane ? 255 + 4 * lane : 254));
  const uint32_t bm2 = lds16(kc + 2 * (lane ? 384 + 2 * lane : 383)), k1024 = lds16(kc + 2 * 512);
  put(34 + lane, am2, am1, a[0], a[0], a[1], a[2], a[2], a[2], a[3], a[4]);
#pragma unroll
  for (int u = 0; u < 2; u++) put(66 + lane + 32 * u, u ? b[u][0] : bm2, b[u][0], b[u][0], b[u][0], b[u][0], b[u][1], b[u][1], b[u][1], b[u][2], b[u][2]);
  if (lane < 10) {
    const uint32_t v = lane == 0 ? k1024 : 0u;
    put(130 + lane, v, v, v, v, v, v, v, 0u, 0u, 0u);
  }
  const uint32_t ft = sb + cv_ft(ch) + 4 * lane;
#pragma unroll
  for (int ty = 0; ty < 2; ty++) {
    const uint32_t v = fv[ty] | (fv[ty + 2] << 16);
    sts32f(ft + ty * 512, __uint_as_float(v));
    sts32f(ft + ty * 512 + 128, 0.f);
    sts32f(ft + ty * 512 + 256 + (lane < 2 ? 120 : -8), __uint_as_float(lane < 2 ? 0u : v));
    sts32f(ft + ty * 512 + 384, 0.f);
  }
}

__device__ __forceinline__ int role_id() { int v; asm volatile("mov.u32 %0, %%ctaid.x;" : "=r"(v)); return v; }
#define GMAP 8
__device__ __forceinline__ int role_rb(int cta) { return 4 * (cta >> 5) + (cta & 3); }
__device__ __forceinline__ int role_hg(int cta) { return 2 * (((cta >> 3) & 3) ^ (((cta >> 5) & 1) * 3)) + ((cta >> 2) & 1); }
__device__ __forceinline__ int role_rb2(int cta) { return cta >> 3; }
__device__ __forceinline__ int role_q2(int cta) { return cta & 7; }

__global__ void __launch_bounds__(NTHREADS, 1) fused_kernel(const __grid_constant__ Params p) {
  extern __shared__ __align__(1024) uint8_t smem[];
  const uint32_t sb = s32(smem);
  const int tid = threadIdx.x, lane = tid & 31;
  const int warp = __shfl_sync(~0u, tid >> 5, 0);
  const uint32_t bar = sb + SM_BAR;
  if (tid == 0) TS(0);
  const int cta0 = role_id();
  if (warp == 0 && elect_one()) {
    const int rb = role_rb(cta0), hg = role_hg(cta0);
#pragma unroll
    for (int c = 0; c < 2; c++) { mbar_init(bar + 8 * (B_XF + c), 1); mbar_init(bar + 8 * (B_KVF + c), 1); }
    fence_async_smem();
#pragma unroll
    for (int c = 0; c < 2; c++) {
      mbar_expect(bar + 8 * (B_XF + c), 16384);
      tma_ld(sb + SM_X + c * 16384, &p.mapX128, (rb >> 3) * DM + c * 64, (rb & 7) * 128, bar + 8 * (B_XF + c));
      mbar_expect(bar + 8 * (B_KVF + c), 24576);
      tma_ld3(sb + SM_W + c * 24576, &p.mapW3, hg * 64, c * 64, 0, bar + 8 * (B_KVF + c));
    }
  }
  if (warp == 1 && elect_one()) {
    const int rb = role_rb(cta0), hg = role_hg(cta0);
#pragma unroll
    for (int c = 2; c < 8; c++) mbar_init(bar + 8 * (B_XF + c), 1);
    mbar_init(bar + 8 * (B_KVF + 2), 1); mbar_init(bar + 8 * B_CW, 1);
    fence_async_smem();
    delay<D_START>();
    mbar_expect(bar + 8 * B_CW, 12288);
    tma_ld3(sb + SM_CW, &p.mapW3h, hg * 64, rb * 32, 0, bar + 8 * B_CW);
#pragma unroll
    for (int c = 2; c < 8; c++) {
      mbar_expect(bar + 8 * (B_XF + c), 16384);
      tma_ld(sb + SM_X + c * 16384, &p.mapX128, (rb >> 3) * DM + c * 64, (rb & 7) * 128, bar + 8 * (B_XF + c));
      if (c < 3) {
        mbar_expect(bar + 8 * (B_KVF + c), 24576);
        tma_ld3(sb + SM_W + c * 24576, &p.mapW3, hg * 64, c * 64, 0, bar + 8 * (B_KVF + c));
      }
    }
    TS(56);
  }
  if ((warp & 2) != 0 && warp < 15 && elect_one()) {
    const int grp = 1 + (warp & 1) + 2 * (warp >> 2), cnt = grp < 4 ? 1 : grp < 5 ? 2 : grp < 7 ? 4 : 8;
#pragma unroll
    for (int k = 0; k < 10; k++)
      if (k != 0 || grp > 3 || grp == 2) mbar_init(bar + 8 * (10 * grp + k), cnt);
    fence_async_smem();
  }

  if (warp < 8) {
    if (tid == 0) TS(1);
    asm volatile("setmaxnreg.inc.sync.aligned.u32 %0;" ::"n"(R_CONS));
    const int cta = role_id();
    auto warp_id = [] { return __shfl_sync(~0u, opaque_tid() >> 5, 0); };
    if (tid == 0) TS(54);
#pragma unroll 1
    for (int layer = 0; layer < 2; layer++) {
      { const int cw = warp_id(); attn_phase(p, sb, layer, role_rb(cta), role_hg(cta), cw >> 2, cw & 3); }
      if (STOP == 1 + 3 * layer) return;
      { const int cw = warp_id(); proj_phase(p, sb, layer, role_rb2(cta), role_q2(cta), cw >> 2, cw & 3); }
      if (STOP == 2 + 3 * layer) return;
      conv_phase(p, sb, layer, cta);
      if (STOP == 3 + 3 * layer) return;
    }
    { const int cw = warp_id(); final_phase(p, sb, cta, cw >> 2, cw & 3); }
  } else if (warp < 12) {
    asm volatile("setmaxnreg.dec.sync.aligned.u32 %0;" ::"n"(R_HELP));
    const int ht = tid - 256;
    const int cta = role_id(), rb = role_rb(cta), hg = role_hg(cta);
    unsigned ep0 = 0;
    if (ht == 0) ep0 = ld_relaxed(&g_cnt[C_CS * 32]);
    bar_sync(0, NTHREADS);
    if (ht == 0) {
      asm volatile("st.shared.u32 [%0], %1;" ::"r"(sb + SM_EP), "r"(ep0 / NCTA) : "memory");
      mbar_arrive(bar + 8 * B_EP);
    }
    mbar_wait(bar + 8 * B_EP, 0);
    stats_publish(sb, 0, rb, hg, opaque_tid() - 256, part_tag(lds32(sb + SM_EP), 0));
    if (ht < 48) {
      const bf16* q = (&p.a_re)[ht >> 3];
      asm volatile("prefetch.global.L2 [%0];" ::"l"(q + cv_chan(cta, (ht >> 1) & 3) * 128 + (ht & 1) * 64));
    }
    {
      KGen kg;
      const uint32_t tab0 = sb + ((ht >> 5) < 2 ? SM_T : SM_T2 - 4096) + (ht >> 5) * 2048;
      const uint32_t tab = tab0 + (ht & 31) * 16, taba = tab0 + ((ht >> 3) & 1) * 1024 + (((ht >> 1) & 8) + (ht & 7)) * 16;
      delay<D_ST0>();
      stats_gather(sb, rb, opaque_tid() - 256, part_tag(lds32(sb + SM_EP), 0));
      if (ht == 0) TS(40);
      const int chn = cv_chan(cta, ht >> 5);
      const ModeIn modes = load_modes(p, chn * 128 + (ht & 31) * 4);
      const bf16 logdt = p.log_dt[chn], dskip = p.dskip[chn];
      if (!HALO_W14 && KG_START != 4) halo_receive(sb, 0, rb, hg, opaque_tid() - 256);
      if (KG_START == 1) mbar_wait(bar + 8 * B_HF, 0);
      kgen_setup(kg, sb, cta, ht, modes, logdt, dskip);
      if (!HALO_W14 && KG_START == 4) halo_receive(sb, 0, rb, hg, opaque_tid() - 256);
      if (KG_START == 2) mbar_wait(bar + 8 * B_HF, 0);
      if (KG_START == 3) mbar_wait(bar + 8 * B_QDONE, 0);
#pragma unroll 1
      for (int u = 0; u < 4; u++) {
        if (u == KG_PRE) {
          KTS(39);
          mbar_wait(bar + 8 * B_AD, 0);
          KTS(41);
        }
        kgen_unit(tab, taba, kg.cur.x, kg.cur.y, {kg.cur.z, kg.cur.w}, kg.T);
        kg.cur = lds128f(kgen_slot(sb, opaque_tid() - 256, u + 1));
      }
      kgen_finish(kg, sb, cta, opaque_tid() - 256);
    }
    KTS(51);
    bar_sync(4, 128);
#pragma unroll 1
    for (int layer = 0; layer < 2; layer++) {
      if (STOP <= 1 + 3 * layer) return;
      mbar_wait(bar + 8 * (EXP_LATE ? B_PS : B_PDONE), layer);
      expand_taps(sb, opaque_tid() - 256);
      conv_zero(sb, opaque_tid() - 256);
      if (ht == 0) TS(52 + layer);
      warp_release(bar + 8 * B_PE);
      if (STOP <= 2 + 3 * layer) return;
      {
        uint4 xr[4], st[4];
        const int c = opaque_tid() - 256;
        const SumAddr sa = conv_sum_addr(sb, c);
        conv_prep_load(sb, layer, cta, c, xr, st);
        conv_prep<true>(sb, layer, cta, c, xr, st, sa);
        if (layer == 1 && ht == 0) TS(62);
        const bf16* xup = g_xT + (size_t)(2 * layer * DM + cta) * LSEQ + (c + 128) * 8;
        const int ahead = layer ? S_AHEAD1 : S_AHEAD0;
        mbar_wait(bar + 8 * (B_U + 3), layer);
        if (ahead == 2) {
          conv_sums(sa, 1, c);
          fence_async_smem();
          bar_arrive(8, 256);
        }
        st[0] = ldcg128(xup);
#pragma unroll
        for (int lc = 0; lc < 4; lc++) {
          if (lc < 3 && lc + ahead < 4) {
            conv_sums(sa, lc + ahead, c);
            fence_async_smem();
            bar_arrive(7 + lc + ahead, 256);
            sched_fence<4>();
          }
          if (lc < 3) st[lc + 1] = ldcg128(xup + (lc + 1) * 128 * LSEQ);
          conv_epi(sb, layer, cta, lc, c, xr[lc], st[lc]);
          warp_release(bar + 8 * (B_E + lc));
          sched_fence<5>();
          if (layer == 1 && lc == 3 && ht == 0) TS(38);
        }
      }
      if (layer == 0 && STOP > 3) {
        const int c1 = role_id();
        stats_publish(sb, 1, role_rb(c1), role_hg(c1), opaque_tid() - 256, part_tag(lds32(sb + SM_EP), 2));
        delay<D_ST>();
        stats_gather(sb, role_rb(c1), opaque_tid() - 256, part_tag(lds32(sb + SM_EP), 2));
        if (ht == 0) TS(25);
        if (!HALO_W14) halo_receive(sb, 1, role_rb(c1), role_hg(c1), opaque_tid() - 256);
      }
    }
  } else {
    asm volatile("setmaxnreg.dec.sync.aligned.u32 %0;" ::"n"(512 - 2 * R_CONS - R_HELP));
    const int cta = role_id(), rb = role_rb(cta), hg = role_hg(cta), rb2 = role_rb2(cta), q2 = role_q2(cta);
    bar_sync(0, NTHREADS);
    if (warp != 12) {
      mbar_wait(bar + 8 * B_EP, 0);
      const uint32_t tag = lds32(sb + SM_EP) % 7 + 1;
      mbar_wait(bar + 8 * B_CW, 0);
      colsum_publish(sb, rb, hg, tid - 416, tag);
      if (tid == 416) TS(50);
      delay<D_CS>();
      colsum_gather(sb, hg, tid - 416, tag);
      __syncwarp();
      if (tid == 416) TS(55);
    }
    if (elect_one()) mbar_arrive(bar + 8 * B_CSF);
    if (warp == 12) {
      if (elect_one()) {
        unsigned epoch = 0;
#pragma unroll 1
        for (int layer = 0; layer < 2; layer++) {
          auto ld_w = [&](int c, int slot) {
            const uint32_t b = bar + 8 * (B_KVF + c);
            mbar_expect(b, 24576);
            tma_ld3(sb + SM_W + slot * 24576, &p.mapW3, hg * 64, c * 64, 0, b);
          };
          if (layer == 0) {
            mbar_wait(bar + 8 * (B_KVF + 2), 0);
            if (rb2 < 4) tma_prefetch2(&p.mapWo128, q2 * 64, rb2 * 128);
            asm volatile("prefetch.tensormap [%0];" ::"l"(&p.mapO) : "memory");
            asm volatile("prefetch.tensormap [%0];" ::"l"(&p.mapO128) : "memory");
            asm volatile("prefetch.tensormap [%0];" ::"l"(&p.mapXT) : "memory");
            asm volatile("prefetch.tensormap [%0];" ::"l"(&p.mapXT3) : "memory");
            mbar_wait(bar + 8 * B_EP, 0);
            epoch = lds32(sb + SM_EP);
          } else {
            mbar_wait(bar + 8 * B_PDONE, 0);
            ld_w(0, 0); ld_w(1, 1);
            mbar_wait(bar + 8 * (W2_LATE ? B_U : B_RE), 0);
            ld_w(2, 2);
          }
          {
            int slot = 0;
#pragma unroll 1
            for (int c = 3; c < 8; c++) {
              mbar_wait(bar + 8 * (B_KVE + c - 3), layer);
              ld_w(c, slot);
              slot = slot == 2 ? 0 : slot + 1;
            }
          }
          if (STOP <= 1 + 3 * layer) return;
          mbar_wait(bar + 8 * B_QDONE, layer);
          mbar_wait(bar + 8 * B_HF, layer);
          mbar_expect(bar + 8 * B_WOF, 65536);
#pragma unroll
          for (int c = 0; c < 4; c++) tma_ld(sb + SM_WO + c * 16384, &p.mapWo128, q2 * 64, c * 128, bar + 8 * B_WOF);
          {
            const uint32_t b = bar + 8 * B_RF;
            mbar_expect(b, 16384);
            if (layer == 0) tma_ld(sb + SM_R, &p.mapX128, (rb2 >> 3) * DM + q2 * 64, (rb2 & 7) * 128, b);
            else tma_ld3(sb + SM_R, &p.mapXT3, 0, DM + q2 * 64, rb2 * 2, b);
          }
#pragma unroll
          for (int c = 0; c < 8; c++) mbar_expect(bar + 8 * (B_OF + c), 16384);
          spin_until(&g_cnt[(C_O + rb2) * 32], (2 * epoch + layer + 1) * 16);
          fence_async_global();
#pragma unroll
          for (int c = 0; c < 8; c++) {
            if (c == 4) { mbar_wait(bar + 8 * B_OST, layer); fence_async_smem(); }
            tma_ld(sb + sm_o(c), &p.mapO128, c * 64, rb2 * 128, bar + 8 * (B_OF + c));
          }
          if (STOP <= 3 + 3 * layer) return;
        }
      }
    } else if (warp == 13) {
      if (elect_one() && STOP > 1) {
        const unsigned target = (lds32(sb + SM_EP) + 1) * NCTA;
        mbar_wait(bar + 8 * B_RE, 0);
        spin_until(&g_cnt[C_CS * 32 + 2], 2 * target);
        mbar_arrive(bar + 8 * B_XV);
        if (STOP <= 3) return;
        auto ld_x = [&](int c) { tma_ld3(sb + SM_X + c * 16384, &p.mapXT3, 0, DM + c * 64, rb * 2, bar + 8 * (B_XF + c)); };
#pragma unroll
        for (int c = 0; c < 8; c++) mbar_expect(bar + 8 * (B_XF + c), 16384);
        spin_until(&g_cnt[C_G1 * 32], target);
        fence_async_global();
        fence_async_smem();
        ld_x(0); ld_x(1);
        int done = 1, it = 0;
        while (done < 4) {
          const uint4 v = ld_tagged((const uint4*)&g_cnt[C_G1 * 32]);
          const int n = 4 + ((int)(v.y - target) >> 31) + ((int)(v.z - target) >> 31) + ((int)(v.w - target) >> 31);
          if (n == done) { if (++it > (1 << 23)) __trap(); continue; }
          if (n == 4) TS(44);
          fence_async_global();
          fence_async_smem();
          if (done == 1) { ld_x(2); ld_x(3); }
          const int h = hg >> 2;
          if (done < 3 && n >= 3) ld_x(4 + h);
          if (n == 4) ld_x(6 + h);
          if (done < 3 && n >= 3) ld_x(5 - h);
          if (n == 4) ld_x(7 - h);
          done = n;
        }
        if (STOP <= 4) return;
        mbar_wait(bar + 8 * B_RE, 1);
        spin_until(&g_cnt[C_CS * 32 + 3], 2 * target);
        mbar_arrive(bar + 8 * B_XV);
      }
    } else if (warp == 15) {
      mbar_wait(bar + 8 * B_EP, 0);
      const unsigned epoch = lds32(sb + SM_EP);
#pragma unroll 1
      for (int layer = 0; layer < 2; layer++) {
        mbar_wait(bar + 8 * (B_KVF + FILL_AT), layer);
#pragma unroll
        for (int k = 0; k < 8; k++) ((uint4*)(g_xT + (size_t)(2 * layer * DM + cta) * LSEQ))[32 * k + lane] = make_uint4(~0u, ~0u, ~0u, ~0u);
        mbar_wait(bar + 8 * (B_KVF + FILL_AT + 1), layer);
#pragma unroll
        for (int k = 0; k < 16; k++)
          ((uint4*)(g_xT + (size_t)(3 * DM + cv_chan(cta, 3 - (k >> 2))) * LSEQ))[128 * layer + 32 * (k & 3) + lane] = make_uint4(~0u, ~0u, ~0u, ~0u);
        if (lane < 4) ((uint4*)g_stats)[layer * 512 + cta * 4 + lane] = make_uint4(0, 0, 0, 0);
        __syncwarp();
        if (elect_one()) {
          red_release(&g_cnt[C_CS * 32 + layer]);
          spin_until(&g_cnt[C_CS * 32 + layer], (epoch + 1) * NCTA);
          mbar_arrive(bar + 8 * B_ZF);
          if (layer == 0 && STOP > 2) {
#pragma unroll
            for (int lc = 0; lc < 4; lc++) {
              mbar_wait(bar + 8 * (B_E + lc), 0);
              fence_reader();
              bulk_st(g_xT + (size_t)(DM + cv_chan(cta, lc)) * LSEQ, sb + cv_s(lc), 4096);
              bulk_commit();
              bulk_wait_all();
              red_relaxed(&g_cnt[C_G1 * 32 + lc]);
              if (lc == 3) TS(18);
            }
          }
        }
        __syncwarp();
        if (STOP <= 3) return;
      }
    } else if (warp == 14) {
      mbar_wait(bar + 8 * B_EP, 0);
      const unsigned epoch = lds32(sb + SM_EP);
#pragma unroll 1
      for (int layer = 0; layer < 2; layer++) {
        if (STOP <= 3 * layer) return;
        if (HALO_W14) halo_receive1(sb, layer, rb, hg, opaque_tid() & 31, 2 * epoch + layer + 1);
        if (STOP <= 1 + 3 * layer) return;
        mbar_wait(bar + 8 * B_ZF, layer);
        proj_stats(sb, layer, rb2, q2, opaque_tid() & 31, part_tag(epoch, 2 * layer + 1));
        if (layer == 1 && lane == 0) TS(5);
        delay<D_PREP>();
        if (lane == 0) mbar_arrive(bar + 8 * B_GB);
      }
    }
  }
}

typedef CUresult (*EncodeFn)(CUtensorMap*, CUtensorMapDataType, cuuint32_t, void*, const cuuint64_t*, const cuuint64_t*,
                             const cuuint32_t*, const cuuint32_t*, CUtensorMapInterleave, CUtensorMapSwizzle,
                             CUtensorMapL2promotion, CUtensorMapFloatOOBfill);

static void make_map(EncodeFn enc, CUtensorMap* m, void* ptr, uint64_t cols, uint64_t rows, uint32_t box_rows) {
  cuuint64_t dims[2] = {cols, rows};
  cuuint64_t strides[1] = {cols * 2};
  cuuint32_t box[2] = {64, box_rows};
  cuuint32_t es[2] = {1, 1};
  enc(m, CU_TENSOR_MAP_DATA_TYPE_BFLOAT16, 2, ptr, dims, strides, box, es, CU_TENSOR_MAP_INTERLEAVE_NONE,
      CU_TENSOR_MAP_SWIZZLE_128B, CU_TENSOR_MAP_L2_PROMOTION_L2_128B, CU_TENSOR_MAP_FLOAT_OOB_FILL_NONE);
}
static void make_map3(EncodeFn enc, CUtensorMap* m, void* ptr, uint64_t d0, uint64_t cols, uint64_t rows, uint64_t blk_stride,
                      uint64_t nblocks, uint32_t nblk, uint32_t box_rows = 64) {
  cuuint64_t dims[3] = {d0, rows, nblocks};
  cuuint64_t strides[2] = {cols * 2, blk_stride * 2};
  cuuint32_t box[3] = {64, box_rows, nblk};
  cuuint32_t es[3] = {1, 1, 1};
  enc(m, CU_TENSOR_MAP_DATA_TYPE_BFLOAT16, 3, ptr, dims, strides, box, es, CU_TENSOR_MAP_INTERLEAVE_NONE,
      CU_TENSOR_MAP_SWIZZLE_128B, CU_TENSOR_MAP_L2_PROMOTION_L2_128B, CU_TENSOR_MAP_FLOAT_OOB_FILL_NONE);
}

extern "C" void kernel_launch(void* const* d_in, const int* in_sizes, int n_in, void* d_out, int out_size) {
  static Params prm;
  static void* cached[13] = {nullptr};
  static bool attr_done = false;
  bool same = attr_done && cached[12] == d_out;
  for (int i = 0; i < 12 && same; i++) same = cached[i] == d_in[i];
  if (!same) {
    void* fn = nullptr;
    cudaDriverEntryPointQueryResult qr;
    cudaGetDriverEntryPoint("cuTensorMapEncodeTiled", &fn, cudaEnableDefault, &qr);
    EncodeFn enc = (EncodeFn)fn;
    void *pO, *pXT;
    cudaGetSymbolAddress(&pO, g_O);
    cudaGetSymbolAddress(&pXT, g_xT);
    make_map(enc, &prm.mapO, pO, DM, LSEQ, 64);
    make_map(enc, &prm.mapXT, pXT, LSEQ, 4 * DM, 64);
    prm.out = (bf16*)d_out;
    make_map(enc, &prm.mapX128, d_in[0], 2 * DM, LSEQ / 2, 128);
    make_map(enc, &prm.mapWo128, d_in[2], DM, DM, 128);
    make_map(enc, &prm.mapO128, pO, DM, LSEQ, 128);
    make_map3(enc, &prm.mapW3, d_in[1], DM, 3 * DM, DM, DM, 3, 3);
    make_map3(enc, &prm.mapW3h, d_in[1], DM, 3 * DM, DM, DM, 3, 3, 32);
    make_map3(enc, &prm.mapXT3, pXT, 64, LSEQ, 4 * DM, 64, 32, 2);
    prm.a_re = (const bf16*)d_in[4]; prm.a_im = (const bf16*)d_in[5];
    prm.b_re = (const bf16*)d_in[6]; prm.b_im = (const bf16*)d_in[7];
    prm.c_re = (const bf16*)d_in[8]; prm.c_im = (const bf16*)d_in[9];
    prm.log_dt = (const bf16*)d_in[10]; prm.dskip = (const bf16*)d_in[11];
    cudaFuncSetAttribute(fused_kernel, cudaFuncAttributeMaxDynamicSharedMemorySize, SM_TOTAL);
    for (int i = 0; i < 12; i++) cached[i] = d_in[i];
    cached[12] = d_out;
    attr_done = true;
  }
  prm.stop = 100;
    fused_kernel<<<NCTA, NTHREADS, SM_TOTAL>>>(prm);
}
```

```cpp
#include <cuda_runtime.h>
#include <cuda_bf16.h>
#include <cuda.h>
#include <stdint.h>

typedef __nv_bfloat16 bf16;

constexpr int LSEQ = 2048;
constexpr int DM = 512;
constexpr int NCTA = 128;
constexpr int NTHREADS = 512;
#define RR 0
#define KG_PRE 2
#define W2_LATE 1
#define FILL_AT 6
#define EXP_LATE 1
#define RFENCE 1
#define D_FIN 500
#define D_PREP 500
#define D_PST 0
#define D_HALO 500
#define STAG 2
#define D_ST 500
#define TLAYER 1
#define KG_PD 1
#define SUM_F32 0
#define CS_LATE0 1
#define D_HALO1 0
#define KG_START 0
#define S_AHEAD0 1
#define S_AHEAD1 2
#define PAUSE 2
#define PARK_FIRST 0
#define P_UNROLL_N 1
constexpr int P_UNROLL = P_UNROLL_N;
#define NORM_FMA 0
#define X_ORDER 1
#define CS_STEP 1
#define G_WAIT 2
#define HALO_W14 1
#define D_START 200
#define D_CS 300
#define D_ST0 400
#define KG_LAST 0
#define X_JIT 0
#define KG_GATE 2
#define R_CONS 192
#define R_HELP 88

constexpr int SM_X = 0;
constexpr int SM_W = 131072;
constexpr int SM_KVX = SM_X;
constexpr int SM_OST = SM_X + 32768;
constexpr int SM_WO = SM_X + 65536;
__host__ __device__ constexpr int sm_o(int c) { return c < 4 ? SM_W + c * 16384 : SM_X + (c - 4) * 16384; }
constexpr int SM_R = 196608;
constexpr int SM_T = 212992;
constexpr int SM_KC = 217088;
constexpr int KC_STRIDE = 648;
constexpr int SM_CS = SM_KC + 4 * KC_STRIDE * 2;
constexpr int SM_CW = SM_R + 8192;
constexpr int SM_EP = SM_CS + 768;
constexpr int SM_BAR = SM_EP + 16;
constexpr int SM_T2 = SM_BAR + 896;
constexpr int SM_HALO = SM_T2 + 4096;
constexpr int SM_ST = SM_HALO + 3072;
constexpr int SM_TOTAL = SM_HALO + 4096;
static_assert(SM_TOTAL <= 232448, "shared memory");

constexpr int CV_UH = 140 * 16;
constexpr int CV_PECH = 1120 * 4;
constexpr int CV_PBW = 2112 * 2;
__host__ __device__ constexpr int cv_s(int lc) { return SM_X + lc * 32768; }
__host__ __device__ constexpr int cv_u(int lc) { return cv_s(lc) + 4096; }
__host__ __device__ constexpr int cv_pe(int lc) { return cv_u(lc) + 2 * CV_UH; }
__host__ __device__ constexpr int cv_pb(int lc) { return cv_pe(lc) + CV_PECH; }
__host__ __device__ constexpr int cv_ft(int lc) { return cv_pb(lc) + 4 * CV_PBW; }
static_assert(cv_ft(0) + 1024 <= 32768, "conv buffers");
__host__ __device__ constexpr int cv_chan(int cta, int lc) { return cta + 128 * lc; }

enum {
  B_XF = 0,
  B_KVF = 8,
  B_OF = 16,
  B_WOF = 24,
  B_T = 31,
  B_RF = 28,
  B_RE = 29,
  B_CW = 30,
  B_GB = 35,
  B_EP = 36,
  B_ZF = 37,
  B_XV = 39,
  B_SD = 38,
  B_KVE = 40,
  B_AD = 45,
  B_OST = 46,
  B_QDONE = 47,
  B_PDONE = 48,
  B_S = 50,
  B_E = 54,
  B_P = 58,
  B_PE = 62,
  B_STF = 63,
  B_CSF = 64,
  B_HF = 65,
  B_U = 70,
  B_PS = 74,
  B_COUNT = 80
};

enum {
  C_CS = 0,
  C_G1 = 2,
  C_O = 4,
  C_COUNT = 20
};

__device__ __align__(128) unsigned g_cnt[C_COUNT * 32];
__device__ __align__(1024) bf16 g_O[LSEQ * DM];
__device__ __align__(1024) bf16 g_xT[4 * DM * LSEQ];
__device__ __align__(1024) uint32_t g_stats[2 * LSEQ];
__device__ __align__(1024) uint4 g_colsum[8 * 16 * 48];
__device__ __align__(1024) uint4 g_halo[16 * 8 * 192];
__device__ __align__(1024) uint2 g_part[16 * 8 * 128];
#define TS(i) do { } while (0)

#define ATS(i, th) do { } while (0)
#define KTS(i) do { if (ht == 0) TS(i); } while (0)
#define FTS(i) do { } while (0)
#define LTS(i) do { } while (0)

#define STOP 100

struct Params {
  CUtensorMap mapO, mapXT, mapX128, mapWo128, mapO128, mapW3, mapW3h, mapXT3;
  const bf16 *a_re, *a_im, *b_re, *b_im, *c_re, *c_im, *log_dt, *dskip;
  bf16* out;
  int stop;
};

__device__ __forceinline__ uint32_t s32(const void* p) { return (uint32_t)__cvta_generic_to_shared(p); }
__device__ __forceinline__ void mbar_init(uint32_t b, int c) { asm volatile("mbarrier.init.shared::cta.b64 [%0], %1;" ::"r"(b), "r"(c) : "memory"); }
__device__ __forceinline__ void mbar_expect(uint32_t b, int bytes) { asm volatile("mbarrier.arrive.expect_tx.shared::cta.b64 _, [%0], %1;" ::"r"(b), "r"(bytes) : "memory"); }
__device__ __forceinline__ void mbar_arrive(uint32_t b) { asm volatile("mbarrier.arrive.shared::cta.b64 _, [%0];" ::"r"(b) : "memory"); }
__device__ __forceinline__ void mbar_arrive_if(uint32_t b, bool c) {
  asm volatile("{\n.reg .pred p;\nsetp.ne.u32 p, %1, 0;\n@p mbarrier.arrive.shared::cta.b64 _, [%0];\n}" ::"r"(b), "r"((uint32_t)c) : "memory");
}
__device__ __forceinline__ void mbar_wait(uint32_t b, int parity) {
  asm volatile("{\n.reg .pred p;\nWAIT_LOOP:\nmbarrier.try_wait.parity.shared::cta.b64 p, [%0], %1;\n@p bra WAIT_DONE;\nbra WAIT_LOOP;\nWAIT_DONE:\n}" ::"r"(b), "r"(parity) : "memory");
}
template <int N> __device__ __forceinline__ void delay() {
  if constexpr (N > 0) {
    uint32_t t0, t;
    asm volatile("mov.u32 %0, %%clock;" : "=r"(t0));
    do { asm volatile("mov.u32 %0, %%clock;" : "=r"(t)); } while (t - t0 < N);
  }
}
#define SF 3
template <int ID> __device__ __forceinline__ void sched_fence() {
  if constexpr ((SF >> ID) & 1)
    asm volatile("{\n.reg .pred p;\n.reg .u32 t;\nsetp.eq.u32 p, %0, 0;\n@p mov.u32 t, %%clock;\n@p st.shared.u32 [%0], t;\n}" ::"r"(gridDim.x) : "memory");
}
__device__ __forceinline__ int opaque_tid() { int v; asm volatile("mov.u32 %0, %%tid.x;" : "=r"(v)); return v; }
__device__ __forceinline__ bool elect_one() {
  uint32_t r;
  asm volatile("{\n.reg .pred p;\nelect.sync _|p, 0xffffffff;\nselp.u32 %0, 1, 0, p;\n}" : "=r"(r));
  return r != 0;
}
__device__ __forceinline__ void tma_ld(uint32_t dst, const CUtensorMap* m, int c0, int c1, uint32_t bar) {
  asm volatile("cp.async.bulk.tensor.2d.shared::cluster.global.mbarrier::complete_tx::bytes [%0], [%1, {%3, %4}], [%2];"
               ::"r"(dst), "l"(m), "r"(bar), "r"(c0), "r"(c1) : "memory");
}
__device__ __forceinline__ void tma_ld3(uint32_t dst, const CUtensorMap* m, int c0, int c1, int c2, uint32_t bar) {
  asm volatile("cp.async.bulk.tensor.3d.shared::cluster.global.mbarrier::complete_tx::bytes [%0], [%1, {%3, %4, %5}], [%2];"
               ::"r"(dst), "l"(m), "r"(bar), "r"(c0), "r"(c1), "r"(c2) : "memory");
}
__device__ __forceinline__ void tma_prefetch2(const CUtensorMap* m, int c0, int c1) {
  asm volatile("cp.async.bulk.prefetch.tensor.2d.L2.global.tile [%0, {%1, %2}];" ::"l"(m), "r"(c0), "r"(c1) : "memory");
}
__device__ __forceinline__ void tma_prefetch3(const CUtensorMap* m, int c0, int c1, int c2) {
  asm volatile("cp.async.bulk.prefetch.tensor.3d.L2.global.tile [%0, {%1, %2, %3}];" ::"l"(m), "r"(c0), "r"(c1), "r"(c2) : "memory");
}
__device__ __forceinline__ void tma_st(const CUtensorMap* m, int c0, int c1, uint32_t src) {
  asm volatile("cp.async.bulk.tensor.2d.global.shared::cta.bulk_group [%0, {%2, %3}], [%1];" ::"l"(m), "r"(src), "r"(c0), "r"(c1) : "memory");
}
__device__ __forceinline__ void bulk_ld(uint32_t dst, const void* src, int bytes, uint32_t bar) {
  asm volatile("cp.async.bulk.shared::cluster.global.mbarrier::complete_tx::bytes [%0], [%1], %2, [%3];" ::"r"(dst), "l"(src), "r"(bytes), "r"(bar) : "memory");
}
__device__ __forceinline__ void bulk_st(void* dst, uint32_t src, int bytes) {
  asm volatile("cp.async.bulk.global.shared::cta.bulk_group [%0], [%1], %2;" ::"l"(dst), "r"(src), "r"(bytes) : "memory");
}
__device__ __forceinline__ void bulk_red_add_f32(void* dst, uint32_t src, int bytes) {
  asm volatile("cp.reduce.async.bulk.global.shared::cta.bulk_group.add.f32 [%0], [%1], %2;" ::"l"(dst), "r"(src), "r"(bytes) : "memory");
}
__device__ __forceinline__ void bulk_commit() { asm volatile("cp.async.bulk.commit_group;" ::: "memory"); }
__device__ __forceinline__ void bulk_wait_all() { asm volatile("cp.async.bulk.wait_group 0;" ::: "memory"); }
__device__ __forceinline__ void fence_async_smem() { asm volatile("fence.proxy.async.shared::cta;" ::: "memory"); }
__device__ __forceinline__ void fence_writer() { if (!RFENCE) fence_async_smem(); }
__device__ __forceinline__ void fence_reader() { if (RFENCE) fence_async_smem(); }
__device__ __forceinline__ void fence_async_global() { asm volatile("fence.proxy.async.global;" ::: "memory"); }
__device__ __forceinline__ void bar_sync(int id, int n) { asm volatile("bar.sync %0, %1;" ::"r"(id), "r"(n) : "memory"); }
__device__ __forceinline__ void bar_arrive(int id, int n) { asm volatile("bar.arrive %0, %1;" ::"r"(id), "r"(n) : "memory"); }
__device__ __forceinline__ void wg_fence() { asm volatile("wgmma.fence.sync.aligned;" ::: "memory"); }
__device__ __forceinline__ void wg_commit() { asm volatile("wgmma.commit_group.sync.aligned;" ::: "memory"); }
template <int N> __device__ __forceinline__ void wg_wait() { asm volatile("wgmma.wait_group.sync.aligned %0;" ::"n"(N) : "memory"); }
__device__ __forceinline__ uint64_t mkdesc(uint32_t addr, uint32_t lbo, uint32_t sbo, int sw) {
  return (uint64_t)((addr & 0x3FFFF) >> 4) | ((uint64_t)(lbo >> 4) << 16) | ((uint64_t)(sbo >> 4) << 32) | ((uint64_t)sw << 62);
}
__device__ __forceinline__ void ldsm4(uint32_t* r, uint32_t a) {
  asm volatile("ldmatrix.sync.aligned.m8n8.x4.shared.b16 {%0,%1,%2,%3}, [%4];" : "=r"(r[0]), "=r"(r[1]), "=r"(r[2]), "=r"(r[3]) : "r"(a) : "memory");
}
__device__ __forceinline__ void ldsm4t(uint32_t* r, uint32_t a) {
  asm volatile("ldmatrix.sync.aligned.m8n8.x4.trans.shared.b16 {%0,%1,%2,%3}, [%4];" : "=r"(r[0]), "=r"(r[1]), "=r"(r[2]), "=r"(r[3]) : "r"(a) : "memory");
}
__device__ __forceinline__ void stsm4(uint32_t a, uint32_t r0, uint32_t r1, uint32_t r2, uint32_t r3) {
  asm volatile("stmatrix.sync.aligned.m8n8.x4.shared.b16 [%0], {%1,%2,%3,%4};" ::"r"(a), "r"(r0), "r"(r1), "r"(r2), "r"(r3) : "memory");
}
__device__ __forceinline__ void stsm4t(uint32_t a, uint32_t r0, uint32_t r1, uint32_t r2, uint32_t r3) {
  asm volatile("stmatrix.sync.aligned.m8n8.x4.trans.shared.b16 [%0], {%1,%2,%3,%4};" ::"r"(a), "r"(r0), "r"(r1), "r"(r2), "r"(r3) : "memory");
}
__device__ __forceinline__ uint32_t movm_t(uint32_t a) { uint32_t r; asm volatile("movmatrix.sync.aligned.m8n8.trans.b16 %0, %1;" : "=r"(r) : "r"(a)); return r; }
__device__ __forceinline__ uint32_t lds32(uint32_t a) { uint32_t v; asm volatile("ld.shared.b32 %0, [%1];" : "=r"(v) : "r"(a) : "memory"); return v; }
__device__ __forceinline__ float2 lds64f(uint32_t a) { float2 v; asm volatile("ld.shared.v2.f32 {%0,%1}, [%2];" : "=f"(v.x), "=f"(v.y) : "r"(a) : "memory"); return v; }
__device__ __forceinline__ float4 lds128f(uint32_t a) { float4 v; asm volatile("ld.shared.v4.f32 {%0,%1,%2,%3}, [%4];" : "=f"(v.x), "=f"(v.y), "=f"(v.z), "=f"(v.w) : "r"(a) : "memory"); return v; }
__device__ __forceinline__ uint4 lds128(uint32_t a) { uint4 v; asm volatile("ld.shared.v4.b32 {%0,%1,%2,%3}, [%4];" : "=r"(v.x), "=r"(v.y), "=r"(v.z), "=r"(v.w) : "r"(a) : "memory"); return v; }
__device__ __forceinline__ void sts128(uint32_t a, uint4 v) { asm volatile("st.shared.v4.b32 [%0], {%1,%2,%3,%4};" ::"r"(a), "r"(v.x), "r"(v.y), "r"(v.z), "r"(v.w) : "memory"); }
__device__ __forceinline__ void sts128f(uint32_t a, float x, float y, float z, float w) { asm volatile("st.shared.v4.f32 [%0], {%1,%2,%3,%4};" ::"r"(a), "f"(x), "f"(y), "f"(z), "f"(w) : "memory"); }
__device__ __forceinline__ void sts32f(uint32_t a, float v) { asm volatile("st.shared.f32 [%0], %1;" ::"r"(a), "f"(v) : "memory"); }
__device__ __forceinline__ void sts16(uint32_t a, uint16_t v) { asm volatile("st.shared.u16 [%0], %1;" ::"r"(a), "h"(v) : "memory"); }
__device__ __forceinline__ uint32_t lds16(uint32_t a) { uint16_t v; asm volatile("ld.shared.u16 %0, [%1];" : "=h"(v) : "r"(a) : "memory"); return v; }
__device__ __forceinline__ uint32_t packbf(float lo, float hi) { uint32_t r; asm("cvt.rn.bf16x2.f32 %0, %1, %2;" : "=r"(r) : "f"(hi), "f"(lo)); return r; }
__device__ __forceinline__ float bf_lo(uint32_t v) { return __uint_as_float(v << 16); }
__device__ __forceinline__ float bf_hi(uint32_t v) { return __uint_as_float(v & 0xffff0000u); }
__device__ __forceinline__ float ex2(float x) { float r; asm("ex2.approx.ftz.f32 %0, %1;" : "=f"(r) : "f"(x)); return r; }
__device__ __forceinline__ float rsqrt_approx(float x) { float r; asm("rsqrt.approx.ftz.f32 %0, %1;" : "=f"(r) : "f"(x)); return r; }
__device__ __forceinline__ float rcp_approx(float x) { float r; asm("rcp.approx.ftz.f32 %0, %1;" : "=f"(r) : "f"(x)); return r; }
__device__ __forceinline__ void mma_bf16(float* d, const uint32_t* a, uint32_t b0, uint32_t b1) {
  asm("mma.sync.aligned.m16n8k16.row.col.f32.bf16.bf16.f32 {%0,%1,%2,%3}, {%4,%5,%6,%7}, {%8,%9}, {%0,%1,%2,%3};"
               : "+f"(d[0]), "+f"(d[1]), "+f"(d[2]), "+f"(d[3]) : "r"(a[0]), "r"(a[1]), "r"(a[2]), "r"(a[3]), "r"(b0), "r"(b1));
}
__device__ __forceinline__ void mma_bf16_k8(float* d, uint32_t a0, uint32_t a1, uint32_t b) {
  asm("mma.sync.aligned.m16n8k8.row.col.f32.bf16.bf16.f32 {%0,%1,%2,%3}, {%4,%5}, {%6}, {%0,%1,%2,%3};"
      : "+f"(d[0]), "+f"(d[1]), "+f"(d[2]), "+f"(d[3]) : "r"(a0), "r"(a1), "r"(b));
}
__device__ __forceinline__ void red_release(unsigned* p) { asm volatile("red.release.gpu.global.add.u32 [%0], 1;" ::"l"(p) : "memory"); }
__device__ __forceinline__ void red_relaxed(unsigned* p) { asm volatile("red.relaxed.gpu.global.add.u32 [%0], 1;" ::"l"(p) : "memory"); }
__device__ __forceinline__ unsigned ld_relaxed(const unsigned* p) { unsigned v; asm volatile("ld.relaxed.gpu.global.u32 %0, [%1];" : "=r"(v) : "l"(p) : "memory"); return v; }
__device__ __forceinline__ void spin_until(const unsigned* p, unsigned target) {
  int it = 0;
  while ((int)(ld_relaxed(p) - target) < 0) {
    if (++it > (1 << 23)) __trap();
  }
}
__device__ __forceinline__ uint4 ldcg128(const void* p) { uint4 v; asm volatile("ld.global.cg.v4.b32 {%0,%1,%2,%3}, [%4];" : "=r"(v.x), "=r"(v.y), "=r"(v.z), "=r"(v.w) : "l"(p) : "memory"); return v; }
__device__ __forceinline__ uint4 ld_tagged(const uint4* p) { uint4 v; asm volatile("ld.relaxed.gpu.global.v4.u32 {%0,%1,%2,%3}, [%4];" : "=r"(v.x), "=r"(v.y), "=r"(v.z), "=r"(v.w) : "l"(p) : "memory"); return v; }
__device__ __forceinline__ uint2 ld_part(const uint2* p) { uint2 v; asm volatile("ld.relaxed.gpu.global.v2.u32 {%0,%1}, [%2];" : "=r"(v.x), "=r"(v.y) : "l"(p) : "memory"); return v; }
__device__ __forceinline__ void st_part(uint2* p, float s, float q, uint32_t tag) {
  asm volatile("st.relaxed.gpu.global.v2.u32 [%0], {%1,%2};" ::"l"(p), "r"(__float_as_uint(s)), "r"((__float_as_uint(q) & ~7u) | tag) : "memory");
}
__device__ __forceinline__ uint32_t part_tag(uint32_t epoch, int k) { return (4 * (epoch % 7) + k) % 7 + 1; }
__device__ __forceinline__ void st_tagged3(uint4* p, uint32_t a, uint32_t b, uint32_t c, uint32_t tag) { asm volatile("st.relaxed.gpu.global.v4.u32 [%0], {%1,%2,%3,%4};" ::"l"(p), "r"(a), "r"(b), "r"(c), "r"(tag) : "memory"); }
__device__ __forceinline__ uint32_t hadd2(uint32_t a, uint32_t b) { uint32_t r; asm("add.rn.bf16x2 %0, %1, %2;" : "=r"(r) : "r"(a), "r"(b)); return r; }
__device__ __forceinline__ uint32_t hfma2(uint32_t a, uint32_t b, uint32_t c) { uint32_t r; asm("fma.rn.bf16x2 %0, %1, %2, %3;" : "=r"(r) : "r"(a), "r"(b), "r"(c)); return r; }
__device__ __forceinline__ uint32_t hmul2(uint32_t a, uint32_t b) { uint32_t r; asm("mul.rn.bf16x2 %0, %1, %2;" : "=r"(r) : "r"(a), "r"(b)); return r; }

template<int N,int TB> __device__ __forceinline__ void wgmma_rs(float* d, const uint32_t* a, uint64_t db, int sd);
template<int N,int TA,int TB> __device__ __forceinline__ void wgmma_ss(float* d, uint64_t da, uint64_t db, int sd);
template<> __device__ __forceinline__ void wgmma_rs<128,0>(float* d, const uint32_t* a, uint64_t db, int sd) {
  asm volatile("{\n.reg .pred p;\nsetp.ne.b32 p, %69, 0;\nwgmma.mma_async.sync.aligned.m64n128k16.f32.bf16.bf16 {%0,%1,%2,%3,%4,%5,%6,%7,%8,%9,%10,%11,%12,%13,%14,%15,%16,%17,%18,%19,%20,%21,%22,%23,%24,%25,%26,%27,%28,%29,%30,%31,%32,%33,%34,%35,%36,%37,%38,%39,%40,%41,%42,%43,%44,%45,%46,%47,%48,%49,%50,%51,%52,%53,%54,%55,%56,%57,%58,%59,%60,%61,%62,%63}, {%64,%65,%66,%67}, %68, p, 1, 1, 0;\n}\n"
   : "+f"(d[0]),"+f"(d[1]),"+f"(d[2]),"+f"(d[3]),"+f"(d[4]),"+f"(d[5]),"+f"(d[6]),"+f"(d[7]),"+f"(d[8]),"+f"(d[9]),"+f"(d[10]),"+f"(d[11]),"+f"(d[12]),"+f"(d[13]),"+f"(d[14]),"+f"(d[15]),"+f"(d[16]),"+f"(d[17]),"+f"(d[18]),"+f"(d[19]),"+f"(d[20]),"+f"(d[21]),"+f"(d[22]),"+f"(d[23]),"+f"(d[24]),"+f"(d[25]),"+f"(d[26]),"+f"(d[27]),"+f"(d[28]),"+f"(d[29]),"+f"(d[30]),"+f"(d[31]),"+f"(d[32]),"+f"(d[33]),"+f"(d[34]),"+f"(d[35]),"+f"(d[36]),"+f"(d[37]),"+f"(d[38]),"+f"(d[39]),"+f"(d[40]),"+f"(d[41]),"+f"(d[42]),"+f"(d[43]),"+f"(d[44]),"+f"(d[45]),"+f"(d[46]),"+f"(d[47]),"+f"(d[48]),"+f"(d[49]),"+f"(d[50]),"+f"(d[51]),"+f"(d[52]),"+f"(d[53]),"+f"(d[54]),"+f"(d[55]),"+f"(d[56]),"+f"(d[57]),"+f"(d[58]),"+f"(d[59]),"+f"(d[60]),"+f"(d[61]),"+f"(d[62]),"+f"(d[63])
   : "r"(a[0]), "r"(a[1]), "r"(a[2]), "r"(a[3]), "l"(db), "r"(sd));
}
template<> __device__ __forceinline__ void wgmma_rs<120,0>(float* d, const uint32_t* a, uint64_t db, int sd) {
  asm volatile("{\n.reg .pred p;\nsetp.ne.b32 p, %65, 0;\nwgmma.mma_async.sync.aligned.m64n120k16.f32.bf16.bf16 {%0,%1,%2,%3,%4,%5,%6,%7,%8,%9,%10,%11,%12,%13,%14,%15,%16,%17,%18,%19,%20,%21,%22,%23,%24,%25,%26,%27,%28,%29,%30,%31,%32,%33,%34,%35,%36,%37,%38,%39,%40,%41,%42,%43,%44,%45,%46,%47,%48,%49,%50,%51,%52,%53,%54,%55,%56,%57,%58,%59}, {%60,%61,%62,%63}, %64, p, 1, 1, 0;\n}\n"
   : "+f"(d[0]),"+f"(d[1]),"+f"(d[2]),"+f"(d[3]),"+f"(d[4]),"+f"(d[5]),"+f"(d[6]),"+f"(d[7]),"+f"(d[8]),"+f"(d[9]),"+f"(d[10]),"+f"(d[11]),"+f"(d[12]),"+f"(d[13]),"+f"(d[14]),"+f"(d[15]),"+f"(d[16]),"+f"(d[17]),"+f"(d[18]),"+f"(d[19]),"+f"(d[20]),"+f"(d[21]),"+f"(d[22]),"+f"(d[23]),"+f"(d[24]),"+f"(d[25]),"+f"(d[26]),"+f"(d[27]),"+f"(d[28]),"+f"(d[29]),"+f"(d[30]),"+f"(d[31]),"+f"(d[32]),"+f"(d[33]),"+f"(d[34]),"+f"(d[35]),"+f"(d[36]),"+f"(d[37]),"+f"(d[38]),"+f"(d[39]),"+f"(d[40]),"+f"(d[41]),"+f"(d[42]),"+f"(d[43]),"+f"(d[44]),"+f"(d[45]),"+f"(d[46]),"+f"(d[47]),"+f"(d[48]),"+f"(d[49]),"+f"(d[50]),"+f"(d[51]),"+f"(d[52]),"+f"(d[53]),"+f"(d[54]),"+f"(d[55]),"+f"(d[56]),"+f"(d[57]),"+f"(d[58]),"+f"(d[59])
   : "r"(a[0]), "r"(a[1]), "r"(a[2]), "r"(a[3]), "l"(db), "r"(sd));
}
template<> __device__ __forceinline__ void wgmma_rs<112,0>(float* d, const uint32_t* a, uint64_t db, int sd) {
  asm volatile("{\n.reg .pred p;\nsetp.ne.b32 p, %61, 0;\nwgmma.mma_async.sync.aligned.m64n112k16.f32.bf16.bf16 {%0,%1,%2,%3,%4,%5,%6,%7,%8,%9,%10,%11,%12,%13,%14,%15,%16,%17,%18,%19,%20,%21,%22,%23,%24,%25,%26,%27,%28,%29,%30,%31,%32,%33,%34,%35,%36,%37,%38,%39,%40,%41,%42,%43,%44,%45,%46,%47,%48,%49,%50,%51,%52,%53,%54,%55}, {%56,%57,%58,%59}, %60, p, 1, 1, 0;\n}\n"
   : "+f"(d[0]),"+f"(d[1]),"+f"(d[2]),"+f"(d[3]),"+f"(d[4]),"+f"(d[5]),"+f"(d[6]),"+f"(d[7]),"+f"(d[8]),"+f"(d[9]),"+f"(d[10]),"+f"(d[11]),"+f"(d[12]),"+f"(d[13]),"+f"(d[14]),"+f"(d[15]),"+f"(d[16]),"+f"(d[17]),"+f"(d[18]),"+f"(d[19]),"+f"(d[20]),"+f"(d[21]),"+f"(d[22]),"+f"(d[23]),"+f"(d[24]),"+f"(d[25]),"+f"(d[26]),"+f"(d[27]),"+f"(d[28]),"+f"(d[29]),"+f"(d[30]),"+f"(d[31]),"+f"(d[32]),"+f"(d[33]),"+f"(d[34]),"+f"(d[35]),"+f"(d[36]),"+f"(d[37]),"+f"(d[38]),"+f"(d[39]),"+f"(d[40]),"+f"(d[41]),"+f"(d[42]),"+f"(d[43]),"+f"(d[44]),"+f"(d[45]),"+f"(d[46]),"+f"(d[47]),"+f"(d[48]),"+f"(d[49]),"+f"(d[50]),"+f"(d[51]),"+f"(d[52]),"+f"(d[53]),"+f"(d[54]),"+f"(d[55])
   : "r"(a[0]), "r"(a[1]), "r"(a[2]), "r"(a[3]), "l"(db), "r"(sd));
}
template<> __device__ __forceinline__ void wgmma_rs<104,0>(float* d, const uint32_t* a, uint64_t db, int sd) {
  asm volatile("{\n.reg .pred p;\nsetp.ne.b32 p, %57, 0;\nwgmma.mma_async.sync.aligned.m64n104k16.f32.bf16.bf16 {%0,%1,%2,%3,%4,%5,%6,%7,%8,%9,%10,%11,%12,%13,%14,%15,%16,%17,%18,%19,%20,%21,%22,%23,%24,%25,%26,%27,%28,%29,%30,%31,%32,%33,%34,%35,%36,%37,%38,%39,%40,%41,%42,%43,%44,%45,%46,%47,%48,%49,%50,%51}, {%52,%53,%54,%55}, %56, p, 1, 1, 0;\n}\n"
   : "+f"(d[0]),"+f"(d[1]),"+f"(d[2]),"+f"(d[3]),"+f"(d[4]),"+f"(d[5]),"+f"(d[6]),"+f"(d[7]),"+f"(d[8]),"+f"(d[9]),"+f"(d[10]),"+f"(d[11]),"+f"(d[12]),"+f"(d[13]),"+f"(d[14]),"+f"(d[15]),"+f"(d[16]),"+f"(d[17]),"+f"(d[18]),"+f"(d[19]),"+f"(d[20]),"+f"(d[21]),"+f"(d[22]),"+f"(d[23]),"+f"(d[24]),"+f"(d[25]),"+f"(d[26]),"+f"(d[27]),"+f"(d[28]),"+f"(d[29]),"+f"(d[30]),"+f"(d[31]),"+f"(d[32]),"+f"(d[33]),"+f"(d[34]),"+f"(d[35]),"+f"(d[36]),"+f"(d[37]),"+f"(d[38]),"+f"(d[39]),"+f"(d[40]),"+f"(d[41]),"+f"(d[42]),"+f"(d[43]),"+f"(d[44]),"+f"(d[45]),"+f"(d[46]),"+f"(d[47]),"+f"(d[48]),"+f"(d[49]),"+f"(d[50]),"+f"(d[51])
   : "r"(a[0]), "r"(a[1]), "r"(a[2]), "r"(a[3]), "l"(db), "r"(sd));
}
template<> __device__ __forceinline__ void wgmma_rs<96,0>(float* d, const uint32_t* a, uint64_t db, int sd) {
  asm volatile("{\n.reg .pred p;\nsetp.ne.b32 p, %53, 0;\nwgmma.mma_async.sync.aligned.m64n96k16.f32.bf16.bf16 {%0,%1,%2,%3,%4,%5,%6,%7,%8,%9,%10,%11,%12,%13,%14,%15,%16,%17,%18,%19,%20,%21,%22,%23,%24,%25,%26,%27,%28,%29,%30,%31,%32,%33,%34,%35,%36,%37,%38,%39,%40,%41,%42,%43,%44,%45,%46,%47}, {%48,%49,%50,%51}, %52, p, 1, 1, 0;\n}\n"
   : "+f"(d[0]),"+f"(d[1]),"+f"(d[2]),"+f"(d[3]),"+f"(d[4]),"+f"(d[5]),"+f"(d[6]),"+f"(d[7]),"+f"(d[8]),"+f"(d[9]),"+f"(d[10]),"+f"(d[11]),"+f"(d[12]),"+f"(d[13]),"+f"(d[14]),"+f"(d[15]),"+f"(d[16]),"+f"(d[17]),"+f"(d[18]),"+f"(d[19]),"+f"(d[20]),"+f"(d[21]),"+f"(d[22]),"+f"(d[23]),"+f"(d[24]),"+f"(d[25]),"+f"(d[26]),"+f"(d[27]),"+f"(d[28]),"+f"(d[29]),"+f"(d[30]),"+f"(d[31]),"+f"(d[32]),"+f"(d[33]),"+f"(d[34]),"+f"(d[35]),"+f"(d[36]),"+f"(d[37]),"+f"(d[38]),"+f"(d[39]),"+f"(d[40]),"+f"(d[41]),"+f"(d[42]),"+f"(d[43]),"+f"(d[44]),"+f"(d[45]),"+f"(d[46]),"+f"(d[47])
   : "r"(a[0]), "r"(a[1]), "r"(a[2]), "r"(a[3]), "l"(db), "r"(sd));
}
template<> __device__ __forceinline__ void wgmma_rs<88,0>(float* d, const uint32_t* a, uint64_t db, int sd) {
  asm volatile("{\n.reg .pred p;\nsetp.ne.b32 p, %49, 0;\nwgmma.mma_async.sync.aligned.m64n88k16.f32.bf16.bf16 {%0,%1,%2,%3,%4,%5,%6,%7,%8,%9,%10,%11,%12,%13,%14,%15,%16,%17,%18,%19,%20,%21,%22,%23,%24,%25,%26,%27,%28,%29,%30,%31,%32,%33,%34,%35,%36,%37,%38,%39,%40,%41,%42,%43}, {%44,%45,%46,%47}, %48, p, 1, 1, 0;\n}\n"
   : "+f"(d[0]),"+f"(d[1]),"+f"(d[2]),"+f"(d[3]),"+f"(d[4]),"+f"(d[5]),"+f"(d[6]),"+f"(d[7]),"+f"(d[8]),"+f"(d[9]),"+f"(d[10]),"+f"(d[11]),"+f"(d[12]),"+f"(d[13]),"+f"(d[14]),"+f"(d[15]),"+f"(d[16]),"+f"(d[17]),"+f"(d[18]),"+f"(d[19]),"+f"(d[20]),"+f"(d[21]),"+f"(d[22]),"+f"(d[23]),"+f"(d[24]),"+f"(d[25]),"+f"(d[26]),"+f"(d[27]),"+f"(d[28]),"+f"(d[29]),"+f"(d[30]),"+f"(d[31]),"+f"(d[32]),"+f"(d[33]),"+f"(d[34]),"+f"(d[35]),"+f"(d[36]),"+f"(d[37]),"+f"(d[38]),"+f"(d[39]),"+f"(d[40]),"+f"(d[41]),"+f"(d[42]),"+f"(d[43])
   : "r"(a[0]), "r"(a[1]), "r"(a[2]), "r"(a[3]), "l"(db), "r"(sd));
}
template<> __device__ __forceinline__ void wgmma_rs<80,0>(float* d, const uint32_t* a, uint64_t db, int sd) {
  asm volatile("{\n.reg .pred p;\nsetp.ne.b32 p, %45, 0;\nwgmma.mma_async.sync.aligned.m64n80k16.f32.bf16.bf16 {%0,%1,%2,%3,%4,%5,%6,%7,%8,%9,%10,%11,%12,%13,%14,%15,%16,%17,%18,%19,%20,%21,%22,%23,%24,%25,%26,%27,%28,%29,%30,%31,%32,%33,%34,%35,%36,%37,%38,%39}, {%40,%41,%42,%43}, %44, p, 1, 1, 0;\n}\n"
   : "+f"(d[0]),"+f"(d[1]),"+f"(d[2]),"+f"(d[3]),"+f"(d[4]),"+f"(d[5]),"+f"(d[6]),"+f"(d[7]),"+f"(d[8]),"+f"(d[9]),"+f"(d[10]),"+f"(d[11]),"+f"(d[12]),"+f"(d[13]),"+f"(d[14]),"+f"(d[15]),"+f"(d[16]),"+f"(d[17]),"+f"(d[18]),"+f"(d[19]),"+f"(d[20]),"+f"(d[21]),"+f"(d[22]),"+f"(d[23]),"+f"(d[24]),"+f"(d[25]),"+f"(d[26]),"+f"(d[27]),"+f"(d[28]),"+f"(d[29]),"+f"(d[30]),"+f"(d[31]),"+f"(d[32]),"+f"(d[33]),"+f"(d[34]),"+f"(d[35]),"+f"(d[36]),"+f"(d[37]),"+f"(d[38]),"+f"(d[39])
   : "r"(a[0]), "r"(a[1]), "r"(a[2]), "r"(a[3]), "l"(db), "r"(sd));
}
template<> __device__ __forceinline__ void wgmma_rs<72,0>(float* d, const uint32_t* a, uint64_t db, int sd) {
  asm volatile("{\n.reg .pred p;\nsetp.ne.b32 p, %41, 0;\nwgmma.mma_async.sync.aligned.m64n72k16.f32.bf16.bf16 {%0,%1,%2,%3,%4,%5,%6,%7,%8,%9,%10,%11,%12,%13,%14,%15,%16,%17,%18,%19,%20,%21,%22,%23,%24,%25,%26,%27,%28,%29,%30,%31,%32,%33,%34,%35}, {%36,%37,%38,%39}, %40, p, 1, 1, 0;\n}\n"
   : "+f"(d[0]),"+f"(d[1]),"+f"(d[2]),"+f"(d[3]),"+f"(d[4]),"+f"(d[5]),"+f"(d[6]),"+f"(d[7]),"+f"(d[8]),"+f"(d[9]),"+f"(d[10]),"+f"(d[11]),"+f"(d[12]),"+f"(d[13]),"+f"(d[14]),"+f"(d[15]),"+f"(d[16]),"+f"(d[17]),"+f"(d[18]),"+f"(d[19]),"+f"(d[20]),"+f"(d[21]),"+f"(d[22]),"+f"(d[23]),"+f"(d[24]),"+f"(d[25]),"+f"(d[26]),"+f"(d[27]),"+f"(d[28]),"+f"(d[29]),"+f"(d[30]),"+f"(d[31]),"+f"(d[32]),"+f"(d[33]),"+f"(d[34]),"+f"(d[35])
   : "r"(a[0]), "r"(a[1]), "r"(a[2]), "r"(a[3]), "l"(db), "r"(sd));
}
template<> __device__ __forceinline__ void wgmma_rs<64,0>(float* d, const uint32_t* a, uint64_t db, int sd) {
  asm volatile("{\n.reg .pred p;\nsetp.ne.b32 p, %37, 0;\nwgmma.mma_async.sync.aligned.m64n64k16.f32.bf16.bf16 {%0,%1,%2,%3,%4,%5,%6,%7,%8,%9,%10,%11,%12,%13,%14,%15,%16,%17,%18,%19,%20,%21,%22,%23,%24,%25,%26,%27,%28,%29,%30,%31}, {%32,%33,%34,%35}, %36, p, 1, 1, 0;\n}\n"
   : "+f"(d[0]),"+f"(d[1]),"+f"(d[2]),"+f"(d[3]),"+f"(d[4]),"+f"(d[5]),"+f"(d[6]),"+f"(d[7]),"+f"(d[8]),"+f"(d[9]),"+f"(d[10]),"+f"(d[11]),"+f"(d[12]),"+f"(d[13]),"+f"(d[14]),"+f"(d[15]),"+f"(d[16]),"+f"(d[17]),"+f"(d[18]),"+f"(d[19]),"+f"(d[20]),"+f"(d[21]),"+f"(d[22]),"+f"(d[23]),"+f"(d[24]),"+f"(d[25]),"+f"(d[26]),"+f"(d[27]),"+f"(d[28]),"+f"(d[29]),"+f"(d[30]),"+f"(d[31])
   : "r"(a[0]), "r"(a[1]), "r"(a[2]), "r"(a[3]), "l"(db), "r"(sd));
}
template<> __device__ __forceinline__ void wgmma_ss<64,0,1>(float* d, uint64_t da, uint64_t db, int sd) {
  asm volatile("{\n.reg .pred p;\nsetp.ne.b32 p, %34, 0;\nwgmma.mma_async.sync.aligned.m64n64k16.f32.bf16.bf16 {%0,%1,%2,%3,%4,%5,%6,%7,%8,%9,%10,%11,%12,%13,%14,%15,%16,%17,%18,%19,%20,%21,%22,%23,%24,%25,%26,%27,%28,%29,%30,%31}, %32, %33, p, 1, 1, 0, 1;\n}\n"
   : "+f"(d[0]),"+f"(d[1]),"+f"(d[2]),"+f"(d[3]),"+f"(d[4]),"+f"(d[5]),"+f"(d[6]),"+f"(d[7]),"+f"(d[8]),"+f"(d[9]),"+f"(d[10]),"+f"(d[11]),"+f"(d[12]),"+f"(d[13]),"+f"(d[14]),"+f"(d[15]),"+f"(d[16]),"+f"(d[17]),"+f"(d[18]),"+f"(d[19]),"+f"(d[20]),"+f"(d[21]),"+f"(d[22]),"+f"(d[23]),"+f"(d[24]),"+f"(d[25]),"+f"(d[26]),"+f"(d[27]),"+f"(d[28]),"+f"(d[29]),"+f"(d[30]),"+f"(d[31])
   : "l"(da), "l"(db), "r"(sd));
}
template<> __device__ __forceinline__ void wgmma_ss<64,1,1>(float* d, uint64_t da, uint64_t db, int sd) {
  asm volatile("{\n.reg .pred p;\nsetp.ne.b32 p, %34, 0;\nwgmma.mma_async.sync.aligned.m64n64k16.f32.bf16.bf16 {%0,%1,%2,%3,%4,%5,%6,%7,%8,%9,%10,%11,%12,%13,%14,%15,%16,%17,%18,%19,%20,%21,%22,%23,%24,%25,%26,%27,%28,%29,%30,%31}, %32, %33, p, 1, 1, 1, 1;\n}\n"
   : "+f"(d[0]),"+f"(d[1]),"+f"(d[2]),"+f"(d[3]),"+f"(d[4]),"+f"(d[5]),"+f"(d[6]),"+f"(d[7]),"+f"(d[8]),"+f"(d[9]),"+f"(d[10]),"+f"(d[11]),"+f"(d[12]),"+f"(d[13]),"+f"(d[14]),"+f"(d[15]),"+f"(d[16]),"+f"(d[17]),"+f"(d[18]),"+f"(d[19]),"+f"(d[20]),"+f"(d[21]),"+f"(d[22]),"+f"(d[23]),"+f"(d[24]),"+f"(d[25]),"+f"(d[26]),"+f"(d[27]),"+f"(d[28]),"+f"(d[29]),"+f"(d[30]),"+f"(d[31])
   : "l"(da), "l"(db), "r"(sd));
}
template<> __device__ __forceinline__ void wgmma_ss<192,0,1>(float* d, uint64_t da, uint64_t db, int sd) {
  asm volatile("{\n.reg .pred p;\nsetp.ne.b32 p, %98, 0;\nwgmma.mma_async.sync.aligned.m64n192k16.f32.bf16.bf16 {%0,%1,%2,%3,%4,%5,%6,%7,%8,%9,%10,%11,%12,%13,%14,%15,%16,%17,%18,%19,%20,%21,%22,%23,%24,%25,%26,%27,%28,%29,%30,%31,%32,%33,%34,%35,%36,%37,%38,%39,%40,%41,%42,%43,%44,%45,%46,%47,%48,%49,%50,%51,%52,%53,%54,%55,%56,%57,%58,%59,%60,%61,%62,%63,%64,%65,%66,%67,%68,%69,%70,%71,%72,%73,%74,%75,%76,%77,%78,%79,%80,%81,%82,%83,%84,%85,%86,%87,%88,%89,%90,%91,%92,%93,%94,%95}, %96, %97, p, 1, 1, 0, 1;\n}\n"
   : "+f"(d[0]),"+f"(d[1]),"+f"(d[2]),"+f"(d[3]),"+f"(d[4]),"+f"(d[5]),"+f"(d[6]),"+f"(d[7]),"+f"(d[8]),"+f"(d[9]),"+f"(d[10]),"+f"(d[11]),"+f"(d[12]),"+f"(d[13]),"+f"(d[14]),"+f"(d[15]),"+f"(d[16]),"+f"(d[17]),"+f"(d[18]),"+f"(d[19]),"+f"(d[20]),"+f"(d[21]),"+f"(d[22]),"+f"(d[23]),"+f"(d[24]),"+f"(d[25]),"+f"(d[26]),"+f"(d[27]),"+f"(d[28]),"+f"(d[29]),"+f"(d[30]),"+f"(d[31]),"+f"(d[32]),"+f"(d[33]),"+f"(d[34]),"+f"(d[35]),"+f"(d[36]),"+f"(d[37]),"+f"(d[38]),"+f"(d[39]),"+f"(d[40]),"+f"(d[41]),"+f"(d[42]),"+f"(d[43]),"+f"(d[44]),"+f"(d[45]),"+f"(d[46]),"+f"(d[47]),"+f"(d[48]),"+f"(d[49]),"+f"(d[50]),"+f"(d[51]),"+f"(d[52]),"+f"(d[53]),"+f"(d[54]),"+f"(d[55]),"+f"(d[56]),"+f"(d[57]),"+f"(d[58]),"+f"(d[59]),"+f"(d[60]),"+f"(d[61]),"+f"(d[62]),"+f"(d[63]),"+f"(d[64]),"+f"(d[65]),"+f"(d[66]),"+f"(d[67]),"+f"(d[68]),"+f"(d[69]),"+f"(d[70]),"+f"(d[71]),"+f"(d[72]),"+f"(d[73]),"+f"(d[74]),"+f"(d[75]),"+f"(d[76]),"+f"(d[77]),"+f"(d[78]),"+f"(d[79]),"+f"(d[80]),"+f"(d[81]),"+f"(d[82]),"+f"(d[83]),"+f"(d[84]),"+f"(d[85]),"+f"(d[86]),"+f"(d[87]),"+f"(d[88]),"+f"(d[89]),"+f"(d[90]),"+f"(d[91]),"+f"(d[92]),"+f"(d[93]),"+f"(d[94]),"+f"(d[95])
   : "l"(da), "l"(db), "r"(sd));
}
template<> __device__ __forceinline__ void wgmma_ss<192,1,1>(float* d, uint64_t da, uint64_t db, int sd) {
  asm volatile("{\n.reg .pred p;\nsetp.ne.b32 p, %98, 0;\nwgmma.mma_async.sync.aligned.m64n192k16.f32.bf16.bf16 {%0,%1,%2,%3,%4,%5,%6,%7,%8,%9,%10,%11,%12,%13,%14,%15,%16,%17,%18,%19,%20,%21,%22,%23,%24,%25,%26,%27,%28,%29,%30,%31,%32,%33,%34,%35,%36,%37,%38,%39,%40,%41,%42,%43,%44,%45,%46,%47,%48,%49,%50,%51,%52,%53,%54,%55,%56,%57,%58,%59,%60,%61,%62,%63,%64,%65,%66,%67,%68,%69,%70,%71,%72,%73,%74,%75,%76,%77,%78,%79,%80,%81,%82,%83,%84,%85,%86,%87,%88,%89,%90,%91,%92,%93,%94,%95}, %96, %97, p, 1, 1, 1, 1;\n}\n"
   : "+f"(d[0]),"+f"(d[1]),"+f"(d[2]),"+f"(d[3]),"+f"(d[4]),"+f"(d[5]),"+f"(d[6]),"+f"(d[7]),"+f"(d[8]),"+f"(d[9]),"+f"(d[10]),"+f"(d[11]),"+f"(d[12]),"+f"(d[13]),"+f"(d[14]),"+f"(d[15]),"+f"(d[16]),"+f"(d[17]),"+f"(d[18]),"+f"(d[19]),"+f"(d[20]),"+f"(d[21]),"+f"(d[22]),"+f"(d[23]),"+f"(d[24]),"+f"(d[25]),"+f"(d[26]),"+f"(d[27]),"+f"(d[28]),"+f"(d[29]),"+f"(d[30]),"+f"(d[31]),"+f"(d[32]),"+f"(d[33]),"+f"(d[34]),"+f"(d[35]),"+f"(d[36]),"+f"(d[37]),"+f"(d[38]),"+f"(d[39]),"+f"(d[40]),"+f"(d[41]),"+f"(d[42]),"+f"(d[43]),"+f"(d[44]),"+f"(d[45]),"+f"(d[46]),"+f"(d[47]),"+f"(d[48]),"+f"(d[49]),"+f"(d[50]),"+f"(d[51]),"+f"(d[52]),"+f"(d[53]),"+f"(d[54]),"+f"(d[55]),"+f"(d[56]),"+f"(d[57]),"+f"(d[58]),"+f"(d[59]),"+f"(d[60]),"+f"(d[61]),"+f"(d[62]),"+f"(d[63]),"+f"(d[64]),"+f"(d[65]),"+f"(d[66]),"+f"(d[67]),"+f"(d[68]),"+f"(d[69]),"+f"(d[70]),"+f"(d[71]),"+f"(d[72]),"+f"(d[73]),"+f"(d[74]),"+f"(d[75]),"+f"(d[76]),"+f"(d[77]),"+f"(d[78]),"+f"(d[79]),"+f"(d[80]),"+f"(d[81]),"+f"(d[82]),"+f"(d[83]),"+f"(d[84]),"+f"(d[85]),"+f"(d[86]),"+f"(d[87]),"+f"(d[88]),"+f"(d[89]),"+f"(d[90]),"+f"(d[91]),"+f"(d[92]),"+f"(d[93]),"+f"(d[94]),"+f"(d[95])
   : "l"(da), "l"(db), "r"(sd));
}

__device__ __forceinline__ void stats_publish(uint32_t sb, int layer, int rb, int hg, int ht, uint32_t tag) {
  const int lane = ht & 31, w = ht >> 5, g = lane >> 2, t = lane & 3, ks = hg & 3;
  uint32_t xa;
  if (layer == 0) {
    const int row = 16 * w + (lane & 15), kc = 2 * ks + (lane >> 4);
    xa = row * 128 + ((kc ^ (row & 7)) << 4);
  } else {
    const int k = 16 * ks + (lane & 7) + 8 * (lane >> 4), pc = 2 * w + ((lane >> 3) & 1);
    xa = k * 128 + ((pc ^ (k & 7)) << 4);
  }
  float s[4] = {0.f, 0.f, 0.f, 0.f}, q[4] = {0.f, 0.f, 0.f, 0.f};
#pragma unroll 1
  for (int c = hg >> 2; c < 8; c += 2) {
    uint32_t A[2][4];
    mbar_wait(sb + SM_BAR + 8 * (B_XF + c), layer);
#pragma unroll
    for (int h = 0; h < 2; h++) {
      if (layer == 0) ldsm4(A[h], sb + SM_X + c * 16384 + h * 8192 + xa);
      else ldsm4t(A[h], sb + SM_X + c * 16384 + h * 8192 + xa);
    }
    if (c >= 6) ATS(48, 256);
    if (c < 2) ATS(51, 256);
#pragma unroll
    for (int r = 0; r < 4; r++)
#pragma unroll
      for (int i = 0; i < 2; i++) {
        const uint32_t v = A[r >> 1][2 * i + (r & 1)];
        const float a = bf_lo(v), b = bf_hi(v);
        s[r] += a + b; q[r] = fmaf(a, a, q[r]); q[r] = fmaf(b, b, q[r]);
      }
  }
#pragma unroll
  for (int r = 0; r < 2; r++) {
    s[r] = ((t & 2) ? s[r + 2] : s[r]) + __shfl_xor_sync(~0u, (t & 2) ? s[r] : s[r + 2], 2);
    q[r] = ((t & 2) ? q[r + 2] : q[r]) + __shfl_xor_sync(~0u, (t & 2) ? q[r] : q[r + 2], 2);
  }
  s[0] = ((t & 1) ? s[1] : s[0]) + __shfl_xor_sync(~0u, (t & 1) ? s[0] : s[1], 1);
  q[0] = ((t & 1) ? q[1] : q[0]) + __shfl_xor_sync(~0u, (t & 1) ? q[0] : q[1], 1);
  st_part(&g_part[(rb * 8 + hg) * 128 + 64 * (t >> 1) + 16 * w + 8 * (t & 1) + g], s[0], q[0], tag);
  ATS(49, 256);
}
__device__ __forceinline__ void stats_gather(uint32_t sb, int rb, int ht, uint32_t tag) {
  const uint2* src = &g_part[rb * 8 * 128 + ht];
  uint2 v[8];
  for (int it = 0;; it++) {
    uint32_t bad = 0;
#pragma unroll
    for (int i = 0; i < 8; i++) v[i] = ld_part(src + i * 128);
#pragma unroll
    for (int i = 0; i < 8; i++) bad |= v[i].y ^ tag;
    if (__all_sync(~0u, (bad & 7u) == 0)) break;
    if (it > (1 << 22)) __trap();
  }
  float s = 0.f, q = 0.f;
#pragma unroll
  for (int i = 0; i < 8; i++) { s += __uint_as_float(v[i].x); q += __uint_as_float(v[i].y); }
  const float mean = s * (1.f / DM);
  const float rstd = rsqrt_approx(fmaxf(q * (1.f / DM) - mean * mean, 0.f) + 1e-5f);
  asm volatile("st.shared.v2.f32 [%0], {%1,%2};" ::"r"(sb + SM_ST + ht * 8), "f"(mean), "f"(rstd) : "memory");
  __syncwarp();
  if (elect_one()) mbar_arrive(sb + SM_BAR + 8 * B_STF);
}
__device__ __forceinline__ void halo_receive(uint32_t sb, int layer, int rb, int hg, int ht) {
  const int lane = ht & 31, h = ht >> 5;
  uint4 kv = make_uint4(0, 0, 0, 0);
  mbar_wait(sb + SM_BAR + 8 * B_SD, layer);
  if (rb & 7) {
    const uint32_t tag = 2 * lds32(sb + SM_EP) + layer + 1;
    const uint4* src = &g_halo[((rb - 1) * 8 + hg) * 192 + h * 48];
    if (layer == 0) delay<D_HALO>(); else delay<D_HALO1>();
    uint4 a;
    uint2 b;
    int it = 0;
    do {
      a = ld_tagged(src + lane); b = ld_part((const uint2*)(src + 32) + lane);
      if (++it > (1 << 22)) __trap();
    } while (!__all_sync(~0u, a.w == tag && b.y == tag));
    kv = make_uint4(a.x, a.y, movm_t(a.z), movm_t(b.x));
  }
  sts128(sb + SM_KVX + h * 512 + lane * 16, kv);
  ATS(61, 256);
  bar_arrive(7, 160);
  if (elect_one()) mbar_arrive(sb + SM_BAR + 8 * B_HF);
}

__device__ __forceinline__ void halo_receive1(uint32_t sb, int layer, int rb, int hg, int lane, uint32_t tag) {
  uint4 a[4];
  uint2 b[4];
  mbar_wait(sb + SM_BAR + 8 * B_SD, layer);
  if (rb & 7) {
    const uint4* src = &g_halo[((rb - 1) * 8 + hg) * 192];
    if (layer == 0) delay<D_HALO>(); else delay<D_HALO1>();
    for (int it = 0;; it++) {
      uint32_t bad = 0;
#pragma unroll
      for (int h = 0; h < 4; h++) { a[h] = ld_tagged(src + h * 48 + lane); b[h] = ld_part((const uint2*)(src + h * 48 + 32) + lane); }
#pragma unroll
      for (int h = 0; h < 4; h++) {
        bad |= (a[h].w ^ tag) | (b[h].y ^ tag);
        a[h].z = movm_t(a[h].z); a[h].w = movm_t(b[h].x);
      }
      if (__all_sync(~0u, bad == 0)) break;
      if (it > (1 << 22)) __trap();
    }
  } else {
#pragma unroll
    for (int h = 0; h < 4; h++) a[h] = make_uint4(0, 0, 0, 0);
  }
#pragma unroll
  for (int h = 0; h < 4; h++) sts128(sb + SM_KVX + h * 512 + lane * 16, a[h]);
  ATS(61, 448);
  bar_arrive(7, 64);
  if (lane < 4) mbar_arrive(sb + SM_BAR + 8 * B_HF);
}

template <bool TR>
__device__ __forceinline__ void gemm_section(float* acc, float2* cs, uint32_t sb, int layer, int wg, int w, int lane) {
  const uint32_t bar = sb + SM_BAR;
  const bool leader = (w == 0) && (lane == 0);
  auto issue = [&](int c, int slot) {
    mbar_wait(bar + 8 * (B_XF + c), layer);
    mbar_wait(bar + 8 * (B_KVF + c), layer);
    const uint64_t da = mkdesc(sb + SM_X + c * 16384 + wg * 8192, TR ? 8192 : 16, 1024, 1);
    const uint64_t db = mkdesc(sb + SM_W + slot * 24576, 8192, 1024, 1);
    wg_fence();
#pragma unroll
    for (int ks = 0; ks < 4; ks++) wgmma_ss<192, TR ? 1 : 0, 1>(acc, da + (TR ? ks * 128 : ks * 2), db + ks * 128, (c | ks) != 0);
    wg_commit();
  };
  auto step = [&](int c, int slot) {
    issue(c, slot);
    wg_wait<1>();
    if (leader) mbar_arrive(bar + 8 * (B_KVE + c - 1));
  };
  if (!TR) bar_sync(0, NTHREADS);
  if (TR && G_WAIT == 3 && wg == 1) bar_sync(14, 256);
  if (TR && G_WAIT == 4 && wg == 1) mbar_wait(bar + 8 * (B_P + 3), 0);
  issue(0, 0);
  if (threadIdx.x == 0) TS(2 + layer * 20 + 0);
  if (threadIdx.x == 128 && layer == 1) TS(60);
  auto ld_cs = [&](int j0) {
#pragma unroll
    for (int j = j0; j < j0 + 8; j++) cs[j] = lds64f(sb + SM_CS + 4 * (8 * j + 2 * (lane & 3)));
  };
  if (TR && CS_STEP == 0) ld_cs(8);
  step(1, 1);
  if (TR && CS_STEP == 0) ld_cs(16);
  if (TR && CS_STEP == 1) ld_cs(8);
  step(2, 2);
  if (TR && CS_STEP == 1) ld_cs(16);
  if (TR && CS_STEP == 2) ld_cs(8);
  step(3, 0);
  if (TR && CS_STEP == 2) ld_cs(16);
  step(4, 1);
  if (TR && CS_STEP == 4) ld_cs(8);
  step(5, 2);
  if (TR && CS_STEP == 4) ld_cs(16);
  if (!TR && !CS_LATE0) { mbar_wait(bar + 8 * B_CSF, 0); ld_cs(8); ld_cs(16); }
  if (wg == 0) bar_sync(5, 256);
  issue(6, 0);
  issue(7, 1);
  if (wg == 1) bar_arrive(5, 256);
  if (!TR && CS_LATE0) { mbar_wait(bar + 8 * B_CSF, 0); ld_cs(8); ld_cs(16); }
}

__device__ __forceinline__ void attn_phase(const Params& p, uint32_t sb, int layer, int rb, int hg, int wg, int w) {
  const int lane = opaque_tid() & 31;
  const int g = lane >> 2, t = lane & 3;
  const uint32_t bar = sb + SM_BAR;
  const int row0 = 64 * wg + 16 * w;
  const bool leader = (w == 0) && (lane == 0);
  float acc[96];
  float2 cs[24];
  if (layer) gemm_section<true>(acc, cs, sb, layer, wg, w, lane);
  else gemm_section<false>(acc, cs, sb, layer, wg, w, lane);
  ATS(41, 224);
  mbar_wait(bar + 8 * B_STF, layer);
  const uint32_t tag = 2 * lds32(sb + SM_EP) + layer + 1;
  const float2 st0 = lds64f(sb + SM_ST + (row0 + g) * 8), st1 = lds64f(sb + SM_ST + (row0 + g + 8) * 8);
  const float mean0 = st0.x, rstd0 = st0.y, mean1 = st1.x, rstd1 = st1.y;
  wg_wait<0>();
  if (threadIdx.x == 0) TS(2 + layer * 20 + 1);
  ATS(39, 224);
  if (leader) mbar_arrive(bar + 8 * B_QDONE);

  uint32_t fp[4][4], fl[4][4], fh[4][4], qa[4][4];
  const int cw = 4 * wg + w;
  {
    const float nm0 = -mean0 * rstd0, nm1 = -mean1 * rstd1;
    const uint32_t kvx = sb + SM_KVX + cw * 2048 + lane * 16;
#pragma unroll
    for (int h = 0; h < 4; h++)
#pragma unroll
      for (int k = 0; k < 4; k++) {
        const int j = 8 + (k >> 1) * 8 + 2 * h + (k & 1);
        fh[h][k] = packbf(fmaf(acc[4 * j + 2], rstd1, nm1 * cs[j].x), fmaf(acc[4 * j + 3], rstd1, nm1 * cs[j].y));
      }
    if (cw == 7) {
      uint4* halo = &g_halo[(rb * 8 + hg) * 192];
#pragma unroll
      for (int h = 0; h < 4; h++) {
        st_tagged3(halo + h * 48 + lane, fh[h][0], fh[h][1], fh[h][2], tag);
        asm volatile("st.relaxed.gpu.global.v2.u32 [%0], {%1,%2};" ::"l"((uint2*)(halo + h * 48 + 32) + lane), "r"(fh[h][3]), "r"(tag) : "memory");
      }
      if (elect_one()) mbar_arrive(bar + 8 * B_SD);
      if (layer == TLAYER && threadIdx.x == 224) TS(47);
    }
#pragma unroll
    for (int h = 0; h < 4; h++) { fh[h][2] = movm_t(fh[h][2]); fh[h][3] = movm_t(fh[h][3]); }
    if (cw != 7) {
#pragma unroll
      for (int h = 0; h < 4; h++) sts128(kvx + 2048 + h * 512, make_uint4(fh[h][0], fh[h][1], fh[h][2], fh[h][3]));
      bar_arrive(8 + cw, 64);
    }
    sched_fence<6>();
    if (layer == TLAYER && threadIdx.x == 0) TS(45);
#pragma unroll
    for (int j = 0; j < 8; j++) cs[j] = lds64f(sb + SM_CS + 4 * (8 * j + 2 * t));
#pragma unroll
    for (int h = 0; h < 4; h++)
#pragma unroll
      for (int k = 0; k < 4; k++) {
        const int j = 8 + (k >> 1) * 8 + 2 * h + (k & 1);
        fl[h][k] = packbf(fmaf(acc[4 * j], rstd0, nm0 * cs[j].x), fmaf(acc[4 * j + 1], rstd0, nm0 * cs[j].y));
        if (k >= 2) fl[h][k] = movm_t(fl[h][k]);
      }
#pragma unroll
    for (int h = 0; h < 4; h++) {
#pragma unroll
      for (int dh = 0; dh < 2; dh++) {
        const int j = 2 * h + dh;
        const float2 c2 = cs[j];
        qa[h][2 * dh] = packbf(fmaf(-mean0, c2.x, acc[4 * j + 0]), fmaf(-mean0, c2.y, acc[4 * j + 1]));
        qa[h][2 * dh + 1] = packbf(fmaf(-mean1, c2.x, acc[4 * j + 2]), fmaf(-mean1, c2.y, acc[4 * j + 3]));
      }
    }
    if (threadIdx.x == 0) TS(2 + layer * 20 + 2);
    sched_fence<0>();
    bar_sync(7 + cw, cw == 0 && !HALO_W14 ? 160 : 64);
#pragma unroll
    for (int h = 0; h < 4; h++) {
      const uint4 v = lds128(kvx + h * 512);
      fp[h][0] = v.x; fp[h][1] = v.y; fp[h][2] = v.z; fp[h][3] = v.w;
    }
    if (threadIdx.x == 0) TS(2 + layer * 20 + 4);
  }

  const bool u0 = 2 * t > g, u1 = 2 * t + 1 > g;
  const uint32_t mU = (u0 ? 0x0000ffffu : 0u) | (u1 ? 0xffff0000u : 0u);
  const float cl2 = 0.25f * 1.4426950408889634f;
  const float sc0 = rstd0 * cl2, sc1 = rstd1 * cl2;
  const float cneg = ((rb & 7) == 0 && cw == 0) ? -INFINITY : 0.f;
  float v[4][4];
#pragma unroll
  for (int h = 0; h < 4; h++) {
    float T0[4] = {cneg, cneg, cneg, cneg}, T1[4] = {0.f, 0.f, 0.f, 0.f}, T2[4] = {0.f, 0.f, 0.f, 0.f};
    mma_bf16(T1, qa[h], fl[h][0], fl[h][1]);
    mma_bf16(T2, qa[h], fh[h][0], fh[h][1]);
    mma_bf16(T0, qa[h], fp[h][0], fp[h][1]);
    v[h][0] = u0 ? T0[0] : T1[0]; v[h][1] = u1 ? T0[1] : T1[1];
    v[h][2] = u0 ? T1[2] : T2[2]; v[h][3] = u1 ? T1[3] : T2[3];
  }
  float m0[4], m1[4];
#pragma unroll
  for (int h = 0; h < 4; h++) { m0[h] = fmaxf(v[h][0], v[h][1]); m1[h] = fmaxf(v[h][2], v[h][3]); }
#pragma unroll
  for (int o = 1; o <= 2; o <<= 1) {
#pragma unroll
    for (int h = 0; h < 4; h++) {
      m0[h] = fmaxf(m0[h], __shfl_xor_sync(~0u, m0[h], o));
      m1[h] = fmaxf(m1[h], __shfl_xor_sync(~0u, m1[h], o));
    }
  }
  float O0[4][4], O1[4][4], Z[4][4];
#pragma unroll
  for (int h = 0; h < 4; h++) {
    const float mm0 = -m0[h] * sc0, mm1 = -m1[h] * sc1;
    const uint32_t P0 = packbf(ex2(fmaf(v[h][0], sc0, mm0)), ex2(fmaf(v[h][1], sc0, mm0)));
    const uint32_t P1 = packbf(ex2(fmaf(v[h][2], sc1, mm1)), ex2(fmaf(v[h][3], sc1, mm1)));
#pragma unroll
    for (int k = 0; k < 4; k++) O0[h][k] = O1[h][k] = Z[h][k] = 0.f;
    mma_bf16_k8(Z[h], P0, P1, 0x3f803f80u);
    mma_bf16_k8(O0[h], P0 & ~mU, P1 & mU, fl[h][2]); mma_bf16_k8(O1[h], P0 & ~mU, P1 & mU, fl[h][3]);
    mma_bf16_k8(O0[h], P0 & mU, 0u, fp[h][2]); mma_bf16_k8(O1[h], P0 & mU, 0u, fp[h][3]);
    mma_bf16_k8(O0[h], 0u, P1 & ~mU, fh[h][2]); mma_bf16_k8(O1[h], 0u, P1 & ~mU, fh[h][3]);
  }
  const uint32_t ob = sb + SM_OST + wg * 8192;
  const int o_row = 16 * w + (lane & 7) + 8 * ((lane >> 3) & 1);
#pragma unroll
  for (int h = 0; h < 4; h++) {
    const float i0 = rcp_approx(Z[h][0]), i1 = rcp_approx(Z[h][2]);
    const int ch = 2 * h + (lane >> 4);
    stsm4(ob + o_row * 128 + ((ch ^ (o_row & 7)) << 4), packbf(O0[h][0] * i0, O0[h][1] * i0), packbf(O0[h][2] * i1, O0[h][3] * i1),
          packbf(O1[h][0] * i0, O1[h][1] * i0), packbf(O1[h][2] * i1, O1[h][3] * i1));
  }
  if (threadIdx.x == 0) TS(2 + layer * 20 + 5);
  ATS(57, 128); ATS(20, 96);
  bar_sync(2 + wg, 128);
  if (w == 0 && elect_one()) {
    fence_async_smem();
    tma_st(&p.mapO, hg * 64, rb * 128 + wg * 64, ob);
    bulk_commit();
    mbar_arrive(bar + 8 * B_AD);
    bulk_wait_all();
    red_relaxed(&g_cnt[(C_O + rb) * 32]);
    mbar_arrive(bar + 8 * B_OST);
    if (threadIdx.x == 0) TS(2 + layer * 20 + 6);
  }
  __syncwarp();
}

__device__ __forceinline__ void proj_phase(const Params& p, uint32_t sb, int layer, int rb, int q, int wg, int w) {
  const int lane = opaque_tid() & 31;
  const bool TR = layer != 0;
  const int t = lane & 3;
  const uint32_t bar = sb + SM_BAR;
  const uint32_t rbx = sb + SM_R + wg * 8192;
  uint32_t res[16];
  mbar_wait(bar + 8 * B_RF, layer);
  if (threadIdx.x == 0) TS(2 + layer * 20 + 7);
  if (!TR) {
#pragma unroll
    for (int j = 0; j < 8; j += 2) {
      const int mi = lane >> 3;
      const int row = 16 * w + (lane & 7) + 8 * (mi & 1), ch = j + (mi >> 1);
      ldsm4(&res[2 * j], rbx + row * 128 + ((ch ^ (row & 7)) << 4));
    }
  } else {
#pragma unroll
    for (int j = 0; j < 8; j += 2) {
      const int mi = lane >> 3;
      const int line = 8 * (j + (mi >> 1)) + (lane & 7), pc = 2 * w + (mi & 1);
      ldsm4t(&res[2 * j], rbx + line * 128 + ((pc ^ (line & 7)) << 4));
    }
  }
  bar_sync(2 + wg, 128);
  float acc[32];
#pragma unroll
  for (int i = 0; i < 16; i++) {
    asm volatile("shl.b32 %0, %1, 16;" : "=f"(acc[2 * i]) : "r"(res[i]));
    asm volatile("and.b32 %0, %1, 0xffff0000;" : "=f"(acc[2 * i + 1]) : "r"(res[i]));
  }
  const uint32_t tag = part_tag(lds32(sb + SM_EP), 2 * layer + 1);
  mbar_wait(bar + 8 * B_ZF, layer);
  mbar_wait(bar + 8 * B_WOF, layer);
#pragma unroll P_UNROLL
  for (int c = 0; c < 8; c++) {
    mbar_wait(bar + 8 * (B_OF + c), layer);
    if (c == 0 && threadIdx.x == 0) TS(2 + layer * 20 + 8);
    const uint64_t da = mkdesc(sb + sm_o(c) + wg * 8192, 16, 1024, 1);
    const uint64_t db = mkdesc(sb + SM_WO + c * 8192, 8192, 1024, 1);
    wg_fence();
#pragma unroll
    for (int ks = 0; ks < 4; ks++) wgmma_ss<64, 0, 1>(acc, da + ks * 2, db + ks * 128, 1);
    wg_commit();
  }
  wg_wait<0>();
#pragma unroll
  for (int i = 0; i < 32; i++) asm volatile("" : "+f"(acc[i]) :: "memory");
  if (threadIdx.x == 0) TS(2 + layer * 20 + 9);
  if (lane == 0 && w == 0) mbar_arrive(bar + 8 * B_PDONE);
  {
    float s[4], qq[4];
#pragma unroll
    for (int k = 0; k < 4; k++) { s[k] = acc[k]; qq[k] = acc[k] * acc[k]; }
#pragma unroll
    for (int j = 1; j < 8; j++)
#pragma unroll
      for (int k = 0; k < 4; k++) { s[k] += acc[4 * j + k]; qq[k] = fmaf(acc[4 * j + k], acc[4 * j + k], qq[k]); }
    const float s0 = s[0] + s[1], s1 = s[2] + s[3], q0 = qq[0] + qq[1], q1 = qq[2] + qq[3];
    float sr = ((t & 1) ? s1 : s0) + __shfl_xor_sync(~0u, (t & 1) ? s0 : s1, 1);
    float qr = ((t & 1) ? q1 : q0) + __shfl_xor_sync(~0u, (t & 1) ? q0 : q1, 1);
    sr += __shfl_xor_sync(~0u, sr, 2);
    qr += __shfl_xor_sync(~0u, qr, 2);
    if (t < 2) st_part(&g_part[(rb * 8 + q) * 128 + 64 * wg + 16 * w + (lane >> 2) + 8 * t], sr, qr, tag);
    __syncwarp();
    if (elect_one()) mbar_arrive(bar + 8 * B_PS);
    sched_fence<7>();
  }
#pragma unroll
  for (int j = 0; j < 8; j += 2) {
    const int mi = lane >> 3;
    const int line = 8 * (j + (mi >> 1)) + (lane & 7), pc = 2 * w + (mi & 1);
    stsm4t(rbx + line * 128 + ((pc ^ (line & 7)) << 4), packbf(acc[4 * j], acc[4 * j + 1]), packbf(acc[4 * j + 2], acc[4 * j + 3]),
           packbf(acc[4 * j + 4], acc[4 * j + 5]), packbf(acc[4 * j + 6], acc[4 * j + 7]));
  }
  fence_writer();
  bar_sync(2 + wg, 128);
  if (w == 0 && elect_one()) {
    fence_reader();
    fence_async_global();
    tma_st(&p.mapXT, rb * 128 + wg * 64, (2 * layer) * DM + q * 64, rbx);
    bulk_commit();
    if (threadIdx.x == 0) TS(2 + layer * 20 + 10);
    bulk_wait_all();
    red_relaxed(&g_cnt[C_CS * 32 + 2 + layer]);
    if (wg == 0) mbar_arrive(bar + 8 * B_RE);
  }
  __syncwarp();
}
__device__ __forceinline__ void proj_stats(uint32_t sb, int layer, int rb, int q, int lane, uint32_t tag) {
  const int r = 16 * q + (lane & 15);
  const uint2* src = &g_part[rb * 8 * 128 + r];
  uint32_t* dst = g_stats + layer * LSEQ + (rb >> 1) * 256 + ((r >> 2) & 1) * 128 + ((rb & 1) * 16 + (r >> 3)) * 4 + (r & 3);
  mbar_wait(sb + SM_BAR + 8 * B_PS, layer);
  delay<D_PST>();
  for (int it = 0;; it++) {
    uint2 v[8];
#pragma unroll
    for (int i = 0; i < 8; i++) v[i] = ld_part(src + i * 128);
    float s[4], qq[4];
    uint32_t bad = 0;
#pragma unroll
    for (int i = 0; i < 4; i++) {
      s[i] = __uint_as_float(v[i].x) + __uint_as_float(v[i + 4].x);
      qq[i] = __uint_as_float(v[i].y) + __uint_as_float(v[i + 4].y);
      bad |= (v[i].y ^ tag) | (v[i + 4].y ^ tag);
    }
    const float mean = ((s[0] + s[1]) + (s[2] + s[3])) * (1.f / DM);
    const float rstd = rsqrt_approx(fmaxf(fmaf((qq[0] + qq[1]) + (qq[2] + qq[3]), 1.f / DM, -mean * mean), 0.f) + 1e-5f);
    const bool ok = __all_sync(~0u, (bad & 7u) == 0);
    if (ok && lane < 16)
      asm volatile("st.relaxed.gpu.global.u32 [%0], %1;" ::"l"(dst), "r"(max(packbf(NORM_FMA ? -mean * rstd : -mean, rstd), 1u)) : "memory");
    if (ok) break;
    if (it > (1 << 22)) __trap();
  }
}

#define NA 14
#define NP 15
template <int M0, int M1> __device__ __forceinline__ void conv_load(uint32_t* A, uint32_t pe) {
#pragma unroll
  for (int m = M0; m < M1; m++) {
    asm volatile("ld.shared.v2.b32 {%0,%1}, [%2];" : "=r"(A[4 * m]), "=r"(A[4 * m + 1]) : "r"(pe + 256 * m) : "memory");
    A[4 * m + 2] = lds32(pe + 256 * m - 4);
  }
}
__device__ __forceinline__ uint32_t copy_reg(uint32_t v, uint32_t zero) { uint32_t r; asm volatile("or.b32 %0, %1, %2;" : "=r"(r) : "r"(v), "r"(zero)); return r; }
__device__ __forceinline__ uint32_t copy_reg2(uint32_t v, uint32_t zero) { uint32_t r; asm volatile("xor.b32 %0, %1, %2;" : "=r"(r) : "r"(v), "r"(zero)); return r; }
__device__ __forceinline__ void conv_park(uint32_t* P, uint32_t pe) {
#pragma unroll
  for (int m = 0; m < NP; m++)
#pragma unroll
    for (int k = 0; k < 3; k++) P[3 * m + k] = lds32(pe + 256 * m - 4 + 4 * k);
}
__device__ __forceinline__ void conv_unpark(uint32_t* A, const uint32_t* P, uint32_t zero) {
#pragma unroll
  for (int m = 0; m < NP; m++) {
    A[4 * m + 2] = copy_reg(P[3 * m], zero); A[4 * m] = copy_reg(P[3 * m + 1], zero);
    A[4 * m + 3] = copy_reg2(P[3 * m + 1], zero); A[4 * m + 1] = copy_reg(P[3 * m + 2], zero);
  }
}
template <int M0, int M1> __device__ __forceinline__ void conv_mmas(float* acc, const uint32_t* A, uint64_t d) {
  if constexpr (M0 < M1) {
    wgmma_rs<128 - 8 * (M0 / 2), 0>(acc, A + 4 * M0, d + (uint64_t)(4 * M0), M0 != 0);
    conv_mmas<M0 + 1, M1>(acc, A, d);
  }
}
struct SumAddr { uint32_t l0, l1, l2, se, so; };
__device__ __forceinline__ SumAddr conv_sum_addr(uint32_t sb, int c) {
  auto ua = [&](int j) { return sb + cv_u(0) + (127 - (j >> 3)) * 16 + (j & 7) * 2; };
  auto sa = [&](int hc) { const int ci = hc & ~1; return sb + cv_s(0) + ((ci >> 3) & 1) * 1024 + (ci >> 4) * 128 + (((ci ^ (ci >> 4)) & 7) << 4) + (hc & 1) * 8; };
  const int j0 = 4 * (c - 1);
  return {ua(j0 - 2), ua(j0), ua(j0 + 4), sa((c + 1) & 127), sa(c) + 2048};
}
__device__ __forceinline__ void sts64(uint32_t a, uint32_t x, uint32_t y) { asm volatile("st.shared.v2.b32 [%0], {%1,%2};" ::"r"(a), "r"(x), "r"(y) : "memory"); }
__device__ __forceinline__ void conv_sums(const SumAddr& sa, int lc, int c) {
  uint32_t e[4], o[4];
  {
    const float2 em = lds64f(sa.l1 + lc * 32768), om = lds64f(sa.l1 + lc * 32768 + CV_UH);
    e[0] = lds32(sa.l0 + lc * 32768); o[0] = lds32(sa.l0 + lc * 32768 + CV_UH);
    e[3] = lds32(sa.l2 + lc * 32768); o[3] = lds32(sa.l2 + lc * 32768 + CV_UH);
    e[1] = __float_as_uint(em.x); e[2] = __float_as_uint(em.y); o[1] = __float_as_uint(om.x); o[2] = __float_as_uint(om.y);
  }
  uint32_t s7e[2], s7o[2], s9e[2], s9o[2];
  uint32_t pw[4], sh[3];
#pragma unroll
  for (int k = 0; k < 4; k++) pw[k] = hadd2(e[k], o[k]);
#pragma unroll
  for (int k = 0; k < 3; k++) sh[k] = __byte_perm(pw[k], pw[k + 1], 0x5432);
#pragma unroll
  for (int k = 0; k < 2; k++) {
    const uint32_t t3 = hadd2(hadd2(sh[k], sh[k + 1]), pw[k + 1]);
    s7e[k] = hadd2(t3, o[k]); s7o[k] = hadd2(t3, e[k + 2]);
    s9e[k] = hadd2(s7o[k], pw[k]); s9o[k] = hadd2(s7e[k], pw[k + 2]);
  }
  if (c == 127) s9e[0] = s9e[1] = s9o[0] = s9o[1] = 0u;
  sts64(sa.se + lc * 32768, s9e[0], s9e[1]); sts64((sa.se ^ 16) + lc * 32768, s9o[0], s9o[1]);
  sts64(sa.so + lc * 32768, s7e[0], s7e[1]); sts64((sa.so ^ 16) + lc * 32768, s7o[0], s7o[1]);
}

__device__ __forceinline__ void conv_epi(uint32_t sb, int layer, int cta, int ch, int c0, uint4 x0, uint4 x1) {
  uint4 v[2][4];
  const uint4 xr[2] = {x0, x1};
  mbar_wait(sb + SM_BAR + 8 * (B_P + ch), layer);
#pragma unroll
  for (int u = 0; u < 2; u++) {
    const uint32_t pb = sb + cv_pb(ch) + u * (CV_PBW / 2) + c0 * 16;
#pragma unroll
    for (int k = 0; k < 4; k++) v[u][k] = lds128(pb + k * CV_PBW);
  }
#pragma unroll
  for (int u = 0; u < 2; u++) {
    uint4 o;
    o.x = hadd2(xr[u].x, hadd2(hadd2(v[u][0].x, v[u][1].x), hadd2(v[u][2].x, v[u][3].x)));
    o.y = hadd2(xr[u].y, hadd2(hadd2(v[u][0].y, v[u][1].y), hadd2(v[u][2].y, v[u][3].y)));
    o.z = hadd2(xr[u].z, hadd2(hadd2(v[u][0].z, v[u][1].z), hadd2(v[u][2].z, v[u][3].z)));
    o.w = hadd2(xr[u].w, hadd2(hadd2(v[u][0].w, v[u][1].w), hadd2(v[u][2].w, v[u][3].w)));
    if (layer == 0) sts128(sb + cv_s(ch) + (c0 + 128 * u) * 16, o);
    else st_tagged3((uint4*)(g_xT + (size_t)(3 * DM + cv_chan(cta, ch)) * LSEQ) + c0 + 128 * u, o.x, o.y, o.z, o.w);
  }
}
__device__ __forceinline__ void warp_release(uint32_t b) {
  fence_writer();
  __syncwarp();
  if (elect_one()) mbar_arrive(b);
}

__device__ __forceinline__ void conv_prep_load(uint32_t sb, int layer, int cta, int c, uint4 (&xr)[4], uint4 (&st)[4]) {
  sched_fence<8>();
  mbar_wait(sb + SM_BAR + 8 * B_GB, layer);
  if (threadIdx.x == 0) TS(2 + layer * 20 + 11);
  xr[0] = ld_tagged((const uint4*)(g_xT + (size_t)(2 * layer * DM + cta) * LSEQ) + c);
#pragma unroll
  for (int i = 0; i < 2; i++) st[i] = ld_tagged((const uint4*)g_stats + layer * 512 + (c >> 5) * 64 + i * 32 + (c & 31));
}
template <bool HELPER>
__device__ __forceinline__ void conv_prep(uint32_t sb, int layer, int cta, int c, uint4 (&xr)[4], uint4 (&st)[4], const SumAddr& sa) {
  const uint32_t bar = sb + SM_BAR;
  const uint4* xin = (const uint4*)(g_xT + (size_t)(2 * layer * DM + cta) * LSEQ) + c;
  for (int it = 0;; it++) {
    const uint32_t vs = min(min(min(st[0].x, st[0].y), min(st[0].z, st[0].w)), min(min(st[1].x, st[1].y), min(st[1].z, st[1].w)));
    if (__all_sync(~0u, vs != 0 && xr[0].x != ~0u)) break;
    if (it > (1 << 22)) __trap();
    if (!__all_sync(~0u, xr[0].x != ~0u)) xr[0] = ld_tagged(xin);
    if (!__all_sync(~0u, vs != 0)) {
#pragma unroll
      for (int i = 0; i < 2; i++) st[i] = ld_tagged((const uint4*)g_stats + layer * 512 + (c >> 5) * 64 + i * 32 + (c & 31));
    }
  }
  const uint32_t nm[4] = {__byte_perm(st[0].x, st[0].y, 0x5410), __byte_perm(st[0].z, st[0].w, 0x5410), __byte_perm(st[1].x, st[1].y, 0x5410), __byte_perm(st[1].z, st[1].w, 0x5410)};
  const uint32_t rs[4] = {__byte_perm(st[0].x, st[0].y, 0x7632), __byte_perm(st[0].z, st[0].w, 0x7632), __byte_perm(st[1].x, st[1].y, 0x7632), __byte_perm(st[1].z, st[1].w, 0x7632)};
  if (threadIdx.x == 0) TS(2 + layer * 20 + 12);
  const int a = c & 127, h = c >> 7;
#pragma unroll
  for (int i = 0; i < 4; i++) {
    if (i == 1) {
      mbar_wait(bar + 8 * B_XV, layer);
#pragma unroll
      for (int j = 1; j < 4; j++) xr[j] = ld_tagged(xin + j * (128 * LSEQ / 8));
      if (HELPER) {
        mbar_wait(bar + 8 * B_U, layer);
        conv_sums(sa, 0, c);
        fence_async_smem();
        bar_arrive(7, 256);
        sched_fence<1>();
        if (layer == 1 && c == 0) TS(46);
      }
    }
    const uint32_t x[4] = {xr[i].x, xr[i].y, xr[i].z, xr[i].w};
    uint32_t u[4];
#pragma unroll
    for (int k = 0; k < 4; k++)
      u[k] = NORM_FMA ? hfma2(x[k], rs[k], nm[k]) : hmul2(hadd2(x[k], nm[k]), rs[k]);
    sts128(sb + cv_u(i) + h * CV_UH + (127 - a) * 16, make_uint4(u[0], u[1], u[2], u[3]));
    warp_release(bar + 8 * (B_U + i));
    sched_fence<2>();
  }
}
__device__ __forceinline__ void conv_zero(uint32_t sb, int ht) {
  if (ht < 96) {
    const int ch = ht / 24, h2 = (ht / 12) & 1, qq = ht % 12;
    sts128(sb + cv_u(ch) + h2 * CV_UH + (128 + qq) * 16, make_uint4(0, 0, 0, 0));
  }
  if (ht >= 80) {
    const int i = ht - 80, ch = i / 12, q2 = i % 12;
    const int w2 = q2 < 2 ? 1 : q2 < 6 ? 2 : 3, cc = q2 < 2 ? q2 : q2 < 6 ? q2 - 2 : q2 - 6;
    sts128(sb + cv_pb(ch) + w2 * CV_PBW + (cc & 1) * (CV_PBW / 2) + (cc >> 1) * 16, make_uint4(0, 0, 0, 0));
  }
}

#define HANDOVER 1
template <int R>
__device__ __forceinline__ void conv_round(uint32_t sb, int layer, int wg, uint32_t* A, const uint32_t* P, uint32_t pb, uint32_t pe2) {
  const uint32_t bar = sb + SM_BAR;
  const int ch = 2 * R + 1 - wg;
  float acc[64];
  const uint64_t d = mkdesc(sb + cv_u(ch), CV_UH, 128, 0);
  FTS(39);
  if (R == 0) {
    mbar_wait(bar + 8 * (B_U + ch), layer);
    fence_reader();
  }
  sched_fence<3>();
  if (R == 1 || wg == 0) bar_sync(10 + ch, 256);
  if (layer == 0 && ch > 0 && ((PAUSE >> (ch - 1)) & 1)) mbar_wait(bar + 8 * (B_E + ch - 1), 0);
  if (layer == 0 && ch > 0 && ((PAUSE >> (ch + 3)) & 1)) mbar_wait(bar + 8 * (B_P + ch - 1), 0);
  FTS(41);
  if (ch == 0 && threadIdx.x == 128) TS(2 + layer * 20 + 13);
  wg_fence();
  conv_mmas<0, 1>(acc, A, d); conv_mmas<2, NA + 1>(acc, A, d);
  wg_commit();
  FTS(51);
  if (HANDOVER == 0 && (R == 0 || wg == 1)) bar_arrive(11 + ch, 256);
  bar_sync(7 + ch, 256);
  wg_fence();
  conv_mmas<1, 2>(acc, A, d); conv_mmas<NA + 1, 17>(acc, A, d);
  wgmma_ss<64, 1, 1>(acc, mkdesc(sb + cv_s(ch), 1024, 1024, 1), mkdesc(sb + cv_ft(ch), 256, 16, 0), 1);
  wgmma_ss<64, 1, 1>(acc, mkdesc(sb + cv_s(ch) + 2048, 1024, 1024, 1), mkdesc(sb + cv_ft(ch) + 512, 256, 16, 0), 1);
  wg_commit();
  if (HANDOVER == 1 && (R == 0 || wg == 1 || (G_WAIT == 3 && layer == 0))) bar_arrive(11 + ch, 256);
  FTS(61);
  wg_wait<0>();
#pragma unroll
  for (int j = 0; j < 16; j += 2)
    stsm4t(pb + R * 65536 - j * 128, packbf(acc[4 * j], acc[4 * j + 1]), packbf(acc[4 * j + 2], acc[4 * j + 3]),
           packbf(acc[4 * j + 4], acc[4 * j + 5]), packbf(acc[4 * j + 6], acc[4 * j + 7]));
  __syncwarp();
  if (elect_one()) mbar_arrive(bar + 8 * (B_P + ch));
  if (threadIdx.x == 0) TS(2 + layer * 20 + 14 + R);
  FTS(57);
  if (R == 0) {
    conv_unpark(A, P, opaque_tid() >> 10);
    mbar_wait(bar + 8 * (B_U + ch + 2), layer);
    fence_reader();
    conv_load<NP, 17>(A, pe2);
#pragma unroll
    for (int m = NP; m < 17; m++) A[4 * m + 3] = lds32(pe2 + 256 * m);
  }
}
__device__ __forceinline__ void conv_phase(const Params& p, uint32_t sb, int layer, int cta) {
  const int tid = opaque_tid();
  const int wg = __shfl_sync(~0u, tid >> 7, 0), w = __shfl_sync(~0u, (tid >> 5) & 3, 0);
  const uint32_t bar = sb + SM_BAR;
  uint32_t A[68], P[3 * NP];
  const uint32_t pe = sb + cv_pe(1 - wg) + 4 * (16 + 16 * w + 2 * ((tid & 31) >> 2) - 4 * (tid & 3));
  mbar_wait(bar + 8 * B_PE, layer);
  conv_load<0, 17>(A, pe);
#pragma unroll
  for (int m = 0; m < 17; m++) A[4 * m + 3] = copy_reg(A[4 * m], tid >> 10);
  if (wg == 0) {
    uint4 xr[4], st[4];
    if (PARK_FIRST) conv_park(P, pe + 65536);
    conv_prep_load(sb, layer, cta, tid + 128, xr, st);
    if (!PARK_FIRST) conv_park(P, pe + 65536);
    conv_prep<false>(sb, layer, cta, opaque_tid() + 128, xr, st, SumAddr());
  } else {
    conv_park(P, pe + 65536);
  }
  uint32_t pb;
  {
    const int l2 = opaque_tid() & 31, mt = l2 >> 3;
    pb = sb + cv_pb(1 - wg) + w * CV_PBW + (mt & 1) * (CV_PBW / 2) + (127 - 8 * (mt >> 1) - (l2 & 7) + w) * 16;
  }
  conv_round<0>(sb, layer, wg, A, P, pb, pe + 65536);
  conv_round<1>(sb, layer, wg, A, P, pb, 0);
  if (G_WAIT == 1 && layer == 0) mbar_wait(bar + 8 * (B_E + 3), layer);
  if (G_WAIT == 2 && layer == 0) mbar_wait(bar + 8 * (B_P + 3), layer);
}

__device__ __forceinline__ void final_phase(const Params& p, uint32_t sb, int cta, int wg, int w) {
  if (wg == 1 && w == 3) return;
  const int lane = opaque_tid() & 31, g = lane >> 2, t = lane & 3;
  const int lc = wg ? w : 3;
  const int pos0 = (cta & 31) * 64, ch0 = 128 * lc + (cta >> 5) * 32;
  const bf16* src = g_xT + (size_t)(3 * DM + ch0 + 8 * (g >> 1) + (g & 1)) * LSEQ + pos0;
  bf16* dst = p.out + (size_t)(2 * (pos0 & 1023) + (pos0 >> 10)) * DM + ch0 + 8 * t;
  constexpr int RS = 2 * DM;
  int it = 0;
  mbar_wait(sb + SM_BAR + 8 * (B_E + lc), 1);
  delay<D_FIN>();
  if (wg == 0) {
    uint2 v[4];
    for (;;) {
#pragma unroll
      for (int q = 0; q < 4; q++) v[q] = ld_part((const uint2*)(src + 2 * q * LSEQ + 16 * w + 4 * t));
      if (__all_sync(~0u, max(max(v[0].x, v[1].x), max(v[2].x, v[3].x)) != ~0u)) break;
      if (++it > (1 << 22)) __trap();
    }
    if (threadIdx.x == 0) TS(42);
    dst += (16 * w + 4 * (g >> 1) + (g & 1)) * RS;
    *(uint4*)dst = make_uint4(movm_t(v[0].x), movm_t(v[1].x), movm_t(v[2].x), movm_t(v[3].x));
    *(uint4*)(dst + 2 * RS) = make_uint4(movm_t(v[0].y), movm_t(v[1].y), movm_t(v[2].y), movm_t(v[3].y));
  } else {
    uint4 v[2][4];
    bool ok;
    do {
      ok = true;
#pragma unroll
      for (int h = 0; h < 2; h++)
#pragma unroll
        for (int q = 0; q < 4; q++) v[h][q] = ld_tagged((const uint4*)(src + 2 * q * LSEQ + 32 * h + 8 * t));
#pragma unroll
      for (int h = 0; h < 2; h++)
#pragma unroll
        for (int q = 0; q < 4; q++) ok = ok && v[h][q].x != ~0u;
      if (++it > (1 << 22)) __trap();
    } while (!__all_sync(~0u, ok));
    dst += (8 * (g >> 1) + (g & 1)) * RS;
#pragma unroll
    for (int h = 0; h < 2; h++) {
      *(uint4*)(dst + (32 * h + 0) * RS) = make_uint4(movm_t(v[h][0].x), movm_t(v[h][1].x), movm_t(v[h][2].x), movm_t(v[h][3].x));
      *(uint4*)(dst + (32 * h + 2) * RS) = make_uint4(movm_t(v[h][0].y), movm_t(v[h][1].y), movm_t(v[h][2].y), movm_t(v[h][3].y));
      *(uint4*)(dst + (32 * h + 4) * RS) = make_uint4(movm_t(v[h][0].z), movm_t(v[h][1].z), movm_t(v[h][2].z), movm_t(v[h][3].z));
      *(uint4*)(dst + (32 * h + 6) * RS) = make_uint4(movm_t(v[h][0].w), movm_t(v[h][1].w), movm_t(v[h][2].w), movm_t(v[h][3].w));
    }
  }
  if (threadIdx.x == 0) TS(43);
  if (threadIdx.x == 192) TS(63);
  if (threadIdx.x == 0) LTS(1);
}

struct cplx { float r, i; };
__device__ __forceinline__ cplx cmul(cplx a, cplx b) { return {fmaf(a.r, b.r, -a.i * b.i), fmaf(a.r, b.i, a.i * b.r)}; }
__device__ __forceinline__ cplx csqr(cplx a) { return {fmaf(a.r, a.r, -a.i * a.i), (a.r + a.r) * a.i}; }
__device__ __forceinline__ cplx cexp_l(float ar2, float ai, float l) {
  const float m = ex2(ar2 * l);
  const float x = ai * l;
  return {m * __cosf(x), m * __sinf(x)};
}

__device__ __forceinline__ void colsum_publish(uint32_t sb, int rb, int hg, int ht, uint32_t tag) {
  const int lane = ht & 31, q = lane & 15, h = lane >> 4;
  const uint32_t src = sb + SM_CW + (ht >> 5) * 4096 + h * 128 + (q & 1) * 8;
  float s[4] = {0.f, 0.f, 0.f, 0.f};
#pragma unroll 8
  for (int r = 0; r < 16; r++) {
    const float2 v = lds64f(src + r * 256 + (((q >> 1) ^ ((2 * r + h) & 7)) << 4));
    s[0] += bf_lo(__float_as_uint(v.x)); s[1] += bf_hi(__float_as_uint(v.x));
    s[2] += bf_lo(__float_as_uint(v.y)); s[3] += bf_hi(__float_as_uint(v.y));
  }
#pragma unroll
  for (int k = 0; k < 4; k++) s[k] += __shfl_xor_sync(~0u, s[k], 16);
  if (h == 0)
    st_tagged3(&g_colsum[(hg * 16 + rb) * 48 + (ht >> 5) * 16 + q], (__float_as_uint(s[0]) & ~7u) | tag, __float_as_uint(s[1]),
               __float_as_uint(s[2]), __float_as_uint(s[3]));
}
__device__ __forceinline__ void colsum_gather(uint32_t sb, int hg, int ht, uint32_t tag) {
  const int lane = ht & 31, rec = (ht >> 5) * 16 + (lane & 15);
  const uint4* src = &g_colsum[(hg * 16 + (lane >> 4) * 8) * 48 + rec];
  float s[4] = {0.f, 0.f, 0.f, 0.f};
#pragma unroll 1
  for (int h = 0; h < 2; h++, src += 4 * 48) {
    uint4 v[4];
    int it = 0;
    do {
#pragma unroll
      for (int i = 0; i < 4; i++) v[i] = ld_tagged(src + i * 48);
      if (++it > (1 << 22)) __trap();
    } while (!__all_sync(~0u, (v[0].x & 7u) == tag && (v[1].x & 7u) == tag && (v[2].x & 7u) == tag && (v[3].x & 7u) == tag));
#pragma unroll
    for (int i = 0; i < 4; i++) {
      s[0] += __uint_as_float(v[i].x & ~7u); s[1] += __uint_as_float(v[i].y); s[2] += __uint_as_float(v[i].z); s[3] += __uint_as_float(v[i].w);
    }
  }
#pragma unroll
  for (int k = 0; k < 4; k++) s[k] += __shfl_xor_sync(~0u, s[k], 16);
  if (lane < 16) sts128f(sb + SM_CS + rec * 16, s[0], s[1], s[2], s[3]);
}

__device__ __forceinline__ uint32_t packh(float lo, float hi) { uint32_t r; asm("cvt.rn.f16x2.f32 %0, %1, %2;" : "=r"(r) : "f"(hi), "f"(lo)); return r; }
__device__ __forceinline__ void mma_f16(float* d, uint32_t a0, uint32_t a1, uint32_t a2, uint32_t a3, uint32_t b0, uint32_t b1) {
  asm volatile("mma.sync.aligned.m16n8k16.row.col.f32.f16.f16.f32 {%0,%1,%2,%3}, {%4,%5,%6,%7}, {%8,%9}, {%0,%1,%2,%3};"
      : "+f"(d[0]), "+f"(d[1]), "+f"(d[2]), "+f"(d[3]) : "r"(a0), "r"(a1), "r"(a2), "r"(a3), "r"(b0), "r"(b1));
}
struct HSeed { uint32_t r, i; };
__device__ __forceinline__ HSeed hseed(cplx s) { return {packh(s.r, s.r), packh(s.i, s.i)}; }
__device__ __forceinline__ void hcmul(uint32_t& o_r, uint32_t& o_i, uint32_t br, uint32_t bi, HSeed s) {
  asm("{\n.reg .b32 t, u;\nmul.rn.f16x2 t, %3, %5;\nneg.f16x2 t, t;\nmul.rn.f16x2 u, %3, %4;\nfma.rn.f16x2 %0, %2, %4, t;\nfma.rn.f16x2 %1, %2, %5, u;\n}"
      : "=&r"(o_r), "=&r"(o_i) : "r"(br), "r"(bi), "r"(s.r), "r"(s.i));
}
struct HTile { uint32_t r[4], i[4]; };
__device__ __forceinline__ void tile_set(HTile& t, int k, cplx a, cplx b) { t.r[k] = packh(a.r, b.r); t.i[k] = packh(a.i, b.i); }
__device__ __forceinline__ void tile_upper(HTile& t, HSeed s) { hcmul(t.r[2], t.i[2], t.r[0], t.i[0], s); hcmul(t.r[3], t.i[3], t.r[1], t.i[1], s); }
__device__ __forceinline__ HTile tile_shift(const HTile& t, HSeed s) {
  HTile o;
#pragma unroll
  for (int k = 0; k < 4; k++) hcmul(o.r[k], o.i[k], t.r[k], t.i[k], s);
  return o;
}
__device__ __forceinline__ void tile_put(const HTile& t, uint32_t a) {
  sts128(a, make_uint4(t.r[0], t.r[1], t.r[2], t.r[3]));
  sts128(a + 512, make_uint4(t.i[0], t.i[1], t.i[2], t.i[3]));
}
__device__ __forceinline__ HTile tile_get(uint32_t a) { HTile o; ldsm4t(o.r, a); ldsm4t(o.i, a + 512); return o; }
__device__ __forceinline__ void tile_mma(float* T, const HTile& a0, const HTile& a1, const HTile& b) {
  mma_f16(T, a0.r[0], a0.r[1], a0.r[2], a0.r[3], b.r[0], b.r[1]);
  mma_f16(T, a0.i[0], a0.i[1], a0.i[2], a0.i[3], b.i[0], b.i[1]);
  mma_f16(T, a1.r[0], a1.r[1], a1.r[2], a1.r[3], b.r[2], b.r[3]);
  mma_f16(T, a1.i[0], a1.i[1], a1.i[2], a1.i[3], b.i[2], b.i[3]);
}
__device__ __forceinline__ void tile_mma2(float* T, float* U, const HTile& a0, const HTile& a1, const HTile& b, const HTile& c) {
  mma_f16(T, a0.r[0], a0.r[1], a0.r[2], a0.r[3], b.r[0], b.r[1]);
  mma_f16(U, a0.r[0], a0.r[1], a0.r[2], a0.r[3], c.r[0], c.r[1]);
  mma_f16(T, a0.i[0], a0.i[1], a0.i[2], a0.i[3], b.i[0], b.i[1]);
  mma_f16(U, a0.i[0], a0.i[1], a0.i[2], a0.i[3], c.i[0], c.i[1]);
  mma_f16(T, a1.r[0], a1.r[1], a1.r[2], a1.r[3], b.r[2], b.r[3]);
  mma_f16(U, a1.r[0], a1.r[1], a1.r[2], a1.r[3], c.r[2], c.r[3]);
  mma_f16(T, a1.i[0], a1.i[1], a1.i[2], a1.i[3], b.i[2], b.i[3]);
  mma_f16(U, a1.i[0], a1.i[1], a1.i[2], a1.i[3], c.i[2], c.i[3]);
}
__device__ __forceinline__ void kgen_unit(uint32_t tab, uint32_t taba, float ar2, float ai, cplx c, float (&T)[5][4]) {
  const cplx z1 = cexp_l(ar2, ai, 1.f), z16 = cexp_l(ar2, ai, 16.f), z256 = cexp_l(ar2, ai, 256.f);
  HTile a0, a1, b0, b1;
  {
    const cplx y1 = {z16.r, -z16.i}, y2 = csqr(y1), y3 = cmul(y2, y1), y4 = csqr(y2), y5 = cmul(y4, y1), y6 = csqr(y3), y7 = cmul(y4, y3);
    HTile t;
    tile_set(t, 0, {1.f, 0.f}, y1); tile_set(t, 1, y2, y3); tile_set(t, 2, y4, y5); tile_set(t, 3, y6, y7);
    const HTile u = tile_shift(t, hseed(csqr(y4)));
    __syncwarp();
    tile_put(t, tab); tile_put(u, tab + 1024);
    __syncwarp();
    a0 = tile_get(taba); a1 = tile_get(taba + 256);
  }
  const cplx z2 = csqr(z1), z4 = csqr(z2), z8 = csqr(z4);
  const HSeed h8 = hseed(z8);
  const cplx d = cmul(c, z256), e = cmul(d, z256);
  {
    const cplx z512 = csqr(z256), f = cmul(e, z512), f8 = cmul(f, z8), f16 = cmul(f, z16), e4 = cmul(e, z4);
    HTile t, u;
    tile_set(t, 0, e4, cmul(e, z8)); tile_set(t, 1, cmul(e4, z8), cmul(e, z16));
    tile_upper(t, hseed(z256));
    tile_set(u, 0, f8, f16); tile_set(u, 1, cmul(f8, z256), cmul(f16, z256));
    tile_upper(u, hseed(z512));
    __syncwarp();
    tile_put(t, tab); tile_put(u, tab + 1024);
    __syncwarp();
    b0 = tile_get(tab); b1 = tile_get(tab + 1024);
  }
  {
    const cplx d2 = cmul(d, z2), d4 = cmul(d, z4);
    HTile t;
    tile_set(t, 0, d2, d4); tile_set(t, 1, cmul(d2, z4), cmul(d, z8));
    tile_upper(t, h8);
    __syncwarp();
    tile_put(t, tab);
    __syncwarp();
    tile_mma2(T[3], T[4], a0, a1, b0, b1);
    b0 = tile_get(tab);
  }
  {
    const cplx c1 = cmul(c, z1), c2 = cmul(c, z2), c3 = cmul(c1, z2), c4 = cmul(c, z4);
    HTile t;
    tile_set(t, 0, c1, c2); tile_set(t, 1, c3, c4); tile_set(t, 2, cmul(c1, z4), cmul(c2, z4)); tile_set(t, 3, cmul(c3, z4), cmul(c4, z4));
    const HTile u = tile_shift(t, h8);
    __syncwarp();
    tile_put(t, tab); tile_put(u, tab + 1024);
    __syncwarp();
    tile_mma(T[2], a0, a1, b0);
    b0 = tile_get(tab); b1 = tile_get(tab + 1024);
    tile_mma2(T[0], T[1], a0, a1, b0, b1);
  }
}
struct ModeIn { uint2 ar, ai, br, bi, cr, ci; };
__device__ __forceinline__ ModeIn load_modes(const Params& p, int idx) {
  return {*(const uint2*)(p.a_re + idx), *(const uint2*)(p.a_im + idx), *(const uint2*)(p.b_re + idx),
          *(const uint2*)(p.b_im + idx), *(const uint2*)(p.c_re + idx), *(const uint2*)(p.c_im + idx)};
}
__device__ __forceinline__ float bf_el(uint2 v, int k) { const uint32_t x = (k & 2) ? v.y : v.x; return (k & 1) ? bf_hi(x) : bf_lo(x); }
struct KGen { float4 cur; float T[5][4]; };
__device__ __forceinline__ uint32_t kgen_slot(uint32_t sb, int ht, int u) {
  return sb + (u < 3 ? SM_KC + (ht >> 5) * (KC_STRIDE * 2) + (u - 1) * 512 + (ht & 31) * 16 + 16 : SM_HALO + 1024 + ht * 16);
}
__device__ __forceinline__ void kgen_setup(KGen& s, uint32_t sb, int cta, int ht, const ModeIn& in, bf16 logdt, bf16 dskip) {
  const float dt = __bfloat162float(__float2bfloat16_rn(expf(__bfloat162float(logdt))));
  float mx = 0.f, k0 = 0.f, ar2[4];
  cplx c[4];
#pragma unroll
  for (int k = 0; k < 4; k++) {
    ar2[k] = (dt * bf_el(in.ar, k)) * 1.4426950408889634f;
    c[k] = cmul({bf_el(in.cr, k), bf_el(in.ci, k)}, {dt * bf_el(in.br, k), dt * bf_el(in.bi, k)});
    k0 += c[k].r;
    mx = fmaxf(mx, fmaxf(fabsf(c[k].r), fabsf(c[k].i)) * ex2(fmaxf(ar2[k] * 2048.f, 0.f)));
  }
  const int ex = min(max(267 - (int)(__reduce_max_sync(~0u, __float_as_uint(mx)) >> 23), 1), 253);
  const float sc = __uint_as_float(ex << 23);
#pragma unroll
  for (int o = 16; o > 0; o >>= 1) k0 += __shfl_xor_sync(~0u, k0, o);
  if ((ht & 31) == 0) {
    const uint32_t kc = sb + SM_KC + (ht >> 5) * (KC_STRIDE * 2);
    sts16(kc, __bfloat16_as_ushort(__float2bfloat16_rn(k0 + __bfloat162float(dskip))));
    sts16(kc + 641 * 2, 0);
    sts32f(kc + 644 * 2, __uint_as_float((254 - ex) << 23));
  }
  s.cur = make_float4(ar2[0], dt * bf_el(in.ai, 0), c[0].r * sc, c[0].i * sc);
#pragma unroll
  for (int k = 1; k < 4; k++) sts128f(kgen_slot(sb, ht, k), ar2[k], dt * bf_el(in.ai, k), c[k].r * sc, c[k].i * sc);
#pragma unroll
  for (int i = 0; i < 5; i++) s.T[i][0] = s.T[i][1] = s.T[i][2] = s.T[i][3] = 0.f;
}
__device__ __forceinline__ void kgen_finish(KGen& s, uint32_t sb, int cta, int ht) {
  const int w = ht >> 5, lane = ht & 31, g = lane >> 2, t = lane & 3;
  const uint32_t kc = sb + SM_KC + w * KC_STRIDE * 2;
  __syncwarp();
  const float inv = __uint_as_float(lds32(kc + 644 * 2));
  auto put = [&](int idx, float v) {
    sts16(kc + idx * 2, __bfloat16_as_ushort(__float2bfloat16_rn(v)));
  };
#pragma unroll
  for (int hi = 0; hi < 2; hi++)
#pragma unroll
    for (int lo = 0; lo < 2; lo++) {
      const int i = g + 8 * hi, j = 2 * t + lo, e = 2 * hi + lo;
      put(16 * i + 1 + j, s.T[0][e] * inv);
      put(16 * i + 9 + j, s.T[1][e] * inv);
      put(257 + 8 * i + j, s.T[2][e] * inv);
      put(385 + 4 * i + (j & 3) + 64 * (j >> 2), s.T[3][e] * inv);
      put(513 + 2 * i + lo + 32 * t, s.T[4][e] * inv);
    }
}

__device__ __forceinline__ void expand_taps(uint32_t sb, int ht) {
  const int ch = ht >> 5, lane = ht & 31;
  const uint32_t kc = sb + SM_KC + ch * KC_STRIDE * 2;
  const uint32_t dst0 = sb + cv_pe(ch);
  auto put = [&](int G, uint32_t u0, uint32_t u1, uint32_t v0, uint32_t v1, uint32_t v2, uint32_t v3, uint32_t v4, uint32_t v5, uint32_t v6, uint32_t v7) {
    const uint32_t dst = dst0 + G * 32;
    sts128(dst, make_uint4(v0 | (u0 << 16), v1 | (u1 << 16), v2 | (v0 << 16), v3 | (v1 << 16)));
    sts128(dst + 16, make_uint4(v4 | (v2 << 16), v5 | (v3 << 16), v6 | (v4 << 16), v7 | (v5 << 16)));
  };
  {
    const uint4 q = lds128(kc + lane * 16);
    const uint32_t pv = lane ? lds32(kc + lane * 16 - 4) : 0u;
    const uint32_t dst = dst0 + (lane + 2) * 32;
    sts128(dst, make_uint4(__byte_perm(q.x, pv, 0x5410), __byte_perm(q.x, pv, 0x7632), __byte_perm(q.y, q.x, 0x5410), __byte_perm(q.y, q.x, 0x7632)));
    sts128(dst + 16, make_uint4(__byte_perm(q.z, q.y, 0x5410), __byte_perm(q.z, q.y, 0x7632), __byte_perm(q.w, q.z, 0x5410), __byte_perm(q.w, q.z, 0x7632)));
    if (lane < 4) sts128(dst0 + lane * 16, make_uint4(0, 0, 0, 0));
  }
  uint32_t a[5], b[2][3], fv[4];
  {
    const uint32_t s1 = kc + 2 * (256 + 4 * lane);
#pragma unroll
    for (int k = 0; k < 5; k++) a[k] = lds16(s1 + 2 * k);
#pragma unroll
    for (int u = 0; u < 2; u++) {
      const uint32_t s2 = kc + 2 * (384 + 2 * (lane + 32 * u));
#pragma unroll
      for (int k = 0; k < 3; k++) b[u][k] = lds16(s2 + 2 * k);
    }
#pragma unroll
    for (int k = 0; k < 4; k++) fv[k] = lds16(kc + 2 * (640 - 4 * lane - k));
  }
  const uint32_t am1 = lds16(kc + 2 * (lane ? 256 + 4 * lane : 255)), am2 = lds16(kc + 2 * (lane ? 255 + 4 * lane : 254));
  const uint32_t bm2 = lds16(kc + 2 * (lane ? 384 + 2 * lane : 383)), k1024 = lds16(kc + 2 * 512);
  put(34 + lane, am2, am1, a[0], a[0], a[1], a[2], a[2], a[2], a[3], a[4]);
#pragma unroll
  for (int u = 0; u < 2; u++) put(66 + lane + 32 * u, u ? b[u][0] : bm2, b[u][0], b[u][0], b[u][0], b[u][0], b[u][1], b[u][1], b[u][1], b[u][2], b[u][2]);
  if (lane < 10) {
    const uint32_t v = lane == 0 ? k1024 : 0u;
    put(130 + lane, v, v, v, v, v, v, v, 0u, 0u, 0u);
  }
  const uint32_t ft = sb + cv_ft(ch) + 4 * lane;
#pragma unroll
  for (int ty = 0; ty < 2; ty++) {
    const uint32_t v = fv[ty] | (fv[ty + 2] << 16);
    sts32f(ft + ty * 512, __uint_as_float(v));
    sts32f(ft + ty * 512 + 128, 0.f);
    sts32f(ft + ty * 512 + 256 + (lane < 2 ? 120 : -8), __uint_as_float(lane < 2 ? 0u : v));
    sts32f(ft + ty * 512 + 384, 0.f);
  }
}

__device__ __forceinline__ int role_id() { int v; asm volatile("mov.u32 %0, %%ctaid.x;" : "=r"(v)); return v; }
#define GMAP 8
__device__ __forceinline__ int role_rb(int cta) { return 4 * (cta >> 5) + (cta & 3); }
__device__ __forceinline__ int role_hg(int cta) { return 2 * (((cta >> 3) & 3) ^ (((cta >> 5) & 1) * 3)) + ((cta >> 2) & 1); }
__device__ __forceinline__ int role_rb2(int cta) { return cta >> 3; }
__device__ __forceinline__ int role_q2(int cta) { return cta & 7; }

__global__ void __launch_bounds__(NTHREADS, 1) fused_kernel(const __grid_constant__ Params p) {
  extern __shared__ __align__(1024) uint8_t smem[];
  const uint32_t sb = s32(smem);
  const int tid = threadIdx.x, lane = tid & 31;
  const int warp = __shfl_sync(~0u, tid >> 5, 0);
  const uint32_t bar = sb + SM_BAR;
  if (tid == 0) TS(0);
  const int cta0 = role_id();
  if (warp == 0 && elect_one()) {
    const int rb = role_rb(cta0), hg = role_hg(cta0);
#pragma unroll
    for (int c = 0; c < 2; c++) { mbar_init(bar + 8 * (B_XF + c), 1); mbar_init(bar + 8 * (B_KVF + c), 1); }
    fence_async_smem();
#pragma unroll
    for (int c = 0; c < 2; c++) {
      mbar_expect(bar + 8 * (B_XF + c), 16384);
      tma_ld(sb + SM_X + c * 16384, &p.mapX128, (rb >> 3) * DM + c * 64, (rb & 7) * 128, bar + 8 * (B_XF + c));
      mbar_expect(bar + 8 * (B_KVF + c), 24576);
      tma_ld3(sb + SM_W + c * 24576, &p.mapW3, hg * 64, c * 64, 0, bar + 8 * (B_KVF + c));
    }
  }
  if (warp == 1 && elect_one()) {
    const int rb = role_rb(cta0), hg = role_hg(cta0);
#pragma unroll
    for (int c = 2; c < 8; c++) mbar_init(bar + 8 * (B_XF + c), 1);
    mbar_init(bar + 8 * (B_KVF + 2), 1); mbar_init(bar + 8 * B_CW, 1);
    fence_async_smem();
    delay<D_START>();
    mbar_expect(bar + 8 * B_CW, 12288);
    tma_ld3(sb + SM_CW, &p.mapW3h, hg * 64, rb * 32, 0, bar + 8 * B_CW);
#pragma unroll
    for (int c = 2; c < 8; c++) {
      mbar_expect(bar + 8 * (B_XF + c), 16384);
      tma_ld(sb + SM_X + c * 16384, &p.mapX128, (rb >> 3) * DM + c * 64, (rb & 7) * 128, bar + 8 * (B_XF + c));
      if (c < 3) {
        mbar_expect(bar + 8 * (B_KVF + c), 24576);
        tma_ld3(sb + SM_W + c * 24576, &p.mapW3, hg * 64, c * 64, 0, bar + 8 * (B_KVF + c));
      }
    }
    TS(56);
  }
  if ((warp & 2) != 0 && warp < 15 && elect_one()) {
    const int grp = 1 + (warp & 1) + 2 * (warp >> 2), cnt = grp < 4 ? 1 : grp < 5 ? 2 : grp < 7 ? 4 : 8;
#pragma unroll
    for (int k = 0; k < 10; k++)
      if (k != 0 || grp > 3 || grp == 2) mbar_init(bar + 8 * (10 * grp + k), cnt);
    fence_async_smem();
  }

  if (warp < 8) {
    if (tid == 0) TS(1);
    asm volatile("setmaxnreg.inc.sync.aligned.u32 %0;" ::"n"(R_CONS));
    const int cta = role_id();
    auto warp_id = [] { return __shfl_sync(~0u, opaque_tid() >> 5, 0); };
    if (tid == 0) TS(54);
#pragma unroll 1
    for (int layer = 0; layer < 2; layer++) {
      { const int cw = warp_id(); attn_phase(p, sb, layer, role_rb(cta), role_hg(cta), cw >> 2, cw & 3); }
      if (STOP == 1 + 3 * layer) return;
      { const int cw = warp_id(); proj_phase(p, sb, layer, role_rb2(cta), role_q2(cta), cw >> 2, cw & 3); }
      if (STOP == 2 + 3 * layer) return;
      conv_phase(p, sb, layer, cta);
      if (STOP == 3 + 3 * layer) return;
    }
    { const int cw = warp_id(); final_phase(p, sb, cta, cw >> 2, cw & 3); }
  } else if (warp < 12) {
    asm volatile("setmaxnreg.dec.sync.aligned.u32 %0;" ::"n"(R_HELP));
    const int ht = tid - 256;
    const int cta = role_id(), rb = role_rb(cta), hg = role_hg(cta);
    unsigned ep0 = 0;
    if (ht == 0) ep0 = ld_relaxed(&g_cnt[C_CS * 32]);
    bar_sync(0, NTHREADS);
    if (ht == 0) {
      asm volatile("st.shared.u32 [%0], %1;" ::"r"(sb + SM_EP), "r"(ep0 / NCTA) : "memory");
      mbar_arrive(bar + 8 * B_EP);
    }
    mbar_wait(bar + 8 * B_EP, 0);
    stats_publish(sb, 0, rb, hg, opaque_tid() - 256, part_tag(lds32(sb + SM_EP), 0));
    if (ht < 48) {
      const bf16* q = (&p.a_re)[ht >> 3];
      asm volatile("prefetch.global.L2 [%0];" ::"l"(q + cv_chan(cta, (ht >> 1) & 3) * 128 + (ht & 1) * 64));
    }
    {
      KGen kg;
      const uint32_t tab0 = sb + ((ht >> 5) < 2 ? SM_T : SM_T2 - 4096) + (ht >> 5) * 2048;
      const uint32_t tab = tab0 + (ht & 31) * 16, taba = tab0 + ((ht >> 3) & 1) * 1024 + (((ht >> 1) & 8) + (ht & 7)) * 16;
      delay<D_ST0>();
      stats_gather(sb, rb, opaque_tid() - 256, part_tag(lds32(sb + SM_EP), 0));
      if (ht == 0) TS(40);
      const int chn = cv_chan(cta, ht >> 5);
      const ModeIn modes = load_modes(p, chn * 128 + (ht & 31) * 4);
      const bf16 logdt = p.log_dt[chn], dskip = p.dskip[chn];
      if (!HALO_W14 && KG_START != 4) halo_receive(sb, 0, rb, hg, opaque_tid() - 256);
      if (KG_START == 1) mbar_wait(bar + 8 * B_HF, 0);
      kgen_setup(kg, sb, cta, ht, modes, logdt, dskip);
      if (!HALO_W14 && KG_START == 4) halo_receive(sb, 0, rb, hg, opaque_tid() - 256);
      if (KG_START == 2) mbar_wait(bar + 8 * B_HF, 0);
      if (KG_START == 3) mbar_wait(bar + 8 * B_QDONE, 0);
#pragma unroll 1
      for (int u = 0; u < 4; u++) {
        if (u == KG_PRE) {
          KTS(39);
          mbar_wait(bar + 8 * B_AD, 0);
          KTS(41);
        }
        kgen_unit(tab, taba, kg.cur.x, kg.cur.y, {kg.cur.z, kg.cur.w}, kg.T);
        kg.cur = lds128f(kgen_slot(sb, opaque_tid() - 256, u + 1));
      }
      kgen_finish(kg, sb, cta, opaque_tid() - 256);
    }
    KTS(51);
    bar_sync(4, 128);
#pragma unroll 1
    for (int layer = 0; layer < 2; layer++) {
      if (STOP <= 1 + 3 * layer) return;
      mbar_wait(bar + 8 * (EXP_LATE ? B_PS : B_PDONE), layer);
      expand_taps(sb, opaque_tid() - 256);
      conv_zero(sb, opaque_tid() - 256);
      if (ht == 0) TS(52 + layer);
      warp_release(bar + 8 * B_PE);
      if (STOP <= 2 + 3 * layer) return;
      {
        uint4 xr[4], st[4];
        const int c = opaque_tid() - 256;
        const SumAddr sa = conv_sum_addr(sb, c);
        conv_prep_load(sb, layer, cta, c, xr, st);
        conv_prep<true>(sb, layer, cta, c, xr, st, sa);
        if (layer == 1 && ht == 0) TS(62);
        const bf16* xup = g_xT + (size_t)(2 * layer * DM + cta) * LSEQ + (c + 128) * 8;
        const int ahead = layer ? S_AHEAD1 : S_AHEAD0;
        mbar_wait(bar + 8 * (B_U + 3), layer);
        if (ahead == 2) {
          conv_sums(sa, 1, c);
          fence_async_smem();
          bar_arrive(8, 256);
        }
        st[0] = ldcg128(xup);
#pragma unroll
        for (int lc = 0; lc < 4; lc++) {
          if (lc < 3 && lc + ahead < 4) {
            conv_sums(sa, lc + ahead, c);
            fence_async_smem();
            bar_arrive(7 + lc + ahead, 256);
            sched_fence<4>();
          }
          if (lc < 3) st[lc + 1] = ldcg128(xup + (lc + 1) * 128 * LSEQ);
          conv_epi(sb, layer, cta, lc, c, xr[lc], st[lc]);
          warp_release(bar + 8 * (B_E + lc));
          sched_fence<5>();
          if (layer == 1 && lc == 3 && ht == 0) TS(38);
        }
      }
      if (layer == 0 && STOP > 3) {
        const int c1 = role_id();
        stats_publish(sb, 1, role_rb(c1), role_hg(c1), opaque_tid() - 256, part_tag(lds32(sb + SM_EP), 2));
        delay<D_ST>();
        stats_gather(sb, role_rb(c1), opaque_tid() - 256, part_tag(lds32(sb + SM_EP), 2));
        if (ht == 0) TS(25);
        if (!HALO_W14) halo_receive(sb, 1, role_rb(c1), role_hg(c1), opaque_tid() - 256);
      }
    }
  } else {
    asm volatile("setmaxnreg.dec.sync.aligned.u32 %0;" ::"n"(512 - 2 * R_CONS - R_HELP));
    const int cta = role_id(), rb = role_rb(cta), hg = role_hg(cta), rb2 = role_rb2(cta), q2 = role_q2(cta);
    bar_sync(0, NTHREADS);
    if (warp != 12) {
      mbar_wait(bar + 8 * B_EP, 0);
      const uint32_t tag = lds32(sb + SM_EP) % 7 + 1;
      mbar_wait(bar + 8 * B_CW, 0);
      colsum_publish(sb, rb, hg, tid - 416, tag);
      if (tid == 416) TS(50);
      delay<D_CS>();
      colsum_gather(sb, hg, tid - 416, tag);
      __syncwarp();
      if (tid == 416) TS(55);
    }
    if (elect_one()) mbar_arrive(bar + 8 * B_CSF);
    if (warp == 12) {
      if (elect_one()) {
        unsigned epoch = 0;
#pragma unroll 1
        for (int layer = 0; layer < 2; layer++) {
          auto ld_w = [&](int c, int slot) {
            const uint32_t b = bar + 8 * (B_KVF + c);
            mbar_expect(b, 24576);
            tma_ld3(sb + SM_W + slot * 24576, &p.mapW3, hg * 64, c * 64, 0, b);
          };
          if (layer == 0) {
            mbar_wait(bar + 8 * (B_KVF + 2), 0);
            if (rb2 < 4) tma_prefetch2(&p.mapWo128, q2 * 64, rb2 * 128);
            asm volatile("prefetch.tensormap [%0];" ::"l"(&p.mapO) : "memory");
            asm volatile("prefetch.tensormap [%0];" ::"l"(&p.mapO128) : "memory");
            asm volatile("prefetch.tensormap [%0];" ::"l"(&p.mapXT) : "memory");
            asm volatile("prefetch.tensormap [%0];" ::"l"(&p.mapXT3) : "memory");
            mbar_wait(bar + 8 * B_EP, 0);
            epoch = lds32(sb + SM_EP);
          } else {
            mbar_wait(bar + 8 * B_PDONE, 0);
            ld_w(0, 0); ld_w(1, 1);
            mbar_wait(bar + 8 * (W2_LATE ? B_U : B_RE), 0);
            ld_w(2, 2);
          }
          {
            int slot = 0;
#pragma unroll 1
            for (int c = 3; c < 8; c++) {
              mbar_wait(bar + 8 * (B_KVE + c - 3), layer);
              ld_w(c, slot);
              slot = slot == 2 ? 0 : slot + 1;
            }
          }
          if (STOP <= 1 + 3 * layer) return;
          mbar_wait(bar + 8 * B_QDONE, layer);
          mbar_wait(bar + 8 * B_HF, layer);
          mbar_expect(bar + 8 * B_WOF, 65536);
#pragma unroll
          for (int c = 0; c < 4; c++) tma_ld(sb + SM_WO + c * 16384, &p.mapWo128, q2 * 64, c * 128, bar + 8 * B_WOF);
          {
            const uint32_t b = bar + 8 * B_RF;
            mbar_expect(b, 16384);
            if (layer == 0) tma_ld(sb + SM_R, &p.mapX128, (rb2 >> 3) * DM + q2 * 64, (rb2 & 7) * 128, b);
            else tma_ld3(sb + SM_R, &p.mapXT3, 0, DM + q2 * 64, rb2 * 2, b);
          }
#pragma unroll
          for (int c = 0; c < 8; c++) mbar_expect(bar + 8 * (B_OF + c), 16384);
          spin_until(&g_cnt[(C_O + rb2) * 32], (2 * epoch + layer + 1) * 16);
          fence_async_global();
#pragma unroll
          for (int c = 0; c < 8; c++) {
            if (c == 4) { mbar_wait(bar + 8 * B_OST, layer); fence_async_smem(); }
            tma_ld(sb + sm_o(c), &p.mapO128, c * 64, rb2 * 128, bar + 8 * (B_OF + c));
          }
          if (STOP <= 3 + 3 * layer) return;
        }
      }
    } else if (warp == 13) {
      if (elect_one() && STOP > 1) {
        const unsigned target = (lds32(sb + SM_EP) + 1) * NCTA;
        mbar_wait(bar + 8 * B_RE, 0);
        spin_until(&g_cnt[C_CS * 32 + 2], 2 * target);
        mbar_arrive(bar + 8 * B_XV);
        if (STOP <= 3) return;
        auto ld_x = [&](int c) { tma_ld3(sb + SM_X + c * 16384, &p.mapXT3, 0, DM + c * 64, rb * 2, bar + 8 * (B_XF + c)); };
#pragma unroll
        for (int c = 0; c < 8; c++) mbar_expect(bar + 8 * (B_XF + c), 16384);
        spin_until(&g_cnt[C_G1 * 32], target);
        fence_async_global();
        fence_async_smem();
        ld_x(0); ld_x(1);
        int done = 1, it = 0;
        while (done < 4) {
          const uint4 v = ld_tagged((const uint4*)&g_cnt[C_G1 * 32]);
          const int n = 4 + ((int)(v.y - target) >> 31) + ((int)(v.z - target) >> 31) + ((int)(v.w - target) >> 31);
          if (n == done) { if (++it > (1 << 23)) __trap(); continue; }
          if (n == 4) TS(44);
          fence_async_global();
          fence_async_smem();
          if (done == 1) { ld_x(2); ld_x(3); }
          const int h = hg >> 2;
          if (done < 3 && n >= 3) ld_x(4 + h);
          if (n == 4) ld_x(6 + h);
          if (done < 3 && n >= 3) ld_x(5 - h);
          if (n == 4) ld_x(7 - h);
          done = n;
        }
        if (STOP <= 4) return;
        mbar_wait(bar + 8 * B_RE, 1);
        spin_until(&g_cnt[C_CS * 32 + 3], 2 * target);
        mbar_arrive(bar + 8 * B_XV);
      }
    } else if (warp == 15) {
      mbar_wait(bar + 8 * B_EP, 0);
      const unsigned epoch = lds32(sb + SM_EP);
#pragma unroll 1
      for (int layer = 0; layer < 2; layer++) {
        mbar_wait(bar + 8 * (B_KVF + FILL_AT), layer);
#pragma unroll
        for (int k = 0; k < 8; k++) ((uint4*)(g_xT + (size_t)(2 * layer * DM + cta) * LSEQ))[32 * k + lane] = make_uint4(~0u, ~0u, ~0u, ~0u);
        mbar_wait(bar + 8 * (B_KVF + FILL_AT + 1), layer);
#pragma unroll
        for (int k = 0; k < 16; k++)
          ((uint4*)(g_xT + (size_t)(3 * DM + cv_chan(cta, 3 - (k >> 2))) * LSEQ))[128 * layer + 32 * (k & 3) + lane] = make_uint4(~0u, ~0u, ~0u, ~0u);
        if (lane < 4) ((uint4*)g_stats)[layer * 512 + cta * 4 + lane] = make_uint4(0, 0, 0, 0);
        __syncwarp();
        if (elect_one()) {
          red_release(&g_cnt[C_CS * 32 + layer]);
          spin_until(&g_cnt[C_CS * 32 + layer], (epoch + 1) * NCTA);
          mbar_arrive(bar + 8 * B_ZF);
          if (layer == 0 && STOP > 2) {
#pragma unroll
            for (int lc = 0; lc < 4; lc++) {
              mbar_wait(bar + 8 * (B_E + lc), 0);
              fence_reader();
              bulk_st(g_xT + (size_t)(DM + cv_chan(cta, lc)) * LSEQ, sb + cv_s(lc), 4096);
              bulk_commit();
              bulk_wait_all();
              red_relaxed(&g_cnt[C_G1 * 32 + lc]);
              if (lc == 3) TS(18);
            }
          }
        }
        __syncwarp();
        if (STOP <= 3) return;
      }
    } else if (warp == 14) {
      mbar_wait(bar + 8 * B_EP, 0);
      const unsigned epoch = lds32(sb + SM_EP);
#pragma unroll 1
      for (int layer = 0; layer < 2; layer++) {
        if (STOP <= 3 * layer) return;
        if (HALO_W14) halo_receive1(sb, layer, rb, hg, opaque_tid() & 31, 2 * epoch + layer + 1);
        if (STOP <= 1 + 3 * layer) return;
        mbar_wait(bar + 8 * B_ZF, layer);
        proj_stats(sb, layer, rb2, q2, opaque_tid() & 31, part_tag(epoch, 2 * layer + 1));
        if (layer == 1 && lane == 0) TS(5);
        delay<D_PREP>();
        if (lane == 0) mbar_arrive(bar + 8 * B_GB);
      }
    }
  }
}

typedef CUresult (*EncodeFn)(CUtensorMap*, CUtensorMapDataType, cuuint32_t, void*, const cuuint64_t*, const cuuint64_t*,
                             const cuuint32_t*, const cuuint32_t*, CUtensorMapInterleave, CUtensorMapSwizzle,
                             CUtensorMapL2promotion, CUtensorMapFloatOOBfill);

static void make_map(EncodeFn enc, CUtensorMap* m, void* ptr, uint64_t cols, uint64_t rows, uint32_t box_rows) {
  cuuint64_t dims[2] = {cols, rows};
  cuuint64_t strides[1] = {cols * 2};
  cuuint32_t box[2] = {64, box_rows};
  cuuint32_t es[2] = {1, 1};
  enc(m, CU_TENSOR_MAP_DATA_TYPE_BFLOAT16, 2, ptr, dims, strides, box, es, CU_TENSOR_MAP_INTERLEAVE_NONE,
      CU_TENSOR_MAP_SWIZZLE_128B, CU_TENSOR_MAP_L2_PROMOTION_L2_128B, CU_TENSOR_MAP_FLOAT_OOB_FILL_NONE);
}
static void make_map3(EncodeFn enc, CUtensorMap* m, void* ptr, uint64_t d0, uint64_t cols, uint64_t rows, uint64_t blk_stride,
                      uint64_t nblocks, uint32_t nblk, uint32_t box_rows = 64) {
  cuuint64_t dims[3] = {d0, rows, nblocks};
  cuuint64_t strides[2] = {cols * 2, blk_stride * 2};
  cuuint32_t box[3] = {64, box_rows, nblk};
  cuuint32_t es[3] = {1, 1, 1};
  enc(m, CU_TENSOR_MAP_DATA_TYPE_BFLOAT16, 3, ptr, dims, strides, box, es, CU_TENSOR_MAP_INTERLEAVE_NONE,
      CU_TENSOR_MAP_SWIZZLE_128B, CU_TENSOR_MAP_L2_PROMOTION_L2_128B, CU_TENSOR_MAP_FLOAT_OOB_FILL_NONE);
}

extern "C" void kernel_launch(void* const* d_in, const int* in_sizes, int n_in, void* d_out, int out_size) {
  static Params prm;
  static void* cached[13] = {nullptr};
  static bool attr_done = false;
  bool same = attr_done && cached[12] == d_out;
  for (int i = 0; i < 12 && same; i++) same = cached[i] == d_in[i];
  if (!same) {
    void* fn = nullptr;
    cudaDriverEntryPointQueryResult qr;
    cudaGetDriverEntryPoint("cuTensorMapEncodeTiled", &fn, cudaEnableDefault, &qr);
    EncodeFn enc = (EncodeFn)fn;
    void *pO, *pXT;
    cudaGetSymbolAddress(&pO, g_O);
    cudaGetSymbolAddress(&pXT, g_xT);
    make_map(enc, &prm.mapO, pO, DM, LSEQ, 64);
    make_map(enc, &prm.mapXT, pXT, LSEQ, 4 * DM, 64);
    prm.out = (bf16*)d_out;
    make_map(enc, &prm.mapX128, d_in[0], 2 * DM, LSEQ / 2, 128);
    make_map(enc, &prm.mapWo128, d_in[2], DM, DM, 128);
    make_map(enc, &prm.mapO128, pO, DM, LSEQ, 128);
    make_map3(enc, &prm.mapW3, d_in[1], DM, 3 * DM, DM, DM, 3, 3);
    make_map3(enc, &prm.mapW3h, d_in[1], DM, 3 * DM, DM, DM, 3, 3, 32);
    make_map3(enc, &prm.mapXT3, pXT, 64, LSEQ, 4 * DM, 64, 32, 2);
    prm.a_re = (const bf16*)d_in[4]; prm.a_im = (const bf16*)d_in[5];
    prm.b_re = (const bf16*)d_in[6]; prm.b_im = (const bf16*)d_in[7];
    prm.c_re = (const bf16*)d_in[8]; prm.c_im = (const bf16*)d_in[9];
    prm.log_dt = (const bf16*)d_in[10]; prm.dskip = (const bf16*)d_in[11];
    cudaFuncSetAttribute(fused_kernel, cudaFuncAttributeMaxDynamicSharedMemorySize, SM_TOTAL);
    for (int i = 0; i < 12; i++) cached[i] = d_in[i];
    cached[12] = d_out;
    attr_done = true;
  }
  prm.stop = 100;
    fused_kernel<<<NCTA, NTHREADS, SM_TOTAL>>>(prm);
}
```

```cpp
#include <cuda_runtime.h>
#include <cuda_bf16.h>
#include <cuda.h>
#include <stdint.h>

typedef __nv_bfloat16 bf16;

constexpr int LSEQ = 2048;
constexpr int DM = 512;
constexpr int NCTA = 128;
constexpr int NTHREADS = 512;
#define RR 0
#define KG_PRE 2
#define W2_LATE 1
#define FILL_AT 6
#define EXP_LATE 1
#define RFENCE 1
#define D_FIN 500
#define D_PREP 500
#define D_PST 0
#define D_HALO 500
#define STAG 2
#define D_ST 500
#define TLAYER 1
#define KG_PD 1
#define SUM_F32 0
#define CS_LATE0 1
#define D_HALO1 0
#define KG_START 0
#define S_AHEAD0 1
#define S_AHEAD1 2
#define PAUSE 2
#define PARK_FIRST 0
#define P_UNROLL_N 1
constexpr int P_UNROLL = P_UNROLL_N;
#define NORM_FMA 0
#define X_ORDER 1
#define CS_STEP 1
#define O_WARP 1
#define D_FIN2 400
#define FIN_D0 2
#define G_WAIT 2
#define HALO_W14 1
#define D_START 200
#define D_CS 300
#define D_ST0 400
#define KG_LAST 0
#define X_JIT 0
#define KG_GATE 2
#define R_CONS 192
#define R_HELP 88

constexpr int SM_X = 0;
constexpr int SM_W = 131072;
constexpr int SM_KVX = SM_X;
constexpr int SM_OST = SM_X + 32768;
constexpr int SM_WO = SM_X + 65536;
__host__ __device__ constexpr int sm_o(int c) { return c < 4 ? SM_W + c * 16384 : SM_X + (c - 4) * 16384; }
constexpr int SM_R = 196608;
constexpr int SM_T = 212992;
constexpr int SM_KC = 217088;
constexpr int KC_STRIDE = 648;
constexpr int SM_CS = SM_KC + 4 * KC_STRIDE * 2;
constexpr int SM_CW = SM_R + 8192;
constexpr int SM_EP = SM_CS + 768;
constexpr int SM_BAR = SM_EP + 16;
constexpr int SM_T2 = SM_BAR + 896;
constexpr int SM_HALO = SM_T2 + 4096;
constexpr int SM_ST = SM_HALO + 3072;
constexpr int SM_TOTAL = SM_HALO + 4096;
static_assert(SM_TOTAL <= 232448, "shared memory");

constexpr int CV_UH = 140 * 16;
constexpr int CV_PECH = 1120 * 4;
constexpr int CV_PBW = 2112 * 2;
__host__ __device__ constexpr int cv_s(int lc) { return SM_X + lc * 32768; }
__host__ __device__ constexpr int cv_u(int lc) { return cv_s(lc) + 4096; }
__host__ __device__ constexpr int cv_pe(int lc) { return cv_u(lc) + 2 * CV_UH; }
__host__ __device__ constexpr int cv_pb(int lc) { return cv_pe(lc) + CV_PECH; }
__host__ __device__ constexpr int cv_ft(int lc) { return cv_pb(lc) + 4 * CV_PBW; }
static_assert(cv_ft(0) + 1024 <= 32768, "conv buffers");
__host__ __device__ constexpr int cv_chan(int cta, int lc) { return cta + 128 * lc; }

enum {
  B_XF = 0,
  B_KVF = 8,
  B_OF = 16,
  B_WOF = 24,
  B_T = 31,
  B_RF = 28,
  B_RE = 29,
  B_CW = 30,
  B_GB = 35,
  B_EP = 36,
  B_ZF = 37,
  B_XV = 39,
  B_SD = 38,
  B_KVE = 40,
  B_AD = 45,
  B_OST = 46,
  B_QDONE = 47,
  B_PDONE = 48,
  B_S = 50,
  B_E = 54,
  B_P = 58,
  B_PE = 62,
  B_STF = 63,
  B_CSF = 64,
  B_HF = 65,
  B_U = 70,
  B_PS = 74,
  B_COUNT = 80
};

enum {
  C_CS = 0,
  C_G1 = 2,
  C_O = 4,
  C_COUNT = 20
};

__device__ __align__(128) unsigned g_cnt[C_COUNT * 32];
__device__ __align__(1024) bf16 g_O[LSEQ * DM];
__device__ __align__(1024) bf16 g_xT[4 * DM * LSEQ];
__device__ __align__(1024) uint32_t g_stats[2 * LSEQ];
__device__ __align__(1024) uint4 g_colsum[8 * 16 * 48];
__device__ __align__(1024) uint4 g_halo[16 * 8 * 192];
__device__ __align__(1024) uint2 g_part[16 * 8 * 128];
#define TS(i) do { } while (0)

#define ATS(i, th) do { } while (0)
#define KTS(i) do { if (ht == 0) TS(i); } while (0)
#define FTS(i) do { } while (0)
#define LTS(i) do { } while (0)

#define STOP 100

struct Params {
  CUtensorMap mapO, mapXT, mapX128, mapWo128, mapO128, mapW3, mapW3h, mapXT3;
  const bf16 *a_re, *a_im, *b_re, *b_im, *c_re, *c_im, *log_dt, *dskip;
  bf16* out;
  int stop;
};

__device__ __forceinline__ uint32_t s32(const void* p) { return (uint32_t)__cvta_generic_to_shared(p); }
__device__ __forceinline__ void mbar_init(uint32_t b, int c) { asm volatile("mbarrier.init.shared::cta.b64 [%0], %1;" ::"r"(b), "r"(c) : "memory"); }
__device__ __forceinline__ void mbar_expect(uint32_t b, int bytes) { asm volatile("mbarrier.arrive.expect_tx.shared::cta.b64 _, [%0], %1;" ::"r"(b), "r"(bytes) : "memory"); }
__device__ __forceinline__ void mbar_arrive(uint32_t b) { asm volatile("mbarrier.arrive.shared::cta.b64 _, [%0];" ::"r"(b) : "memory"); }
__device__ __forceinline__ void mbar_arrive_if(uint32_t b, bool c) {
  asm volatile("{\n.reg .pred p;\nsetp.ne.u32 p, %1, 0;\n@p mbarrier.arrive.shared::cta.b64 _, [%0];\n}" ::"r"(b), "r"((uint32_t)c) : "memory");
}
__device__ __forceinline__ void mbar_wait(uint32_t b, int parity) {
  asm volatile("{\n.reg .pred p;\nWAIT_LOOP:\nmbarrier.try_wait.parity.shared::cta.b64 p, [%0], %1;\n@p bra WAIT_DONE;\nbra WAIT_LOOP;\nWAIT_DONE:\n}" ::"r"(b), "r"(parity) : "memory");
}
template <int N> __device__ __forceinline__ void delay() {
  if constexpr (N > 0) {
    uint32_t t0, t;
    asm volatile("mov.u32 %0, %%clock;" : "=r"(t0));
    do { asm volatile("mov.u32 %0, %%clock;" : "=r"(t)); } while (t - t0 < N);
  }
}
#define SF 3
template <int ID> __device__ __forceinline__ void sched_fence() {
  if constexpr ((SF >> ID) & 1)
    asm volatile("{\n.reg .pred p;\n.reg .u32 t;\nsetp.eq.u32 p, %0, 0;\n@p mov.u32 t, %%clock;\n@p st.shared.u32 [%0], t;\n}" ::"r"(gridDim.x) : "memory");
}
__device__ __forceinline__ int opaque_tid() { int v; asm volatile("mov.u32 %0, %%tid.x;" : "=r"(v)); return v; }
__device__ __forceinline__ bool elect_one() {
  uint32_t r;
  asm volatile("{\n.reg .pred p;\nelect.sync _|p, 0xffffffff;\nselp.u32 %0, 1, 0, p;\n}" : "=r"(r));
  return r != 0;
}
__device__ __forceinline__ void tma_ld(uint32_t dst, const CUtensorMap* m, int c0, int c1, uint32_t bar) {
  asm volatile("cp.async.bulk.tensor.2d.shared::cluster.global.mbarrier::complete_tx::bytes [%0], [%1, {%3, %4}], [%2];"
               ::"r"(dst), "l"(m), "r"(bar), "r"(c0), "r"(c1) : "memory");
}
__device__ __forceinline__ void tma_ld3(uint32_t dst, const CUtensorMap* m, int c0, int c1, int c2, uint32_t bar) {
  asm volatile("cp.async.bulk.tensor.3d.shared::cluster.global.mbarrier::complete_tx::bytes [%0], [%1, {%3, %4, %5}], [%2];"
               ::"r"(dst), "l"(m), "r"(bar), "r"(c0), "r"(c1), "r"(c2) : "memory");
}
__device__ __forceinline__ void tma_prefetch2(const CUtensorMap* m, int c0, int c1) {
  asm volatile("cp.async.bulk.prefetch.tensor.2d.L2.global.tile [%0, {%1, %2}];" ::"l"(m), "r"(c0), "r"(c1) : "memory");
}
__device__ __forceinline__ void tma_prefetch3(const CUtensorMap* m, int c0, int c1, int c2) {
  asm volatile("cp.async.bulk.prefetch.tensor.3d.L2.global.tile [%0, {%1, %2, %3}];" ::"l"(m), "r"(c0), "r"(c1), "r"(c2) : "memory");
}
__device__ __forceinline__ void tma_st(const CUtensorMap* m, int c0, int c1, uint32_t src) {
  asm volatile("cp.async.bulk.tensor.2d.global.shared::cta.bulk_group [%0, {%2, %3}], [%1];" ::"l"(m), "r"(src), "r"(c0), "r"(c1) : "memory");
}
__device__ __forceinline__ void bulk_ld(uint32_t dst, const void* src, int bytes, uint32_t bar) {
  asm volatile("cp.async.bulk.shared::cluster.global.mbarrier::complete_tx::bytes [%0], [%1], %2, [%3];" ::"r"(dst), "l"(src), "r"(bytes), "r"(bar) : "memory");
}
__device__ __forceinline__ void bulk_st(void* dst, uint32_t src, int bytes) {
  asm volatile("cp.async.bulk.global.shared::cta.bulk_group [%0], [%1], %2;" ::"l"(dst), "r"(src), "r"(bytes) : "memory");
}
__device__ __forceinline__ void bulk_red_add_f32(void* dst, uint32_t src, int bytes) {
  asm volatile("cp.reduce.async.bulk.global.shared::cta.bulk_group.add.f32 [%0], [%1], %2;" ::"l"(dst), "r"(src), "r"(bytes) : "memory");
}
__device__ __forceinline__ void bulk_commit() { asm volatile("cp.async.bulk.commit_group;" ::: "memory"); }
__device__ __forceinline__ void bulk_wait_all() { asm volatile("cp.async.bulk.wait_group 0;" ::: "memory"); }
__device__ __forceinline__ void fence_async_smem() { asm volatile("fence.proxy.async.shared::cta;" ::: "memory"); }
__device__ __forceinline__ void fence_writer() { if (!RFENCE) fence_async_smem(); }
__device__ __forceinline__ void fence_reader() { if (RFENCE) fence_async_smem(); }
__device__ __forceinline__ void fence_async_global() { asm volatile("fence.proxy.async.global;" ::: "memory"); }
__device__ __forceinline__ void bar_sync(int id, int n) { asm volatile("bar.sync %0, %1;" ::"r"(id), "r"(n) : "memory"); }
__device__ __forceinline__ void bar_arrive(int id, int n) { asm volatile("bar.arrive %0, %1;" ::"r"(id), "r"(n) : "memory"); }
__device__ __forceinline__ void wg_fence() { asm volatile("wgmma.fence.sync.aligned;" ::: "memory"); }
__device__ __forceinline__ void wg_commit() { asm volatile("wgmma.commit_group.sync.aligned;" ::: "memory"); }
template <int N> __device__ __forceinline__ void wg_wait() { asm volatile("wgmma.wait_group.sync.aligned %0;" ::"n"(N) : "memory"); }
__device__ __forceinline__ uint64_t mkdesc(uint32_t addr, uint32_t lbo, uint32_t sbo, int sw) {
  return (uint64_t)((addr & 0x3FFFF) >> 4) | ((uint64_t)(lbo >> 4) << 16) | ((uint64_t)(sbo >> 4) << 32) | ((uint64_t)sw << 62);
}
__device__ __forceinline__ void ldsm4(uint32_t* r, uint32_t a) {
  asm volatile("ldmatrix.sync.aligned.m8n8.x4.shared.b16 {%0,%1,%2,%3}, [%4];" : "=r"(r[0]), "=r"(r[1]), "=r"(r[2]), "=r"(r[3]) : "r"(a) : "memory");
}
__device__ __forceinline__ void ldsm4t(uint32_t* r, uint32_t a) {
  asm volatile("ldmatrix.sync.aligned.m8n8.x4.trans.shared.b16 {%0,%1,%2,%3}, [%4];" : "=r"(r[0]), "=r"(r[1]), "=r"(r[2]), "=r"(r[3]) : "r"(a) : "memory");
}
__device__ __forceinline__ void stsm4(uint32_t a, uint32_t r0, uint32_t r1, uint32_t r2, uint32_t r3) {
  asm volatile("stmatrix.sync.aligned.m8n8.x4.shared.b16 [%0], {%1,%2,%3,%4};" ::"r"(a), "r"(r0), "r"(r1), "r"(r2), "r"(r3) : "memory");
}
__device__ __forceinline__ void stsm4t(uint32_t a, uint32_t r0, uint32_t r1, uint32_t r2, uint32_t r3) {
  asm volatile("stmatrix.sync.aligned.m8n8.x4.trans.shared.b16 [%0], {%1,%2,%3,%4};" ::"r"(a), "r"(r0), "r"(r1), "r"(r2), "r"(r3) : "memory");
}
__device__ __forceinline__ uint32_t movm_t(uint32_t a) { uint32_t r; asm volatile("movmatrix.sync.aligned.m8n8.trans.b16 %0, %1;" : "=r"(r) : "r"(a)); return r; }
__device__ __forceinline__ uint32_t lds32(uint32_t a) { uint32_t v; asm volatile("ld.shared.b32 %0, [%1];" : "=r"(v) : "r"(a) : "memory"); return v; }
__device__ __forceinline__ float2 lds64f(uint32_t a) { float2 v; asm volatile("ld.shared.v2.f32 {%0,%1}, [%2];" : "=f"(v.x), "=f"(v.y) : "r"(a) : "memory"); return v; }
__device__ __forceinline__ float4 lds128f(uint32_t a) { float4 v; asm volatile("ld.shared.v4.f32 {%0,%1,%2,%3}, [%4];" : "=f"(v.x), "=f"(v.y), "=f"(v.z), "=f"(v.w) : "r"(a) : "memory"); return v; }
__device__ __forceinline__ uint4 lds128(uint32_t a) { uint4 v; asm volatile("ld.shared.v4.b32 {%0,%1,%2,%3}, [%4];" : "=r"(v.x), "=r"(v.y), "=r"(v.z), "=r"(v.w) : "r"(a) : "memory"); return v; }
__device__ __forceinline__ void sts128(uint32_t a, uint4 v) { asm volatile("st.shared.v4.b32 [%0], {%1,%2,%3,%4};" ::"r"(a), "r"(v.x), "r"(v.y), "r"(v.z), "r"(v.w) : "memory"); }
__device__ __forceinline__ void sts128f(uint32_t a, float x, float y, float z, float w) { asm volatile("st.shared.v4.f32 [%0], {%1,%2,%3,%4};" ::"r"(a), "f"(x), "f"(y), "f"(z), "f"(w) : "memory"); }
__device__ __forceinline__ void sts32f(uint32_t a, float v) { asm volatile("st.shared.f32 [%0], %1;" ::"r"(a), "f"(v) : "memory"); }
__device__ __forceinline__ void sts16(uint32_t a, uint16_t v) { asm volatile("st.shared.u16 [%0], %1;" ::"r"(a), "h"(v) : "memory"); }
__device__ __forceinline__ uint32_t lds16(uint32_t a) { uint16_t v; asm volatile("ld.shared.u16 %0, [%1];" : "=h"(v) : "r"(a) : "memory"); return v; }
__device__ __forceinline__ uint32_t packbf(float lo, float hi) { uint32_t r; asm("cvt.rn.bf16x2.f32 %0, %1, %2;" : "=r"(r) : "f"(hi), "f"(lo)); return r; }
__device__ __forceinline__ float bf_lo(uint32_t v) { return __uint_as_float(v << 16); }
__device__ __forceinline__ float bf_hi(uint32_t v) { return __uint_as_float(v & 0xffff0000u); }
__device__ __forceinline__ float ex2(float x) { float r; asm("ex2.approx.ftz.f32 %0, %1;" : "=f"(r) : "f"(x)); return r; }
__device__ __forceinline__ float rsqrt_approx(float x) { float r; asm("rsqrt.approx.ftz.f32 %0, %1;" : "=f"(r) : "f"(x)); return r; }
__device__ __forceinline__ float rcp_approx(float x) { float r; asm("rcp.approx.ftz.f32 %0, %1;" : "=f"(r) : "f"(x)); return r; }
__device__ __forceinline__ void mma_bf16(float* d, const uint32_t* a, uint32_t b0, uint32_t b1) {
  asm("mma.sync.aligned.m16n8k16.row.col.f32.bf16.bf16.f32 {%0,%1,%2,%3}, {%4,%5,%6,%7}, {%8,%9}, {%0,%1,%2,%3};"
               : "+f"(d[0]), "+f"(d[1]), "+f"(d[2]), "+f"(d[3]) : "r"(a[0]), "r"(a[1]), "r"(a[2]), "r"(a[3]), "r"(b0), "r"(b1));
}
__device__ __forceinline__ void mma_bf16_k8(float* d, uint32_t a0, uint32_t a1, uint32_t b) {
  asm("mma.sync.aligned.m16n8k8.row.col.f32.bf16.bf16.f32 {%0,%1,%2,%3}, {%4,%5}, {%6}, {%0,%1,%2,%3};"
      : "+f"(d[0]), "+f"(d[1]), "+f"(d[2]), "+f"(d[3]) : "r"(a0), "r"(a1), "r"(b));
}
__device__ __forceinline__ void red_release(unsigned* p) { asm volatile("red.release.gpu.global.add.u32 [%0], 1;" ::"l"(p) : "memory"); }
__device__ __forceinline__ void red_relaxed(unsigned* p) { asm volatile("red.relaxed.gpu.global.add.u32 [%0], 1;" ::"l"(p) : "memory"); }
__device__ __forceinline__ unsigned ld_relaxed(const unsigned* p) { unsigned v; asm volatile("ld.relaxed.gpu.global.u32 %0, [%1];" : "=r"(v) : "l"(p) : "memory"); return v; }
__device__ __forceinline__ void spin_until(const unsigned* p, unsigned target) {
  int it = 0;
  while ((int)(ld_relaxed(p) - target) < 0) {
    if (++it > (1 << 23)) __trap();
  }
}
__device__ __forceinline__ uint4 ldcg128(const void* p) { uint4 v; asm volatile("ld.global.cg.v4.b32 {%0,%1,%2,%3}, [%4];" : "=r"(v.x), "=r"(v.y), "=r"(v.z), "=r"(v.w) : "l"(p) : "memory"); return v; }
__device__ __forceinline__ uint4 ld_tagged(const uint4* p) { uint4 v; asm volatile("ld.relaxed.gpu.global.v4.u32 {%0,%1,%2,%3}, [%4];" : "=r"(v.x), "=r"(v.y), "=r"(v.z), "=r"(v.w) : "l"(p) : "memory"); return v; }
__device__ __forceinline__ uint2 ld_part(const uint2* p) { uint2 v; asm volatile("ld.relaxed.gpu.global.v2.u32 {%0,%1}, [%2];" : "=r"(v.x), "=r"(v.y) : "l"(p) : "memory"); return v; }
__device__ __forceinline__ void st_part(uint2* p, float s, float q, uint32_t tag) {
  asm volatile("st.relaxed.gpu.global.v2.u32 [%0], {%1,%2};" ::"l"(p), "r"(__float_as_uint(s)), "r"((__float_as_uint(q) & ~7u) | tag) : "memory");
}
__device__ __forceinline__ uint32_t part_tag(uint32_t epoch, int k) { return (4 * (epoch % 7) + k) % 7 + 1; }
__device__ __forceinline__ void st_tagged3(uint4* p, uint32_t a, uint32_t b, uint32_t c, uint32_t tag) { asm volatile("st.relaxed.gpu.global.v4.u32 [%0], {%1,%2,%3,%4};" ::"l"(p), "r"(a), "r"(b), "r"(c), "r"(tag) : "memory"); }
__device__ __forceinline__ uint32_t hadd2(uint32_t a, uint32_t b) { uint32_t r; asm("add.rn.bf16x2 %0, %1, %2;" : "=r"(r) : "r"(a), "r"(b)); return r; }
__device__ __forceinline__ uint32_t hfma2(uint32_t a, uint32_t b, uint32_t c) { uint32_t r; asm("fma.rn.bf16x2 %0, %1, %2, %3;" : "=r"(r) : "r"(a), "r"(b), "r"(c)); return r; }
__device__ __forceinline__ uint32_t hmul2(uint32_t a, uint32_t b) { uint32_t r; asm("mul.rn.bf16x2 %0, %1, %2;" : "=r"(r) : "r"(a), "r"(b)); return r; }

template<int N,int TB> __device__ __forceinline__ void wgmma_rs(float* d, const uint32_t* a, uint64_t db, int sd);
template<int N,int TA,int TB> __device__ __forceinline__ void wgmma_ss(float* d, uint64_t da, uint64_t db, int sd);
template<> __device__ __forceinline__ void wgmma_rs<128,0>(float* d, const uint32_t* a, uint64_t db, int sd) {
  asm volatile("{\n.reg .pred p;\nsetp.ne.b32 p, %69, 0;\nwgmma.mma_async.sync.aligned.m64n128k16.f32.bf16.bf16 {%0,%1,%2,%3,%4,%5,%6,%7,%8,%9,%10,%11,%12,%13,%14,%15,%16,%17,%18,%19,%20,%21,%22,%23,%24,%25,%26,%27,%28,%29,%30,%31,%32,%33,%34,%35,%36,%37,%38,%39,%40,%41,%42,%43,%44,%45,%46,%47,%48,%49,%50,%51,%52,%53,%54,%55,%56,%57,%58,%59,%60,%61,%62,%63}, {%64,%65,%66,%67}, %68, p, 1, 1, 0;\n}\n"
   : "+f"(d[0]),"+f"(d[1]),"+f"(d[2]),"+f"(d[3]),"+f"(d[4]),"+f"(d[5]),"+f"(d[6]),"+f"(d[7]),"+f"(d[8]),"+f"(d[9]),"+f"(d[10]),"+f"(d[11]),"+f"(d[12]),"+f"(d[13]),"+f"(d[14]),"+f"(d[15]),"+f"(d[16]),"+f"(d[17]),"+f"(d[18]),"+f"(d[19]),"+f"(d[20]),"+f"(d[21]),"+f"(d[22]),"+f"(d[23]),"+f"(d[24]),"+f"(d[25]),"+f"(d[26]),"+f"(d[27]),"+f"(d[28]),"+f"(d[29]),"+f"(d[30]),"+f"(d[31]),"+f"(d[32]),"+f"(d[33]),"+f"(d[34]),"+f"(d[35]),"+f"(d[36]),"+f"(d[37]),"+f"(d[38]),"+f"(d[39]),"+f"(d[40]),"+f"(d[41]),"+f"(d[42]),"+f"(d[43]),"+f"(d[44]),"+f"(d[45]),"+f"(d[46]),"+f"(d[47]),"+f"(d[48]),"+f"(d[49]),"+f"(d[50]),"+f"(d[51]),"+f"(d[52]),"+f"(d[53]),"+f"(d[54]),"+f"(d[55]),"+f"(d[56]),"+f"(d[57]),"+f"(d[58]),"+f"(d[59]),"+f"(d[60]),"+f"(d[61]),"+f"(d[62]),"+f"(d[63])
   : "r"(a[0]), "r"(a[1]), "r"(a[2]), "r"(a[3]), "l"(db), "r"(sd));
}
template<> __device__ __forceinline__ void wgmma_rs<120,0>(float* d, const uint32_t* a, uint64_t db, int sd) {
  asm volatile("{\n.reg .pred p;\nsetp.ne.b32 p, %65, 0;\nwgmma.mma_async.sync.aligned.m64n120k16.f32.bf16.bf16 {%0,%1,%2,%3,%4,%5,%6,%7,%8,%9,%10,%11,%12,%13,%14,%15,%16,%17,%18,%19,%20,%21,%22,%23,%24,%25,%26,%27,%28,%29,%30,%31,%32,%33,%34,%35,%36,%37,%38,%39,%40,%41,%42,%43,%44,%45,%46,%47,%48,%49,%50,%51,%52,%53,%54,%55,%56,%57,%58,%59}, {%60,%61,%62,%63}, %64, p, 1, 1, 0;\n}\n"
   : "+f"(d[0]),"+f"(d[1]),"+f"(d[2]),"+f"(d[3]),"+f"(d[4]),"+f"(d[5]),"+f"(d[6]),"+f"(d[7]),"+f"(d[8]),"+f"(d[9]),"+f"(d[10]),"+f"(d[11]),"+f"(d[12]),"+f"(d[13]),"+f"(d[14]),"+f"(d[15]),"+f"(d[16]),"+f"(d[17]),"+f"(d[18]),"+f"(d[19]),"+f"(d[20]),"+f"(d[21]),"+f"(d[22]),"+f"(d[23]),"+f"(d[24]),"+f"(d[25]),"+f"(d[26]),"+f"(d[27]),"+f"(d[28]),"+f"(d[29]),"+f"(d[30]),"+f"(d[31]),"+f"(d[32]),"+f"(d[33]),"+f"(d[34]),"+f"(d[35]),"+f"(d[36]),"+f"(d[37]),"+f"(d[38]),"+f"(d[39]),"+f"(d[40]),"+f"(d[41]),"+f"(d[42]),"+f"(d[43]),"+f"(d[44]),"+f"(d[45]),"+f"(d[46]),"+f"(d[47]),"+f"(d[48]),"+f"(d[49]),"+f"(d[50]),"+f"(d[51]),"+f"(d[52]),"+f"(d[53]),"+f"(d[54]),"+f"(d[55]),"+f"(d[56]),"+f"(d[57]),"+f"(d[58]),"+f"(d[59])
   : "r"(a[0]), "r"(a[1]), "r"(a[2]), "r"(a[3]), "l"(db), "r"(sd));
}
template<> __device__ __forceinline__ void wgmma_rs<112,0>(float* d, const uint32_t* a, uint64_t db, int sd) {
  asm volatile("{\n.reg .pred p;\nsetp.ne.b32 p, %61, 0;\nwgmma.mma_async.sync.aligned.m64n112k16.f32.bf16.bf16 {%0,%1,%2,%3,%4,%5,%6,%7,%8,%9,%10,%11,%12,%13,%14,%15,%16,%17,%18,%19,%20,%21,%22,%23,%24,%25,%26,%27,%28,%29,%30,%31,%32,%33,%34,%35,%36,%37,%38,%39,%40,%41,%42,%43,%44,%45,%46,%47,%48,%49,%50,%51,%52,%53,%54,%55}, {%56,%57,%58,%59}, %60, p, 1, 1, 0;\n}\n"
   : "+f"(d[0]),"+f"(d[1]),"+f"(d[2]),"+f"(d[3]),"+f"(d[4]),"+f"(d[5]),"+f"(d[6]),"+f"(d[7]),"+f"(d[8]),"+f"(d[9]),"+f"(d[10]),"+f"(d[11]),"+f"(d[12]),"+f"(d[13]),"+f"(d[14]),"+f"(d[15]),"+f"(d[16]),"+f"(d[17]),"+f"(d[18]),"+f"(d[19]),"+f"(d[20]),"+f"(d[21]),"+f"(d[22]),"+f"(d[23]),"+f"(d[24]),"+f"(d[25]),"+f"(d[26]),"+f"(d[27]),"+f"(d[28]),"+f"(d[29]),"+f"(d[30]),"+f"(d[31]),"+f"(d[32]),"+f"(d[33]),"+f"(d[34]),"+f"(d[35]),"+f"(d[36]),"+f"(d[37]),"+f"(d[38]),"+f"(d[39]),"+f"(d[40]),"+f"(d[41]),"+f"(d[42]),"+f"(d[43]),"+f"(d[44]),"+f"(d[45]),"+f"(d[46]),"+f"(d[47]),"+f"(d[48]),"+f"(d[49]),"+f"(d[50]),"+f"(d[51]),"+f"(d[52]),"+f"(d[53]),"+f"(d[54]),"+f"(d[55])
   : "r"(a[0]), "r"(a[1]), "r"(a[2]), "r"(a[3]), "l"(db), "r"(sd));
}
template<> __device__ __forceinline__ void wgmma_rs<104,0>(float* d, const uint32_t* a, uint64_t db, int sd) {
  asm volatile("{\n.reg .pred p;\nsetp.ne.b32 p, %57, 0;\nwgmma.mma_async.sync.aligned.m64n104k16.f32.bf16.bf16 {%0,%1,%2,%3,%4,%5,%6,%7,%8,%9,%10,%11,%12,%13,%14,%15,%16,%17,%18,%19,%20,%21,%22,%23,%24,%25,%26,%27,%28,%29,%30,%31,%32,%33,%34,%35,%36,%37,%38,%39,%40,%41,%42,%43,%44,%45,%46,%47,%48,%49,%50,%51}, {%52,%53,%54,%55}, %56, p, 1, 1, 0;\n}\n"
   : "+f"(d[0]),"+f"(d[1]),"+f"(d[2]),"+f"(d[3]),"+f"(d[4]),"+f"(d[5]),"+f"(d[6]),"+f"(d[7]),"+f"(d[8]),"+f"(d[9]),"+f"(d[10]),"+f"(d[11]),"+f"(d[12]),"+f"(d[13]),"+f"(d[14]),"+f"(d[15]),"+f"(d[16]),"+f"(d[17]),"+f"(d[18]),"+f"(d[19]),"+f"(d[20]),"+f"(d[21]),"+f"(d[22]),"+f"(d[23]),"+f"(d[24]),"+f"(d[25]),"+f"(d[26]),"+f"(d[27]),"+f"(d[28]),"+f"(d[29]),"+f"(d[30]),"+f"(d[31]),"+f"(d[32]),"+f"(d[33]),"+f"(d[34]),"+f"(d[35]),"+f"(d[36]),"+f"(d[37]),"+f"(d[38]),"+f"(d[39]),"+f"(d[40]),"+f"(d[41]),"+f"(d[42]),"+f"(d[43]),"+f"(d[44]),"+f"(d[45]),"+f"(d[46]),"+f"(d[47]),"+f"(d[48]),"+f"(d[49]),"+f"(d[50]),"+f"(d[51])
   : "r"(a[0]), "r"(a[1]), "r"(a[2]), "r"(a[3]), "l"(db), "r"(sd));
}
template<> __device__ __forceinline__ void wgmma_rs<96,0>(float* d, const uint32_t* a, uint64_t db, int sd) {
  asm volatile("{\n.reg .pred p;\nsetp.ne.b32 p, %53, 0;\nwgmma.mma_async.sync.aligned.m64n96k16.f32.bf16.bf16 {%0,%1,%2,%3,%4,%5,%6,%7,%8,%9,%10,%11,%12,%13,%14,%15,%16,%17,%18,%19,%20,%21,%22,%23,%24,%25,%26,%27,%28,%29,%30,%31,%32,%33,%34,%35,%36,%37,%38,%39,%40,%41,%42,%43,%44,%45,%46,%47}, {%48,%49,%50,%51}, %52, p, 1, 1, 0;\n}\n"
   : "+f"(d[0]),"+f"(d[1]),"+f"(d[2]),"+f"(d[3]),"+f"(d[4]),"+f"(d[5]),"+f"(d[6]),"+f"(d[7]),"+f"(d[8]),"+f"(d[9]),"+f"(d[10]),"+f"(d[11]),"+f"(d[12]),"+f"(d[13]),"+f"(d[14]),"+f"(d[15]),"+f"(d[16]),"+f"(d[17]),"+f"(d[18]),"+f"(d[19]),"+f"(d[20]),"+f"(d[21]),"+f"(d[22]),"+f"(d[23]),"+f"(d[24]),"+f"(d[25]),"+f"(d[26]),"+f"(d[27]),"+f"(d[28]),"+f"(d[29]),"+f"(d[30]),"+f"(d[31]),"+f"(d[32]),"+f"(d[33]),"+f"(d[34]),"+f"(d[35]),"+f"(d[36]),"+f"(d[37]),"+f"(d[38]),"+f"(d[39]),"+f"(d[40]),"+f"(d[41]),"+f"(d[42]),"+f"(d[43]),"+f"(d[44]),"+f"(d[45]),"+f"(d[46]),"+f"(d[47])
   : "r"(a[0]), "r"(a[1]), "r"(a[2]), "r"(a[3]), "l"(db), "r"(sd));
}
template<> __device__ __forceinline__ void wgmma_rs<88,0>(float* d, const uint32_t* a, uint64_t db, int sd) {
  asm volatile("{\n.reg .pred p;\nsetp.ne.b32 p, %49, 0;\nwgmma.mma_async.sync.aligned.m64n88k16.f32.bf16.bf16 {%0,%1,%2,%3,%4,%5,%6,%7,%8,%9,%10,%11,%12,%13,%14,%15,%16,%17,%18,%19,%20,%21,%22,%23,%24,%25,%26,%27,%28,%29,%30,%31,%32,%33,%34,%35,%36,%37,%38,%39,%40,%41,%42,%43}, {%44,%45,%46,%47}, %48, p, 1, 1, 0;\n}\n"
   : "+f"(d[0]),"+f"(d[1]),"+f"(d[2]),"+f"(d[3]),"+f"(d[4]),"+f"(d[5]),"+f"(d[6]),"+f"(d[7]),"+f"(d[8]),"+f"(d[9]),"+f"(d[10]),"+f"(d[11]),"+f"(d[12]),"+f"(d[13]),"+f"(d[14]),"+f"(d[15]),"+f"(d[16]),"+f"(d[17]),"+f"(d[18]),"+f"(d[19]),"+f"(d[20]),"+f"(d[21]),"+f"(d[22]),"+f"(d[23]),"+f"(d[24]),"+f"(d[25]),"+f"(d[26]),"+f"(d[27]),"+f"(d[28]),"+f"(d[29]),"+f"(d[30]),"+f"(d[31]),"+f"(d[32]),"+f"(d[33]),"+f"(d[34]),"+f"(d[35]),"+f"(d[36]),"+f"(d[37]),"+f"(d[38]),"+f"(d[39]),"+f"(d[40]),"+f"(d[41]),"+f"(d[42]),"+f"(d[43])
   : "r"(a[0]), "r"(a[1]), "r"(a[2]), "r"(a[3]), "l"(db), "r"(sd));
}
template<> __device__ __forceinline__ void wgmma_rs<80,0>(float* d, const uint32_t* a, uint64_t db, int sd) {
  asm volatile("{\n.reg .pred p;\nsetp.ne.b32 p, %45, 0;\nwgmma.mma_async.sync.aligned.m64n80k16.f32.bf16.bf16 {%0,%1,%2,%3,%4,%5,%6,%7,%8,%9,%10,%11,%12,%13,%14,%15,%16,%17,%18,%19,%20,%21,%22,%23,%24,%25,%26,%27,%28,%29,%30,%31,%32,%33,%34,%35,%36,%37,%38,%39}, {%40,%41,%42,%43}, %44, p, 1, 1, 0;\n}\n"
   : "+f"(d[0]),"+f"(d[1]),"+f"(d[2]),"+f"(d[3]),"+f"(d[4]),"+f"(d[5]),"+f"(d[6]),"+f"(d[7]),"+f"(d[8]),"+f"(d[9]),"+f"(d[10]),"+f"(d[11]),"+f"(d[12]),"+f"(d[13]),"+f"(d[14]),"+f"(d[15]),"+f"(d[16]),"+f"(d[17]),"+f"(d[18]),"+f"(d[19]),"+f"(d[20]),"+f"(d[21]),"+f"(d[22]),"+f"(d[23]),"+f"(d[24]),"+f"(d[25]),"+f"(d[26]),"+f"(d[27]),"+f"(d[28]),"+f"(d[29]),"+f"(d[30]),"+f"(d[31]),"+f"(d[32]),"+f"(d[33]),"+f"(d[34]),"+f"(d[35]),"+f"(d[36]),"+f"(d[37]),"+f"(d[38]),"+f"(d[39])
   : "r"(a[0]), "r"(a[1]), "r"(a[2]), "r"(a[3]), "l"(db), "r"(sd));
}
template<> __device__ __forceinline__ void wgmma_rs<72,0>(float* d, const uint32_t* a, uint64_t db, int sd) {
  asm volatile("{\n.reg .pred p;\nsetp.ne.b32 p, %41, 0;\nwgmma.mma_async.sync.aligned.m64n72k16.f32.bf16.bf16 {%0,%1,%2,%3,%4,%5,%6,%7,%8,%9,%10,%11,%12,%13,%14,%15,%16,%17,%18,%19,%20,%21,%22,%23,%24,%25,%26,%27,%28,%29,%30,%31,%32,%33,%34,%35}, {%36,%37,%38,%39}, %40, p, 1, 1, 0;\n}\n"
   : "+f"(d[0]),"+f"(d[1]),"+f"(d[2]),"+f"(d[3]),"+f"(d[4]),"+f"(d[5]),"+f"(d[6]),"+f"(d[7]),"+f"(d[8]),"+f"(d[9]),"+f"(d[10]),"+f"(d[11]),"+f"(d[12]),"+f"(d[13]),"+f"(d[14]),"+f"(d[15]),"+f"(d[16]),"+f"(d[17]),"+f"(d[18]),"+f"(d[19]),"+f"(d[20]),"+f"(d[21]),"+f"(d[22]),"+f"(d[23]),"+f"(d[24]),"+f"(d[25]),"+f"(d[26]),"+f"(d[27]),"+f"(d[28]),"+f"(d[29]),"+f"(d[30]),"+f"(d[31]),"+f"(d[32]),"+f"(d[33]),"+f"(d[34]),"+f"(d[35])
   : "r"(a[0]), "r"(a[1]), "r"(a[2]), "r"(a[3]), "l"(db), "r"(sd));
}
template<> __device__ __forceinline__ void wgmma_rs<64,0>(float* d, const uint32_t* a, uint64_t db, int sd) {
  asm volatile("{\n.reg .pred p;\nsetp.ne.b32 p, %37, 0;\nwgmma.mma_async.sync.aligned.m64n64k16.f32.bf16.bf16 {%0,%1,%2,%3,%4,%5,%6,%7,%8,%9,%10,%11,%12,%13,%14,%15,%16,%17,%18,%19,%20,%21,%22,%23,%24,%25,%26,%27,%28,%29,%30,%31}, {%32,%33,%34,%35}, %36, p, 1, 1, 0;\n}\n"
   : "+f"(d[0]),"+f"(d[1]),"+f"(d[2]),"+f"(d[3]),"+f"(d[4]),"+f"(d[5]),"+f"(d[6]),"+f"(d[7]),"+f"(d[8]),"+f"(d[9]),"+f"(d[10]),"+f"(d[11]),"+f"(d[12]),"+f"(d[13]),"+f"(d[14]),"+f"(d[15]),"+f"(d[16]),"+f"(d[17]),"+f"(d[18]),"+f"(d[19]),"+f"(d[20]),"+f"(d[21]),"+f"(d[22]),"+f"(d[23]),"+f"(d[24]),"+f"(d[25]),"+f"(d[26]),"+f"(d[27]),"+f"(d[28]),"+f"(d[29]),"+f"(d[30]),"+f"(d[31])
   : "r"(a[0]), "r"(a[1]), "r"(a[2]), "r"(a[3]), "l"(db), "r"(sd));
}
template<> __device__ __forceinline__ void wgmma_ss<64,0,1>(float* d, uint64_t da, uint64_t db, int sd) {
  asm volatile("{\n.reg .pred p;\nsetp.ne.b32 p, %34, 0;\nwgmma.mma_async.sync.aligned.m64n64k16.f32.bf16.bf16 {%0,%1,%2,%3,%4,%5,%6,%7,%8,%9,%10,%11,%12,%13,%14,%15,%16,%17,%18,%19,%20,%21,%22,%23,%24,%25,%26,%27,%28,%29,%30,%31}, %32, %33, p, 1, 1, 0, 1;\n}\n"
   : "+f"(d[0]),"+f"(d[1]),"+f"(d[2]),"+f"(d[3]),"+f"(d[4]),"+f"(d[5]),"+f"(d[6]),"+f"(d[7]),"+f"(d[8]),"+f"(d[9]),"+f"(d[10]),"+f"(d[11]),"+f"(d[12]),"+f"(d[13]),"+f"(d[14]),"+f"(d[15]),"+f"(d[16]),"+f"(d[17]),"+f"(d[18]),"+f"(d[19]),"+f"(d[20]),"+f"(d[21]),"+f"(d[22]),"+f"(d[23]),"+f"(d[24]),"+f"(d[25]),"+f"(d[26]),"+f"(d[27]),"+f"(d[28]),"+f"(d[29]),"+f"(d[30]),"+f"(d[31])
   : "l"(da), "l"(db), "r"(sd));
}
template<> __device__ __forceinline__ void wgmma_ss<64,1,1>(float* d, uint64_t da, uint64_t db, int sd) {
  asm volatile("{\n.reg .pred p;\nsetp.ne.b32 p, %34, 0;\nwgmma.mma_async.sync.aligned.m64n64k16.f32.bf16.bf16 {%0,%1,%2,%3,%4,%5,%6,%7,%8,%9,%10,%11,%12,%13,%14,%15,%16,%17,%18,%19,%20,%21,%22,%23,%24,%25,%26,%27,%28,%29,%30,%31}, %32, %33, p, 1, 1, 1, 1;\n}\n"
   : "+f"(d[0]),"+f"(d[1]),"+f"(d[2]),"+f"(d[3]),"+f"(d[4]),"+f"(d[5]),"+f"(d[6]),"+f"(d[7]),"+f"(d[8]),"+f"(d[9]),"+f"(d[10]),"+f"(d[11]),"+f"(d[12]),"+f"(d[13]),"+f"(d[14]),"+f"(d[15]),"+f"(d[16]),"+f"(d[17]),"+f"(d[18]),"+f"(d[19]),"+f"(d[20]),"+f"(d[21]),"+f"(d[22]),"+f"(d[23]),"+f"(d[24]),"+f"(d[25]),"+f"(d[26]),"+f"(d[27]),"+f"(d[28]),"+f"(d[29]),"+f"(d[30]),"+f"(d[31])
   : "l"(da), "l"(db), "r"(sd));
}
template<> __device__ __forceinline__ void wgmma_ss<192,0,1>(float* d, uint64_t da, uint64_t db, int sd) {
  asm volatile("{\n.reg .pred p;\nsetp.ne.b32 p, %98, 0;\nwgmma.mma_async.sync.aligned.m64n192k16.f32.bf16.bf16 {%0,%1,%2,%3,%4,%5,%6,%7,%8,%9,%10,%11,%12,%13,%14,%15,%16,%17,%18,%19,%20,%21,%22,%23,%24,%25,%26,%27,%28,%29,%30,%31,%32,%33,%34,%35,%36,%37,%38,%39,%40,%41,%42,%43,%44,%45,%46,%47,%48,%49,%50,%51,%52,%53,%54,%55,%56,%57,%58,%59,%60,%61,%62,%63,%64,%65,%66,%67,%68,%69,%70,%71,%72,%73,%74,%75,%76,%77,%78,%79,%80,%81,%82,%83,%84,%85,%86,%87,%88,%89,%90,%91,%92,%93,%94,%95}, %96, %97, p, 1, 1, 0, 1;\n}\n"
   : "+f"(d[0]),"+f"(d[1]),"+f"(d[2]),"+f"(d[3]),"+f"(d[4]),"+f"(d[5]),"+f"(d[6]),"+f"(d[7]),"+f"(d[8]),"+f"(d[9]),"+f"(d[10]),"+f"(d[11]),"+f"(d[12]),"+f"(d[13]),"+f"(d[14]),"+f"(d[15]),"+f"(d[16]),"+f"(d[17]),"+f"(d[18]),"+f"(d[19]),"+f"(d[20]),"+f"(d[21]),"+f"(d[22]),"+f"(d[23]),"+f"(d[24]),"+f"(d[25]),"+f"(d[26]),"+f"(d[27]),"+f"(d[28]),"+f"(d[29]),"+f"(d[30]),"+f"(d[31]),"+f"(d[32]),"+f"(d[33]),"+f"(d[34]),"+f"(d[35]),"+f"(d[36]),"+f"(d[37]),"+f"(d[38]),"+f"(d[39]),"+f"(d[40]),"+f"(d[41]),"+f"(d[42]),"+f"(d[43]),"+f"(d[44]),"+f"(d[45]),"+f"(d[46]),"+f"(d[47]),"+f"(d[48]),"+f"(d[49]),"+f"(d[50]),"+f"(d[51]),"+f"(d[52]),"+f"(d[53]),"+f"(d[54]),"+f"(d[55]),"+f"(d[56]),"+f"(d[57]),"+f"(d[58]),"+f"(d[59]),"+f"(d[60]),"+f"(d[61]),"+f"(d[62]),"+f"(d[63]),"+f"(d[64]),"+f"(d[65]),"+f"(d[66]),"+f"(d[67]),"+f"(d[68]),"+f"(d[69]),"+f"(d[70]),"+f"(d[71]),"+f"(d[72]),"+f"(d[73]),"+f"(d[74]),"+f"(d[75]),"+f"(d[76]),"+f"(d[77]),"+f"(d[78]),"+f"(d[79]),"+f"(d[80]),"+f"(d[81]),"+f"(d[82]),"+f"(d[83]),"+f"(d[84]),"+f"(d[85]),"+f"(d[86]),"+f"(d[87]),"+f"(d[88]),"+f"(d[89]),"+f"(d[90]),"+f"(d[91]),"+f"(d[92]),"+f"(d[93]),"+f"(d[94]),"+f"(d[95])
   : "l"(da), "l"(db), "r"(sd));
}
template<> __device__ __forceinline__ void wgmma_ss<192,1,1>(float* d, uint64_t da, uint64_t db, int sd) {
  asm volatile("{\n.reg .pred p;\nsetp.ne.b32 p, %98, 0;\nwgmma.mma_async.sync.aligned.m64n192k16.f32.bf16.bf16 {%0,%1,%2,%3,%4,%5,%6,%7,%8,%9,%10,%11,%12,%13,%14,%15,%16,%17,%18,%19,%20,%21,%22,%23,%24,%25,%26,%27,%28,%29,%30,%31,%32,%33,%34,%35,%36,%37,%38,%39,%40,%41,%42,%43,%44,%45,%46,%47,%48,%49,%50,%51,%52,%53,%54,%55,%56,%57,%58,%59,%60,%61,%62,%63,%64,%65,%66,%67,%68,%69,%70,%71,%72,%73,%74,%75,%76,%77,%78,%79,%80,%81,%82,%83,%84,%85,%86,%87,%88,%89,%90,%91,%92,%93,%94,%95}, %96, %97, p, 1, 1, 1, 1;\n}\n"
   : "+f"(d[0]),"+f"(d[1]),"+f"(d[2]),"+f"(d[3]),"+f"(d[4]),"+f"(d[5]),"+f"(d[6]),"+f"(d[7]),"+f"(d[8]),"+f"(d[9]),"+f"(d[10]),"+f"(d[11]),"+f"(d[12]),"+f"(d[13]),"+f"(d[14]),"+f"(d[15]),"+f"(d[16]),"+f"(d[17]),"+f"(d[18]),"+f"(d[19]),"+f"(d[20]),"+f"(d[21]),"+f"(d[22]),"+f"(d[23]),"+f"(d[24]),"+f"(d[25]),"+f"(d[26]),"+f"(d[27]),"+f"(d[28]),"+f"(d[29]),"+f"(d[30]),"+f"(d[31]),"+f"(d[32]),"+f"(d[33]),"+f"(d[34]),"+f"(d[35]),"+f"(d[36]),"+f"(d[37]),"+f"(d[38]),"+f"(d[39]),"+f"(d[40]),"+f"(d[41]),"+f"(d[42]),"+f"(d[43]),"+f"(d[44]),"+f"(d[45]),"+f"(d[46]),"+f"(d[47]),"+f"(d[48]),"+f"(d[49]),"+f"(d[50]),"+f"(d[51]),"+f"(d[52]),"+f"(d[53]),"+f"(d[54]),"+f"(d[55]),"+f"(d[56]),"+f"(d[57]),"+f"(d[58]),"+f"(d[59]),"+f"(d[60]),"+f"(d[61]),"+f"(d[62]),"+f"(d[63]),"+f"(d[64]),"+f"(d[65]),"+f"(d[66]),"+f"(d[67]),"+f"(d[68]),"+f"(d[69]),"+f"(d[70]),"+f"(d[71]),"+f"(d[72]),"+f"(d[73]),"+f"(d[74]),"+f"(d[75]),"+f"(d[76]),"+f"(d[77]),"+f"(d[78]),"+f"(d[79]),"+f"(d[80]),"+f"(d[81]),"+f"(d[82]),"+f"(d[83]),"+f"(d[84]),"+f"(d[85]),"+f"(d[86]),"+f"(d[87]),"+f"(d[88]),"+f"(d[89]),"+f"(d[90]),"+f"(d[91]),"+f"(d[92]),"+f"(d[93]),"+f"(d[94]),"+f"(d[95])
   : "l"(da), "l"(db), "r"(sd));
}

__device__ __forceinline__ void stats_publish(uint32_t sb, int layer, int rb, int hg, int ht, uint32_t tag) {
  const int lane = ht & 31, w = ht >> 5, g = lane >> 2, t = lane & 3, ks = hg & 3;
  uint32_t xa;
  if (layer == 0) {
    const int row = 16 * w + (lane & 15), kc = 2 * ks + (lane >> 4);
    xa = row * 128 + ((kc ^ (row & 7)) << 4);
  } else {
    const int k = 16 * ks + (lane & 7) + 8 * (lane >> 4), pc = 2 * w + ((lane >> 3) & 1);
    xa = k * 128 + ((pc ^ (k & 7)) << 4);
  }
  float s[4] = {0.f, 0.f, 0.f, 0.f}, q[4] = {0.f, 0.f, 0.f, 0.f};
#pragma unroll 1
  for (int c = hg >> 2; c < 8; c += 2) {
    uint32_t A[2][4];
    mbar_wait(sb + SM_BAR + 8 * (B_XF + c), layer);
#pragma unroll
    for (int h = 0; h < 2; h++) {
      if (layer == 0) ldsm4(A[h], sb + SM_X + c * 16384 + h * 8192 + xa);
      else ldsm4t(A[h], sb + SM_X + c * 16384 + h * 8192 + xa);
    }
    if (c >= 6) ATS(48, 256);
    if (c < 2) ATS(51, 256);
#pragma unroll
    for (int r = 0; r < 4; r++)
#pragma unroll
      for (int i = 0; i < 2; i++) {
        const uint32_t v = A[r >> 1][2 * i + (r & 1)];
        const float a = bf_lo(v), b = bf_hi(v);
        s[r] += a + b; q[r] = fmaf(a, a, q[r]); q[r] = fmaf(b, b, q[r]);
      }
  }
#pragma unroll
  for (int r = 0; r < 2; r++) {
    s[r] = ((t & 2) ? s[r + 2] : s[r]) + __shfl_xor_sync(~0u, (t & 2) ? s[r] : s[r + 2], 2);
    q[r] = ((t & 2) ? q[r + 2] : q[r]) + __shfl_xor_sync(~0u, (t & 2) ? q[r] : q[r + 2], 2);
  }
  s[0] = ((t & 1) ? s[1] : s[0]) + __shfl_xor_sync(~0u, (t & 1) ? s[0] : s[1], 1);
  q[0] = ((t & 1) ? q[1] : q[0]) + __shfl_xor_sync(~0u, (t & 1) ? q[0] : q[1], 1);
  st_part(&g_part[(rb * 8 + hg) * 128 + 64 * (t >> 1) + 16 * w + 8 * (t & 1) + g], s[0], q[0], tag);
  ATS(49, 256);
}
__device__ __forceinline__ void stats_gather(uint32_t sb, int rb, int ht, uint32_t tag) {
  const uint2* src = &g_part[rb * 8 * 128 + ht];
  uint2 v[8];
  for (int it = 0;; it++) {
    uint32_t bad = 0;
#pragma unroll
    for (int i = 0; i < 8; i++) v[i] = ld_part(src + i * 128);
#pragma unroll
    for (int i = 0; i < 8; i++) bad |= v[i].y ^ tag;
    if (__all_sync(~0u, (bad & 7u) == 0)) break;
    if (it > (1 << 22)) __trap();
  }
  float s = 0.f, q = 0.f;
#pragma unroll
  for (int i = 0; i < 8; i++) { s += __uint_as_float(v[i].x); q += __uint_as_float(v[i].y); }
  const float mean = s * (1.f / DM);
  const float rstd = rsqrt_approx(fmaxf(q * (1.f / DM) - mean * mean, 0.f) + 1e-5f);
  asm volatile("st.shared.v2.f32 [%0], {%1,%2};" ::"r"(sb + SM_ST + ht * 8), "f"(mean), "f"(rstd) : "memory");
  __syncwarp();
  if (elect_one()) mbar_arrive(sb + SM_BAR + 8 * B_STF);
}
__device__ __forceinline__ void halo_receive(uint32_t sb, int layer, int rb, int hg, int ht) {
  const int lane = ht & 31, h = ht >> 5;
  uint4 kv = make_uint4(0, 0, 0, 0);
  mbar_wait(sb + SM_BAR + 8 * B_SD, layer);
  if (rb & 7) {
    const uint32_t tag = 2 * lds32(sb + SM_EP) + layer + 1;
    const uint4* src = &g_halo[((rb - 1) * 8 + hg) * 192 + h * 48];
    if (layer == 0) delay<D_HALO>(); else delay<D_HALO1>();
    uint4 a;
    uint2 b;
    int it = 0;
    do {
      a = ld_tagged(src + lane); b = ld_part((const uint2*)(src + 32) + lane);
      if (++it > (1 << 22)) __trap();
    } while (!__all_sync(~0u, a.w == tag && b.y == tag));
    kv = make_uint4(a.x, a.y, movm_t(a.z), movm_t(b.x));
  }
  sts128(sb + SM_KVX + h * 512 + lane * 16, kv);
  ATS(61, 256);
  bar_arrive(7, 160);
  if (elect_one()) mbar_arrive(sb + SM_BAR + 8 * B_HF);
}

__device__ __forceinline__ void halo_receive1(uint32_t sb, int layer, int rb, int hg, int lane, uint32_t tag) {
  uint4 a[4];
  uint2 b[4];
  mbar_wait(sb + SM_BAR + 8 * B_SD, layer);
  if (rb & 7) {
    const uint4* src = &g_halo[((rb - 1) * 8 + hg) * 192];
    if (layer == 0) delay<D_HALO>(); else delay<D_HALO1>();
    for (int it = 0;; it++) {
      uint32_t bad = 0;
#pragma unroll
      for (int h = 0; h < 4; h++) { a[h] = ld_tagged(src + h * 48 + lane); b[h] = ld_part((const uint2*)(src + h * 48 + 32) + lane); }
#pragma unroll
      for (int h = 0; h < 4; h++) {
        bad |= (a[h].w ^ tag) | (b[h].y ^ tag);
        a[h].z = movm_t(a[h].z); a[h].w = movm_t(b[h].x);
      }
      if (__all_sync(~0u, bad == 0)) break;
      if (it > (1 << 22)) __trap();
    }
  } else {
#pragma unroll
    for (int h = 0; h < 4; h++) a[h] = make_uint4(0, 0, 0, 0);
  }
#pragma unroll
  for (int h = 0; h < 4; h++) sts128(sb + SM_KVX + h * 512 + lane * 16, a[h]);
  ATS(61, 448);
  bar_arrive(7, 64);
  if (lane < 4) mbar_arrive(sb + SM_BAR + 8 * B_HF);
}

template <bool TR>
__device__ __forceinline__ void gemm_section(float* acc, float2* cs, uint32_t sb, int layer, int wg, int w, int lane) {
  const uint32_t bar = sb + SM_BAR;
  const bool leader = (w == 0) && (lane == 0);
  auto issue = [&](int c, int slot) {
    mbar_wait(bar + 8 * (B_XF + c), layer);
    mbar_wait(bar + 8 * (B_KVF + c), layer);
    const uint64_t da = mkdesc(sb + SM_X + c * 16384 + wg * 8192, TR ? 8192 : 16, 1024, 1);
    const uint64_t db = mkdesc(sb + SM_W + slot * 24576, 8192, 1024, 1);
    wg_fence();
#pragma unroll
    for (int ks = 0; ks < 4; ks++) wgmma_ss<192, TR ? 1 : 0, 1>(acc, da + (TR ? ks * 128 : ks * 2), db + ks * 128, (c | ks) != 0);
    wg_commit();
  };
  auto step = [&](int c, int slot) {
    issue(c, slot);
    wg_wait<1>();
    if (leader) mbar_arrive(bar + 8 * (B_KVE + c - 1));
  };
  if (!TR) bar_sync(0, NTHREADS);
  if (TR && G_WAIT == 3 && wg == 1) bar_sync(14, 256);
  if (TR && G_WAIT == 4 && wg == 1) mbar_wait(bar + 8 * (B_P + 3), 0);
  issue(0, 0);
  if (threadIdx.x == 0) TS(2 + layer * 20 + 0);
  if (threadIdx.x == 128 && layer == 1) TS(60);
  auto ld_cs = [&](int j0) {
#pragma unroll
    for (int j = j0; j < j0 + 8; j++) cs[j] = lds64f(sb + SM_CS + 4 * (8 * j + 2 * (lane & 3)));
  };
  if (TR && CS_STEP == 0) ld_cs(8);
  step(1, 1);
  if (TR && CS_STEP == 0) ld_cs(16);
  if (TR && CS_STEP == 1) ld_cs(8);
  step(2, 2);
  if (TR && CS_STEP == 1) ld_cs(16);
  if (TR && CS_STEP == 2) ld_cs(8);
  step(3, 0);
  if (TR && CS_STEP == 2) ld_cs(16);
  step(4, 1);
  if (TR && CS_STEP == 4) ld_cs(8);
  step(5, 2);
  if (TR && CS_STEP == 4) ld_cs(16);
  if (!TR && !CS_LATE0) { mbar_wait(bar + 8 * B_CSF, 0); ld_cs(8); ld_cs(16); }
  if (wg == 0) bar_sync(5, 256);
  issue(6, 0);
  issue(7, 1);
  if (wg == 1) bar_arrive(5, 256);
  if (!TR && CS_LATE0) { mbar_wait(bar + 8 * B_CSF, 0); ld_cs(8); ld_cs(16); }
}

__device__ __forceinline__ void attn_phase(const Params& p, uint32_t sb, int layer, int rb, int hg, int wg, int w) {
  const int lane = opaque_tid() & 31;
  const int g = lane >> 2, t = lane & 3;
  const uint32_t bar = sb + SM_BAR;
  const int row0 = 64 * wg + 16 * w;
  const bool leader = (w == 0) && (lane == 0);
  float acc[96];
  float2 cs[24];
  if (layer) gemm_section<true>(acc, cs, sb, layer, wg, w, lane);
  else gemm_section<false>(acc, cs, sb, layer, wg, w, lane);
  ATS(41, 224);
  mbar_wait(bar + 8 * B_STF, layer);
  const uint32_t tag = 2 * lds32(sb + SM_EP) + layer + 1;
  const float2 st0 = lds64f(sb + SM_ST + (row0 + g) * 8), st1 = lds64f(sb + SM_ST + (row0 + g + 8) * 8);
  const float mean0 = st0.x, rstd0 = st0.y, mean1 = st1.x, rstd1 = st1.y;
  wg_wait<0>();
  if (threadIdx.x == 0) TS(2 + layer * 20 + 1);
  ATS(39, 224);
  if (leader) mbar_arrive(bar + 8 * B_QDONE);

  uint32_t fp[4][4], fl[4][4], fh[4][4], qa[4][4];
  const int cw = 4 * wg + w;
  {
    const float nm0 = -mean0 * rstd0, nm1 = -mean1 * rstd1;
    const uint32_t kvx = sb + SM_KVX + cw * 2048 + lane * 16;
#pragma unroll
    for (int h = 0; h < 4; h++)
#pragma unroll
      for (int k = 0; k < 4; k++) {
        const int j = 8 + (k >> 1) * 8 + 2 * h + (k & 1);
        fh[h][k] = packbf(fmaf(acc[4 * j + 2], rstd1, nm1 * cs[j].x), fmaf(acc[4 * j + 3], rstd1, nm1 * cs[j].y));
      }
    if (cw == 7) {
      uint4* halo = &g_halo[(rb * 8 + hg) * 192];
#pragma unroll
      for (int h = 0; h < 4; h++) {
        st_tagged3(halo + h * 48 + lane, fh[h][0], fh[h][1], fh[h][2], tag);
        asm volatile("st.relaxed.gpu.global.v2.u32 [%0], {%1,%2};" ::"l"((uint2*)(halo + h * 48 + 32) + lane), "r"(fh[h][3]), "r"(tag) : "memory");
      }
      if (elect_one()) mbar_arrive(bar + 8 * B_SD);
      if (layer == TLAYER && threadIdx.x == 224) TS(47);
    }
#pragma unroll
    for (int h = 0; h < 4; h++) { fh[h][2] = movm_t(fh[h][2]); fh[h][3] = movm_t(fh[h][3]); }
    if (cw != 7) {
#pragma unroll
      for (int h = 0; h < 4; h++) sts128(kvx + 2048 + h * 512, make_uint4(fh[h][0], fh[h][1], fh[h][2], fh[h][3]));
      bar_arrive(8 + cw, 64);
    }
    sched_fence<6>();
    if (layer == TLAYER && threadIdx.x == 0) TS(45);
#pragma unroll
    for (int j = 0; j < 8; j++) cs[j] = lds64f(sb + SM_CS + 4 * (8 * j + 2 * t));
#pragma unroll
    for (int h = 0; h < 4; h++)
#pragma unroll
      for (int k = 0; k < 4; k++) {
        const int j = 8 + (k >> 1) * 8 + 2 * h + (k & 1);
        fl[h][k] = packbf(fmaf(acc[4 * j], rstd0, nm0 * cs[j].x), fmaf(acc[4 * j + 1], rstd0, nm0 * cs[j].y));
        if (k >= 2) fl[h][k] = movm_t(fl[h][k]);
      }
#pragma unroll
    for (int h = 0; h < 4; h++) {
#pragma unroll
      for (int dh = 0; dh < 2; dh++) {
        const int j = 2 * h + dh;
        const float2 c2 = cs[j];
        qa[h][2 * dh] = packbf(fmaf(-mean0, c2.x, acc[4 * j + 0]), fmaf(-mean0, c2.y, acc[4 * j + 1]));
        qa[h][2 * dh + 1] = packbf(fmaf(-mean1, c2.x, acc[4 * j + 2]), fmaf(-mean1, c2.y, acc[4 * j + 3]));
      }
    }
    if (threadIdx.x == 0) TS(2 + layer * 20 + 2);
    sched_fence<0>();
    bar_sync(7 + cw, cw == 0 && !HALO_W14 ? 160 : 64);
#pragma unroll
    for (int h = 0; h < 4; h++) {
      const uint4 v = lds128(kvx + h * 512);
      fp[h][0] = v.x; fp[h][1] = v.y; fp[h][2] = v.z; fp[h][3] = v.w;
    }
    if (threadIdx.x == 0) TS(2 + layer * 20 + 4);
  }

  const bool u0 = 2 * t > g, u1 = 2 * t + 1 > g;
  const uint32_t mU = (u0 ? 0x0000ffffu : 0u) | (u1 ? 0xffff0000u : 0u);
  const float cl2 = 0.25f * 1.4426950408889634f;
  const float sc0 = rstd0 * cl2, sc1 = rstd1 * cl2;
  const float cneg = ((rb & 7) == 0 && cw == 0) ? -INFINITY : 0.f;
  float v[4][4];
#pragma unroll
  for (int h = 0; h < 4; h++) {
    float T0[4] = {cneg, cneg, cneg, cneg}, T1[4] = {0.f, 0.f, 0.f, 0.f}, T2[4] = {0.f, 0.f, 0.f, 0.f};
    mma_bf16(T1, qa[h], fl[h][0], fl[h][1]);
    mma_bf16(T2, qa[h], fh[h][0], fh[h][1]);
    mma_bf16(T0, qa[h], fp[h][0], fp[h][1]);
    v[h][0] = u0 ? T0[0] : T1[0]; v[h][1] = u1 ? T0[1] : T1[1];
    v[h][2] = u0 ? T1[2] : T2[2]; v[h][3] = u1 ? T1[3] : T2[3];
  }
  float m0[4], m1[4];
#pragma unroll
  for (int h = 0; h < 4; h++) { m0[h] = fmaxf(v[h][0], v[h][1]); m1[h] = fmaxf(v[h][2], v[h][3]); }
#pragma unroll
  for (int o = 1; o <= 2; o <<= 1) {
#pragma unroll
    for (int h = 0; h < 4; h++) {
      m0[h] = fmaxf(m0[h], __shfl_xor_sync(~0u, m0[h], o));
      m1[h] = fmaxf(m1[h], __shfl_xor_sync(~0u, m1[h], o));
    }
  }
  float O0[4][4], O1[4][4], Z[4][4];
#pragma unroll
  for (int h = 0; h < 4; h++) {
    const float mm0 = -m0[h] * sc0, mm1 = -m1[h] * sc1;
    const uint32_t P0 = packbf(ex2(fmaf(v[h][0], sc0, mm0)), ex2(fmaf(v[h][1], sc0, mm0)));
    const uint32_t P1 = packbf(ex2(fmaf(v[h][2], sc1, mm1)), ex2(fmaf(v[h][3], sc1, mm1)));
#pragma unroll
    for (int k = 0; k < 4; k++) O0[h][k] = O1[h][k] = Z[h][k] = 0.f;
    mma_bf16_k8(Z[h], P0, P1, 0x3f803f80u);
    mma_bf16_k8(O0[h], P0 & ~mU, P1 & mU, fl[h][2]); mma_bf16_k8(O1[h], P0 & ~mU, P1 & mU, fl[h][3]);
    mma_bf16_k8(O0[h], P0 & mU, 0u, fp[h][2]); mma_bf16_k8(O1[h], P0 & mU, 0u, fp[h][3]);
    mma_bf16_k8(O0[h], 0u, P1 & ~mU, fh[h][2]); mma_bf16_k8(O1[h], 0u, P1 & ~mU, fh[h][3]);
  }
  const uint32_t ob = sb + SM_OST + wg * 8192;
  const int o_row = 16 * w + (lane & 7) + 8 * ((lane >> 3) & 1);
#pragma unroll
  for (int h = 0; h < 4; h++) {
    const float i0 = rcp_approx(Z[h][0]), i1 = rcp_approx(Z[h][2]);
    const int ch = 2 * h + (lane >> 4);
    stsm4(ob + o_row * 128 + ((ch ^ (o_row & 7)) << 4), packbf(O0[h][0] * i0, O0[h][1] * i0), packbf(O0[h][2] * i1, O0[h][3] * i1),
          packbf(O1[h][0] * i0, O1[h][1] * i0), packbf(O1[h][2] * i1, O1[h][3] * i1));
  }
  if (threadIdx.x == 0) TS(2 + layer * 20 + 5);
  ATS(57, 128); ATS(20, 96);
  __syncwarp();
  if (elect_one()) {
    fence_async_smem();
    tma_st(&p.mapO, hg * 64, rb * 128 + row0, ob + w * 2048);
    bulk_commit();
    bulk_wait_all();
    uint32_t old;
    asm volatile("atom.acq_rel.cta.shared.inc.u32 %0, [%1], 7;" : "=r"(old) : "r"(sb + SM_EP + 4) : "memory");
    if (old == 7) {
      asm volatile("red.relaxed.gpu.global.add.u32 [%0], 2;" ::"l"(&g_cnt[(C_O + rb) * 32]) : "memory");
      asm volatile("mbarrier.arrive.shared::cta.b64 _, [%0], 2;" ::"r"(bar + 8 * B_OST) : "memory");
      asm volatile("mbarrier.arrive.shared::cta.b64 _, [%0], 2;" ::"r"(bar + 8 * B_AD) : "memory");
      TS(2 + layer * 20 + 6);
    }
  }
  __syncwarp();
}

__device__ __forceinline__ void proj_phase(const Params& p, uint32_t sb, int layer, int rb, int q, int wg, int w) {
  const int lane = opaque_tid() & 31;
  const bool TR = layer != 0;
  const int t = lane & 3;
  const uint32_t bar = sb + SM_BAR;
  const uint32_t rbx = sb + SM_R + wg * 8192;
  uint32_t res[16];
  mbar_wait(bar + 8 * B_RF, layer);
  if (threadIdx.x == 0) TS(2 + layer * 20 + 7);
  if (!TR) {
#pragma unroll
    for (int j = 0; j < 8; j += 2) {
      const int mi = lane >> 3;
      const int row = 16 * w + (lane & 7) + 8 * (mi & 1), ch = j + (mi >> 1);
      ldsm4(&res[2 * j], rbx + row * 128 + ((ch ^ (row & 7)) << 4));
    }
  } else {
#pragma unroll
    for (int j = 0; j < 8; j += 2) {
      const int mi = lane >> 3;
      const int line = 8 * (j + (mi >> 1)) + (lane & 7), pc = 2 * w + (mi & 1);
      ldsm4t(&res[2 * j], rbx + line * 128 + ((pc ^ (line & 7)) << 4));
    }
  }
  bar_sync(2 + wg, 128);
  float acc[32];
#pragma unroll
  for (int i = 0; i < 16; i++) {
    asm volatile("shl.b32 %0, %1, 16;" : "=f"(acc[2 * i]) : "r"(res[i]));
    asm volatile("and.b32 %0, %1, 0xffff0000;" : "=f"(acc[2 * i + 1]) : "r"(res[i]));
  }
  const uint32_t tag = part_tag(lds32(sb + SM_EP), 2 * layer + 1);
  mbar_wait(bar + 8 * B_ZF, layer);
  mbar_wait(bar + 8 * B_WOF, layer);
#pragma unroll P_UNROLL
  for (int c = 0; c < 8; c++) {
    mbar_wait(bar + 8 * (B_OF + c), layer);
    if (c == 0 && threadIdx.x == 0) TS(2 + layer * 20 + 8);
    const uint64_t da = mkdesc(sb + sm_o(c) + wg * 8192, 16, 1024, 1);
    const uint64_t db = mkdesc(sb + SM_WO + c * 8192, 8192, 1024, 1);
    wg_fence();
#pragma unroll
    for (int ks = 0; ks < 4; ks++) wgmma_ss<64, 0, 1>(acc, da + ks * 2, db + ks * 128, 1);
    wg_commit();
  }
  wg_wait<0>();
#pragma unroll
  for (int i = 0; i < 32; i++) asm volatile("" : "+f"(acc[i]) :: "memory");
  if (threadIdx.x == 0) TS(2 + layer * 20 + 9);
  if (lane == 0 && w == 0) mbar_arrive(bar + 8 * B_PDONE);
  {
    float s[4], qq[4];
#pragma unroll
    for (int k = 0; k < 4; k++) { s[k] = acc[k]; qq[k] = acc[k] * acc[k]; }
#pragma unroll
    for (int j = 1; j < 8; j++)
#pragma unroll
      for (int k = 0; k < 4; k++) { s[k] += acc[4 * j + k]; qq[k] = fmaf(acc[4 * j + k], acc[4 * j + k], qq[k]); }
    const float s0 = s[0] + s[1], s1 = s[2] + s[3], q0 = qq[0] + qq[1], q1 = qq[2] + qq[3];
    float sr = ((t & 1) ? s1 : s0) + __shfl_xor_sync(~0u, (t & 1) ? s0 : s1, 1);
    float qr = ((t & 1) ? q1 : q0) + __shfl_xor_sync(~0u, (t & 1) ? q0 : q1, 1);
    sr += __shfl_xor_sync(~0u, sr, 2);
    qr += __shfl_xor_sync(~0u, qr, 2);
    if (t < 2) st_part(&g_part[(rb * 8 + q) * 128 + 64 * wg + 16 * w + (lane >> 2) + 8 * t], sr, qr, tag);
    __syncwarp();
    if (elect_one()) mbar_arrive(bar + 8 * B_PS);
    sched_fence<7>();
  }
#pragma unroll
  for (int j = 0; j < 8; j += 2) {
    const int mi = lane >> 3;
    const int line = 8 * (j + (mi >> 1)) + (lane & 7), pc = 2 * w + (mi & 1);
    stsm4t(rbx + line * 128 + ((pc ^ (line & 7)) << 4), packbf(acc[4 * j], acc[4 * j + 1]), packbf(acc[4 * j + 2], acc[4 * j + 3]),
           packbf(acc[4 * j + 4], acc[4 * j + 5]), packbf(acc[4 * j + 6], acc[4 * j + 7]));
  }
  fence_writer();
  bar_sync(2 + wg, 128);
  if (w == 0 && elect_one()) {
    fence_reader();
    fence_async_global();
    tma_st(&p.mapXT, rb * 128 + wg * 64, (2 * layer) * DM + q * 64, rbx);
    bulk_commit();
    if (threadIdx.x == 0) TS(2 + layer * 20 + 10);
    bulk_wait_all();
    red_relaxed(&g_cnt[C_CS * 32 + 2 + layer]);
    if (wg == 0) mbar_arrive(bar + 8 * B_RE);
  }
  __syncwarp();
}
__device__ __forceinline__ void proj_stats(uint32_t sb, int layer, int rb, int q, int lane, uint32_t tag) {
  const int r = 16 * q + (lane & 15);
  const uint2* src = &g_part[rb * 8 * 128 + r];
  uint32_t* dst = g_stats + layer * LSEQ + (rb >> 1) * 256 + ((r >> 2) & 1) * 128 + ((rb & 1) * 16 + (r >> 3)) * 4 + (r & 3);
  mbar_wait(sb + SM_BAR + 8 * B_PS, layer);
  delay<D_PST>();
  for (int it = 0;; it++) {
    uint2 v[8];
#pragma unroll
    for (int i = 0; i < 8; i++) v[i] = ld_part(src + i * 128);
    float s[4], qq[4];
    uint32_t bad = 0;
#pragma unroll
    for (int i = 0; i < 4; i++) {
      s[i] = __uint_as_float(v[i].x) + __uint_as_float(v[i + 4].x);
      qq[i] = __uint_as_float(v[i].y) + __uint_as_float(v[i + 4].y);
      bad |= (v[i].y ^ tag) | (v[i + 4].y ^ tag);
    }
    const float mean = ((s[0] + s[1]) + (s[2] + s[3])) * (1.f / DM);
    const float rstd = rsqrt_approx(fmaxf(fmaf((qq[0] + qq[1]) + (qq[2] + qq[3]), 1.f / DM, -mean * mean), 0.f) + 1e-5f);
    const bool ok = __all_sync(~0u, (bad & 7u) == 0);
    if (ok && lane < 16)
      asm volatile("st.relaxed.gpu.global.u32 [%0], %1;" ::"l"(dst), "r"(max(packbf(NORM_FMA ? -mean * rstd : -mean, rstd), 1u)) : "memory");
    if (ok) break;
    if (it > (1 << 22)) __trap();
  }
}

#define NA 14
#define NP 15
template <int M0, int M1> __device__ __forceinline__ void conv_load(uint32_t* A, uint32_t pe) {
#pragma unroll
  for (int m = M0; m < M1; m++) {
    asm volatile("ld.shared.v2.b32 {%0,%1}, [%2];" : "=r"(A[4 * m]), "=r"(A[4 * m + 1]) : "r"(pe + 256 * m) : "memory");
    A[4 * m + 2] = lds32(pe + 256 * m - 4);
  }
}
__device__ __forceinline__ uint32_t copy_reg(uint32_t v, uint32_t zero) { uint32_t r; asm volatile("or.b32 %0, %1, %2;" : "=r"(r) : "r"(v), "r"(zero)); return r; }
__device__ __forceinline__ uint32_t copy_reg2(uint32_t v, uint32_t zero) { uint32_t r; asm volatile("xor.b32 %0, %1, %2;" : "=r"(r) : "r"(v), "r"(zero)); return r; }
__device__ __forceinline__ void conv_park(uint32_t* P, uint32_t pe) {
#pragma unroll
  for (int m = 0; m < NP; m++)
#pragma unroll
    for (int k = 0; k < 3; k++) P[3 * m + k] = lds32(pe + 256 * m - 4 + 4 * k);
}
__device__ __forceinline__ void conv_unpark(uint32_t* A, const uint32_t* P, uint32_t zero) {
#pragma unroll
  for (int m = 0; m < NP; m++) {
    A[4 * m + 2] = copy_reg(P[3 * m], zero); A[4 * m] = copy_reg(P[3 * m + 1], zero);
    A[4 * m + 3] = copy_reg2(P[3 * m + 1], zero); A[4 * m + 1] = copy_reg(P[3 * m + 2], zero);
  }
}
template <int M0, int M1> __device__ __forceinline__ void conv_mmas(float* acc, const uint32_t* A, uint64_t d) {
  if constexpr (M0 < M1) {
    wgmma_rs<128 - 8 * (M0 / 2), 0>(acc, A + 4 * M0, d + (uint64_t)(4 * M0), M0 != 0);
    conv_mmas<M0 + 1, M1>(acc, A, d);
  }
}
struct SumAddr { uint32_t l0, l1, l2, se, so; };
__device__ __forceinline__ SumAddr conv_sum_addr(uint32_t sb, int c) {
  auto ua = [&](int j) { return sb + cv_u(0) + (127 - (j >> 3)) * 16 + (j & 7) * 2; };
  auto sa = [&](int hc) { const int ci = hc & ~1; return sb + cv_s(0) + ((ci >> 3) & 1) * 1024 + (ci >> 4) * 128 + (((ci ^ (ci >> 4)) & 7) << 4) + (hc & 1) * 8; };
  const int j0 = 4 * (c - 1);
  return {ua(j0 - 2), ua(j0), ua(j0 + 4), sa((c + 1) & 127), sa(c) + 2048};
}
__device__ __forceinline__ void sts64(uint32_t a, uint32_t x, uint32_t y) { asm volatile("st.shared.v2.b32 [%0], {%1,%2};" ::"r"(a), "r"(x), "r"(y) : "memory"); }
__device__ __forceinline__ void conv_sums(const SumAddr& sa, int lc, int c) {
  uint32_t e[4], o[4];
  {
    const float2 em = lds64f(sa.l1 + lc * 32768), om = lds64f(sa.l1 + lc * 32768 + CV_UH);
    e[0] = lds32(sa.l0 + lc * 32768); o[0] = lds32(sa.l0 + lc * 32768 + CV_UH);
    e[3] = lds32(sa.l2 + lc * 32768); o[3] = lds32(sa.l2 + lc * 32768 + CV_UH);
    e[1] = __float_as_uint(em.x); e[2] = __float_as_uint(em.y); o[1] = __float_as_uint(om.x); o[2] = __float_as_uint(om.y);
  }
  uint32_t s7e[2], s7o[2], s9e[2], s9o[2];
  uint32_t pw[4], sh[3];
#pragma unroll
  for (int k = 0; k < 4; k++) pw[k] = hadd2(e[k], o[k]);
#pragma unroll
  for (int k = 0; k < 3; k++) sh[k] = __byte_perm(pw[k], pw[k + 1], 0x5432);
#pragma unroll
  for (int k = 0; k < 2; k++) {
    const uint32_t t3 = hadd2(hadd2(sh[k], sh[k + 1]), pw[k + 1]);
    s7e[k] = hadd2(t3, o[k]); s7o[k] = hadd2(t3, e[k + 2]);
    s9e[k] = hadd2(s7o[k], pw[k]); s9o[k] = hadd2(s7e[k], pw[k + 2]);
  }
  if (c == 127) s9e[0] = s9e[1] = s9o[0] = s9o[1] = 0u;
  sts64(sa.se + lc * 32768, s9e[0], s9e[1]); sts64((sa.se ^ 16) + lc * 32768, s9o[0], s9o[1]);
  sts64(sa.so + lc * 32768, s7e[0], s7e[1]); sts64((sa.so ^ 16) + lc * 32768, s7o[0], s7o[1]);
}

__device__ __forceinline__ void conv_epi(uint32_t sb, int layer, int cta, int ch, int c0, uint4 x0, uint4 x1) {
  uint4 v[2][4];
  const uint4 xr[2] = {x0, x1};
  mbar_wait(sb + SM_BAR + 8 * (B_P + ch), layer);
#pragma unroll
  for (int u = 0; u < 2; u++) {
    const uint32_t pb = sb + cv_pb(ch) + u * (CV_PBW / 2) + c0 * 16;
#pragma unroll
    for (int k = 0; k < 4; k++) v[u][k] = lds128(pb + k * CV_PBW);
  }
#pragma unroll
  for (int u = 0; u < 2; u++) {
    uint4 o;
    o.x = hadd2(xr[u].x, hadd2(hadd2(v[u][0].x, v[u][1].x), hadd2(v[u][2].x, v[u][3].x)));
    o.y = hadd2(xr[u].y, hadd2(hadd2(v[u][0].y, v[u][1].y), hadd2(v[u][2].y, v[u][3].y)));
    o.z = hadd2(xr[u].z, hadd2(hadd2(v[u][0].z, v[u][1].z), hadd2(v[u][2].z, v[u][3].z)));
    o.w = hadd2(xr[u].w, hadd2(hadd2(v[u][0].w, v[u][1].w), hadd2(v[u][2].w, v[u][3].w)));
    if (layer == 0) sts128(sb + cv_s(ch) + (c0 + 128 * u) * 16, o);
    else st_tagged3((uint4*)(g_xT + (size_t)(3 * DM + cv_chan(cta, ch)) * LSEQ) + c0 + 128 * u, o.x, o.y, o.z, o.w);
  }
}
__device__ __forceinline__ void warp_release(uint32_t b) {
  fence_writer();
  __syncwarp();
  if (elect_one()) mbar_arrive(b);
}

__device__ __forceinline__ void conv_prep_load(uint32_t sb, int layer, int cta, int c, uint4 (&xr)[4], uint4 (&st)[4]) {
  sched_fence<8>();
  mbar_wait(sb + SM_BAR + 8 * B_GB, layer);
  if (threadIdx.x == 0) TS(2 + layer * 20 + 11);
  xr[0] = ld_tagged((const uint4*)(g_xT + (size_t)(2 * layer * DM + cta) * LSEQ) + c);
#pragma unroll
  for (int i = 0; i < 2; i++) st[i] = ld_tagged((const uint4*)g_stats + layer * 512 + (c >> 5) * 64 + i * 32 + (c & 31));
}
template <bool HELPER>
__device__ __forceinline__ void conv_prep(uint32_t sb, int layer, int cta, int c, uint4 (&xr)[4], uint4 (&st)[4], const SumAddr& sa) {
  const uint32_t bar = sb + SM_BAR;
  const uint4* xin = (const uint4*)(g_xT + (size_t)(2 * layer * DM + cta) * LSEQ) + c;
  for (int it = 0;; it++) {
    const uint32_t vs = min(min(min(st[0].x, st[0].y), min(st[0].z, st[0].w)), min(min(st[1].x, st[1].y), min(st[1].z, st[1].w)));
    if (__all_sync(~0u, vs != 0 && xr[0].x != ~0u)) break;
    if (it > (1 << 22)) __trap();
    if (!__all_sync(~0u, xr[0].x != ~0u)) xr[0] = ld_tagged(xin);
    if (!__all_sync(~0u, vs != 0)) {
#pragma unroll
      for (int i = 0; i < 2; i++) st[i] = ld_tagged((const uint4*)g_stats + layer * 512 + (c >> 5) * 64 + i * 32 + (c & 31));
    }
  }
  const uint32_t nm[4] = {__byte_perm(st[0].x, st[0].y, 0x5410), __byte_perm(st[0].z, st[0].w, 0x5410), __byte_perm(st[1].x, st[1].y, 0x5410), __byte_perm(st[1].z, st[1].w, 0x5410)};
  const uint32_t rs[4] = {__byte_perm(st[0].x, st[0].y, 0x7632), __byte_perm(st[0].z, st[0].w, 0x7632), __byte_perm(st[1].x, st[1].y, 0x7632), __byte_perm(st[1].z, st[1].w, 0x7632)};
  if (threadIdx.x == 0) TS(2 + layer * 20 + 12);
  const int a = c & 127, h = c >> 7;
#pragma unroll
  for (int i = 0; i < 4; i++) {
    if (i == 1) {
      mbar_wait(bar + 8 * B_XV, layer);
#pragma unroll
      for (int j = 1; j < 4; j++) xr[j] = ld_tagged(xin + j * (128 * LSEQ / 8));
      if (HELPER) {
        mbar_wait(bar + 8 * B_U, layer);
        conv_sums(sa, 0, c);
        fence_async_smem();
        bar_arrive(7, 256);
        sched_fence<1>();
        if (layer == 1 && c == 0) TS(46);
      }
    }
    const uint32_t x[4] = {xr[i].x, xr[i].y, xr[i].z, xr[i].w};
    uint32_t u[4];
#pragma unroll
    for (int k = 0; k < 4; k++)
      u[k] = NORM_FMA ? hfma2(x[k], rs[k], nm[k]) : hmul2(hadd2(x[k], nm[k]), rs[k]);
    sts128(sb + cv_u(i) + h * CV_UH + (127 - a) * 16, make_uint4(u[0], u[1], u[2], u[3]));
    warp_release(bar + 8 * (B_U + i));
    sched_fence<2>();
  }
}
__device__ __forceinline__ void conv_zero(uint32_t sb, int ht) {
  if (ht < 96) {
    const int ch = ht / 24, h2 = (ht / 12) & 1, qq = ht % 12;
    sts128(sb + cv_u(ch) + h2 * CV_UH + (128 + qq) * 16, make_uint4(0, 0, 0, 0));
  }
  if (ht >= 80) {
    const int i = ht - 80, ch = i / 12, q2 = i % 12;
    const int w2 = q2 < 2 ? 1 : q2 < 6 ? 2 : 3, cc = q2 < 2 ? q2 : q2 < 6 ? q2 - 2 : q2 - 6;
    sts128(sb + cv_pb(ch) + w2 * CV_PBW + (cc & 1) * (CV_PBW / 2) + (cc >> 1) * 16, make_uint4(0, 0, 0, 0));
  }
}

#define HANDOVER 1
template <int R>
__device__ __forceinline__ void conv_round(uint32_t sb, int layer, int wg, uint32_t* A, const uint32_t* P, uint32_t pb, uint32_t pe2) {
  const uint32_t bar = sb + SM_BAR;
  const int ch = 2 * R + 1 - wg;
  float acc[64];
  const uint64_t d = mkdesc(sb + cv_u(ch), CV_UH, 128, 0);
  FTS(39);
  if (R == 0) {
    mbar_wait(bar + 8 * (B_U + ch), layer);
    fence_reader();
  }
  sched_fence<3>();
  if (R == 1 || wg == 0) bar_sync(10 + ch, 256);
  if (layer == 0 && ch > 0 && ((PAUSE >> (ch - 1)) & 1)) mbar_wait(bar + 8 * (B_E + ch - 1), 0);
  if (layer == 0 && ch > 0 && ((PAUSE >> (ch + 3)) & 1)) mbar_wait(bar + 8 * (B_P + ch - 1), 0);
  FTS(41);
  if (ch == 0 && threadIdx.x == 128) TS(2 + layer * 20 + 13);
  wg_fence();
  conv_mmas<0, 1>(acc, A, d); conv_mmas<2, NA + 1>(acc, A, d);
  wg_commit();
  FTS(51);
  if (HANDOVER == 0 && (R == 0 || wg == 1)) bar_arrive(11 + ch, 256);
  bar_sync(7 + ch, 256);
  wg_fence();
  conv_mmas<1, 2>(acc, A, d); conv_mmas<NA + 1, 17>(acc, A, d);
  wgmma_ss<64, 1, 1>(acc, mkdesc(sb + cv_s(ch), 1024, 1024, 1), mkdesc(sb + cv_ft(ch), 256, 16, 0), 1);
  wgmma_ss<64, 1, 1>(acc, mkdesc(sb + cv_s(ch) + 2048, 1024, 1024, 1), mkdesc(sb + cv_ft(ch) + 512, 256, 16, 0), 1);
  wg_commit();
  if (HANDOVER == 1 && (R == 0 || wg == 1 || (G_WAIT == 3 && layer == 0))) bar_arrive(11 + ch, 256);
  FTS(61);
  wg_wait<0>();
#pragma unroll
  for (int j = 0; j < 16; j += 2)
    stsm4t(pb + R * 65536 - j * 128, packbf(acc[4 * j], acc[4 * j + 1]), packbf(acc[4 * j + 2], acc[4 * j + 3]),
           packbf(acc[4 * j + 4], acc[4 * j + 5]), packbf(acc[4 * j + 6], acc[4 * j + 7]));
  __syncwarp();
  if (elect_one()) mbar_arrive(bar + 8 * (B_P + ch));
  if (threadIdx.x == 0) TS(2 + layer * 20 + 14 + R);
  FTS(57);
  if (R == 0) {
    conv_unpark(A, P, opaque_tid() >> 10);
    mbar_wait(bar + 8 * (B_U + ch + 2), layer);
    fence_reader();
    conv_load<NP, 17>(A, pe2);
#pragma unroll
    for (int m = NP; m < 17; m++) A[4 * m + 3] = lds32(pe2 + 256 * m);
  }
}
__device__ __forceinline__ void conv_phase(const Params& p, uint32_t sb, int layer, int cta) {
  const int tid = opaque_tid();
  const int wg = __shfl_sync(~0u, tid >> 7, 0), w = __shfl_sync(~0u, (tid >> 5) & 3, 0);
  const uint32_t bar = sb + SM_BAR;
  uint32_t A[68], P[3 * NP];
  const uint32_t pe = sb + cv_pe(1 - wg) + 4 * (16 + 16 * w + 2 * ((tid & 31) >> 2) - 4 * (tid & 3));
  mbar_wait(bar + 8 * B_PE, layer);
  conv_load<0, 17>(A, pe);
#pragma unroll
  for (int m = 0; m < 17; m++) A[4 * m + 3] = copy_reg(A[4 * m], tid >> 10);
  if (wg == 0) {
    uint4 xr[4], st[4];
    if (PARK_FIRST) conv_park(P, pe + 65536);
    conv_prep_load(sb, layer, cta, tid + 128, xr, st);
    if (!PARK_FIRST) conv_park(P, pe + 65536);
    conv_prep<false>(sb, layer, cta, opaque_tid() + 128, xr, st, SumAddr());
  } else {
    conv_park(P, pe + 65536);
  }
  uint32_t pb;
  {
    const int l2 = opaque_tid() & 31, mt = l2 >> 3;
    pb = sb + cv_pb(1 - wg) + w * CV_PBW + (mt & 1) * (CV_PBW / 2) + (127 - 8 * (mt >> 1) - (l2 & 7) + w) * 16;
  }
  conv_round<0>(sb, layer, wg, A, P, pb, pe + 65536);
  conv_round<1>(sb, layer, wg, A, P, pb, 0);
  if (G_WAIT == 1 && layer == 0) mbar_wait(bar + 8 * (B_E + 3), layer);
  if (G_WAIT == 2 && layer == 0) mbar_wait(bar + 8 * (B_P + 3), layer);
}

__device__ __forceinline__ void final_phase(const Params& p, uint32_t sb, int cta, int wg, int w) {
  const int lane = opaque_tid() & 31, g = lane >> 2, t = lane & 3;
  constexpr int RS = 2 * DM;
  int it = 0;
  {
    const int lc = wg ? 0 : 3;
    const int p0 = (cta & 15) * 128 + 32 * w, c0 = 128 * lc + (cta >> 4) * 16;
    const bf16* src = g_xT + (size_t)(3 * DM + c0 + 4 * (g >> 1) + (g & 1)) * LSEQ + p0 + 8 * t;
    bf16* dst = p.out + (size_t)(2 * ((p0 & 1023) + 8 * (g >> 1) + (g & 1)) + (p0 >> 10)) * DM + c0 + 4 * t;
    if (wg == 0) {
      mbar_wait(sb + SM_BAR + 8 * (B_E + 3), 1);
      delay<D_FIN>();
    }
    uint4 a, b;
    for (;;) {
      a = ld_tagged((const uint4*)src); b = ld_tagged((const uint4*)(src + 2 * LSEQ));
      if (__all_sync(~0u, max(a.x, b.x) != ~0u)) break;
      if (++it > (1 << 22)) __trap();
    }
    if (threadIdx.x == 0) TS(42);
    *(uint2*)dst = make_uint2(movm_t(a.x), movm_t(b.x));
    *(uint2*)(dst + 2 * RS) = make_uint2(movm_t(a.y), movm_t(b.y));
    *(uint2*)(dst + 4 * RS) = make_uint2(movm_t(a.z), movm_t(b.z));
    *(uint2*)(dst + 6 * RS) = make_uint2(movm_t(a.w), movm_t(b.w));
  }
  if (wg == 1) {
    const int lc = 1 + (w >> 1);
    const int p0 = (cta & 31) * 64 + 32 * (w & 1), c0 = 128 * lc + (cta >> 5) * 32;
    const bf16* src = g_xT + (size_t)(3 * DM + c0 + 8 * (g >> 1) + (g & 1)) * LSEQ + p0 + 8 * t;
    bf16* dst = p.out + (size_t)(2 * ((p0 & 1023) + 8 * (g >> 1) + (g & 1)) + (p0 >> 10)) * DM + c0 + 8 * t;
    mbar_wait(sb + SM_BAR + 8 * (B_E + lc), 1);
    if (lc >= FIN_D0) delay<D_FIN2>();
    uint4 v[4];
    for (;;) {
#pragma unroll
      for (int q = 0; q < 4; q++) v[q] = ld_tagged((const uint4*)(src + 2 * q * LSEQ));
      if (__all_sync(~0u, max(max(v[0].x, v[1].x), max(v[2].x, v[3].x)) != ~0u)) break;
      if (++it > (1 << 22)) __trap();
    }
    *(uint4*)dst = make_uint4(movm_t(v[0].x), movm_t(v[1].x), movm_t(v[2].x), movm_t(v[3].x));
    *(uint4*)(dst + 2 * RS) = make_uint4(movm_t(v[0].y), movm_t(v[1].y), movm_t(v[2].y), movm_t(v[3].y));
    *(uint4*)(dst + 4 * RS) = make_uint4(movm_t(v[0].z), movm_t(v[1].z), movm_t(v[2].z), movm_t(v[3].z));
    *(uint4*)(dst + 6 * RS) = make_uint4(movm_t(v[0].w), movm_t(v[1].w), movm_t(v[2].w), movm_t(v[3].w));
  }
  if (threadIdx.x == 0) TS(43);
  if (threadIdx.x == 192) TS(63);
  if (threadIdx.x == 160) TS(53);
  if (threadIdx.x == 0) LTS(1);
}

struct cplx { float r, i; };
__device__ __forceinline__ cplx cmul(cplx a, cplx b) { return {fmaf(a.r, b.r, -a.i * b.i), fmaf(a.r, b.i, a.i * b.r)}; }
__device__ __forceinline__ cplx csqr(cplx a) { return {fmaf(a.r, a.r, -a.i * a.i), (a.r + a.r) * a.i}; }
__device__ __forceinline__ cplx cexp_l(float ar2, float ai, float l) {
  const float m = ex2(ar2 * l);
  const float x = ai * l;
  return {m * __cosf(x), m * __sinf(x)};
}

__device__ __forceinline__ void colsum_publish(uint32_t sb, int rb, int hg, int ht, uint32_t tag) {
  const int lane = ht & 31, q = lane & 15, h = lane >> 4;
  const uint32_t src = sb + SM_CW + (ht >> 5) * 4096 + h * 128 + (q & 1) * 8;
  float s[4] = {0.f, 0.f, 0.f, 0.f};
#pragma unroll 8
  for (int r = 0; r < 16; r++) {
    const float2 v = lds64f(src + r * 256 + (((q >> 1) ^ ((2 * r + h) & 7)) << 4));
    s[0] += bf_lo(__float_as_uint(v.x)); s[1] += bf_hi(__float_as_uint(v.x));
    s[2] += bf_lo(__float_as_uint(v.y)); s[3] += bf_hi(__float_as_uint(v.y));
  }
#pragma unroll
  for (int k = 0; k < 4; k++) s[k] += __shfl_xor_sync(~0u, s[k], 16);
  if (h == 0)
    st_tagged3(&g_colsum[(hg * 16 + rb) * 48 + (ht >> 5) * 16 + q], (__float_as_uint(s[0]) & ~7u) | tag, __float_as_uint(s[1]),
               __float_as_uint(s[2]), __float_as_uint(s[3]));
}
__device__ __forceinline__ void colsum_gather(uint32_t sb, int hg, int ht, uint32_t tag) {
  const int lane = ht & 31, rec = (ht >> 5) * 16 + (lane & 15);
  const uint4* src = &g_colsum[(hg * 16 + (lane >> 4) * 8) * 48 + rec];
  float s[4] = {0.f, 0.f, 0.f, 0.f};
#pragma unroll 1
  for (int h = 0; h < 2; h++, src += 4 * 48) {
    uint4 v[4];
    int it = 0;
    do {
#pragma unroll
      for (int i = 0; i < 4; i++) v[i] = ld_tagged(src + i * 48);
      if (++it > (1 << 22)) __trap();
    } while (!__all_sync(~0u, (v[0].x & 7u) == tag && (v[1].x & 7u) == tag && (v[2].x & 7u) == tag && (v[3].x & 7u) == tag));
#pragma unroll
    for (int i = 0; i < 4; i++) {
      s[0] += __uint_as_float(v[i].x & ~7u); s[1] += __uint_as_float(v[i].y); s[2] += __uint_as_float(v[i].z); s[3] += __uint_as_float(v[i].w);
    }
  }
#pragma unroll
  for (int k = 0; k < 4; k++) s[k] += __shfl_xor_sync(~0u, s[k], 16);
  if (lane < 16) sts128f(sb + SM_CS + rec * 16, s[0], s[1], s[2], s[3]);
}

__device__ __forceinline__ uint32_t packh(float lo, float hi) { uint32_t r; asm("cvt.rn.f16x2.f32 %0, %1, %2;" : "=r"(r) : "f"(hi), "f"(lo)); return r; }
__device__ __forceinline__ void mma_f16(float* d, uint32_t a0, uint32_t a1, uint32_t a2, uint32_t a3, uint32_t b0, uint32_t b1) {
  asm volatile("mma.sync.aligned.m16n8k16.row.col.f32.f16.f16.f32 {%0,%1,%2,%3}, {%4,%5,%6,%7}, {%8,%9}, {%0,%1,%2,%3};"
      : "+f"(d[0]), "+f"(d[1]), "+f"(d[2]), "+f"(d[3]) : "r"(a0), "r"(a1), "r"(a2), "r"(a3), "r"(b0), "r"(b1));
}
struct HSeed { uint32_t r, i; };
__device__ __forceinline__ HSeed hseed(cplx s) { return {packh(s.r, s.r), packh(s.i, s.i)}; }
__device__ __forceinline__ void hcmul(uint32_t& o_r, uint32_t& o_i, uint32_t br, uint32_t bi, HSeed s) {
  asm("{\n.reg .b32 t, u;\nmul.rn.f16x2 t, %3, %5;\nneg.f16x2 t, t;\nmul.rn.f16x2 u, %3, %4;\nfma.rn.f16x2 %0, %2, %4, t;\nfma.rn.f16x2 %1, %2, %5, u;\n}"
      : "=&r"(o_r), "=&r"(o_i) : "r"(br), "r"(bi), "r"(s.r), "r"(s.i));
}
struct HTile { uint32_t r[4], i[4]; };
__device__ __forceinline__ void tile_set(HTile& t, int k, cplx a, cplx b) { t.r[k] = packh(a.r, b.r); t.i[k] = packh(a.i, b.i); }
__device__ __forceinline__ void tile_upper(HTile& t, HSeed s) { hcmul(t.r[2], t.i[2], t.r[0], t.i[0], s); hcmul(t.r[3], t.i[3], t.r[1], t.i[1], s); }
__device__ __forceinline__ HTile tile_shift(const HTile& t, HSeed s) {
  HTile o;
#pragma unroll
  for (int k = 0; k < 4; k++) hcmul(o.r[k], o.i[k], t.r[k], t.i[k], s);
  return o;
}
__device__ __forceinline__ void tile_put(const HTile& t, uint32_t a) {
  sts128(a, make_uint4(t.r[0], t.r[1], t.r[2], t.r[3]));
  sts128(a + 512, make_uint4(t.i[0], t.i[1], t.i[2], t.i[3]));
}
__device__ __forceinline__ HTile tile_get(uint32_t a) { HTile o; ldsm4t(o.r, a); ldsm4t(o.i, a + 512); return o; }
__device__ __forceinline__ void tile_mma(float* T, const HTile& a0, const HTile& a1, const HTile& b) {
  mma_f16(T, a0.r[0], a0.r[1], a0.r[2], a0.r[3], b.r[0], b.r[1]);
  mma_f16(T, a0.i[0], a0.i[1], a0.i[2], a0.i[3], b.i[0], b.i[1]);
  mma_f16(T, a1.r[0], a1.r[1], a1.r[2], a1.r[3], b.r[2], b.r[3]);
  mma_f16(T, a1.i[0], a1.i[1], a1.i[2], a1.i[3], b.i[2], b.i[3]);
}
__device__ __forceinline__ void tile_mma2(float* T, float* U, const HTile& a0, const HTile& a1, const HTile& b, const HTile& c) {
  mma_f16(T, a0.r[0], a0.r[1], a0.r[2], a0.r[3], b.r[0], b.r[1]);
  mma_f16(U, a0.r[0], a0.r[1], a0.r[2], a0.r[3], c.r[0], c.r[1]);
  mma_f16(T, a0.i[0], a0.i[1], a0.i[2], a0.i[3], b.i[0], b.i[1]);
  mma_f16(U, a0.i[0], a0.i[1], a0.i[2], a0.i[3], c.i[0], c.i[1]);
  mma_f16(T, a1.r[0], a1.r[1], a1.r[2], a1.r[3], b.r[2], b.r[3]);
  mma_f16(U, a1.r[0], a1.r[1], a1.r[2], a1.r[3], c.r[2], c.r[3]);
  mma_f16(T, a1.i[0], a1.i[1], a1.i[2], a1.i[3], b.i[2], b.i[3]);
  mma_f16(U, a1.i[0], a1.i[1], a1.i[2], a1.i[3], c.i[2], c.i[3]);
}
__device__ __forceinline__ void kgen_unit(uint32_t tab, uint32_t taba, float ar2, float ai, cplx c, float (&T)[5][4]) {
  const cplx z1 = cexp_l(ar2, ai, 1.f), z16 = cexp_l(ar2, ai, 16.f), z256 = cexp_l(ar2, ai, 256.f);
  HTile a0, a1, b0, b1;
  {
    const cplx y1 = {z16.r, -z16.i}, y2 = csqr(y1), y3 = cmul(y2, y1), y4 = csqr(y2), y5 = cmul(y4, y1), y6 = csqr(y3), y7 = cmul(y4, y3);
    HTile t;
    tile_set(t, 0, {1.f, 0.f}, y1); tile_set(t, 1, y2, y3); tile_set(t, 2, y4, y5); tile_set(t, 3, y6, y7);
    const HTile u = tile_shift(t, hseed(csqr(y4)));
    __syncwarp();
    tile_put(t, tab); tile_put(u, tab + 1024);
    __syncwarp();
    a0 = tile_get(taba); a1 = tile_get(taba + 256);
  }
  const cplx z2 = csqr(z1), z4 = csqr(z2), z8 = csqr(z4);
  const HSeed h8 = hseed(z8);
  const cplx d = cmul(c, z256), e = cmul(d, z256);
  {
    const cplx z512 = csqr(z256), f = cmul(e, z512), f8 = cmul(f, z8), f16 = cmul(f, z16), e4 = cmul(e, z4);
    HTile t, u;
    tile_set(t, 0, e4, cmul(e, z8)); tile_set(t, 1, cmul(e4, z8), cmul(e, z16));
    tile_upper(t, hseed(z256));
    tile_set(u, 0, f8, f16); tile_set(u, 1, cmul(f8, z256), cmul(f16, z256));
    tile_upper(u, hseed(z512));
    __syncwarp();
    tile_put(t, tab); tile_put(u, tab + 1024);
    __syncwarp();
    b0 = tile_get(tab); b1 = tile_get(tab + 1024);
  }
  {
    const cplx d2 = cmul(d, z2), d4 = cmul(d, z4);
    HTile t;
    tile_set(t, 0, d2, d4); tile_set(t, 1, cmul(d2, z4), cmul(d, z8));
    tile_upper(t, h8);
    __syncwarp();
    tile_put(t, tab);
    __syncwarp();
    tile_mma2(T[3], T[4], a0, a1, b0, b1);
    b0 = tile_get(tab);
  }
  {
    const cplx c1 = cmul(c, z1), c2 = cmul(c, z2), c3 = cmul(c1, z2), c4 = cmul(c, z4);
    HTile t;
    tile_set(t, 0, c1, c2); tile_set(t, 1, c3, c4); tile_set(t, 2, cmul(c1, z4), cmul(c2, z4)); tile_set(t, 3, cmul(c3, z4), cmul(c4, z4));
    const HTile u = tile_shift(t, h8);
    __syncwarp();
    tile_put(t, tab); tile_put(u, tab + 1024);
    __syncwarp();
    tile_mma(T[2], a0, a1, b0);
    b0 = tile_get(tab); b1 = tile_get(tab + 1024);
    tile_mma2(T[0], T[1], a0, a1, b0, b1);
  }
}
struct ModeIn { uint2 ar, ai, br, bi, cr, ci; };
__device__ __forceinline__ ModeIn load_modes(const Params& p, int idx) {
  return {*(const uint2*)(p.a_re + idx), *(const uint2*)(p.a_im + idx), *(const uint2*)(p.b_re + idx),
          *(const uint2*)(p.b_im + idx), *(const uint2*)(p.c_re + idx), *(const uint2*)(p.c_im + idx)};
}
__device__ __forceinline__ float bf_el(uint2 v, int k) { const uint32_t x = (k & 2) ? v.y : v.x; return (k & 1) ? bf_hi(x) : bf_lo(x); }
struct KGen { float4 cur; float T[5][4]; };
__device__ __forceinline__ uint32_t kgen_slot(uint32_t sb, int ht, int u) {
  return sb + (u < 3 ? SM_KC + (ht >> 5) * (KC_STRIDE * 2) + (u - 1) * 512 + (ht & 31) * 16 + 16 : SM_HALO + 1024 + ht * 16);
}
__device__ __forceinline__ void kgen_setup(KGen& s, uint32_t sb, int cta, int ht, const ModeIn& in, bf16 logdt, bf16 dskip) {
  const float dt = __bfloat162float(__float2bfloat16_rn(expf(__bfloat162float(logdt))));
  float mx = 0.f, k0 = 0.f, ar2[4];
  cplx c[4];
#pragma unroll
  for (int k = 0; k < 4; k++) {
    ar2[k] = (dt * bf_el(in.ar, k)) * 1.4426950408889634f;
    c[k] = cmul({bf_el(in.cr, k), bf_el(in.ci, k)}, {dt * bf_el(in.br, k), dt * bf_el(in.bi, k)});
    k0 += c[k].r;
    mx = fmaxf(mx, fmaxf(fabsf(c[k].r), fabsf(c[k].i)) * ex2(fmaxf(ar2[k] * 2048.f, 0.f)));
  }
  const int ex = min(max(267 - (int)(__reduce_max_sync(~0u, __float_as_uint(mx)) >> 23), 1), 253);
  const float sc = __uint_as_float(ex << 23);
#pragma unroll
  for (int o = 16; o > 0; o >>= 1) k0 += __shfl_xor_sync(~0u, k0, o);
  if ((ht & 31) == 0) {
    const uint32_t kc = sb + SM_KC + (ht >> 5) * (KC_STRIDE * 2);
    sts16(kc, __bfloat16_as_ushort(__float2bfloat16_rn(k0 + __bfloat162float(dskip))));
    sts16(kc + 641 * 2, 0);
    sts32f(kc + 644 * 2, __uint_as_float((254 - ex) << 23));
  }
  s.cur = make_float4(ar2[0], dt * bf_el(in.ai, 0), c[0].r * sc, c[0].i * sc);
#pragma unroll
  for (int k = 1; k < 4; k++) sts128f(kgen_slot(sb, ht, k), ar2[k], dt * bf_el(in.ai, k), c[k].r * sc, c[k].i * sc);
#pragma unroll
  for (int i = 0; i < 5; i++) s.T[i][0] = s.T[i][1] = s.T[i][2] = s.T[i][3] = 0.f;
}
__device__ __forceinline__ void kgen_finish(KGen& s, uint32_t sb, int cta, int ht) {
  const int w = ht >> 5, lane = ht & 31, g = lane >> 2, t = lane & 3;
  const uint32_t kc = sb + SM_KC + w * KC_STRIDE * 2;
  __syncwarp();
  const float inv = __uint_as_float(lds32(kc + 644 * 2));
  auto put = [&](int idx, float v) {
    sts16(kc + idx * 2, __bfloat16_as_ushort(__float2bfloat16_rn(v)));
  };
#pragma unroll
  for (int hi = 0; hi < 2; hi++)
#pragma unroll
    for (int lo = 0; lo < 2; lo++) {
      const int i = g + 8 * hi, j = 2 * t + lo, e = 2 * hi + lo;
      put(16 * i + 1 + j, s.T[0][e] * inv);
      put(16 * i + 9 + j, s.T[1][e] * inv);
      put(257 + 8 * i + j, s.T[2][e] * inv);
      put(385 + 4 * i + (j & 3) + 64 * (j >> 2), s.T[3][e] * inv);
      put(513 + 2 * i + lo + 32 * t, s.T[4][e] * inv);
    }
}

__device__ __forceinline__ void expand_taps(uint32_t sb, int ht) {
  const int ch = ht >> 5, lane = ht & 31;
  const uint32_t kc = sb + SM_KC + ch * KC_STRIDE * 2;
  const uint32_t dst0 = sb + cv_pe(ch);
  auto put = [&](int G, uint32_t u0, uint32_t u1, uint32_t v0, uint32_t v1, uint32_t v2, uint32_t v3, uint32_t v4, uint32_t v5, uint32_t v6, uint32_t v7) {
    const uint32_t dst = dst0 + G * 32;
    sts128(dst, make_uint4(v0 | (u0 << 16), v1 | (u1 << 16), v2 | (v0 << 16), v3 | (v1 << 16)));
    sts128(dst + 16, make_uint4(v4 | (v2 << 16), v5 | (v3 << 16), v6 | (v4 << 16), v7 | (v5 << 16)));
  };
  {
    const uint4 q = lds128(kc + lane * 16);
    const uint32_t pv = lane ? lds32(kc + lane * 16 - 4) : 0u;
    const uint32_t dst = dst0 + (lane + 2) * 32;
    sts128(dst, make_uint4(__byte_perm(q.x, pv, 0x5410), __byte_perm(q.x, pv, 0x7632), __byte_perm(q.y, q.x, 0x5410), __byte_perm(q.y, q.x, 0x7632)));
    sts128(dst + 16, make_uint4(__byte_perm(q.z, q.y, 0x5410), __byte_perm(q.z, q.y, 0x7632), __byte_perm(q.w, q.z, 0x5410), __byte_perm(q.w, q.z, 0x7632)));
    if (lane < 4) sts128(dst0 + lane * 16, make_uint4(0, 0, 0, 0));
  }
  uint32_t a[5], b[2][3], fv[4];
  {
    const uint32_t s1 = kc + 2 * (256 + 4 * lane);
#pragma unroll
    for (int k = 0; k < 5; k++) a[k] = lds16(s1 + 2 * k);
#pragma unroll
    for (int u = 0; u < 2; u++) {
      const uint32_t s2 = kc + 2 * (384 + 2 * (lane + 32 * u));
#pragma unroll
      for (int k = 0; k < 3; k++) b[u][k] = lds16(s2 + 2 * k);
    }
#pragma unroll
    for (int k = 0; k < 4; k++) fv[k] = lds16(kc + 2 * (640 - 4 * lane - k));
  }
  const uint32_t am1 = lds16(kc + 2 * (lane ? 256 + 4 * lane : 255)), am2 = lds16(kc + 2 * (lane ? 255 + 4 * lane : 254));
  const uint32_t bm2 = lds16(kc + 2 * (lane ? 384 + 2 * lane : 383)), k1024 = lds16(kc + 2 * 512);
  put(34 + lane, am2, am1, a[0], a[0], a[1], a[2], a[2], a[2], a[3], a[4]);
#pragma unroll
  for (int u = 0; u < 2; u++) put(66 + lane + 32 * u, u ? b[u][0] : bm2, b[u][0], b[u][0], b[u][0], b[u][0], b[u][1], b[u][1], b[u][1], b[u][2], b[u][2]);
  if (lane < 10) {
    const uint32_t v = lane == 0 ? k1024 : 0u;
    put(130 + lane, v, v, v, v, v, v, v, 0u, 0u, 0u);
  }
  const uint32_t ft = sb + cv_ft(ch) + 4 * lane;
#pragma unroll
  for (int ty = 0; ty < 2; ty++) {
    const uint32_t v = fv[ty] | (fv[ty + 2] << 16);
    sts32f(ft + ty * 512, __uint_as_float(v));
    sts32f(ft + ty * 512 + 128, 0.f);
    sts32f(ft + ty * 512 + 256 + (lane < 2 ? 120 : -8), __uint_as_float(lane < 2 ? 0u : v));
    sts32f(ft + ty * 512 + 384, 0.f);
  }
}

__device__ __forceinline__ int role_id() { int v; asm volatile("mov.u32 %0, %%ctaid.x;" : "=r"(v)); return v; }
#define GMAP 8
__device__ __forceinline__ int role_rb(int cta) { return 4 * (cta >> 5) + (cta & 3); }
__device__ __forceinline__ int role_hg(int cta) { return 2 * (((cta >> 3) & 3) ^ (((cta >> 5) & 1) * 3)) + ((cta >> 2) & 1); }
__device__ __forceinline__ int role_rb2(int cta) { return cta >> 3; }
__device__ __forceinline__ int role_q2(int cta) { return cta & 7; }

__global__ void __launch_bounds__(NTHREADS, 1) fused_kernel(const __grid_constant__ Params p) {
  extern __shared__ __align__(1024) uint8_t smem[];
  const uint32_t sb = s32(smem);
  const int tid = threadIdx.x, lane = tid & 31;
  const int warp = __shfl_sync(~0u, tid >> 5, 0);
  const uint32_t bar = sb + SM_BAR;
  if (tid == 0) TS(0);
  const int cta0 = role_id();
  if (warp == 0 && elect_one()) {
    const int rb = role_rb(cta0), hg = role_hg(cta0);
#pragma unroll
    for (int c = 0; c < 2; c++) { mbar_init(bar + 8 * (B_XF + c), 1); mbar_init(bar + 8 * (B_KVF + c), 1); }
    fence_async_smem();
#pragma unroll
    for (int c = 0; c < 2; c++) {
      mbar_expect(bar + 8 * (B_XF + c), 16384);
      tma_ld(sb + SM_X + c * 16384, &p.mapX128, (rb >> 3) * DM + c * 64, (rb & 7) * 128, bar + 8 * (B_XF + c));
      mbar_expect(bar + 8 * (B_KVF + c), 24576);
      tma_ld3(sb + SM_W + c * 24576, &p.mapW3, hg * 64, c * 64, 0, bar + 8 * (B_KVF + c));
    }
  }
  if (warp == 1 && elect_one()) {
    const int rb = role_rb(cta0), hg = role_hg(cta0);
#pragma unroll
    for (int c = 2; c < 8; c++) mbar_init(bar + 8 * (B_XF + c), 1);
    mbar_init(bar + 8 * (B_KVF + 2), 1); mbar_init(bar + 8 * B_CW, 1);
    fence_async_smem();
    delay<D_START>();
    mbar_expect(bar + 8 * B_CW, 12288);
    tma_ld3(sb + SM_CW, &p.mapW3h, hg * 64, rb * 32, 0, bar + 8 * B_CW);
#pragma unroll
    for (int c = 2; c < 8; c++) {
      mbar_expect(bar + 8 * (B_XF + c), 16384);
      tma_ld(sb + SM_X + c * 16384, &p.mapX128, (rb >> 3) * DM + c * 64, (rb & 7) * 128, bar + 8 * (B_XF + c));
      if (c < 3) {
        mbar_expect(bar + 8 * (B_KVF + c), 24576);
        tma_ld3(sb + SM_W + c * 24576, &p.mapW3, hg * 64, c * 64, 0, bar + 8 * (B_KVF + c));
      }
    }
    TS(56);
  }
  if ((warp & 2) != 0 && warp < 15 && elect_one()) {
    const int grp = 1 + (warp & 1) + 2 * (warp >> 2), cnt = grp < 4 ? 1 : grp < 5 ? 2 : grp < 7 ? 4 : 8;
#pragma unroll
    for (int k = 0; k < 10; k++)
      if (k != 0 || grp > 3 || grp == 2) mbar_init(bar + 8 * (10 * grp + k), cnt);
    fence_async_smem();
  }

  if (warp < 8) {
    if (tid == 0) TS(1);
    asm volatile("setmaxnreg.inc.sync.aligned.u32 %0;" ::"n"(R_CONS));
    const int cta = role_id();
    auto warp_id = [] { return __shfl_sync(~0u, opaque_tid() >> 5, 0); };
    if (tid == 0) TS(54);
#pragma unroll 1
    for (int layer = 0; layer < 2; layer++) {
      { const int cw = warp_id(); attn_phase(p, sb, layer, role_rb(cta), role_hg(cta), cw >> 2, cw & 3); }
      if (STOP == 1 + 3 * layer) return;
      { const int cw = warp_id(); proj_phase(p, sb, layer, role_rb2(cta), role_q2(cta), cw >> 2, cw & 3); }
      if (STOP == 2 + 3 * layer) return;
      conv_phase(p, sb, layer, cta);
      if (STOP == 3 + 3 * layer) return;
    }
    { const int cw = warp_id(); final_phase(p, sb, cta, cw >> 2, cw & 3); }
  } else if (warp < 12) {
    asm volatile("setmaxnreg.dec.sync.aligned.u32 %0;" ::"n"(R_HELP));
    const int ht = tid - 256;
    const int cta = role_id(), rb = role_rb(cta), hg = role_hg(cta);
    unsigned ep0 = 0;
    if (ht == 0) ep0 = ld_relaxed(&g_cnt[C_CS * 32]);
    bar_sync(0, NTHREADS);
    if (ht == 0) {
      asm volatile("st.shared.v2.u32 [%0], {%1, 0};" ::"r"(sb + SM_EP), "r"(ep0 / NCTA) : "memory");
      mbar_arrive(bar + 8 * B_EP);
    }
    mbar_wait(bar + 8 * B_EP, 0);
    stats_publish(sb, 0, rb, hg, opaque_tid() - 256, part_tag(lds32(sb + SM_EP), 0));
    if (ht < 48) {
      const bf16* q = (&p.a_re)[ht >> 3];
      asm volatile("prefetch.global.L2 [%0];" ::"l"(q + cv_chan(cta, (ht >> 1) & 3) * 128 + (ht & 1) * 64));
    }
    {
      KGen kg;
      const uint32_t tab0 = sb + ((ht >> 5) < 2 ? SM_T : SM_T2 - 4096) + (ht >> 5) * 2048;
      const uint32_t tab = tab0 + (ht & 31) * 16, taba = tab0 + ((ht >> 3) & 1) * 1024 + (((ht >> 1) & 8) + (ht & 7)) * 16;
      delay<D_ST0>();
      stats_gather(sb, rb, opaque_tid() - 256, part_tag(lds32(sb + SM_EP), 0));
      if (ht == 0) TS(40);
      const int chn = cv_chan(cta, ht >> 5);
      const ModeIn modes = load_modes(p, chn * 128 + (ht & 31) * 4);
      const bf16 logdt = p.log_dt[chn], dskip = p.dskip[chn];
      if (!HALO_W14 && KG_START != 4) halo_receive(sb, 0, rb, hg, opaque_tid() - 256);
      if (KG_START == 1) mbar_wait(bar + 8 * B_HF, 0);
      kgen_setup(kg, sb, cta, ht, modes, logdt, dskip);
      if (!HALO_W14 && KG_START == 4) halo_receive(sb, 0, rb, hg, opaque_tid() - 256);
      if (KG_START == 2) mbar_wait(bar + 8 * B_HF, 0);
      if (KG_START == 3) mbar_wait(bar + 8 * B_QDONE, 0);
#pragma unroll 1
      for (int u = 0; u < 4; u++) {
        if (u == KG_PRE) {
          KTS(39);
          mbar_wait(bar + 8 * B_AD, 0);
          KTS(41);
        }
        kgen_unit(tab, taba, kg.cur.x, kg.cur.y, {kg.cur.z, kg.cur.w}, kg.T);
        kg.cur = lds128f(kgen_slot(sb, opaque_tid() - 256, u + 1));
      }
      kgen_finish(kg, sb, cta, opaque_tid() - 256);
    }
    KTS(51);
    bar_sync(4, 128);
#pragma unroll 1
    for (int layer = 0; layer < 2; layer++) {
      if (STOP <= 1 + 3 * layer) return;
      mbar_wait(bar + 8 * (EXP_LATE ? B_PS : B_PDONE), layer);
      expand_taps(sb, opaque_tid() - 256);
      conv_zero(sb, opaque_tid() - 256);
      if (ht == 0) TS(52 + layer);
      warp_release(bar + 8 * B_PE);
      if (STOP <= 2 + 3 * layer) return;
      {
        uint4 xr[4], st[4];
        const int c = opaque_tid() - 256;
        const SumAddr sa = conv_sum_addr(sb, c);
        conv_prep_load(sb, layer, cta, c, xr, st);
        conv_prep<true>(sb, layer, cta, c, xr, st, sa);
        if (layer == 1 && ht == 0) TS(62);
        const bf16* xup = g_xT + (size_t)(2 * layer * DM + cta) * LSEQ + (c + 128) * 8;
        const int ahead = layer ? S_AHEAD1 : S_AHEAD0;
        mbar_wait(bar + 8 * (B_U + 3), layer);
        if (ahead == 2) {
          conv_sums(sa, 1, c);
          fence_async_smem();
          bar_arrive(8, 256);
        }
        st[0] = ldcg128(xup);
#pragma unroll
        for (int lc = 0; lc < 4; lc++) {
          if (lc < 3 && lc + ahead < 4) {
            conv_sums(sa, lc + ahead, c);
            fence_async_smem();
            bar_arrive(7 + lc + ahead, 256);
            sched_fence<4>();
          }
          if (lc < 3) st[lc + 1] = ldcg128(xup + (lc + 1) * 128 * LSEQ);
          conv_epi(sb, layer, cta, lc, c, xr[lc], st[lc]);
          warp_release(bar + 8 * (B_E + lc));
          sched_fence<5>();
          if (layer == 1 && lc == 3 && ht == 0) TS(38);
        }
      }
      if (layer == 0 && STOP > 3) {
        const int c1 = role_id();
        stats_publish(sb, 1, role_rb(c1), role_hg(c1), opaque_tid() - 256, part_tag(lds32(sb + SM_EP), 2));
        delay<D_ST>();
        stats_gather(sb, role_rb(c1), opaque_tid() - 256, part_tag(lds32(sb + SM_EP), 2));
        if (ht == 0) TS(25);
        if (!HALO_W14) halo_receive(sb, 1, role_rb(c1), role_hg(c1), opaque_tid() - 256);
      }
    }
  } else {
    asm volatile("setmaxnreg.dec.sync.aligned.u32 %0;" ::"n"(512 - 2 * R_CONS - R_HELP));
    const int cta = role_id(), rb = role_rb(cta), hg = role_hg(cta), rb2 = role_rb2(cta), q2 = role_q2(cta);
    bar_sync(0, NTHREADS);
    if (warp != 12) {
      mbar_wait(bar + 8 * B_EP, 0);
      const uint32_t tag = lds32(sb + SM_EP) % 7 + 1;
      mbar_wait(bar + 8 * B_CW, 0);
      colsum_publish(sb, rb, hg, tid - 416, tag);
      if (tid == 416) TS(50);
      delay<D_CS>();
      colsum_gather(sb, hg, tid - 416, tag);
      __syncwarp();
      if (tid == 416) TS(55);
    }
    if (elect_one()) mbar_arrive(bar + 8 * B_CSF);
    if (warp == 12) {
      if (elect_one()) {
        unsigned epoch = 0;
#pragma unroll 1
        for (int layer = 0; layer < 2; layer++) {
          auto ld_w = [&](int c, int slot) {
            const uint32_t b = bar + 8 * (B_KVF + c);
            mbar_expect(b, 24576);
            tma_ld3(sb + SM_W + slot * 24576, &p.mapW3, hg * 64, c * 64, 0, b);
          };
          if (layer == 0) {
            mbar_wait(bar + 8 * (B_KVF + 2), 0);
            if (rb2 < 4) tma_prefetch2(&p.mapWo128, q2 * 64, rb2 * 128);
            asm volatile("prefetch.tensormap [%0];" ::"l"(&p.mapO) : "memory");
            asm volatile("prefetch.tensormap [%0];" ::"l"(&p.mapO128) : "memory");
            asm volatile("prefetch.tensormap [%0];" ::"l"(&p.mapXT) : "memory");
            asm volatile("prefetch.tensormap [%0];" ::"l"(&p.mapXT3) : "memory");
            mbar_wait(bar + 8 * B_EP, 0);
            epoch = lds32(sb + SM_EP);
          } else {
            mbar_wait(bar + 8 * B_PDONE, 0);
            ld_w(0, 0); ld_w(1, 1);
            mbar_wait(bar + 8 * (W2_LATE ? B_U : B_RE), 0);
            ld_w(2, 2);
          }
          {
            int slot = 0;
#pragma unroll 1
            for (int c = 3; c < 8; c++) {
              mbar_wait(bar + 8 * (B_KVE + c - 3), layer);
              ld_w(c, slot);
              slot = slot == 2 ? 0 : slot + 1;
            }
          }
          if (STOP <= 1 + 3 * layer) return;
          mbar_wait(bar + 8 * B_QDONE, layer);
          mbar_wait(bar + 8 * B_HF, layer);
          mbar_expect(bar + 8 * B_WOF, 65536);
#pragma unroll
          for (int c = 0; c < 4; c++) tma_ld(sb + SM_WO + c * 16384, &p.mapWo128, q2 * 64, c * 128, bar + 8 * B_WOF);
          {
            const uint32_t b = bar + 8 * B_RF;
            mbar_expect(b, 16384);
            if (layer == 0) tma_ld(sb + SM_R, &p.mapX128, (rb2 >> 3) * DM + q2 * 64, (rb2 & 7) * 128, b);
            else tma_ld3(sb + SM_R, &p.mapXT3, 0, DM + q2 * 64, rb2 * 2, b);
          }
#pragma unroll
          for (int c = 0; c < 8; c++) mbar_expect(bar + 8 * (B_OF + c), 16384);
          spin_until(&g_cnt[(C_O + rb2) * 32], (2 * epoch + layer + 1) * 16);
          fence_async_global();
#pragma unroll
          for (int c = 0; c < 8; c++) {
            if (c == 4) { mbar_wait(bar + 8 * B_OST, layer); fence_async_smem(); }
            tma_ld(sb + sm_o(c), &p.mapO128, c * 64, rb2 * 128, bar + 8 * (B_OF + c));
          }
          if (STOP <= 3 + 3 * layer) return;
        }
      }
    } else if (warp == 13) {
      if (elect_one() && STOP > 1) {
        const unsigned target = (lds32(sb + SM_EP) + 1) * NCTA;
        mbar_wait(bar + 8 * B_RE, 0);
        spin_until(&g_cnt[C_CS * 32 + 2], 2 * target);
        mbar_arrive(bar + 8 * B_XV);
        if (STOP <= 3) return;
        auto ld_x = [&](int c) { tma_ld3(sb + SM_X + c * 16384, &p.mapXT3, 0, DM + c * 64, rb * 2, bar + 8 * (B_XF + c)); };
#pragma unroll
        for (int c = 0; c < 8; c++) mbar_expect(bar + 8 * (B_XF + c), 16384);
        spin_until(&g_cnt[C_G1 * 32], target);
        fence_async_global();
        fence_async_smem();
        ld_x(0); ld_x(1);
        int done = 1, it = 0;
        while (done < 4) {
          const uint4 v = ld_tagged((const uint4*)&g_cnt[C_G1 * 32]);
          const int n = 4 + ((int)(v.y - target) >> 31) + ((int)(v.z - target) >> 31) + ((int)(v.w - target) >> 31);
          if (n == done) { if (++it > (1 << 23)) __trap(); continue; }
          if (n == 4) TS(44);
          fence_async_global();
          fence_async_smem();
          if (done == 1) { ld_x(2); ld_x(3); }
          const int h = hg >> 2;
          if (done < 3 && n >= 3) ld_x(4 + h);
          if (n == 4) ld_x(6 + h);
          if (done < 3 && n >= 3) ld_x(5 - h);
          if (n == 4) ld_x(7 - h);
          done = n;
        }
        if (STOP <= 4) return;
        mbar_wait(bar + 8 * B_RE, 1);
        spin_until(&g_cnt[C_CS * 32 + 3], 2 * target);
        mbar_arrive(bar + 8 * B_XV);
      }
    } else if (warp == 15) {
      mbar_wait(bar + 8 * B_EP, 0);
      const unsigned epoch = lds32(sb + SM_EP);
#pragma unroll 1
      for (int layer = 0; layer < 2; layer++) {
        mbar_wait(bar + 8 * (B_KVF + FILL_AT), layer);
#pragma unroll
        for (int k = 0; k < 8; k++) ((uint4*)(g_xT + (size_t)(2 * layer * DM + cta) * LSEQ))[32 * k + lane] = make_uint4(~0u, ~0u, ~0u, ~0u);
        mbar_wait(bar + 8 * (B_KVF + FILL_AT + 1), layer);
#pragma unroll
        for (int k = 0; k < 16; k++)
          ((uint4*)(g_xT + (size_t)(3 * DM + cv_chan(cta, 3 - (k >> 2))) * LSEQ))[128 * layer + 32 * (k & 3) + lane] = make_uint4(~0u, ~0u, ~0u, ~0u);
        if (lane < 4) ((uint4*)g_stats)[layer * 512 + cta * 4 + lane] = make_uint4(0, 0, 0, 0);
        __syncwarp();
        if (elect_one()) {
          red_release(&g_cnt[C_CS * 32 + layer]);
          spin_until(&g_cnt[C_CS * 32 + layer], (epoch + 1) * NCTA);
          mbar_arrive(bar + 8 * B_ZF);
          if (layer == 0 && STOP > 2) {
#pragma unroll
            for (int lc = 0; lc < 4; lc++) {
              mbar_wait(bar + 8 * (B_E + lc), 0);
              fence_reader();
              bulk_st(g_xT + (size_t)(DM + cv_chan(cta, lc)) * LSEQ, sb + cv_s(lc), 4096);
              bulk_commit();
              bulk_wait_all();
              red_relaxed(&g_cnt[C_G1 * 32 + lc]);
              if (lc == 3) TS(18);
            }
          }
        }
        __syncwarp();
        if (STOP <= 3) return;
      }
    } else if (warp == 14) {
      mbar_wait(bar + 8 * B_EP, 0);
      const unsigned epoch = lds32(sb + SM_EP);
#pragma unroll 1
      for (int layer = 0; layer < 2; layer++) {
        if (STOP <= 3 * layer) return;
        if (HALO_W14) halo_receive1(sb, layer, rb, hg, opaque_tid() & 31, 2 * epoch + layer + 1);
        if (STOP <= 1 + 3 * layer) return;
        mbar_wait(bar + 8 * B_ZF, layer);
        proj_stats(sb, layer, rb2, q2, opaque_tid() & 31, part_tag(epoch, 2 * layer + 1));
        if (layer == 1 && lane == 0) TS(5);
        delay<D_PREP>();
        if (lane == 0) mbar_arrive(bar + 8 * B_GB);
      }
    }
  }
}

typedef CUresult (*EncodeFn)(CUtensorMap*, CUtensorMapDataType, cuuint32_t, void*, const cuuint64_t*, const cuuint64_t*,
                             const cuuint32_t*, const cuuint32_t*, CUtensorMapInterleave, CUtensorMapSwizzle,
                             CUtensorMapL2promotion, CUtensorMapFloatOOBfill);

static void make_map(EncodeFn enc, CUtensorMap* m, void* ptr, uint64_t cols, uint64_t rows, uint32_t box_rows) {
  cuuint64_t dims[2] = {cols, rows};
  cuuint64_t strides[1] = {cols * 2};
  cuuint32_t box[2] = {64, box_rows};
  cuuint32_t es[2] = {1, 1};
  enc(m, CU_TENSOR_MAP_DATA_TYPE_BFLOAT16, 2, ptr, dims, strides, box, es, CU_TENSOR_MAP_INTERLEAVE_NONE,
      CU_TENSOR_MAP_SWIZZLE_128B, CU_TENSOR_MAP_L2_PROMOTION_L2_128B, CU_TENSOR_MAP_FLOAT_OOB_FILL_NONE);
}
static void make_map3(EncodeFn enc, CUtensorMap* m, void* ptr, uint64_t d0, uint64_t cols, uint64_t rows, uint64_t blk_stride,
                      uint64_t nblocks, uint32_t nblk, uint32_t box_rows = 64) {
  cuuint64_t dims[3] = {d0, rows, nblocks};
  cuuint64_t strides[2] = {cols * 2, blk_stride * 2};
  cuuint32_t box[3] = {64, box_rows, nblk};
  cuuint32_t es[3] = {1, 1, 1};
  enc(m, CU_TENSOR_MAP_DATA_TYPE_BFLOAT16, 3, ptr, dims, strides, box, es, CU_TENSOR_MAP_INTERLEAVE_NONE,
      CU_TENSOR_MAP_SWIZZLE_128B, CU_TENSOR_MAP_L2_PROMOTION_L2_128B, CU_TENSOR_MAP_FLOAT_OOB_FILL_NONE);
}

extern "C" void kernel_launch(void* const* d_in, const int* in_sizes, int n_in, void* d_out, int out_size) {
  static Params prm;
  static void* cached[13] = {nullptr};
  static bool attr_done = false;
  bool same = attr_done && cached[12] == d_out;
  for (int i = 0; i < 12 && same; i++) same = cached[i] == d_in[i];
  if (!same) {
    void* fn = nullptr;
    cudaDriverEntryPointQueryResult qr;
    cudaGetDriverEntryPoint("cuTensorMapEncodeTiled", &fn, cudaEnableDefault, &qr);
    EncodeFn enc = (EncodeFn)fn;
    void *pO, *pXT;
    cudaGetSymbolAddress(&pO, g_O);
    cudaGetSymbolAddress(&pXT, g_xT);
    make_map(enc, &prm.mapO, pO, DM, LSEQ, O_WARP ? 16 : 64);
    make_map(enc, &prm.mapXT, pXT, LSEQ, 4 * DM, 64);
    prm.out = (bf16*)d_out;
    make_map(enc, &prm.mapX128, d_in[0], 2 * DM, LSEQ / 2, 128);
    make_map(enc, &prm.mapWo128, d_in[2], DM, DM, 128);
    make_map(enc, &prm.mapO128, pO, DM, LSEQ, 128);
    make_map3(enc, &prm.mapW3, d_in[1], DM, 3 * DM, DM, DM, 3, 3);
    make_map3(enc, &prm.mapW3h, d_in[1], DM, 3 * DM, DM, DM, 3, 3, 32);
    make_map3(enc, &prm.mapXT3, pXT, 64, LSEQ, 4 * DM, 64, 32, 2);
    prm.a_re = (const bf16*)d_in[4]; prm.a_im = (const bf16*)d_in[5];
    prm.b_re = (const bf16*)d_in[6]; prm.b_im = (const bf16*)d_in[7];
    prm.c_re = (const bf16*)d_in[8]; prm.c_im = (const bf16*)d_in[9];
    prm.log_dt = (const bf16*)d_in[10]; prm.dskip = (const bf16*)d_in[11];
    cudaFuncSetAttribute(fused_kernel, cudaFuncAttributeMaxDynamicSharedMemorySize, SM_TOTAL);
    for (int i = 0; i < 12; i++) cached[i] = d_in[i];
    cached[12] = d_out;
    attr_done = true;
  }
  prm.stop = 100;
    fused_kernel<<<NCTA, NTHREADS, SM_TOTAL>>>(prm);
}
```

```cpp
#include <cuda_runtime.h>
#include <cuda_bf16.h>
#include <cuda.h>
#include <stdint.h>

typedef __nv_bfloat16 bf16;

constexpr int LSEQ = 2048;
constexpr int DM = 512;
constexpr int NCTA = 128;
constexpr int NTHREADS = 512;
#define RR 0
#define KG_PRE 2
#define WO_EARLY 3
#define FILL_AT 6
#define EXP_LATE 1
#define RFENCE 1
#define D_FIN 500
#define D_PREP 500
#define D_PST 0
#define D_HALO 500
#define STAG 2
#define D_ST 500
#define TLAYER 1
#define KG_PD 1
#define SUM_F32 0
#define CS_LATE0 1
#define D_HALO1 0
#define KG_START 0
#define S_AHEAD0 1
#define S_AHEAD1 2
#define PAUSE 2
#define PARK_FIRST 0
#define P_UNROLL_N 1
constexpr int P_UNROLL = P_UNROLL_N;
#define NORM_FMA 0
#define X_ORDER 1
#define CS_STEP 1
#define O_WARP 1
#define D_FIN2 400
#define FIN_D0 2
#define QD_AT 1
#define RES_AT B_HF
#define G_WAIT 2
#define HALO_W14 1
#define D_START 200
#define D_CS 300
#define D_ST0 400
#define KG_LAST 0
#define X_JIT 0
#define KG_GATE 2
#define R_CONS 192
#define R_HELP 88

constexpr int SM_X = 0;
constexpr int SM_W = 131072;
constexpr int SM_KVX = SM_X;
constexpr int SM_WO = SM_X + 16384;
constexpr int SM_OST = SM_W + 49152;
__host__ __device__ constexpr int sm_o(int c) { return c < 7 ? SM_X + (5 + c) * 16384 : SM_KVX; }
constexpr int SM_R = 196608;
constexpr int SM_T = 212992;
constexpr int SM_KC = 217088;
constexpr int KC_STRIDE = 648;
constexpr int SM_CS = SM_KC + 4 * KC_STRIDE * 2;
constexpr int SM_CW = SM_R + 8192;
constexpr int SM_EP = SM_CS + 768;
constexpr int SM_BAR = SM_EP + 16;
constexpr int SM_T2 = SM_BAR + 896;
constexpr int SM_HALO = SM_T2 + 4096;
constexpr int SM_ST = SM_HALO + 3072;
constexpr int SM_TOTAL = SM_HALO + 4096;
static_assert(SM_TOTAL <= 232448, "shared memory");

constexpr int CV_UH = 140 * 16;
constexpr int CV_PECH = 1120 * 4;
constexpr int CV_PBW = 2112 * 2;
__host__ __device__ constexpr int cv_s(int lc) { return SM_X + lc * 32768; }
__host__ __device__ constexpr int cv_u(int lc) { return cv_s(lc) + 4096; }
__host__ __device__ constexpr int cv_pe(int lc) { return cv_u(lc) + 2 * CV_UH; }
__host__ __device__ constexpr int cv_pb(int lc) { return cv_pe(lc) + CV_PECH; }
__host__ __device__ constexpr int cv_ft(int lc) { return cv_pb(lc) + 4 * CV_PBW; }
static_assert(cv_ft(0) + 1024 <= 32768, "conv buffers");
__host__ __device__ constexpr int cv_chan(int cta, int lc) { return cta + 128 * lc; }

enum {
  B_XF = 0,
  B_KVF = 8,
  B_OF = 16,
  B_WOF = 24,
  B_T = 31,
  B_RF = 28,
  B_RE = 29,
  B_CW = 30,
  B_GB = 35,
  B_EP = 36,
  B_ZF = 37,
  B_XV = 39,
  B_SD = 38,
  B_KVE = 40,
  B_AD = 45,
  B_OST = 46,
  B_QDONE = 47,
  B_PDONE = 48,
  B_S = 50,
  B_E = 54,
  B_P = 58,
  B_PE = 62,
  B_STF = 63,
  B_CSF = 64,
  B_HF = 65,
  B_U = 70,
  B_PS = 74,
  B_COUNT = 80
};

enum {
  C_CS = 0,
  C_G1 = 2,
  C_O = 4,
  C_COUNT = 20
};

__device__ __align__(128) unsigned g_cnt[C_COUNT * 32];
__device__ __align__(1024) bf16 g_O[LSEQ * DM];
__device__ __align__(1024) bf16 g_xT[4 * DM * LSEQ];
__device__ __align__(1024) uint32_t g_stats[2 * LSEQ];
__device__ __align__(1024) uint4 g_colsum[8 * 16 * 48];
__device__ __align__(1024) uint4 g_halo[16 * 8 * 192];
__device__ __align__(1024) uint2 g_part[16 * 8 * 128];
#define TS(i) do { } while (0)

#define ATS(i, th) do { } while (0)
#define KTS(i) do { if (ht == 0) TS(i); } while (0)
#define FTS(i) do { } while (0)
#define LTS(i) do { } while (0)

#define STOP 100

struct Params {
  CUtensorMap mapO, mapXT, mapX128, mapWo128, mapO128, mapW3, mapW3h, mapXT3;
  const bf16 *a_re, *a_im, *b_re, *b_im, *c_re, *c_im, *log_dt, *dskip;
  bf16* out;
  int stop;
};

__device__ __forceinline__ uint32_t s32(const void* p) { return (uint32_t)__cvta_generic_to_shared(p); }
__device__ __forceinline__ void mbar_init(uint32_t b, int c) { asm volatile("mbarrier.init.shared::cta.b64 [%0], %1;" ::"r"(b), "r"(c) : "memory"); }
__device__ __forceinline__ void mbar_expect(uint32_t b, int bytes) { asm volatile("mbarrier.arrive.expect_tx.shared::cta.b64 _, [%0], %1;" ::"r"(b), "r"(bytes) : "memory"); }
__device__ __forceinline__ void mbar_arrive(uint32_t b) { asm volatile("mbarrier.arrive.shared::cta.b64 _, [%0];" ::"r"(b) : "memory"); }
__device__ __forceinline__ void mbar_arrive_if(uint32_t b, bool c) {
  asm volatile("{\n.reg .pred p;\nsetp.ne.u32 p, %1, 0;\n@p mbarrier.arrive.shared::cta.b64 _, [%0];\n}" ::"r"(b), "r"((uint32_t)c) : "memory");
}
__device__ __forceinline__ void mbar_wait(uint32_t b, int parity) {
  asm volatile("{\n.reg .pred p;\nWAIT_LOOP:\nmbarrier.try_wait.parity.shared::cta.b64 p, [%0], %1;\n@p bra WAIT_DONE;\nbra WAIT_LOOP;\nWAIT_DONE:\n}" ::"r"(b), "r"(parity) : "memory");
}
template <int N> __device__ __forceinline__ void delay() {
  if constexpr (N > 0) {
    uint32_t t0, t;
    asm volatile("mov.u32 %0, %%clock;" : "=r"(t0));
    do { asm volatile("mov.u32 %0, %%clock;" : "=r"(t)); } while (t - t0 < N);
  }
}
#define SF 3
template <int ID> __device__ __forceinline__ void sched_fence() {
  if constexpr ((SF >> ID) & 1)
    asm volatile("{\n.reg .pred p;\n.reg .u32 t;\nsetp.eq.u32 p, %0, 0;\n@p mov.u32 t, %%clock;\n@p st.shared.u32 [%0], t;\n}" ::"r"(gridDim.x) : "memory");
}
__device__ __forceinline__ int opaque_tid() { int v; asm volatile("mov.u32 %0, %%tid.x;" : "=r"(v)); return v; }
__device__ __forceinline__ bool elect_one() {
  uint32_t r;
  asm volatile("{\n.reg .pred p;\nelect.sync _|p, 0xffffffff;\nselp.u32 %0, 1, 0, p;\n}" : "=r"(r));
  return r != 0;
}
__device__ __forceinline__ void tma_ld(uint32_t dst, const CUtensorMap* m, int c0, int c1, uint32_t bar) {
  asm volatile("cp.async.bulk.tensor.2d.shared::cluster.global.mbarrier::complete_tx::bytes [%0], [%1, {%3, %4}], [%2];"
               ::"r"(dst), "l"(m), "r"(bar), "r"(c0), "r"(c1) : "memory");
}
__device__ __forceinline__ void tma_ld3(uint32_t dst, const CUtensorMap* m, int c0, int c1, int c2, uint32_t bar) {
  asm volatile("cp.async.bulk.tensor.3d.shared::cluster.global.mbarrier::complete_tx::bytes [%0], [%1, {%3, %4, %5}], [%2];"
               ::"r"(dst), "l"(m), "r"(bar), "r"(c0), "r"(c1), "r"(c2) : "memory");
}
__device__ __forceinline__ void tma_prefetch2(const CUtensorMap* m, int c0, int c1) {
  asm volatile("cp.async.bulk.prefetch.tensor.2d.L2.global.tile [%0, {%1, %2}];" ::"l"(m), "r"(c0), "r"(c1) : "memory");
}
__device__ __forceinline__ void tma_prefetch3(const CUtensorMap* m, int c0, int c1, int c2) {
  asm volatile("cp.async.bulk.prefetch.tensor.3d.L2.global.tile [%0, {%1, %2, %3}];" ::"l"(m), "r"(c0), "r"(c1), "r"(c2) : "memory");
}
__device__ __forceinline__ void tma_st(const CUtensorMap* m, int c0, int c1, uint32_t src) {
  asm volatile("cp.async.bulk.tensor.2d.global.shared::cta.bulk_group [%0, {%2, %3}], [%1];" ::"l"(m), "r"(src), "r"(c0), "r"(c1) : "memory");
}
__device__ __forceinline__ void bulk_ld(uint32_t dst, const void* src, int bytes, uint32_t bar) {
  asm volatile("cp.async.bulk.shared::cluster.global.mbarrier::complete_tx::bytes [%0], [%1], %2, [%3];" ::"r"(dst), "l"(src), "r"(bytes), "r"(bar) : "memory");
}
__device__ __forceinline__ void bulk_st(void* dst, uint32_t src, int bytes) {
  asm volatile("cp.async.bulk.global.shared::cta.bulk_group [%0], [%1], %2;" ::"l"(dst), "r"(src), "r"(bytes) : "memory");
}
__device__ __forceinline__ void bulk_red_add_f32(void* dst, uint32_t src, int bytes) {
  asm volatile("cp.reduce.async.bulk.global.shared::cta.bulk_group.add.f32 [%0], [%1], %2;" ::"l"(dst), "r"(src), "r"(bytes) : "memory");
}
__device__ __forceinline__ void bulk_commit() { asm volatile("cp.async.bulk.commit_group;" ::: "memory"); }
__device__ __forceinline__ void bulk_wait_all() { asm volatile("cp.async.bulk.wait_group 0;" ::: "memory"); }
__device__ __forceinline__ void fence_async_smem() { asm volatile("fence.proxy.async.shared::cta;" ::: "memory"); }
__device__ __forceinline__ void fence_writer() { if (!RFENCE) fence_async_smem(); }
__device__ __forceinline__ void fence_reader() { if (RFENCE) fence_async_smem(); }
__device__ __forceinline__ void fence_async_global() { asm volatile("fence.proxy.async.global;" ::: "memory"); }
__device__ __forceinline__ void bar_sync(int id, int n) { asm volatile("bar.sync %0, %1;" ::"r"(id), "r"(n) : "memory"); }
__device__ __forceinline__ void bar_arrive(int id, int n) { asm volatile("bar.arrive %0, %1;" ::"r"(id), "r"(n) : "memory"); }
__device__ __forceinline__ void wg_fence() { asm volatile("wgmma.fence.sync.aligned;" ::: "memory"); }
__device__ __forceinline__ void wg_commit() { asm volatile("wgmma.commit_group.sync.aligned;" ::: "memory"); }
template <int N> __device__ __forceinline__ void wg_wait() { asm volatile("wgmma.wait_group.sync.aligned %0;" ::"n"(N) : "memory"); }
__device__ __forceinline__ uint64_t mkdesc(uint32_t addr, uint32_t lbo, uint32_t sbo, int sw) {
  return (uint64_t)((addr & 0x3FFFF) >> 4) | ((uint64_t)(lbo >> 4) << 16) | ((uint64_t)(sbo >> 4) << 32) | ((uint64_t)sw << 62);
}
__device__ __forceinline__ void ldsm4(uint32_t* r, uint32_t a) {
  asm volatile("ldmatrix.sync.aligned.m8n8.x4.shared.b16 {%0,%1,%2,%3}, [%4];" : "=r"(r[0]), "=r"(r[1]), "=r"(r[2]), "=r"(r[3]) : "r"(a) : "memory");
}
__device__ __forceinline__ void ldsm4t(uint32_t* r, uint32_t a) {
  asm volatile("ldmatrix.sync.aligned.m8n8.x4.trans.shared.b16 {%0,%1,%2,%3}, [%4];" : "=r"(r[0]), "=r"(r[1]), "=r"(r[2]), "=r"(r[3]) : "r"(a) : "memory");
}
__device__ __forceinline__ void stsm4(uint32_t a, uint32_t r0, uint32_t r1, uint32_t r2, uint32_t r3) {
  asm volatile("stmatrix.sync.aligned.m8n8.x4.shared.b16 [%0], {%1,%2,%3,%4};" ::"r"(a), "r"(r0), "r"(r1), "r"(r2), "r"(r3) : "memory");
}
__device__ __forceinline__ void stsm4t(uint32_t a, uint32_t r0, uint32_t r1, uint32_t r2, uint32_t r3) {
  asm volatile("stmatrix.sync.aligned.m8n8.x4.trans.shared.b16 [%0], {%1,%2,%3,%4};" ::"r"(a), "r"(r0), "r"(r1), "r"(r2), "r"(r3) : "memory");
}
__device__ __forceinline__ uint32_t movm_t(uint32_t a) { uint32_t r; asm volatile("movmatrix.sync.aligned.m8n8.trans.b16 %0, %1;" : "=r"(r) : "r"(a)); return r; }
__device__ __forceinline__ uint32_t lds32(uint32_t a) { uint32_t v; asm volatile("ld.shared.b32 %0, [%1];" : "=r"(v) : "r"(a) : "memory"); return v; }
__device__ __forceinline__ float2 lds64f(uint32_t a) { float2 v; asm volatile("ld.shared.v2.f32 {%0,%1}, [%2];" : "=f"(v.x), "=f"(v.y) : "r"(a) : "memory"); return v; }
__device__ __forceinline__ float4 lds128f(uint32_t a) { float4 v; asm volatile("ld.shared.v4.f32 {%0,%1,%2,%3}, [%4];" : "=f"(v.x), "=f"(v.y), "=f"(v.z), "=f"(v.w) : "r"(a) : "memory"); return v; }
__device__ __forceinline__ uint4 lds128(uint32_t a) { uint4 v; asm volatile("ld.shared.v4.b32 {%0,%1,%2,%3}, [%4];" : "=r"(v.x), "=r"(v.y), "=r"(v.z), "=r"(v.w) : "r"(a) : "memory"); return v; }
__device__ __forceinline__ void sts128(uint32_t a, uint4 v) { asm volatile("st.shared.v4.b32 [%0], {%1,%2,%3,%4};" ::"r"(a), "r"(v.x), "r"(v.y), "r"(v.z), "r"(v.w) : "memory"); }
__device__ __forceinline__ void sts128f(uint32_t a, float x, float y, float z, float w) { asm volatile("st.shared.v4.f32 [%0], {%1,%2,%3,%4};" ::"r"(a), "f"(x), "f"(y), "f"(z), "f"(w) : "memory"); }
__device__ __forceinline__ void sts32f(uint32_t a, float v) { asm volatile("st.shared.f32 [%0], %1;" ::"r"(a), "f"(v) : "memory"); }
__device__ __forceinline__ void sts16(uint32_t a, uint16_t v) { asm volatile("st.shared.u16 [%0], %1;" ::"r"(a), "h"(v) : "memory"); }
__device__ __forceinline__ uint32_t lds16(uint32_t a) { uint16_t v; asm volatile("ld.shared.u16 %0, [%1];" : "=h"(v) : "r"(a) : "memory"); return v; }
__device__ __forceinline__ uint32_t packbf(float lo, float hi) { uint32_t r; asm("cvt.rn.bf16x2.f32 %0, %1, %2;" : "=r"(r) : "f"(hi), "f"(lo)); return r; }
__device__ __forceinline__ float bf_lo(uint32_t v) { return __uint_as_float(v << 16); }
__device__ __forceinline__ float bf_hi(uint32_t v) { return __uint_as_float(v & 0xffff0000u); }
__device__ __forceinline__ float ex2(float x) { float r; asm("ex2.approx.ftz.f32 %0, %1;" : "=f"(r) : "f"(x)); return r; }
__device__ __forceinline__ float rsqrt_approx(float x) { float r; asm("rsqrt.approx.ftz.f32 %0, %1;" : "=f"(r) : "f"(x)); return r; }
__device__ __forceinline__ float rcp_approx(float x) { float r; asm("rcp.approx.ftz.f32 %0, %1;" : "=f"(r) : "f"(x)); return r; }
__device__ __forceinline__ void mma_bf16(float* d, const uint32_t* a, uint32_t b0, uint32_t b1) {
  asm("mma.sync.aligned.m16n8k16.row.col.f32.bf16.bf16.f32 {%0,%1,%2,%3}, {%4,%5,%6,%7}, {%8,%9}, {%0,%1,%2,%3};"
               : "+f"(d[0]), "+f"(d[1]), "+f"(d[2]), "+f"(d[3]) : "r"(a[0]), "r"(a[1]), "r"(a[2]), "r"(a[3]), "r"(b0), "r"(b1));
}
__device__ __forceinline__ void mma_bf16_k8(float* d, uint32_t a0, uint32_t a1, uint32_t b) {
  asm("mma.sync.aligned.m16n8k8.row.col.f32.bf16.bf16.f32 {%0,%1,%2,%3}, {%4,%5}, {%6}, {%0,%1,%2,%3};"
      : "+f"(d[0]), "+f"(d[1]), "+f"(d[2]), "+f"(d[3]) : "r"(a0), "r"(a1), "r"(b));
}
__device__ __forceinline__ void red_release(unsigned* p) { asm volatile("red.release.gpu.global.add.u32 [%0], 1;" ::"l"(p) : "memory"); }
__device__ __forceinline__ void red_relaxed(unsigned* p) { asm volatile("red.relaxed.gpu.global.add.u32 [%0], 1;" ::"l"(p) : "memory"); }
__device__ __forceinline__ unsigned ld_relaxed(const unsigned* p) { unsigned v; asm volatile("ld.relaxed.gpu.global.u32 %0, [%1];" : "=r"(v) : "l"(p) : "memory"); return v; }
__device__ __forceinline__ void spin_until(const unsigned* p, unsigned target) {
  int it = 0;
  while ((int)(ld_relaxed(p) - target) < 0) {
    if (++it > (1 << 23)) __trap();
  }
}
__device__ __forceinline__ uint4 ldcg128(const void* p) { uint4 v; asm volatile("ld.global.cg.v4.b32 {%0,%1,%2,%3}, [%4];" : "=r"(v.x), "=r"(v.y), "=r"(v.z), "=r"(v.w) : "l"(p) : "memory"); return v; }
__device__ __forceinline__ uint4 ld_tagged(const uint4* p) { uint4 v; asm volatile("ld.relaxed.gpu.global.v4.u32 {%0,%1,%2,%3}, [%4];" : "=r"(v.x), "=r"(v.y), "=r"(v.z), "=r"(v.w) : "l"(p) : "memory"); return v; }
__device__ __forceinline__ uint2 ld_part(const uint2* p) { uint2 v; asm volatile("ld.relaxed.gpu.global.v2.u32 {%0,%1}, [%2];" : "=r"(v.x), "=r"(v.y) : "l"(p) : "memory"); return v; }
__device__ __forceinline__ void st_part(uint2* p, float s, float q, uint32_t tag) {
  asm volatile("st.relaxed.gpu.global.v2.u32 [%0], {%1,%2};" ::"l"(p), "r"(__float_as_uint(s)), "r"((__float_as_uint(q) & ~7u) | tag) : "memory");
}
__device__ __forceinline__ uint32_t part_tag(uint32_t epoch, int k) { return (4 * (epoch % 7) + k) % 7 + 1; }
__device__ __forceinline__ void st_tagged3(uint4* p, uint32_t a, uint32_t b, uint32_t c, uint32_t tag) { asm volatile("st.relaxed.gpu.global.v4.u32 [%0], {%1,%2,%3,%4};" ::"l"(p), "r"(a), "r"(b), "r"(c), "r"(tag) : "memory"); }
__device__ __forceinline__ uint32_t hadd2(uint32_t a, uint32_t b) { uint32_t r; asm("add.rn.bf16x2 %0, %1, %2;" : "=r"(r) : "r"(a), "r"(b)); return r; }
__device__ __forceinline__ uint32_t hfma2(uint32_t a, uint32_t b, uint32_t c) { uint32_t r; asm("fma.rn.bf16x2 %0, %1, %2, %3;" : "=r"(r) : "r"(a), "r"(b), "r"(c)); return r; }
__device__ __forceinline__ uint32_t hmul2(uint32_t a, uint32_t b) { uint32_t r; asm("mul.rn.bf16x2 %0, %1, %2;" : "=r"(r) : "r"(a), "r"(b)); return r; }

template<int N,int TB> __device__ __forceinline__ void wgmma_rs(float* d, const uint32_t* a, uint64_t db, int sd);
template<int N,int TA,int TB> __device__ __forceinline__ void wgmma_ss(float* d, uint64_t da, uint64_t db, int sd);
template<> __device__ __forceinline__ void wgmma_rs<128,0>(float* d, const uint32_t* a, uint64_t db, int sd) {
  asm volatile("{\n.reg .pred p;\nsetp.ne.b32 p, %69, 0;\nwgmma.mma_async.sync.aligned.m64n128k16.f32.bf16.bf16 {%0,%1,%2,%3,%4,%5,%6,%7,%8,%9,%10,%11,%12,%13,%14,%15,%16,%17,%18,%19,%20,%21,%22,%23,%24,%25,%26,%27,%28,%29,%30,%31,%32,%33,%34,%35,%36,%37,%38,%39,%40,%41,%42,%43,%44,%45,%46,%47,%48,%49,%50,%51,%52,%53,%54,%55,%56,%57,%58,%59,%60,%61,%62,%63}, {%64,%65,%66,%67}, %68, p, 1, 1, 0;\n}\n"
   : "+f"(d[0]),"+f"(d[1]),"+f"(d[2]),"+f"(d[3]),"+f"(d[4]),"+f"(d[5]),"+f"(d[6]),"+f"(d[7]),"+f"(d[8]),"+f"(d[9]),"+f"(d[10]),"+f"(d[11]),"+f"(d[12]),"+f"(d[13]),"+f"(d[14]),"+f"(d[15]),"+f"(d[16]),"+f"(d[17]),"+f"(d[18]),"+f"(d[19]),"+f"(d[20]),"+f"(d[21]),"+f"(d[22]),"+f"(d[23]),"+f"(d[24]),"+f"(d[25]),"+f"(d[26]),"+f"(d[27]),"+f"(d[28]),"+f"(d[29]),"+f"(d[30]),"+f"(d[31]),"+f"(d[32]),"+f"(d[33]),"+f"(d[34]),"+f"(d[35]),"+f"(d[36]),"+f"(d[37]),"+f"(d[38]),"+f"(d[39]),"+f"(d[40]),"+f"(d[41]),"+f"(d[42]),"+f"(d[43]),"+f"(d[44]),"+f"(d[45]),"+f"(d[46]),"+f"(d[47]),"+f"(d[48]),"+f"(d[49]),"+f"(d[50]),"+f"(d[51]),"+f"(d[52]),"+f"(d[53]),"+f"(d[54]),"+f"(d[55]),"+f"(d[56]),"+f"(d[57]),"+f"(d[58]),"+f"(d[59]),"+f"(d[60]),"+f"(d[61]),"+f"(d[62]),"+f"(d[63])
   : "r"(a[0]), "r"(a[1]), "r"(a[2]), "r"(a[3]), "l"(db), "r"(sd));
}
template<> __device__ __forceinline__ void wgmma_rs<120,0>(float* d, const uint32_t* a, uint64_t db, int sd) {
  asm volatile("{\n.reg .pred p;\nsetp.ne.b32 p, %65, 0;\nwgmma.mma_async.sync.aligned.m64n120k16.f32.bf16.bf16 {%0,%1,%2,%3,%4,%5,%6,%7,%8,%9,%10,%11,%12,%13,%14,%15,%16,%17,%18,%19,%20,%21,%22,%23,%24,%25,%26,%27,%28,%29,%30,%31,%32,%33,%34,%35,%36,%37,%38,%39,%40,%41,%42,%43,%44,%45,%46,%47,%48,%49,%50,%51,%52,%53,%54,%55,%56,%57,%58,%59}, {%60,%61,%62,%63}, %64, p, 1, 1, 0;\n}\n"
   : "+f"(d[0]),"+f"(d[1]),"+f"(d[2]),"+f"(d[3]),"+f"(d[4]),"+f"(d[5]),"+f"(d[6]),"+f"(d[7]),"+f"(d[8]),"+f"(d[9]),"+f"(d[10]),"+f"(d[11]),"+f"(d[12]),"+f"(d[13]),"+f"(d[14]),"+f"(d[15]),"+f"(d[16]),"+f"(d[17]),"+f"(d[18]),"+f"(d[19]),"+f"(d[20]),"+f"(d[21]),"+f"(d[22]),"+f"(d[23]),"+f"(d[24]),"+f"(d[25]),"+f"(d[26]),"+f"(d[27]),"+f"(d[28]),"+f"(d[29]),"+f"(d[30]),"+f"(d[31]),"+f"(d[32]),"+f"(d[33]),"+f"(d[34]),"+f"(d[35]),"+f"(d[36]),"+f"(d[37]),"+f"(d[38]),"+f"(d[39]),"+f"(d[40]),"+f"(d[41]),"+f"(d[42]),"+f"(d[43]),"+f"(d[44]),"+f"(d[45]),"+f"(d[46]),"+f"(d[47]),"+f"(d[48]),"+f"(d[49]),"+f"(d[50]),"+f"(d[51]),"+f"(d[52]),"+f"(d[53]),"+f"(d[54]),"+f"(d[55]),"+f"(d[56]),"+f"(d[57]),"+f"(d[58]),"+f"(d[59])
   : "r"(a[0]), "r"(a[1]), "r"(a[2]), "r"(a[3]), "l"(db), "r"(sd));
}
template<> __device__ __forceinline__ void wgmma_rs<112,0>(float* d, const uint32_t* a, uint64_t db, int sd) {
  asm volatile("{\n.reg .pred p;\nsetp.ne.b32 p, %61, 0;\nwgmma.mma_async.sync.aligned.m64n112k16.f32.bf16.bf16 {%0,%1,%2,%3,%4,%5,%6,%7,%8,%9,%10,%11,%12,%13,%14,%15,%16,%17,%18,%19,%20,%21,%22,%23,%24,%25,%26,%27,%28,%29,%30,%31,%32,%33,%34,%35,%36,%37,%38,%39,%40,%41,%42,%43,%44,%45,%46,%47,%48,%49,%50,%51,%52,%53,%54,%55}, {%56,%57,%58,%59}, %60, p, 1, 1, 0;\n}\n"
   : "+f"(d[0]),"+f"(d[1]),"+f"(d[2]),"+f"(d[3]),"+f"(d[4]),"+f"(d[5]),"+f"(d[6]),"+f"(d[7]),"+f"(d[8]),"+f"(d[9]),"+f"(d[10]),"+f"(d[11]),"+f"(d[12]),"+f"(d[13]),"+f"(d[14]),"+f"(d[15]),"+f"(d[16]),"+f"(d[17]),"+f"(d[18]),"+f"(d[19]),"+f"(d[20]),"+f"(d[21]),"+f"(d[22]),"+f"(d[23]),"+f"(d[24]),"+f"(d[25]),"+f"(d[26]),"+f"(d[27]),"+f"(d[28]),"+f"(d[29]),"+f"(d[30]),"+f"(d[31]),"+f"(d[32]),"+f"(d[33]),"+f"(d[34]),"+f"(d[35]),"+f"(d[36]),"+f"(d[37]),"+f"(d[38]),"+f"(d[39]),"+f"(d[40]),"+f"(d[41]),"+f"(d[42]),"+f"(d[43]),"+f"(d[44]),"+f"(d[45]),"+f"(d[46]),"+f"(d[47]),"+f"(d[48]),"+f"(d[49]),"+f"(d[50]),"+f"(d[51]),"+f"(d[52]),"+f"(d[53]),"+f"(d[54]),"+f"(d[55])
   : "r"(a[0]), "r"(a[1]), "r"(a[2]), "r"(a[3]), "l"(db), "r"(sd));
}
template<> __device__ __forceinline__ void wgmma_rs<104,0>(float* d, const uint32_t* a, uint64_t db, int sd) {
  asm volatile("{\n.reg .pred p;\nsetp.ne.b32 p, %57, 0;\nwgmma.mma_async.sync.aligned.m64n104k16.f32.bf16.bf16 {%0,%1,%2,%3,%4,%5,%6,%7,%8,%9,%10,%11,%12,%13,%14,%15,%16,%17,%18,%19,%20,%21,%22,%23,%24,%25,%26,%27,%28,%29,%30,%31,%32,%33,%34,%35,%36,%37,%38,%39,%40,%41,%42,%43,%44,%45,%46,%47,%48,%49,%50,%51}, {%52,%53,%54,%55}, %56, p, 1, 1, 0;\n}\n"
   : "+f"(d[0]),"+f"(d[1]),"+f"(d[2]),"+f"(d[3]),"+f"(d[4]),"+f"(d[5]),"+f"(d[6]),"+f"(d[7]),"+f"(d[8]),"+f"(d[9]),"+f"(d[10]),"+f"(d[11]),"+f"(d[12]),"+f"(d[13]),"+f"(d[14]),"+f"(d[15]),"+f"(d[16]),"+f"(d[17]),"+f"(d[18]),"+f"(d[19]),"+f"(d[20]),"+f"(d[21]),"+f"(d[22]),"+f"(d[23]),"+f"(d[24]),"+f"(d[25]),"+f"(d[26]),"+f"(d[27]),"+f"(d[28]),"+f"(d[29]),"+f"(d[30]),"+f"(d[31]),"+f"(d[32]),"+f"(d[33]),"+f"(d[34]),"+f"(d[35]),"+f"(d[36]),"+f"(d[37]),"+f"(d[38]),"+f"(d[39]),"+f"(d[40]),"+f"(d[41]),"+f"(d[42]),"+f"(d[43]),"+f"(d[44]),"+f"(d[45]),"+f"(d[46]),"+f"(d[47]),"+f"(d[48]),"+f"(d[49]),"+f"(d[50]),"+f"(d[51])
   : "r"(a[0]), "r"(a[1]), "r"(a[2]), "r"(a[3]), "l"(db), "r"(sd));
}
template<> __device__ __forceinline__ void wgmma_rs<96,0>(float* d, const uint32_t* a, uint64_t db, int sd) {
  asm volatile("{\n.reg .pred p;\nsetp.ne.b32 p, %53, 0;\nwgmma.mma_async.sync.aligned.m64n96k16.f32.bf16.bf16 {%0,%1,%2,%3,%4,%5,%6,%7,%8,%9,%10,%11,%12,%13,%14,%15,%16,%17,%18,%19,%20,%21,%22,%23,%24,%25,%26,%27,%28,%29,%30,%31,%32,%33,%34,%35,%36,%37,%38,%39,%40,%41,%42,%43,%44,%45,%46,%47}, {%48,%49,%50,%51}, %52, p, 1, 1, 0;\n}\n"
   : "+f"(d[0]),"+f"(d[1]),"+f"(d[2]),"+f"(d[3]),"+f"(d[4]),"+f"(d[5]),"+f"(d[6]),"+f"(d[7]),"+f"(d[8]),"+f"(d[9]),"+f"(d[10]),"+f"(d[11]),"+f"(d[12]),"+f"(d[13]),"+f"(d[14]),"+f"(d[15]),"+f"(d[16]),"+f"(d[17]),"+f"(d[18]),"+f"(d[19]),"+f"(d[20]),"+f"(d[21]),"+f"(d[22]),"+f"(d[23]),"+f"(d[24]),"+f"(d[25]),"+f"(d[26]),"+f"(d[27]),"+f"(d[28]),"+f"(d[29]),"+f"(d[30]),"+f"(d[31]),"+f"(d[32]),"+f"(d[33]),"+f"(d[34]),"+f"(d[35]),"+f"(d[36]),"+f"(d[37]),"+f"(d[38]),"+f"(d[39]),"+f"(d[40]),"+f"(d[41]),"+f"(d[42]),"+f"(d[43]),"+f"(d[44]),"+f"(d[45]),"+f"(d[46]),"+f"(d[47])
   : "r"(a[0]), "r"(a[1]), "r"(a[2]), "r"(a[3]), "l"(db), "r"(sd));
}
template<> __device__ __forceinline__ void wgmma_rs<88,0>(float* d, const uint32_t* a, uint64_t db, int sd) {
  asm volatile("{\n.reg .pred p;\nsetp.ne.b32 p, %49, 0;\nwgmma.mma_async.sync.aligned.m64n88k16.f32.bf16.bf16 {%0,%1,%2,%3,%4,%5,%6,%7,%8,%9,%10,%11,%12,%13,%14,%15,%16,%17,%18,%19,%20,%21,%22,%23,%24,%25,%26,%27,%28,%29,%30,%31,%32,%33,%34,%35,%36,%37,%38,%39,%40,%41,%42,%43}, {%44,%45,%46,%47}, %48, p, 1, 1, 0;\n}\n"
   : "+f"(d[0]),"+f"(d[1]),"+f"(d[2]),"+f"(d[3]),"+f"(d[4]),"+f"(d[5]),"+f"(d[6]),"+f"(d[7]),"+f"(d[8]),"+f"(d[9]),"+f"(d[10]),"+f"(d[11]),"+f"(d[12]),"+f"(d[13]),"+f"(d[14]),"+f"(d[15]),"+f"(d[16]),"+f"(d[17]),"+f"(d[18]),"+f"(d[19]),"+f"(d[20]),"+f"(d[21]),"+f"(d[22]),"+f"(d[23]),"+f"(d[24]),"+f"(d[25]),"+f"(d[26]),"+f"(d[27]),"+f"(d[28]),"+f"(d[29]),"+f"(d[30]),"+f"(d[31]),"+f"(d[32]),"+f"(d[33]),"+f"(d[34]),"+f"(d[35]),"+f"(d[36]),"+f"(d[37]),"+f"(d[38]),"+f"(d[39]),"+f"(d[40]),"+f"(d[41]),"+f"(d[42]),"+f"(d[43])
   : "r"(a[0]), "r"(a[1]), "r"(a[2]), "r"(a[3]), "l"(db), "r"(sd));
}
template<> __device__ __forceinline__ void wgmma_rs<80,0>(float* d, const uint32_t* a, uint64_t db, int sd) {
  asm volatile("{\n.reg .pred p;\nsetp.ne.b32 p, %45, 0;\nwgmma.mma_async.sync.aligned.m64n80k16.f32.bf16.bf16 {%0,%1,%2,%3,%4,%5,%6,%7,%8,%9,%10,%11,%12,%13,%14,%15,%16,%17,%18,%19,%20,%21,%22,%23,%24,%25,%26,%27,%28,%29,%30,%31,%32,%33,%34,%35,%36,%37,%38,%39}, {%40,%41,%42,%43}, %44, p, 1, 1, 0;\n}\n"
   : "+f"(d[0]),"+f"(d[1]),"+f"(d[2]),"+f"(d[3]),"+f"(d[4]),"+f"(d[5]),"+f"(d[6]),"+f"(d[7]),"+f"(d[8]),"+f"(d[9]),"+f"(d[10]),"+f"(d[11]),"+f"(d[12]),"+f"(d[13]),"+f"(d[14]),"+f"(d[15]),"+f"(d[16]),"+f"(d[17]),"+f"(d[18]),"+f"(d[19]),"+f"(d[20]),"+f"(d[21]),"+f"(d[22]),"+f"(d[23]),"+f"(d[24]),"+f"(d[25]),"+f"(d[26]),"+f"(d[27]),"+f"(d[28]),"+f"(d[29]),"+f"(d[30]),"+f"(d[31]),"+f"(d[32]),"+f"(d[33]),"+f"(d[34]),"+f"(d[35]),"+f"(d[36]),"+f"(d[37]),"+f"(d[38]),"+f"(d[39])
   : "r"(a[0]), "r"(a[1]), "r"(a[2]), "r"(a[3]), "l"(db), "r"(sd));
}
template<> __device__ __forceinline__ void wgmma_rs<72,0>(float* d, const uint32_t* a, uint64_t db, int sd) {
  asm volatile("{\n.reg .pred p;\nsetp.ne.b32 p, %41, 0;\nwgmma.mma_async.sync.aligned.m64n72k16.f32.bf16.bf16 {%0,%1,%2,%3,%4,%5,%6,%7,%8,%9,%10,%11,%12,%13,%14,%15,%16,%17,%18,%19,%20,%21,%22,%23,%24,%25,%26,%27,%28,%29,%30,%31,%32,%33,%34,%35}, {%36,%37,%38,%39}, %40, p, 1, 1, 0;\n}\n"
   : "+f"(d[0]),"+f"(d[1]),"+f"(d[2]),"+f"(d[3]),"+f"(d[4]),"+f"(d[5]),"+f"(d[6]),"+f"(d[7]),"+f"(d[8]),"+f"(d[9]),"+f"(d[10]),"+f"(d[11]),"+f"(d[12]),"+f"(d[13]),"+f"(d[14]),"+f"(d[15]),"+f"(d[16]),"+f"(d[17]),"+f"(d[18]),"+f"(d[19]),"+f"(d[20]),"+f"(d[21]),"+f"(d[22]),"+f"(d[23]),"+f"(d[24]),"+f"(d[25]),"+f"(d[26]),"+f"(d[27]),"+f"(d[28]),"+f"(d[29]),"+f"(d[30]),"+f"(d[31]),"+f"(d[32]),"+f"(d[33]),"+f"(d[34]),"+f"(d[35])
   : "r"(a[0]), "r"(a[1]), "r"(a[2]), "r"(a[3]), "l"(db), "r"(sd));
}
template<> __device__ __forceinline__ void wgmma_rs<64,0>(float* d, const uint32_t* a, uint64_t db, int sd) {
  asm volatile("{\n.reg .pred p;\nsetp.ne.b32 p, %37, 0;\nwgmma.mma_async.sync.aligned.m64n64k16.f32.bf16.bf16 {%0,%1,%2,%3,%4,%5,%6,%7,%8,%9,%10,%11,%12,%13,%14,%15,%16,%17,%18,%19,%20,%21,%22,%23,%24,%25,%26,%27,%28,%29,%30,%31}, {%32,%33,%34,%35}, %36, p, 1, 1, 0;\n}\n"
   : "+f"(d[0]),"+f"(d[1]),"+f"(d[2]),"+f"(d[3]),"+f"(d[4]),"+f"(d[5]),"+f"(d[6]),"+f"(d[7]),"+f"(d[8]),"+f"(d[9]),"+f"(d[10]),"+f"(d[11]),"+f"(d[12]),"+f"(d[13]),"+f"(d[14]),"+f"(d[15]),"+f"(d[16]),"+f"(d[17]),"+f"(d[18]),"+f"(d[19]),"+f"(d[20]),"+f"(d[21]),"+f"(d[22]),"+f"(d[23]),"+f"(d[24]),"+f"(d[25]),"+f"(d[26]),"+f"(d[27]),"+f"(d[28]),"+f"(d[29]),"+f"(d[30]),"+f"(d[31])
   : "r"(a[0]), "r"(a[1]), "r"(a[2]), "r"(a[3]), "l"(db), "r"(sd));
}
template<> __device__ __forceinline__ void wgmma_ss<64,0,1>(float* d, uint64_t da, uint64_t db, int sd) {
  asm volatile("{\n.reg .pred p;\nsetp.ne.b32 p, %34, 0;\nwgmma.mma_async.sync.aligned.m64n64k16.f32.bf16.bf16 {%0,%1,%2,%3,%4,%5,%6,%7,%8,%9,%10,%11,%12,%13,%14,%15,%16,%17,%18,%19,%20,%21,%22,%23,%24,%25,%26,%27,%28,%29,%30,%31}, %32, %33, p, 1, 1, 0, 1;\n}\n"
   : "+f"(d[0]),"+f"(d[1]),"+f"(d[2]),"+f"(d[3]),"+f"(d[4]),"+f"(d[5]),"+f"(d[6]),"+f"(d[7]),"+f"(d[8]),"+f"(d[9]),"+f"(d[10]),"+f"(d[11]),"+f"(d[12]),"+f"(d[13]),"+f"(d[14]),"+f"(d[15]),"+f"(d[16]),"+f"(d[17]),"+f"(d[18]),"+f"(d[19]),"+f"(d[20]),"+f"(d[21]),"+f"(d[22]),"+f"(d[23]),"+f"(d[24]),"+f"(d[25]),"+f"(d[26]),"+f"(d[27]),"+f"(d[28]),"+f"(d[29]),"+f"(d[30]),"+f"(d[31])
   : "l"(da), "l"(db), "r"(sd));
}
template<> __device__ __forceinline__ void wgmma_ss<64,1,1>(float* d, uint64_t da, uint64_t db, int sd) {
  asm volatile("{\n.reg .pred p;\nsetp.ne.b32 p, %34, 0;\nwgmma.mma_async.sync.aligned.m64n64k16.f32.bf16.bf16 {%0,%1,%2,%3,%4,%5,%6,%7,%8,%9,%10,%11,%12,%13,%14,%15,%16,%17,%18,%19,%20,%21,%22,%23,%24,%25,%26,%27,%28,%29,%30,%31}, %32, %33, p, 1, 1, 1, 1;\n}\n"
   : "+f"(d[0]),"+f"(d[1]),"+f"(d[2]),"+f"(d[3]),"+f"(d[4]),"+f"(d[5]),"+f"(d[6]),"+f"(d[7]),"+f"(d[8]),"+f"(d[9]),"+f"(d[10]),"+f"(d[11]),"+f"(d[12]),"+f"(d[13]),"+f"(d[14]),"+f"(d[15]),"+f"(d[16]),"+f"(d[17]),"+f"(d[18]),"+f"(d[19]),"+f"(d[20]),"+f"(d[21]),"+f"(d[22]),"+f"(d[23]),"+f"(d[24]),"+f"(d[25]),"+f"(d[26]),"+f"(d[27]),"+f"(d[28]),"+f"(d[29]),"+f"(d[30]),"+f"(d[31])
   : "l"(da), "l"(db), "r"(sd));
}
template<> __device__ __forceinline__ void wgmma_ss<192,0,1>(float* d, uint64_t da, uint64_t db, int sd) {
  asm volatile("{\n.reg .pred p;\nsetp.ne.b32 p, %98, 0;\nwgmma.mma_async.sync.aligned.m64n192k16.f32.bf16.bf16 {%0,%1,%2,%3,%4,%5,%6,%7,%8,%9,%10,%11,%12,%13,%14,%15,%16,%17,%18,%19,%20,%21,%22,%23,%24,%25,%26,%27,%28,%29,%30,%31,%32,%33,%34,%35,%36,%37,%38,%39,%40,%41,%42,%43,%44,%45,%46,%47,%48,%49,%50,%51,%52,%53,%54,%55,%56,%57,%58,%59,%60,%61,%62,%63,%64,%65,%66,%67,%68,%69,%70,%71,%72,%73,%74,%75,%76,%77,%78,%79,%80,%81,%82,%83,%84,%85,%86,%87,%88,%89,%90,%91,%92,%93,%94,%95}, %96, %97, p, 1, 1, 0, 1;\n}\n"
   : "+f"(d[0]),"+f"(d[1]),"+f"(d[2]),"+f"(d[3]),"+f"(d[4]),"+f"(d[5]),"+f"(d[6]),"+f"(d[7]),"+f"(d[8]),"+f"(d[9]),"+f"(d[10]),"+f"(d[11]),"+f"(d[12]),"+f"(d[13]),"+f"(d[14]),"+f"(d[15]),"+f"(d[16]),"+f"(d[17]),"+f"(d[18]),"+f"(d[19]),"+f"(d[20]),"+f"(d[21]),"+f"(d[22]),"+f"(d[23]),"+f"(d[24]),"+f"(d[25]),"+f"(d[26]),"+f"(d[27]),"+f"(d[28]),"+f"(d[29]),"+f"(d[30]),"+f"(d[31]),"+f"(d[32]),"+f"(d[33]),"+f"(d[34]),"+f"(d[35]),"+f"(d[36]),"+f"(d[37]),"+f"(d[38]),"+f"(d[39]),"+f"(d[40]),"+f"(d[41]),"+f"(d[42]),"+f"(d[43]),"+f"(d[44]),"+f"(d[45]),"+f"(d[46]),"+f"(d[47]),"+f"(d[48]),"+f"(d[49]),"+f"(d[50]),"+f"(d[51]),"+f"(d[52]),"+f"(d[53]),"+f"(d[54]),"+f"(d[55]),"+f"(d[56]),"+f"(d[57]),"+f"(d[58]),"+f"(d[59]),"+f"(d[60]),"+f"(d[61]),"+f"(d[62]),"+f"(d[63]),"+f"(d[64]),"+f"(d[65]),"+f"(d[66]),"+f"(d[67]),"+f"(d[68]),"+f"(d[69]),"+f"(d[70]),"+f"(d[71]),"+f"(d[72]),"+f"(d[73]),"+f"(d[74]),"+f"(d[75]),"+f"(d[76]),"+f"(d[77]),"+f"(d[78]),"+f"(d[79]),"+f"(d[80]),"+f"(d[81]),"+f"(d[82]),"+f"(d[83]),"+f"(d[84]),"+f"(d[85]),"+f"(d[86]),"+f"(d[87]),"+f"(d[88]),"+f"(d[89]),"+f"(d[90]),"+f"(d[91]),"+f"(d[92]),"+f"(d[93]),"+f"(d[94]),"+f"(d[95])
   : "l"(da), "l"(db), "r"(sd));
}
template<> __device__ __forceinline__ void wgmma_ss<192,1,1>(float* d, uint64_t da, uint64_t db, int sd) {
  asm volatile("{\n.reg .pred p;\nsetp.ne.b32 p, %98, 0;\nwgmma.mma_async.sync.aligned.m64n192k16.f32.bf16.bf16 {%0,%1,%2,%3,%4,%5,%6,%7,%8,%9,%10,%11,%12,%13,%14,%15,%16,%17,%18,%19,%20,%21,%22,%23,%24,%25,%26,%27,%28,%29,%30,%31,%32,%33,%34,%35,%36,%37,%38,%39,%40,%41,%42,%43,%44,%45,%46,%47,%48,%49,%50,%51,%52,%53,%54,%55,%56,%57,%58,%59,%60,%61,%62,%63,%64,%65,%66,%67,%68,%69,%70,%71,%72,%73,%74,%75,%76,%77,%78,%79,%80,%81,%82,%83,%84,%85,%86,%87,%88,%89,%90,%91,%92,%93,%94,%95}, %96, %97, p, 1, 1, 1, 1;\n}\n"
   : "+f"(d[0]),"+f"(d[1]),"+f"(d[2]),"+f"(d[3]),"+f"(d[4]),"+f"(d[5]),"+f"(d[6]),"+f"(d[7]),"+f"(d[8]),"+f"(d[9]),"+f"(d[10]),"+f"(d[11]),"+f"(d[12]),"+f"(d[13]),"+f"(d[14]),"+f"(d[15]),"+f"(d[16]),"+f"(d[17]),"+f"(d[18]),"+f"(d[19]),"+f"(d[20]),"+f"(d[21]),"+f"(d[22]),"+f"(d[23]),"+f"(d[24]),"+f"(d[25]),"+f"(d[26]),"+f"(d[27]),"+f"(d[28]),"+f"(d[29]),"+f"(d[30]),"+f"(d[31]),"+f"(d[32]),"+f"(d[33]),"+f"(d[34]),"+f"(d[35]),"+f"(d[36]),"+f"(d[37]),"+f"(d[38]),"+f"(d[39]),"+f"(d[40]),"+f"(d[41]),"+f"(d[42]),"+f"(d[43]),"+f"(d[44]),"+f"(d[45]),"+f"(d[46]),"+f"(d[47]),"+f"(d[48]),"+f"(d[49]),"+f"(d[50]),"+f"(d[51]),"+f"(d[52]),"+f"(d[53]),"+f"(d[54]),"+f"(d[55]),"+f"(d[56]),"+f"(d[57]),"+f"(d[58]),"+f"(d[59]),"+f"(d[60]),"+f"(d[61]),"+f"(d[62]),"+f"(d[63]),"+f"(d[64]),"+f"(d[65]),"+f"(d[66]),"+f"(d[67]),"+f"(d[68]),"+f"(d[69]),"+f"(d[70]),"+f"(d[71]),"+f"(d[72]),"+f"(d[73]),"+f"(d[74]),"+f"(d[75]),"+f"(d[76]),"+f"(d[77]),"+f"(d[78]),"+f"(d[79]),"+f"(d[80]),"+f"(d[81]),"+f"(d[82]),"+f"(d[83]),"+f"(d[84]),"+f"(d[85]),"+f"(d[86]),"+f"(d[87]),"+f"(d[88]),"+f"(d[89]),"+f"(d[90]),"+f"(d[91]),"+f"(d[92]),"+f"(d[93]),"+f"(d[94]),"+f"(d[95])
   : "l"(da), "l"(db), "r"(sd));
}

__device__ __forceinline__ void stats_publish(uint32_t sb, int layer, int rb, int hg, int ht, uint32_t tag) {
  const int lane = ht & 31, w = ht >> 5, g = lane >> 2, t = lane & 3, ks = hg & 3;
  uint32_t xa;
  if (layer == 0) {
    const int row = 16 * w + (lane & 15), kc = 2 * ks + (lane >> 4);
    xa = row * 128 + ((kc ^ (row & 7)) << 4);
  } else {
    const int k = 16 * ks + (lane & 7) + 8 * (lane >> 4), pc = 2 * w + ((lane >> 3) & 1);
    xa = k * 128 + ((pc ^ (k & 7)) << 4);
  }
  float s[4] = {0.f, 0.f, 0.f, 0.f}, q[4] = {0.f, 0.f, 0.f, 0.f};
#pragma unroll 1
  for (int c = hg >> 2; c < 8; c += 2) {
    uint32_t A[2][4];
    mbar_wait(sb + SM_BAR + 8 * (B_XF + c), layer);
#pragma unroll
    for (int h = 0; h < 2; h++) {
      if (layer == 0) ldsm4(A[h], sb + SM_X + c * 16384 + h * 8192 + xa);
      else ldsm4t(A[h], sb + SM_X + c * 16384 + h * 8192 + xa);
    }
    if (c >= 6) ATS(48, 256);
    if (c < 2) ATS(51, 256);
#pragma unroll
    for (int r = 0; r < 4; r++)
#pragma unroll
      for (int i = 0; i < 2; i++) {
        const uint32_t v = A[r >> 1][2 * i + (r & 1)];
        const float a = bf_lo(v), b = bf_hi(v);
        s[r] += a + b; q[r] = fmaf(a, a, q[r]); q[r] = fmaf(b, b, q[r]);
      }
  }
#pragma unroll
  for (int r = 0; r < 2; r++) {
    s[r] = ((t & 2) ? s[r + 2] : s[r]) + __shfl_xor_sync(~0u, (t & 2) ? s[r] : s[r + 2], 2);
    q[r] = ((t & 2) ? q[r + 2] : q[r]) + __shfl_xor_sync(~0u, (t & 2) ? q[r] : q[r + 2], 2);
  }
  s[0] = ((t & 1) ? s[1] : s[0]) + __shfl_xor_sync(~0u, (t & 1) ? s[0] : s[1], 1);
  q[0] = ((t & 1) ? q[1] : q[0]) + __shfl_xor_sync(~0u, (t & 1) ? q[0] : q[1], 1);
  st_part(&g_part[(rb * 8 + hg) * 128 + 64 * (t >> 1) + 16 * w + 8 * (t & 1) + g], s[0], q[0], tag);
  ATS(49, 256);
}
__device__ __forceinline__ void stats_gather(uint32_t sb, int rb, int ht, uint32_t tag) {
  const uint2* src = &g_part[rb * 8 * 128 + ht];
  uint2 v[8];
  for (int it = 0;; it++) {
    uint32_t bad = 0;
#pragma unroll
    for (int i = 0; i < 8; i++) v[i] = ld_part(src + i * 128);
#pragma unroll
    for (int i = 0; i < 8; i++) bad |= v[i].y ^ tag;
    if (__all_sync(~0u, (bad & 7u) == 0)) break;
    if (it > (1 << 22)) __trap();
  }
  float s = 0.f, q = 0.f;
#pragma unroll
  for (int i = 0; i < 8; i++) { s += __uint_as_float(v[i].x); q += __uint_as_float(v[i].y); }
  const float mean = s * (1.f / DM);
  const float rstd = rsqrt_approx(fmaxf(q * (1.f / DM) - mean * mean, 0.f) + 1e-5f);
  asm volatile("st.shared.v2.f32 [%0], {%1,%2};" ::"r"(sb + SM_ST + ht * 8), "f"(mean), "f"(rstd) : "memory");
  __syncwarp();
  if (elect_one()) mbar_arrive(sb + SM_BAR + 8 * B_STF);
}
__device__ __forceinline__ void halo_receive(uint32_t sb, int layer, int rb, int hg, int ht) {
  const int lane = ht & 31, h = ht >> 5;
  uint4 kv = make_uint4(0, 0, 0, 0);
  mbar_wait(sb + SM_BAR + 8 * B_SD, layer);
  if (rb & 7) {
    const uint32_t tag = 2 * lds32(sb + SM_EP) + layer + 1;
    const uint4* src = &g_halo[((rb - 1) * 8 + hg) * 192 + h * 48];
    if (layer == 0) delay<D_HALO>(); else delay<D_HALO1>();
    uint4 a;
    uint2 b;
    int it = 0;
    do {
      a = ld_tagged(src + lane); b = ld_part((const uint2*)(src + 32) + lane);
      if (++it > (1 << 22)) __trap();
    } while (!__all_sync(~0u, a.w == tag && b.y == tag));
    kv = make_uint4(a.x, a.y, movm_t(a.z), movm_t(b.x));
  }
  sts128(sb + SM_KVX + h * 512 + lane * 16, kv);
  ATS(61, 256);
  bar_arrive(7, 160);
  if (elect_one()) mbar_arrive(sb + SM_BAR + 8 * B_HF);
}

__device__ __forceinline__ void halo_receive1(uint32_t sb, int layer, int rb, int hg, int lane, uint32_t tag) {
  uint4 a[4];
  uint2 b[4];
  mbar_wait(sb + SM_BAR + 8 * B_SD, layer);
  if (rb & 7) {
    const uint4* src = &g_halo[((rb - 1) * 8 + hg) * 192];
    if (layer == 0) delay<D_HALO>(); else delay<D_HALO1>();
    for (int it = 0;; it++) {
      uint32_t bad = 0;
#pragma unroll
      for (int h = 0; h < 4; h++) { a[h] = ld_tagged(src + h * 48 + lane); b[h] = ld_part((const uint2*)(src + h * 48 + 32) + lane); }
#pragma unroll
      for (int h = 0; h < 4; h++) {
        bad |= (a[h].w ^ tag) | (b[h].y ^ tag);
        a[h].z = movm_t(a[h].z); a[h].w = movm_t(b[h].x);
      }
      if (__all_sync(~0u, bad == 0)) break;
      if (it > (1 << 22)) __trap();
    }
  } else {
#pragma unroll
    for (int h = 0; h < 4; h++) a[h] = make_uint4(0, 0, 0, 0);
  }
#pragma unroll
  for (int h = 0; h < 4; h++) sts128(sb + SM_KVX + h * 512 + lane * 16, a[h]);
  ATS(61, 448);
  bar_arrive(7, 64);
  if (lane < 4) mbar_arrive(sb + SM_BAR + 8 * B_HF);
}

template <bool TR>
__device__ __forceinline__ void gemm_section(float* acc, float2* cs, uint32_t sb, int layer, int wg, int w, int lane) {
  const uint32_t bar = sb + SM_BAR;
  const bool leader = (w == 0) && (lane == 0);
  auto issue = [&](int c, int slot) {
    mbar_wait(bar + 8 * (B_XF + c), layer);
    mbar_wait(bar + 8 * (B_KVF + c), layer);
    const uint64_t da = mkdesc(sb + SM_X + c * 16384 + wg * 8192, TR ? 8192 : 16, 1024, 1);
    const uint64_t db = mkdesc(sb + SM_W + slot * 24576, 8192, 1024, 1);
    wg_fence();
#pragma unroll
    for (int ks = 0; ks < 4; ks++) wgmma_ss<192, TR ? 1 : 0, 1>(acc, da + (TR ? ks * 128 : ks * 2), db + ks * 128, (c | ks) != 0);
    wg_commit();
  };
  auto step = [&](int c, int slot) {
    issue(c, slot);
    wg_wait<1>();
    if (leader) mbar_arrive(bar + 8 * (B_KVE + c - 1));
  };
  if (!TR) bar_sync(0, NTHREADS);
  if (TR && G_WAIT == 3 && wg == 1) bar_sync(14, 256);
  if (TR && G_WAIT == 4 && wg == 1) mbar_wait(bar + 8 * (B_P + 3), 0);
  issue(0, 0);
  if (threadIdx.x == 0) TS(2 + layer * 20 + 0);
  if (threadIdx.x == 128 && layer == 1) TS(60);
  auto ld_cs = [&](int j0) {
#pragma unroll
    for (int j = j0; j < j0 + 8; j++) cs[j] = lds64f(sb + SM_CS + 4 * (8 * j + 2 * (lane & 3)));
  };
  if (TR && CS_STEP == 0) ld_cs(8);
  step(1, 1);
  if (TR && CS_STEP == 0) ld_cs(16);
  if (TR && CS_STEP == 1) ld_cs(8);
  step(2, 2);
  if (TR && CS_STEP == 1) ld_cs(16);
  if (TR && CS_STEP == 2) ld_cs(8);
  step(3, 0);
  if (TR && CS_STEP == 2) ld_cs(16);
  step(4, 1);
  if (TR && CS_STEP == 4) ld_cs(8);
  step(5, 2);
  if (TR && CS_STEP == 4) ld_cs(16);
  if (!TR && !CS_LATE0) { mbar_wait(bar + 8 * B_CSF, 0); ld_cs(8); ld_cs(16); }
  if (wg == 0) bar_sync(5, 256);
  issue(6, 0);
  issue(7, 1);
  if (wg == 1) bar_arrive(5, 256);
  if (!TR && CS_LATE0) { mbar_wait(bar + 8 * B_CSF, 0); ld_cs(8); ld_cs(16); }
}

__device__ __forceinline__ void attn_phase(const Params& p, uint32_t sb, int layer, int rb, int hg, int wg, int w) {
  const int lane = opaque_tid() & 31;
  const int g = lane >> 2, t = lane & 3;
  const uint32_t bar = sb + SM_BAR;
  const int row0 = 64 * wg + 16 * w;
  const bool leader = (w == 0) && (lane == 0);
  float acc[96];
  float2 cs[24];
  if (layer) gemm_section<true>(acc, cs, sb, layer, wg, w, lane);
  else gemm_section<false>(acc, cs, sb, layer, wg, w, lane);
  ATS(41, 224);
  mbar_wait(bar + 8 * B_STF, layer);
  const uint32_t tag = 2 * lds32(sb + SM_EP) + layer + 1;
  const float2 st0 = lds64f(sb + SM_ST + (row0 + g) * 8), st1 = lds64f(sb + SM_ST + (row0 + g + 8) * 8);
  const float mean0 = st0.x, rstd0 = st0.y, mean1 = st1.x, rstd1 = st1.y;
  wg_wait<0>();
  if (threadIdx.x == 0) TS(2 + layer * 20 + 1);
  ATS(39, 224);
  if (leader) mbar_arrive(bar + 8 * B_QDONE);

  uint32_t fp[4][4], fl[4][4], fh[4][4], qa[4][4];
  const int cw = 4 * wg + w;
  {
    const float nm0 = -mean0 * rstd0, nm1 = -mean1 * rstd1;
    const uint32_t kvx = sb + SM_KVX + cw * 2048 + lane * 16;
#pragma unroll
    for (int h = 0; h < 4; h++)
#pragma unroll
      for (int k = 0; k < 4; k++) {
        const int j = 8 + (k >> 1) * 8 + 2 * h + (k & 1);
        fh[h][k] = packbf(fmaf(acc[4 * j + 2], rstd1, nm1 * cs[j].x), fmaf(acc[4 * j + 3], rstd1, nm1 * cs[j].y));
      }
    if (cw == 7) {
      uint4* halo = &g_halo[(rb * 8 + hg) * 192];
#pragma unroll
      for (int h = 0; h < 4; h++) {
        st_tagged3(halo + h * 48 + lane, fh[h][0], fh[h][1], fh[h][2], tag);
        asm volatile("st.relaxed.gpu.global.v2.u32 [%0], {%1,%2};" ::"l"((uint2*)(halo + h * 48 + 32) + lane), "r"(fh[h][3]), "r"(tag) : "memory");
      }
      if (elect_one()) mbar_arrive(bar + 8 * B_SD);
      if (layer == TLAYER && threadIdx.x == 224) TS(47);
    }
#pragma unroll
    for (int h = 0; h < 4; h++) { fh[h][2] = movm_t(fh[h][2]); fh[h][3] = movm_t(fh[h][3]); }
    if (cw != 7) {
#pragma unroll
      for (int h = 0; h < 4; h++) sts128(kvx + 2048 + h * 512, make_uint4(fh[h][0], fh[h][1], fh[h][2], fh[h][3]));
      bar_arrive(8 + cw, 64);
    }
    sched_fence<6>();
    if (layer == TLAYER && threadIdx.x == 0) TS(45);
#pragma unroll
    for (int j = 0; j < 8; j++) cs[j] = lds64f(sb + SM_CS + 4 * (8 * j + 2 * t));
#pragma unroll
    for (int h = 0; h < 4; h++)
#pragma unroll
      for (int k = 0; k < 4; k++) {
        const int j = 8 + (k >> 1) * 8 + 2 * h + (k & 1);
        fl[h][k] = packbf(fmaf(acc[4 * j], rstd0, nm0 * cs[j].x), fmaf(acc[4 * j + 1], rstd0, nm0 * cs[j].y));
        if (k >= 2) fl[h][k] = movm_t(fl[h][k]);
      }
#pragma unroll
    for (int h = 0; h < 4; h++) {
#pragma unroll
      for (int dh = 0; dh < 2; dh++) {
        const int j = 2 * h + dh;
        const float2 c2 = cs[j];
        qa[h][2 * dh] = packbf(fmaf(-mean0, c2.x, acc[4 * j + 0]), fmaf(-mean0, c2.y, acc[4 * j + 1]));
        qa[h][2 * dh + 1] = packbf(fmaf(-mean1, c2.x, acc[4 * j + 2]), fmaf(-mean1, c2.y, acc[4 * j + 3]));
      }
    }
    if (threadIdx.x == 0) TS(2 + layer * 20 + 2);
    if (QD_AT == 1) mbar_wait(bar + 8 * B_QDONE, layer);
    sched_fence<0>();
    bar_sync(7 + cw, cw == 0 && !HALO_W14 ? 160 : 64);
#pragma unroll
    for (int h = 0; h < 4; h++) {
      const uint4 v = lds128(kvx + h * 512);
      fp[h][0] = v.x; fp[h][1] = v.y; fp[h][2] = v.z; fp[h][3] = v.w;
    }
    if (threadIdx.x == 0) TS(2 + layer * 20 + 4);
  }

  const bool u0 = 2 * t > g, u1 = 2 * t + 1 > g;
  const uint32_t mU = (u0 ? 0x0000ffffu : 0u) | (u1 ? 0xffff0000u : 0u);
  const float cl2 = 0.25f * 1.4426950408889634f;
  const float sc0 = rstd0 * cl2, sc1 = rstd1 * cl2;
  const float cneg = ((rb & 7) == 0 && cw == 0) ? -INFINITY : 0.f;
  float v[4][4];
#pragma unroll
  for (int h = 0; h < 4; h++) {
    float T0[4] = {cneg, cneg, cneg, cneg}, T1[4] = {0.f, 0.f, 0.f, 0.f}, T2[4] = {0.f, 0.f, 0.f, 0.f};
    mma_bf16(T1, qa[h], fl[h][0], fl[h][1]);
    mma_bf16(T2, qa[h], fh[h][0], fh[h][1]);
    mma_bf16(T0, qa[h], fp[h][0], fp[h][1]);
    v[h][0] = u0 ? T0[0] : T1[0]; v[h][1] = u1 ? T0[1] : T1[1];
    v[h][2] = u0 ? T1[2] : T2[2]; v[h][3] = u1 ? T1[3] : T2[3];
  }
  float m0[4], m1[4];
#pragma unroll
  for (int h = 0; h < 4; h++) { m0[h] = fmaxf(v[h][0], v[h][1]); m1[h] = fmaxf(v[h][2], v[h][3]); }
#pragma unroll
  for (int o = 1; o <= 2; o <<= 1) {
#pragma unroll
    for (int h = 0; h < 4; h++) {
      m0[h] = fmaxf(m0[h], __shfl_xor_sync(~0u, m0[h], o));
      m1[h] = fmaxf(m1[h], __shfl_xor_sync(~0u, m1[h], o));
    }
  }
  float O0[4][4], O1[4][4], Z[4][4];
#pragma unroll
  for (int h = 0; h < 4; h++) {
    const float mm0 = -m0[h] * sc0, mm1 = -m1[h] * sc1;
    const uint32_t P0 = packbf(ex2(fmaf(v[h][0], sc0, mm0)), ex2(fmaf(v[h][1], sc0, mm0)));
    const uint32_t P1 = packbf(ex2(fmaf(v[h][2], sc1, mm1)), ex2(fmaf(v[h][3], sc1, mm1)));
#pragma unroll
    for (int k = 0; k < 4; k++) O0[h][k] = O1[h][k] = Z[h][k] = 0.f;
    mma_bf16_k8(Z[h], P0, P1, 0x3f803f80u);
    mma_bf16_k8(O0[h], P0 & ~mU, P1 & mU, fl[h][2]); mma_bf16_k8(O1[h], P0 & ~mU, P1 & mU, fl[h][3]);
    mma_bf16_k8(O0[h], P0 & mU, 0u, fp[h][2]); mma_bf16_k8(O1[h], P0 & mU, 0u, fp[h][3]);
    mma_bf16_k8(O0[h], 0u, P1 & ~mU, fh[h][2]); mma_bf16_k8(O1[h], 0u, P1 & ~mU, fh[h][3]);
  }
  const uint32_t ob = sb + SM_OST + wg * 8192;
  if (QD_AT == 0) mbar_wait(bar + 8 * B_QDONE, layer);
  const int o_row = 16 * w + (lane & 7) + 8 * ((lane >> 3) & 1);
#pragma unroll
  for (int h = 0; h < 4; h++) {
    const float i0 = rcp_approx(Z[h][0]), i1 = rcp_approx(Z[h][2]);
    const int ch = 2 * h + (lane >> 4);
    stsm4(ob + o_row * 128 + ((ch ^ (o_row & 7)) << 4), packbf(O0[h][0] * i0, O0[h][1] * i0), packbf(O0[h][2] * i1, O0[h][3] * i1),
          packbf(O1[h][0] * i0, O1[h][1] * i0), packbf(O1[h][2] * i1, O1[h][3] * i1));
  }
  if (threadIdx.x == 0) TS(2 + layer * 20 + 5);
  ATS(57, 128); ATS(20, 96);
  __syncwarp();
  if (elect_one()) {
    fence_async_smem();
    tma_st(&p.mapO, hg * 64, rb * 128 + row0, ob + w * 2048);
    bulk_commit();
    bulk_wait_all();
    uint32_t old;
    asm volatile("atom.acq_rel.cta.shared.inc.u32 %0, [%1], 7;" : "=r"(old) : "r"(sb + SM_EP + 4) : "memory");
    if (old == 7) {
      asm volatile("red.relaxed.gpu.global.add.u32 [%0], 2;" ::"l"(&g_cnt[(C_O + rb) * 32]) : "memory");
      asm volatile("mbarrier.arrive.shared::cta.b64 _, [%0], 2;" ::"r"(bar + 8 * B_OST) : "memory");
      asm volatile("mbarrier.arrive.shared::cta.b64 _, [%0], 2;" ::"r"(bar + 8 * B_AD) : "memory");
      TS(2 + layer * 20 + 6);
    }
  }
  __syncwarp();
}

__device__ __forceinline__ void proj_phase(const Params& p, uint32_t sb, int layer, int rb, int q, int wg, int w) {
  const int lane = opaque_tid() & 31;
  const bool TR = layer != 0;
  const int t = lane & 3;
  const uint32_t bar = sb + SM_BAR;
  const uint32_t rbx = sb + SM_R + wg * 8192;
  uint32_t res[16];
  mbar_wait(bar + 8 * B_RF, layer);
  if (threadIdx.x == 0) TS(2 + layer * 20 + 7);
  if (!TR) {
#pragma unroll
    for (int j = 0; j < 8; j += 2) {
      const int mi = lane >> 3;
      const int row = 16 * w + (lane & 7) + 8 * (mi & 1), ch = j + (mi >> 1);
      ldsm4(&res[2 * j], rbx + row * 128 + ((ch ^ (row & 7)) << 4));
    }
  } else {
#pragma unroll
    for (int j = 0; j < 8; j += 2) {
      const int mi = lane >> 3;
      const int line = 8 * (j + (mi >> 1)) + (lane & 7), pc = 2 * w + (mi & 1);
      ldsm4t(&res[2 * j], rbx + line * 128 + ((pc ^ (line & 7)) << 4));
    }
  }
  bar_sync(2 + wg, 128);
  float acc[32];
#pragma unroll
  for (int i = 0; i < 16; i++) {
    asm volatile("shl.b32 %0, %1, 16;" : "=f"(acc[2 * i]) : "r"(res[i]));
    asm volatile("and.b32 %0, %1, 0xffff0000;" : "=f"(acc[2 * i + 1]) : "r"(res[i]));
  }
  const uint32_t tag = part_tag(lds32(sb + SM_EP), 2 * layer + 1);
  mbar_wait(bar + 8 * B_ZF, layer);
  mbar_wait(bar + 8 * B_WOF, layer);
#pragma unroll P_UNROLL
  for (int c = 0; c < 8; c++) {
    mbar_wait(bar + 8 * (B_OF + c), layer);
    if (c == 0 && threadIdx.x == 0) TS(2 + layer * 20 + 8);
    const uint64_t da = mkdesc(sb + sm_o(c) + wg * 8192, 16, 1024, 1);
    const uint64_t db = mkdesc(sb + SM_WO + c * 8192, 8192, 1024, 1);
    wg_fence();
#pragma unroll
    for (int ks = 0; ks < 4; ks++) wgmma_ss<64, 0, 1>(acc, da + ks * 2, db + ks * 128, 1);
    wg_commit();
  }
  wg_wait<0>();
#pragma unroll
  for (int i = 0; i < 32; i++) asm volatile("" : "+f"(acc[i]) :: "memory");
  if (threadIdx.x == 0) TS(2 + layer * 20 + 9);
  if (lane == 0 && w == 0) mbar_arrive(bar + 8 * B_PDONE);
  {
    float s[4], qq[4];
#pragma unroll
    for (int k = 0; k < 4; k++) { s[k] = acc[k]; qq[k] = acc[k] * acc[k]; }
#pragma unroll
    for (int j = 1; j < 8; j++)
#pragma unroll
      for (int k = 0; k < 4; k++) { s[k] += acc[4 * j + k]; qq[k] = fmaf(acc[4 * j + k], acc[4 * j + k], qq[k]); }
    const float s0 = s[0] + s[1], s1 = s[2] + s[3], q0 = qq[0] + qq[1], q1 = qq[2] + qq[3];
    float sr = ((t & 1) ? s1 : s0) + __shfl_xor_sync(~0u, (t & 1) ? s0 : s1, 1);
    float qr = ((t & 1) ? q1 : q0) + __shfl_xor_sync(~0u, (t & 1) ? q0 : q1, 1);
    sr += __shfl_xor_sync(~0u, sr, 2);
    qr += __shfl_xor_sync(~0u, qr, 2);
    if (t < 2) st_part(&g_part[(rb * 8 + q) * 128 + 64 * wg + 16 * w + (lane >> 2) + 8 * t], sr, qr, tag);
    __syncwarp();
    if (elect_one()) mbar_arrive(bar + 8 * B_PS);
    sched_fence<7>();
  }
#pragma unroll
  for (int j = 0; j < 8; j += 2) {
    const int mi = lane >> 3;
    const int line = 8 * (j + (mi >> 1)) + (lane & 7), pc = 2 * w + (mi & 1);
    stsm4t(rbx + line * 128 + ((pc ^ (line & 7)) << 4), packbf(acc[4 * j], acc[4 * j + 1]), packbf(acc[4 * j + 2], acc[4 * j + 3]),
           packbf(acc[4 * j + 4], acc[4 * j + 5]), packbf(acc[4 * j + 6], acc[4 * j + 7]));
  }
  fence_writer();
  bar_sync(2 + wg, 128);
  if (w == 0 && elect_one()) {
    fence_reader();
    fence_async_global();
    tma_st(&p.mapXT, rb * 128 + wg * 64, (2 * layer) * DM + q * 64, rbx);
    bulk_commit();
    if (threadIdx.x == 0) TS(2 + layer * 20 + 10);
    bulk_wait_all();
    red_relaxed(&g_cnt[C_CS * 32 + 2 + layer]);
    if (wg == 0) mbar_arrive(bar + 8 * B_RE);
  }
  __syncwarp();
}
__device__ __forceinline__ void proj_stats(uint32_t sb, int layer, int rb, int q, int lane, uint32_t tag) {
  const int r = 16 * q + (lane & 15);
  const uint2* src = &g_part[rb * 8 * 128 + r];
  uint32_t* dst = g_stats + layer * LSEQ + (rb >> 1) * 256 + ((r >> 2) & 1) * 128 + ((rb & 1) * 16 + (r >> 3)) * 4 + (r & 3);
  mbar_wait(sb + SM_BAR + 8 * B_PS, layer);
  delay<D_PST>();
  for (int it = 0;; it++) {
    uint2 v[8];
#pragma unroll
    for (int i = 0; i < 8; i++) v[i] = ld_part(src + i * 128);
    float s[4], qq[4];
    uint32_t bad = 0;
#pragma unroll
    for (int i = 0; i < 4; i++) {
      s[i] = __uint_as_float(v[i].x) + __uint_as_float(v[i + 4].x);
      qq[i] = __uint_as_float(v[i].y) + __uint_as_float(v[i + 4].y);
      bad |= (v[i].y ^ tag) | (v[i + 4].y ^ tag);
    }
    const float mean = ((s[0] + s[1]) + (s[2] + s[3])) * (1.f / DM);
    const float rstd = rsqrt_approx(fmaxf(fmaf((qq[0] + qq[1]) + (qq[2] + qq[3]), 1.f / DM, -mean * mean), 0.f) + 1e-5f);
    const bool ok = __all_sync(~0u, (bad & 7u) == 0);
    if (ok && lane < 16)
      asm volatile("st.relaxed.gpu.global.u32 [%0], %1;" ::"l"(dst), "r"(max(packbf(NORM_FMA ? -mean * rstd : -mean, rstd), 1u)) : "memory");
    if (ok) break;
    if (it > (1 << 22)) __trap();
  }
}

#define NA 14
#define NP 15
template <int M0, int M1> __device__ __forceinline__ void conv_load(uint32_t* A, uint32_t pe) {
#pragma unroll
  for (int m = M0; m < M1; m++) {
    asm volatile("ld.shared.v2.b32 {%0,%1}, [%2];" : "=r"(A[4 * m]), "=r"(A[4 * m + 1]) : "r"(pe + 256 * m) : "memory");
    A[4 * m + 2] = lds32(pe + 256 * m - 4);
  }
}
__device__ __forceinline__ uint32_t copy_reg(uint32_t v, uint32_t zero) { uint32_t r; asm volatile("or.b32 %0, %1, %2;" : "=r"(r) : "r"(v), "r"(zero)); return r; }
__device__ __forceinline__ uint32_t copy_reg2(uint32_t v, uint32_t zero) { uint32_t r; asm volatile("xor.b32 %0, %1, %2;" : "=r"(r) : "r"(v), "r"(zero)); return r; }
__device__ __forceinline__ void conv_park(uint32_t* P, uint32_t pe) {
#pragma unroll
  for (int m = 0; m < NP; m++)
#pragma unroll
    for (int k = 0; k < 3; k++) P[3 * m + k] = lds32(pe + 256 * m - 4 + 4 * k);
}
__device__ __forceinline__ void conv_unpark(uint32_t* A, const uint32_t* P, uint32_t zero) {
#pragma unroll
  for (int m = 0; m < NP; m++) {
    A[4 * m + 2] = copy_reg(P[3 * m], zero); A[4 * m] = copy_reg(P[3 * m + 1], zero);
    A[4 * m + 3] = copy_reg2(P[3 * m + 1], zero); A[4 * m + 1] = copy_reg(P[3 * m + 2], zero);
  }
}
template <int M0, int M1> __device__ __forceinline__ void conv_mmas(float* acc, const uint32_t* A, uint64_t d) {
  if constexpr (M0 < M1) {
    wgmma_rs<128 - 8 * (M0 / 2), 0>(acc, A + 4 * M0, d + (uint64_t)(4 * M0), M0 != 0);
    conv_mmas<M0 + 1, M1>(acc, A, d);
  }
}
struct SumAddr { uint32_t l0, l1, l2, se, so; };
__device__ __forceinline__ SumAddr conv_sum_addr(uint32_t sb, int c) {
  auto ua = [&](int j) { return sb + cv_u(0) + (127 - (j >> 3)) * 16 + (j & 7) * 2; };
  auto sa = [&](int hc) { const int ci = hc & ~1; return sb + cv_s(0) + ((ci >> 3) & 1) * 1024 + (ci >> 4) * 128 + (((ci ^ (ci >> 4)) & 7) << 4) + (hc & 1) * 8; };
  const int j0 = 4 * (c - 1);
  return {ua(j0 - 2), ua(j0), ua(j0 + 4), sa((c + 1) & 127), sa(c) + 2048};
}
__device__ __forceinline__ void sts64(uint32_t a, uint32_t x, uint32_t y) { asm volatile("st.shared.v2.b32 [%0], {%1,%2};" ::"r"(a), "r"(x), "r"(y) : "memory"); }
__device__ __forceinline__ void conv_sums(const SumAddr& sa, int lc, int c) {
  uint32_t e[4], o[4];
  {
    const float2 em = lds64f(sa.l1 + lc * 32768), om = lds64f(sa.l1 + lc * 32768 + CV_UH);
    e[0] = lds32(sa.l0 + lc * 32768); o[0] = lds32(sa.l0 + lc * 32768 + CV_UH);
    e[3] = lds32(sa.l2 + lc * 32768); o[3] = lds32(sa.l2 + lc * 32768 + CV_UH);
    e[1] = __float_as_uint(em.x); e[2] = __float_as_uint(em.y); o[1] = __float_as_uint(om.x); o[2] = __float_as_uint(om.y);
  }
  uint32_t s7e[2], s7o[2], s9e[2], s9o[2];
  uint32_t pw[4], sh[3];
#pragma unroll
  for (int k = 0; k < 4; k++) pw[k] = hadd2(e[k], o[k]);
#pragma unroll
  for (int k = 0; k < 3; k++) sh[k] = __byte_perm(pw[k], pw[k + 1], 0x5432);
#pragma unroll
  for (int k = 0; k < 2; k++) {
    const uint32_t t3 = hadd2(hadd2(sh[k], sh[k + 1]), pw[k + 1]);
    s7e[k] = hadd2(t3, o[k]); s7o[k] = hadd2(t3, e[k + 2]);
    s9e[k] = hadd2(s7o[k], pw[k]); s9o[k] = hadd2(s7e[k], pw[k + 2]);
  }
  if (c == 127) s9e[0] = s9e[1] = s9o[0] = s9o[1] = 0u;
  sts64(sa.se + lc * 32768, s9e[0], s9e[1]); sts64((sa.se ^ 16) + lc * 32768, s9o[0], s9o[1]);
  sts64(sa.so + lc * 32768, s7e[0], s7e[1]); sts64((sa.so ^ 16) + lc * 32768, s7o[0], s7o[1]);
}

__device__ __forceinline__ void conv_epi(uint32_t sb, int layer, int cta, int ch, int c0, uint4 x0, uint4 x1) {
  uint4 v[2][4];
  const uint4 xr[2] = {x0, x1};
  mbar_wait(sb + SM_BAR + 8 * (B_P + ch), layer);
#pragma unroll
  for (int u = 0; u < 2; u++) {
    const uint32_t pb = sb + cv_pb(ch) + u * (CV_PBW / 2) + c0 * 16;
#pragma unroll
    for (int k = 0; k < 4; k++) v[u][k] = lds128(pb + k * CV_PBW);
  }
#pragma unroll
  for (int u = 0; u < 2; u++) {
    uint4 o;
    o.x = hadd2(xr[u].x, hadd2(hadd2(v[u][0].x, v[u][1].x), hadd2(v[u][2].x, v[u][3].x)));
    o.y = hadd2(xr[u].y, hadd2(hadd2(v[u][0].y, v[u][1].y), hadd2(v[u][2].y, v[u][3].y)));
    o.z = hadd2(xr[u].z, hadd2(hadd2(v[u][0].z, v[u][1].z), hadd2(v[u][2].z, v[u][3].z)));
    o.w = hadd2(xr[u].w, hadd2(hadd2(v[u][0].w, v[u][1].w), hadd2(v[u][2].w, v[u][3].w)));
    if (layer == 0) sts128(sb + cv_s(ch) + (c0 + 128 * u) * 16, o);
    else st_tagged3((uint4*)(g_xT + (size_t)(3 * DM + cv_chan(cta, ch)) * LSEQ) + c0 + 128 * u, o.x, o.y, o.z, o.w);
  }
}
__device__ __forceinline__ void warp_release(uint32_t b) {
  fence_writer();
  __syncwarp();
  if (elect_one()) mbar_arrive(b);
}

__device__ __forceinline__ void conv_prep_load(uint32_t sb, int layer, int cta, int c, uint4 (&xr)[4], uint4 (&st)[4]) {
  sched_fence<8>();
  mbar_wait(sb + SM_BAR + 8 * B_GB, layer);
  if (threadIdx.x == 0) TS(2 + layer * 20 + 11);
  xr[0] = ld_tagged((const uint4*)(g_xT + (size_t)(2 * layer * DM + cta) * LSEQ) + c);
#pragma unroll
  for (int i = 0; i < 2; i++) st[i] = ld_tagged((const uint4*)g_stats + layer * 512 + (c >> 5) * 64 + i * 32 + (c & 31));
}
template <bool HELPER>
__device__ __forceinline__ void conv_prep(uint32_t sb, int layer, int cta, int c, uint4 (&xr)[4], uint4 (&st)[4], const SumAddr& sa) {
  const uint32_t bar = sb + SM_BAR;
  const uint4* xin = (const uint4*)(g_xT + (size_t)(2 * layer * DM + cta) * LSEQ) + c;
  for (int it = 0;; it++) {
    const uint32_t vs = min(min(min(st[0].x, st[0].y), min(st[0].z, st[0].w)), min(min(st[1].x, st[1].y), min(st[1].z, st[1].w)));
    if (__all_sync(~0u, vs != 0 && xr[0].x != ~0u)) break;
    if (it > (1 << 22)) __trap();
    if (!__all_sync(~0u, xr[0].x != ~0u)) xr[0] = ld_tagged(xin);
    if (!__all_sync(~0u, vs != 0)) {
#pragma unroll
      for (int i = 0; i < 2; i++) st[i] = ld_tagged((const uint4*)g_stats + layer * 512 + (c >> 5) * 64 + i * 32 + (c & 31));
    }
  }
  const uint32_t nm[4] = {__byte_perm(st[0].x, st[0].y, 0x5410), __byte_perm(st[0].z, st[0].w, 0x5410), __byte_perm(st[1].x, st[1].y, 0x5410), __byte_perm(st[1].z, st[1].w, 0x5410)};
  const uint32_t rs[4] = {__byte_perm(st[0].x, st[0].y, 0x7632), __byte_perm(st[0].z, st[0].w, 0x7632), __byte_perm(st[1].x, st[1].y, 0x7632), __byte_perm(st[1].z, st[1].w, 0x7632)};
  if (threadIdx.x == 0) TS(2 + layer * 20 + 12);
  const int a = c & 127, h = c >> 7;
#pragma unroll
  for (int i = 0; i < 4; i++) {
    if (i == 1) {
      mbar_wait(bar + 8 * B_XV, layer);
#pragma unroll
      for (int j = 1; j < 4; j++) xr[j] = ld_tagged(xin + j * (128 * LSEQ / 8));
      if (HELPER) {
        mbar_wait(bar + 8 * B_U, layer);
        conv_sums(sa, 0, c);
        fence_async_smem();
        bar_arrive(7, 256);
        sched_fence<1>();
        if (layer == 1 && c == 0) TS(46);
      }
    }
    const uint32_t x[4] = {xr[i].x, xr[i].y, xr[i].z, xr[i].w};
    uint32_t u[4];
#pragma unroll
    for (int k = 0; k < 4; k++)
      u[k] = NORM_FMA ? hfma2(x[k], rs[k], nm[k]) : hmul2(hadd2(x[k], nm[k]), rs[k]);
    sts128(sb + cv_u(i) + h * CV_UH + (127 - a) * 16, make_uint4(u[0], u[1], u[2], u[3]));
    warp_release(bar + 8 * (B_U + i));
    sched_fence<2>();
  }
}
__device__ __forceinline__ void conv_zero(uint32_t sb, int ht) {
  if (ht < 96) {
    const int ch = ht / 24, h2 = (ht / 12) & 1, qq = ht % 12;
    sts128(sb + cv_u(ch) + h2 * CV_UH + (128 + qq) * 16, make_uint4(0, 0, 0, 0));
  }
  if (ht >= 80) {
    const int i = ht - 80, ch = i / 12, q2 = i % 12;
    const int w2 = q2 < 2 ? 1 : q2 < 6 ? 2 : 3, cc = q2 < 2 ? q2 : q2 < 6 ? q2 - 2 : q2 - 6;
    sts128(sb + cv_pb(ch) + w2 * CV_PBW + (cc & 1) * (CV_PBW / 2) + (cc >> 1) * 16, make_uint4(0, 0, 0, 0));
  }
}

#define HANDOVER 1
template <int R>
__device__ __forceinline__ void conv_round(uint32_t sb, int layer, int wg, uint32_t* A, const uint32_t* P, uint32_t pb, uint32_t pe2) {
  const uint32_t bar = sb + SM_BAR;
  const int ch = 2 * R + 1 - wg;
  float acc[64];
  const uint64_t d = mkdesc(sb + cv_u(ch), CV_UH, 128, 0);
  FTS(39);
  if (R == 0) {
    mbar_wait(bar + 8 * (B_U + ch), layer);
    fence_reader();
  }
  sched_fence<3>();
  if (R == 1 || wg == 0) bar_sync(10 + ch, 256);
  if (layer == 0 && ch > 0 && ((PAUSE >> (ch - 1)) & 1)) mbar_wait(bar + 8 * (B_E + ch - 1), 0);
  if (layer == 0 && ch > 0 && ((PAUSE >> (ch + 3)) & 1)) mbar_wait(bar + 8 * (B_P + ch - 1), 0);
  FTS(41);
  if (ch == 0 && threadIdx.x == 128) TS(2 + layer * 20 + 13);
  wg_fence();
  conv_mmas<0, 1>(acc, A, d); conv_mmas<2, NA + 1>(acc, A, d);
  wg_commit();
  FTS(51);
  if (HANDOVER == 0 && (R == 0 || wg == 1)) bar_arrive(11 + ch, 256);
  bar_sync(7 + ch, 256);
  wg_fence();
  conv_mmas<1, 2>(acc, A, d); conv_mmas<NA + 1, 17>(acc, A, d);
  wgmma_ss<64, 1, 1>(acc, mkdesc(sb + cv_s(ch), 1024, 1024, 1), mkdesc(sb + cv_ft(ch), 256, 16, 0), 1);
  wgmma_ss<64, 1, 1>(acc, mkdesc(sb + cv_s(ch) + 2048, 1024, 1024, 1), mkdesc(sb + cv_ft(ch) + 512, 256, 16, 0), 1);
  wg_commit();
  if (HANDOVER == 1 && (R == 0 || wg == 1 || (G_WAIT == 3 && layer == 0))) bar_arrive(11 + ch, 256);
  FTS(61);
  wg_wait<0>();
#pragma unroll
  for (int j = 0; j < 16; j += 2)
    stsm4t(pb + R * 65536 - j * 128, packbf(acc[4 * j], acc[4 * j + 1]), packbf(acc[4 * j + 2], acc[4 * j + 3]),
           packbf(acc[4 * j + 4], acc[4 * j + 5]), packbf(acc[4 * j + 6], acc[4 * j + 7]));
  __syncwarp();
  if (elect_one()) mbar_arrive(bar + 8 * (B_P + ch));
  if (threadIdx.x == 0) TS(2 + layer * 20 + 14 + R);
  FTS(57);
  if (R == 0) {
    conv_unpark(A, P, opaque_tid() >> 10);
    mbar_wait(bar + 8 * (B_U + ch + 2), layer);
    fence_reader();
    conv_load<NP, 17>(A, pe2);
#pragma unroll
    for (int m = NP; m < 17; m++) A[4 * m + 3] = lds32(pe2 + 256 * m);
  }
}
__device__ __forceinline__ void conv_phase(const Params& p, uint32_t sb, int layer, int cta) {
  const int tid = opaque_tid();
  const int wg = __shfl_sync(~0u, tid >> 7, 0), w = __shfl_sync(~0u, (tid >> 5) & 3, 0);
  const uint32_t bar = sb + SM_BAR;
  uint32_t A[68], P[3 * NP];
  const uint32_t pe = sb + cv_pe(1 - wg) + 4 * (16 + 16 * w + 2 * ((tid & 31) >> 2) - 4 * (tid & 3));
  mbar_wait(bar + 8 * B_PE, layer);
  conv_load<0, 17>(A, pe);
#pragma unroll
  for (int m = 0; m < 17; m++) A[4 * m + 3] = copy_reg(A[4 * m], tid >> 10);
  if (wg == 0) {
    uint4 xr[4], st[4];
    if (PARK_FIRST) conv_park(P, pe + 65536);
    conv_prep_load(sb, layer, cta, tid + 128, xr, st);
    if (!PARK_FIRST) conv_park(P, pe + 65536);
    conv_prep<false>(sb, layer, cta, opaque_tid() + 128, xr, st, SumAddr());
  } else {
    conv_park(P, pe + 65536);
  }
  uint32_t pb;
  {
    const int l2 = opaque_tid() & 31, mt = l2 >> 3;
    pb = sb + cv_pb(1 - wg) + w * CV_PBW + (mt & 1) * (CV_PBW / 2) + (127 - 8 * (mt >> 1) - (l2 & 7) + w) * 16;
  }
  conv_round<0>(sb, layer, wg, A, P, pb, pe + 65536);
  conv_round<1>(sb, layer, wg, A, P, pb, 0);
  if (G_WAIT == 1 && layer == 0) mbar_wait(bar + 8 * (B_E + 3), layer);
  if (G_WAIT == 2 && layer == 0) mbar_wait(bar + 8 * (B_P + 3), layer);
}

__device__ __forceinline__ void final_phase(const Params& p, uint32_t sb, int cta, int wg, int w) {
  const int lane = opaque_tid() & 31, g = lane >> 2, t = lane & 3;
  constexpr int RS = 2 * DM;
  int it = 0;
  {
    const int lc = wg ? 0 : 3;
    const int p0 = (cta & 15) * 128 + 32 * w, c0 = 128 * lc + (cta >> 4) * 16;
    const bf16* src = g_xT + (size_t)(3 * DM + c0 + 4 * (g >> 1) + (g & 1)) * LSEQ + p0 + 8 * t;
    bf16* dst = p.out + (size_t)(2 * ((p0 & 1023) + 8 * (g >> 1) + (g & 1)) + (p0 >> 10)) * DM + c0 + 4 * t;
    if (wg == 0) {
      mbar_wait(sb + SM_BAR + 8 * (B_E + 3), 1);
      delay<D_FIN>();
    }
    uint4 a, b;
    for (;;) {
      a = ld_tagged((const uint4*)src); b = ld_tagged((const uint4*)(src + 2 * LSEQ));
      if (__all_sync(~0u, max(a.x, b.x) != ~0u)) break;
      if (++it > (1 << 22)) __trap();
    }
    if (threadIdx.x == 0) TS(42);
    *(uint2*)dst = make_uint2(movm_t(a.x), movm_t(b.x));
    *(uint2*)(dst + 2 * RS) = make_uint2(movm_t(a.y), movm_t(b.y));
    *(uint2*)(dst + 4 * RS) = make_uint2(movm_t(a.z), movm_t(b.z));
    *(uint2*)(dst + 6 * RS) = make_uint2(movm_t(a.w), movm_t(b.w));
  }
  if (wg == 1) {
    const int lc = 1 + (w >> 1);
    const int p0 = (cta & 31) * 64 + 32 * (w & 1), c0 = 128 * lc + (cta >> 5) * 32;
    const bf16* src = g_xT + (size_t)(3 * DM + c0 + 8 * (g >> 1) + (g & 1)) * LSEQ + p0 + 8 * t;
    bf16* dst = p.out + (size_t)(2 * ((p0 & 1023) + 8 * (g >> 1) + (g & 1)) + (p0 >> 10)) * DM + c0 + 8 * t;
    mbar_wait(sb + SM_BAR + 8 * (B_E + lc), 1);
    if (lc >= FIN_D0) delay<D_FIN2>();
    uint4 v[4];
    for (;;) {
#pragma unroll
      for (int q = 0; q < 4; q++) v[q] = ld_tagged((const uint4*)(src + 2 * q * LSEQ));
      if (__all_sync(~0u, max(max(v[0].x, v[1].x), max(v[2].x, v[3].x)) != ~0u)) break;
      if (++it > (1 << 22)) __trap();
    }
    *(uint4*)dst = make_uint4(movm_t(v[0].x), movm_t(v[1].x), movm_t(v[2].x), movm_t(v[3].x));
    *(uint4*)(dst + 2 * RS) = make_uint4(movm_t(v[0].y), movm_t(v[1].y), movm_t(v[2].y), movm_t(v[3].y));
    *(uint4*)(dst + 4 * RS) = make_uint4(movm_t(v[0].z), movm_t(v[1].z), movm_t(v[2].z), movm_t(v[3].z));
    *(uint4*)(dst + 6 * RS) = make_uint4(movm_t(v[0].w), movm_t(v[1].w), movm_t(v[2].w), movm_t(v[3].w));
  }
  if (threadIdx.x == 0) TS(43);
  if (threadIdx.x == 192) TS(63);
  if (threadIdx.x == 160) TS(53);
  if (threadIdx.x == 0) LTS(1);
}

struct cplx { float r, i; };
__device__ __forceinline__ cplx cmul(cplx a, cplx b) { return {fmaf(a.r, b.r, -a.i * b.i), fmaf(a.r, b.i, a.i * b.r)}; }
__device__ __forceinline__ cplx csqr(cplx a) { return {fmaf(a.r, a.r, -a.i * a.i), (a.r + a.r) * a.i}; }
__device__ __forceinline__ cplx cexp_l(float ar2, float ai, float l) {
  const float m = ex2(ar2 * l);
  const float x = ai * l;
  return {m * __cosf(x), m * __sinf(x)};
}

__device__ __forceinline__ void colsum_publish(uint32_t sb, int rb, int hg, int ht, uint32_t tag) {
  const int lane = ht & 31, q = lane & 15, h = lane >> 4;
  const uint32_t src = sb + SM_CW + (ht >> 5) * 4096 + h * 128 + (q & 1) * 8;
  float s[4] = {0.f, 0.f, 0.f, 0.f};
#pragma unroll 8
  for (int r = 0; r < 16; r++) {
    const float2 v = lds64f(src + r * 256 + (((q >> 1) ^ ((2 * r + h) & 7)) << 4));
    s[0] += bf_lo(__float_as_uint(v.x)); s[1] += bf_hi(__float_as_uint(v.x));
    s[2] += bf_lo(__float_as_uint(v.y)); s[3] += bf_hi(__float_as_uint(v.y));
  }
#pragma unroll
  for (int k = 0; k < 4; k++) s[k] += __shfl_xor_sync(~0u, s[k], 16);
  if (h == 0)
    st_tagged3(&g_colsum[(hg * 16 + rb) * 48 + (ht >> 5) * 16 + q], (__float_as_uint(s[0]) & ~7u) | tag, __float_as_uint(s[1]),
               __float_as_uint(s[2]), __float_as_uint(s[3]));
}
__device__ __forceinline__ void colsum_gather(uint32_t sb, int hg, int ht, uint32_t tag) {
  const int lane = ht & 31, rec = (ht >> 5) * 16 + (lane & 15);
  const uint4* src = &g_colsum[(hg * 16 + (lane >> 4) * 8) * 48 + rec];
  float s[4] = {0.f, 0.f, 0.f, 0.f};
#pragma unroll 1
  for (int h = 0; h < 2; h++, src += 4 * 48) {
    uint4 v[4];
    int it = 0;
    do {
#pragma unroll
      for (int i = 0; i < 4; i++) v[i] = ld_tagged(src + i * 48);
      if (++it > (1 << 22)) __trap();
    } while (!__all_sync(~0u, (v[0].x & 7u) == tag && (v[1].x & 7u) == tag && (v[2].x & 7u) == tag && (v[3].x & 7u) == tag));
#pragma unroll
    for (int i = 0; i < 4; i++) {
      s[0] += __uint_as_float(v[i].x & ~7u); s[1] += __uint_as_float(v[i].y); s[2] += __uint_as_float(v[i].z); s[3] += __uint_as_float(v[i].w);
    }
  }
#pragma unroll
  for (int k = 0; k < 4; k++) s[k] += __shfl_xor_sync(~0u, s[k], 16);
  if (lane < 16) sts128f(sb + SM_CS + rec * 16, s[0], s[1], s[2], s[3]);
}

__device__ __forceinline__ uint32_t packh(float lo, float hi) { uint32_t r; asm("cvt.rn.f16x2.f32 %0, %1, %2;" : "=r"(r) : "f"(hi), "f"(lo)); return r; }
__device__ __forceinline__ void mma_f16(float* d, uint32_t a0, uint32_t a1, uint32_t a2, uint32_t a3, uint32_t b0, uint32_t b1) {
  asm volatile("mma.sync.aligned.m16n8k16.row.col.f32.f16.f16.f32 {%0,%1,%2,%3}, {%4,%5,%6,%7}, {%8,%9}, {%0,%1,%2,%3};"
      : "+f"(d[0]), "+f"(d[1]), "+f"(d[2]), "+f"(d[3]) : "r"(a0), "r"(a1), "r"(a2), "r"(a3), "r"(b0), "r"(b1));
}
struct HSeed { uint32_t r, i; };
__device__ __forceinline__ HSeed hseed(cplx s) { return {packh(s.r, s.r), packh(s.i, s.i)}; }
__device__ __forceinline__ void hcmul(uint32_t& o_r, uint32_t& o_i, uint32_t br, uint32_t bi, HSeed s) {
  asm("{\n.reg .b32 t, u;\nmul.rn.f16x2 t, %3, %5;\nneg.f16x2 t, t;\nmul.rn.f16x2 u, %3, %4;\nfma.rn.f16x2 %0, %2, %4, t;\nfma.rn.f16x2 %1, %2, %5, u;\n}"
      : "=&r"(o_r), "=&r"(o_i) : "r"(br), "r"(bi), "r"(s.r), "r"(s.i));
}
struct HTile { uint32_t r[4], i[4]; };
__device__ __forceinline__ void tile_set(HTile& t, int k, cplx a, cplx b) { t.r[k] = packh(a.r, b.r); t.i[k] = packh(a.i, b.i); }
__device__ __forceinline__ void tile_upper(HTile& t, HSeed s) { hcmul(t.r[2], t.i[2], t.r[0], t.i[0], s); hcmul(t.r[3], t.i[3], t.r[1], t.i[1], s); }
__device__ __forceinline__ HTile tile_shift(const HTile& t, HSeed s) {
  HTile o;
#pragma unroll
  for (int k = 0; k < 4; k++) hcmul(o.r[k], o.i[k], t.r[k], t.i[k], s);
  return o;
}
__device__ __forceinline__ void tile_put(const HTile& t, uint32_t a) {
  sts128(a, make_uint4(t.r[0], t.r[1], t.r[2], t.r[3]));
  sts128(a + 512, make_uint4(t.i[0], t.i[1], t.i[2], t.i[3]));
}
__device__ __forceinline__ HTile tile_get(uint32_t a) { HTile o; ldsm4t(o.r, a); ldsm4t(o.i, a + 512); return o; }
__device__ __forceinline__ void tile_mma(float* T, const HTile& a0, const HTile& a1, const HTile& b) {
  mma_f16(T, a0.r[0], a0.r[1], a0.r[2], a0.r[3], b.r[0], b.r[1]);
  mma_f16(T, a0.i[0], a0.i[1], a0.i[2], a0.i[3], b.i[0], b.i[1]);
  mma_f16(T, a1.r[0], a1.r[1], a1.r[2], a1.r[3], b.r[2], b.r[3]);
  mma_f16(T, a1.i[0], a1.i[1], a1.i[2], a1.i[3], b.i[2], b.i[3]);
}
__device__ __forceinline__ void tile_mma2(float* T, float* U, const HTile& a0, const HTile& a1, const HTile& b, const HTile& c) {
  mma_f16(T, a0.r[0], a0.r[1], a0.r[2], a0.r[3], b.r[0], b.r[1]);
  mma_f16(U, a0.r[0], a0.r[1], a0.r[2], a0.r[3], c.r[0], c.r[1]);
  mma_f16(T, a0.i[0], a0.i[1], a0.i[2], a0.i[3], b.i[0], b.i[1]);
  mma_f16(U, a0.i[0], a0.i[1], a0.i[2], a0.i[3], c.i[0], c.i[1]);
  mma_f16(T, a1.r[0], a1.r[1], a1.r[2], a1.r[3], b.r[2], b.r[3]);
  mma_f16(U, a1.r[0], a1.r[1], a1.r[2], a1.r[3], c.r[2], c.r[3]);
  mma_f16(T, a1.i[0], a1.i[1], a1.i[2], a1.i[3], b.i[2], b.i[3]);
  mma_f16(U, a1.i[0], a1.i[1], a1.i[2], a1.i[3], c.i[2], c.i[3]);
}
__device__ __forceinline__ void kgen_unit(uint32_t tab, uint32_t taba, float ar2, float ai, cplx c, float (&T)[5][4]) {
  const cplx z1 = cexp_l(ar2, ai, 1.f), z16 = cexp_l(ar2, ai, 16.f), z256 = cexp_l(ar2, ai, 256.f);
  HTile a0, a1, b0, b1;
  {
    const cplx y1 = {z16.r, -z16.i}, y2 = csqr(y1), y3 = cmul(y2, y1), y4 = csqr(y2), y5 = cmul(y4, y1), y6 = csqr(y3), y7 = cmul(y4, y3);
    HTile t;
    tile_set(t, 0, {1.f, 0.f}, y1); tile_set(t, 1, y2, y3); tile_set(t, 2, y4, y5); tile_set(t, 3, y6, y7);
    const HTile u = tile_shift(t, hseed(csqr(y4)));
    __syncwarp();
    tile_put(t, tab); tile_put(u, tab + 1024);
    __syncwarp();
    a0 = tile_get(taba); a1 = tile_get(taba + 256);
  }
  const cplx z2 = csqr(z1), z4 = csqr(z2), z8 = csqr(z4);
  const HSeed h8 = hseed(z8);
  const cplx d = cmul(c, z256), e = cmul(d, z256);
  {
    const cplx z512 = csqr(z256), f = cmul(e, z512), f8 = cmul(f, z8), f16 = cmul(f, z16), e4 = cmul(e, z4);
    HTile t, u;
    tile_set(t, 0, e4, cmul(e, z8)); tile_set(t, 1, cmul(e4, z8), cmul(e, z16));
    tile_upper(t, hseed(z256));
    tile_set(u, 0, f8, f16); tile_set(u, 1, cmul(f8, z256), cmul(f16, z256));
    tile_upper(u, hseed(z512));
    __syncwarp();
    tile_put(t, tab); tile_put(u, tab + 1024);
    __syncwarp();
    b0 = tile_get(tab); b1 = tile_get(tab + 1024);
  }
  {
    const cplx d2 = cmul(d, z2), d4 = cmul(d, z4);
    HTile t;
    tile_set(t, 0, d2, d4); tile_set(t, 1, cmul(d2, z4), cmul(d, z8));
    tile_upper(t, h8);
    __syncwarp();
    tile_put(t, tab);
    __syncwarp();
    tile_mma2(T[3], T[4], a0, a1, b0, b1);
    b0 = tile_get(tab);
  }
  {
    const cplx c1 = cmul(c, z1), c2 = cmul(c, z2), c3 = cmul(c1, z2), c4 = cmul(c, z4);
    HTile t;
    tile_set(t, 0, c1, c2); tile_set(t, 1, c3, c4); tile_set(t, 2, cmul(c1, z4), cmul(c2, z4)); tile_set(t, 3, cmul(c3, z4), cmul(c4, z4));
    const HTile u = tile_shift(t, h8);
    __syncwarp();
    tile_put(t, tab); tile_put(u, tab + 1024);
    __syncwarp();
    tile_mma(T[2], a0, a1, b0);
    b0 = tile_get(tab); b1 = tile_get(tab + 1024);
    tile_mma2(T[0], T[1], a0, a1, b0, b1);
  }
}
struct ModeIn { uint2 ar, ai, br, bi, cr, ci; };
__device__ __forceinline__ ModeIn load_modes(const Params& p, int idx) {
  return {*(const uint2*)(p.a_re + idx), *(const uint2*)(p.a_im + idx), *(const uint2*)(p.b_re + idx),
          *(const uint2*)(p.b_im + idx), *(const uint2*)(p.c_re + idx), *(const uint2*)(p.c_im + idx)};
}
__device__ __forceinline__ float bf_el(uint2 v, int k) { const uint32_t x = (k & 2) ? v.y : v.x; return (k & 1) ? bf_hi(x) : bf_lo(x); }
struct KGen { float4 cur; float T[5][4]; };
__device__ __forceinline__ uint32_t kgen_slot(uint32_t sb, int ht, int u) {
  return sb + (u < 3 ? SM_KC + (ht >> 5) * (KC_STRIDE * 2) + (u - 1) * 512 + (ht & 31) * 16 + 16 : SM_HALO + 1024 + ht * 16);
}
__device__ __forceinline__ void kgen_setup(KGen& s, uint32_t sb, int cta, int ht, const ModeIn& in, bf16 logdt, bf16 dskip) {
  const float dt = __bfloat162float(__float2bfloat16_rn(expf(__bfloat162float(logdt))));
  float mx = 0.f, k0 = 0.f, ar2[4];
  cplx c[4];
#pragma unroll
  for (int k = 0; k < 4; k++) {
    ar2[k] = (dt * bf_el(in.ar, k)) * 1.4426950408889634f;
    c[k] = cmul({bf_el(in.cr, k), bf_el(in.ci, k)}, {dt * bf_el(in.br, k), dt * bf_el(in.bi, k)});
    k0 += c[k].r;
    mx = fmaxf(mx, fmaxf(fabsf(c[k].r), fabsf(c[k].i)) * ex2(fmaxf(ar2[k] * 2048.f, 0.f)));
  }
  const int ex = min(max(267 - (int)(__reduce_max_sync(~0u, __float_as_uint(mx)) >> 23), 1), 253);
  const float sc = __uint_as_float(ex << 23);
#pragma unroll
  for (int o = 16; o > 0; o >>= 1) k0 += __shfl_xor_sync(~0u, k0, o);
  if ((ht & 31) == 0) {
    const uint32_t kc = sb + SM_KC + (ht >> 5) * (KC_STRIDE * 2);
    sts16(kc, __bfloat16_as_ushort(__float2bfloat16_rn(k0 + __bfloat162float(dskip))));
    sts16(kc + 641 * 2, 0);
    sts32f(kc + 644 * 2, __uint_as_float((254 - ex) << 23));
  }
  s.cur = make_float4(ar2[0], dt * bf_el(in.ai, 0), c[0].r * sc, c[0].i * sc);
#pragma unroll
  for (int k = 1; k < 4; k++) sts128f(kgen_slot(sb, ht, k), ar2[k], dt * bf_el(in.ai, k), c[k].r * sc, c[k].i * sc);
#pragma unroll
  for (int i = 0; i < 5; i++) s.T[i][0] = s.T[i][1] = s.T[i][2] = s.T[i][3] = 0.f;
}
__device__ __forceinline__ void kgen_finish(KGen& s, uint32_t sb, int cta, int ht) {
  const int w = ht >> 5, lane = ht & 31, g = lane >> 2, t = lane & 3;
  const uint32_t kc = sb + SM_KC + w * KC_STRIDE * 2;
  __syncwarp();
  const float inv = __uint_as_float(lds32(kc + 644 * 2));
  auto put = [&](int idx, float v) {
    sts16(kc + idx * 2, __bfloat16_as_ushort(__float2bfloat16_rn(v)));
  };
#pragma unroll
  for (int hi = 0; hi < 2; hi++)
#pragma unroll
    for (int lo = 0; lo < 2; lo++) {
      const int i = g + 8 * hi, j = 2 * t + lo, e = 2 * hi + lo;
      put(16 * i + 1 + j, s.T[0][e] * inv);
      put(16 * i + 9 + j, s.T[1][e] * inv);
      put(257 + 8 * i + j, s.T[2][e] * inv);
      put(385 + 4 * i + (j & 3) + 64 * (j >> 2), s.T[3][e] * inv);
      put(513 + 2 * i + lo + 32 * t, s.T[4][e] * inv);
    }
}

__device__ __forceinline__ void expand_taps(uint32_t sb, int ht) {
  const int ch = ht >> 5, lane = ht & 31;
  const uint32_t kc = sb + SM_KC + ch * KC_STRIDE * 2;
  const uint32_t dst0 = sb + cv_pe(ch);
  auto put = [&](int G, uint32_t u0, uint32_t u1, uint32_t v0, uint32_t v1, uint32_t v2, uint32_t v3, uint32_t v4, uint32_t v5, uint32_t v6, uint32_t v7) {
    const uint32_t dst = dst0 + G * 32;
    sts128(dst, make_uint4(v0 | (u0 << 16), v1 | (u1 << 16), v2 | (v0 << 16), v3 | (v1 << 16)));
    sts128(dst + 16, make_uint4(v4 | (v2 << 16), v5 | (v3 << 16), v6 | (v4 << 16), v7 | (v5 << 16)));
  };
  {
    const uint4 q = lds128(kc + lane * 16);
    const uint32_t pv = lane ? lds32(kc + lane * 16 - 4) : 0u;
    const uint32_t dst = dst0 + (lane + 2) * 32;
    sts128(dst, make_uint4(__byte_perm(q.x, pv, 0x5410), __byte_perm(q.x, pv, 0x7632), __byte_perm(q.y, q.x, 0x5410), __byte_perm(q.y, q.x, 0x7632)));
    sts128(dst + 16, make_uint4(__byte_perm(q.z, q.y, 0x5410), __byte_perm(q.z, q.y, 0x7632), __byte_perm(q.w, q.z, 0x5410), __byte_perm(q.w, q.z, 0x7632)));
    if (lane < 4) sts128(dst0 + lane * 16, make_uint4(0, 0, 0, 0));
  }
  uint32_t a[5], b[2][3], fv[4];
  {
    const uint32_t s1 = kc + 2 * (256 + 4 * lane);
#pragma unroll
    for (int k = 0; k < 5; k++) a[k] = lds16(s1 + 2 * k);
#pragma unroll
    for (int u = 0; u < 2; u++) {
      const uint32_t s2 = kc + 2 * (384 + 2 * (lane + 32 * u));
#pragma unroll
      for (int k = 0; k < 3; k++) b[u][k] = lds16(s2 + 2 * k);
    }
#pragma unroll
    for (int k = 0; k < 4; k++) fv[k] = lds16(kc + 2 * (640 - 4 * lane - k));
  }
  const uint32_t am1 = lds16(kc + 2 * (lane ? 256 + 4 * lane : 255)), am2 = lds16(kc + 2 * (lane ? 255 + 4 * lane : 254));
  const uint32_t bm2 = lds16(kc + 2 * (lane ? 384 + 2 * lane : 383)), k1024 = lds16(kc + 2 * 512);
  put(34 + lane, am2, am1, a[0], a[0], a[1], a[2], a[2], a[2], a[3], a[4]);
#pragma unroll
  for (int u = 0; u < 2; u++) put(66 + lane + 32 * u, u ? b[u][0] : bm2, b[u][0], b[u][0], b[u][0], b[u][0], b[u][1], b[u][1], b[u][1], b[u][2], b[u][2]);
  if (lane < 10) {
    const uint32_t v = lane == 0 ? k1024 : 0u;
    put(130 + lane, v, v, v, v, v, v, v, 0u, 0u, 0u);
  }
  const uint32_t ft = sb + cv_ft(ch) + 4 * lane;
#pragma unroll
  for (int ty = 0; ty < 2; ty++) {
    const uint32_t v = fv[ty] | (fv[ty + 2] << 16);
    sts32f(ft + ty * 512, __uint_as_float(v));
    sts32f(ft + ty * 512 + 128, 0.f);
    sts32f(ft + ty * 512 + 256 + (lane < 2 ? 120 : -8), __uint_as_float(lane < 2 ? 0u : v));
    sts32f(ft + ty * 512 + 384, 0.f);
  }
}

__device__ __forceinline__ int role_id() { int v; asm volatile("mov.u32 %0, %%ctaid.x;" : "=r"(v)); return v; }
#define GMAP 8
__device__ __forceinline__ int role_rb(int cta) { return 4 * (cta >> 5) + (cta & 3); }
__device__ __forceinline__ int role_hg(int cta) { return 2 * (((cta >> 3) & 3) ^ (((cta >> 5) & 1) * 3)) + ((cta >> 2) & 1); }
__device__ __forceinline__ int role_rb2(int cta) { return cta >> 3; }
__device__ __forceinline__ int role_q2(int cta) { return cta & 7; }

__global__ void __launch_bounds__(NTHREADS, 1) fused_kernel(const __grid_constant__ Params p) {
  extern __shared__ __align__(1024) uint8_t smem[];
  const uint32_t sb = s32(smem);
  const int tid = threadIdx.x, lane = tid & 31;
  const int warp = __shfl_sync(~0u, tid >> 5, 0);
  const uint32_t bar = sb + SM_BAR;
  if (tid == 0) TS(0);
  const int cta0 = role_id();
  if (warp == 0 && elect_one()) {
    const int rb = role_rb(cta0), hg = role_hg(cta0);
#pragma unroll
    for (int c = 0; c < 2; c++) { mbar_init(bar + 8 * (B_XF + c), 1); mbar_init(bar + 8 * (B_KVF + c), 1); }
    fence_async_smem();
#pragma unroll
    for (int c = 0; c < 2; c++) {
      mbar_expect(bar + 8 * (B_XF + c), 16384);
      tma_ld(sb + SM_X + c * 16384, &p.mapX128, (rb >> 3) * DM + c * 64, (rb & 7) * 128, bar + 8 * (B_XF + c));
      mbar_expect(bar + 8 * (B_KVF + c), 24576);
      tma_ld3(sb + SM_W + c * 24576, &p.mapW3, hg * 64, c * 64, 0, bar + 8 * (B_KVF + c));
    }
  }
  if (warp == 1 && elect_one()) {
    const int rb = role_rb(cta0), hg = role_hg(cta0);
#pragma unroll
    for (int c = 2; c < 8; c++) mbar_init(bar + 8 * (B_XF + c), 1);
    mbar_init(bar + 8 * (B_KVF + 2), 1); mbar_init(bar + 8 * B_CW, 1);
    fence_async_smem();
    delay<D_START>();
    mbar_expect(bar + 8 * B_CW, 12288);
    tma_ld3(sb + SM_CW, &p.mapW3h, hg * 64, rb * 32, 0, bar + 8 * B_CW);
#pragma unroll
    for (int c = 2; c < 8; c++) {
      mbar_expect(bar + 8 * (B_XF + c), 16384);
      tma_ld(sb + SM_X + c * 16384, &p.mapX128, (rb >> 3) * DM + c * 64, (rb & 7) * 128, bar + 8 * (B_XF + c));
      if (c < 3) {
        mbar_expect(bar + 8 * (B_KVF + c), 24576);
        tma_ld3(sb + SM_W + c * 24576, &p.mapW3, hg * 64, c * 64, 0, bar + 8 * (B_KVF + c));
      }
    }
    TS(56);
  }
  if ((warp & 2) != 0 && warp < 15 && elect_one()) {
    const int grp = 1 + (warp & 1) + 2 * (warp >> 2), cnt = grp < 4 ? 1 : grp < 5 ? 2 : grp < 7 ? 4 : 8;
#pragma unroll
    for (int k = 0; k < 10; k++)
      if (k != 0 || grp > 3 || grp == 2) mbar_init(bar + 8 * (10 * grp + k), cnt);
    fence_async_smem();
  }

  if (warp < 8) {
    if (tid == 0) TS(1);
    asm volatile("setmaxnreg.inc.sync.aligned.u32 %0;" ::"n"(R_CONS));
    const int cta = role_id();
    auto warp_id = [] { return __shfl_sync(~0u, opaque_tid() >> 5, 0); };
    if (tid == 0) TS(54);
#pragma unroll 1
    for (int layer = 0; layer < 2; layer++) {
      { const int cw = warp_id(); attn_phase(p, sb, layer, role_rb(cta), role_hg(cta), cw >> 2, cw & 3); }
      if (STOP == 1 + 3 * layer) return;
      { const int cw = warp_id(); proj_phase(p, sb, layer, role_rb2(cta), role_q2(cta), cw >> 2, cw & 3); }
      if (STOP == 2 + 3 * layer) return;
      conv_phase(p, sb, layer, cta);
      if (STOP == 3 + 3 * layer) return;
    }
    { const int cw = warp_id(); final_phase(p, sb, cta, cw >> 2, cw & 3); }
  } else if (warp < 12) {
    asm volatile("setmaxnreg.dec.sync.aligned.u32 %0;" ::"n"(R_HELP));
    const int ht = tid - 256;
    const int cta = role_id(), rb = role_rb(cta), hg = role_hg(cta);
    unsigned ep0 = 0;
    if (ht == 0) ep0 = ld_relaxed(&g_cnt[C_CS * 32]);
    bar_sync(0, NTHREADS);
    if (ht == 0) {
      asm volatile("st.shared.v2.u32 [%0], {%1, 0};" ::"r"(sb + SM_EP), "r"(ep0 / NCTA) : "memory");
      mbar_arrive(bar + 8 * B_EP);
    }
    mbar_wait(bar + 8 * B_EP, 0);
    stats_publish(sb, 0, rb, hg, opaque_tid() - 256, part_tag(lds32(sb + SM_EP), 0));
    if (ht < 48) {
      const bf16* q = (&p.a_re)[ht >> 3];
      asm volatile("prefetch.global.L2 [%0];" ::"l"(q + cv_chan(cta, (ht >> 1) & 3) * 128 + (ht & 1) * 64));
    }
    {
      KGen kg;
      const uint32_t tab0 = sb + ((ht >> 5) < 2 ? SM_T : SM_T2 - 4096) + (ht >> 5) * 2048;
      const uint32_t tab = tab0 + (ht & 31) * 16, taba = tab0 + ((ht >> 3) & 1) * 1024 + (((ht >> 1) & 8) + (ht & 7)) * 16;
      delay<D_ST0>();
      stats_gather(sb, rb, opaque_tid() - 256, part_tag(lds32(sb + SM_EP), 0));
      if (ht == 0) TS(40);
      const int chn = cv_chan(cta, ht >> 5);
      const ModeIn modes = load_modes(p, chn * 128 + (ht & 31) * 4);
      const bf16 logdt = p.log_dt[chn], dskip = p.dskip[chn];
      if (!HALO_W14 && KG_START != 4) halo_receive(sb, 0, rb, hg, opaque_tid() - 256);
      if (KG_START == 1) mbar_wait(bar + 8 * B_HF, 0);
      kgen_setup(kg, sb, cta, ht, modes, logdt, dskip);
      if (!HALO_W14 && KG_START == 4) halo_receive(sb, 0, rb, hg, opaque_tid() - 256);
      if (KG_START == 2) mbar_wait(bar + 8 * B_HF, 0);
      if (KG_START == 3) mbar_wait(bar + 8 * B_QDONE, 0);
#pragma unroll 1
      for (int u = 0; u < 4; u++) {
        if (u == KG_PRE) {
          KTS(39);
          mbar_wait(bar + 8 * B_AD, 0);
          KTS(41);
        }
        kgen_unit(tab, taba, kg.cur.x, kg.cur.y, {kg.cur.z, kg.cur.w}, kg.T);
        kg.cur = lds128f(kgen_slot(sb, opaque_tid() - 256, u + 1));
      }
      kgen_finish(kg, sb, cta, opaque_tid() - 256);
    }
    KTS(51);
    bar_sync(4, 128);
#pragma unroll 1
    for (int layer = 0; layer < 2; layer++) {
      if (STOP <= 1 + 3 * layer) return;
      mbar_wait(bar + 8 * (EXP_LATE ? B_PS : B_PDONE), layer);
      expand_taps(sb, opaque_tid() - 256);
      conv_zero(sb, opaque_tid() - 256);
      if (ht == 0) TS(52 + layer);
      warp_release(bar + 8 * B_PE);
      if (STOP <= 2 + 3 * layer) return;
      {
        uint4 xr[4], st[4];
        const int c = opaque_tid() - 256;
        const SumAddr sa = conv_sum_addr(sb, c);
        conv_prep_load(sb, layer, cta, c, xr, st);
        conv_prep<true>(sb, layer, cta, c, xr, st, sa);
        if (layer == 1 && ht == 0) TS(62);
        const bf16* xup = g_xT + (size_t)(2 * layer * DM + cta) * LSEQ + (c + 128) * 8;
        const int ahead = layer ? S_AHEAD1 : S_AHEAD0;
        mbar_wait(bar + 8 * (B_U + 3), layer);
        if (ahead == 2) {
          conv_sums(sa, 1, c);
          fence_async_smem();
          bar_arrive(8, 256);
        }
        st[0] = ldcg128(xup);
#pragma unroll
        for (int lc = 0; lc < 4; lc++) {
          if (lc < 3 && lc + ahead < 4) {
            conv_sums(sa, lc + ahead, c);
            fence_async_smem();
            bar_arrive(7 + lc + ahead, 256);
            sched_fence<4>();
          }
          if (lc < 3) st[lc + 1] = ldcg128(xup + (lc + 1) * 128 * LSEQ);
          conv_epi(sb, layer, cta, lc, c, xr[lc], st[lc]);
          warp_release(bar + 8 * (B_E + lc));
          sched_fence<5>();
          if (layer == 1 && lc == 3 && ht == 0) TS(38);
        }
      }
      if (layer == 0 && STOP > 3) {
        const int c1 = role_id();
        stats_publish(sb, 1, role_rb(c1), role_hg(c1), opaque_tid() - 256, part_tag(lds32(sb + SM_EP), 2));
        delay<D_ST>();
        stats_gather(sb, role_rb(c1), opaque_tid() - 256, part_tag(lds32(sb + SM_EP), 2));
        if (ht == 0) TS(25);
        if (!HALO_W14) halo_receive(sb, 1, role_rb(c1), role_hg(c1), opaque_tid() - 256);
      }
    }
  } else {
    asm volatile("setmaxnreg.dec.sync.aligned.u32 %0;" ::"n"(512 - 2 * R_CONS - R_HELP));
    const int cta = role_id(), rb = role_rb(cta), hg = role_hg(cta), rb2 = role_rb2(cta), q2 = role_q2(cta);
    bar_sync(0, NTHREADS);
    if (warp != 12) {
      mbar_wait(bar + 8 * B_EP, 0);
      const uint32_t tag = lds32(sb + SM_EP) % 7 + 1;
      mbar_wait(bar + 8 * B_CW, 0);
      colsum_publish(sb, rb, hg, tid - 416, tag);
      if (tid == 416) TS(50);
      delay<D_CS>();
      colsum_gather(sb, hg, tid - 416, tag);
      __syncwarp();
      if (tid == 416) TS(55);
    }
    if (elect_one()) mbar_arrive(bar + 8 * B_CSF);
    if (warp == 12) {
      if (elect_one()) {
        unsigned epoch = 0;
#pragma unroll 1
        for (int layer = 0; layer < 2; layer++) {
          auto ld_w = [&](int c, int slot) {
            const uint32_t b = bar + 8 * (B_KVF + c);
            mbar_expect(b, 24576);
            tma_ld3(sb + SM_W + slot * 24576, &p.mapW3, hg * 64, c * 64, 0, b);
          };
          if (layer == 0) {
            mbar_wait(bar + 8 * (B_KVF + 2), 0);
            if (rb2 < 4) tma_prefetch2(&p.mapWo128, q2 * 64, rb2 * 128);
            asm volatile("prefetch.tensormap [%0];" ::"l"(&p.mapO) : "memory");
            asm volatile("prefetch.tensormap [%0];" ::"l"(&p.mapO128) : "memory");
            asm volatile("prefetch.tensormap [%0];" ::"l"(&p.mapXT) : "memory");
            asm volatile("prefetch.tensormap [%0];" ::"l"(&p.mapXT3) : "memory");
            mbar_wait(bar + 8 * B_EP, 0);
            epoch = lds32(sb + SM_EP);
          } else {
            mbar_wait(bar + 8 * (B_U + 3), 0);
            ld_w(0, 0); ld_w(1, 1); ld_w(2, 2);
          }
          {
            int slot = 0;
#pragma unroll 1
            for (int c = 3; c < 8; c++) {
              mbar_wait(bar + 8 * (B_KVE + c - 3), layer);
              ld_w(c, slot);
              slot = slot == 2 ? 0 : slot + 1;
            }
          }
          if (STOP <= 1 + 3 * layer) return;
          auto ld_wo = [&] {
            fence_async_smem();
            mbar_expect(bar + 8 * B_WOF, 65536);
#pragma unroll
            for (int c = 0; c < 4; c++) tma_ld(sb + SM_WO + c * 16384, &p.mapWo128, q2 * 64, c * 128, bar + 8 * B_WOF);
          };
          const bool early = (WO_EARLY >> layer) & 1;
          if (early) { mbar_wait(bar + 8 * B_STF, layer); ld_wo(); }
          mbar_wait(bar + 8 * B_QDONE, layer);
          mbar_wait(bar + 8 * RES_AT, layer);
          if (!early) ld_wo();
          {
            const uint32_t b = bar + 8 * B_RF;
            mbar_expect(b, 16384);
            if (layer == 0) tma_ld(sb + SM_R, &p.mapX128, (rb2 >> 3) * DM + q2 * 64, (rb2 & 7) * 128, b);
            else tma_ld3(sb + SM_R, &p.mapXT3, 0, DM + q2 * 64, rb2 * 2, b);
          }
#pragma unroll
          for (int c = 0; c < 8; c++) mbar_expect(bar + 8 * (B_OF + c), 16384);
          spin_until(&g_cnt[(C_O + rb2) * 32], (2 * epoch + layer + 1) * 16);
          fence_async_global();
#pragma unroll
          for (int c = 0; c < 8; c++) {
            if (c == 6) { mbar_wait(bar + 8 * B_OST, layer); fence_async_smem(); }
            tma_ld(sb + sm_o(c), &p.mapO128, c * 64, rb2 * 128, bar + 8 * (B_OF + c));
          }
          if (STOP <= 3 + 3 * layer) return;
        }
      }
    } else if (warp == 13) {
      if (elect_one() && STOP > 1) {
        const unsigned target = (lds32(sb + SM_EP) + 1) * NCTA;
        mbar_wait(bar + 8 * B_RE, 0);
        spin_until(&g_cnt[C_CS * 32 + 2], 2 * target);
        mbar_arrive(bar + 8 * B_XV);
        if (STOP <= 3) return;
        auto ld_x = [&](int c) { tma_ld3(sb + SM_X + c * 16384, &p.mapXT3, 0, DM + c * 64, rb * 2, bar + 8 * (B_XF + c)); };
#pragma unroll
        for (int c = 0; c < 8; c++) mbar_expect(bar + 8 * (B_XF + c), 16384);
        spin_until(&g_cnt[C_G1 * 32], target);
        fence_async_global();
        fence_async_smem();
        ld_x(0); ld_x(1);
        int done = 1, it = 0;
        while (done < 4) {
          const uint4 v = ld_tagged((const uint4*)&g_cnt[C_G1 * 32]);
          const int n = 4 + ((int)(v.y - target) >> 31) + ((int)(v.z - target) >> 31) + ((int)(v.w - target) >> 31);
          if (n == done) { if (++it > (1 << 23)) __trap(); continue; }
          if (n == 4) TS(44);
          fence_async_global();
          fence_async_smem();
          if (done == 1) { ld_x(2); ld_x(3); }
          const int h = hg >> 2;
          if (done < 3 && n >= 3) ld_x(4 + h);
          if (n == 4) ld_x(6 + h);
          if (done < 3 && n >= 3) ld_x(5 - h);
          if (n == 4) ld_x(7 - h);
          done = n;
        }
        if (STOP <= 4) return;
        mbar_wait(bar + 8 * B_RE, 1);
        spin_until(&g_cnt[C_CS * 32 + 3], 2 * target);
        mbar_arrive(bar + 8 * B_XV);
      }
    } else if (warp == 15) {
      mbar_wait(bar + 8 * B_EP, 0);
      const unsigned epoch = lds32(sb + SM_EP);
#pragma unroll 1
      for (int layer = 0; layer < 2; layer++) {
        mbar_wait(bar + 8 * (B_KVF + FILL_AT), layer);
#pragma unroll
        for (int k = 0; k < 8; k++) ((uint4*)(g_xT + (size_t)(2 * layer * DM + cta) * LSEQ))[32 * k + lane] = make_uint4(~0u, ~0u, ~0u, ~0u);
        mbar_wait(bar + 8 * (B_KVF + FILL_AT + 1), layer);
#pragma unroll
        for (int k = 0; k < 16; k++)
          ((uint4*)(g_xT + (size_t)(3 * DM + cv_chan(cta, 3 - (k >> 2))) * LSEQ))[128 * layer + 32 * (k & 3) + lane] = make_uint4(~0u, ~0u, ~0u, ~0u);
        if (lane < 4) ((uint4*)g_stats)[layer * 512 + cta * 4 + lane] = make_uint4(0, 0, 0, 0);
        __syncwarp();
        if (elect_one()) {
          red_release(&g_cnt[C_CS * 32 + layer]);
          spin_until(&g_cnt[C_CS * 32 + layer], (epoch + 1) * NCTA);
          mbar_arrive(bar + 8 * B_ZF);
          if (layer == 0 && STOP > 2) {
#pragma unroll
            for (int lc = 0; lc < 4; lc++) {
              mbar_wait(bar + 8 * (B_E + lc), 0);
              fence_reader();
              bulk_st(g_xT + (size_t)(DM + cv_chan(cta, lc)) * LSEQ, sb + cv_s(lc), 4096);
              bulk_commit();
              bulk_wait_all();
              red_relaxed(&g_cnt[C_G1 * 32 + lc]);
              if (lc == 3) TS(18);
            }
          }
        }
        __syncwarp();
        if (STOP <= 3) return;
      }
    } else if (warp == 14) {
      mbar_wait(bar + 8 * B_EP, 0);
      const unsigned epoch = lds32(sb + SM_EP);
#pragma unroll 1
      for (int layer = 0; layer < 2; layer++) {
        if (STOP <= 3 * layer) return;
        if (HALO_W14) halo_receive1(sb, layer, rb, hg, opaque_tid() & 31, 2 * epoch + layer + 1);
        if (STOP <= 1 + 3 * layer) return;
        mbar_wait(bar + 8 * B_ZF, layer);
        proj_stats(sb, layer, rb2, q2, opaque_tid() & 31, part_tag(epoch, 2 * layer + 1));
        if (layer == 1 && lane == 0) TS(5);
        delay<D_PREP>();
        if (lane == 0) mbar_arrive(bar + 8 * B_GB);
      }
    }
  }
}

typedef CUresult (*EncodeFn)(CUtensorMap*, CUtensorMapDataType, cuuint32_t, void*, const cuuint64_t*, const cuuint64_t*,
                             const cuuint32_t*, const cuuint32_t*, CUtensorMapInterleave, CUtensorMapSwizzle,
                             CUtensorMapL2promotion, CUtensorMapFloatOOBfill);

static void make_map(EncodeFn enc, CUtensorMap* m, void* ptr, uint64_t cols, uint64_t rows, uint32_t box_rows) {
  cuuint64_t dims[2] = {cols, rows};
  cuuint64_t strides[1] = {cols * 2};
  cuuint32_t box[2] = {64, box_rows};
  cuuint32_t es[2] = {1, 1};
  enc(m, CU_TENSOR_MAP_DATA_TYPE_BFLOAT16, 2, ptr, dims, strides, box, es, CU_TENSOR_MAP_INTERLEAVE_NONE,
      CU_TENSOR_MAP_SWIZZLE_128B, CU_TENSOR_MAP_L2_PROMOTION_L2_128B, CU_TENSOR_MAP_FLOAT_OOB_FILL_NONE);
}
static void make_map3(EncodeFn enc, CUtensorMap* m, void* ptr, uint64_t d0, uint64_t cols, uint64_t rows, uint64_t blk_stride,
                      uint64_t nblocks, uint32_t nblk, uint32_t box_rows = 64) {
  cuuint64_t dims[3] = {d0, rows, nblocks};
  cuuint64_t strides[2] = {cols * 2, blk_stride * 2};
  cuuint32_t box[3] = {64, box_rows, nblk};
  cuuint32_t es[3] = {1, 1, 1};
  enc(m, CU_TENSOR_MAP_DATA_TYPE_BFLOAT16, 3, ptr, dims, strides, box, es, CU_TENSOR_MAP_INTERLEAVE_NONE,
      CU_TENSOR_MAP_SWIZZLE_128B, CU_TENSOR_MAP_L2_PROMOTION_L2_128B, CU_TENSOR_MAP_FLOAT_OOB_FILL_NONE);
}

extern "C" void kernel_launch(void* const* d_in, const int* in_sizes, int n_in, void* d_out, int out_size) {
  static Params prm;
  static void* cached[13] = {nullptr};
  static bool attr_done = false;
  bool same = attr_done && cached[12] == d_out;
  for (int i = 0; i < 12 && same; i++) same = cached[i] == d_in[i];
  if (!same) {
    void* fn = nullptr;
    cudaDriverEntryPointQueryResult qr;
    cudaGetDriverEntryPoint("cuTensorMapEncodeTiled", &fn, cudaEnableDefault, &qr);
    EncodeFn enc = (EncodeFn)fn;
    void *pO, *pXT;
    cudaGetSymbolAddress(&pO, g_O);
    cudaGetSymbolAddress(&pXT, g_xT);
    make_map(enc, &prm.mapO, pO, DM, LSEQ, O_WARP ? 16 : 64);
    make_map(enc, &prm.mapXT, pXT, LSEQ, 4 * DM, 64);
    prm.out = (bf16*)d_out;
    make_map(enc, &prm.mapX128, d_in[0], 2 * DM, LSEQ / 2, 128);
    make_map(enc, &prm.mapWo128, d_in[2], DM, DM, 128);
    make_map(enc, &prm.mapO128, pO, DM, LSEQ, 128);
    make_map3(enc, &prm.mapW3, d_in[1], DM, 3 * DM, DM, DM, 3, 3);
    make_map3(enc, &prm.mapW3h, d_in[1], DM, 3 * DM, DM, DM, 3, 3, 32);
    make_map3(enc, &prm.mapXT3, pXT, 64, LSEQ, 4 * DM, 64, 32, 2);
    prm.a_re = (const bf16*)d_in[4]; prm.a_im = (const bf16*)d_in[5];
    prm.b_re = (const bf16*)d_in[6]; prm.b_im = (const bf16*)d_in[7];
    prm.c_re = (const bf16*)d_in[8]; prm.c_im = (const bf16*)d_in[9];
    prm.log_dt = (const bf16*)d_in[10]; prm.dskip = (const bf16*)d_in[11];
    cudaFuncSetAttribute(fused_kernel, cudaFuncAttributeMaxDynamicSharedMemorySize, SM_TOTAL);
    for (int i = 0; i < 12; i++) cached[i] = d_in[i];
    cached[12] = d_out;
    attr_done = true;
  }
  prm.stop = 100;
    fused_kernel<<<NCTA, NTHREADS, SM_TOTAL>>>(prm);
}
```

```cpp
#include <cuda_runtime.h>
#include <cuda_bf16.h>
#include <cuda.h>
#include <stdint.h>

typedef __nv_bfloat16 bf16;

constexpr int LSEQ = 2048;
constexpr int DM = 512;
constexpr int NCTA = 128;
constexpr int NTHREADS = 512;
#define RR 0
#define KG_PRE 2
#define WO_E0 4
#define WO_E1 2
#define FILL_AT 6
#define EXP_LATE 1
#define RFENCE 1
#define D_FIN 500
#define D_PREP 600
#define D_PST 0
#define D_HALO 500
#define STAG 2
#define D_ST 500
#define TLAYER 1
#define KG_PD 1
#define SUM_F32 0
#define CS_LATE0 0
#define D_HALO1 0
#define KG_START 0
#define S_AHEAD0 1
#define S_AHEAD1 2
#define PAUSE 2
#define PARK_FIRST 0
#define P_UNROLL_N 1
constexpr int P_UNROLL = P_UNROLL_N;
#define NORM_FMA 0
#define X_ORDER 1
#define CS_STEP 1
#define D_FIN2 400
#define FIN_D0 2
#define QD_AT 1
#define G_WAIT 2
#define HALO_W14 1
#define D_START 200
#define D_CS 400
#define D_ST0 500
#define KG_LAST 0
#define X_JIT 0
#define KG_GATE 2
#define R_CONS 192
#define R_HELP 88

constexpr int SM_X = 0;
constexpr int SM_W = 131072;
constexpr int SM_KVX = SM_X;
constexpr int SM_WO = SM_X + 16384;
constexpr int SM_OST = SM_W + 49152;
__host__ __device__ constexpr int sm_o(int c) { return c < 7 ? SM_X + (5 + c) * 16384 : SM_KVX; }
constexpr int SM_R = 196608;
constexpr int SM_T = 212992;
constexpr int SM_KC = 217088;
constexpr int KC_STRIDE = 648;
constexpr int SM_CS = SM_KC + 4 * KC_STRIDE * 2;
constexpr int SM_CW = SM_R + 8192;
constexpr int SM_EP = SM_CS + 768;
constexpr int SM_BAR = SM_EP + 16;
constexpr int SM_T2 = SM_BAR + 896;
constexpr int SM_HALO = SM_T2 + 4096;
constexpr int SM_ST = SM_HALO + 3072;
constexpr int SM_TOTAL = SM_HALO + 4096;
static_assert(SM_TOTAL <= 232448, "shared memory");

constexpr int CV_UH = 140 * 16;
constexpr int CV_PECH = 1120 * 4;
constexpr int CV_PBW = 2112 * 2;
__host__ __device__ constexpr int cv_s(int lc) { return SM_X + lc * 32768; }
__host__ __device__ constexpr int cv_u(int lc) { return cv_s(lc) + 4096; }
__host__ __device__ constexpr int cv_pe(int lc) { return cv_u(lc) + 2 * CV_UH; }
__host__ __device__ constexpr int cv_pb(int lc) { return cv_pe(lc) + CV_PECH; }
__host__ __device__ constexpr int cv_ft(int lc) { return cv_pb(lc) + 4 * CV_PBW; }
static_assert(cv_ft(0) + 1024 <= 32768, "conv buffers");
__host__ __device__ constexpr int cv_chan(int cta, int lc) { return cta + 128 * lc; }

enum {
  B_XF = 0,
  B_KVF = 8,
  B_OF = 16,
  B_WOF = 24,
  B_T = 31,
  B_RF = 28,
  B_RE = 29,
  B_CW = 30,
  B_GB = 35,
  B_EP = 36,
  B_ZF = 37,
  B_XV = 39,
  B_SD = 38,
  B_KVE = 40,
  B_OST = 46,
  B_QDONE = 47,
  B_PDONE = 48,
  B_S = 50,
  B_E = 54,
  B_P = 58,
  B_PE = 62,
  B_STF = 63,
  B_CSF = 64,
  B_HF = 65,
  B_U = 70,
  B_AD = 75,
  B_PS = 74,
  B_COUNT = 80
};

enum {
  C_CS = 0,
  C_G1 = 2,
  C_O = 4,
  C_COUNT = 20
};

__device__ __align__(128) unsigned g_cnt[C_COUNT * 32];
__device__ __align__(1024) bf16 g_O[LSEQ * DM];
__device__ __align__(1024) bf16 g_xT[4 * DM * LSEQ];
__device__ __align__(1024) uint32_t g_stats[2 * LSEQ];
__device__ __align__(1024) uint4 g_colsum[8 * 16 * 48];
__device__ __align__(1024) uint4 g_halo[16 * 8 * 192];
__device__ __align__(1024) uint2 g_part[16 * 8 * 128];
#define TS(i) do { } while (0)

#define ATS(i, th) do { } while (0)
#define KTS(i) do { if (ht == 0) TS(i); } while (0)
#define FTS(i) do { } while (0)
#define LTS(i) do { } while (0)

#define STOP 100

struct Params {
  CUtensorMap mapO, mapXT, mapX128, mapWo128, mapO128, mapW3, mapW3h, mapXT3;
  const bf16 *a_re, *a_im, *b_re, *b_im, *c_re, *c_im, *log_dt, *dskip;
  bf16* out;
  int stop;
};

__device__ __forceinline__ uint32_t s32(const void* p) { return (uint32_t)__cvta_generic_to_shared(p); }
__device__ __forceinline__ void mbar_init(uint32_t b, int c) { asm volatile("mbarrier.init.shared::cta.b64 [%0], %1;" ::"r"(b), "r"(c) : "memory"); }
__device__ __forceinline__ void mbar_expect(uint32_t b, int bytes) { asm volatile("mbarrier.arrive.expect_tx.shared::cta.b64 _, [%0], %1;" ::"r"(b), "r"(bytes) : "memory"); }
__device__ __forceinline__ void mbar_arrive(uint32_t b) { asm volatile("mbarrier.arrive.shared::cta.b64 _, [%0];" ::"r"(b) : "memory"); }
__device__ __forceinline__ void mbar_arrive_if(uint32_t b, bool c) {
  asm volatile("{\n.reg .pred p;\nsetp.ne.u32 p, %1, 0;\n@p mbarrier.arrive.shared::cta.b64 _, [%0];\n}" ::"r"(b), "r"((uint32_t)c) : "memory");
}
__device__ __forceinline__ void mbar_wait(uint32_t b, int parity) {
  asm volatile("{\n.reg .pred p;\nWAIT_LOOP:\nmbarrier.try_wait.parity.shared::cta.b64 p, [%0], %1;\n@p bra WAIT_DONE;\nbra WAIT_LOOP;\nWAIT_DONE:\n}" ::"r"(b), "r"(parity) : "memory");
}
template <int N> __device__ __forceinline__ void delay() {
  if constexpr (N > 0) {
    uint32_t t0, t;
    asm volatile("mov.u32 %0, %%clock;" : "=r"(t0));
    do { asm volatile("mov.u32 %0, %%clock;" : "=r"(t)); } while (t - t0 < N);
  }
}
#define SF 3
template <int ID> __device__ __forceinline__ void sched_fence() {
  if constexpr ((SF >> ID) & 1)
    asm volatile("{\n.reg .pred p;\n.reg .u32 t;\nsetp.eq.u32 p, %0, 0;\n@p mov.u32 t, %%clock;\n@p st.shared.u32 [%0], t;\n}" ::"r"(gridDim.x) : "memory");
}
__device__ __forceinline__ int opaque_tid() { int v; asm volatile("mov.u32 %0, %%tid.x;" : "=r"(v)); return v; }
__device__ __forceinline__ bool elect_one() {
  uint32_t r;
  asm volatile("{\n.reg .pred p;\nelect.sync _|p, 0xffffffff;\nselp.u32 %0, 1, 0, p;\n}" : "=r"(r));
  return r != 0;
}
__device__ __forceinline__ void tma_ld(uint32_t dst, const CUtensorMap* m, int c0, int c1, uint32_t bar) {
  asm volatile("cp.async.bulk.tensor.2d.shared::cluster.global.mbarrier::complete_tx::bytes [%0], [%1, {%3, %4}], [%2];"
               ::"r"(dst), "l"(m), "r"(bar), "r"(c0), "r"(c1) : "memory");
}
__device__ __forceinline__ void tma_ld3(uint32_t dst, const CUtensorMap* m, int c0, int c1, int c2, uint32_t bar) {
  asm volatile("cp.async.bulk.tensor.3d.shared::cluster.global.mbarrier::complete_tx::bytes [%0], [%1, {%3, %4, %5}], [%2];"
               ::"r"(dst), "l"(m), "r"(bar), "r"(c0), "r"(c1), "r"(c2) : "memory");
}
__device__ __forceinline__ void tma_prefetch2(const CUtensorMap* m, int c0, int c1) {
  asm volatile("cp.async.bulk.prefetch.tensor.2d.L2.global.tile [%0, {%1, %2}];" ::"l"(m), "r"(c0), "r"(c1) : "memory");
}
__device__ __forceinline__ void tma_prefetch3(const CUtensorMap* m, int c0, int c1, int c2) {
  asm volatile("cp.async.bulk.prefetch.tensor.3d.L2.global.tile [%0, {%1, %2, %3}];" ::"l"(m), "r"(c0), "r"(c1), "r"(c2) : "memory");
}
__device__ __forceinline__ void tma_st(const CUtensorMap* m, int c0, int c1, uint32_t src) {
  asm volatile("cp.async.bulk.tensor.2d.global.shared::cta.bulk_group [%0, {%2, %3}], [%1];" ::"l"(m), "r"(src), "r"(c0), "r"(c1) : "memory");
}
__device__ __forceinline__ void bulk_ld(uint32_t dst, const void* src, int bytes, uint32_t bar) {
  asm volatile("cp.async.bulk.shared::cluster.global.mbarrier::complete_tx::bytes [%0], [%1], %2, [%3];" ::"r"(dst), "l"(src), "r"(bytes), "r"(bar) : "memory");
}
__device__ __forceinline__ void bulk_st(void* dst, uint32_t src, int bytes) {
  asm volatile("cp.async.bulk.global.shared::cta.bulk_group [%0], [%1], %2;" ::"l"(dst), "r"(src), "r"(bytes) : "memory");
}
__device__ __forceinline__ void bulk_red_add_f32(void* dst, uint32_t src, int bytes) {
  asm volatile("cp.reduce.async.bulk.global.shared::cta.bulk_group.add.f32 [%0], [%1], %2;" ::"l"(dst), "r"(src), "r"(bytes) : "memory");
}
__device__ __forceinline__ void bulk_commit() { asm volatile("cp.async.bulk.commit_group;" ::: "memory"); }
__device__ __forceinline__ void bulk_wait_all() { asm volatile("cp.async.bulk.wait_group 0;" ::: "memory"); }
__device__ __forceinline__ void fence_async_smem() { asm volatile("fence.proxy.async.shared::cta;" ::: "memory"); }
__device__ __forceinline__ void fence_writer() { if (!RFENCE) fence_async_smem(); }
__device__ __forceinline__ void fence_reader() { if (RFENCE) fence_async_smem(); }
__device__ __forceinline__ void fence_async_global() { asm volatile("fence.proxy.async.global;" ::: "memory"); }
__device__ __forceinline__ void bar_sync(int id, int n) { asm volatile("bar.sync %0, %1;" ::"r"(id), "r"(n) : "memory"); }
__device__ __forceinline__ void bar_arrive(int id, int n) { asm volatile("bar.arrive %0, %1;" ::"r"(id), "r"(n) : "memory"); }
__device__ __forceinline__ void wg_fence() { asm volatile("wgmma.fence.sync.aligned;" ::: "memory"); }
__device__ __forceinline__ void wg_commit() { asm volatile("wgmma.commit_group.sync.aligned;" ::: "memory"); }
template <int N> __device__ __forceinline__ void wg_wait() { asm volatile("wgmma.wait_group.sync.aligned %0;" ::"n"(N) : "memory"); }
__device__ __forceinline__ uint64_t mkdesc(uint32_t addr, uint32_t lbo, uint32_t sbo, int sw) {
  return (uint64_t)((addr & 0x3FFFF) >> 4) | ((uint64_t)(lbo >> 4) << 16) | ((uint64_t)(sbo >> 4) << 32) | ((uint64_t)sw << 62);
}
__device__ __forceinline__ void ldsm4(uint32_t* r, uint32_t a) {
  asm volatile("ldmatrix.sync.aligned.m8n8.x4.shared.b16 {%0,%1,%2,%3}, [%4];" : "=r"(r[0]), "=r"(r[1]), "=r"(r[2]), "=r"(r[3]) : "r"(a) : "memory");
}
__device__ __forceinline__ void ldsm4t(uint32_t* r, uint32_t a) {
  asm volatile("ldmatrix.sync.aligned.m8n8.x4.trans.shared.b16 {%0,%1,%2,%3}, [%4];" : "=r"(r[0]), "=r"(r[1]), "=r"(r[2]), "=r"(r[3]) : "r"(a) : "memory");
}
__device__ __forceinline__ void stsm4(uint32_t a, uint32_t r0, uint32_t r1, uint32_t r2, uint32_t r3) {
  asm volatile("stmatrix.sync.aligned.m8n8.x4.shared.b16 [%0], {%1,%2,%3,%4};" ::"r"(a), "r"(r0), "r"(r1), "r"(r2), "r"(r3) : "memory");
}
__device__ __forceinline__ void stsm4t(uint32_t a, uint32_t r0, uint32_t r1, uint32_t r2, uint32_t r3) {
  asm volatile("stmatrix.sync.aligned.m8n8.x4.trans.shared.b16 [%0], {%1,%2,%3,%4};" ::"r"(a), "r"(r0), "r"(r1), "r"(r2), "r"(r3) : "memory");
}
__device__ __forceinline__ uint32_t movm_t(uint32_t a) { uint32_t r; asm volatile("movmatrix.sync.aligned.m8n8.trans.b16 %0, %1;" : "=r"(r) : "r"(a)); return r; }
__device__ __forceinline__ uint32_t lds32(uint32_t a) { uint32_t v; asm volatile("ld.shared.b32 %0, [%1];" : "=r"(v) : "r"(a) : "memory"); return v; }
__device__ __forceinline__ float2 lds64f(uint32_t a) { float2 v; asm volatile("ld.shared.v2.f32 {%0,%1}, [%2];" : "=f"(v.x), "=f"(v.y) : "r"(a) : "memory"); return v; }
__device__ __forceinline__ float4 lds128f(uint32_t a) { float4 v; asm volatile("ld.shared.v4.f32 {%0,%1,%2,%3}, [%4];" : "=f"(v.x), "=f"(v.y), "=f"(v.z), "=f"(v.w) : "r"(a) : "memory"); return v; }
__device__ __forceinline__ uint4 lds128(uint32_t a) { uint4 v; asm volatile("ld.shared.v4.b32 {%0,%1,%2,%3}, [%4];" : "=r"(v.x), "=r"(v.y), "=r"(v.z), "=r"(v.w) : "r"(a) : "memory"); return v; }
__device__ __forceinline__ void sts128(uint32_t a, uint4 v) { asm volatile("st.shared.v4.b32 [%0], {%1,%2,%3,%4};" ::"r"(a), "r"(v.x), "r"(v.y), "r"(v.z), "r"(v.w) : "memory"); }
__device__ __forceinline__ void sts128f(uint32_t a, float x, float y, float z, float w) { asm volatile("st.shared.v4.f32 [%0], {%1,%2,%3,%4};" ::"r"(a), "f"(x), "f"(y), "f"(z), "f"(w) : "memory"); }
__device__ __forceinline__ void sts32f(uint32_t a, float v) { asm volatile("st.shared.f32 [%0], %1;" ::"r"(a), "f"(v) : "memory"); }
__device__ __forceinline__ void sts16(uint32_t a, uint16_t v) { asm volatile("st.shared.u16 [%0], %1;" ::"r"(a), "h"(v) : "memory"); }
__device__ __forceinline__ uint32_t lds16(uint32_t a) { uint16_t v; asm volatile("ld.shared.u16 %0, [%1];" : "=h"(v) : "r"(a) : "memory"); return v; }
__device__ __forceinline__ uint32_t packbf(float lo, float hi) { uint32_t r; asm("cvt.rn.bf16x2.f32 %0, %1, %2;" : "=r"(r) : "f"(hi), "f"(lo)); return r; }
__device__ __forceinline__ float bf_lo(uint32_t v) { return __uint_as_float(v << 16); }
__device__ __forceinline__ float bf_hi(uint32_t v) { return __uint_as_float(v & 0xffff0000u); }
__device__ __forceinline__ float ex2(float x) { float r; asm("ex2.approx.ftz.f32 %0, %1;" : "=f"(r) : "f"(x)); return r; }
__device__ __forceinline__ float rsqrt_approx(float x) { float r; asm("rsqrt.approx.ftz.f32 %0, %1;" : "=f"(r) : "f"(x)); return r; }
__device__ __forceinline__ float rcp_approx(float x) { float r; asm("rcp.approx.ftz.f32 %0, %1;" : "=f"(r) : "f"(x)); return r; }
__device__ __forceinline__ void mma_bf16(float* d, const uint32_t* a, uint32_t b0, uint32_t b1) {
  asm("mma.sync.aligned.m16n8k16.row.col.f32.bf16.bf16.f32 {%0,%1,%2,%3}, {%4,%5,%6,%7}, {%8,%9}, {%0,%1,%2,%3};"
               : "+f"(d[0]), "+f"(d[1]), "+f"(d[2]), "+f"(d[3]) : "r"(a[0]), "r"(a[1]), "r"(a[2]), "r"(a[3]), "r"(b0), "r"(b1));
}
__device__ __forceinline__ void mma_bf16_k8(float* d, uint32_t a0, uint32_t a1, uint32_t b) {
  asm("mma.sync.aligned.m16n8k8.row.col.f32.bf16.bf16.f32 {%0,%1,%2,%3}, {%4,%5}, {%6}, {%0,%1,%2,%3};"
      : "+f"(d[0]), "+f"(d[1]), "+f"(d[2]), "+f"(d[3]) : "r"(a0), "r"(a1), "r"(b));
}
__device__ __forceinline__ void red_release(unsigned* p) { asm volatile("red.release.gpu.global.add.u32 [%0], 1;" ::"l"(p) : "memory"); }
__device__ __forceinline__ void red_relaxed(unsigned* p) { asm volatile("red.relaxed.gpu.global.add.u32 [%0], 1;" ::"l"(p) : "memory"); }
__device__ __forceinline__ unsigned ld_relaxed(const unsigned* p) { unsigned v; asm volatile("ld.relaxed.gpu.global.u32 %0, [%1];" : "=r"(v) : "l"(p) : "memory"); return v; }
__device__ __forceinline__ void spin_until(const unsigned* p, unsigned target) {
  int it = 0;
  while ((int)(ld_relaxed(p) - target) < 0) {
    if (++it > (1 << 23)) __trap();
  }
}
__device__ __forceinline__ uint4 ldcg128(const void* p) { uint4 v; asm volatile("ld.global.cg.v4.b32 {%0,%1,%2,%3}, [%4];" : "=r"(v.x), "=r"(v.y), "=r"(v.z), "=r"(v.w) : "l"(p) : "memory"); return v; }
__device__ __forceinline__ uint4 ld_tagged(const uint4* p) { uint4 v; asm volatile("ld.relaxed.gpu.global.v4.u32 {%0,%1,%2,%3}, [%4];" : "=r"(v.x), "=r"(v.y), "=r"(v.z), "=r"(v.w) : "l"(p) : "memory"); return v; }
__device__ __forceinline__ uint2 ld_part(const uint2* p) { uint2 v; asm volatile("ld.relaxed.gpu.global.v2.u32 {%0,%1}, [%2];" : "=r"(v.x), "=r"(v.y) : "l"(p) : "memory"); return v; }
__device__ __forceinline__ void st_part(uint2* p, float s, float q, uint32_t tag) {
  asm volatile("st.relaxed.gpu.global.v2.u32 [%0], {%1,%2};" ::"l"(p), "r"(__float_as_uint(s)), "r"((__float_as_uint(q) & ~7u) | tag) : "memory");
}
__device__ __forceinline__ uint32_t part_tag(uint32_t epoch, int k) { return (4 * (epoch % 7) + k) % 7 + 1; }
__device__ __forceinline__ void st_tagged3(uint4* p, uint32_t a, uint32_t b, uint32_t c, uint32_t tag) { asm volatile("st.relaxed.gpu.global.v4.u32 [%0], {%1,%2,%3,%4};" ::"l"(p), "r"(a), "r"(b), "r"(c), "r"(tag) : "memory"); }
__device__ __forceinline__ uint32_t hadd2(uint32_t a, uint32_t b) { uint32_t r; asm("add.rn.bf16x2 %0, %1, %2;" : "=r"(r) : "r"(a), "r"(b)); return r; }
__device__ __forceinline__ uint32_t hfma2(uint32_t a, uint32_t b, uint32_t c) { uint32_t r; asm("fma.rn.bf16x2 %0, %1, %2, %3;" : "=r"(r) : "r"(a), "r"(b), "r"(c)); return r; }
__device__ __forceinline__ uint32_t hmul2(uint32_t a, uint32_t b) { uint32_t r; asm("mul.rn.bf16x2 %0, %1, %2;" : "=r"(r) : "r"(a), "r"(b)); return r; }

template<int N,int TB> __device__ __forceinline__ void wgmma_rs(float* d, const uint32_t* a, uint64_t db, int sd);
template<int N,int TA,int TB> __device__ __forceinline__ void wgmma_ss(float* d, uint64_t da, uint64_t db, int sd);
template<> __device__ __forceinline__ void wgmma_rs<128,0>(float* d, const uint32_t* a, uint64_t db, int sd) {
  asm volatile("{\n.reg .pred p;\nsetp.ne.b32 p, %69, 0;\nwgmma.mma_async.sync.aligned.m64n128k16.f32.bf16.bf16 {%0,%1,%2,%3,%4,%5,%6,%7,%8,%9,%10,%11,%12,%13,%14,%15,%16,%17,%18,%19,%20,%21,%22,%23,%24,%25,%26,%27,%28,%29,%30,%31,%32,%33,%34,%35,%36,%37,%38,%39,%40,%41,%42,%43,%44,%45,%46,%47,%48,%49,%50,%51,%52,%53,%54,%55,%56,%57,%58,%59,%60,%61,%62,%63}, {%64,%65,%66,%67}, %68, p, 1, 1, 0;\n}\n"
   : "+f"(d[0]),"+f"(d[1]),"+f"(d[2]),"+f"(d[3]),"+f"(d[4]),"+f"(d[5]),"+f"(d[6]),"+f"(d[7]),"+f"(d[8]),"+f"(d[9]),"+f"(d[10]),"+f"(d[11]),"+f"(d[12]),"+f"(d[13]),"+f"(d[14]),"+f"(d[15]),"+f"(d[16]),"+f"(d[17]),"+f"(d[18]),"+f"(d[19]),"+f"(d[20]),"+f"(d[21]),"+f"(d[22]),"+f"(d[23]),"+f"(d[24]),"+f"(d[25]),"+f"(d[26]),"+f"(d[27]),"+f"(d[28]),"+f"(d[29]),"+f"(d[30]),"+f"(d[31]),"+f"(d[32]),"+f"(d[33]),"+f"(d[34]),"+f"(d[35]),"+f"(d[36]),"+f"(d[37]),"+f"(d[38]),"+f"(d[39]),"+f"(d[40]),"+f"(d[41]),"+f"(d[42]),"+f"(d[43]),"+f"(d[44]),"+f"(d[45]),"+f"(d[46]),"+f"(d[47]),"+f"(d[48]),"+f"(d[49]),"+f"(d[50]),"+f"(d[51]),"+f"(d[52]),"+f"(d[53]),"+f"(d[54]),"+f"(d[55]),"+f"(d[56]),"+f"(d[57]),"+f"(d[58]),"+f"(d[59]),"+f"(d[60]),"+f"(d[61]),"+f"(d[62]),"+f"(d[63])
   : "r"(a[0]), "r"(a[1]), "r"(a[2]), "r"(a[3]), "l"(db), "r"(sd));
}
template<> __device__ __forceinline__ void wgmma_rs<120,0>(float* d, const uint32_t* a, uint64_t db, int sd) {
  asm volatile("{\n.reg .pred p;\nsetp.ne.b32 p, %65, 0;\nwgmma.mma_async.sync.aligned.m64n120k16.f32.bf16.bf16 {%0,%1,%2,%3,%4,%5,%6,%7,%8,%9,%10,%11,%12,%13,%14,%15,%16,%17,%18,%19,%20,%21,%22,%23,%24,%25,%26,%27,%28,%29,%30,%31,%32,%33,%34,%35,%36,%37,%38,%39,%40,%41,%42,%43,%44,%45,%46,%47,%48,%49,%50,%51,%52,%53,%54,%55,%56,%57,%58,%59}, {%60,%61,%62,%63}, %64, p, 1, 1, 0;\n}\n"
   : "+f"(d[0]),"+f"(d[1]),"+f"(d[2]),"+f"(d[3]),"+f"(d[4]),"+f"(d[5]),"+f"(d[6]),"+f"(d[7]),"+f"(d[8]),"+f"(d[9]),"+f"(d[10]),"+f"(d[11]),"+f"(d[12]),"+f"(d[13]),"+f"(d[14]),"+f"(d[15]),"+f"(d[16]),"+f"(d[17]),"+f"(d[18]),"+f"(d[19]),"+f"(d[20]),"+f"(d[21]),"+f"(d[22]),"+f"(d[23]),"+f"(d[24]),"+f"(d[25]),"+f"(d[26]),"+f"(d[27]),"+f"(d[28]),"+f"(d[29]),"+f"(d[30]),"+f"(d[31]),"+f"(d[32]),"+f"(d[33]),"+f"(d[34]),"+f"(d[35]),"+f"(d[36]),"+f"(d[37]),"+f"(d[38]),"+f"(d[39]),"+f"(d[40]),"+f"(d[41]),"+f"(d[42]),"+f"(d[43]),"+f"(d[44]),"+f"(d[45]),"+f"(d[46]),"+f"(d[47]),"+f"(d[48]),"+f"(d[49]),"+f"(d[50]),"+f"(d[51]),"+f"(d[52]),"+f"(d[53]),"+f"(d[54]),"+f"(d[55]),"+f"(d[56]),"+f"(d[57]),"+f"(d[58]),"+f"(d[59])
   : "r"(a[0]), "r"(a[1]), "r"(a[2]), "r"(a[3]), "l"(db), "r"(sd));
}
template<> __device__ __forceinline__ void wgmma_rs<112,0>(float* d, const uint32_t* a, uint64_t db, int sd) {
  asm volatile("{\n.reg .pred p;\nsetp.ne.b32 p, %61, 0;\nwgmma.mma_async.sync.aligned.m64n112k16.f32.bf16.bf16 {%0,%1,%2,%3,%4,%5,%6,%7,%8,%9,%10,%11,%12,%13,%14,%15,%16,%17,%18,%19,%20,%21,%22,%23,%24,%25,%26,%27,%28,%29,%30,%31,%32,%33,%34,%35,%36,%37,%38,%39,%40,%41,%42,%43,%44,%45,%46,%47,%48,%49,%50,%51,%52,%53,%54,%55}, {%56,%57,%58,%59}, %60, p, 1, 1, 0;\n}\n"
   : "+f"(d[0]),"+f"(d[1]),"+f"(d[2]),"+f"(d[3]),"+f"(d[4]),"+f"(d[5]),"+f"(d[6]),"+f"(d[7]),"+f"(d[8]),"+f"(d[9]),"+f"(d[10]),"+f"(d[11]),"+f"(d[12]),"+f"(d[13]),"+f"(d[14]),"+f"(d[15]),"+f"(d[16]),"+f"(d[17]),"+f"(d[18]),"+f"(d[19]),"+f"(d[20]),"+f"(d[21]),"+f"(d[22]),"+f"(d[23]),"+f"(d[24]),"+f"(d[25]),"+f"(d[26]),"+f"(d[27]),"+f"(d[28]),"+f"(d[29]),"+f"(d[30]),"+f"(d[31]),"+f"(d[32]),"+f"(d[33]),"+f"(d[34]),"+f"(d[35]),"+f"(d[36]),"+f"(d[37]),"+f"(d[38]),"+f"(d[39]),"+f"(d[40]),"+f"(d[41]),"+f"(d[42]),"+f"(d[43]),"+f"(d[44]),"+f"(d[45]),"+f"(d[46]),"+f"(d[47]),"+f"(d[48]),"+f"(d[49]),"+f"(d[50]),"+f"(d[51]),"+f"(d[52]),"+f"(d[53]),"+f"(d[54]),"+f"(d[55])
   : "r"(a[0]), "r"(a[1]), "r"(a[2]), "r"(a[3]), "l"(db), "r"(sd));
}
template<> __device__ __forceinline__ void wgmma_rs<104,0>(float* d, const uint32_t* a, uint64_t db, int sd) {
  asm volatile("{\n.reg .pred p;\nsetp.ne.b32 p, %57, 0;\nwgmma.mma_async.sync.aligned.m64n104k16.f32.bf16.bf16 {%0,%1,%2,%3,%4,%5,%6,%7,%8,%9,%10,%11,%12,%13,%14,%15,%16,%17,%18,%19,%20,%21,%22,%23,%24,%25,%26,%27,%28,%29,%30,%31,%32,%33,%34,%35,%36,%37,%38,%39,%40,%41,%42,%43,%44,%45,%46,%47,%48,%49,%50,%51}, {%52,%53,%54,%55}, %56, p, 1, 1, 0;\n}\n"
   : "+f"(d[0]),"+f"(d[1]),"+f"(d[2]),"+f"(d[3]),"+f"(d[4]),"+f"(d[5]),"+f"(d[6]),"+f"(d[7]),"+f"(d[8]),"+f"(d[9]),"+f"(d[10]),"+f"(d[11]),"+f"(d[12]),"+f"(d[13]),"+f"(d[14]),"+f"(d[15]),"+f"(d[16]),"+f"(d[17]),"+f"(d[18]),"+f"(d[19]),"+f"(d[20]),"+f"(d[21]),"+f"(d[22]),"+f"(d[23]),"+f"(d[24]),"+f"(d[25]),"+f"(d[26]),"+f"(d[27]),"+f"(d[28]),"+f"(d[29]),"+f"(d[30]),"+f"(d[31]),"+f"(d[32]),"+f"(d[33]),"+f"(d[34]),"+f"(d[35]),"+f"(d[36]),"+f"(d[37]),"+f"(d[38]),"+f"(d[39]),"+f"(d[40]),"+f"(d[41]),"+f"(d[42]),"+f"(d[43]),"+f"(d[44]),"+f"(d[45]),"+f"(d[46]),"+f"(d[47]),"+f"(d[48]),"+f"(d[49]),"+f"(d[50]),"+f"(d[51])
   : "r"(a[0]), "r"(a[1]), "r"(a[2]), "r"(a[3]), "l"(db), "r"(sd));
}
template<> __device__ __forceinline__ void wgmma_rs<96,0>(float* d, const uint32_t* a, uint64_t db, int sd) {
  asm volatile("{\n.reg .pred p;\nsetp.ne.b32 p, %53, 0;\nwgmma.mma_async.sync.aligned.m64n96k16.f32.bf16.bf16 {%0,%1,%2,%3,%4,%5,%6,%7,%8,%9,%10,%11,%12,%13,%14,%15,%16,%17,%18,%19,%20,%21,%22,%23,%24,%25,%26,%27,%28,%29,%30,%31,%32,%33,%34,%35,%36,%37,%38,%39,%40,%41,%42,%43,%44,%45,%46,%47}, {%48,%49,%50,%51}, %52, p, 1, 1, 0;\n}\n"
   : "+f"(d[0]),"+f"(d[1]),"+f"(d[2]),"+f"(d[3]),"+f"(d[4]),"+f"(d[5]),"+f"(d[6]),"+f"(d[7]),"+f"(d[8]),"+f"(d[9]),"+f"(d[10]),"+f"(d[11]),"+f"(d[12]),"+f"(d[13]),"+f"(d[14]),"+f"(d[15]),"+f"(d[16]),"+f"(d[17]),"+f"(d[18]),"+f"(d[19]),"+f"(d[20]),"+f"(d[21]),"+f"(d[22]),"+f"(d[23]),"+f"(d[24]),"+f"(d[25]),"+f"(d[26]),"+f"(d[27]),"+f"(d[28]),"+f"(d[29]),"+f"(d[30]),"+f"(d[31]),"+f"(d[32]),"+f"(d[33]),"+f"(d[34]),"+f"(d[35]),"+f"(d[36]),"+f"(d[37]),"+f"(d[38]),"+f"(d[39]),"+f"(d[40]),"+f"(d[41]),"+f"(d[42]),"+f"(d[43]),"+f"(d[44]),"+f"(d[45]),"+f"(d[46]),"+f"(d[47])
   : "r"(a[0]), "r"(a[1]), "r"(a[2]), "r"(a[3]), "l"(db), "r"(sd));
}
template<> __device__ __forceinline__ void wgmma_rs<88,0>(float* d, const uint32_t* a, uint64_t db, int sd) {
  asm volatile("{\n.reg .pred p;\nsetp.ne.b32 p, %49, 0;\nwgmma.mma_async.sync.aligned.m64n88k16.f32.bf16.bf16 {%0,%1,%2,%3,%4,%5,%6,%7,%8,%9,%10,%11,%12,%13,%14,%15,%16,%17,%18,%19,%20,%21,%22,%23,%24,%25,%26,%27,%28,%29,%30,%31,%32,%33,%34,%35,%36,%37,%38,%39,%40,%41,%42,%43}, {%44,%45,%46,%47}, %48, p, 1, 1, 0;\n}\n"
   : "+f"(d[0]),"+f"(d[1]),"+f"(d[2]),"+f"(d[3]),"+f"(d[4]),"+f"(d[5]),"+f"(d[6]),"+f"(d[7]),"+f"(d[8]),"+f"(d[9]),"+f"(d[10]),"+f"(d[11]),"+f"(d[12]),"+f"(d[13]),"+f"(d[14]),"+f"(d[15]),"+f"(d[16]),"+f"(d[17]),"+f"(d[18]),"+f"(d[19]),"+f"(d[20]),"+f"(d[21]),"+f"(d[22]),"+f"(d[23]),"+f"(d[24]),"+f"(d[25]),"+f"(d[26]),"+f"(d[27]),"+f"(d[28]),"+f"(d[29]),"+f"(d[30]),"+f"(d[31]),"+f"(d[32]),"+f"(d[33]),"+f"(d[34]),"+f"(d[35]),"+f"(d[36]),"+f"(d[37]),"+f"(d[38]),"+f"(d[39]),"+f"(d[40]),"+f"(d[41]),"+f"(d[42]),"+f"(d[43])
   : "r"(a[0]), "r"(a[1]), "r"(a[2]), "r"(a[3]), "l"(db), "r"(sd));
}
template<> __device__ __forceinline__ void wgmma_rs<80,0>(float* d, const uint32_t* a, uint64_t db, int sd) {
  asm volatile("{\n.reg .pred p;\nsetp.ne.b32 p, %45, 0;\nwgmma.mma_async.sync.aligned.m64n80k16.f32.bf16.bf16 {%0,%1,%2,%3,%4,%5,%6,%7,%8,%9,%10,%11,%12,%13,%14,%15,%16,%17,%18,%19,%20,%21,%22,%23,%24,%25,%26,%27,%28,%29,%30,%31,%32,%33,%34,%35,%36,%37,%38,%39}, {%40,%41,%42,%43}, %44, p, 1, 1, 0;\n}\n"
   : "+f"(d[0]),"+f"(d[1]),"+f"(d[2]),"+f"(d[3]),"+f"(d[4]),"+f"(d[5]),"+f"(d[6]),"+f"(d[7]),"+f"(d[8]),"+f"(d[9]),"+f"(d[10]),"+f"(d[11]),"+f"(d[12]),"+f"(d[13]),"+f"(d[14]),"+f"(d[15]),"+f"(d[16]),"+f"(d[17]),"+f"(d[18]),"+f"(d[19]),"+f"(d[20]),"+f"(d[21]),"+f"(d[22]),"+f"(d[23]),"+f"(d[24]),"+f"(d[25]),"+f"(d[26]),"+f"(d[27]),"+f"(d[28]),"+f"(d[29]),"+f"(d[30]),"+f"(d[31]),"+f"(d[32]),"+f"(d[33]),"+f"(d[34]),"+f"(d[35]),"+f"(d[36]),"+f"(d[37]),"+f"(d[38]),"+f"(d[39])
   : "r"(a[0]), "r"(a[1]), "r"(a[2]), "r"(a[3]), "l"(db), "r"(sd));
}
template<> __device__ __forceinline__ void wgmma_rs<72,0>(float* d, const uint32_t* a, uint64_t db, int sd) {
  asm volatile("{\n.reg .pred p;\nsetp.ne.b32 p, %41, 0;\nwgmma.mma_async.sync.aligned.m64n72k16.f32.bf16.bf16 {%0,%1,%2,%3,%4,%5,%6,%7,%8,%9,%10,%11,%12,%13,%14,%15,%16,%17,%18,%19,%20,%21,%22,%23,%24,%25,%26,%27,%28,%29,%30,%31,%32,%33,%34,%35}, {%36,%37,%38,%39}, %40, p, 1, 1, 0;\n}\n"
   : "+f"(d[0]),"+f"(d[1]),"+f"(d[2]),"+f"(d[3]),"+f"(d[4]),"+f"(d[5]),"+f"(d[6]),"+f"(d[7]),"+f"(d[8]),"+f"(d[9]),"+f"(d[10]),"+f"(d[11]),"+f"(d[12]),"+f"(d[13]),"+f"(d[14]),"+f"(d[15]),"+f"(d[16]),"+f"(d[17]),"+f"(d[18]),"+f"(d[19]),"+f"(d[20]),"+f"(d[21]),"+f"(d[22]),"+f"(d[23]),"+f"(d[24]),"+f"(d[25]),"+f"(d[26]),"+f"(d[27]),"+f"(d[28]),"+f"(d[29]),"+f"(d[30]),"+f"(d[31]),"+f"(d[32]),"+f"(d[33]),"+f"(d[34]),"+f"(d[35])
   : "r"(a[0]), "r"(a[1]), "r"(a[2]), "r"(a[3]), "l"(db), "r"(sd));
}
template<> __device__ __forceinline__ void wgmma_rs<64,0>(float* d, const uint32_t* a, uint64_t db, int sd) {
  asm volatile("{\n.reg .pred p;\nsetp.ne.b32 p, %37, 0;\nwgmma.mma_async.sync.aligned.m64n64k16.f32.bf16.bf16 {%0,%1,%2,%3,%4,%5,%6,%7,%8,%9,%10,%11,%12,%13,%14,%15,%16,%17,%18,%19,%20,%21,%22,%23,%24,%25,%26,%27,%28,%29,%30,%31}, {%32,%33,%34,%35}, %36, p, 1, 1, 0;\n}\n"
   : "+f"(d[0]),"+f"(d[1]),"+f"(d[2]),"+f"(d[3]),"+f"(d[4]),"+f"(d[5]),"+f"(d[6]),"+f"(d[7]),"+f"(d[8]),"+f"(d[9]),"+f"(d[10]),"+f"(d[11]),"+f"(d[12]),"+f"(d[13]),"+f"(d[14]),"+f"(d[15]),"+f"(d[16]),"+f"(d[17]),"+f"(d[18]),"+f"(d[19]),"+f"(d[20]),"+f"(d[21]),"+f"(d[22]),"+f"(d[23]),"+f"(d[24]),"+f"(d[25]),"+f"(d[26]),"+f"(d[27]),"+f"(d[28]),"+f"(d[29]),"+f"(d[30]),"+f"(d[31])
   : "r"(a[0]), "r"(a[1]), "r"(a[2]), "r"(a[3]), "l"(db), "r"(sd));
}
template<> __device__ __forceinline__ void wgmma_ss<64,0,1>(float* d, uint64_t da, uint64_t db, int sd) {
  asm volatile("{\n.reg .pred p;\nsetp.ne.b32 p, %34, 0;\nwgmma.mma_async.sync.aligned.m64n64k16.f32.bf16.bf16 {%0,%1,%2,%3,%4,%5,%6,%7,%8,%9,%10,%11,%12,%13,%14,%15,%16,%17,%18,%19,%20,%21,%22,%23,%24,%25,%26,%27,%28,%29,%30,%31}, %32, %33, p, 1, 1, 0, 1;\n}\n"
   : "+f"(d[0]),"+f"(d[1]),"+f"(d[2]),"+f"(d[3]),"+f"(d[4]),"+f"(d[5]),"+f"(d[6]),"+f"(d[7]),"+f"(d[8]),"+f"(d[9]),"+f"(d[10]),"+f"(d[11]),"+f"(d[12]),"+f"(d[13]),"+f"(d[14]),"+f"(d[15]),"+f"(d[16]),"+f"(d[17]),"+f"(d[18]),"+f"(d[19]),"+f"(d[20]),"+f"(d[21]),"+f"(d[22]),"+f"(d[23]),"+f"(d[24]),"+f"(d[25]),"+f"(d[26]),"+f"(d[27]),"+f"(d[28]),"+f"(d[29]),"+f"(d[30]),"+f"(d[31])
   : "l"(da), "l"(db), "r"(sd));
}
template<> __device__ __forceinline__ void wgmma_ss<64,1,1>(float* d, uint64_t da, uint64_t db, int sd) {
  asm volatile("{\n.reg .pred p;\nsetp.ne.b32 p, %34, 0;\nwgmma.mma_async.sync.aligned.m64n64k16.f32.bf16.bf16 {%0,%1,%2,%3,%4,%5,%6,%7,%8,%9,%10,%11,%12,%13,%14,%15,%16,%17,%18,%19,%20,%21,%22,%23,%24,%25,%26,%27,%28,%29,%30,%31}, %32, %33, p, 1, 1, 1, 1;\n}\n"
   : "+f"(d[0]),"+f"(d[1]),"+f"(d[2]),"+f"(d[3]),"+f"(d[4]),"+f"(d[5]),"+f"(d[6]),"+f"(d[7]),"+f"(d[8]),"+f"(d[9]),"+f"(d[10]),"+f"(d[11]),"+f"(d[12]),"+f"(d[13]),"+f"(d[14]),"+f"(d[15]),"+f"(d[16]),"+f"(d[17]),"+f"(d[18]),"+f"(d[19]),"+f"(d[20]),"+f"(d[21]),"+f"(d[22]),"+f"(d[23]),"+f"(d[24]),"+f"(d[25]),"+f"(d[26]),"+f"(d[27]),"+f"(d[28]),"+f"(d[29]),"+f"(d[30]),"+f"(d[31])
   : "l"(da), "l"(db), "r"(sd));
}
template<> __device__ __forceinline__ void wgmma_ss<192,0,1>(float* d, uint64_t da, uint64_t db, int sd) {
  asm volatile("{\n.reg .pred p;\nsetp.ne.b32 p, %98, 0;\nwgmma.mma_async.sync.aligned.m64n192k16.f32.bf16.bf16 {%0,%1,%2,%3,%4,%5,%6,%7,%8,%9,%10,%11,%12,%13,%14,%15,%16,%17,%18,%19,%20,%21,%22,%23,%24,%25,%26,%27,%28,%29,%30,%31,%32,%33,%34,%35,%36,%37,%38,%39,%40,%41,%42,%43,%44,%45,%46,%47,%48,%49,%50,%51,%52,%53,%54,%55,%56,%57,%58,%59,%60,%61,%62,%63,%64,%65,%66,%67,%68,%69,%70,%71,%72,%73,%74,%75,%76,%77,%78,%79,%80,%81,%82,%83,%84,%85,%86,%87,%88,%89,%90,%91,%92,%93,%94,%95}, %96, %97, p, 1, 1, 0, 1;\n}\n"
   : "+f"(d[0]),"+f"(d[1]),"+f"(d[2]),"+f"(d[3]),"+f"(d[4]),"+f"(d[5]),"+f"(d[6]),"+f"(d[7]),"+f"(d[8]),"+f"(d[9]),"+f"(d[10]),"+f"(d[11]),"+f"(d[12]),"+f"(d[13]),"+f"(d[14]),"+f"(d[15]),"+f"(d[16]),"+f"(d[17]),"+f"(d[18]),"+f"(d[19]),"+f"(d[20]),"+f"(d[21]),"+f"(d[22]),"+f"(d[23]),"+f"(d[24]),"+f"(d[25]),"+f"(d[26]),"+f"(d[27]),"+f"(d[28]),"+f"(d[29]),"+f"(d[30]),"+f"(d[31]),"+f"(d[32]),"+f"(d[33]),"+f"(d[34]),"+f"(d[35]),"+f"(d[36]),"+f"(d[37]),"+f"(d[38]),"+f"(d[39]),"+f"(d[40]),"+f"(d[41]),"+f"(d[42]),"+f"(d[43]),"+f"(d[44]),"+f"(d[45]),"+f"(d[46]),"+f"(d[47]),"+f"(d[48]),"+f"(d[49]),"+f"(d[50]),"+f"(d[51]),"+f"(d[52]),"+f"(d[53]),"+f"(d[54]),"+f"(d[55]),"+f"(d[56]),"+f"(d[57]),"+f"(d[58]),"+f"(d[59]),"+f"(d[60]),"+f"(d[61]),"+f"(d[62]),"+f"(d[63]),"+f"(d[64]),"+f"(d[65]),"+f"(d[66]),"+f"(d[67]),"+f"(d[68]),"+f"(d[69]),"+f"(d[70]),"+f"(d[71]),"+f"(d[72]),"+f"(d[73]),"+f"(d[74]),"+f"(d[75]),"+f"(d[76]),"+f"(d[77]),"+f"(d[78]),"+f"(d[79]),"+f"(d[80]),"+f"(d[81]),"+f"(d[82]),"+f"(d[83]),"+f"(d[84]),"+f"(d[85]),"+f"(d[86]),"+f"(d[87]),"+f"(d[88]),"+f"(d[89]),"+f"(d[90]),"+f"(d[91]),"+f"(d[92]),"+f"(d[93]),"+f"(d[94]),"+f"(d[95])
   : "l"(da), "l"(db), "r"(sd));
}
template<> __device__ __forceinline__ void wgmma_ss<192,1,1>(float* d, uint64_t da, uint64_t db, int sd) {
  asm volatile("{\n.reg .pred p;\nsetp.ne.b32 p, %98, 0;\nwgmma.mma_async.sync.aligned.m64n192k16.f32.bf16.bf16 {%0,%1,%2,%3,%4,%5,%6,%7,%8,%9,%10,%11,%12,%13,%14,%15,%16,%17,%18,%19,%20,%21,%22,%23,%24,%25,%26,%27,%28,%29,%30,%31,%32,%33,%34,%35,%36,%37,%38,%39,%40,%41,%42,%43,%44,%45,%46,%47,%48,%49,%50,%51,%52,%53,%54,%55,%56,%57,%58,%59,%60,%61,%62,%63,%64,%65,%66,%67,%68,%69,%70,%71,%72,%73,%74,%75,%76,%77,%78,%79,%80,%81,%82,%83,%84,%85,%86,%87,%88,%89,%90,%91,%92,%93,%94,%95}, %96, %97, p, 1, 1, 1, 1;\n}\n"
   : "+f"(d[0]),"+f"(d[1]),"+f"(d[2]),"+f"(d[3]),"+f"(d[4]),"+f"(d[5]),"+f"(d[6]),"+f"(d[7]),"+f"(d[8]),"+f"(d[9]),"+f"(d[10]),"+f"(d[11]),"+f"(d[12]),"+f"(d[13]),"+f"(d[14]),"+f"(d[15]),"+f"(d[16]),"+f"(d[17]),"+f"(d[18]),"+f"(d[19]),"+f"(d[20]),"+f"(d[21]),"+f"(d[22]),"+f"(d[23]),"+f"(d[24]),"+f"(d[25]),"+f"(d[26]),"+f"(d[27]),"+f"(d[28]),"+f"(d[29]),"+f"(d[30]),"+f"(d[31]),"+f"(d[32]),"+f"(d[33]),"+f"(d[34]),"+f"(d[35]),"+f"(d[36]),"+f"(d[37]),"+f"(d[38]),"+f"(d[39]),"+f"(d[40]),"+f"(d[41]),"+f"(d[42]),"+f"(d[43]),"+f"(d[44]),"+f"(d[45]),"+f"(d[46]),"+f"(d[47]),"+f"(d[48]),"+f"(d[49]),"+f"(d[50]),"+f"(d[51]),"+f"(d[52]),"+f"(d[53]),"+f"(d[54]),"+f"(d[55]),"+f"(d[56]),"+f"(d[57]),"+f"(d[58]),"+f"(d[59]),"+f"(d[60]),"+f"(d[61]),"+f"(d[62]),"+f"(d[63]),"+f"(d[64]),"+f"(d[65]),"+f"(d[66]),"+f"(d[67]),"+f"(d[68]),"+f"(d[69]),"+f"(d[70]),"+f"(d[71]),"+f"(d[72]),"+f"(d[73]),"+f"(d[74]),"+f"(d[75]),"+f"(d[76]),"+f"(d[77]),"+f"(d[78]),"+f"(d[79]),"+f"(d[80]),"+f"(d[81]),"+f"(d[82]),"+f"(d[83]),"+f"(d[84]),"+f"(d[85]),"+f"(d[86]),"+f"(d[87]),"+f"(d[88]),"+f"(d[89]),"+f"(d[90]),"+f"(d[91]),"+f"(d[92]),"+f"(d[93]),"+f"(d[94]),"+f"(d[95])
   : "l"(da), "l"(db), "r"(sd));
}

__device__ __forceinline__ void stats_publish(uint32_t sb, int layer, int rb, int hg, int ht, uint32_t tag) {
  const int lane = ht & 31, w = ht >> 5, g = lane >> 2, t = lane & 3, ks = hg & 3;
  uint32_t xa;
  if (layer == 0) {
    const int row = 16 * w + (lane & 15), kc = 2 * ks + (lane >> 4);
    xa = row * 128 + ((kc ^ (row & 7)) << 4);
  } else {
    const int k = 16 * ks + (lane & 7) + 8 * (lane >> 4), pc = 2 * w + ((lane >> 3) & 1);
    xa = k * 128 + ((pc ^ (k & 7)) << 4);
  }
  float s[4] = {0.f, 0.f, 0.f, 0.f}, q[4] = {0.f, 0.f, 0.f, 0.f};
#pragma unroll 1
  for (int c = hg >> 2; c < 8; c += 2) {
    uint32_t A[2][4];
    mbar_wait(sb + SM_BAR + 8 * (B_XF + c), layer);
#pragma unroll
    for (int h = 0; h < 2; h++) {
      if (layer == 0) ldsm4(A[h], sb + SM_X + c * 16384 + h * 8192 + xa);
      else ldsm4t(A[h], sb + SM_X + c * 16384 + h * 8192 + xa);
    }
    if (c >= 6) ATS(48, 256);
    if (c < 2) ATS(51, 256);
#pragma unroll
    for (int r = 0; r < 4; r++)
#pragma unroll
      for (int i = 0; i < 2; i++) {
        const uint32_t v = A[r >> 1][2 * i + (r & 1)];
        const float a = bf_lo(v), b = bf_hi(v);
        s[r] += a + b; q[r] = fmaf(a, a, q[r]); q[r] = fmaf(b, b, q[r]);
      }
  }
#pragma unroll
  for (int r = 0; r < 2; r++) {
    s[r] = ((t & 2) ? s[r + 2] : s[r]) + __shfl_xor_sync(~0u, (t & 2) ? s[r] : s[r + 2], 2);
    q[r] = ((t & 2) ? q[r + 2] : q[r]) + __shfl_xor_sync(~0u, (t & 2) ? q[r] : q[r + 2], 2);
  }
  s[0] = ((t & 1) ? s[1] : s[0]) + __shfl_xor_sync(~0u, (t & 1) ? s[0] : s[1], 1);
  q[0] = ((t & 1) ? q[1] : q[0]) + __shfl_xor_sync(~0u, (t & 1) ? q[0] : q[1], 1);
  st_part(&g_part[(rb * 8 + hg) * 128 + 64 * (t >> 1) + 16 * w + 8 * (t & 1) + g], s[0], q[0], tag);
  ATS(49, 256);
}
__device__ __forceinline__ void stats_gather(uint32_t sb, int rb, int ht, uint32_t tag) {
  const uint2* src = &g_part[rb * 8 * 128 + ht];
  uint2 v[8];
  for (int it = 0;; it++) {
    uint32_t bad = 0;
#pragma unroll
    for (int i = 0; i < 8; i++) v[i] = ld_part(src + i * 128);
#pragma unroll
    for (int i = 0; i < 8; i++) bad |= v[i].y ^ tag;
    if (__all_sync(~0u, (bad & 7u) == 0)) break;
    if (it > (1 << 22)) __trap();
  }
  float s = 0.f, q = 0.f;
#pragma unroll
  for (int i = 0; i < 8; i++) { s += __uint_as_float(v[i].x); q += __uint_as_float(v[i].y); }
  const float mean = s * (1.f / DM);
  const float rstd = rsqrt_approx(fmaxf(q * (1.f / DM) - mean * mean, 0.f) + 1e-5f);
  asm volatile("st.shared.v2.f32 [%0], {%1,%2};" ::"r"(sb + SM_ST + ht * 8), "f"(mean), "f"(rstd) : "memory");
  __syncwarp();
  if (elect_one()) mbar_arrive(sb + SM_BAR + 8 * B_STF);
}
__device__ __forceinline__ void halo_receive(uint32_t sb, int layer, int rb, int hg, int ht) {
  const int lane = ht & 31, h = ht >> 5;
  uint4 kv = make_uint4(0, 0, 0, 0);
  mbar_wait(sb + SM_BAR + 8 * B_SD, layer);
  if (rb & 7) {
    const uint32_t tag = 2 * lds32(sb + SM_EP) + layer + 1;
    const uint4* src = &g_halo[((rb - 1) * 8 + hg) * 192 + h * 48];
    if (layer == 0) delay<D_HALO>(); else delay<D_HALO1>();
    uint4 a;
    uint2 b;
    int it = 0;
    do {
      a = ld_tagged(src + lane); b = ld_part((const uint2*)(src + 32) + lane);
      if (++it > (1 << 22)) __trap();
    } while (!__all_sync(~0u, a.w == tag && b.y == tag));
    kv = make_uint4(a.x, a.y, movm_t(a.z), movm_t(b.x));
  }
  sts128(sb + SM_KVX + h * 512 + lane * 16, kv);
  ATS(61, 256);
  bar_arrive(7, 160);
  if (elect_one()) mbar_arrive(sb + SM_BAR + 8 * B_HF);
}

__device__ __forceinline__ void halo_receive1(uint32_t sb, int layer, int rb, int hg, int lane, uint32_t tag) {
  uint4 a[4];
  uint2 b[4];
  mbar_wait(sb + SM_BAR + 8 * B_SD, layer);
  if (rb & 7) {
    const uint4* src = &g_halo[((rb - 1) * 8 + hg) * 192];
    if (layer == 0) delay<D_HALO>(); else delay<D_HALO1>();
    for (int it = 0;; it++) {
      uint32_t bad = 0;
#pragma unroll
      for (int h = 0; h < 4; h++) { a[h] = ld_tagged(src + h * 48 + lane); b[h] = ld_part((const uint2*)(src + h * 48 + 32) + lane); }
#pragma unroll
      for (int h = 0; h < 4; h++) {
        bad |= (a[h].w ^ tag) | (b[h].y ^ tag);
        a[h].z = movm_t(a[h].z); a[h].w = movm_t(b[h].x);
      }
      if (__all_sync(~0u, bad == 0)) break;
      if (it > (1 << 22)) __trap();
    }
  } else {
#pragma unroll
    for (int h = 0; h < 4; h++) a[h] = make_uint4(0, 0, 0, 0);
  }
#pragma unroll
  for (int h = 0; h < 4; h++) sts128(sb + SM_KVX + h * 512 + lane * 16, a[h]);
  ATS(61, 448);
  bar_arrive(7, 64);
  if (lane < 4) mbar_arrive(sb + SM_BAR + 8 * B_HF);
}

template <bool TR>
__device__ __forceinline__ void gemm_section(float* acc, float2* cs, uint32_t sb, int layer, int wg, int w, int lane) {
  const uint32_t bar = sb + SM_BAR;
  const bool leader = (w == 0) && (lane == 0);
  auto issue = [&](int c, int slot) {
    mbar_wait(bar + 8 * (B_XF + c), layer);
    mbar_wait(bar + 8 * (B_KVF + c), layer);
    const uint64_t da = mkdesc(sb + SM_X + c * 16384 + wg * 8192, TR ? 8192 : 16, 1024, 1);
    const uint64_t db = mkdesc(sb + SM_W + slot * 24576, 8192, 1024, 1);
    wg_fence();
#pragma unroll
    for (int ks = 0; ks < 4; ks++) wgmma_ss<192, TR ? 1 : 0, 1>(acc, da + (TR ? ks * 128 : ks * 2), db + ks * 128, (c | ks) != 0);
    wg_commit();
  };
  auto step = [&](int c, int slot) {
    issue(c, slot);
    wg_wait<1>();
    if (leader) mbar_arrive(bar + 8 * (B_KVE + c - 1));
  };
  if (!TR) bar_sync(0, NTHREADS);
  if (TR && G_WAIT == 3 && wg == 1) bar_sync(14, 256);
  if (TR && G_WAIT == 4 && wg == 1) mbar_wait(bar + 8 * (B_P + 3), 0);
  issue(0, 0);
  if (threadIdx.x == 0) TS(2 + layer * 20 + 0);
  if (threadIdx.x == 128 && layer == 1) TS(60);
  auto ld_cs = [&](int j0) {
#pragma unroll
    for (int j = j0; j < j0 + 8; j++) cs[j] = lds64f(sb + SM_CS + 4 * (8 * j + 2 * (lane & 3)));
  };
  if (TR && CS_STEP == 0) ld_cs(8);
  step(1, 1);
  if (TR && CS_STEP == 0) ld_cs(16);
  if (TR && CS_STEP == 1) ld_cs(8);
  step(2, 2);
  if (TR && CS_STEP == 1) ld_cs(16);
  if (TR && CS_STEP == 2) ld_cs(8);
  step(3, 0);
  if (TR && CS_STEP == 2) ld_cs(16);
  step(4, 1);
  if (TR && CS_STEP == 4) ld_cs(8);
  step(5, 2);
  if (TR && CS_STEP == 4) ld_cs(16);
  if (!TR && !CS_LATE0) { mbar_wait(bar + 8 * B_CSF, 0); ld_cs(8); ld_cs(16); }
  if (wg == 0) bar_sync(5, 256);
  issue(6, 0);
  issue(7, 1);
  if (wg == 1) bar_arrive(5, 256);
  if (!TR && CS_LATE0) { mbar_wait(bar + 8 * B_CSF, 0); ld_cs(8); ld_cs(16); }
}

__device__ __forceinline__ void attn_phase(const Params& p, uint32_t sb, int layer, int rb, int hg, int wg, int w) {
  const int lane = opaque_tid() & 31;
  const int g = lane >> 2, t = lane & 3;
  const uint32_t bar = sb + SM_BAR;
  const int row0 = 64 * wg + 16 * w;
  const bool leader = (w == 0) && (lane == 0);
  float acc[96];
  float2 cs[24];
  if (layer) gemm_section<true>(acc, cs, sb, layer, wg, w, lane);
  else gemm_section<false>(acc, cs, sb, layer, wg, w, lane);
  ATS(41, 224);
  mbar_wait(bar + 8 * B_STF, layer);
  const uint32_t tag = 2 * lds32(sb + SM_EP) + layer + 1;
  const float2 st0 = lds64f(sb + SM_ST + (row0 + g) * 8), st1 = lds64f(sb + SM_ST + (row0 + g + 8) * 8);
  const float mean0 = st0.x, rstd0 = st0.y, mean1 = st1.x, rstd1 = st1.y;
  wg_wait<0>();
  if (threadIdx.x == 0) TS(2 + layer * 20 + 1);
  ATS(39, 224);
  if (leader) mbar_arrive(bar + 8 * B_QDONE);

  uint32_t fp[4][4], fl[4][4], fh[4][4], qa[4][4];
  const int cw = 4 * wg + w;
  {
    const float nm0 = -mean0 * rstd0, nm1 = -mean1 * rstd1;
    const uint32_t kvx = sb + SM_KVX + cw * 2048 + lane * 16;
#pragma unroll
    for (int h = 0; h < 4; h++)
#pragma unroll
      for (int k = 0; k < 4; k++) {
        const int j = 8 + (k >> 1) * 8 + 2 * h + (k & 1);
        fh[h][k] = packbf(fmaf(acc[4 * j + 2], rstd1, nm1 * cs[j].x), fmaf(acc[4 * j + 3], rstd1, nm1 * cs[j].y));
      }
    if (cw == 7) {
      uint4* halo = &g_halo[(rb * 8 + hg) * 192];
#pragma unroll
      for (int h = 0; h < 4; h++) {
        st_tagged3(halo + h * 48 + lane, fh[h][0], fh[h][1], fh[h][2], tag);
        asm volatile("st.relaxed.gpu.global.v2.u32 [%0], {%1,%2};" ::"l"((uint2*)(halo + h * 48 + 32) + lane), "r"(fh[h][3]), "r"(tag) : "memory");
      }
      if (elect_one()) mbar_arrive(bar + 8 * B_SD);
      if (layer == TLAYER && threadIdx.x == 224) TS(47);
    }
#pragma unroll
    for (int h = 0; h < 4; h++) { fh[h][2] = movm_t(fh[h][2]); fh[h][3] = movm_t(fh[h][3]); }
    if (cw != 7) {
#pragma unroll
      for (int h = 0; h < 4; h++) sts128(kvx + 2048 + h * 512, make_uint4(fh[h][0], fh[h][1], fh[h][2], fh[h][3]));
      bar_arrive(8 + cw, 64);
    }
    sched_fence<6>();
    if (layer == TLAYER && threadIdx.x == 0) TS(45);
#pragma unroll
    for (int j = 0; j < 8; j++) cs[j] = lds64f(sb + SM_CS + 4 * (8 * j + 2 * t));
#pragma unroll
    for (int h = 0; h < 4; h++)
#pragma unroll
      for (int k = 0; k < 4; k++) {
        const int j = 8 + (k >> 1) * 8 + 2 * h + (k & 1);
        fl[h][k] = packbf(fmaf(acc[4 * j], rstd0, nm0 * cs[j].x), fmaf(acc[4 * j + 1], rstd0, nm0 * cs[j].y));
        if (k >= 2) fl[h][k] = movm_t(fl[h][k]);
      }
#pragma unroll
    for (int h = 0; h < 4; h++) {
#pragma unroll
      for (int dh = 0; dh < 2; dh++) {
        const int j = 2 * h + dh;
        const float2 c2 = cs[j];
        qa[h][2 * dh] = packbf(fmaf(-mean0, c2.x, acc[4 * j + 0]), fmaf(-mean0, c2.y, acc[4 * j + 1]));
        qa[h][2 * dh + 1] = packbf(fmaf(-mean1, c2.x, acc[4 * j + 2]), fmaf(-mean1, c2.y, acc[4 * j + 3]));
      }
    }
    if (threadIdx.x == 0) TS(2 + layer * 20 + 2);
    if (QD_AT == 1) mbar_wait(bar + 8 * B_QDONE, layer);
    sched_fence<0>();
    bar_sync(7 + cw, cw == 0 && !HALO_W14 ? 160 : 64);
#pragma unroll
    for (int h = 0; h < 4; h++) {
      const uint4 v = lds128(kvx + h * 512);
      fp[h][0] = v.x; fp[h][1] = v.y; fp[h][2] = v.z; fp[h][3] = v.w;
    }
    if (threadIdx.x == 0) TS(2 + layer * 20 + 4);
  }

  const bool u0 = 2 * t > g, u1 = 2 * t + 1 > g;
  const uint32_t mU = (u0 ? 0x0000ffffu : 0u) | (u1 ? 0xffff0000u : 0u);
  const float cl2 = 0.25f * 1.4426950408889634f;
  const float sc0 = rstd0 * cl2, sc1 = rstd1 * cl2;
  const float cneg = ((rb & 7) == 0 && cw == 0) ? -INFINITY : 0.f;
  float v[4][4];
#pragma unroll
  for (int h = 0; h < 4; h++) {
    float T0[4] = {cneg, cneg, cneg, cneg}, T1[4] = {0.f, 0.f, 0.f, 0.f}, T2[4] = {0.f, 0.f, 0.f, 0.f};
    mma_bf16(T1, qa[h], fl[h][0], fl[h][1]);
    mma_bf16(T2, qa[h], fh[h][0], fh[h][1]);
    mma_bf16(T0, qa[h], fp[h][0], fp[h][1]);
    v[h][0] = u0 ? T0[0] : T1[0]; v[h][1] = u1 ? T0[1] : T1[1];
    v[h][2] = u0 ? T1[2] : T2[2]; v[h][3] = u1 ? T1[3] : T2[3];
  }
  float m0[4], m1[4];
#pragma unroll
  for (int h = 0; h < 4; h++) { m0[h] = fmaxf(v[h][0], v[h][1]); m1[h] = fmaxf(v[h][2], v[h][3]); }
#pragma unroll
  for (int o = 1; o <= 2; o <<= 1) {
#pragma unroll
    for (int h = 0; h < 4; h++) {
      m0[h] = fmaxf(m0[h], __shfl_xor_sync(~0u, m0[h], o));
      m1[h] = fmaxf(m1[h], __shfl_xor_sync(~0u, m1[h], o));
    }
  }
  float O0[4][4], O1[4][4], Z[4][4];
#pragma unroll
  for (int h = 0; h < 4; h++) {
    const float mm0 = -m0[h] * sc0, mm1 = -m1[h] * sc1;
    const uint32_t P0 = packbf(ex2(fmaf(v[h][0], sc0, mm0)), ex2(fmaf(v[h][1], sc0, mm0)));
    const uint32_t P1 = packbf(ex2(fmaf(v[h][2], sc1, mm1)), ex2(fmaf(v[h][3], sc1, mm1)));
#pragma unroll
    for (int k = 0; k < 4; k++) O0[h][k] = O1[h][k] = Z[h][k] = 0.f;
    mma_bf16_k8(Z[h], P0, P1, 0x3f803f80u);
    mma_bf16_k8(O0[h], P0 & ~mU, P1 & mU, fl[h][2]); mma_bf16_k8(O1[h], P0 & ~mU, P1 & mU, fl[h][3]);
    mma_bf16_k8(O0[h], P0 & mU, 0u, fp[h][2]); mma_bf16_k8(O1[h], P0 & mU, 0u, fp[h][3]);
    mma_bf16_k8(O0[h], 0u, P1 & ~mU, fh[h][2]); mma_bf16_k8(O1[h], 0u, P1 & ~mU, fh[h][3]);
  }
  const uint32_t ob = sb + SM_OST + wg * 8192;
  if (QD_AT == 0) mbar_wait(bar + 8 * B_QDONE, layer);
  const int o_row = 16 * w + (lane & 7) + 8 * ((lane >> 3) & 1);
#pragma unroll
  for (int h = 0; h < 4; h++) {
    const float i0 = rcp_approx(Z[h][0]), i1 = rcp_approx(Z[h][2]);
    const int ch = 2 * h + (lane >> 4);
    stsm4(ob + o_row * 128 + ((ch ^ (o_row & 7)) << 4), packbf(O0[h][0] * i0, O0[h][1] * i0), packbf(O0[h][2] * i1, O0[h][3] * i1),
          packbf(O1[h][0] * i0, O1[h][1] * i0), packbf(O1[h][2] * i1, O1[h][3] * i1));
  }
  if (threadIdx.x == 0) TS(2 + layer * 20 + 5);
  ATS(57, 128); ATS(20, 96);
  __syncwarp();
  if (elect_one()) {
    fence_async_smem();
    tma_st(&p.mapO, hg * 64, rb * 128 + row0, ob + w * 2048);
    bulk_commit();
    mbar_arrive(bar + 8 * B_AD);
    bulk_wait_all();
    uint32_t old;
    asm volatile("atom.acq_rel.cta.shared.inc.u32 %0, [%1], 7;" : "=r"(old) : "r"(sb + SM_EP + 4) : "memory");
    if (old == 7) {
      asm volatile("red.relaxed.gpu.global.add.u32 [%0], 2;" ::"l"(&g_cnt[(C_O + rb) * 32]) : "memory");
      asm volatile("mbarrier.arrive.shared::cta.b64 _, [%0], 2;" ::"r"(bar + 8 * B_OST) : "memory");
      TS(2 + layer * 20 + 6);
    }
  }
  __syncwarp();
}

__device__ __forceinline__ void proj_phase(const Params& p, uint32_t sb, int layer, int rb, int q, int wg, int w) {
  const int lane = opaque_tid() & 31;
  const bool TR = layer != 0;
  const int t = lane & 3;
  const uint32_t bar = sb + SM_BAR;
  const uint32_t rbx = sb + SM_R + wg * 8192;
  uint32_t res[16];
  mbar_wait(bar + 8 * B_RF, layer);
  if (threadIdx.x == 0) TS(2 + layer * 20 + 7);
  if (!TR) {
#pragma unroll
    for (int j = 0; j < 8; j += 2) {
      const int mi = lane >> 3;
      const int row = 16 * w + (lane & 7) + 8 * (mi & 1), ch = j + (mi >> 1);
      ldsm4(&res[2 * j], rbx + row * 128 + ((ch ^ (row & 7)) << 4));
    }
  } else {
#pragma unroll
    for (int j = 0; j < 8; j += 2) {
      const int mi = lane >> 3;
      const int line = 8 * (j + (mi >> 1)) + (lane & 7), pc = 2 * w + (mi & 1);
      ldsm4t(&res[2 * j], rbx + line * 128 + ((pc ^ (line & 7)) << 4));
    }
  }
  bar_sync(2 + wg, 128);
  float acc[32];
#pragma unroll
  for (int i = 0; i < 16; i++) {
    asm volatile("shl.b32 %0, %1, 16;" : "=f"(acc[2 * i]) : "r"(res[i]));
    asm volatile("and.b32 %0, %1, 0xffff0000;" : "=f"(acc[2 * i + 1]) : "r"(res[i]));
  }
  const uint32_t tag = part_tag(lds32(sb + SM_EP), 2 * layer + 1);
  mbar_wait(bar + 8 * B_ZF, layer);
  mbar_wait(bar + 8 * B_WOF, layer);
#pragma unroll P_UNROLL
  for (int c = 0; c < 8; c++) {
    mbar_wait(bar + 8 * (B_OF + c), layer);
    if (c == 0 && threadIdx.x == 0) TS(2 + layer * 20 + 8);
    const uint64_t da = mkdesc(sb + sm_o(c) + wg * 8192, 16, 1024, 1);
    const uint64_t db = mkdesc(sb + SM_WO + c * 8192, 8192, 1024, 1);
    wg_fence();
#pragma unroll
    for (int ks = 0; ks < 4; ks++) wgmma_ss<64, 0, 1>(acc, da + ks * 2, db + ks * 128, 1);
    wg_commit();
  }
  wg_wait<0>();
#pragma unroll
  for (int i = 0; i < 32; i++) asm volatile("" : "+f"(acc[i]) :: "memory");
  if (threadIdx.x == 0) TS(2 + layer * 20 + 9);
  if (lane == 0 && w == 0) mbar_arrive(bar + 8 * B_PDONE);
  {
    float s[4], qq[4];
#pragma unroll
    for (int k = 0; k < 4; k++) { s[k] = acc[k]; qq[k] = acc[k] * acc[k]; }
#pragma unroll
    for (int j = 1; j < 8; j++)
#pragma unroll
      for (int k = 0; k < 4; k++) { s[k] += acc[4 * j + k]; qq[k] = fmaf(acc[4 * j + k], acc[4 * j + k], qq[k]); }
    const float s0 = s[0] + s[1], s1 = s[2] + s[3], q0 = qq[0] + qq[1], q1 = qq[2] + qq[3];
    float sr = ((t & 1) ? s1 : s0) + __shfl_xor_sync(~0u, (t & 1) ? s0 : s1, 1);
    float qr = ((t & 1) ? q1 : q0) + __shfl_xor_sync(~0u, (t & 1) ? q0 : q1, 1);
    sr += __shfl_xor_sync(~0u, sr, 2);
    qr += __shfl_xor_sync(~0u, qr, 2);
    if (t < 2) st_part(&g_part[(rb * 8 + q) * 128 + 64 * wg + 16 * w + (lane >> 2) + 8 * t], sr, qr, tag);
    __syncwarp();
    if (elect_one()) mbar_arrive(bar + 8 * B_PS);
    sched_fence<7>();
  }
#pragma unroll
  for (int j = 0; j < 8; j += 2) {
    const int mi = lane >> 3;
    const int line = 8 * (j + (mi >> 1)) + (lane & 7), pc = 2 * w + (mi & 1);
    stsm4t(rbx + line * 128 + ((pc ^ (line & 7)) << 4), packbf(acc[4 * j], acc[4 * j + 1]), packbf(acc[4 * j + 2], acc[4 * j + 3]),
           packbf(acc[4 * j + 4], acc[4 * j + 5]), packbf(acc[4 * j + 6], acc[4 * j + 7]));
  }
  fence_writer();
  bar_sync(2 + wg, 128);
  if (w == 0 && elect_one()) {
    fence_reader();
    fence_async_global();
    tma_st(&p.mapXT, rb * 128 + wg * 64, (2 * layer) * DM + q * 64, rbx);
    bulk_commit();
    if (threadIdx.x == 0) TS(2 + layer * 20 + 10);
    bulk_wait_all();
    red_relaxed(&g_cnt[C_CS * 32 + 2 + layer]);
    if (wg == 0) mbar_arrive(bar + 8 * B_RE);
  }
  __syncwarp();
}
__device__ __forceinline__ void proj_stats(uint32_t sb, int layer, int rb, int q, int lane, uint32_t tag) {
  const int r = 16 * q + (lane & 15);
  const uint2* src = &g_part[rb * 8 * 128 + r];
  uint32_t* dst = g_stats + layer * LSEQ + (rb >> 1) * 256 + ((r >> 2) & 1) * 128 + ((rb & 1) * 16 + (r >> 3)) * 4 + (r & 3);
  mbar_wait(sb + SM_BAR + 8 * B_PS, layer);
  delay<D_PST>();
  for (int it = 0;; it++) {
    uint2 v[8];
#pragma unroll
    for (int i = 0; i < 8; i++) v[i] = ld_part(src + i * 128);
    float s[4], qq[4];
    uint32_t bad = 0;
#pragma unroll
    for (int i = 0; i < 4; i++) {
      s[i] = __uint_as_float(v[i].x) + __uint_as_float(v[i + 4].x);
      qq[i] = __uint_as_float(v[i].y) + __uint_as_float(v[i + 4].y);
      bad |= (v[i].y ^ tag) | (v[i + 4].y ^ tag);
    }
    const float mean = ((s[0] + s[1]) + (s[2] + s[3])) * (1.f / DM);
    const float rstd = rsqrt_approx(fmaxf(fmaf((qq[0] + qq[1]) + (qq[2] + qq[3]), 1.f / DM, -mean * mean), 0.f) + 1e-5f);
    const bool ok = __all_sync(~0u, (bad & 7u) == 0);
    if (ok && lane < 16)
      asm volatile("st.relaxed.gpu.global.u32 [%0], %1;" ::"l"(dst), "r"(max(packbf(NORM_FMA ? -mean * rstd : -mean, rstd), 1u)) : "memory");
    if (ok) break;
    if (it > (1 << 22)) __trap();
  }
}

#define NA 14
#define NP 15
template <int M0, int M1> __device__ __forceinline__ void conv_load(uint32_t* A, uint32_t pe) {
#pragma unroll
  for (int m = M0; m < M1; m++) {
    asm volatile("ld.shared.v2.b32 {%0,%1}, [%2];" : "=r"(A[4 * m]), "=r"(A[4 * m + 1]) : "r"(pe + 256 * m) : "memory");
    A[4 * m + 2] = lds32(pe + 256 * m - 4);
  }
}
__device__ __forceinline__ uint32_t copy_reg(uint32_t v, uint32_t zero) { uint32_t r; asm volatile("or.b32 %0, %1, %2;" : "=r"(r) : "r"(v), "r"(zero)); return r; }
__device__ __forceinline__ uint32_t copy_reg2(uint32_t v, uint32_t zero) { uint32_t r; asm volatile("xor.b32 %0, %1, %2;" : "=r"(r) : "r"(v), "r"(zero)); return r; }
__device__ __forceinline__ void conv_park(uint32_t* P, uint32_t pe) {
#pragma unroll
  for (int m = 0; m < NP; m++)
#pragma unroll
    for (int k = 0; k < 3; k++) P[3 * m + k] = lds32(pe + 256 * m - 4 + 4 * k);
}
__device__ __forceinline__ void conv_unpark(uint32_t* A, const uint32_t* P, uint32_t zero) {
#pragma unroll
  for (int m = 0; m < NP; m++) {
    A[4 * m + 2] = copy_reg(P[3 * m], zero); A[4 * m] = copy_reg(P[3 * m + 1], zero);
    A[4 * m + 3] = copy_reg2(P[3 * m + 1], zero); A[4 * m + 1] = copy_reg(P[3 * m + 2], zero);
  }
}
template <int M0, int M1> __device__ __forceinline__ void conv_mmas(float* acc, const uint32_t* A, uint64_t d) {
  if constexpr (M0 < M1) {
    wgmma_rs<128 - 8 * (M0 / 2), 0>(acc, A + 4 * M0, d + (uint64_t)(4 * M0), M0 != 0);
    conv_mmas<M0 + 1, M1>(acc, A, d);
  }
}
struct SumAddr { uint32_t l0, l1, l2, se, so; };
__device__ __forceinline__ SumAddr conv_sum_addr(uint32_t sb, int c) {
  auto ua = [&](int j) { return sb + cv_u(0) + (127 - (j >> 3)) * 16 + (j & 7) * 2; };
  auto sa = [&](int hc) { const int ci = hc & ~1; return sb + cv_s(0) + ((ci >> 3) & 1) * 1024 + (ci >> 4) * 128 + (((ci ^ (ci >> 4)) & 7) << 4) + (hc & 1) * 8; };
  const int j0 = 4 * (c - 1);
  return {ua(j0 - 2), ua(j0), ua(j0 + 4), sa((c + 1) & 127), sa(c) + 2048};
}
__device__ __forceinline__ void sts64(uint32_t a, uint32_t x, uint32_t y) { asm volatile("st.shared.v2.b32 [%0], {%1,%2};" ::"r"(a), "r"(x), "r"(y) : "memory"); }
__device__ __forceinline__ void conv_sums(const SumAddr& sa, int lc, int c) {
  uint32_t e[4], o[4];
  {
    const float2 em = lds64f(sa.l1 + lc * 32768), om = lds64f(sa.l1 + lc * 32768 + CV_UH);
    e[0] = lds32(sa.l0 + lc * 32768); o[0] = lds32(sa.l0 + lc * 32768 + CV_UH);
    e[3] = lds32(sa.l2 + lc * 32768); o[3] = lds32(sa.l2 + lc * 32768 + CV_UH);
    e[1] = __float_as_uint(em.x); e[2] = __float_as_uint(em.y); o[1] = __float_as_uint(om.x); o[2] = __float_as_uint(om.y);
  }
  uint32_t s7e[2], s7o[2], s9e[2], s9o[2];
  uint32_t pw[4], sh[3];
#pragma unroll
  for (int k = 0; k < 4; k++) pw[k] = hadd2(e[k], o[k]);
#pragma unroll
  for (int k = 0; k < 3; k++) sh[k] = __byte_perm(pw[k], pw[k + 1], 0x5432);
#pragma unroll
  for (int k = 0; k < 2; k++) {
    const uint32_t t3 = hadd2(hadd2(sh[k], sh[k + 1]), pw[k + 1]);
    s7e[k] = hadd2(t3, o[k]); s7o[k] = hadd2(t3, e[k + 2]);
    s9e[k] = hadd2(s7o[k], pw[k]); s9o[k] = hadd2(s7e[k], pw[k + 2]);
  }
  if (c == 127) s9e[0] = s9e[1] = s9o[0] = s9o[1] = 0u;
  sts64(sa.se + lc * 32768, s9e[0], s9e[1]); sts64((sa.se ^ 16) + lc * 32768, s9o[0], s9o[1]);
  sts64(sa.so + lc * 32768, s7e[0], s7e[1]); sts64((sa.so ^ 16) + lc * 32768, s7o[0], s7o[1]);
}

__device__ __forceinline__ void conv_epi(uint32_t sb, int layer, int cta, int ch, int c0, uint4 x0, uint4 x1) {
  uint4 v[2][4];
  const uint4 xr[2] = {x0, x1};
  mbar_wait(sb + SM_BAR + 8 * (B_P + ch), layer);
#pragma unroll
  for (int u = 0; u < 2; u++) {
    const uint32_t pb = sb + cv_pb(ch) + u * (CV_PBW / 2) + c0 * 16;
#pragma unroll
    for (int k = 0; k < 4; k++) v[u][k] = lds128(pb + k * CV_PBW);
  }
#pragma unroll
  for (int u = 0; u < 2; u++) {
    uint4 o;
    o.x = hadd2(xr[u].x, hadd2(hadd2(v[u][0].x, v[u][1].x), hadd2(v[u][2].x, v[u][3].x)));
    o.y = hadd2(xr[u].y, hadd2(hadd2(v[u][0].y, v[u][1].y), hadd2(v[u][2].y, v[u][3].y)));
    o.z = hadd2(xr[u].z, hadd2(hadd2(v[u][0].z, v[u][1].z), hadd2(v[u][2].z, v[u][3].z)));
    o.w = hadd2(xr[u].w, hadd2(hadd2(v[u][0].w, v[u][1].w), hadd2(v[u][2].w, v[u][3].w)));
    if (layer == 0) sts128(sb + cv_s(ch) + (c0 + 128 * u) * 16, o);
    else st_tagged3((uint4*)(g_xT + (size_t)(3 * DM + cv_chan(cta, ch)) * LSEQ) + c0 + 128 * u, o.x, o.y, o.z, o.w);
  }
}
__device__ __forceinline__ void warp_release(uint32_t b) {
  fence_writer();
  __syncwarp();
  if (elect_one()) mbar_arrive(b);
}

__device__ __forceinline__ void conv_prep_load(uint32_t sb, int layer, int cta, int c, uint4 (&xr)[4], uint4 (&st)[4]) {
  sched_fence<8>();
  mbar_wait(sb + SM_BAR + 8 * B_GB, layer);
  if (threadIdx.x == 0) TS(2 + layer * 20 + 11);
  xr[0] = ld_tagged((const uint4*)(g_xT + (size_t)(2 * layer * DM + cta) * LSEQ) + c);
#pragma unroll
  for (int i = 0; i < 2; i++) st[i] = ld_tagged((const uint4*)g_stats + layer * 512 + (c >> 5) * 64 + i * 32 + (c & 31));
}
template <bool HELPER>
__device__ __forceinline__ void conv_prep(uint32_t sb, int layer, int cta, int c, uint4 (&xr)[4], uint4 (&st)[4], const SumAddr& sa) {
  const uint32_t bar = sb + SM_BAR;
  const uint4* xin = (const uint4*)(g_xT + (size_t)(2 * layer * DM + cta) * LSEQ) + c;
  for (int it = 0;; it++) {
    const uint32_t vs = min(min(min(st[0].x, st[0].y), min(st[0].z, st[0].w)), min(min(st[1].x, st[1].y), min(st[1].z, st[1].w)));
    if (__all_sync(~0u, vs != 0 && xr[0].x != ~0u)) break;
    if (it > (1 << 22)) __trap();
    if (!__all_sync(~0u, xr[0].x != ~0u)) xr[0] = ld_tagged(xin);
    if (!__all_sync(~0u, vs != 0)) {
#pragma unroll
      for (int i = 0; i < 2; i++) st[i] = ld_tagged((const uint4*)g_stats + layer * 512 + (c >> 5) * 64 + i * 32 + (c & 31));
    }
  }
  const uint32_t nm[4] = {__byte_perm(st[0].x, st[0].y, 0x5410), __byte_perm(st[0].z, st[0].w, 0x5410), __byte_perm(st[1].x, st[1].y, 0x5410), __byte_perm(st[1].z, st[1].w, 0x5410)};
  const uint32_t rs[4] = {__byte_perm(st[0].x, st[0].y, 0x7632), __byte_perm(st[0].z, st[0].w, 0x7632), __byte_perm(st[1].x, st[1].y, 0x7632), __byte_perm(st[1].z, st[1].w, 0x7632)};
  if (threadIdx.x == 0) TS(2 + layer * 20 + 12);
  const int a = c & 127, h = c >> 7;
#pragma unroll
  for (int i = 0; i < 4; i++) {
    if (i == 1) {
      mbar_wait(bar + 8 * B_XV, layer);
#pragma unroll
      for (int j = 1; j < 4; j++) xr[j] = ld_tagged(xin + j * (128 * LSEQ / 8));
      if (HELPER) {
        mbar_wait(bar + 8 * B_U, layer);
        conv_sums(sa, 0, c);
        fence_async_smem();
        bar_arrive(7, 256);
        sched_fence<1>();
        if (layer == 1 && c == 0) TS(46);
      }
    }
    const uint32_t x[4] = {xr[i].x, xr[i].y, xr[i].z, xr[i].w};
    uint32_t u[4];
#pragma unroll
    for (int k = 0; k < 4; k++)
      u[k] = NORM_FMA ? hfma2(x[k], rs[k], nm[k]) : hmul2(hadd2(x[k], nm[k]), rs[k]);
    sts128(sb + cv_u(i) + h * CV_UH + (127 - a) * 16, make_uint4(u[0], u[1], u[2], u[3]));
    warp_release(bar + 8 * (B_U + i));
    sched_fence<2>();
  }
}
__device__ __forceinline__ void conv_zero(uint32_t sb, int ht) {
  if (ht < 96) {
    const int ch = ht / 24, h2 = (ht / 12) & 1, qq = ht % 12;
    sts128(sb + cv_u(ch) + h2 * CV_UH + (128 + qq) * 16, make_uint4(0, 0, 0, 0));
  }
  if (ht >= 80) {
    const int i = ht - 80, ch = i / 12, q2 = i % 12;
    const int w2 = q2 < 2 ? 1 : q2 < 6 ? 2 : 3, cc = q2 < 2 ? q2 : q2 < 6 ? q2 - 2 : q2 - 6;
    sts128(sb + cv_pb(ch) + w2 * CV_PBW + (cc & 1) * (CV_PBW / 2) + (cc >> 1) * 16, make_uint4(0, 0, 0, 0));
  }
}

#define HANDOVER 1
template <int R>
__device__ __forceinline__ void conv_round(uint32_t sb, int layer, int wg, uint32_t* A, const uint32_t* P, uint32_t pb, uint32_t pe2) {
  const uint32_t bar = sb + SM_BAR;
  const int ch = 2 * R + 1 - wg;
  float acc[64];
  const uint64_t d = mkdesc(sb + cv_u(ch), CV_UH, 128, 0);
  FTS(39);
  if (R == 0) {
    mbar_wait(bar + 8 * (B_U + ch), layer);
    fence_reader();
  }
  sched_fence<3>();
  if (R == 1 || wg == 0) bar_sync(10 + ch, 256);
  if (layer == 0 && ch > 0 && ((PAUSE >> (ch - 1)) & 1)) mbar_wait(bar + 8 * (B_E + ch - 1), 0);
  if (layer == 0 && ch > 0 && ((PAUSE >> (ch + 3)) & 1)) mbar_wait(bar + 8 * (B_P + ch - 1), 0);
  FTS(41);
  if (ch == 0 && threadIdx.x == 128) TS(2 + layer * 20 + 13);
  wg_fence();
  conv_mmas<0, 1>(acc, A, d); conv_mmas<2, NA + 1>(acc, A, d);
  wg_commit();
  FTS(51);
  if (HANDOVER == 0 && (R == 0 || wg == 1)) bar_arrive(11 + ch, 256);
  bar_sync(7 + ch, 256);
  wg_fence();
  conv_mmas<1, 2>(acc, A, d); conv_mmas<NA + 1, 17>(acc, A, d);
  wgmma_ss<64, 1, 1>(acc, mkdesc(sb + cv_s(ch), 1024, 1024, 1), mkdesc(sb + cv_ft(ch), 256, 16, 0), 1);
  wgmma_ss<64, 1, 1>(acc, mkdesc(sb + cv_s(ch) + 2048, 1024, 1024, 1), mkdesc(sb + cv_ft(ch) + 512, 256, 16, 0), 1);
  wg_commit();
  if (HANDOVER == 1 && (R == 0 || wg == 1 || (G_WAIT == 3 && layer == 0))) bar_arrive(11 + ch, 256);
  FTS(61);
  wg_wait<0>();
#pragma unroll
  for (int j = 0; j < 16; j += 2)
    stsm4t(pb + R * 65536 - j * 128, packbf(acc[4 * j], acc[4 * j + 1]), packbf(acc[4 * j + 2], acc[4 * j + 3]),
           packbf(acc[4 * j + 4], acc[4 * j + 5]), packbf(acc[4 * j + 6], acc[4 * j + 7]));
  __syncwarp();
  if (elect_one()) mbar_arrive(bar + 8 * (B_P + ch));
  if (threadIdx.x == 0) TS(2 + layer * 20 + 14 + R);
  FTS(57);
  if (R == 0) {
    conv_unpark(A, P, opaque_tid() >> 10);
    mbar_wait(bar + 8 * (B_U + ch + 2), layer);
    fence_reader();
    conv_load<NP, 17>(A, pe2);
#pragma unroll
    for (int m = NP; m < 17; m++) A[4 * m + 3] = lds32(pe2 + 256 * m);
  }
}
__device__ __forceinline__ void conv_phase(const Params& p, uint32_t sb, int layer, int cta) {
  const int tid = opaque_tid();
  const int wg = __shfl_sync(~0u, tid >> 7, 0), w = __shfl_sync(~0u, (tid >> 5) & 3, 0);
  const uint32_t bar = sb + SM_BAR;
  uint32_t A[68], P[3 * NP];
  const uint32_t pe = sb + cv_pe(1 - wg) + 4 * (16 + 16 * w + 2 * ((tid & 31) >> 2) - 4 * (tid & 3));
  mbar_wait(bar + 8 * B_PE, layer);
  conv_load<0, 17>(A, pe);
#pragma unroll
  for (int m = 0; m < 17; m++) A[4 * m + 3] = copy_reg(A[4 * m], tid >> 10);
  if (wg == 0) {
    uint4 xr[4], st[4];
    if (PARK_FIRST) conv_park(P, pe + 65536);
    conv_prep_load(sb, layer, cta, tid + 128, xr, st);
    if (!PARK_FIRST) conv_park(P, pe + 65536);
    conv_prep<false>(sb, layer, cta, opaque_tid() + 128, xr, st, SumAddr());
  } else {
    conv_park(P, pe + 65536);
  }
  uint32_t pb;
  {
    const int l2 = opaque_tid() & 31, mt = l2 >> 3;
    pb = sb + cv_pb(1 - wg) + w * CV_PBW + (mt & 1) * (CV_PBW / 2) + (127 - 8 * (mt >> 1) - (l2 & 7) + w) * 16;
  }
  conv_round<0>(sb, layer, wg, A, P, pb, pe + 65536);
  conv_round<1>(sb, layer, wg, A, P, pb, 0);
  if (G_WAIT == 1 && layer == 0) mbar_wait(bar + 8 * (B_E + 3), layer);
  if (G_WAIT == 2 && layer == 0) mbar_wait(bar + 8 * (B_P + 3), layer);
}

__device__ __forceinline__ void final_phase(const Params& p, uint32_t sb, int cta, int wg, int w) {
  const int lane = opaque_tid() & 31, g = lane >> 2, t = lane & 3;
  constexpr int RS = 2 * DM;
  int it = 0;
  {
    const int lc = wg ? 0 : 3;
    const int p0 = (cta & 15) * 128 + 32 * w, c0 = 128 * lc + (cta >> 4) * 16;
    const bf16* src = g_xT + (size_t)(3 * DM + c0 + 4 * (g >> 1) + (g & 1)) * LSEQ + p0 + 8 * t;
    bf16* dst = p.out + (size_t)(2 * ((p0 & 1023) + 8 * (g >> 1) + (g & 1)) + (p0 >> 10)) * DM + c0 + 4 * t;
    if (wg == 0) {
      mbar_wait(sb + SM_BAR + 8 * (B_E + 3), 1);
      delay<D_FIN>();
    }
    uint4 a, b;
    for (;;) {
      a = ld_tagged((const uint4*)src); b = ld_tagged((const uint4*)(src + 2 * LSEQ));
      if (__all_sync(~0u, max(a.x, b.x) != ~0u)) break;
      if (++it > (1 << 22)) __trap();
    }
    if (threadIdx.x == 0) TS(42);
    *(uint2*)dst = make_uint2(movm_t(a.x), movm_t(b.x));
    *(uint2*)(dst + 2 * RS) = make_uint2(movm_t(a.y), movm_t(b.y));
    *(uint2*)(dst + 4 * RS) = make_uint2(movm_t(a.z), movm_t(b.z));
    *(uint2*)(dst + 6 * RS) = make_uint2(movm_t(a.w), movm_t(b.w));
  }
  if (wg == 1) {
    const int lc = 1 + (w >> 1);
    const int p0 = (cta & 31) * 64 + 32 * (w & 1), c0 = 128 * lc + (cta >> 5) * 32;
    const bf16* src = g_xT + (size_t)(3 * DM + c0 + 8 * (g >> 1) + (g & 1)) * LSEQ + p0 + 8 * t;
    bf16* dst = p.out + (size_t)(2 * ((p0 & 1023) + 8 * (g >> 1) + (g & 1)) + (p0 >> 10)) * DM + c0 + 8 * t;
    mbar_wait(sb + SM_BAR + 8 * (B_E + lc), 1);
    if (lc >= FIN_D0) delay<D_FIN2>();
    uint4 v[4];
    for (;;) {
#pragma unroll
      for (int q = 0; q < 4; q++) v[q] = ld_tagged((const uint4*)(src + 2 * q * LSEQ));
      if (__all_sync(~0u, max(max(v[0].x, v[1].x), max(v[2].x, v[3].x)) != ~0u)) break;
      if (++it > (1 << 22)) __trap();
    }
    *(uint4*)dst = make_uint4(movm_t(v[0].x), movm_t(v[1].x), movm_t(v[2].x), movm_t(v[3].x));
    *(uint4*)(dst + 2 * RS) = make_uint4(movm_t(v[0].y), movm_t(v[1].y), movm_t(v[2].y), movm_t(v[3].y));
    *(uint4*)(dst + 4 * RS) = make_uint4(movm_t(v[0].z), movm_t(v[1].z), movm_t(v[2].z), movm_t(v[3].z));
    *(uint4*)(dst + 6 * RS) = make_uint4(movm_t(v[0].w), movm_t(v[1].w), movm_t(v[2].w), movm_t(v[3].w));
  }
  if (threadIdx.x == 0) TS(43);
  if (threadIdx.x == 192) TS(63);
  if (threadIdx.x == 160) TS(53);
  if (threadIdx.x == 0) LTS(1);
}

struct cplx { float r, i; };
__device__ __forceinline__ cplx cmul(cplx a, cplx b) { return {fmaf(a.r, b.r, -a.i * b.i), fmaf(a.r, b.i, a.i * b.r)}; }
__device__ __forceinline__ cplx csqr(cplx a) { return {fmaf(a.r, a.r, -a.i * a.i), (a.r + a.r) * a.i}; }
__device__ __forceinline__ cplx cexp_l(float ar2, float ai, float l) {
  const float m = ex2(ar2 * l);
  const float x = ai * l;
  return {m * __cosf(x), m * __sinf(x)};
}

__device__ __forceinline__ void colsum_publish(uint32_t sb, int rb, int hg, int ht, uint32_t tag) {
  const int lane = ht & 31, q = lane & 15, h = lane >> 4;
  const uint32_t src = sb + SM_CW + (ht >> 5) * 4096 + h * 128 + (q & 1) * 8;
  float s[4] = {0.f, 0.f, 0.f, 0.f};
#pragma unroll 8
  for (int r = 0; r < 16; r++) {
    const float2 v = lds64f(src + r * 256 + (((q >> 1) ^ ((2 * r + h) & 7)) << 4));
    s[0] += bf_lo(__float_as_uint(v.x)); s[1] += bf_hi(__float_as_uint(v.x));
    s[2] += bf_lo(__float_as_uint(v.y)); s[3] += bf_hi(__float_as_uint(v.y));
  }
#pragma unroll
  for (int k = 0; k < 4; k++) s[k] += __shfl_xor_sync(~0u, s[k], 16);
  if (h == 0)
    st_tagged3(&g_colsum[(hg * 16 + rb) * 48 + (ht >> 5) * 16 + q], (__float_as_uint(s[0]) & ~7u) | tag, __float_as_uint(s[1]),
               __float_as_uint(s[2]), __float_as_uint(s[3]));
}
__device__ __forceinline__ void colsum_gather(uint32_t sb, int hg, int ht, uint32_t tag) {
  const int lane = ht & 31, rec = (ht >> 5) * 16 + (lane & 15);
  const uint4* src = &g_colsum[(hg * 16 + (lane >> 4) * 8) * 48 + rec];
  float s[4] = {0.f, 0.f, 0.f, 0.f};
#pragma unroll 1
  for (int h = 0; h < 2; h++, src += 4 * 48) {
    uint4 v[4];
    int it = 0;
    do {
#pragma unroll
      for (int i = 0; i < 4; i++) v[i] = ld_tagged(src + i * 48);
      if (++it > (1 << 22)) __trap();
    } while (!__all_sync(~0u, (v[0].x & 7u) == tag && (v[1].x & 7u) == tag && (v[2].x & 7u) == tag && (v[3].x & 7u) == tag));
#pragma unroll
    for (int i = 0; i < 4; i++) {
      s[0] += __uint_as_float(v[i].x & ~7u); s[1] += __uint_as_float(v[i].y); s[2] += __uint_as_float(v[i].z); s[3] += __uint_as_float(v[i].w);
    }
  }
#pragma unroll
  for (int k = 0; k < 4; k++) s[k] += __shfl_xor_sync(~0u, s[k], 16);
  if (lane < 16) sts128f(sb + SM_CS + rec * 16, s[0], s[1], s[2], s[3]);
}

__device__ __forceinline__ uint32_t packh(float lo, float hi) { uint32_t r; asm("cvt.rn.f16x2.f32 %0, %1, %2;" : "=r"(r) : "f"(hi), "f"(lo)); return r; }
__device__ __forceinline__ void mma_f16(float* d, uint32_t a0, uint32_t a1, uint32_t a2, uint32_t a3, uint32_t b0, uint32_t b1) {
  asm volatile("mma.sync.aligned.m16n8k16.row.col.f32.f16.f16.f32 {%0,%1,%2,%3}, {%4,%5,%6,%7}, {%8,%9}, {%0,%1,%2,%3};"
      : "+f"(d[0]), "+f"(d[1]), "+f"(d[2]), "+f"(d[3]) : "r"(a0), "r"(a1), "r"(a2), "r"(a3), "r"(b0), "r"(b1));
}
struct HSeed { uint32_t r, i; };
__device__ __forceinline__ HSeed hseed(cplx s) { return {packh(s.r, s.r), packh(s.i, s.i)}; }
__device__ __forceinline__ void hcmul(uint32_t& o_r, uint32_t& o_i, uint32_t br, uint32_t bi, HSeed s) {
  asm("{\n.reg .b32 t, u;\nmul.rn.f16x2 t, %3, %5;\nneg.f16x2 t, t;\nmul.rn.f16x2 u, %3, %4;\nfma.rn.f16x2 %0, %2, %4, t;\nfma.rn.f16x2 %1, %2, %5, u;\n}"
      : "=&r"(o_r), "=&r"(o_i) : "r"(br), "r"(bi), "r"(s.r), "r"(s.i));
}
struct HTile { uint32_t r[4], i[4]; };
__device__ __forceinline__ void tile_set(HTile& t, int k, cplx a, cplx b) { t.r[k] = packh(a.r, b.r); t.i[k] = packh(a.i, b.i); }
__device__ __forceinline__ void tile_upper(HTile& t, HSeed s) { hcmul(t.r[2], t.i[2], t.r[0], t.i[0], s); hcmul(t.r[3], t.i[3], t.r[1], t.i[1], s); }
__device__ __forceinline__ HTile tile_shift(const HTile& t, HSeed s) {
  HTile o;
#pragma unroll
  for (int k = 0; k < 4; k++) hcmul(o.r[k], o.i[k], t.r[k], t.i[k], s);
  return o;
}
__device__ __forceinline__ void tile_put(const HTile& t, uint32_t a) {
  sts128(a, make_uint4(t.r[0], t.r[1], t.r[2], t.r[3]));
  sts128(a + 512, make_uint4(t.i[0], t.i[1], t.i[2], t.i[3]));
}
__device__ __forceinline__ HTile tile_get(uint32_t a) { HTile o; ldsm4t(o.r, a); ldsm4t(o.i, a + 512); return o; }
__device__ __forceinline__ void tile_mma(float* T, const HTile& a0, const HTile& a1, const HTile& b) {
  mma_f16(T, a0.r[0], a0.r[1], a0.r[2], a0.r[3], b.r[0], b.r[1]);
  mma_f16(T, a0.i[0], a0.i[1], a0.i[2], a0.i[3], b.i[0], b.i[1]);
  mma_f16(T, a1.r[0], a1.r[1], a1.r[2], a1.r[3], b.r[2], b.r[3]);
  mma_f16(T, a1.i[0], a1.i[1], a1.i[2], a1.i[3], b.i[2], b.i[3]);
}
__device__ __forceinline__ void tile_mma2(float* T, float* U, const HTile& a0, const HTile& a1, const HTile& b, const HTile& c) {
  mma_f16(T, a0.r[0], a0.r[1], a0.r[2], a0.r[3], b.r[0], b.r[1]);
  mma_f16(U, a0.r[0], a0.r[1], a0.r[2], a0.r[3], c.r[0], c.r[1]);
  mma_f16(T, a0.i[0], a0.i[1], a0.i[2], a0.i[3], b.i[0], b.i[1]);
  mma_f16(U, a0.i[0], a0.i[1], a0.i[2], a0.i[3], c.i[0], c.i[1]);
  mma_f16(T, a1.r[0], a1.r[1], a1.r[2], a1.r[3], b.r[2], b.r[3]);
  mma_f16(U, a1.r[0], a1.r[1], a1.r[2], a1.r[3], c.r[2], c.r[3]);
  mma_f16(T, a1.i[0], a1.i[1], a1.i[2], a1.i[3], b.i[2], b.i[3]);
  mma_f16(U, a1.i[0], a1.i[1], a1.i[2], a1.i[3], c.i[2], c.i[3]);
}
__device__ __forceinline__ void kgen_unit(uint32_t tab, uint32_t taba, float ar2, float ai, cplx c, float (&T)[5][4]) {
  const cplx z1 = cexp_l(ar2, ai, 1.f), z16 = cexp_l(ar2, ai, 16.f), z256 = cexp_l(ar2, ai, 256.f);
  HTile a0, a1, b0, b1;
  {
    const cplx y1 = {z16.r, -z16.i}, y2 = csqr(y1), y3 = cmul(y2, y1), y4 = csqr(y2), y5 = cmul(y4, y1), y6 = csqr(y3), y7 = cmul(y4, y3);
    HTile t;
    tile_set(t, 0, {1.f, 0.f}, y1); tile_set(t, 1, y2, y3); tile_set(t, 2, y4, y5); tile_set(t, 3, y6, y7);
    const HTile u = tile_shift(t, hseed(csqr(y4)));
    __syncwarp();
    tile_put(t, tab); tile_put(u, tab + 1024);
    __syncwarp();
    a0 = tile_get(taba); a1 = tile_get(taba + 256);
  }
  const cplx z2 = csqr(z1), z4 = csqr(z2), z8 = csqr(z4);
  const HSeed h8 = hseed(z8);
  const cplx d = cmul(c, z256), e = cmul(d, z256);
  {
    const cplx z512 = csqr(z256), f = cmul(e, z512), f8 = cmul(f, z8), f16 = cmul(f, z16), e4 = cmul(e, z4);
    HTile t, u;
    tile_set(t, 0, e4, cmul(e, z8)); tile_set(t, 1, cmul(e4, z8), cmul(e, z16));
    tile_upper(t, hseed(z256));
    tile_set(u, 0, f8, f16); tile_set(u, 1, cmul(f8, z256), cmul(f16, z256));
    tile_upper(u, hseed(z512));
    __syncwarp();
    tile_put(t, tab); tile_put(u, tab + 1024);
    __syncwarp();
    b0 = tile_get(tab); b1 = tile_get(tab + 1024);
  }
  {
    const cplx d2 = cmul(d, z2), d4 = cmul(d, z4);
    HTile t;
    tile_set(t, 0, d2, d4); tile_set(t, 1, cmul(d2, z4), cmul(d, z8));
    tile_upper(t, h8);
    __syncwarp();
    tile_put(t, tab);
    __syncwarp();
    tile_mma2(T[3], T[4], a0, a1, b0, b1);
    b0 = tile_get(tab);
  }
  {
    const cplx c1 = cmul(c, z1), c2 = cmul(c, z2), c3 = cmul(c1, z2), c4 = cmul(c, z4);
    HTile t;
    tile_set(t, 0, c1, c2); tile_set(t, 1, c3, c4); tile_set(t, 2, cmul(c1, z4), cmul(c2, z4)); tile_set(t, 3, cmul(c3, z4), cmul(c4, z4));
    const HTile u = tile_shift(t, h8);
    __syncwarp();
    tile_put(t, tab); tile_put(u, tab + 1024);
    __syncwarp();
    tile_mma(T[2], a0, a1, b0);
    b0 = tile_get(tab); b1 = tile_get(tab + 1024);
    tile_mma2(T[0], T[1], a0, a1, b0, b1);
  }
}
struct ModeIn { uint2 ar, ai, br, bi, cr, ci; };
__device__ __forceinline__ ModeIn load_modes(const Params& p, int idx) {
  return {*(const uint2*)(p.a_re + idx), *(const uint2*)(p.a_im + idx), *(const uint2*)(p.b_re + idx),
          *(const uint2*)(p.b_im + idx), *(const uint2*)(p.c_re + idx), *(const uint2*)(p.c_im + idx)};
}
__device__ __forceinline__ float bf_el(uint2 v, int k) { const uint32_t x = (k & 2) ? v.y : v.x; return (k & 1) ? bf_hi(x) : bf_lo(x); }
struct KGen { float4 cur; float T[5][4]; };
__device__ __forceinline__ uint32_t kgen_slot(uint32_t sb, int ht, int u) {
  return sb + (u < 3 ? SM_KC + (ht >> 5) * (KC_STRIDE * 2) + (u - 1) * 512 + (ht & 31) * 16 + 16 : SM_HALO + 1024 + ht * 16);
}
__device__ __forceinline__ void kgen_setup(KGen& s, uint32_t sb, int cta, int ht, const ModeIn& in, bf16 logdt, bf16 dskip) {
  const float dt = __bfloat162float(__float2bfloat16_rn(expf(__bfloat162float(logdt))));
  float mx = 0.f, k0 = 0.f, ar2[4];
  cplx c[4];
#pragma unroll
  for (int k = 0; k < 4; k++) {
    ar2[k] = (dt * bf_el(in.ar, k)) * 1.4426950408889634f;
    c[k] = cmul({bf_el(in.cr, k), bf_el(in.ci, k)}, {dt * bf_el(in.br, k), dt * bf_el(in.bi, k)});
    k0 += c[k].r;
    mx = fmaxf(mx, fmaxf(fabsf(c[k].r), fabsf(c[k].i)) * ex2(fmaxf(ar2[k] * 2048.f, 0.f)));
  }
  const int ex = min(max(267 - (int)(__reduce_max_sync(~0u, __float_as_uint(mx)) >> 23), 1), 253);
  const float sc = __uint_as_float(ex << 23);
#pragma unroll
  for (int o = 16; o > 0; o >>= 1) k0 += __shfl_xor_sync(~0u, k0, o);
  if ((ht & 31) == 0) {
    const uint32_t kc = sb + SM_KC + (ht >> 5) * (KC_STRIDE * 2);
    sts16(kc, __bfloat16_as_ushort(__float2bfloat16_rn(k0 + __bfloat162float(dskip))));
    sts16(kc + 641 * 2, 0);
    sts32f(kc + 644 * 2, __uint_as_float((254 - ex) << 23));
  }
  s.cur = make_float4(ar2[0], dt * bf_el(in.ai, 0), c[0].r * sc, c[0].i * sc);
#pragma unroll
  for (int k = 1; k < 4; k++) sts128f(kgen_slot(sb, ht, k), ar2[k], dt * bf_el(in.ai, k), c[k].r * sc, c[k].i * sc);
#pragma unroll
  for (int i = 0; i < 5; i++) s.T[i][0] = s.T[i][1] = s.T[i][2] = s.T[i][3] = 0.f;
}
__device__ __forceinline__ void kgen_finish(KGen& s, uint32_t sb, int cta, int ht) {
  const int w = ht >> 5, lane = ht & 31, g = lane >> 2, t = lane & 3;
  const uint32_t kc = sb + SM_KC + w * KC_STRIDE * 2;
  __syncwarp();
  const float inv = __uint_as_float(lds32(kc + 644 * 2));
  auto put = [&](int idx, float v) {
    sts16(kc + idx * 2, __bfloat16_as_ushort(__float2bfloat16_rn(v)));
  };
#pragma unroll
  for (int hi = 0; hi < 2; hi++)
#pragma unroll
    for (int lo = 0; lo < 2; lo++) {
      const int i = g + 8 * hi, j = 2 * t + lo, e = 2 * hi + lo;
      put(16 * i + 1 + j, s.T[0][e] * inv);
      put(16 * i + 9 + j, s.T[1][e] * inv);
      put(257 + 8 * i + j, s.T[2][e] * inv);
      put(385 + 4 * i + (j & 3) + 64 * (j >> 2), s.T[3][e] * inv);
      put(513 + 2 * i + lo + 32 * t, s.T[4][e] * inv);
    }
}

__device__ __forceinline__ void expand_taps(uint32_t sb, int ht) {
  const int ch = ht >> 5, lane = ht & 31;
  const uint32_t kc = sb + SM_KC + ch * KC_STRIDE * 2;
  const uint32_t dst0 = sb + cv_pe(ch);
  auto put = [&](int G, uint32_t u0, uint32_t u1, uint32_t v0, uint32_t v1, uint32_t v2, uint32_t v3, uint32_t v4, uint32_t v5, uint32_t v6, uint32_t v7) {
    const uint32_t dst = dst0 + G * 32;
    sts128(dst, make_uint4(v0 | (u0 << 16), v1 | (u1 << 16), v2 | (v0 << 16), v3 | (v1 << 16)));
    sts128(dst + 16, make_uint4(v4 | (v2 << 16), v5 | (v3 << 16), v6 | (v4 << 16), v7 | (v5 << 16)));
  };
  {
    const uint4 q = lds128(kc + lane * 16);
    const uint32_t pv = lane ? lds32(kc + lane * 16 - 4) : 0u;
    const uint32_t dst = dst0 + (lane + 2) * 32;
    sts128(dst, make_uint4(__byte_perm(q.x, pv, 0x5410), __byte_perm(q.x, pv, 0x7632), __byte_perm(q.y, q.x, 0x5410), __byte_perm(q.y, q.x, 0x7632)));
    sts128(dst + 16, make_uint4(__byte_perm(q.z, q.y, 0x5410), __byte_perm(q.z, q.y, 0x7632), __byte_perm(q.w, q.z, 0x5410), __byte_perm(q.w, q.z, 0x7632)));
    if (lane < 4) sts128(dst0 + lane * 16, make_uint4(0, 0, 0, 0));
  }
  uint32_t a[5], b[2][3], fv[4];
  {
    const uint32_t s1 = kc + 2 * (256 + 4 * lane);
#pragma unroll
    for (int k = 0; k < 5; k++) a[k] = lds16(s1 + 2 * k);
#pragma unroll
    for (int u = 0; u < 2; u++) {
      const uint32_t s2 = kc + 2 * (384 + 2 * (lane + 32 * u));
#pragma unroll
      for (int k = 0; k < 3; k++) b[u][k] = lds16(s2 + 2 * k);
    }
#pragma unroll
    for (int k = 0; k < 4; k++) fv[k] = lds16(kc + 2 * (640 - 4 * lane - k));
  }
  const uint32_t am1 = lds16(kc + 2 * (lane ? 256 + 4 * lane : 255)), am2 = lds16(kc + 2 * (lane ? 255 + 4 * lane : 254));
  const uint32_t bm2 = lds16(kc + 2 * (lane ? 384 + 2 * lane : 383)), k1024 = lds16(kc + 2 * 512);
  put(34 + lane, am2, am1, a[0], a[0], a[1], a[2], a[2], a[2], a[3], a[4]);
#pragma unroll
  for (int u = 0; u < 2; u++) put(66 + lane + 32 * u, u ? b[u][0] : bm2, b[u][0], b[u][0], b[u][0], b[u][0], b[u][1], b[u][1], b[u][1], b[u][2], b[u][2]);
  if (lane < 10) {
    const uint32_t v = lane == 0 ? k1024 : 0u;
    put(130 + lane, v, v, v, v, v, v, v, 0u, 0u, 0u);
  }
  const uint32_t ft = sb + cv_ft(ch) + 4 * lane;
#pragma unroll
  for (int ty = 0; ty < 2; ty++) {
    const uint32_t v = fv[ty] | (fv[ty + 2] << 16);
    sts32f(ft + ty * 512, __uint_as_float(v));
    sts32f(ft + ty * 512 + 128, 0.f);
    sts32f(ft + ty * 512 + 256 + (lane < 2 ? 120 : -8), __uint_as_float(lane < 2 ? 0u : v));
    sts32f(ft + ty * 512 + 384, 0.f);
  }
}

__device__ __forceinline__ int role_id() { int v; asm volatile("mov.u32 %0, %%ctaid.x;" : "=r"(v)); return v; }
#define GMAP 8
__device__ __forceinline__ int role_rb(int cta) { return 4 * (cta >> 5) + (cta & 3); }
__device__ __forceinline__ int role_hg(int cta) { return 2 * (((cta >> 3) & 3) ^ (((cta >> 5) & 1) * 3)) + ((cta >> 2) & 1); }
__device__ __forceinline__ int role_rb2(int cta) { return cta >> 3; }
__device__ __forceinline__ int role_q2(int cta) { return cta & 7; }

__global__ void __launch_bounds__(NTHREADS, 1) fused_kernel(const __grid_constant__ Params p) {
  extern __shared__ __align__(1024) uint8_t smem[];
  const uint32_t sb = s32(smem);
  const int tid = threadIdx.x, lane = tid & 31;
  const int warp = __shfl_sync(~0u, tid >> 5, 0);
  const uint32_t bar = sb + SM_BAR;
  if (tid == 0) TS(0);
  const int cta0 = role_id();
  if (warp == 0 && elect_one()) {
    const int rb = role_rb(cta0), hg = role_hg(cta0);
#pragma unroll
    for (int c = 0; c < 2; c++) { mbar_init(bar + 8 * (B_XF + c), 1); mbar_init(bar + 8 * (B_KVF + c), 1); }
    fence_async_smem();
#pragma unroll
    for (int c = 0; c < 2; c++) {
      mbar_expect(bar + 8 * (B_XF + c), 16384);
      tma_ld(sb + SM_X + c * 16384, &p.mapX128, (rb >> 3) * DM + c * 64, (rb & 7) * 128, bar + 8 * (B_XF + c));
      mbar_expect(bar + 8 * (B_KVF + c), 24576);
      tma_ld3(sb + SM_W + c * 24576, &p.mapW3, hg * 64, c * 64, 0, bar + 8 * (B_KVF + c));
    }
  }
  if (warp == 1 && elect_one()) {
    const int rb = role_rb(cta0), hg = role_hg(cta0);
#pragma unroll
    for (int c = 2; c < 8; c++) mbar_init(bar + 8 * (B_XF + c), 1);
    mbar_init(bar + 8 * (B_KVF + 2), 1); mbar_init(bar + 8 * B_CW, 1);
    fence_async_smem();
    delay<D_START>();
    mbar_expect(bar + 8 * B_CW, 12288);
    tma_ld3(sb + SM_CW, &p.mapW3h, hg * 64, rb * 32, 0, bar + 8 * B_CW);
#pragma unroll
    for (int c = 2; c < 8; c++) {
      mbar_expect(bar + 8 * (B_XF + c), 16384);
      tma_ld(sb + SM_X + c * 16384, &p.mapX128, (rb >> 3) * DM + c * 64, (rb & 7) * 128, bar + 8 * (B_XF + c));
      if (c < 3) {
        mbar_expect(bar + 8 * (B_KVF + c), 24576);
        tma_ld3(sb + SM_W + c * 24576, &p.mapW3, hg * 64, c * 64, 0, bar + 8 * (B_KVF + c));
      }
    }
    TS(56);
  }
  if ((warp & 2) != 0 && warp < 15 && elect_one()) {
    const int grp = 1 + (warp & 1) + 2 * (warp >> 2), cnt = grp < 4 ? 1 : grp < 5 ? 2 : grp < 7 ? 4 : 8;
#pragma unroll
    for (int k = 0; k < 10; k++)
      if (k != 0 || grp > 3 || grp == 2) mbar_init(bar + 8 * (10 * grp + k), cnt);
    fence_async_smem();
  }

  if (warp < 8) {
    if (tid == 0) TS(1);
    asm volatile("setmaxnreg.inc.sync.aligned.u32 %0;" ::"n"(R_CONS));
    const int cta = role_id();
    auto warp_id = [] { return __shfl_sync(~0u, opaque_tid() >> 5, 0); };
    if (tid == 0) TS(54);
#pragma unroll 1
    for (int layer = 0; layer < 2; layer++) {
      { const int cw = warp_id(); attn_phase(p, sb, layer, role_rb(cta), role_hg(cta), cw >> 2, cw & 3); }
      if (STOP == 1 + 3 * layer) return;
      { const int cw = warp_id(); proj_phase(p, sb, layer, role_rb2(cta), role_q2(cta), cw >> 2, cw & 3); }
      if (STOP == 2 + 3 * layer) return;
      conv_phase(p, sb, layer, cta);
      if (STOP == 3 + 3 * layer) return;
    }
    { const int cw = warp_id(); final_phase(p, sb, cta, cw >> 2, cw & 3); }
  } else if (warp < 12) {
    asm volatile("setmaxnreg.dec.sync.aligned.u32 %0;" ::"n"(R_HELP));
    const int ht = tid - 256;
    const int cta = role_id(), rb = role_rb(cta), hg = role_hg(cta);
    unsigned ep0 = 0;
    if (ht == 0) ep0 = ld_relaxed(&g_cnt[C_CS * 32]);
    bar_sync(0, NTHREADS);
    if (ht == 0) {
      asm volatile("st.shared.v2.u32 [%0], {%1, 0};" ::"r"(sb + SM_EP), "r"(ep0 / NCTA) : "memory");
      mbar_arrive(bar + 8 * B_EP);
    }
    mbar_wait(bar + 8 * B_EP, 0);
    stats_publish(sb, 0, rb, hg, opaque_tid() - 256, part_tag(lds32(sb + SM_EP), 0));
    if (ht < 48) {
      const bf16* q = (&p.a_re)[ht >> 3];
      asm volatile("prefetch.global.L2 [%0];" ::"l"(q + cv_chan(cta, (ht >> 1) & 3) * 128 + (ht & 1) * 64));
    }
    {
      KGen kg;
      const uint32_t tab0 = sb + ((ht >> 5) < 2 ? SM_T : SM_T2 - 4096) + (ht >> 5) * 2048;
      const uint32_t tab = tab0 + (ht & 31) * 16, taba = tab0 + ((ht >> 3) & 1) * 1024 + (((ht >> 1) & 8) + (ht & 7)) * 16;
      delay<D_ST0>();
      stats_gather(sb, rb, opaque_tid() - 256, part_tag(lds32(sb + SM_EP), 0));
      if (ht == 0) TS(40);
      const int chn = cv_chan(cta, ht >> 5);
      const ModeIn modes = load_modes(p, chn * 128 + (ht & 31) * 4);
      const bf16 logdt = p.log_dt[chn], dskip = p.dskip[chn];
      if (!HALO_W14 && KG_START != 4) halo_receive(sb, 0, rb, hg, opaque_tid() - 256);
      if (KG_START == 1) mbar_wait(bar + 8 * B_HF, 0);
      kgen_setup(kg, sb, cta, ht, modes, logdt, dskip);
      if (!HALO_W14 && KG_START == 4) halo_receive(sb, 0, rb, hg, opaque_tid() - 256);
      if (KG_START == 2) mbar_wait(bar + 8 * B_HF, 0);
      if (KG_START == 3) mbar_wait(bar + 8 * B_QDONE, 0);
#pragma unroll 1
      for (int u = 0; u < 4; u++) {
        if (u == KG_PRE) {
          KTS(39);
          mbar_wait(bar + 8 * B_AD, 0);
          KTS(41);
        }
        kgen_unit(tab, taba, kg.cur.x, kg.cur.y, {kg.cur.z, kg.cur.w}, kg.T);
        kg.cur = lds128f(kgen_slot(sb, opaque_tid() - 256, u + 1));
      }
      kgen_finish(kg, sb, cta, opaque_tid() - 256);
    }
    KTS(51);
    bar_sync(4, 128);
#pragma unroll 1
    for (int layer = 0; layer < 2; layer++) {
      if (STOP <= 1 + 3 * layer) return;
      mbar_wait(bar + 8 * (EXP_LATE ? B_PS : B_PDONE), layer);
      expand_taps(sb, opaque_tid() - 256);
      conv_zero(sb, opaque_tid() - 256);
      if (ht == 0) TS(52 + layer);
      warp_release(bar + 8 * B_PE);
      if (STOP <= 2 + 3 * layer) return;
      {
        uint4 xr[4], st[4];
        const int c = opaque_tid() - 256;
        const SumAddr sa = conv_sum_addr(sb, c);
        conv_prep_load(sb, layer, cta, c, xr, st);
        conv_prep<true>(sb, layer, cta, c, xr, st, sa);
        if (layer == 1 && ht == 0) TS(62);
        const bf16* xup = g_xT + (size_t)(2 * layer * DM + cta) * LSEQ + (c + 128) * 8;
        const int ahead = layer ? S_AHEAD1 : S_AHEAD0;
        mbar_wait(bar + 8 * (B_U + 3), layer);
        if (ahead == 2) {
          conv_sums(sa, 1, c);
          fence_async_smem();
          bar_arrive(8, 256);
        }
        st[0] = ldcg128(xup);
#pragma unroll
        for (int lc = 0; lc < 4; lc++) {
          if (lc < 3 && lc + ahead < 4) {
            conv_sums(sa, lc + ahead, c);
            fence_async_smem();
            bar_arrive(7 + lc + ahead, 256);
            sched_fence<4>();
          }
          if (lc < 3) st[lc + 1] = ldcg128(xup + (lc + 1) * 128 * LSEQ);
          conv_epi(sb, layer, cta, lc, c, xr[lc], st[lc]);
          warp_release(bar + 8 * (B_E + lc));
          sched_fence<5>();
          if (layer == 1 && lc == 3 && ht == 0) TS(38);
        }
      }
      if (layer == 0 && STOP > 3) {
        const int c1 = role_id();
        stats_publish(sb, 1, role_rb(c1), role_hg(c1), opaque_tid() - 256, part_tag(lds32(sb + SM_EP), 2));
        delay<D_ST>();
        stats_gather(sb, role_rb(c1), opaque_tid() - 256, part_tag(lds32(sb + SM_EP), 2));
        if (ht == 0) TS(25);
        if (!HALO_W14) halo_receive(sb, 1, role_rb(c1), role_hg(c1), opaque_tid() - 256);
      }
    }
  } else {
    asm volatile("setmaxnreg.dec.sync.aligned.u32 %0;" ::"n"(512 - 2 * R_CONS - R_HELP));
    const int cta = role_id(), rb = role_rb(cta), hg = role_hg(cta), rb2 = role_rb2(cta), q2 = role_q2(cta);
    bar_sync(0, NTHREADS);
    if (warp != 12) {
      mbar_wait(bar + 8 * B_EP, 0);
      const uint32_t tag = lds32(sb + SM_EP) % 7 + 1;
      mbar_wait(bar + 8 * B_CW, 0);
      colsum_publish(sb, rb, hg, tid - 416, tag);
      if (tid == 416) TS(50);
      delay<D_CS>();
      colsum_gather(sb, hg, tid - 416, tag);
      __syncwarp();
      if (tid == 416) TS(55);
    }
    if (elect_one()) mbar_arrive(bar + 8 * B_CSF);
    if (warp == 12) {
      if (elect_one()) {
        unsigned epoch = 0;
#pragma unroll 1
        for (int layer = 0; layer < 2; layer++) {
          auto ld_w = [&](int c, int slot) {
            const uint32_t b = bar + 8 * (B_KVF + c);
            mbar_expect(b, 24576);
            tma_ld3(sb + SM_W + slot * 24576, &p.mapW3, hg * 64, c * 64, 0, b);
          };
          if (layer == 0) {
            mbar_wait(bar + 8 * (B_KVF + 2), 0);
            if (rb2 < 4) tma_prefetch2(&p.mapWo128, q2 * 64, rb2 * 128);
            asm volatile("prefetch.tensormap [%0];" ::"l"(&p.mapO) : "memory");
            asm volatile("prefetch.tensormap [%0];" ::"l"(&p.mapO128) : "memory");
            asm volatile("prefetch.tensormap [%0];" ::"l"(&p.mapXT) : "memory");
            asm volatile("prefetch.tensormap [%0];" ::"l"(&p.mapXT3) : "memory");
            mbar_wait(bar + 8 * B_EP, 0);
            epoch = lds32(sb + SM_EP);
          } else {
            mbar_wait(bar + 8 * (B_U + 3), 0);
            ld_w(0, 0); ld_w(1, 1); ld_w(2, 2);
          }
          {
            int slot = 0;
#pragma unroll 1
            for (int c = 3; c < 8; c++) {
              mbar_wait(bar + 8 * (B_KVE + c - 3), layer);
              ld_w(c, slot);
              slot = slot == 2 ? 0 : slot + 1;
            }
          }
          if (STOP <= 1 + 3 * layer) return;
          const int early = layer ? WO_E1 : WO_E0;
          mbar_wait(bar + 8 * B_STF, layer);
          fence_async_smem();
          mbar_expect(bar + 8 * B_WOF, 65536);
#pragma unroll
          for (int c = 0; c < 4; c++) if (c < early) tma_ld(sb + SM_WO + c * 16384, &p.mapWo128, q2 * 64, c * 128, bar + 8 * B_WOF);
          mbar_wait(bar + 8 * B_QDONE, layer);
          mbar_wait(bar + 8 * B_HF, layer);
#pragma unroll
          for (int c = 0; c < 4; c++) if (c >= early) tma_ld(sb + SM_WO + c * 16384, &p.mapWo128, q2 * 64, c * 128, bar + 8 * B_WOF);
          {
            const uint32_t b = bar + 8 * B_RF;
            mbar_expect(b, 16384);
            if (layer == 0) tma_ld(sb + SM_R, &p.mapX128, (rb2 >> 3) * DM + q2 * 64, (rb2 & 7) * 128, b);
            else tma_ld3(sb + SM_R, &p.mapXT3, 0, DM + q2 * 64, rb2 * 2, b);
          }
#pragma unroll
          for (int c = 0; c < 8; c++) mbar_expect(bar + 8 * (B_OF + c), 16384);
          spin_until(&g_cnt[(C_O + rb2) * 32], (2 * epoch + layer + 1) * 16);
          fence_async_global();
#pragma unroll
          for (int c = 0; c < 8; c++) {
            if (c == 6) { mbar_wait(bar + 8 * B_OST, layer); fence_async_smem(); }
            tma_ld(sb + sm_o(c), &p.mapO128, c * 64, rb2 * 128, bar + 8 * (B_OF + c));
          }
          if (STOP <= 3 + 3 * layer) return;
        }
      }
    } else if (warp == 13) {
      if (elect_one() && STOP > 1) {
        const unsigned target = (lds32(sb + SM_EP) + 1) * NCTA;
        mbar_wait(bar + 8 * B_RE, 0);
        spin_until(&g_cnt[C_CS * 32 + 2], 2 * target);
        mbar_arrive(bar + 8 * B_XV);
        if (STOP <= 3) return;
        auto ld_x = [&](int c) { tma_ld3(sb + SM_X + c * 16384, &p.mapXT3, 0, DM + c * 64, rb * 2, bar + 8 * (B_XF + c)); };
#pragma unroll
        for (int c = 0; c < 8; c++) mbar_expect(bar + 8 * (B_XF + c), 16384);
        spin_until(&g_cnt[C_G1 * 32], target);
        fence_async_global();
        fence_async_smem();
        ld_x(0); ld_x(1);
        int done = 1, it = 0;
        while (done < 4) {
          const uint4 v = ld_tagged((const uint4*)&g_cnt[C_G1 * 32]);
          const int n = 4 + ((int)(v.y - target) >> 31) + ((int)(v.z - target) >> 31) + ((int)(v.w - target) >> 31);
          if (n == done) { if (++it > (1 << 23)) __trap(); continue; }
          if (n == 4) TS(44);
          fence_async_global();
          fence_async_smem();
          if (done == 1) { ld_x(2); ld_x(3); }
          const int h = hg >> 2;
          if (done < 3 && n >= 3) ld_x(4 + h);
          if (n == 4) ld_x(6 + h);
          if (done < 3 && n >= 3) ld_x(5 - h);
          if (n == 4) ld_x(7 - h);
          done = n;
        }
        if (STOP <= 4) return;
        mbar_wait(bar + 8 * B_RE, 1);
        spin_until(&g_cnt[C_CS * 32 + 3], 2 * target);
        mbar_arrive(bar + 8 * B_XV);
      }
    } else if (warp == 15) {
      mbar_wait(bar + 8 * B_EP, 0);
      const unsigned epoch = lds32(sb + SM_EP);
#pragma unroll 1
      for (int layer = 0; layer < 2; layer++) {
        mbar_wait(bar + 8 * (B_KVF + FILL_AT), layer);
#pragma unroll
        for (int k = 0; k < 8; k++) ((uint4*)(g_xT + (size_t)(2 * layer * DM + cta) * LSEQ))[32 * k + lane] = make_uint4(~0u, ~0u, ~0u, ~0u);
        mbar_wait(bar + 8 * (B_KVF + FILL_AT + 1), layer);
#pragma unroll
        for (int k = 0; k < 16; k++)
          ((uint4*)(g_xT + (size_t)(3 * DM + cv_chan(cta, 3 - (k >> 2))) * LSEQ))[128 * layer + 32 * (k & 3) + lane] = make_uint4(~0u, ~0u, ~0u, ~0u);
        if (lane < 4) ((uint4*)g_stats)[layer * 512 + cta * 4 + lane] = make_uint4(0, 0, 0, 0);
        __syncwarp();
        if (elect_one()) {
          red_release(&g_cnt[C_CS * 32 + layer]);
          spin_until(&g_cnt[C_CS * 32 + layer], (epoch + 1) * NCTA);
          mbar_arrive(bar + 8 * B_ZF);
          if (layer == 0 && STOP > 2) {
#pragma unroll
            for (int lc = 0; lc < 4; lc++) {
              mbar_wait(bar + 8 * (B_E + lc), 0);
              fence_reader();
              bulk_st(g_xT + (size_t)(DM + cv_chan(cta, lc)) * LSEQ, sb + cv_s(lc), 4096);
              bulk_commit();
              bulk_wait_all();
              red_relaxed(&g_cnt[C_G1 * 32 + lc]);
              if (lc == 3) TS(18);
            }
          }
        }
        __syncwarp();
        if (STOP <= 3) return;
      }
    } else if (warp == 14) {
      mbar_wait(bar + 8 * B_EP, 0);
      const unsigned epoch = lds32(sb + SM_EP);
#pragma unroll 1
      for (int layer = 0; layer < 2; layer++) {
        if (STOP <= 3 * layer) return;
        if (HALO_W14) halo_receive1(sb, layer, rb, hg, opaque_tid() & 31, 2 * epoch + layer + 1);
        if (STOP <= 1 + 3 * layer) return;
        mbar_wait(bar + 8 * B_ZF, layer);
        proj_stats(sb, layer, rb2, q2, opaque_tid() & 31, part_tag(epoch, 2 * layer + 1));
        if (layer == 1 && lane == 0) TS(5);
        delay<D_PREP>();
        if (lane == 0) mbar_arrive(bar + 8 * B_GB);
      }
    }
  }
}

typedef CUresult (*EncodeFn)(CUtensorMap*, CUtensorMapDataType, cuuint32_t, void*, const cuuint64_t*, const cuuint64_t*,
                             const cuuint32_t*, const cuuint32_t*, CUtensorMapInterleave, CUtensorMapSwizzle,
                             CUtensorMapL2promotion, CUtensorMapFloatOOBfill);

static void make_map(EncodeFn enc, CUtensorMap* m, void* ptr, uint64_t cols, uint64_t rows, uint32_t box_rows) {
  cuuint64_t dims[2] = {cols, rows};
  cuuint64_t strides[1] = {cols * 2};
  cuuint32_t box[2] = {64, box_rows};
  cuuint32_t es[2] = {1, 1};
  enc(m, CU_TENSOR_MAP_DATA_TYPE_BFLOAT16, 2, ptr, dims, strides, box, es, CU_TENSOR_MAP_INTERLEAVE_NONE,
      CU_TENSOR_MAP_SWIZZLE_128B, CU_TENSOR_MAP_L2_PROMOTION_L2_128B, CU_TENSOR_MAP_FLOAT_OOB_FILL_NONE);
}
static void make_map3(EncodeFn enc, CUtensorMap* m, void* ptr, uint64_t d0, uint64_t cols, uint64_t rows, uint64_t blk_stride,
                      uint64_t nblocks, uint32_t nblk, uint32_t box_rows = 64) {
  cuuint64_t dims[3] = {d0, rows, nblocks};
  cuuint64_t strides[2] = {cols * 2, blk_stride * 2};
  cuuint32_t box[3] = {64, box_rows, nblk};
  cuuint32_t es[3] = {1, 1, 1};
  enc(m, CU_TENSOR_MAP_DATA_TYPE_BFLOAT16, 3, ptr, dims, strides, box, es, CU_TENSOR_MAP_INTERLEAVE_NONE,
      CU_TENSOR_MAP_SWIZZLE_128B, CU_TENSOR_MAP_L2_PROMOTION_L2_128B, CU_TENSOR_MAP_FLOAT_OOB_FILL_NONE);
}

extern "C" void kernel_launch(void* const* d_in, const int* in_sizes, int n_in, void* d_out, int out_size) {
  static Params prm;
  static void* cached[13] = {nullptr};
  static bool attr_done = false;
  bool same = attr_done && cached[12] == d_out;
  for (int i = 0; i < 12 && same; i++) same = cached[i] == d_in[i];
  if (!same) {
    void* fn = nullptr;
    cudaDriverEntryPointQueryResult qr;
    cudaGetDriverEntryPoint("cuTensorMapEncodeTiled", &fn, cudaEnableDefault, &qr);
    EncodeFn enc = (EncodeFn)fn;
    void *pO, *pXT;
    cudaGetSymbolAddress(&pO, g_O);
    cudaGetSymbolAddress(&pXT, g_xT);
    make_map(enc, &prm.mapO, pO, DM, LSEQ, 16);
    make_map(enc, &prm.mapXT, pXT, LSEQ, 4 * DM, 64);
    prm.out = (bf16*)d_out;
    make_map(enc, &prm.mapX128, d_in[0], 2 * DM, LSEQ / 2, 128);
    make_map(enc, &prm.mapWo128, d_in[2], DM, DM, 128);
    make_map(enc, &prm.mapO128, pO, DM, LSEQ, 128);
    make_map3(enc, &prm.mapW3, d_in[1], DM, 3 * DM, DM, DM, 3, 3);
    make_map3(enc, &prm.mapW3h, d_in[1], DM, 3 * DM, DM, DM, 3, 3, 32);
    make_map3(enc, &prm.mapXT3, pXT, 64, LSEQ, 4 * DM, 64, 32, 2);
    prm.a_re = (const bf16*)d_in[4]; prm.a_im = (const bf16*)d_in[5];
    prm.b_re = (const bf16*)d_in[6]; prm.b_im = (const bf16*)d_in[7];
    prm.c_re = (const bf16*)d_in[8]; prm.c_im = (const bf16*)d_in[9];
    prm.log_dt = (const bf16*)d_in[10]; prm.dskip = (const bf16*)d_in[11];
    cudaFuncSetAttribute(fused_kernel, cudaFuncAttributeMaxDynamicSharedMemorySize, SM_TOTAL);
    for (int i = 0; i < 12; i++) cached[i] = d_in[i];
    cached[12] = d_out;
    attr_done = true;
  }
  prm.stop = 100;
    fused_kernel<<<NCTA, NTHREADS, SM_TOTAL>>>(prm);
}
```

```cpp
#include <cuda_runtime.h>
#include <cuda_bf16.h>
#include <cuda.h>
#include <stdint.h>

typedef __nv_bfloat16 bf16;

constexpr int LSEQ = 2048;
constexpr int DM = 512;
constexpr int NCTA = 128;
constexpr int NTHREADS = 512;
#define RR 0
#define KG_PRE 2
#define WO_E0 4
#define WO_E1 2
#define FILL_AT 6
#define EXP_LATE 1
#define RFENCE 1
#define D_FIN 500
#define D_PREP 600
#define D_PST 0
#define D_HALO 500
#define STAG0 2
#define STAG1 2
#define D_ST 500
#define TLAYER 1
#define KG_PD 1
#define SUM_F32 0
#define CS_LATE0 0
#define D_HALO1 0
#define KG_START 0
#define S_AHEAD0 1
#define S_AHEAD1 2
#define PAUSE 2
#define PARK_FIRST 0
#define P_UNROLL_N 1
constexpr int P_UNROLL = P_UNROLL_N;
#define PUB 1
#define X_ORDER 1
#define CS_STEP 1
#define D_FIN2 400
#define FIN_D0 2
#define QD_AT 1
#define G_WAIT 2
#define HALO_W14 1
#define D_START 200
#define D_CS 400
#define D_ST0 500
#define KG_LAST 0
#define X_JIT 0
#define KG_GATE 2
#define R_CONS 192
#define R_HELP 88

constexpr int SM_X = 0;
constexpr int SM_W = 131072;
constexpr int SM_KVX = SM_X;
constexpr int SM_WO = SM_X + 16384;
constexpr int SM_OST = SM_W + 49152;
__host__ __device__ constexpr int sm_o(int c) { return c < 7 ? SM_X + (5 + c) * 16384 : SM_KVX; }
constexpr int SM_R = 196608;
constexpr int SM_T = 212992;
constexpr int SM_KC = 217088;
constexpr int KC_STRIDE = 648;
constexpr int SM_CS = SM_KC + 4 * KC_STRIDE * 2;
constexpr int SM_CW = SM_R + 8192;
constexpr int SM_EP = SM_CS + 768;
constexpr int SM_BAR = SM_EP + 16;
constexpr int SM_T2 = SM_BAR + 896;
constexpr int SM_HALO = SM_T2 + 4096;
constexpr int SM_ST = SM_HALO + 3072;
constexpr int SM_TOTAL = SM_HALO + 4096;
static_assert(SM_TOTAL <= 232448, "shared memory");

constexpr int CV_UH = 140 * 16;
constexpr int CV_PECH = 1120 * 4;
constexpr int CV_PBW = 2112 * 2;
__host__ __device__ constexpr int cv_s(int lc) { return SM_X + lc * 32768; }
__host__ __device__ constexpr int cv_u(int lc) { return cv_s(lc) + 4096; }
__host__ __device__ constexpr int cv_pe(int lc) { return cv_u(lc) + 2 * CV_UH; }
__host__ __device__ constexpr int cv_pb(int lc) { return cv_pe(lc) + CV_PECH; }
__host__ __device__ constexpr int cv_ft(int lc) { return cv_pb(lc) + 4 * CV_PBW; }
static_assert(cv_ft(0) + 1024 <= 32768, "conv buffers");
__host__ __device__ constexpr int cv_chan(int cta, int lc) { return cta + 128 * lc; }

enum {
  B_XF = 0,
  B_KVF = 8,
  B_OF = 16,
  B_WOF = 24,
  B_T = 31,
  B_RF = 28,
  B_RE = 29,
  B_CW = 30,
  B_GB = 35,
  B_EP = 36,
  B_ZF = 37,
  B_XV = 39,
  B_SD = 38,
  B_KVE = 40,
  B_OST = 46,
  B_QDONE = 47,
  B_PDONE = 48,
  B_S = 50,
  B_E = 54,
  B_P = 58,
  B_PE = 62,
  B_STF = 63,
  B_CSF = 64,
  B_HF = 65,
  B_U = 70,
  B_AD = 75,
  B_PS = 74,
  B_COUNT = 80
};

enum {
  C_CS = 0,
  C_G1 = 2,
  C_O = 4,
  C_COUNT = 20
};

__device__ __align__(128) unsigned g_cnt[C_COUNT * 32];
__device__ __align__(1024) bf16 g_O[LSEQ * DM];
__device__ __align__(1024) bf16 g_xT[4 * DM * LSEQ];
__device__ __align__(1024) uint32_t g_stats[2 * LSEQ];
__device__ __align__(1024) uint4 g_colsum[8 * 16 * 48];
__device__ __align__(1024) uint4 g_halo[16 * 8 * 192];
__device__ __align__(1024) uint2 g_part[16 * 8 * 128];
#define TS(i) do { } while (0)

#define ATS(i, th) do { } while (0)
#define KTS(i) do { if (ht == 0) TS(i); } while (0)
#define FTS(i) do { } while (0)
#define LTS(i) do { } while (0)

#define STOP 100

struct Params {
  CUtensorMap mapO, mapXT, mapX128, mapWo128, mapO128, mapW3, mapW3h, mapXT3;
  const bf16 *a_re, *a_im, *b_re, *b_im, *c_re, *c_im, *log_dt, *dskip;
  bf16* out;
  int stop;
};

__device__ __forceinline__ uint32_t s32(const void* p) { return (uint32_t)__cvta_generic_to_shared(p); }
__device__ __forceinline__ void mbar_init(uint32_t b, int c) { asm volatile("mbarrier.init.shared::cta.b64 [%0], %1;" ::"r"(b), "r"(c) : "memory"); }
__device__ __forceinline__ void mbar_expect(uint32_t b, int bytes) { asm volatile("mbarrier.arrive.expect_tx.shared::cta.b64 _, [%0], %1;" ::"r"(b), "r"(bytes) : "memory"); }
__device__ __forceinline__ void mbar_arrive(uint32_t b) { asm volatile("mbarrier.arrive.shared::cta.b64 _, [%0];" ::"r"(b) : "memory"); }
__device__ __forceinline__ void mbar_arrive_if(uint32_t b, bool c) {
  asm volatile("{\n.reg .pred p;\nsetp.ne.u32 p, %1, 0;\n@p mbarrier.arrive.shared::cta.b64 _, [%0];\n}" ::"r"(b), "r"((uint32_t)c) : "memory");
}
__device__ __forceinline__ void mbar_wait(uint32_t b, int parity) {
  asm volatile("{\n.reg .pred p;\nWAIT_LOOP:\nmbarrier.try_wait.parity.shared::cta.b64 p, [%0], %1;\n@p bra WAIT_DONE;\nbra WAIT_LOOP;\nWAIT_DONE:\n}" ::"r"(b), "r"(parity) : "memory");
}
template <int N> __device__ __forceinline__ void delay() {
  if constexpr (N > 0) {
    uint32_t t0, t;
    asm volatile("mov.u32 %0, %%clock;" : "=r"(t0));
    do { asm volatile("mov.u32 %0, %%clock;" : "=r"(t)); } while (t - t0 < N);
  }
}
#define SF 3
template <int ID> __device__ __forceinline__ void sched_fence() {
  if constexpr ((SF >> ID) & 1)
    asm volatile("{\n.reg .pred p;\n.reg .u32 t;\nsetp.eq.u32 p, %0, 0;\n@p mov.u32 t, %%clock;\n@p st.shared.u32 [%0], t;\n}" ::"r"(gridDim.x) : "memory");
}
__device__ __forceinline__ int opaque_tid() { int v; asm volatile("mov.u32 %0, %%tid.x;" : "=r"(v)); return v; }
__device__ __forceinline__ bool elect_one() {
  uint32_t r;
  asm volatile("{\n.reg .pred p;\nelect.sync _|p, 0xffffffff;\nselp.u32 %0, 1, 0, p;\n}" : "=r"(r));
  return r != 0;
}
__device__ __forceinline__ void tma_ld(uint32_t dst, const CUtensorMap* m, int c0, int c1, uint32_t bar) {
  asm volatile("cp.async.bulk.tensor.2d.shared::cluster.global.mbarrier::complete_tx::bytes [%0], [%1, {%3, %4}], [%2];"
               ::"r"(dst), "l"(m), "r"(bar), "r"(c0), "r"(c1) : "memory");
}
__device__ __forceinline__ void tma_ld3(uint32_t dst, const CUtensorMap* m, int c0, int c1, int c2, uint32_t bar) {
  asm volatile("cp.async.bulk.tensor.3d.shared::cluster.global.mbarrier::complete_tx::bytes [%0], [%1, {%3, %4, %5}], [%2];"
               ::"r"(dst), "l"(m), "r"(bar), "r"(c0), "r"(c1), "r"(c2) : "memory");
}
__device__ __forceinline__ void tma_prefetch2(const CUtensorMap* m, int c0, int c1) {
  asm volatile("cp.async.bulk.prefetch.tensor.2d.L2.global.tile [%0, {%1, %2}];" ::"l"(m), "r"(c0), "r"(c1) : "memory");
}
__device__ __forceinline__ void tma_prefetch3(const CUtensorMap* m, int c0, int c1, int c2) {
  asm volatile("cp.async.bulk.prefetch.tensor.3d.L2.global.tile [%0, {%1, %2, %3}];" ::"l"(m), "r"(c0), "r"(c1), "r"(c2) : "memory");
}
__device__ __forceinline__ void tma_st(const CUtensorMap* m, int c0, int c1, uint32_t src) {
  asm volatile("cp.async.bulk.tensor.2d.global.shared::cta.bulk_group [%0, {%2, %3}], [%1];" ::"l"(m), "r"(src), "r"(c0), "r"(c1) : "memory");
}
__device__ __forceinline__ void bulk_ld(uint32_t dst, const void* src, int bytes, uint32_t bar) {
  asm volatile("cp.async.bulk.shared::cluster.global.mbarrier::complete_tx::bytes [%0], [%1], %2, [%3];" ::"r"(dst), "l"(src), "r"(bytes), "r"(bar) : "memory");
}
__device__ __forceinline__ void bulk_st(void* dst, uint32_t src, int bytes) {
  asm volatile("cp.async.bulk.global.shared::cta.bulk_group [%0], [%1], %2;" ::"l"(dst), "r"(src), "r"(bytes) : "memory");
}
__device__ __forceinline__ void bulk_red_add_f32(void* dst, uint32_t src, int bytes) {
  asm volatile("cp.reduce.async.bulk.global.shared::cta.bulk_group.add.f32 [%0], [%1], %2;" ::"l"(dst), "r"(src), "r"(bytes) : "memory");
}
__device__ __forceinline__ void bulk_commit() { asm volatile("cp.async.bulk.commit_group;" ::: "memory"); }
__device__ __forceinline__ void bulk_wait_all() { asm volatile("cp.async.bulk.wait_group 0;" ::: "memory"); }
__device__ __forceinline__ void fence_async_smem() { asm volatile("fence.proxy.async.shared::cta;" ::: "memory"); }
__device__ __forceinline__ void fence_writer() { if (!RFENCE) fence_async_smem(); }
__device__ __forceinline__ void fence_reader() { if (RFENCE) fence_async_smem(); }
__device__ __forceinline__ void fence_async_global() { asm volatile("fence.proxy.async.global;" ::: "memory"); }
__device__ __forceinline__ void bar_sync(int id, int n) { asm volatile("bar.sync %0, %1;" ::"r"(id), "r"(n) : "memory"); }
__device__ __forceinline__ void bar_arrive(int id, int n) { asm volatile("bar.arrive %0, %1;" ::"r"(id), "r"(n) : "memory"); }
__device__ __forceinline__ void wg_fence() { asm volatile("wgmma.fence.sync.aligned;" ::: "memory"); }
__device__ __forceinline__ void wg_commit() { asm volatile("wgmma.commit_group.sync.aligned;" ::: "memory"); }
template <int N> __device__ __forceinline__ void wg_wait() { asm volatile("wgmma.wait_group.sync.aligned %0;" ::"n"(N) : "memory"); }
__device__ __forceinline__ uint64_t mkdesc(uint32_t addr, uint32_t lbo, uint32_t sbo, int sw) {
  return (uint64_t)((addr & 0x3FFFF) >> 4) | ((uint64_t)(lbo >> 4) << 16) | ((uint64_t)(sbo >> 4) << 32) | ((uint64_t)sw << 62);
}
__device__ __forceinline__ void ldsm4(uint32_t* r, uint32_t a) {
  asm volatile("ldmatrix.sync.aligned.m8n8.x4.shared.b16 {%0,%1,%2,%3}, [%4];" : "=r"(r[0]), "=r"(r[1]), "=r"(r[2]), "=r"(r[3]) : "r"(a) : "memory");
}
__device__ __forceinline__ void ldsm4t(uint32_t* r, uint32_t a) {
  asm volatile("ldmatrix.sync.aligned.m8n8.x4.trans.shared.b16 {%0,%1,%2,%3}, [%4];" : "=r"(r[0]), "=r"(r[1]), "=r"(r[2]), "=r"(r[3]) : "r"(a) : "memory");
}
__device__ __forceinline__ void stsm4(uint32_t a, uint32_t r0, uint32_t r1, uint32_t r2, uint32_t r3) {
  asm volatile("stmatrix.sync.aligned.m8n8.x4.shared.b16 [%0], {%1,%2,%3,%4};" ::"r"(a), "r"(r0), "r"(r1), "r"(r2), "r"(r3) : "memory");
}
__device__ __forceinline__ void stsm4t(uint32_t a, uint32_t r0, uint32_t r1, uint32_t r2, uint32_t r3) {
  asm volatile("stmatrix.sync.aligned.m8n8.x4.trans.shared.b16 [%0], {%1,%2,%3,%4};" ::"r"(a), "r"(r0), "r"(r1), "r"(r2), "r"(r3) : "memory");
}
__device__ __forceinline__ uint32_t movm_t(uint32_t a) { uint32_t r; asm volatile("movmatrix.sync.aligned.m8n8.trans.b16 %0, %1;" : "=r"(r) : "r"(a)); return r; }
__device__ __forceinline__ uint32_t lds32(uint32_t a) { uint32_t v; asm volatile("ld.shared.b32 %0, [%1];" : "=r"(v) : "r"(a) : "memory"); return v; }
__device__ __forceinline__ float2 lds64f(uint32_t a) { float2 v; asm volatile("ld.shared.v2.f32 {%0,%1}, [%2];" : "=f"(v.x), "=f"(v.y) : "r"(a) : "memory"); return v; }
__device__ __forceinline__ float4 lds128f(uint32_t a) { float4 v; asm volatile("ld.shared.v4.f32 {%0,%1,%2,%3}, [%4];" : "=f"(v.x), "=f"(v.y), "=f"(v.z), "=f"(v.w) : "r"(a) : "memory"); return v; }
__device__ __forceinline__ uint4 lds128(uint32_t a) { uint4 v; asm volatile("ld.shared.v4.b32 {%0,%1,%2,%3}, [%4];" : "=r"(v.x), "=r"(v.y), "=r"(v.z), "=r"(v.w) : "r"(a) : "memory"); return v; }
__device__ __forceinline__ void sts128(uint32_t a, uint4 v) { asm volatile("st.shared.v4.b32 [%0], {%1,%2,%3,%4};" ::"r"(a), "r"(v.x), "r"(v.y), "r"(v.z), "r"(v.w) : "memory"); }
__device__ __forceinline__ void sts128f(uint32_t a, float x, float y, float z, float w) { asm volatile("st.shared.v4.f32 [%0], {%1,%2,%3,%4};" ::"r"(a), "f"(x), "f"(y), "f"(z), "f"(w) : "memory"); }
__device__ __forceinline__ void sts32f(uint32_t a, float v) { asm volatile("st.shared.f32 [%0], %1;" ::"r"(a), "f"(v) : "memory"); }
__device__ __forceinline__ void sts16(uint32_t a, uint16_t v) { asm volatile("st.shared.u16 [%0], %1;" ::"r"(a), "h"(v) : "memory"); }
__device__ __forceinline__ uint32_t lds16(uint32_t a) { uint16_t v; asm volatile("ld.shared.u16 %0, [%1];" : "=h"(v) : "r"(a) : "memory"); return v; }
__device__ __forceinline__ uint32_t packbf(float lo, float hi) { uint32_t r; asm("cvt.rn.bf16x2.f32 %0, %1, %2;" : "=r"(r) : "f"(hi), "f"(lo)); return r; }
__device__ __forceinline__ float bf_lo(uint32_t v) { return __uint_as_float(v << 16); }
__device__ __forceinline__ float bf_hi(uint32_t v) { return __uint_as_float(v & 0xffff0000u); }
__device__ __forceinline__ float ex2(float x) { float r; asm("ex2.approx.ftz.f32 %0, %1;" : "=f"(r) : "f"(x)); return r; }
__device__ __forceinline__ float rsqrt_approx(float x) { float r; asm("rsqrt.approx.ftz.f32 %0, %1;" : "=f"(r) : "f"(x)); return r; }
__device__ __forceinline__ float rcp_approx(float x) { float r; asm("rcp.approx.ftz.f32 %0, %1;" : "=f"(r) : "f"(x)); return r; }
__device__ __forceinline__ void mma_bf16(float* d, const uint32_t* a, uint32_t b0, uint32_t b1) {
  asm("mma.sync.aligned.m16n8k16.row.col.f32.bf16.bf16.f32 {%0,%1,%2,%3}, {%4,%5,%6,%7}, {%8,%9}, {%0,%1,%2,%3};"
               : "+f"(d[0]), "+f"(d[1]), "+f"(d[2]), "+f"(d[3]) : "r"(a[0]), "r"(a[1]), "r"(a[2]), "r"(a[3]), "r"(b0), "r"(b1));
}
__device__ __forceinline__ void mma_bf16_k8(float* d, uint32_t a0, uint32_t a1, uint32_t b) {
  asm("mma.sync.aligned.m16n8k8.row.col.f32.bf16.bf16.f32 {%0,%1,%2,%3}, {%4,%5}, {%6}, {%0,%1,%2,%3};"
      : "+f"(d[0]), "+f"(d[1]), "+f"(d[2]), "+f"(d[3]) : "r"(a0), "r"(a1), "r"(b));
}
__device__ __forceinline__ void red_release(unsigned* p) { asm volatile("red.release.gpu.global.add.u32 [%0], 1;" ::"l"(p) : "memory"); }
__device__ __forceinline__ void red_relaxed(unsigned* p) { asm volatile("red.relaxed.gpu.global.add.u32 [%0], 1;" ::"l"(p) : "memory"); }
__device__ __forceinline__ unsigned ld_relaxed(const unsigned* p) { unsigned v; asm volatile("ld.relaxed.gpu.global.u32 %0, [%1];" : "=r"(v) : "l"(p) : "memory"); return v; }
__device__ __forceinline__ void spin_until(const unsigned* p, unsigned target) {
  int it = 0;
  while ((int)(ld_relaxed(p) - target) < 0) {
    if (++it > (1 << 23)) __trap();
  }
}
__device__ __forceinline__ uint4 ldcg128(const void* p) { uint4 v; asm volatile("ld.global.cg.v4.b32 {%0,%1,%2,%3}, [%4];" : "=r"(v.x), "=r"(v.y), "=r"(v.z), "=r"(v.w) : "l"(p) : "memory"); return v; }
__device__ __forceinline__ uint4 ld_tagged(const uint4* p) { uint4 v; asm volatile("ld.relaxed.gpu.global.v4.u32 {%0,%1,%2,%3}, [%4];" : "=r"(v.x), "=r"(v.y), "=r"(v.z), "=r"(v.w) : "l"(p) : "memory"); return v; }
__device__ __forceinline__ uint2 ld_part(const uint2* p) { uint2 v; asm volatile("ld.relaxed.gpu.global.v2.u32 {%0,%1}, [%2];" : "=r"(v.x), "=r"(v.y) : "l"(p) : "memory"); return v; }
__device__ __forceinline__ void st_part(uint2* p, float s, float q, uint32_t tag) {
  if (PUB & 2) asm volatile("{\n.reg .b64 v, o;\nmov.b64 v, {%1,%2};\natom.relaxed.gpu.global.exch.b64 o, [%0], v;\n}" ::"l"(p), "r"(__float_as_uint(s)), "r"((__float_as_uint(q) & ~7u) | tag) : "memory");
  else asm volatile("st.relaxed.gpu.global.v2.u32 [%0], {%1,%2};" ::"l"(p), "r"(__float_as_uint(s)), "r"((__float_as_uint(q) & ~7u) | tag) : "memory");
}
__device__ __forceinline__ uint32_t part_tag(uint32_t epoch, int k) { return (4 * (epoch % 7) + k) % 7 + 1; }
__device__ __forceinline__ void st_tagged3(uint4* p, uint32_t a, uint32_t b, uint32_t c, uint32_t tag) { asm volatile("st.relaxed.gpu.global.v4.u32 [%0], {%1,%2,%3,%4};" ::"l"(p), "r"(a), "r"(b), "r"(c), "r"(tag) : "memory"); }
__device__ __forceinline__ uint32_t hadd2(uint32_t a, uint32_t b) { uint32_t r; asm("add.rn.bf16x2 %0, %1, %2;" : "=r"(r) : "r"(a), "r"(b)); return r; }
__device__ __forceinline__ uint32_t hfma2(uint32_t a, uint32_t b, uint32_t c) { uint32_t r; asm("fma.rn.bf16x2 %0, %1, %2, %3;" : "=r"(r) : "r"(a), "r"(b), "r"(c)); return r; }
__device__ __forceinline__ uint32_t hmul2(uint32_t a, uint32_t b) { uint32_t r; asm("mul.rn.bf16x2 %0, %1, %2;" : "=r"(r) : "r"(a), "r"(b)); return r; }

template<int N,int TB> __device__ __forceinline__ void wgmma_rs(float* d, const uint32_t* a, uint64_t db, int sd);
template<int N,int TA,int TB> __device__ __forceinline__ void wgmma_ss(float* d, uint64_t da, uint64_t db, int sd);
template<> __device__ __forceinline__ void wgmma_rs<128,0>(float* d, const uint32_t* a, uint64_t db, int sd) {
  asm volatile("{\n.reg .pred p;\nsetp.ne.b32 p, %69, 0;\nwgmma.mma_async.sync.aligned.m64n128k16.f32.bf16.bf16 {%0,%1,%2,%3,%4,%5,%6,%7,%8,%9,%10,%11,%12,%13,%14,%15,%16,%17,%18,%19,%20,%21,%22,%23,%24,%25,%26,%27,%28,%29,%30,%31,%32,%33,%34,%35,%36,%37,%38,%39,%40,%41,%42,%43,%44,%45,%46,%47,%48,%49,%50,%51,%52,%53,%54,%55,%56,%57,%58,%59,%60,%61,%62,%63}, {%64,%65,%66,%67}, %68, p, 1, 1, 0;\n}\n"
   : "+f"(d[0]),"+f"(d[1]),"+f"(d[2]),"+f"(d[3]),"+f"(d[4]),"+f"(d[5]),"+f"(d[6]),"+f"(d[7]),"+f"(d[8]),"+f"(d[9]),"+f"(d[10]),"+f"(d[11]),"+f"(d[12]),"+f"(d[13]),"+f"(d[14]),"+f"(d[15]),"+f"(d[16]),"+f"(d[17]),"+f"(d[18]),"+f"(d[19]),"+f"(d[20]),"+f"(d[21]),"+f"(d[22]),"+f"(d[23]),"+f"(d[24]),"+f"(d[25]),"+f"(d[26]),"+f"(d[27]),"+f"(d[28]),"+f"(d[29]),"+f"(d[30]),"+f"(d[31]),"+f"(d[32]),"+f"(d[33]),"+f"(d[34]),"+f"(d[35]),"+f"(d[36]),"+f"(d[37]),"+f"(d[38]),"+f"(d[39]),"+f"(d[40]),"+f"(d[41]),"+f"(d[42]),"+f"(d[43]),"+f"(d[44]),"+f"(d[45]),"+f"(d[46]),"+f"(d[47]),"+f"(d[48]),"+f"(d[49]),"+f"(d[50]),"+f"(d[51]),"+f"(d[52]),"+f"(d[53]),"+f"(d[54]),"+f"(d[55]),"+f"(d[56]),"+f"(d[57]),"+f"(d[58]),"+f"(d[59]),"+f"(d[60]),"+f"(d[61]),"+f"(d[62]),"+f"(d[63])
   : "r"(a[0]), "r"(a[1]), "r"(a[2]), "r"(a[3]), "l"(db), "r"(sd));
}
template<> __device__ __forceinline__ void wgmma_rs<120,0>(float* d, const uint32_t* a, uint64_t db, int sd) {
  asm volatile("{\n.reg .pred p;\nsetp.ne.b32 p, %65, 0;\nwgmma.mma_async.sync.aligned.m64n120k16.f32.bf16.bf16 {%0,%1,%2,%3,%4,%5,%6,%7,%8,%9,%10,%11,%12,%13,%14,%15,%16,%17,%18,%19,%20,%21,%22,%23,%24,%25,%26,%27,%28,%29,%30,%31,%32,%33,%34,%35,%36,%37,%38,%39,%40,%41,%42,%43,%44,%45,%46,%47,%48,%49,%50,%51,%52,%53,%54,%55,%56,%57,%58,%59}, {%60,%61,%62,%63}, %64, p, 1, 1, 0;\n}\n"
   : "+f"(d[0]),"+f"(d[1]),"+f"(d[2]),"+f"(d[3]),"+f"(d[4]),"+f"(d[5]),"+f"(d[6]),"+f"(d[7]),"+f"(d[8]),"+f"(d[9]),"+f"(d[10]),"+f"(d[11]),"+f"(d[12]),"+f"(d[13]),"+f"(d[14]),"+f"(d[15]),"+f"(d[16]),"+f"(d[17]),"+f"(d[18]),"+f"(d[19]),"+f"(d[20]),"+f"(d[21]),"+f"(d[22]),"+f"(d[23]),"+f"(d[24]),"+f"(d[25]),"+f"(d[26]),"+f"(d[27]),"+f"(d[28]),"+f"(d[29]),"+f"(d[30]),"+f"(d[31]),"+f"(d[32]),"+f"(d[33]),"+f"(d[34]),"+f"(d[35]),"+f"(d[36]),"+f"(d[37]),"+f"(d[38]),"+f"(d[39]),"+f"(d[40]),"+f"(d[41]),"+f"(d[42]),"+f"(d[43]),"+f"(d[44]),"+f"(d[45]),"+f"(d[46]),"+f"(d[47]),"+f"(d[48]),"+f"(d[49]),"+f"(d[50]),"+f"(d[51]),"+f"(d[52]),"+f"(d[53]),"+f"(d[54]),"+f"(d[55]),"+f"(d[56]),"+f"(d[57]),"+f"(d[58]),"+f"(d[59])
   : "r"(a[0]), "r"(a[1]), "r"(a[2]), "r"(a[3]), "l"(db), "r"(sd));
}
template<> __device__ __forceinline__ void wgmma_rs<112,0>(float* d, const uint32_t* a, uint64_t db, int sd) {
  asm volatile("{\n.reg .pred p;\nsetp.ne.b32 p, %61, 0;\nwgmma.mma_async.sync.aligned.m64n112k16.f32.bf16.bf16 {%0,%1,%2,%3,%4,%5,%6,%7,%8,%9,%10,%11,%12,%13,%14,%15,%16,%17,%18,%19,%20,%21,%22,%23,%24,%25,%26,%27,%28,%29,%30,%31,%32,%33,%34,%35,%36,%37,%38,%39,%40,%41,%42,%43,%44,%45,%46,%47,%48,%49,%50,%51,%52,%53,%54,%55}, {%56,%57,%58,%59}, %60, p, 1, 1, 0;\n}\n"
   : "+f"(d[0]),"+f"(d[1]),"+f"(d[2]),"+f"(d[3]),"+f"(d[4]),"+f"(d[5]),"+f"(d[6]),"+f"(d[7]),"+f"(d[8]),"+f"(d[9]),"+f"(d[10]),"+f"(d[11]),"+f"(d[12]),"+f"(d[13]),"+f"(d[14]),"+f"(d[15]),"+f"(d[16]),"+f"(d[17]),"+f"(d[18]),"+f"(d[19]),"+f"(d[20]),"+f"(d[21]),"+f"(d[22]),"+f"(d[23]),"+f"(d[24]),"+f"(d[25]),"+f"(d[26]),"+f"(d[27]),"+f"(d[28]),"+f"(d[29]),"+f"(d[30]),"+f"(d[31]),"+f"(d[32]),"+f"(d[33]),"+f"(d[34]),"+f"(d[35]),"+f"(d[36]),"+f"(d[37]),"+f"(d[38]),"+f"(d[39]),"+f"(d[40]),"+f"(d[41]),"+f"(d[42]),"+f"(d[43]),"+f"(d[44]),"+f"(d[45]),"+f"(d[46]),"+f"(d[47]),"+f"(d[48]),"+f"(d[49]),"+f"(d[50]),"+f"(d[51]),"+f"(d[52]),"+f"(d[53]),"+f"(d[54]),"+f"(d[55])
   : "r"(a[0]), "r"(a[1]), "r"(a[2]), "r"(a[3]), "l"(db), "r"(sd));
}
template<> __device__ __forceinline__ void wgmma_rs<104,0>(float* d, const uint32_t* a, uint64_t db, int sd) {
  asm volatile("{\n.reg .pred p;\nsetp.ne.b32 p, %57, 0;\nwgmma.mma_async.sync.aligned.m64n104k16.f32.bf16.bf16 {%0,%1,%2,%3,%4,%5,%6,%7,%8,%9,%10,%11,%12,%13,%14,%15,%16,%17,%18,%19,%20,%21,%22,%23,%24,%25,%26,%27,%28,%29,%30,%31,%32,%33,%34,%35,%36,%37,%38,%39,%40,%41,%42,%43,%44,%45,%46,%47,%48,%49,%50,%51}, {%52,%53,%54,%55}, %56, p, 1, 1, 0;\n}\n"
   : "+f"(d[0]),"+f"(d[1]),"+f"(d[2]),"+f"(d[3]),"+f"(d[4]),"+f"(d[5]),"+f"(d[6]),"+f"(d[7]),"+f"(d[8]),"+f"(d[9]),"+f"(d[10]),"+f"(d[11]),"+f"(d[12]),"+f"(d[13]),"+f"(d[14]),"+f"(d[15]),"+f"(d[16]),"+f"(d[17]),"+f"(d[18]),"+f"(d[19]),"+f"(d[20]),"+f"(d[21]),"+f"(d[22]),"+f"(d[23]),"+f"(d[24]),"+f"(d[25]),"+f"(d[26]),"+f"(d[27]),"+f"(d[28]),"+f"(d[29]),"+f"(d[30]),"+f"(d[31]),"+f"(d[32]),"+f"(d[33]),"+f"(d[34]),"+f"(d[35]),"+f"(d[36]),"+f"(d[37]),"+f"(d[38]),"+f"(d[39]),"+f"(d[40]),"+f"(d[41]),"+f"(d[42]),"+f"(d[43]),"+f"(d[44]),"+f"(d[45]),"+f"(d[46]),"+f"(d[47]),"+f"(d[48]),"+f"(d[49]),"+f"(d[50]),"+f"(d[51])
   : "r"(a[0]), "r"(a[1]), "r"(a[2]), "r"(a[3]), "l"(db), "r"(sd));
}
template<> __device__ __forceinline__ void wgmma_rs<96,0>(float* d, const uint32_t* a, uint64_t db, int sd) {
  asm volatile("{\n.reg .pred p;\nsetp.ne.b32 p, %53, 0;\nwgmma.mma_async.sync.aligned.m64n96k16.f32.bf16.bf16 {%0,%1,%2,%3,%4,%5,%6,%7,%8,%9,%10,%11,%12,%13,%14,%15,%16,%17,%18,%19,%20,%21,%22,%23,%24,%25,%26,%27,%28,%29,%30,%31,%32,%33,%34,%35,%36,%37,%38,%39,%40,%41,%42,%43,%44,%45,%46,%47}, {%48,%49,%50,%51}, %52, p, 1, 1, 0;\n}\n"
   : "+f"(d[0]),"+f"(d[1]),"+f"(d[2]),"+f"(d[3]),"+f"(d[4]),"+f"(d[5]),"+f"(d[6]),"+f"(d[7]),"+f"(d[8]),"+f"(d[9]),"+f"(d[10]),"+f"(d[11]),"+f"(d[12]),"+f"(d[13]),"+f"(d[14]),"+f"(d[15]),"+f"(d[16]),"+f"(d[17]),"+f"(d[18]),"+f"(d[19]),"+f"(d[20]),"+f"(d[21]),"+f"(d[22]),"+f"(d[23]),"+f"(d[24]),"+f"(d[25]),"+f"(d[26]),"+f"(d[27]),"+f"(d[28]),"+f"(d[29]),"+f"(d[30]),"+f"(d[31]),"+f"(d[32]),"+f"(d[33]),"+f"(d[34]),"+f"(d[35]),"+f"(d[36]),"+f"(d[37]),"+f"(d[38]),"+f"(d[39]),"+f"(d[40]),"+f"(d[41]),"+f"(d[42]),"+f"(d[43]),"+f"(d[44]),"+f"(d[45]),"+f"(d[46]),"+f"(d[47])
   : "r"(a[0]), "r"(a[1]), "r"(a[2]), "r"(a[3]), "l"(db), "r"(sd));
}
template<> __device__ __forceinline__ void wgmma_rs<88,0>(float* d, const uint32_t* a, uint64_t db, int sd) {
  asm volatile("{\n.reg .pred p;\nsetp.ne.b32 p, %49, 0;\nwgmma.mma_async.sync.aligned.m64n88k16.f32.bf16.bf16 {%0,%1,%2,%3,%4,%5,%6,%7,%8,%9,%10,%11,%12,%13,%14,%15,%16,%17,%18,%19,%20,%21,%22,%23,%24,%25,%26,%27,%28,%29,%30,%31,%32,%33,%34,%35,%36,%37,%38,%39,%40,%41,%42,%43}, {%44,%45,%46,%47}, %48, p, 1, 1, 0;\n}\n"
   : "+f"(d[0]),"+f"(d[1]),"+f"(d[2]),"+f"(d[3]),"+f"(d[4]),"+f"(d[5]),"+f"(d[6]),"+f"(d[7]),"+f"(d[8]),"+f"(d[9]),"+f"(d[10]),"+f"(d[11]),"+f"(d[12]),"+f"(d[13]),"+f"(d[14]),"+f"(d[15]),"+f"(d[16]),"+f"(d[17]),"+f"(d[18]),"+f"(d[19]),"+f"(d[20]),"+f"(d[21]),"+f"(d[22]),"+f"(d[23]),"+f"(d[24]),"+f"(d[25]),"+f"(d[26]),"+f"(d[27]),"+f"(d[28]),"+f"(d[29]),"+f"(d[30]),"+f"(d[31]),"+f"(d[32]),"+f"(d[33]),"+f"(d[34]),"+f"(d[35]),"+f"(d[36]),"+f"(d[37]),"+f"(d[38]),"+f"(d[39]),"+f"(d[40]),"+f"(d[41]),"+f"(d[42]),"+f"(d[43])
   : "r"(a[0]), "r"(a[1]), "r"(a[2]), "r"(a[3]), "l"(db), "r"(sd));
}
template<> __device__ __forceinline__ void wgmma_rs<80,0>(float* d, const uint32_t* a, uint64_t db, int sd) {
  asm volatile("{\n.reg .pred p;\nsetp.ne.b32 p, %45, 0;\nwgmma.mma_async.sync.aligned.m64n80k16.f32.bf16.bf16 {%0,%1,%2,%3,%4,%5,%6,%7,%8,%9,%10,%11,%12,%13,%14,%15,%16,%17,%18,%19,%20,%21,%22,%23,%24,%25,%26,%27,%28,%29,%30,%31,%32,%33,%34,%35,%36,%37,%38,%39}, {%40,%41,%42,%43}, %44, p, 1, 1, 0;\n}\n"
   : "+f"(d[0]),"+f"(d[1]),"+f"(d[2]),"+f"(d[3]),"+f"(d[4]),"+f"(d[5]),"+f"(d[6]),"+f"(d[7]),"+f"(d[8]),"+f"(d[9]),"+f"(d[10]),"+f"(d[11]),"+f"(d[12]),"+f"(d[13]),"+f"(d[14]),"+f"(d[15]),"+f"(d[16]),"+f"(d[17]),"+f"(d[18]),"+f"(d[19]),"+f"(d[20]),"+f"(d[21]),"+f"(d[22]),"+f"(d[23]),"+f"(d[24]),"+f"(d[25]),"+f"(d[26]),"+f"(d[27]),"+f"(d[28]),"+f"(d[29]),"+f"(d[30]),"+f"(d[31]),"+f"(d[32]),"+f"(d[33]),"+f"(d[34]),"+f"(d[35]),"+f"(d[36]),"+f"(d[37]),"+f"(d[38]),"+f"(d[39])
   : "r"(a[0]), "r"(a[1]), "r"(a[2]), "r"(a[3]), "l"(db), "r"(sd));
}
template<> __device__ __forceinline__ void wgmma_rs<72,0>(float* d, const uint32_t* a, uint64_t db, int sd) {
  asm volatile("{\n.reg .pred p;\nsetp.ne.b32 p, %41, 0;\nwgmma.mma_async.sync.aligned.m64n72k16.f32.bf16.bf16 {%0,%1,%2,%3,%4,%5,%6,%7,%8,%9,%10,%11,%12,%13,%14,%15,%16,%17,%18,%19,%20,%21,%22,%23,%24,%25,%26,%27,%28,%29,%30,%31,%32,%33,%34,%35}, {%36,%37,%38,%39}, %40, p, 1, 1, 0;\n}\n"
   : "+f"(d[0]),"+f"(d[1]),"+f"(d[2]),"+f"(d[3]),"+f"(d[4]),"+f"(d[5]),"+f"(d[6]),"+f"(d[7]),"+f"(d[8]),"+f"(d[9]),"+f"(d[10]),"+f"(d[11]),"+f"(d[12]),"+f"(d[13]),"+f"(d[14]),"+f"(d[15]),"+f"(d[16]),"+f"(d[17]),"+f"(d[18]),"+f"(d[19]),"+f"(d[20]),"+f"(d[21]),"+f"(d[22]),"+f"(d[23]),"+f"(d[24]),"+f"(d[25]),"+f"(d[26]),"+f"(d[27]),"+f"(d[28]),"+f"(d[29]),"+f"(d[30]),"+f"(d[31]),"+f"(d[32]),"+f"(d[33]),"+f"(d[34]),"+f"(d[35])
   : "r"(a[0]), "r"(a[1]), "r"(a[2]), "r"(a[3]), "l"(db), "r"(sd));
}
template<> __device__ __forceinline__ void wgmma_rs<64,0>(float* d, const uint32_t* a, uint64_t db, int sd) {
  asm volatile("{\n.reg .pred p;\nsetp.ne.b32 p, %37, 0;\nwgmma.mma_async.sync.aligned.m64n64k16.f32.bf16.bf16 {%0,%1,%2,%3,%4,%5,%6,%7,%8,%9,%10,%11,%12,%13,%14,%15,%16,%17,%18,%19,%20,%21,%22,%23,%24,%25,%26,%27,%28,%29,%30,%31}, {%32,%33,%34,%35}, %36, p, 1, 1, 0;\n}\n"
   : "+f"(d[0]),"+f"(d[1]),"+f"(d[2]),"+f"(d[3]),"+f"(d[4]),"+f"(d[5]),"+f"(d[6]),"+f"(d[7]),"+f"(d[8]),"+f"(d[9]),"+f"(d[10]),"+f"(d[11]),"+f"(d[12]),"+f"(d[13]),"+f"(d[14]),"+f"(d[15]),"+f"(d[16]),"+f"(d[17]),"+f"(d[18]),"+f"(d[19]),"+f"(d[20]),"+f"(d[21]),"+f"(d[22]),"+f"(d[23]),"+f"(d[24]),"+f"(d[25]),"+f"(d[26]),"+f"(d[27]),"+f"(d[28]),"+f"(d[29]),"+f"(d[30]),"+f"(d[31])
   : "r"(a[0]), "r"(a[1]), "r"(a[2]), "r"(a[3]), "l"(db), "r"(sd));
}
template<> __device__ __forceinline__ void wgmma_ss<64,0,1>(float* d, uint64_t da, uint64_t db, int sd) {
  asm volatile("{\n.reg .pred p;\nsetp.ne.b32 p, %34, 0;\nwgmma.mma_async.sync.aligned.m64n64k16.f32.bf16.bf16 {%0,%1,%2,%3,%4,%5,%6,%7,%8,%9,%10,%11,%12,%13,%14,%15,%16,%17,%18,%19,%20,%21,%22,%23,%24,%25,%26,%27,%28,%29,%30,%31}, %32, %33, p, 1, 1, 0, 1;\n}\n"
   : "+f"(d[0]),"+f"(d[1]),"+f"(d[2]),"+f"(d[3]),"+f"(d[4]),"+f"(d[5]),"+f"(d[6]),"+f"(d[7]),"+f"(d[8]),"+f"(d[9]),"+f"(d[10]),"+f"(d[11]),"+f"(d[12]),"+f"(d[13]),"+f"(d[14]),"+f"(d[15]),"+f"(d[16]),"+f"(d[17]),"+f"(d[18]),"+f"(d[19]),"+f"(d[20]),"+f"(d[21]),"+f"(d[22]),"+f"(d[23]),"+f"(d[24]),"+f"(d[25]),"+f"(d[26]),"+f"(d[27]),"+f"(d[28]),"+f"(d[29]),"+f"(d[30]),"+f"(d[31])
   : "l"(da), "l"(db), "r"(sd));
}
template<> __device__ __forceinline__ void wgmma_ss<64,1,1>(float* d, uint64_t da, uint64_t db, int sd) {
  asm volatile("{\n.reg .pred p;\nsetp.ne.b32 p, %34, 0;\nwgmma.mma_async.sync.aligned.m64n64k16.f32.bf16.bf16 {%0,%1,%2,%3,%4,%5,%6,%7,%8,%9,%10,%11,%12,%13,%14,%15,%16,%17,%18,%19,%20,%21,%22,%23,%24,%25,%26,%27,%28,%29,%30,%31}, %32, %33, p, 1, 1, 1, 1;\n}\n"
   : "+f"(d[0]),"+f"(d[1]),"+f"(d[2]),"+f"(d[3]),"+f"(d[4]),"+f"(d[5]),"+f"(d[6]),"+f"(d[7]),"+f"(d[8]),"+f"(d[9]),"+f"(d[10]),"+f"(d[11]),"+f"(d[12]),"+f"(d[13]),"+f"(d[14]),"+f"(d[15]),"+f"(d[16]),"+f"(d[17]),"+f"(d[18]),"+f"(d[19]),"+f"(d[20]),"+f"(d[21]),"+f"(d[22]),"+f"(d[23]),"+f"(d[24]),"+f"(d[25]),"+f"(d[26]),"+f"(d[27]),"+f"(d[28]),"+f"(d[29]),"+f"(d[30]),"+f"(d[31])
   : "l"(da), "l"(db), "r"(sd));
}
template<> __device__ __forceinline__ void wgmma_ss<192,0,1>(float* d, uint64_t da, uint64_t db, int sd) {
  asm volatile("{\n.reg .pred p;\nsetp.ne.b32 p, %98, 0;\nwgmma.mma_async.sync.aligned.m64n192k16.f32.bf16.bf16 {%0,%1,%2,%3,%4,%5,%6,%7,%8,%9,%10,%11,%12,%13,%14,%15,%16,%17,%18,%19,%20,%21,%22,%23,%24,%25,%26,%27,%28,%29,%30,%31,%32,%33,%34,%35,%36,%37,%38,%39,%40,%41,%42,%43,%44,%45,%46,%47,%48,%49,%50,%51,%52,%53,%54,%55,%56,%57,%58,%59,%60,%61,%62,%63,%64,%65,%66,%67,%68,%69,%70,%71,%72,%73,%74,%75,%76,%77,%78,%79,%80,%81,%82,%83,%84,%85,%86,%87,%88,%89,%90,%91,%92,%93,%94,%95}, %96, %97, p, 1, 1, 0, 1;\n}\n"
   : "+f"(d[0]),"+f"(d[1]),"+f"(d[2]),"+f"(d[3]),"+f"(d[4]),"+f"(d[5]),"+f"(d[6]),"+f"(d[7]),"+f"(d[8]),"+f"(d[9]),"+f"(d[10]),"+f"(d[11]),"+f"(d[12]),"+f"(d[13]),"+f"(d[14]),"+f"(d[15]),"+f"(d[16]),"+f"(d[17]),"+f"(d[18]),"+f"(d[19]),"+f"(d[20]),"+f"(d[21]),"+f"(d[22]),"+f"(d[23]),"+f"(d[24]),"+f"(d[25]),"+f"(d[26]),"+f"(d[27]),"+f"(d[28]),"+f"(d[29]),"+f"(d[30]),"+f"(d[31]),"+f"(d[32]),"+f"(d[33]),"+f"(d[34]),"+f"(d[35]),"+f"(d[36]),"+f"(d[37]),"+f"(d[38]),"+f"(d[39]),"+f"(d[40]),"+f"(d[41]),"+f"(d[42]),"+f"(d[43]),"+f"(d[44]),"+f"(d[45]),"+f"(d[46]),"+f"(d[47]),"+f"(d[48]),"+f"(d[49]),"+f"(d[50]),"+f"(d[51]),"+f"(d[52]),"+f"(d[53]),"+f"(d[54]),"+f"(d[55]),"+f"(d[56]),"+f"(d[57]),"+f"(d[58]),"+f"(d[59]),"+f"(d[60]),"+f"(d[61]),"+f"(d[62]),"+f"(d[63]),"+f"(d[64]),"+f"(d[65]),"+f"(d[66]),"+f"(d[67]),"+f"(d[68]),"+f"(d[69]),"+f"(d[70]),"+f"(d[71]),"+f"(d[72]),"+f"(d[73]),"+f"(d[74]),"+f"(d[75]),"+f"(d[76]),"+f"(d[77]),"+f"(d[78]),"+f"(d[79]),"+f"(d[80]),"+f"(d[81]),"+f"(d[82]),"+f"(d[83]),"+f"(d[84]),"+f"(d[85]),"+f"(d[86]),"+f"(d[87]),"+f"(d[88]),"+f"(d[89]),"+f"(d[90]),"+f"(d[91]),"+f"(d[92]),"+f"(d[93]),"+f"(d[94]),"+f"(d[95])
   : "l"(da), "l"(db), "r"(sd));
}
template<> __device__ __forceinline__ void wgmma_ss<192,1,1>(float* d, uint64_t da, uint64_t db, int sd) {
  asm volatile("{\n.reg .pred p;\nsetp.ne.b32 p, %98, 0;\nwgmma.mma_async.sync.aligned.m64n192k16.f32.bf16.bf16 {%0,%1,%2,%3,%4,%5,%6,%7,%8,%9,%10,%11,%12,%13,%14,%15,%16,%17,%18,%19,%20,%21,%22,%23,%24,%25,%26,%27,%28,%29,%30,%31,%32,%33,%34,%35,%36,%37,%38,%39,%40,%41,%42,%43,%44,%45,%46,%47,%48,%49,%50,%51,%52,%53,%54,%55,%56,%57,%58,%59,%60,%61,%62,%63,%64,%65,%66,%67,%68,%69,%70,%71,%72,%73,%74,%75,%76,%77,%78,%79,%80,%81,%82,%83,%84,%85,%86,%87,%88,%89,%90,%91,%92,%93,%94,%95}, %96, %97, p, 1, 1, 1, 1;\n}\n"
   : "+f"(d[0]),"+f"(d[1]),"+f"(d[2]),"+f"(d[3]),"+f"(d[4]),"+f"(d[5]),"+f"(d[6]),"+f"(d[7]),"+f"(d[8]),"+f"(d[9]),"+f"(d[10]),"+f"(d[11]),"+f"(d[12]),"+f"(d[13]),"+f"(d[14]),"+f"(d[15]),"+f"(d[16]),"+f"(d[17]),"+f"(d[18]),"+f"(d[19]),"+f"(d[20]),"+f"(d[21]),"+f"(d[22]),"+f"(d[23]),"+f"(d[24]),"+f"(d[25]),"+f"(d[26]),"+f"(d[27]),"+f"(d[28]),"+f"(d[29]),"+f"(d[30]),"+f"(d[31]),"+f"(d[32]),"+f"(d[33]),"+f"(d[34]),"+f"(d[35]),"+f"(d[36]),"+f"(d[37]),"+f"(d[38]),"+f"(d[39]),"+f"(d[40]),"+f"(d[41]),"+f"(d[42]),"+f"(d[43]),"+f"(d[44]),"+f"(d[45]),"+f"(d[46]),"+f"(d[47]),"+f"(d[48]),"+f"(d[49]),"+f"(d[50]),"+f"(d[51]),"+f"(d[52]),"+f"(d[53]),"+f"(d[54]),"+f"(d[55]),"+f"(d[56]),"+f"(d[57]),"+f"(d[58]),"+f"(d[59]),"+f"(d[60]),"+f"(d[61]),"+f"(d[62]),"+f"(d[63]),"+f"(d[64]),"+f"(d[65]),"+f"(d[66]),"+f"(d[67]),"+f"(d[68]),"+f"(d[69]),"+f"(d[70]),"+f"(d[71]),"+f"(d[72]),"+f"(d[73]),"+f"(d[74]),"+f"(d[75]),"+f"(d[76]),"+f"(d[77]),"+f"(d[78]),"+f"(d[79]),"+f"(d[80]),"+f"(d[81]),"+f"(d[82]),"+f"(d[83]),"+f"(d[84]),"+f"(d[85]),"+f"(d[86]),"+f"(d[87]),"+f"(d[88]),"+f"(d[89]),"+f"(d[90]),"+f"(d[91]),"+f"(d[92]),"+f"(d[93]),"+f"(d[94]),"+f"(d[95])
   : "l"(da), "l"(db), "r"(sd));
}

__device__ __forceinline__ void stats_publish(uint32_t sb, int layer, int rb, int hg, int ht, uint32_t tag) {
  const int lane = ht & 31, w = ht >> 5, g = lane >> 2, t = lane & 3, ks = hg & 3;
  uint32_t xa;
  if (layer == 0) {
    const int row = 16 * w + (lane & 15), kc = 2 * ks + (lane >> 4);
    xa = row * 128 + ((kc ^ (row & 7)) << 4);
  } else {
    const int k = 16 * ks + (lane & 7) + 8 * (lane >> 4), pc = 2 * w + ((lane >> 3) & 1);
    xa = k * 128 + ((pc ^ (k & 7)) << 4);
  }
  float s[4] = {0.f, 0.f, 0.f, 0.f}, q[4] = {0.f, 0.f, 0.f, 0.f};
#pragma unroll 1
  for (int c = hg >> 2; c < 8; c += 2) {
    uint32_t A[2][4];
    mbar_wait(sb + SM_BAR + 8 * (B_XF + c), layer);
#pragma unroll
    for (int h = 0; h < 2; h++) {
      if (layer == 0) ldsm4(A[h], sb + SM_X + c * 16384 + h * 8192 + xa);
      else ldsm4t(A[h], sb + SM_X + c * 16384 + h * 8192 + xa);
    }
    if (c >= 6) ATS(48, 256);
    if (c < 2) ATS(51, 256);
#pragma unroll
    for (int r = 0; r < 4; r++)
#pragma unroll
      for (int i = 0; i < 2; i++) {
        const uint32_t v = A[r >> 1][2 * i + (r & 1)];
        const float a = bf_lo(v), b = bf_hi(v);
        s[r] += a + b; q[r] = fmaf(a, a, q[r]); q[r] = fmaf(b, b, q[r]);
      }
  }
#pragma unroll
  for (int r = 0; r < 2; r++) {
    s[r] = ((t & 2) ? s[r + 2] : s[r]) + __shfl_xor_sync(~0u, (t & 2) ? s[r] : s[r + 2], 2);
    q[r] = ((t & 2) ? q[r + 2] : q[r]) + __shfl_xor_sync(~0u, (t & 2) ? q[r] : q[r + 2], 2);
  }
  s[0] = ((t & 1) ? s[1] : s[0]) + __shfl_xor_sync(~0u, (t & 1) ? s[0] : s[1], 1);
  q[0] = ((t & 1) ? q[1] : q[0]) + __shfl_xor_sync(~0u, (t & 1) ? q[0] : q[1], 1);
  st_part(&g_part[(rb * 8 + hg) * 128 + 64 * (t >> 1) + 16 * w + 8 * (t & 1) + g], s[0], q[0], tag);
  ATS(49, 256);
}
__device__ __forceinline__ void stats_gather(uint32_t sb, int rb, int ht, uint32_t tag) {
  const uint2* src = &g_part[rb * 8 * 128 + ht];
  uint2 v[8];
  for (int it = 0;; it++) {
    uint32_t bad = 0;
#pragma unroll
    for (int i = 0; i < 8; i++) v[i] = ld_part(src + i * 128);
#pragma unroll
    for (int i = 0; i < 8; i++) bad |= v[i].y ^ tag;
    if (__all_sync(~0u, (bad & 7u) == 0)) break;
    if (it > (1 << 22)) __trap();
  }
  float s = 0.f, q = 0.f;
#pragma unroll
  for (int i = 0; i < 8; i++) { s += __uint_as_float(v[i].x); q += __uint_as_float(v[i].y); }
  const float mean = s * (1.f / DM);
  const float rstd = rsqrt_approx(fmaxf(q * (1.f / DM) - mean * mean, 0.f) + 1e-5f);
  asm volatile("st.shared.v2.f32 [%0], {%1,%2};" ::"r"(sb + SM_ST + ht * 8), "f"(mean), "f"(rstd) : "memory");
  __syncwarp();
  if (elect_one()) mbar_arrive(sb + SM_BAR + 8 * B_STF);
}
__device__ __forceinline__ void halo_receive(uint32_t sb, int layer, int rb, int hg, int ht) {
  const int lane = ht & 31, h = ht >> 5;
  uint4 kv = make_uint4(0, 0, 0, 0);
  mbar_wait(sb + SM_BAR + 8 * B_SD, layer);
  if (rb & 7) {
    const uint32_t tag = 2 * lds32(sb + SM_EP) + layer + 1;
    const uint4* src = &g_halo[((rb - 1) * 8 + hg) * 192 + h * 48];
    if (layer == 0) delay<D_HALO>(); else delay<D_HALO1>();
    uint4 a;
    uint2 b;
    int it = 0;
    do {
      a = ld_tagged(src + lane); b = ld_part((const uint2*)(src + 32) + lane);
      if (++it > (1 << 22)) __trap();
    } while (!__all_sync(~0u, a.w == tag && b.y == tag));
    kv = make_uint4(a.x, a.y, movm_t(a.z), movm_t(b.x));
  }
  sts128(sb + SM_KVX + h * 512 + lane * 16, kv);
  ATS(61, 256);
  bar_arrive(7, 160);
  if (elect_one()) mbar_arrive(sb + SM_BAR + 8 * B_HF);
}

__device__ __forceinline__ void halo_receive1(uint32_t sb, int layer, int rb, int hg, int lane, uint32_t tag) {
  uint4 a[4];
  uint2 b[4];
  mbar_wait(sb + SM_BAR + 8 * B_SD, layer);
  if (rb & 7) {
    const uint4* src = &g_halo[((rb - 1) * 8 + hg) * 192];
    if (layer == 0) delay<D_HALO>(); else delay<D_HALO1>();
    for (int it = 0;; it++) {
      uint32_t bad = 0;
#pragma unroll
      for (int h = 0; h < 4; h++) { a[h] = ld_tagged(src + h * 48 + lane); b[h] = ld_part((const uint2*)(src + h * 48 + 32) + lane); }
#pragma unroll
      for (int h = 0; h < 4; h++) {
        bad |= (a[h].w ^ tag) | (b[h].y ^ tag);
        a[h].z = movm_t(a[h].z); a[h].w = movm_t(b[h].x);
      }
      if (__all_sync(~0u, bad == 0)) break;
      if (it > (1 << 22)) __trap();
    }
  } else {
#pragma unroll
    for (int h = 0; h < 4; h++) a[h] = make_uint4(0, 0, 0, 0);
  }
#pragma unroll
  for (int h = 0; h < 4; h++) sts128(sb + SM_KVX + h * 512 + lane * 16, a[h]);
  ATS(61, 448);
  bar_arrive(7, 64);
  if (lane < 4) mbar_arrive(sb + SM_BAR + 8 * B_HF);
}

template <bool TR>
__device__ __forceinline__ void gemm_section(float* acc, float2* cs, uint32_t sb, int layer, int wg, int w, int lane) {
  const uint32_t bar = sb + SM_BAR;
  const bool leader = (w == 0) && (lane == 0);
  auto issue = [&](int c, int slot) {
    mbar_wait(bar + 8 * (B_XF + c), layer);
    mbar_wait(bar + 8 * (B_KVF + c), layer);
    const uint64_t da = mkdesc(sb + SM_X + c * 16384 + wg * 8192, TR ? 8192 : 16, 1024, 1);
    const uint64_t db = mkdesc(sb + SM_W + slot * 24576, 8192, 1024, 1);
    wg_fence();
#pragma unroll
    for (int ks = 0; ks < 4; ks++) wgmma_ss<192, TR ? 1 : 0, 1>(acc, da + (TR ? ks * 128 : ks * 2), db + ks * 128, (c | ks) != 0);
    wg_commit();
  };
  auto step = [&](int c, int slot) {
    issue(c, slot);
    wg_wait<1>();
    if (leader) mbar_arrive(bar + 8 * (B_KVE + c - 1));
  };
  if (!TR) bar_sync(0, NTHREADS);
  if (TR && G_WAIT == 3 && wg == 1) bar_sync(14, 256);
  if (TR && G_WAIT == 4 && wg == 1) mbar_wait(bar + 8 * (B_P + 3), 0);
  issue(0, 0);
  if (threadIdx.x == 0) TS(2 + layer * 20 + 0);
  if (threadIdx.x == 128 && layer == 1) TS(60);
  auto ld_cs = [&](int j0) {
#pragma unroll
    for (int j = j0; j < j0 + 8; j++) cs[j] = lds64f(sb + SM_CS + 4 * (8 * j + 2 * (lane & 3)));
  };
  if (TR && CS_STEP == 0) ld_cs(8);
  step(1, 1);
  if (TR && CS_STEP == 0) ld_cs(16);
  if (TR && CS_STEP == 1) ld_cs(8);
  step(2, 2);
  if (TR && CS_STEP == 1) ld_cs(16);
  if (TR && CS_STEP == 2) ld_cs(8);
  step(3, 0);
  if (TR && CS_STEP == 2) ld_cs(16);
  step(4, 1);
  if ((TR ? STAG1 : STAG0) == 3) {
    if (wg == 0) {
      wg_wait<0>();
      if (leader) mbar_arrive(bar + 8 * (B_KVE + 4));
      bar_sync(5, 256);
    }
    issue(5, 2);
    wg_wait<1>();
    if (leader && wg == 1) mbar_arrive(bar + 8 * (B_KVE + 4));
    if (!TR && !CS_LATE0) { mbar_wait(bar + 8 * B_CSF, 0); ld_cs(8); ld_cs(16); }
  } else {
    step(5, 2);
    if (!TR && !CS_LATE0) { mbar_wait(bar + 8 * B_CSF, 0); ld_cs(8); ld_cs(16); }
    if (wg == 0) bar_sync(5, 256);
  }
  issue(6, 0);
  issue(7, 1);
  if (wg == 1) bar_arrive(5, 256);
  if (!TR && CS_LATE0) { mbar_wait(bar + 8 * B_CSF, 0); ld_cs(8); ld_cs(16); }
}

__device__ __forceinline__ void attn_phase(const Params& p, uint32_t sb, int layer, int rb, int hg, int wg, int w) {
  const int lane = opaque_tid() & 31;
  const int g = lane >> 2, t = lane & 3;
  const uint32_t bar = sb + SM_BAR;
  const int row0 = 64 * wg + 16 * w;
  const bool leader = (w == 0) && (lane == 0);
  float acc[96];
  float2 cs[24];
  if (layer) gemm_section<true>(acc, cs, sb, layer, wg, w, lane);
  else gemm_section<false>(acc, cs, sb, layer, wg, w, lane);
  ATS(41, 224);
  mbar_wait(bar + 8 * B_STF, layer);
  const uint32_t tag = 2 * lds32(sb + SM_EP) + layer + 1;
  const float2 st0 = lds64f(sb + SM_ST + (row0 + g) * 8), st1 = lds64f(sb + SM_ST + (row0 + g + 8) * 8);
  const float mean0 = st0.x, rstd0 = st0.y, mean1 = st1.x, rstd1 = st1.y;
  wg_wait<0>();
  if (threadIdx.x == 0) TS(2 + layer * 20 + 1);
  ATS(39, 224);
  if (leader) mbar_arrive(bar + 8 * B_QDONE);

  uint32_t fp[4][4], fl[4][4], fh[4][4], qa[4][4];
  const int cw = 4 * wg + w;
  {
    const float nm0 = -mean0 * rstd0, nm1 = -mean1 * rstd1;
    const uint32_t kvx = sb + SM_KVX + cw * 2048 + lane * 16;
#pragma unroll
    for (int h = 0; h < 4; h++)
#pragma unroll
      for (int k = 0; k < 4; k++) {
        const int j = 8 + (k >> 1) * 8 + 2 * h + (k & 1);
        fh[h][k] = packbf(fmaf(acc[4 * j + 2], rstd1, nm1 * cs[j].x), fmaf(acc[4 * j + 3], rstd1, nm1 * cs[j].y));
      }
    if (cw == 7) {
      uint4* halo = &g_halo[(rb * 8 + hg) * 192];
#pragma unroll
      for (int h = 0; h < 4; h++) {
        st_tagged3(halo + h * 48 + lane, fh[h][0], fh[h][1], fh[h][2], tag);
        asm volatile("st.relaxed.gpu.global.v2.u32 [%0], {%1,%2};" ::"l"((uint2*)(halo + h * 48 + 32) + lane), "r"(fh[h][3]), "r"(tag) : "memory");
      }
      if (elect_one()) mbar_arrive(bar + 8 * B_SD);
      if (layer == TLAYER && threadIdx.x == 224) TS(47);
    }
#pragma unroll
    for (int h = 0; h < 4; h++) { fh[h][2] = movm_t(fh[h][2]); fh[h][3] = movm_t(fh[h][3]); }
    if (cw != 7) {
#pragma unroll
      for (int h = 0; h < 4; h++) sts128(kvx + 2048 + h * 512, make_uint4(fh[h][0], fh[h][1], fh[h][2], fh[h][3]));
      bar_arrive(8 + cw, 64);
    }
    sched_fence<6>();
    if (layer == TLAYER && threadIdx.x == 0) TS(45);
#pragma unroll
    for (int j = 0; j < 8; j++) cs[j] = lds64f(sb + SM_CS + 4 * (8 * j + 2 * t));
#pragma unroll
    for (int h = 0; h < 4; h++)
#pragma unroll
      for (int k = 0; k < 4; k++) {
        const int j = 8 + (k >> 1) * 8 + 2 * h + (k & 1);
        fl[h][k] = packbf(fmaf(acc[4 * j], rstd0, nm0 * cs[j].x), fmaf(acc[4 * j + 1], rstd0, nm0 * cs[j].y));
        if (k >= 2) fl[h][k] = movm_t(fl[h][k]);
      }
#pragma unroll
    for (int h = 0; h < 4; h++) {
#pragma unroll
      for (int dh = 0; dh < 2; dh++) {
        const int j = 2 * h + dh;
        const float2 c2 = cs[j];
        qa[h][2 * dh] = packbf(fmaf(-mean0, c2.x, acc[4 * j + 0]), fmaf(-mean0, c2.y, acc[4 * j + 1]));
        qa[h][2 * dh + 1] = packbf(fmaf(-mean1, c2.x, acc[4 * j + 2]), fmaf(-mean1, c2.y, acc[4 * j + 3]));
      }
    }
    if (threadIdx.x == 0) TS(2 + layer * 20 + 2);
    if (QD_AT == 1 || (QD_AT == 3 && wg == 0)) mbar_wait(bar + 8 * B_QDONE, layer);
    sched_fence<0>();
    bar_sync(7 + cw, cw == 0 && !HALO_W14 ? 160 : 64);
#pragma unroll
    for (int h = 0; h < 4; h++) {
      const uint4 v = lds128(kvx + h * 512);
      fp[h][0] = v.x; fp[h][1] = v.y; fp[h][2] = v.z; fp[h][3] = v.w;
    }
    if (threadIdx.x == 0) TS(2 + layer * 20 + 4);
  }

  const bool u0 = 2 * t > g, u1 = 2 * t + 1 > g;
  const uint32_t mU = (u0 ? 0x0000ffffu : 0u) | (u1 ? 0xffff0000u : 0u);
  const float cl2 = 0.25f * 1.4426950408889634f;
  const float sc0 = rstd0 * cl2, sc1 = rstd1 * cl2;
  const float cneg = ((rb & 7) == 0 && cw == 0) ? -INFINITY : 0.f;
  float v[4][4];
#pragma unroll
  for (int h = 0; h < 4; h++) {
    float T0[4] = {cneg, cneg, cneg, cneg}, T1[4] = {0.f, 0.f, 0.f, 0.f}, T2[4] = {0.f, 0.f, 0.f, 0.f};
    mma_bf16(T1, qa[h], fl[h][0], fl[h][1]);
    mma_bf16(T2, qa[h], fh[h][0], fh[h][1]);
    mma_bf16(T0, qa[h], fp[h][0], fp[h][1]);
    v[h][0] = u0 ? T0[0] : T1[0]; v[h][1] = u1 ? T0[1] : T1[1];
    v[h][2] = u0 ? T1[2] : T2[2]; v[h][3] = u1 ? T1[3] : T2[3];
  }
  float m0[4], m1[4];
#pragma unroll
  for (int h = 0; h < 4; h++) { m0[h] = fmaxf(v[h][0], v[h][1]); m1[h] = fmaxf(v[h][2], v[h][3]); }
#pragma unroll
  for (int o = 1; o <= 2; o <<= 1) {
#pragma unroll
    for (int h = 0; h < 4; h++) {
      m0[h] = fmaxf(m0[h], __shfl_xor_sync(~0u, m0[h], o));
      m1[h] = fmaxf(m1[h], __shfl_xor_sync(~0u, m1[h], o));
    }
  }
  float O0[4][4], O1[4][4], Z[4][4];
#pragma unroll
  for (int h = 0; h < 4; h++) {
    const float mm0 = -m0[h] * sc0, mm1 = -m1[h] * sc1;
    const uint32_t P0 = packbf(ex2(fmaf(v[h][0], sc0, mm0)), ex2(fmaf(v[h][1], sc0, mm0)));
    const uint32_t P1 = packbf(ex2(fmaf(v[h][2], sc1, mm1)), ex2(fmaf(v[h][3], sc1, mm1)));
#pragma unroll
    for (int k = 0; k < 4; k++) O0[h][k] = O1[h][k] = Z[h][k] = 0.f;
    mma_bf16_k8(Z[h], P0, P1, 0x3f803f80u);
    mma_bf16_k8(O0[h], P0 & ~mU, P1 & mU, fl[h][2]); mma_bf16_k8(O1[h], P0 & ~mU, P1 & mU, fl[h][3]);
    mma_bf16_k8(O0[h], P0 & mU, 0u, fp[h][2]); mma_bf16_k8(O1[h], P0 & mU, 0u, fp[h][3]);
    mma_bf16_k8(O0[h], 0u, P1 & ~mU, fh[h][2]); mma_bf16_k8(O1[h], 0u, P1 & ~mU, fh[h][3]);
  }
  const uint32_t ob = sb + SM_OST + wg * 8192;
  if (QD_AT == 0 || (QD_AT == 3 && wg == 1)) mbar_wait(bar + 8 * B_QDONE, layer);
  const int o_row = 16 * w + (lane & 7) + 8 * ((lane >> 3) & 1);
#pragma unroll
  for (int h = 0; h < 4; h++) {
    const float i0 = rcp_approx(Z[h][0]), i1 = rcp_approx(Z[h][2]);
    const int ch = 2 * h + (lane >> 4);
    stsm4(ob + o_row * 128 + ((ch ^ (o_row & 7)) << 4), packbf(O0[h][0] * i0, O0[h][1] * i0), packbf(O0[h][2] * i1, O0[h][3] * i1),
          packbf(O1[h][0] * i0, O1[h][1] * i0), packbf(O1[h][2] * i1, O1[h][3] * i1));
  }
  if (threadIdx.x == 0) TS(2 + layer * 20 + 5);
  ATS(57, 128); ATS(20, 96);
  __syncwarp();
  if (elect_one()) {
    fence_async_smem();
    tma_st(&p.mapO, hg * 64, rb * 128 + row0, ob + w * 2048);
    bulk_commit();
    mbar_arrive(bar + 8 * B_AD);
    bulk_wait_all();
    uint32_t old;
    asm volatile("atom.acq_rel.cta.shared.inc.u32 %0, [%1], 7;" : "=r"(old) : "r"(sb + SM_EP + 4) : "memory");
    if (old == 7) {
      asm volatile("red.relaxed.gpu.global.add.u32 [%0], 2;" ::"l"(&g_cnt[(C_O + rb) * 32]) : "memory");
      asm volatile("mbarrier.arrive.shared::cta.b64 _, [%0], 2;" ::"r"(bar + 8 * B_OST) : "memory");
      TS(2 + layer * 20 + 6);
    }
  }
  __syncwarp();
}

__device__ __forceinline__ void proj_phase(const Params& p, uint32_t sb, int layer, int rb, int q, int wg, int w) {
  const int lane = opaque_tid() & 31;
  const bool TR = layer != 0;
  const int t = lane & 3;
  const uint32_t bar = sb + SM_BAR;
  const uint32_t rbx = sb + SM_R + wg * 8192;
  uint32_t res[16];
  mbar_wait(bar + 8 * B_RF, layer);
  if (threadIdx.x == 0) TS(2 + layer * 20 + 7);
  if (!TR) {
#pragma unroll
    for (int j = 0; j < 8; j += 2) {
      const int mi = lane >> 3;
      const int row = 16 * w + (lane & 7) + 8 * (mi & 1), ch = j + (mi >> 1);
      ldsm4(&res[2 * j], rbx + row * 128 + ((ch ^ (row & 7)) << 4));
    }
  } else {
#pragma unroll
    for (int j = 0; j < 8; j += 2) {
      const int mi = lane >> 3;
      const int line = 8 * (j + (mi >> 1)) + (lane & 7), pc = 2 * w + (mi & 1);
      ldsm4t(&res[2 * j], rbx + line * 128 + ((pc ^ (line & 7)) << 4));
    }
  }
  bar_sync(2 + wg, 128);
  float acc[32];
#pragma unroll
  for (int i = 0; i < 16; i++) {
    asm volatile("shl.b32 %0, %1, 16;" : "=f"(acc[2 * i]) : "r"(res[i]));
    asm volatile("and.b32 %0, %1, 0xffff0000;" : "=f"(acc[2 * i + 1]) : "r"(res[i]));
  }
  const uint32_t tag = part_tag(lds32(sb + SM_EP), 2 * layer + 1);
  mbar_wait(bar + 8 * B_ZF, layer);
  mbar_wait(bar + 8 * B_WOF, layer);
#pragma unroll P_UNROLL
  for (int c = 0; c < 8; c++) {
    mbar_wait(bar + 8 * (B_OF + c), layer);
    if (c == 0 && threadIdx.x == 0) TS(2 + layer * 20 + 8);
    const uint64_t da = mkdesc(sb + sm_o(c) + wg * 8192, 16, 1024, 1);
    const uint64_t db = mkdesc(sb + SM_WO + c * 8192, 8192, 1024, 1);
    wg_fence();
#pragma unroll
    for (int ks = 0; ks < 4; ks++) wgmma_ss<64, 0, 1>(acc, da + ks * 2, db + ks * 128, 1);
    wg_commit();
  }
  wg_wait<0>();
#pragma unroll
  for (int i = 0; i < 32; i++) asm volatile("" : "+f"(acc[i]) :: "memory");
  if (threadIdx.x == 0) TS(2 + layer * 20 + 9);
  if (lane == 0 && w == 0) mbar_arrive(bar + 8 * B_PDONE);
  {
    float s[4], qq[4];
#pragma unroll
    for (int k = 0; k < 4; k++) { s[k] = acc[k]; qq[k] = acc[k] * acc[k]; }
#pragma unroll
    for (int j = 1; j < 8; j++)
#pragma unroll
      for (int k = 0; k < 4; k++) { s[k] += acc[4 * j + k]; qq[k] = fmaf(acc[4 * j + k], acc[4 * j + k], qq[k]); }
    const float s0 = s[0] + s[1], s1 = s[2] + s[3], q0 = qq[0] + qq[1], q1 = qq[2] + qq[3];
    float sr = ((t & 1) ? s1 : s0) + __shfl_xor_sync(~0u, (t & 1) ? s0 : s1, 1);
    float qr = ((t & 1) ? q1 : q0) + __shfl_xor_sync(~0u, (t & 1) ? q0 : q1, 1);
    sr += __shfl_xor_sync(~0u, sr, 2);
    qr += __shfl_xor_sync(~0u, qr, 2);
    if (t < 2) st_part(&g_part[(rb * 8 + q) * 128 + 64 * wg + 16 * w + (lane >> 2) + 8 * t], sr, qr, tag);
    __syncwarp();
    if (elect_one()) mbar_arrive(bar + 8 * B_PS);
    sched_fence<7>();
  }
#pragma unroll
  for (int j = 0; j < 8; j += 2) {
    const int mi = lane >> 3;
    const int line = 8 * (j + (mi >> 1)) + (lane & 7), pc = 2 * w + (mi & 1);
    stsm4t(rbx + line * 128 + ((pc ^ (line & 7)) << 4), packbf(acc[4 * j], acc[4 * j + 1]), packbf(acc[4 * j + 2], acc[4 * j + 3]),
           packbf(acc[4 * j + 4], acc[4 * j + 5]), packbf(acc[4 * j + 6], acc[4 * j + 7]));
  }
  fence_writer();
  bar_sync(2 + wg, 128);
  if (w == 0 && elect_one()) {
    fence_reader();
    fence_async_global();
    tma_st(&p.mapXT, rb * 128 + wg * 64, (2 * layer) * DM + q * 64, rbx);
    bulk_commit();
    if (threadIdx.x == 0) TS(2 + layer * 20 + 10);
    bulk_wait_all();
    red_relaxed(&g_cnt[C_CS * 32 + 2 + layer]);
    if (wg == 0) mbar_arrive(bar + 8 * B_RE);
  }
  __syncwarp();
}
__device__ __forceinline__ void proj_stats(uint32_t sb, int layer, int rb, int q, int lane, uint32_t tag) {
  const int r = 16 * q + (lane & 15);
  const uint2* src = &g_part[rb * 8 * 128 + r];
  uint32_t* dst = g_stats + layer * LSEQ + (rb >> 1) * 256 + ((r >> 2) & 1) * 128 + ((rb & 1) * 16 + (r >> 3)) * 4 + (r & 3);
  mbar_wait(sb + SM_BAR + 8 * B_PS, layer);
  delay<D_PST>();
  for (int it = 0;; it++) {
    uint2 v[8];
#pragma unroll
    for (int i = 0; i < 8; i++) v[i] = ld_part(src + i * 128);
    float s[4], qq[4];
    uint32_t bad = 0;
#pragma unroll
    for (int i = 0; i < 4; i++) {
      s[i] = __uint_as_float(v[i].x) + __uint_as_float(v[i + 4].x);
      qq[i] = __uint_as_float(v[i].y) + __uint_as_float(v[i + 4].y);
      bad |= (v[i].y ^ tag) | (v[i + 4].y ^ tag);
    }
    const float mean = ((s[0] + s[1]) + (s[2] + s[3])) * (1.f / DM);
    const float rstd = rsqrt_approx(fmaxf(fmaf((qq[0] + qq[1]) + (qq[2] + qq[3]), 1.f / DM, -mean * mean), 0.f) + 1e-5f);
    const bool ok = __all_sync(~0u, (bad & 7u) == 0);
    if (ok && lane < 16)
    {
      if (PUB & 1) asm volatile("red.relaxed.gpu.global.or.b32 [%0], %1;" ::"l"(dst), "r"(max(packbf(-mean, rstd), 1u)) : "memory");
      else asm volatile("st.relaxed.gpu.global.u32 [%0], %1;" ::"l"(dst), "r"(max(packbf(-mean, rstd), 1u)) : "memory");
    }
    if (ok) break;
    if (it > (1 << 22)) __trap();
  }
}

#define NA 14
#define NP 15
template <int M0, int M1> __device__ __forceinline__ void conv_load(uint32_t* A, uint32_t pe) {
#pragma unroll
  for (int m = M0; m < M1; m++) {
    asm volatile("ld.shared.v2.b32 {%0,%1}, [%2];" : "=r"(A[4 * m]), "=r"(A[4 * m + 1]) : "r"(pe + 256 * m) : "memory");
    A[4 * m + 2] = lds32(pe + 256 * m - 4);
  }
}
__device__ __forceinline__ uint32_t copy_reg(uint32_t v, uint32_t zero) { uint32_t r; asm volatile("or.b32 %0, %1, %2;" : "=r"(r) : "r"(v), "r"(zero)); return r; }
__device__ __forceinline__ uint32_t copy_reg2(uint32_t v, uint32_t zero) { uint32_t r; asm volatile("xor.b32 %0, %1, %2;" : "=r"(r) : "r"(v), "r"(zero)); return r; }
__device__ __forceinline__ void conv_park(uint32_t* P, uint32_t pe) {
#pragma unroll
  for (int m = 0; m < NP; m++)
#pragma unroll
    for (int k = 0; k < 3; k++) P[3 * m + k] = lds32(pe + 256 * m - 4 + 4 * k);
}
__device__ __forceinline__ void conv_unpark(uint32_t* A, const uint32_t* P, uint32_t zero) {
#pragma unroll
  for (int m = 0; m < NP; m++) {
    A[4 * m + 2] = copy_reg(P[3 * m], zero); A[4 * m] = copy_reg(P[3 * m + 1], zero);
    A[4 * m + 3] = copy_reg2(P[3 * m + 1], zero); A[4 * m + 1] = copy_reg(P[3 * m + 2], zero);
  }
}
template <int M0, int M1> __device__ __forceinline__ void conv_mmas(float* acc, const uint32_t* A, uint64_t d) {
  if constexpr (M0 < M1) {
    wgmma_rs<128 - 8 * (M0 / 2), 0>(acc, A + 4 * M0, d + (uint64_t)(4 * M0), M0 != 0);
    conv_mmas<M0 + 1, M1>(acc, A, d);
  }
}
struct SumAddr { uint32_t l0, l1, l2, se, so; };
__device__ __forceinline__ SumAddr conv_sum_addr(uint32_t sb, int c) {
  auto ua = [&](int j) { return sb + cv_u(0) + (127 - (j >> 3)) * 16 + (j & 7) * 2; };
  auto sa = [&](int hc) { const int ci = hc & ~1; return sb + cv_s(0) + ((ci >> 3) & 1) * 1024 + (ci >> 4) * 128 + (((ci ^ (ci >> 4)) & 7) << 4) + (hc & 1) * 8; };
  const int j0 = 4 * (c - 1);
  return {ua(j0 - 2), ua(j0), ua(j0 + 4), sa((c + 1) & 127), sa(c) + 2048};
}
__device__ __forceinline__ void sts64(uint32_t a, uint32_t x, uint32_t y) { asm volatile("st.shared.v2.b32 [%0], {%1,%2};" ::"r"(a), "r"(x), "r"(y) : "memory"); }
__device__ __forceinline__ void conv_sums(const SumAddr& sa, int lc, int c) {
  uint32_t e[4], o[4];
  {
    const float2 em = lds64f(sa.l1 + lc * 32768), om = lds64f(sa.l1 + lc * 32768 + CV_UH);
    e[0] = lds32(sa.l0 + lc * 32768); o[0] = lds32(sa.l0 + lc * 32768 + CV_UH);
    e[3] = lds32(sa.l2 + lc * 32768); o[3] = lds32(sa.l2 + lc * 32768 + CV_UH);
    e[1] = __float_as_uint(em.x); e[2] = __float_as_uint(em.y); o[1] = __float_as_uint(om.x); o[2] = __float_as_uint(om.y);
  }
  uint32_t s7e[2], s7o[2], s9e[2], s9o[2];
  uint32_t pw[4], sh[3];
#pragma unroll
  for (int k = 0; k < 4; k++) pw[k] = hadd2(e[k], o[k]);
#pragma unroll
  for (int k = 0; k < 3; k++) sh[k] = __byte_perm(pw[k], pw[k + 1], 0x5432);
#pragma unroll
  for (int k = 0; k < 2; k++) {
    const uint32_t t3 = hadd2(hadd2(sh[k], sh[k + 1]), pw[k + 1]);
    s7e[k] = hadd2(t3, o[k]); s7o[k] = hadd2(t3, e[k + 2]);
    s9e[k] = hadd2(s7o[k], pw[k]); s9o[k] = hadd2(s7e[k], pw[k + 2]);
  }
  if (c == 127) s9e[0] = s9e[1] = s9o[0] = s9o[1] = 0u;
  sts64(sa.se + lc * 32768, s9e[0], s9e[1]); sts64((sa.se ^ 16) + lc * 32768, s9o[0], s9o[1]);
  sts64(sa.so + lc * 32768, s7e[0], s7e[1]); sts64((sa.so ^ 16) + lc * 32768, s7o[0], s7o[1]);
}

__device__ __forceinline__ void conv_epi(uint32_t sb, int layer, int cta, int ch, int c0, uint4 x0, uint4 x1) {
  uint4 v[2][4];
  const uint4 xr[2] = {x0, x1};
  mbar_wait(sb + SM_BAR + 8 * (B_P + ch), layer);
#pragma unroll
  for (int u = 0; u < 2; u++) {
    const uint32_t pb = sb + cv_pb(ch) + u * (CV_PBW / 2) + c0 * 16;
#pragma unroll
    for (int k = 0; k < 4; k++) v[u][k] = lds128(pb + k * CV_PBW);
  }
#pragma unroll
  for (int u = 0; u < 2; u++) {
    uint4 o;
    o.x = hadd2(xr[u].x, hadd2(hadd2(v[u][0].x, v[u][1].x), hadd2(v[u][2].x, v[u][3].x)));
    o.y = hadd2(xr[u].y, hadd2(hadd2(v[u][0].y, v[u][1].y), hadd2(v[u][2].y, v[u][3].y)));
    o.z = hadd2(xr[u].z, hadd2(hadd2(v[u][0].z, v[u][1].z), hadd2(v[u][2].z, v[u][3].z)));
    o.w = hadd2(xr[u].w, hadd2(hadd2(v[u][0].w, v[u][1].w), hadd2(v[u][2].w, v[u][3].w)));
    if (layer == 0) sts128(sb + cv_s(ch) + (c0 + 128 * u) * 16, o);
    else if ((PUB & 4) && ch == 3) {
      uint2* d = (uint2*)((uint4*)(g_xT + (size_t)(3 * DM + cv_chan(cta, ch)) * LSEQ) + c0 + 128 * u);
      asm volatile("{\n.reg .b64 a, b;\nmov.b64 a, {%1,%2};\nmov.b64 b, {%3,%4};\nred.relaxed.gpu.global.and.b64 [%0+8], b;\nred.relaxed.gpu.global.and.b64 [%0], a;\n}" ::"l"(d), "r"(o.x), "r"(o.y), "r"(o.z), "r"(o.w) : "memory");
    } else st_tagged3((uint4*)(g_xT + (size_t)(3 * DM + cv_chan(cta, ch)) * LSEQ) + c0 + 128 * u, o.x, o.y, o.z, o.w);
  }
}
__device__ __forceinline__ void warp_release(uint32_t b) {
  fence_writer();
  __syncwarp();
  if (elect_one()) mbar_arrive(b);
}

__device__ __forceinline__ void conv_prep_load(uint32_t sb, int layer, int cta, int c, uint4 (&xr)[4], uint4 (&st)[4]) {
  sched_fence<8>();
  mbar_wait(sb + SM_BAR + 8 * B_GB, layer);
  if (threadIdx.x == 0) TS(2 + layer * 20 + 11);
  xr[0] = ld_tagged((const uint4*)(g_xT + (size_t)(2 * layer * DM + cta) * LSEQ) + c);
#pragma unroll
  for (int i = 0; i < 2; i++) st[i] = ld_tagged((const uint4*)g_stats + layer * 512 + (c >> 5) * 64 + i * 32 + (c & 31));
}
template <bool HELPER>
__device__ __forceinline__ void conv_prep(uint32_t sb, int layer, int cta, int c, uint4 (&xr)[4], uint4 (&st)[4], const SumAddr& sa) {
  const uint32_t bar = sb + SM_BAR;
  const uint4* xin = (const uint4*)(g_xT + (size_t)(2 * layer * DM + cta) * LSEQ) + c;
  for (int it = 0;; it++) {
    const uint32_t vs = min(min(min(st[0].x, st[0].y), min(st[0].z, st[0].w)), min(min(st[1].x, st[1].y), min(st[1].z, st[1].w)));
    if (__all_sync(~0u, vs != 0 && xr[0].x != ~0u)) break;
    if (it > (1 << 22)) __trap();
    if (!__all_sync(~0u, xr[0].x != ~0u)) xr[0] = ld_tagged(xin);
    if (!__all_sync(~0u, vs != 0)) {
#pragma unroll
      for (int i = 0; i < 2; i++) st[i] = ld_tagged((const uint4*)g_stats + layer * 512 + (c >> 5) * 64 + i * 32 + (c & 31));
    }
  }
  const uint32_t nm[4] = {__byte_perm(st[0].x, st[0].y, 0x5410), __byte_perm(st[0].z, st[0].w, 0x5410), __byte_perm(st[1].x, st[1].y, 0x5410), __byte_perm(st[1].z, st[1].w, 0x5410)};
  const uint32_t rs[4] = {__byte_perm(st[0].x, st[0].y, 0x7632), __byte_perm(st[0].z, st[0].w, 0x7632), __byte_perm(st[1].x, st[1].y, 0x7632), __byte_perm(st[1].z, st[1].w, 0x7632)};
  if (threadIdx.x == 0) TS(2 + layer * 20 + 12);
  const int a = c & 127, h = c >> 7;
#pragma unroll
  for (int i = 0; i < 4; i++) {
    if (i == 1) {
      mbar_wait(bar + 8 * B_XV, layer);
#pragma unroll
      for (int j = 1; j < 4; j++) xr[j] = ld_tagged(xin + j * (128 * LSEQ / 8));
      if (HELPER) {
        mbar_wait(bar + 8 * B_U, layer);
        conv_sums(sa, 0, c);
        fence_async_smem();
        bar_arrive(7, 256);
        sched_fence<1>();
        if (layer == 1 && c == 0) TS(46);
      }
    }
    const uint32_t x[4] = {xr[i].x, xr[i].y, xr[i].z, xr[i].w};
    uint32_t u[4];
#pragma unroll
    for (int k = 0; k < 4; k++)
      u[k] = hmul2(hadd2(x[k], nm[k]), rs[k]);
    sts128(sb + cv_u(i) + h * CV_UH + (127 - a) * 16, make_uint4(u[0], u[1], u[2], u[3]));
    warp_release(bar + 8 * (B_U + i));
    sched_fence<2>();
  }
}
__device__ __forceinline__ void conv_zero(uint32_t sb, int ht) {
  if (ht < 96) {
    const int ch = ht / 24, h2 = (ht / 12) & 1, qq = ht % 12;
    sts128(sb + cv_u(ch) + h2 * CV_UH + (128 + qq) * 16, make_uint4(0, 0, 0, 0));
  }
  if (ht >= 80) {
    const int i = ht - 80, ch = i / 12, q2 = i % 12;
    const int w2 = q2 < 2 ? 1 : q2 < 6 ? 2 : 3, cc = q2 < 2 ? q2 : q2 < 6 ? q2 - 2 : q2 - 6;
    sts128(sb + cv_pb(ch) + w2 * CV_PBW + (cc & 1) * (CV_PBW / 2) + (cc >> 1) * 16, make_uint4(0, 0, 0, 0));
  }
}

#define HANDOVER 1
template <int R>
__device__ __forceinline__ void conv_round(uint32_t sb, int layer, int wg, uint32_t* A, const uint32_t* P, uint32_t pb, uint32_t pe2) {
  const uint32_t bar = sb + SM_BAR;
  const int ch = 2 * R + 1 - wg;
  float acc[64];
  const uint64_t d = mkdesc(sb + cv_u(ch), CV_UH, 128, 0);
  FTS(39);
  if (R == 0) {
    mbar_wait(bar + 8 * (B_U + ch), layer);
    fence_reader();
  }
  sched_fence<3>();
  if (R == 1 || wg == 0) bar_sync(10 + ch, 256);
  if (layer == 0 && ch > 0 && ((PAUSE >> (ch - 1)) & 1)) mbar_wait(bar + 8 * (B_E + ch - 1), 0);
  if (layer == 0 && ch > 0 && ((PAUSE >> (ch + 3)) & 1)) mbar_wait(bar + 8 * (B_P + ch - 1), 0);
  FTS(41);
  if (ch == 0 && threadIdx.x == 128) TS(2 + layer * 20 + 13);
  wg_fence();
  conv_mmas<0, 1>(acc, A, d); conv_mmas<2, NA + 1>(acc, A, d);
  wg_commit();
  FTS(51);
  if (HANDOVER == 0 && (R == 0 || wg == 1)) bar_arrive(11 + ch, 256);
  bar_sync(7 + ch, 256);
  wg_fence();
  conv_mmas<1, 2>(acc, A, d); conv_mmas<NA + 1, 17>(acc, A, d);
  wgmma_ss<64, 1, 1>(acc, mkdesc(sb + cv_s(ch), 1024, 1024, 1), mkdesc(sb + cv_ft(ch), 256, 16, 0), 1);
  wgmma_ss<64, 1, 1>(acc, mkdesc(sb + cv_s(ch) + 2048, 1024, 1024, 1), mkdesc(sb + cv_ft(ch) + 512, 256, 16, 0), 1);
  wg_commit();
  if (HANDOVER == 1 && (R == 0 || wg == 1 || (G_WAIT == 3 && layer == 0))) bar_arrive(11 + ch, 256);
  FTS(61);
  wg_wait<0>();
#pragma unroll
  for (int j = 0; j < 16; j += 2)
    stsm4t(pb + R * 65536 - j * 128, packbf(acc[4 * j], acc[4 * j + 1]), packbf(acc[4 * j + 2], acc[4 * j + 3]),
           packbf(acc[4 * j + 4], acc[4 * j + 5]), packbf(acc[4 * j + 6], acc[4 * j + 7]));
  __syncwarp();
  if (elect_one()) mbar_arrive(bar + 8 * (B_P + ch));
  if (threadIdx.x == 0) TS(2 + layer * 20 + 14 + R);
  FTS(57);
  if (R == 0) {
    conv_unpark(A, P, opaque_tid() >> 10);
    mbar_wait(bar + 8 * (B_U + ch + 2), layer);
    fence_reader();
    conv_load<NP, 17>(A, pe2);
#pragma unroll
    for (int m = NP; m < 17; m++) A[4 * m + 3] = lds32(pe2 + 256 * m);
  }
}
__device__ __forceinline__ void conv_phase(const Params& p, uint32_t sb, int layer, int cta) {
  const int tid = opaque_tid();
  const int wg = __shfl_sync(~0u, tid >> 7, 0), w = __shfl_sync(~0u, (tid >> 5) & 3, 0);
  const uint32_t bar = sb + SM_BAR;
  uint32_t A[68], P[3 * NP];
  const uint32_t pe = sb + cv_pe(1 - wg) + 4 * (16 + 16 * w + 2 * ((tid & 31) >> 2) - 4 * (tid & 3));
  mbar_wait(bar + 8 * B_PE, layer);
  conv_load<0, 17>(A, pe);
#pragma unroll
  for (int m = 0; m < 17; m++) A[4 * m + 3] = copy_reg(A[4 * m], tid >> 10);
  if (wg == 0) {
    uint4 xr[4], st[4];
    if (PARK_FIRST) conv_park(P, pe + 65536);
    conv_prep_load(sb, layer, cta, tid + 128, xr, st);
    if (!PARK_FIRST) conv_park(P, pe + 65536);
    conv_prep<false>(sb, layer, cta, opaque_tid() + 128, xr, st, SumAddr());
  } else {
    conv_park(P, pe + 65536);
  }
  uint32_t pb;
  {
    const int l2 = opaque_tid() & 31, mt = l2 >> 3;
    pb = sb + cv_pb(1 - wg) + w * CV_PBW + (mt & 1) * (CV_PBW / 2) + (127 - 8 * (mt >> 1) - (l2 & 7) + w) * 16;
  }
  conv_round<0>(sb, layer, wg, A, P, pb, pe + 65536);
  conv_round<1>(sb, layer, wg, A, P, pb, 0);
  if (G_WAIT == 1 && layer == 0) mbar_wait(bar + 8 * (B_E + 3), layer);
  if (G_WAIT == 2 && layer == 0) mbar_wait(bar + 8 * (B_P + 3), layer);
}

__device__ __forceinline__ void final_phase(const Params& p, uint32_t sb, int cta, int wg, int w) {
  const int lane = opaque_tid() & 31, g = lane >> 2, t = lane & 3;
  constexpr int RS = 2 * DM;
  int it = 0;
  {
    const int lc = wg ? 0 : 3;
    const int p0 = (cta & 15) * 128 + 32 * w, c0 = 128 * lc + (cta >> 4) * 16;
    const bf16* src = g_xT + (size_t)(3 * DM + c0 + 4 * (g >> 1) + (g & 1)) * LSEQ + p0 + 8 * t;
    bf16* dst = p.out + (size_t)(2 * ((p0 & 1023) + 8 * (g >> 1) + (g & 1)) + (p0 >> 10)) * DM + c0 + 4 * t;
    if (wg == 0) {
      mbar_wait(sb + SM_BAR + 8 * (B_E + 3), 1);
      delay<D_FIN>();
    }
    uint4 a, b;
    for (;;) {
      a = ld_tagged((const uint4*)src); b = ld_tagged((const uint4*)(src + 2 * LSEQ));
      if (__all_sync(~0u, max(a.x, b.x) != ~0u)) break;
      if (++it > (1 << 22)) __trap();
    }
    if (threadIdx.x == 0) TS(42);
    *(uint2*)dst = make_uint2(movm_t(a.x), movm_t(b.x));
    *(uint2*)(dst + 2 * RS) = make_uint2(movm_t(a.y), movm_t(b.y));
    *(uint2*)(dst + 4 * RS) = make_uint2(movm_t(a.z), movm_t(b.z));
    *(uint2*)(dst + 6 * RS) = make_uint2(movm_t(a.w), movm_t(b.w));
  }
  if (wg == 1) {
    const int lc = 1 + (w >> 1);
    const int p0 = (cta & 31) * 64 + 32 * (w & 1), c0 = 128 * lc + (cta >> 5) * 32;
    const bf16* src = g_xT + (size_t)(3 * DM + c0 + 8 * (g >> 1) + (g & 1)) * LSEQ + p0 + 8 * t;
    bf16* dst = p.out + (size_t)(2 * ((p0 & 1023) + 8 * (g >> 1) + (g & 1)) + (p0 >> 10)) * DM + c0 + 8 * t;
    mbar_wait(sb + SM_BAR + 8 * (B_E + lc), 1);
    if (lc >= FIN_D0) delay<D_FIN2>();
    uint4 v[4];
    for (;;) {
#pragma unroll
      for (int q = 0; q < 4; q++) v[q] = ld_tagged((const uint4*)(src + 2 * q * LSEQ));
      if (__all_sync(~0u, max(max(v[0].x, v[1].x), max(v[2].x, v[3].x)) != ~0u)) break;
      if (++it > (1 << 22)) __trap();
    }
    *(uint4*)dst = make_uint4(movm_t(v[0].x), movm_t(v[1].x), movm_t(v[2].x), movm_t(v[3].x));
    *(uint4*)(dst + 2 * RS) = make_uint4(movm_t(v[0].y), movm_t(v[1].y), movm_t(v[2].y), movm_t(v[3].y));
    *(uint4*)(dst + 4 * RS) = make_uint4(movm_t(v[0].z), movm_t(v[1].z), movm_t(v[2].z), movm_t(v[3].z));
    *(uint4*)(dst + 6 * RS) = make_uint4(movm_t(v[0].w), movm_t(v[1].w), movm_t(v[2].w), movm_t(v[3].w));
  }
  if (threadIdx.x == 0) TS(43);
  if (threadIdx.x == 192) TS(63);
  if (threadIdx.x == 160) TS(53);
  if (threadIdx.x == 0) LTS(1);
}

struct cplx { float r, i; };
__device__ __forceinline__ cplx cmul(cplx a, cplx b) { return {fmaf(a.r, b.r, -a.i * b.i), fmaf(a.r, b.i, a.i * b.r)}; }
__device__ __forceinline__ cplx csqr(cplx a) { return {fmaf(a.r, a.r, -a.i * a.i), (a.r + a.r) * a.i}; }
__device__ __forceinline__ cplx cexp_l(float ar2, float ai, float l) {
  const float m = ex2(ar2 * l);
  const float x = ai * l;
  return {m * __cosf(x), m * __sinf(x)};
}

__device__ __forceinline__ void colsum_publish(uint32_t sb, int rb, int hg, int ht, uint32_t tag) {
  const int lane = ht & 31, q = lane & 15, h = lane >> 4;
  const uint32_t src = sb + SM_CW + (ht >> 5) * 4096 + h * 128 + (q & 1) * 8;
  float s[4] = {0.f, 0.f, 0.f, 0.f};
#pragma unroll 8
  for (int r = 0; r < 16; r++) {
    const float2 v = lds64f(src + r * 256 + (((q >> 1) ^ ((2 * r + h) & 7)) << 4));
    s[0] += bf_lo(__float_as_uint(v.x)); s[1] += bf_hi(__float_as_uint(v.x));
    s[2] += bf_lo(__float_as_uint(v.y)); s[3] += bf_hi(__float_as_uint(v.y));
  }
#pragma unroll
  for (int k = 0; k < 4; k++) s[k] += __shfl_xor_sync(~0u, s[k], 16);
  if (h == 0)
    st_tagged3(&g_colsum[(hg * 16 + rb) * 48 + (ht >> 5) * 16 + q], (__float_as_uint(s[0]) & ~7u) | tag, __float_as_uint(s[1]),
               __float_as_uint(s[2]), __float_as_uint(s[3]));
}
__device__ __forceinline__ void colsum_gather(uint32_t sb, int hg, int ht, uint32_t tag) {
  const int lane = ht & 31, rec = (ht >> 5) * 16 + (lane & 15);
  const uint4* src = &g_colsum[(hg * 16 + (lane >> 4) * 8) * 48 + rec];
  float s[4] = {0.f, 0.f, 0.f, 0.f};
#pragma unroll 1
  for (int h = 0; h < 2; h++, src += 4 * 48) {
    uint4 v[4];
    int it = 0;
    do {
#pragma unroll
      for (int i = 0; i < 4; i++) v[i] = ld_tagged(src + i * 48);
      if (++it > (1 << 22)) __trap();
    } while (!__all_sync(~0u, (v[0].x & 7u) == tag && (v[1].x & 7u) == tag && (v[2].x & 7u) == tag && (v[3].x & 7u) == tag));
#pragma unroll
    for (int i = 0; i < 4; i++) {
      s[0] += __uint_as_float(v[i].x & ~7u); s[1] += __uint_as_float(v[i].y); s[2] += __uint_as_float(v[i].z); s[3] += __uint_as_float(v[i].w);
    }
  }
#pragma unroll
  for (int k = 0; k < 4; k++) s[k] += __shfl_xor_sync(~0u, s[k], 16);
  if (lane < 16) sts128f(sb + SM_CS + rec * 16, s[0], s[1], s[2], s[3]);
}

__device__ __forceinline__ uint32_t packh(float lo, float hi) { uint32_t r; asm("cvt.rn.f16x2.f32 %0, %1, %2;" : "=r"(r) : "f"(hi), "f"(lo)); return r; }
__device__ __forceinline__ void mma_f16(float* d, uint32_t a0, uint32_t a1, uint32_t a2, uint32_t a3, uint32_t b0, uint32_t b1) {
  asm volatile("mma.sync.aligned.m16n8k16.row.col.f32.f16.f16.f32 {%0,%1,%2,%3}, {%4,%5,%6,%7}, {%8,%9}, {%0,%1,%2,%3};"
      : "+f"(d[0]), "+f"(d[1]), "+f"(d[2]), "+f"(d[3]) : "r"(a0), "r"(a1), "r"(a2), "r"(a3), "r"(b0), "r"(b1));
}
struct HSeed { uint32_t r, i; };
__device__ __forceinline__ HSeed hseed(cplx s) { return {packh(s.r, s.r), packh(s.i, s.i)}; }
__device__ __forceinline__ void hcmul(uint32_t& o_r, uint32_t& o_i, uint32_t br, uint32_t bi, HSeed s) {
  asm("{\n.reg .b32 t, u;\nmul.rn.f16x2 t, %3, %5;\nneg.f16x2 t, t;\nmul.rn.f16x2 u, %3, %4;\nfma.rn.f16x2 %0, %2, %4, t;\nfma.rn.f16x2 %1, %2, %5, u;\n}"
      : "=&r"(o_r), "=&r"(o_i) : "r"(br), "r"(bi), "r"(s.r), "r"(s.i));
}
struct HTile { uint32_t r[4], i[4]; };
__device__ __forceinline__ void tile_set(HTile& t, int k, cplx a, cplx b) { t.r[k] = packh(a.r, b.r); t.i[k] = packh(a.i, b.i); }
__device__ __forceinline__ void tile_upper(HTile& t, HSeed s) { hcmul(t.r[2], t.i[2], t.r[0], t.i[0], s); hcmul(t.r[3], t.i[3], t.r[1], t.i[1], s); }
__device__ __forceinline__ HTile tile_shift(const HTile& t, HSeed s) {
  HTile o;
#pragma unroll
  for (int k = 0; k < 4; k++) hcmul(o.r[k], o.i[k], t.r[k], t.i[k], s);
  return o;
}
__device__ __forceinline__ void tile_put(const HTile& t, uint32_t a) {
  sts128(a, make_uint4(t.r[0], t.r[1], t.r[2], t.r[3]));
  sts128(a + 512, make_uint4(t.i[0], t.i[1], t.i[2], t.i[3]));
}
__device__ __forceinline__ HTile tile_get(uint32_t a) { HTile o; ldsm4t(o.r, a); ldsm4t(o.i, a + 512); return o; }
__device__ __forceinline__ void tile_mma(float* T, const HTile& a0, const HTile& a1, const HTile& b) {
  mma_f16(T, a0.r[0], a0.r[1], a0.r[2], a0.r[3], b.r[0], b.r[1]);
  mma_f16(T, a0.i[0], a0.i[1], a0.i[2], a0.i[3], b.i[0], b.i[1]);
  mma_f16(T, a1.r[0], a1.r[1], a1.r[2], a1.r[3], b.r[2], b.r[3]);
  mma_f16(T, a1.i[0], a1.i[1], a1.i[2], a1.i[3], b.i[2], b.i[3]);
}
__device__ __forceinline__ void tile_mma2(float* T, float* U, const HTile& a0, const HTile& a1, const HTile& b, const HTile& c) {
  mma_f16(T, a0.r[0], a0.r[1], a0.r[2], a0.r[3], b.r[0], b.r[1]);
  mma_f16(U, a0.r[0], a0.r[1], a0.r[2], a0.r[3], c.r[0], c.r[1]);
  mma_f16(T, a0.i[0], a0.i[1], a0.i[2], a0.i[3], b.i[0], b.i[1]);
  mma_f16(U, a0.i[0], a0.i[1], a0.i[2], a0.i[3], c.i[0], c.i[1]);
  mma_f16(T, a1.r[0], a1.r[1], a1.r[2], a1.r[3], b.r[2], b.r[3]);
  mma_f16(U, a1.r[0], a1.r[1], a1.r[2], a1.r[3], c.r[2], c.r[3]);
  mma_f16(T, a1.i[0], a1.i[1], a1.i[2], a1.i[3], b.i[2], b.i[3]);
  mma_f16(U, a1.i[0], a1.i[1], a1.i[2], a1.i[3], c.i[2], c.i[3]);
}
__device__ __forceinline__ void kgen_unit(uint32_t tab, uint32_t taba, float ar2, float ai, cplx c, float (&T)[5][4]) {
  const cplx z1 = cexp_l(ar2, ai, 1.f), z16 = cexp_l(ar2, ai, 16.f), z256 = cexp_l(ar2, ai, 256.f);
  HTile a0, a1, b0, b1;
  {
    const cplx y1 = {z16.r, -z16.i}, y2 = csqr(y1), y3 = cmul(y2, y1), y4 = csqr(y2), y5 = cmul(y4, y1), y6 = csqr(y3), y7 = cmul(y4, y3);
    HTile t;
    tile_set(t, 0, {1.f, 0.f}, y1); tile_set(t, 1, y2, y3); tile_set(t, 2, y4, y5); tile_set(t, 3, y6, y7);
    const HTile u = tile_shift(t, hseed(csqr(y4)));
    __syncwarp();
    tile_put(t, tab); tile_put(u, tab + 1024);
    __syncwarp();
    a0 = tile_get(taba); a1 = tile_get(taba + 256);
  }
  const cplx z2 = csqr(z1), z4 = csqr(z2), z8 = csqr(z4);
  const HSeed h8 = hseed(z8);
  const cplx d = cmul(c, z256), e = cmul(d, z256);
  {
    const cplx z512 = csqr(z256), f = cmul(e, z512), f8 = cmul(f, z8), f16 = cmul(f, z16), e4 = cmul(e, z4);
    HTile t, u;
    tile_set(t, 0, e4, cmul(e, z8)); tile_set(t, 1, cmul(e4, z8), cmul(e, z16));
    tile_upper(t, hseed(z256));
    tile_set(u, 0, f8, f16); tile_set(u, 1, cmul(f8, z256), cmul(f16, z256));
    tile_upper(u, hseed(z512));
    __syncwarp();
    tile_put(t, tab); tile_put(u, tab + 1024);
    __syncwarp();
    b0 = tile_get(tab); b1 = tile_get(tab + 1024);
  }
  {
    const cplx d2 = cmul(d, z2), d4 = cmul(d, z4);
    HTile t;
    tile_set(t, 0, d2, d4); tile_set(t, 1, cmul(d2, z4), cmul(d, z8));
    tile_upper(t, h8);
    __syncwarp();
    tile_put(t, tab);
    __syncwarp();
    tile_mma2(T[3], T[4], a0, a1, b0, b1);
    b0 = tile_get(tab);
  }
  {
    const cplx c1 = cmul(c, z1), c2 = cmul(c, z2), c3 = cmul(c1, z2), c4 = cmul(c, z4);
    HTile t;
    tile_set(t, 0, c1, c2); tile_set(t, 1, c3, c4); tile_set(t, 2, cmul(c1, z4), cmul(c2, z4)); tile_set(t, 3, cmul(c3, z4), cmul(c4, z4));
    const HTile u = tile_shift(t, h8);
    __syncwarp();
    tile_put(t, tab); tile_put(u, tab + 1024);
    __syncwarp();
    tile_mma(T[2], a0, a1, b0);
    b0 = tile_get(tab); b1 = tile_get(tab + 1024);
    tile_mma2(T[0], T[1], a0, a1, b0, b1);
  }
}
struct ModeIn { uint2 ar, ai, br, bi, cr, ci; };
__device__ __forceinline__ ModeIn load_modes(const Params& p, int idx) {
  return {*(const uint2*)(p.a_re + idx), *(const uint2*)(p.a_im + idx), *(const uint2*)(p.b_re + idx),
          *(const uint2*)(p.b_im + idx), *(const uint2*)(p.c_re + idx), *(const uint2*)(p.c_im + idx)};
}
__device__ __forceinline__ float bf_el(uint2 v, int k) { const uint32_t x = (k & 2) ? v.y : v.x; return (k & 1) ? bf_hi(x) : bf_lo(x); }
struct KGen { float4 cur; float T[5][4]; };
__device__ __forceinline__ uint32_t kgen_slot(uint32_t sb, int ht, int u) {
  return sb + (u < 3 ? SM_KC + (ht >> 5) * (KC_STRIDE * 2) + (u - 1) * 512 + (ht & 31) * 16 + 16 : SM_HALO + 1024 + ht * 16);
}
__device__ __forceinline__ void kgen_setup(KGen& s, uint32_t sb, int cta, int ht, const ModeIn& in, bf16 logdt, bf16 dskip) {
  const float dt = __bfloat162float(__float2bfloat16_rn(expf(__bfloat162float(logdt))));
  float mx = 0.f, k0 = 0.f, ar2[4];
  cplx c[4];
#pragma unroll
  for (int k = 0; k < 4; k++) {
    ar2[k] = (dt * bf_el(in.ar, k)) * 1.4426950408889634f;
    c[k] = cmul({bf_el(in.cr, k), bf_el(in.ci, k)}, {dt * bf_el(in.br, k), dt * bf_el(in.bi, k)});
    k0 += c[k].r;
    mx = fmaxf(mx, fmaxf(fabsf(c[k].r), fabsf(c[k].i)) * ex2(fmaxf(ar2[k] * 2048.f, 0.f)));
  }
  const int ex = min(max(267 - (int)(__reduce_max_sync(~0u, __float_as_uint(mx)) >> 23), 1), 253);
  const float sc = __uint_as_float(ex << 23);
#pragma unroll
  for (int o = 16; o > 0; o >>= 1) k0 += __shfl_xor_sync(~0u, k0, o);
  if ((ht & 31) == 0) {
    const uint32_t kc = sb + SM_KC + (ht >> 5) * (KC_STRIDE * 2);
    sts16(kc, __bfloat16_as_ushort(__float2bfloat16_rn(k0 + __bfloat162float(dskip))));
    sts16(kc + 641 * 2, 0);
    sts32f(kc + 644 * 2, __uint_as_float((254 - ex) << 23));
  }
  s.cur = make_float4(ar2[0], dt * bf_el(in.ai, 0), c[0].r * sc, c[0].i * sc);
#pragma unroll
  for (int k = 1; k < 4; k++) sts128f(kgen_slot(sb, ht, k), ar2[k], dt * bf_el(in.ai, k), c[k].r * sc, c[k].i * sc);
#pragma unroll
  for (int i = 0; i < 5; i++) s.T[i][0] = s.T[i][1] = s.T[i][2] = s.T[i][3] = 0.f;
}
__device__ __forceinline__ void kgen_finish(KGen& s, uint32_t sb, int cta, int ht) {
  const int w = ht >> 5, lane = ht & 31, g = lane >> 2, t = lane & 3;
  const uint32_t kc = sb + SM_KC + w * KC_STRIDE * 2;
  __syncwarp();
  const float inv = __uint_as_float(lds32(kc + 644 * 2));
  auto put = [&](int idx, float v) {
    sts16(kc + idx * 2, __bfloat16_as_ushort(__float2bfloat16_rn(v)));
  };
#pragma unroll
  for (int hi = 0; hi < 2; hi++)
#pragma unroll
    for (int lo = 0; lo < 2; lo++) {
      const int i = g + 8 * hi, j = 2 * t + lo, e = 2 * hi + lo;
      put(16 * i + 1 + j, s.T[0][e] * inv);
      put(16 * i + 9 + j, s.T[1][e] * inv);
      put(257 + 8 * i + j, s.T[2][e] * inv);
      put(385 + 4 * i + (j & 3) + 64 * (j >> 2), s.T[3][e] * inv);
      put(513 + 2 * i + lo + 32 * t, s.T[4][e] * inv);
    }
}

__device__ __forceinline__ void expand_taps(uint32_t sb, int ht) {
  const int ch = ht >> 5, lane = ht & 31;
  const uint32_t kc = sb + SM_KC + ch * KC_STRIDE * 2;
  const uint32_t dst0 = sb + cv_pe(ch);
  auto put = [&](int G, uint32_t u0, uint32_t u1, uint32_t v0, uint32_t v1, uint32_t v2, uint32_t v3, uint32_t v4, uint32_t v5, uint32_t v6, uint32_t v7) {
    const uint32_t dst = dst0 + G * 32;
    sts128(dst, make_uint4(v0 | (u0 << 16), v1 | (u1 << 16), v2 | (v0 << 16), v3 | (v1 << 16)));
    sts128(dst + 16, make_uint4(v4 | (v2 << 16), v5 | (v3 << 16), v6 | (v4 << 16), v7 | (v5 << 16)));
  };
  {
    const uint4 q = lds128(kc + lane * 16);
    const uint32_t pv = lane ? lds32(kc + lane * 16 - 4) : 0u;
    const uint32_t dst = dst0 + (lane + 2) * 32;
    sts128(dst, make_uint4(__byte_perm(q.x, pv, 0x5410), __byte_perm(q.x, pv, 0x7632), __byte_perm(q.y, q.x, 0x5410), __byte_perm(q.y, q.x, 0x7632)));
    sts128(dst + 16, make_uint4(__byte_perm(q.z, q.y, 0x5410), __byte_perm(q.z, q.y, 0x7632), __byte_perm(q.w, q.z, 0x5410), __byte_perm(q.w, q.z, 0x7632)));
    if (lane < 4) sts128(dst0 + lane * 16, make_uint4(0, 0, 0, 0));
  }
  uint32_t a[5], b[2][3], fv[4];
  {
    const uint32_t s1 = kc + 2 * (256 + 4 * lane);
#pragma unroll
    for (int k = 0; k < 5; k++) a[k] = lds16(s1 + 2 * k);
#pragma unroll
    for (int u = 0; u < 2; u++) {
      const uint32_t s2 = kc + 2 * (384 + 2 * (lane + 32 * u));
#pragma unroll
      for (int k = 0; k < 3; k++) b[u][k] = lds16(s2 + 2 * k);
    }
#pragma unroll
    for (int k = 0; k < 4; k++) fv[k] = lds16(kc + 2 * (640 - 4 * lane - k));
  }
  const uint32_t am1 = lds16(kc + 2 * (lane ? 256 + 4 * lane : 255)), am2 = lds16(kc + 2 * (lane ? 255 + 4 * lane : 254));
  const uint32_t bm2 = lds16(kc + 2 * (lane ? 384 + 2 * lane : 383)), k1024 = lds16(kc + 2 * 512);
  put(34 + lane, am2, am1, a[0], a[0], a[1], a[2], a[2], a[2], a[3], a[4]);
#pragma unroll
  for (int u = 0; u < 2; u++) put(66 + lane + 32 * u, u ? b[u][0] : bm2, b[u][0], b[u][0], b[u][0], b[u][0], b[u][1], b[u][1], b[u][1], b[u][2], b[u][2]);
  if (lane < 10) {
    const uint32_t v = lane == 0 ? k1024 : 0u;
    put(130 + lane, v, v, v, v, v, v, v, 0u, 0u, 0u);
  }
  const uint32_t ft = sb + cv_ft(ch) + 4 * lane;
#pragma unroll
  for (int ty = 0; ty < 2; ty++) {
    const uint32_t v = fv[ty] | (fv[ty + 2] << 16);
    sts32f(ft + ty * 512, __uint_as_float(v));
    sts32f(ft + ty * 512 + 128, 0.f);
    sts32f(ft + ty * 512 + 256 + (lane < 2 ? 120 : -8), __uint_as_float(lane < 2 ? 0u : v));
    sts32f(ft + ty * 512 + 384, 0.f);
  }
}

__device__ __forceinline__ int role_id() { int v; asm volatile("mov.u32 %0, %%ctaid.x;" : "=r"(v)); return v; }
#define GMAP 8
__device__ __forceinline__ int role_rb(int cta) { return 4 * (cta >> 5) + (cta & 3); }
__device__ __forceinline__ int role_hg(int cta) { return 2 * (((cta >> 3) & 3) ^ (((cta >> 5) & 1) * 3)) + ((cta >> 2) & 1); }
__device__ __forceinline__ int role_rb2(int cta) { return cta >> 3; }
__device__ __forceinline__ int role_q2(int cta) { return cta & 7; }

__global__ void __launch_bounds__(NTHREADS, 1) fused_kernel(const __grid_constant__ Params p) {
  extern __shared__ __align__(1024) uint8_t smem[];
  const uint32_t sb = s32(smem);
  const int tid = threadIdx.x, lane = tid & 31;
  const int warp = __shfl_sync(~0u, tid >> 5, 0);
  const uint32_t bar = sb + SM_BAR;
  if (tid == 0) TS(0);
  const int cta0 = role_id();
  if (warp == 0 && elect_one()) {
    const int rb = role_rb(cta0), hg = role_hg(cta0);
#pragma unroll
    for (int c = 0; c < 2; c++) { mbar_init(bar + 8 * (B_XF + c), 1); mbar_init(bar + 8 * (B_KVF + c), 1); }
    fence_async_smem();
#pragma unroll
    for (int c = 0; c < 2; c++) {
      mbar_expect(bar + 8 * (B_XF + c), 16384);
      tma_ld(sb + SM_X + c * 16384, &p.mapX128, (rb >> 3) * DM + c * 64, (rb & 7) * 128, bar + 8 * (B_XF + c));
      mbar_expect(bar + 8 * (B_KVF + c), 24576);
      tma_ld3(sb + SM_W + c * 24576, &p.mapW3, hg * 64, c * 64, 0, bar + 8 * (B_KVF + c));
    }
  }
  if (warp == 1 && elect_one()) {
    const int rb = role_rb(cta0), hg = role_hg(cta0);
#pragma unroll
    for (int c = 2; c < 8; c++) mbar_init(bar + 8 * (B_XF + c), 1);
    mbar_init(bar + 8 * (B_KVF + 2), 1); mbar_init(bar + 8 * B_CW, 1);
    fence_async_smem();
    delay<D_START>();
    mbar_expect(bar + 8 * B_CW, 12288);
    tma_ld3(sb + SM_CW, &p.mapW3h, hg * 64, rb * 32, 0, bar + 8 * B_CW);
#pragma unroll
    for (int c = 2; c < 8; c++) {
      mbar_expect(bar + 8 * (B_XF + c), 16384);
      tma_ld(sb + SM_X + c * 16384, &p.mapX128, (rb >> 3) * DM + c * 64, (rb & 7) * 128, bar + 8 * (B_XF + c));
      if (c < 3) {
        mbar_expect(bar + 8 * (B_KVF + c), 24576);
        tma_ld3(sb + SM_W + c * 24576, &p.mapW3, hg * 64, c * 64, 0, bar + 8 * (B_KVF + c));
      }
    }
    TS(56);
  }
  if ((warp & 2) != 0 && warp < 15 && elect_one()) {
    const int grp = 1 + (warp & 1) + 2 * (warp >> 2), cnt = grp < 4 ? 1 : grp < 5 ? 2 : grp < 7 ? 4 : 8;
#pragma unroll
    for (int k = 0; k < 10; k++)
      if (k != 0 || grp > 3 || grp == 2) mbar_init(bar + 8 * (10 * grp + k), cnt);
    fence_async_smem();
  }

  if (warp < 8) {
    if (tid == 0) TS(1);
    asm volatile("setmaxnreg.inc.sync.aligned.u32 %0;" ::"n"(R_CONS));
    const int cta = role_id();
    auto warp_id = [] { return __shfl_sync(~0u, opaque_tid() >> 5, 0); };
    if (tid == 0) TS(54);
#pragma unroll 1
    for (int layer = 0; layer < 2; layer++) {
      { const int cw = warp_id(); attn_phase(p, sb, layer, role_rb(cta), role_hg(cta), cw >> 2, cw & 3); }
      if (STOP == 1 + 3 * layer) return;
      { const int cw = warp_id(); proj_phase(p, sb, layer, role_rb2(cta), role_q2(cta), cw >> 2, cw & 3); }
      if (STOP == 2 + 3 * layer) return;
      conv_phase(p, sb, layer, cta);
      if (STOP == 3 + 3 * layer) return;
    }
    { const int cw = warp_id(); final_phase(p, sb, cta, cw >> 2, cw & 3); }
  } else if (warp < 12) {
    asm volatile("setmaxnreg.dec.sync.aligned.u32 %0;" ::"n"(R_HELP));
    const int ht = tid - 256;
    const int cta = role_id(), rb = role_rb(cta), hg = role_hg(cta);
    unsigned ep0 = 0;
    if (ht == 0) ep0 = ld_relaxed(&g_cnt[C_CS * 32]);
    bar_sync(0, NTHREADS);
    if (ht == 0) {
      asm volatile("st.shared.v2.u32 [%0], {%1, 0};" ::"r"(sb + SM_EP), "r"(ep0 / NCTA) : "memory");
      mbar_arrive(bar + 8 * B_EP);
    }
    mbar_wait(bar + 8 * B_EP, 0);
    stats_publish(sb, 0, rb, hg, opaque_tid() - 256, part_tag(lds32(sb + SM_EP), 0));
    if (ht < 48) {
      const bf16* q = (&p.a_re)[ht >> 3];
      asm volatile("prefetch.global.L2 [%0];" ::"l"(q + cv_chan(cta, (ht >> 1) & 3) * 128 + (ht & 1) * 64));
    }
    {
      KGen kg;
      const uint32_t tab0 = sb + ((ht >> 5) < 2 ? SM_T : SM_T2 - 4096) + (ht >> 5) * 2048;
      const uint32_t tab = tab0 + (ht & 31) * 16, taba = tab0 + ((ht >> 3) & 1) * 1024 + (((ht >> 1) & 8) + (ht & 7)) * 16;
      delay<D_ST0>();
      stats_gather(sb, rb, opaque_tid() - 256, part_tag(lds32(sb + SM_EP), 0));
      if (ht == 0) TS(40);
      const int chn = cv_chan(cta, ht >> 5);
      const ModeIn modes = load_modes(p, chn * 128 + (ht & 31) * 4);
      const bf16 logdt = p.log_dt[chn], dskip = p.dskip[chn];
      if (!HALO_W14 && KG_START != 4) halo_receive(sb, 0, rb, hg, opaque_tid() - 256);
      if (KG_START == 1) mbar_wait(bar + 8 * B_HF, 0);
      kgen_setup(kg, sb, cta, ht, modes, logdt, dskip);
      if (!HALO_W14 && KG_START == 4) halo_receive(sb, 0, rb, hg, opaque_tid() - 256);
      if (KG_START == 2) mbar_wait(bar + 8 * B_HF, 0);
      if (KG_START == 3) mbar_wait(bar + 8 * B_QDONE, 0);
#pragma unroll 1
      for (int u = 0; u < 4; u++) {
        if (u == KG_PRE) {
          KTS(39);
          mbar_wait(bar + 8 * B_AD, 0);
          KTS(41);
        }
        kgen_unit(tab, taba, kg.cur.x, kg.cur.y, {kg.cur.z, kg.cur.w}, kg.T);
        kg.cur = lds128f(kgen_slot(sb, opaque_tid() - 256, u + 1));
      }
      kgen_finish(kg, sb, cta, opaque_tid() - 256);
    }
    KTS(51);
    bar_sync(4, 128);
#pragma unroll 1
    for (int layer = 0; layer < 2; layer++) {
      if (STOP <= 1 + 3 * layer) return;
      mbar_wait(bar + 8 * (EXP_LATE ? B_PS : B_PDONE), layer);
      expand_taps(sb, opaque_tid() - 256);
      conv_zero(sb, opaque_tid() - 256);
      if (ht == 0) TS(52 + layer);
      warp_release(bar + 8 * B_PE);
      if (STOP <= 2 + 3 * layer) return;
      {
        uint4 xr[4], st[4];
        const int c = opaque_tid() - 256;
        const SumAddr sa = conv_sum_addr(sb, c);
        conv_prep_load(sb, layer, cta, c, xr, st);
        conv_prep<true>(sb, layer, cta, c, xr, st, sa);
        if (layer == 1 && ht == 0) TS(62);
        const bf16* xup = g_xT + (size_t)(2 * layer * DM + cta) * LSEQ + (c + 128) * 8;
        const int ahead = layer ? S_AHEAD1 : S_AHEAD0;
        mbar_wait(bar + 8 * (B_U + 3), layer);
        if (ahead == 2) {
          conv_sums(sa, 1, c);
          fence_async_smem();
          bar_arrive(8, 256);
        }
        st[0] = ldcg128(xup);
#pragma unroll
        for (int lc = 0; lc < 4; lc++) {
          if (lc < 3 && lc + ahead < 4) {
            conv_sums(sa, lc + ahead, c);
            fence_async_smem();
            bar_arrive(7 + lc + ahead, 256);
            sched_fence<4>();
          }
          if (lc < 3) st[lc + 1] = ldcg128(xup + (lc + 1) * 128 * LSEQ);
          conv_epi(sb, layer, cta, lc, c, xr[lc], st[lc]);
          warp_release(bar + 8 * (B_E + lc));
          sched_fence<5>();
          if (layer == 1 && lc == 3 && ht == 0) TS(38);
        }
      }
      if (layer == 0 && STOP > 3) {
        const int c1 = role_id();
        stats_publish(sb, 1, role_rb(c1), role_hg(c1), opaque_tid() - 256, part_tag(lds32(sb + SM_EP), 2));
        delay<D_ST>();
        stats_gather(sb, role_rb(c1), opaque_tid() - 256, part_tag(lds32(sb + SM_EP), 2));
        if (ht == 0) TS(25);
        if (!HALO_W14) halo_receive(sb, 1, role_rb(c1), role_hg(c1), opaque_tid() - 256);
      }
    }
  } else {
    asm volatile("setmaxnreg.dec.sync.aligned.u32 %0;" ::"n"(512 - 2 * R_CONS - R_HELP));
    const int cta = role_id(), rb = role_rb(cta), hg = role_hg(cta), rb2 = role_rb2(cta), q2 = role_q2(cta);
    bar_sync(0, NTHREADS);
    if (warp != 12) {
      mbar_wait(bar + 8 * B_EP, 0);
      const uint32_t tag = lds32(sb + SM_EP) % 7 + 1;
      mbar_wait(bar + 8 * B_CW, 0);
      colsum_publish(sb, rb, hg, tid - 416, tag);
      if (tid == 416) TS(50);
      delay<D_CS>();
      colsum_gather(sb, hg, tid - 416, tag);
      __syncwarp();
      if (tid == 416) TS(55);
    }
    if (elect_one()) mbar_arrive(bar + 8 * B_CSF);
    if (warp == 12) {
      if (elect_one()) {
        unsigned epoch = 0;
#pragma unroll 1
        for (int layer = 0; layer < 2; layer++) {
          auto ld_w = [&](int c, int slot) {
            const uint32_t b = bar + 8 * (B_KVF + c);
            mbar_expect(b, 24576);
            tma_ld3(sb + SM_W + slot * 24576, &p.mapW3, hg * 64, c * 64, 0, b);
          };
          if (layer == 0) {
            mbar_wait(bar + 8 * (B_KVF + 2), 0);
            if (rb2 < 4) tma_prefetch2(&p.mapWo128, q2 * 64, rb2 * 128);
            asm volatile("prefetch.tensormap [%0];" ::"l"(&p.mapO) : "memory");
            asm volatile("prefetch.tensormap [%0];" ::"l"(&p.mapO128) : "memory");
            asm volatile("prefetch.tensormap [%0];" ::"l"(&p.mapXT) : "memory");
            asm volatile("prefetch.tensormap [%0];" ::"l"(&p.mapXT3) : "memory");
            mbar_wait(bar + 8 * B_EP, 0);
            epoch = lds32(sb + SM_EP);
          } else {
            mbar_wait(bar + 8 * (B_U + 3), 0);
            ld_w(0, 0); ld_w(1, 1); ld_w(2, 2);
          }
          {
            int slot = 0;
#pragma unroll 1
            for (int c = 3; c < 8; c++) {
              mbar_wait(bar + 8 * (B_KVE + c - 3), layer);
              ld_w(c, slot);
              slot = slot == 2 ? 0 : slot + 1;
            }
          }
          if (STOP <= 1 + 3 * layer) return;
          const int early = layer ? WO_E1 : WO_E0;
          mbar_wait(bar + 8 * B_STF, layer);
          fence_async_smem();
          mbar_expect(bar + 8 * B_WOF, 65536);
#pragma unroll
          for (int c = 0; c < 4; c++) if (c < early) tma_ld(sb + SM_WO + c * 16384, &p.mapWo128, q2 * 64, c * 128, bar + 8 * B_WOF);
          mbar_wait(bar + 8 * B_QDONE, layer);
          mbar_wait(bar + 8 * B_HF, layer);
#pragma unroll
          for (int c = 0; c < 4; c++) if (c >= early) tma_ld(sb + SM_WO + c * 16384, &p.mapWo128, q2 * 64, c * 128, bar + 8 * B_WOF);
          {
            const uint32_t b = bar + 8 * B_RF;
            mbar_expect(b, 16384);
            if (layer == 0) tma_ld(sb + SM_R, &p.mapX128, (rb2 >> 3) * DM + q2 * 64, (rb2 & 7) * 128, b);
            else tma_ld3(sb + SM_R, &p.mapXT3, 0, DM + q2 * 64, rb2 * 2, b);
          }
#pragma unroll
          for (int c = 0; c < 8; c++) mbar_expect(bar + 8 * (B_OF + c), 16384);
          spin_until(&g_cnt[(C_O + rb2) * 32], (2 * epoch + layer + 1) * 16);
          fence_async_global();
#pragma unroll
          for (int c = 0; c < 8; c++) {
            if (c == 6) { mbar_wait(bar + 8 * B_OST, layer); fence_async_smem(); }
            tma_ld(sb + sm_o(c), &p.mapO128, c * 64, rb2 * 128, bar + 8 * (B_OF + c));
          }
          if (STOP <= 3 + 3 * layer) return;
        }
      }
    } else if (warp == 13) {
      if (elect_one() && STOP > 1) {
        const unsigned target = (lds32(sb + SM_EP) + 1) * NCTA;
        mbar_wait(bar + 8 * B_RE, 0);
        spin_until(&g_cnt[C_CS * 32 + 2], 2 * target);
        mbar_arrive(bar + 8 * B_XV);
        if (STOP <= 3) return;
        auto ld_x = [&](int c) { tma_ld3(sb + SM_X + c * 16384, &p.mapXT3, 0, DM + c * 64, rb * 2, bar + 8 * (B_XF + c)); };
#pragma unroll
        for (int c = 0; c < 8; c++) mbar_expect(bar + 8 * (B_XF + c), 16384);
        spin_until(&g_cnt[C_G1 * 32], target);
        fence_async_global();
        fence_async_smem();
        ld_x(0); ld_x(1);
        int done = 1, it = 0;
        while (done < 4) {
          const uint4 v = ld_tagged((const uint4*)&g_cnt[C_G1 * 32]);
          const int n = 4 + ((int)(v.y - target) >> 31) + ((int)(v.z - target) >> 31) + ((int)(v.w - target) >> 31);
          if (n == done) { if (++it > (1 << 23)) __trap(); continue; }
          if (n == 4) TS(44);
          fence_async_global();
          fence_async_smem();
          if (done == 1) { ld_x(2); ld_x(3); }
          const int h = hg >> 2;
          if (done < 3 && n >= 3) ld_x(4 + h);
          if (n == 4) ld_x(6 + h);
          if (done < 3 && n >= 3) ld_x(5 - h);
          if (n == 4) ld_x(7 - h);
          done = n;
        }
        if (STOP <= 4) return;
        mbar_wait(bar + 8 * B_RE, 1);
        spin_until(&g_cnt[C_CS * 32 + 3], 2 * target);
        mbar_arrive(bar + 8 * B_XV);
      }
    } else if (warp == 15) {
      mbar_wait(bar + 8 * B_EP, 0);
      const unsigned epoch = lds32(sb + SM_EP);
#pragma unroll 1
      for (int layer = 0; layer < 2; layer++) {
        mbar_wait(bar + 8 * (B_KVF + FILL_AT), layer);
#pragma unroll
        for (int k = 0; k < 8; k++) ((uint4*)(g_xT + (size_t)(2 * layer * DM + cta) * LSEQ))[32 * k + lane] = make_uint4(~0u, ~0u, ~0u, ~0u);
        mbar_wait(bar + 8 * (B_KVF + FILL_AT + 1), layer);
#pragma unroll
        for (int k = 0; k < 16; k++)
          ((uint4*)(g_xT + (size_t)(3 * DM + cv_chan(cta, 3 - (k >> 2))) * LSEQ))[128 * layer + 32 * (k & 3) + lane] = make_uint4(~0u, ~0u, ~0u, ~0u);
        if (lane < 4) ((uint4*)g_stats)[layer * 512 + cta * 4 + lane] = make_uint4(0, 0, 0, 0);
        __syncwarp();
        if (elect_one()) {
          red_release(&g_cnt[C_CS * 32 + layer]);
          spin_until(&g_cnt[C_CS * 32 + layer], (epoch + 1) * NCTA);
          mbar_arrive(bar + 8 * B_ZF);
          if (layer == 0 && STOP > 2) {
#pragma unroll
            for (int lc = 0; lc < 4; lc++) {
              mbar_wait(bar + 8 * (B_E + lc), 0);
              fence_reader();
              bulk_st(g_xT + (size_t)(DM + cv_chan(cta, lc)) * LSEQ, sb + cv_s(lc), 4096);
              bulk_commit();
              bulk_wait_all();
              red_relaxed(&g_cnt[C_G1 * 32 + lc]);
              if (lc == 3) TS(18);
            }
          }
        }
        __syncwarp();
        if (STOP <= 3) return;
      }
    } else if (warp == 14) {
      mbar_wait(bar + 8 * B_EP, 0);
      const unsigned epoch = lds32(sb + SM_EP);
#pragma unroll 1
      for (int layer = 0; layer < 2; layer++) {
        if (STOP <= 3 * layer) return;
        if (HALO_W14) halo_receive1(sb, layer, rb, hg, opaque_tid() & 31, 2 * epoch + layer + 1);
        if (STOP <= 1 + 3 * layer) return;
        mbar_wait(bar + 8 * B_ZF, layer);
        proj_stats(sb, layer, rb2, q2, opaque_tid() & 31, part_tag(epoch, 2 * layer + 1));
        if (layer == 1 && lane == 0) TS(5);
        delay<D_PREP>();
        if (lane == 0) mbar_arrive(bar + 8 * B_GB);
      }
    }
  }
}

typedef CUresult (*EncodeFn)(CUtensorMap*, CUtensorMapDataType, cuuint32_t, void*, const cuuint64_t*, const cuuint64_t*,
                             const cuuint32_t*, const cuuint32_t*, CUtensorMapInterleave, CUtensorMapSwizzle,
                             CUtensorMapL2promotion, CUtensorMapFloatOOBfill);

static void make_map(EncodeFn enc, CUtensorMap* m, void* ptr, uint64_t cols, uint64_t rows, uint32_t box_rows) {
  cuuint64_t dims[2] = {cols, rows};
  cuuint64_t strides[1] = {cols * 2};
  cuuint32_t box[2] = {64, box_rows};
  cuuint32_t es[2] = {1, 1};
  enc(m, CU_TENSOR_MAP_DATA_TYPE_BFLOAT16, 2, ptr, dims, strides, box, es, CU_TENSOR_MAP_INTERLEAVE_NONE,
      CU_TENSOR_MAP_SWIZZLE_128B, CU_TENSOR_MAP_L2_PROMOTION_L2_128B, CU_TENSOR_MAP_FLOAT_OOB_FILL_NONE);
}
static void make_map3(EncodeFn enc, CUtensorMap* m, void* ptr, uint64_t d0, uint64_t cols, uint64_t rows, uint64_t blk_stride,
                      uint64_t nblocks, uint32_t nblk, uint32_t box_rows = 64) {
  cuuint64_t dims[3] = {d0, rows, nblocks};
  cuuint64_t strides[2] = {cols * 2, blk_stride * 2};
  cuuint32_t box[3] = {64, box_rows, nblk};
  cuuint32_t es[3] = {1, 1, 1};
  enc(m, CU_TENSOR_MAP_DATA_TYPE_BFLOAT16, 3, ptr, dims, strides, box, es, CU_TENSOR_MAP_INTERLEAVE_NONE,
      CU_TENSOR_MAP_SWIZZLE_128B, CU_TENSOR_MAP_L2_PROMOTION_L2_128B, CU_TENSOR_MAP_FLOAT_OOB_FILL_NONE);
}

extern "C" void kernel_launch(void* const* d_in, const int* in_sizes, int n_in, void* d_out, int out_size) {
  static Params prm;
  static void* cached[13] = {nullptr};
  static bool attr_done = false;
  bool same = attr_done && cached[12] == d_out;
  for (int i = 0; i < 12 && same; i++) same = cached[i] == d_in[i];
  if (!same) {
    void* fn = nullptr;
    cudaDriverEntryPointQueryResult qr;
    cudaGetDriverEntryPoint("cuTensorMapEncodeTiled", &fn, cudaEnableDefault, &qr);
    EncodeFn enc = (EncodeFn)fn;
    void *pO, *pXT;
    cudaGetSymbolAddress(&pO, g_O);
    cudaGetSymbolAddress(&pXT, g_xT);
    make_map(enc, &prm.mapO, pO, DM, LSEQ, 16);
    make_map(enc, &prm.mapXT, pXT, LSEQ, 4 * DM, 64);
    prm.out = (bf16*)d_out;
    make_map(enc, &prm.mapX128, d_in[0], 2 * DM, LSEQ / 2, 128);
    make_map(enc, &prm.mapWo128, d_in[2], DM, DM, 128);
    make_map(enc, &prm.mapO128, pO, DM, LSEQ, 128);
    make_map3(enc, &prm.mapW3, d_in[1], DM, 3 * DM, DM, DM, 3, 3);
    make_map3(enc, &prm.mapW3h, d_in[1], DM, 3 * DM, DM, DM, 3, 3, 32);
    make_map3(enc, &prm.mapXT3, pXT, 64, LSEQ, 4 * DM, 64, 32, 2);
    prm.a_re = (const bf16*)d_in[4]; prm.a_im = (const bf16*)d_in[5];
    prm.b_re = (const bf16*)d_in[6]; prm.b_im = (const bf16*)d_in[7];
    prm.c_re = (const bf16*)d_in[8]; prm.c_im = (const bf16*)d_in[9];
    prm.log_dt = (const bf16*)d_in[10]; prm.dskip = (const bf16*)d_in[11];
    cudaFuncSetAttribute(fused_kernel, cudaFuncAttributeMaxDynamicSharedMemorySize, SM_TOTAL);
    for (int i = 0; i < 12; i++) cached[i] = d_in[i];
    cached[12] = d_out;
    attr_done = true;
  }
  prm.stop = 100;
    fused_kernel<<<NCTA, NTHREADS, SM_TOTAL>>>(prm);
}
```

```cpp
#include <cuda_runtime.h>
#include <cuda_bf16.h>
#include <cuda.h>
#include <stdint.h>

typedef __nv_bfloat16 bf16;

constexpr int LSEQ = 2048;
constexpr int DM = 512;
constexpr int NCTA = 128;
constexpr int NTHREADS = 512;
#define RR 0
#define KG_PRE 2
#define WO_E0 4
#define WO_E1 2
#define FILL_AT 6
#define EXP_LATE 1
#define RFENCE 1
#define D_FIN 500
#define D_PREP 600
#define D_PST 0
#define D_HALO 500
#define STAG0 2
#define STAG1 2
#define D_ST 500
#define TLAYER 1
#define KG_PD 1
#define SUM_F32 0
#define CS_LATE0 0
#define D_HALO1 0
#define KG_START 0
#define S_AHEAD0 1
#define S_AHEAD1 2
#define PAUSE 2
#define PARK_FIRST 0
#define P_UNROLL_N 1
constexpr int P_UNROLL = P_UNROLL_N;
#define PUB 1
#define X_ORDER 1
#define CS_STEP 1
#define D_FIN2 400
#define FIN_D0 2
#define QD_AT 1
#define G_WAIT 2
#define HALO_W14 1
#define D_START 200
#define D_CS 400
#define D_ST0 500
#define KG_LAST 0
#define X_JIT 0
#define KG_GATE 2
#define R_CONS 192
#define R_HELP 88

constexpr int SM_X = 0;
constexpr int SM_W = 131072;
constexpr int SM_KVX = SM_X;
constexpr int SM_WO = SM_X + 16384;
constexpr int SM_OST = SM_W + 49152;
__host__ __device__ constexpr int sm_o(int c) { return c < 7 ? SM_X + (5 + c) * 16384 : SM_KVX; }
constexpr int SM_R = 196608;
constexpr int SM_T = 212992;
constexpr int SM_KC = 217088;
constexpr int KC_STRIDE = 648;
constexpr int SM_CS = SM_KC + 4 * KC_STRIDE * 2;
constexpr int SM_CW = SM_R + 8192;
constexpr int SM_EP = SM_CS + 768;
constexpr int SM_BAR = SM_EP + 16;
constexpr int SM_T2 = SM_BAR + 896;
constexpr int SM_HALO = SM_T2 + 4096;
constexpr int SM_ST = SM_HALO + 3072;
constexpr int SM_TOTAL = SM_HALO + 4096;
static_assert(SM_TOTAL <= 232448, "shared memory");

constexpr int CV_UH = 140 * 16;
constexpr int CV_PECH = 1120 * 4;
constexpr int CV_PBW = 2112 * 2;
__host__ __device__ constexpr int cv_s(int lc) { return SM_X + lc * 32768; }
__host__ __device__ constexpr int cv_u(int lc) { return cv_s(lc) + 4096; }
__host__ __device__ constexpr int cv_pe(int lc) { return cv_u(lc) + 2 * CV_UH; }
__host__ __device__ constexpr int cv_pb(int lc) { return cv_pe(lc) + CV_PECH; }
__host__ __device__ constexpr int cv_ft(int lc) { return cv_pb(lc) + 4 * CV_PBW; }
static_assert(cv_ft(0) + 1024 <= 32768, "conv buffers");
__host__ __device__ constexpr int cv_chan(int cta, int lc) { return cta + 128 * lc; }

enum {
  B_XF = 0,
  B_KVF = 8,
  B_OF = 16,
  B_WOF = 24,
  B_T = 31,
  B_RF = 28,
  B_RE = 29,
  B_CW = 30,
  B_GB = 35,
  B_EP = 36,
  B_ZF = 37,
  B_XV = 39,
  B_SD = 38,
  B_KVE = 40,
  B_OST = 46,
  B_QDONE = 47,
  B_PDONE = 48,
  B_S = 50,
  B_E = 54,
  B_P = 58,
  B_PE = 62,
  B_STF = 63,
  B_CSF = 64,
  B_HF = 65,
  B_U = 70,
  B_AD = 75,
  B_PS = 74,
  B_COUNT = 80
};

enum {
  C_CS = 0,
  C_G1 = 2,
  C_O = 4,
  C_COUNT = 20
};

__device__ __align__(128) unsigned g_cnt[C_COUNT * 32];
__device__ __align__(1024) bf16 g_O[LSEQ * DM];
__device__ __align__(1024) bf16 g_xT[4 * DM * LSEQ];
__device__ __align__(1024) uint32_t g_stats[2 * LSEQ];
__device__ __align__(1024) uint4 g_colsum[8 * 16 * 48];
__device__ __align__(1024) uint4 g_halo[16 * 8 * 192];
__device__ __align__(1024) uint2 g_part[16 * 8 * 128];
#define TS(i) do { } while (0)

#define ATS(i, th) do { } while (0)
#define KTS(i) do { if (ht == 0) TS(i); } while (0)
#define FTS(i) do { } while (0)
#define LTS(i) do { } while (0)

#define STOP 100

struct Params {
  CUtensorMap mapO, mapXT, mapX128, mapWo128, mapO128, mapW3, mapW3h, mapXT3;
  const bf16 *a_re, *a_im, *b_re, *b_im, *c_re, *c_im, *log_dt, *dskip;
  bf16* out;
  int stop;
};

__device__ __forceinline__ uint32_t s32(const void* p) { return (uint32_t)__cvta_generic_to_shared(p); }
__device__ __forceinline__ void mbar_init(uint32_t b, int c) { asm volatile("mbarrier.init.shared::cta.b64 [%0], %1;" ::"r"(b), "r"(c) : "memory"); }
__device__ __forceinline__ void mbar_expect(uint32_t b, int bytes) { asm volatile("mbarrier.arrive.expect_tx.shared::cta.b64 _, [%0], %1;" ::"r"(b), "r"(bytes) : "memory"); }
__device__ __forceinline__ void mbar_arrive(uint32_t b) { asm volatile("mbarrier.arrive.shared::cta.b64 _, [%0];" ::"r"(b) : "memory"); }
__device__ __forceinline__ void mbar_arrive_if(uint32_t b, bool c) {
  asm volatile("{\n.reg .pred p;\nsetp.ne.u32 p, %1, 0;\n@p mbarrier.arrive.shared::cta.b64 _, [%0];\n}" ::"r"(b), "r"((uint32_t)c) : "memory");
}
__device__ __forceinline__ void mbar_wait(uint32_t b, int parity) {
  asm volatile("{\n.reg .pred p;\nWAIT_LOOP:\nmbarrier.try_wait.parity.shared::cta.b64 p, [%0], %1;\n@p bra WAIT_DONE;\nbra WAIT_LOOP;\nWAIT_DONE:\n}" ::"r"(b), "r"(parity) : "memory");
}
template <int N> __device__ __forceinline__ void delay() {
  if constexpr (N > 0) {
    uint32_t t0, t;
    asm volatile("mov.u32 %0, %%clock;" : "=r"(t0));
    do { asm volatile("mov.u32 %0, %%clock;" : "=r"(t)); } while (t - t0 < N);
  }
}
#define SF 3
template <int ID> __device__ __forceinline__ void sched_fence() {
  if constexpr ((SF >> ID) & 1)
    asm volatile("{\n.reg .pred p;\n.reg .u32 t;\nsetp.eq.u32 p, %0, 0;\n@p mov.u32 t, %%clock;\n@p st.shared.u32 [%0], t;\n}" ::"r"(gridDim.x) : "memory");
}
#define KEEP 0xf
template <int ID> __device__ __forceinline__ void tensor_keepalive() {
  if constexpr ((KEEP >> ID) & 1)
    asm volatile("{\n.reg .pred p;\n.reg .f32 a, b, c, d, z;\nmov.f32 z, 0f00000000;\nsetp.eq.u32 p, %0, 0;\n"
                 "mma.sync.aligned.m16n8k8.row.col.f32.bf16.bf16.f32 {a,b,c,d}, {%0,%0}, {%0}, {z,z,z,z};\n@p st.shared.f32 [%0], a;\n}" ::"r"(gridDim.x) : "memory");
}
__device__ __forceinline__ int opaque_tid() { int v; asm volatile("mov.u32 %0, %%tid.x;" : "=r"(v)); return v; }
__device__ __forceinline__ bool elect_one() {
  uint32_t r;
  asm volatile("{\n.reg .pred p;\nelect.sync _|p, 0xffffffff;\nselp.u32 %0, 1, 0, p;\n}" : "=r"(r));
  return r != 0;
}
__device__ __forceinline__ void tma_ld(uint32_t dst, const CUtensorMap* m, int c0, int c1, uint32_t bar) {
  asm volatile("cp.async.bulk.tensor.2d.shared::cluster.global.mbarrier::complete_tx::bytes [%0], [%1, {%3, %4}], [%2];"
               ::"r"(dst), "l"(m), "r"(bar), "r"(c0), "r"(c1) : "memory");
}
__device__ __forceinline__ void tma_ld3(uint32_t dst, const CUtensorMap* m, int c0, int c1, int c2, uint32_t bar) {
  asm volatile("cp.async.bulk.tensor.3d.shared::cluster.global.mbarrier::complete_tx::bytes [%0], [%1, {%3, %4, %5}], [%2];"
               ::"r"(dst), "l"(m), "r"(bar), "r"(c0), "r"(c1), "r"(c2) : "memory");
}
__device__ __forceinline__ void tma_prefetch2(const CUtensorMap* m, int c0, int c1) {
  asm volatile("cp.async.bulk.prefetch.tensor.2d.L2.global.tile [%0, {%1, %2}];" ::"l"(m), "r"(c0), "r"(c1) : "memory");
}
__device__ __forceinline__ void tma_prefetch3(const CUtensorMap* m, int c0, int c1, int c2) {
  asm volatile("cp.async.bulk.prefetch.tensor.3d.L2.global.tile [%0, {%1, %2, %3}];" ::"l"(m), "r"(c0), "r"(c1), "r"(c2) : "memory");
}
__device__ __forceinline__ void tma_st(const CUtensorMap* m, int c0, int c1, uint32_t src) {
  asm volatile("cp.async.bulk.tensor.2d.global.shared::cta.bulk_group [%0, {%2, %3}], [%1];" ::"l"(m), "r"(src), "r"(c0), "r"(c1) : "memory");
}
__device__ __forceinline__ void bulk_ld(uint32_t dst, const void* src, int bytes, uint32_t bar) {
  asm volatile("cp.async.bulk.shared::cluster.global.mbarrier::complete_tx::bytes [%0], [%1], %2, [%3];" ::"r"(dst), "l"(src), "r"(bytes), "r"(bar) : "memory");
}
__device__ __forceinline__ void bulk_st(void* dst, uint32_t src, int bytes) {
  asm volatile("cp.async.bulk.global.shared::cta.bulk_group [%0], [%1], %2;" ::"l"(dst), "r"(src), "r"(bytes) : "memory");
}
__device__ __forceinline__ void bulk_red_add_f32(void* dst, uint32_t src, int bytes) {
  asm volatile("cp.reduce.async.bulk.global.shared::cta.bulk_group.add.f32 [%0], [%1], %2;" ::"l"(dst), "r"(src), "r"(bytes) : "memory");
}
__device__ __forceinline__ void bulk_commit() { asm volatile("cp.async.bulk.commit_group;" ::: "memory"); }
__device__ __forceinline__ void bulk_wait_all() { asm volatile("cp.async.bulk.wait_group 0;" ::: "memory"); }
__device__ __forceinline__ void fence_async_smem() { asm volatile("fence.proxy.async.shared::cta;" ::: "memory"); }
__device__ __forceinline__ void fence_writer() { if (!RFENCE) fence_async_smem(); }
__device__ __forceinline__ void fence_reader() { if (RFENCE) fence_async_smem(); }
__device__ __forceinline__ void fence_async_global() { asm volatile("fence.proxy.async.global;" ::: "memory"); }
__device__ __forceinline__ void bar_sync(int id, int n) { asm volatile("bar.sync %0, %1;" ::"r"(id), "r"(n) : "memory"); }
__device__ __forceinline__ void bar_arrive(int id, int n) { asm volatile("bar.arrive %0, %1;" ::"r"(id), "r"(n) : "memory"); }
__device__ __forceinline__ void wg_fence() { asm volatile("wgmma.fence.sync.aligned;" ::: "memory"); }
__device__ __forceinline__ void wg_commit() { asm volatile("wgmma.commit_group.sync.aligned;" ::: "memory"); }
template <int N> __device__ __forceinline__ void wg_wait() { asm volatile("wgmma.wait_group.sync.aligned %0;" ::"n"(N) : "memory"); }
__device__ __forceinline__ uint64_t mkdesc(uint32_t addr, uint32_t lbo, uint32_t sbo, int sw) {
  return (uint64_t)((addr & 0x3FFFF) >> 4) | ((uint64_t)(lbo >> 4) << 16) | ((uint64_t)(sbo >> 4) << 32) | ((uint64_t)sw << 62);
}
__device__ __forceinline__ void ldsm4(uint32_t* r, uint32_t a) {
  asm volatile("ldmatrix.sync.aligned.m8n8.x4.shared.b16 {%0,%1,%2,%3}, [%4];" : "=r"(r[0]), "=r"(r[1]), "=r"(r[2]), "=r"(r[3]) : "r"(a) : "memory");
}
__device__ __forceinline__ void ldsm4t(uint32_t* r, uint32_t a) {
  asm volatile("ldmatrix.sync.aligned.m8n8.x4.trans.shared.b16 {%0,%1,%2,%3}, [%4];" : "=r"(r[0]), "=r"(r[1]), "=r"(r[2]), "=r"(r[3]) : "r"(a) : "memory");
}
__device__ __forceinline__ void stsm4(uint32_t a, uint32_t r0, uint32_t r1, uint32_t r2, uint32_t r3) {
  asm volatile("stmatrix.sync.aligned.m8n8.x4.shared.b16 [%0], {%1,%2,%3,%4};" ::"r"(a), "r"(r0), "r"(r1), "r"(r2), "r"(r3) : "memory");
}
__device__ __forceinline__ void stsm4t(uint32_t a, uint32_t r0, uint32_t r1, uint32_t r2, uint32_t r3) {
  asm volatile("stmatrix.sync.aligned.m8n8.x4.trans.shared.b16 [%0], {%1,%2,%3,%4};" ::"r"(a), "r"(r0), "r"(r1), "r"(r2), "r"(r3) : "memory");
}
__device__ __forceinline__ uint32_t movm_t(uint32_t a) { uint32_t r; asm volatile("movmatrix.sync.aligned.m8n8.trans.b16 %0, %1;" : "=r"(r) : "r"(a)); return r; }
__device__ __forceinline__ uint32_t lds32(uint32_t a) { uint32_t v; asm volatile("ld.shared.b32 %0, [%1];" : "=r"(v) : "r"(a) : "memory"); return v; }
__device__ __forceinline__ float2 lds64f(uint32_t a) { float2 v; asm volatile("ld.shared.v2.f32 {%0,%1}, [%2];" : "=f"(v.x), "=f"(v.y) : "r"(a) : "memory"); return v; }
__device__ __forceinline__ float4 lds128f(uint32_t a) { float4 v; asm volatile("ld.shared.v4.f32 {%0,%1,%2,%3}, [%4];" : "=f"(v.x), "=f"(v.y), "=f"(v.z), "=f"(v.w) : "r"(a) : "memory"); return v; }
__device__ __forceinline__ uint4 lds128(uint32_t a) { uint4 v; asm volatile("ld.shared.v4.b32 {%0,%1,%2,%3}, [%4];" : "=r"(v.x), "=r"(v.y), "=r"(v.z), "=r"(v.w) : "r"(a) : "memory"); return v; }
__device__ __forceinline__ void sts128(uint32_t a, uint4 v) { asm volatile("st.shared.v4.b32 [%0], {%1,%2,%3,%4};" ::"r"(a), "r"(v.x), "r"(v.y), "r"(v.z), "r"(v.w) : "memory"); }
__device__ __forceinline__ void sts128f(uint32_t a, float x, float y, float z, float w) { asm volatile("st.shared.v4.f32 [%0], {%1,%2,%3,%4};" ::"r"(a), "f"(x), "f"(y), "f"(z), "f"(w) : "memory"); }
__device__ __forceinline__ void sts32f(uint32_t a, float v) { asm volatile("st.shared.f32 [%0], %1;" ::"r"(a), "f"(v) : "memory"); }
__device__ __forceinline__ void sts16(uint32_t a, uint16_t v) { asm volatile("st.shared.u16 [%0], %1;" ::"r"(a), "h"(v) : "memory"); }
__device__ __forceinline__ uint32_t lds16(uint32_t a) { uint16_t v; asm volatile("ld.shared.u16 %0, [%1];" : "=h"(v) : "r"(a) : "memory"); return v; }
__device__ __forceinline__ uint32_t packbf(float lo, float hi) { uint32_t r; asm("cvt.rn.bf16x2.f32 %0, %1, %2;" : "=r"(r) : "f"(hi), "f"(lo)); return r; }
__device__ __forceinline__ float bf_lo(uint32_t v) { return __uint_as_float(v << 16); }
__device__ __forceinline__ float bf_hi(uint32_t v) { return __uint_as_float(v & 0xffff0000u); }
__device__ __forceinline__ float ex2(float x) { float r; asm("ex2.approx.ftz.f32 %0, %1;" : "=f"(r) : "f"(x)); return r; }
__device__ __forceinline__ float rsqrt_approx(float x) { float r; asm("rsqrt.approx.ftz.f32 %0, %1;" : "=f"(r) : "f"(x)); return r; }
__device__ __forceinline__ float rcp_approx(float x) { float r; asm("rcp.approx.ftz.f32 %0, %1;" : "=f"(r) : "f"(x)); return r; }
__device__ __forceinline__ void mma_bf16(float* d, const uint32_t* a, uint32_t b0, uint32_t b1) {
  asm("mma.sync.aligned.m16n8k16.row.col.f32.bf16.bf16.f32 {%0,%1,%2,%3}, {%4,%5,%6,%7}, {%8,%9}, {%0,%1,%2,%3};"
               : "+f"(d[0]), "+f"(d[1]), "+f"(d[2]), "+f"(d[3]) : "r"(a[0]), "r"(a[1]), "r"(a[2]), "r"(a[3]), "r"(b0), "r"(b1));
}
__device__ __forceinline__ void mma_bf16_k8(float* d, uint32_t a0, uint32_t a1, uint32_t b) {
  asm("mma.sync.aligned.m16n8k8.row.col.f32.bf16.bf16.f32 {%0,%1,%2,%3}, {%4,%5}, {%6}, {%0,%1,%2,%3};"
      : "+f"(d[0]), "+f"(d[1]), "+f"(d[2]), "+f"(d[3]) : "r"(a0), "r"(a1), "r"(b));
}
__device__ __forceinline__ void red_release(unsigned* p) { asm volatile("red.release.gpu.global.add.u32 [%0], 1;" ::"l"(p) : "memory"); }
__device__ __forceinline__ void red_relaxed(unsigned* p) { asm volatile("red.relaxed.gpu.global.add.u32 [%0], 1;" ::"l"(p) : "memory"); }
__device__ __forceinline__ unsigned ld_relaxed(const unsigned* p) { unsigned v; asm volatile("ld.relaxed.gpu.global.u32 %0, [%1];" : "=r"(v) : "l"(p) : "memory"); return v; }
__device__ __forceinline__ void spin_until(const unsigned* p, unsigned target) {
  int it = 0;
  while ((int)(ld_relaxed(p) - target) < 0) {
    if (++it > (1 << 23)) __trap();
  }
}
__device__ __forceinline__ uint4 ldcg128(const void* p) { uint4 v; asm volatile("ld.global.cg.v4.b32 {%0,%1,%2,%3}, [%4];" : "=r"(v.x), "=r"(v.y), "=r"(v.z), "=r"(v.w) : "l"(p) : "memory"); return v; }
__device__ __forceinline__ uint4 ld_tagged(const uint4* p) { uint4 v; asm volatile("ld.relaxed.gpu.global.v4.u32 {%0,%1,%2,%3}, [%4];" : "=r"(v.x), "=r"(v.y), "=r"(v.z), "=r"(v.w) : "l"(p) : "memory"); return v; }
__device__ __forceinline__ uint2 ld_part(const uint2* p) { uint2 v; asm volatile("ld.relaxed.gpu.global.v2.u32 {%0,%1}, [%2];" : "=r"(v.x), "=r"(v.y) : "l"(p) : "memory"); return v; }
__device__ __forceinline__ void st_part(uint2* p, float s, float q, uint32_t tag) {
  if (PUB & 2) asm volatile("{\n.reg .b64 v, o;\nmov.b64 v, {%1,%2};\natom.relaxed.gpu.global.exch.b64 o, [%0], v;\n}" ::"l"(p), "r"(__float_as_uint(s)), "r"((__float_as_uint(q) & ~7u) | tag) : "memory");
  else asm volatile("st.relaxed.gpu.global.v2.u32 [%0], {%1,%2};" ::"l"(p), "r"(__float_as_uint(s)), "r"((__float_as_uint(q) & ~7u) | tag) : "memory");
}
__device__ __forceinline__ uint32_t part_tag(uint32_t epoch, int k) { return (4 * (epoch % 7) + k) % 7 + 1; }
__device__ __forceinline__ void st_tagged3(uint4* p, uint32_t a, uint32_t b, uint32_t c, uint32_t tag) { asm volatile("st.relaxed.gpu.global.v4.u32 [%0], {%1,%2,%3,%4};" ::"l"(p), "r"(a), "r"(b), "r"(c), "r"(tag) : "memory"); }
__device__ __forceinline__ uint32_t hadd2(uint32_t a, uint32_t b) { uint32_t r; asm("add.rn.bf16x2 %0, %1, %2;" : "=r"(r) : "r"(a), "r"(b)); return r; }
__device__ __forceinline__ uint32_t hfma2(uint32_t a, uint32_t b, uint32_t c) { uint32_t r; asm("fma.rn.bf16x2 %0, %1, %2, %3;" : "=r"(r) : "r"(a), "r"(b), "r"(c)); return r; }
__device__ __forceinline__ uint32_t hmul2(uint32_t a, uint32_t b) { uint32_t r; asm("mul.rn.bf16x2 %0, %1, %2;" : "=r"(r) : "r"(a), "r"(b)); return r; }

template<int N,int TB> __device__ __forceinline__ void wgmma_rs(float* d, const uint32_t* a, uint64_t db, int sd);
template<int N,int TA,int TB> __device__ __forceinline__ void wgmma_ss(float* d, uint64_t da, uint64_t db, int sd);
template<> __device__ __forceinline__ void wgmma_rs<128,0>(float* d, const uint32_t* a, uint64_t db, int sd) {
  asm volatile("{\n.reg .pred p;\nsetp.ne.b32 p, %69, 0;\nwgmma.mma_async.sync.aligned.m64n128k16.f32.bf16.bf16 {%0,%1,%2,%3,%4,%5,%6,%7,%8,%9,%10,%11,%12,%13,%14,%15,%16,%17,%18,%19,%20,%21,%22,%23,%24,%25,%26,%27,%28,%29,%30,%31,%32,%33,%34,%35,%36,%37,%38,%39,%40,%41,%42,%43,%44,%45,%46,%47,%48,%49,%50,%51,%52,%53,%54,%55,%56,%57,%58,%59,%60,%61,%62,%63}, {%64,%65,%66,%67}, %68, p, 1, 1, 0;\n}\n"
   : "+f"(d[0]),"+f"(d[1]),"+f"(d[2]),"+f"(d[3]),"+f"(d[4]),"+f"(d[5]),"+f"(d[6]),"+f"(d[7]),"+f"(d[8]),"+f"(d[9]),"+f"(d[10]),"+f"(d[11]),"+f"(d[12]),"+f"(d[13]),"+f"(d[14]),"+f"(d[15]),"+f"(d[16]),"+f"(d[17]),"+f"(d[18]),"+f"(d[19]),"+f"(d[20]),"+f"(d[21]),"+f"(d[22]),"+f"(d[23]),"+f"(d[24]),"+f"(d[25]),"+f"(d[26]),"+f"(d[27]),"+f"(d[28]),"+f"(d[29]),"+f"(d[30]),"+f"(d[31]),"+f"(d[32]),"+f"(d[33]),"+f"(d[34]),"+f"(d[35]),"+f"(d[36]),"+f"(d[37]),"+f"(d[38]),"+f"(d[39]),"+f"(d[40]),"+f"(d[41]),"+f"(d[42]),"+f"(d[43]),"+f"(d[44]),"+f"(d[45]),"+f"(d[46]),"+f"(d[47]),"+f"(d[48]),"+f"(d[49]),"+f"(d[50]),"+f"(d[51]),"+f"(d[52]),"+f"(d[53]),"+f"(d[54]),"+f"(d[55]),"+f"(d[56]),"+f"(d[57]),"+f"(d[58]),"+f"(d[59]),"+f"(d[60]),"+f"(d[61]),"+f"(d[62]),"+f"(d[63])
   : "r"(a[0]), "r"(a[1]), "r"(a[2]), "r"(a[3]), "l"(db), "r"(sd));
}
template<> __device__ __forceinline__ void wgmma_rs<120,0>(float* d, const uint32_t* a, uint64_t db, int sd) {
  asm volatile("{\n.reg .pred p;\nsetp.ne.b32 p, %65, 0;\nwgmma.mma_async.sync.aligned.m64n120k16.f32.bf16.bf16 {%0,%1,%2,%3,%4,%5,%6,%7,%8,%9,%10,%11,%12,%13,%14,%15,%16,%17,%18,%19,%20,%21,%22,%23,%24,%25,%26,%27,%28,%29,%30,%31,%32,%33,%34,%35,%36,%37,%38,%39,%40,%41,%42,%43,%44,%45,%46,%47,%48,%49,%50,%51,%52,%53,%54,%55,%56,%57,%58,%59}, {%60,%61,%62,%63}, %64, p, 1, 1, 0;\n}\n"
   : "+f"(d[0]),"+f"(d[1]),"+f"(d[2]),"+f"(d[3]),"+f"(d[4]),"+f"(d[5]),"+f"(d[6]),"+f"(d[7]),"+f"(d[8]),"+f"(d[9]),"+f"(d[10]),"+f"(d[11]),"+f"(d[12]),"+f"(d[13]),"+f"(d[14]),"+f"(d[15]),"+f"(d[16]),"+f"(d[17]),"+f"(d[18]),"+f"(d[19]),"+f"(d[20]),"+f"(d[21]),"+f"(d[22]),"+f"(d[23]),"+f"(d[24]),"+f"(d[25]),"+f"(d[26]),"+f"(d[27]),"+f"(d[28]),"+f"(d[29]),"+f"(d[30]),"+f"(d[31]),"+f"(d[32]),"+f"(d[33]),"+f"(d[34]),"+f"(d[35]),"+f"(d[36]),"+f"(d[37]),"+f"(d[38]),"+f"(d[39]),"+f"(d[40]),"+f"(d[41]),"+f"(d[42]),"+f"(d[43]),"+f"(d[44]),"+f"(d[45]),"+f"(d[46]),"+f"(d[47]),"+f"(d[48]),"+f"(d[49]),"+f"(d[50]),"+f"(d[51]),"+f"(d[52]),"+f"(d[53]),"+f"(d[54]),"+f"(d[55]),"+f"(d[56]),"+f"(d[57]),"+f"(d[58]),"+f"(d[59])
   : "r"(a[0]), "r"(a[1]), "r"(a[2]), "r"(a[3]), "l"(db), "r"(sd));
}
template<> __device__ __forceinline__ void wgmma_rs<112,0>(float* d, const uint32_t* a, uint64_t db, int sd) {
  asm volatile("{\n.reg .pred p;\nsetp.ne.b32 p, %61, 0;\nwgmma.mma_async.sync.aligned.m64n112k16.f32.bf16.bf16 {%0,%1,%2,%3,%4,%5,%6,%7,%8,%9,%10,%11,%12,%13,%14,%15,%16,%17,%18,%19,%20,%21,%22,%23,%24,%25,%26,%27,%28,%29,%30,%31,%32,%33,%34,%35,%36,%37,%38,%39,%40,%41,%42,%43,%44,%45,%46,%47,%48,%49,%50,%51,%52,%53,%54,%55}, {%56,%57,%58,%59}, %60, p, 1, 1, 0;\n}\n"
   : "+f"(d[0]),"+f"(d[1]),"+f"(d[2]),"+f"(d[3]),"+f"(d[4]),"+f"(d[5]),"+f"(d[6]),"+f"(d[7]),"+f"(d[8]),"+f"(d[9]),"+f"(d[10]),"+f"(d[11]),"+f"(d[12]),"+f"(d[13]),"+f"(d[14]),"+f"(d[15]),"+f"(d[16]),"+f"(d[17]),"+f"(d[18]),"+f"(d[19]),"+f"(d[20]),"+f"(d[21]),"+f"(d[22]),"+f"(d[23]),"+f"(d[24]),"+f"(d[25]),"+f"(d[26]),"+f"(d[27]),"+f"(d[28]),"+f"(d[29]),"+f"(d[30]),"+f"(d[31]),"+f"(d[32]),"+f"(d[33]),"+f"(d[34]),"+f"(d[35]),"+f"(d[36]),"+f"(d[37]),"+f"(d[38]),"+f"(d[39]),"+f"(d[40]),"+f"(d[41]),"+f"(d[42]),"+f"(d[43]),"+f"(d[44]),"+f"(d[45]),"+f"(d[46]),"+f"(d[47]),"+f"(d[48]),"+f"(d[49]),"+f"(d[50]),"+f"(d[51]),"+f"(d[52]),"+f"(d[53]),"+f"(d[54]),"+f"(d[55])
   : "r"(a[0]), "r"(a[1]), "r"(a[2]), "r"(a[3]), "l"(db), "r"(sd));
}
template<> __device__ __forceinline__ void wgmma_rs<104,0>(float* d, const uint32_t* a, uint64_t db, int sd) {
  asm volatile("{\n.reg .pred p;\nsetp.ne.b32 p, %57, 0;\nwgmma.mma_async.sync.aligned.m64n104k16.f32.bf16.bf16 {%0,%1,%2,%3,%4,%5,%6,%7,%8,%9,%10,%11,%12,%13,%14,%15,%16,%17,%18,%19,%20,%21,%22,%23,%24,%25,%26,%27,%28,%29,%30,%31,%32,%33,%34,%35,%36,%37,%38,%39,%40,%41,%42,%43,%44,%45,%46,%47,%48,%49,%50,%51}, {%52,%53,%54,%55}, %56, p, 1, 1, 0;\n}\n"
   : "+f"(d[0]),"+f"(d[1]),"+f"(d[2]),"+f"(d[3]),"+f"(d[4]),"+f"(d[5]),"+f"(d[6]),"+f"(d[7]),"+f"(d[8]),"+f"(d[9]),"+f"(d[10]),"+f"(d[11]),"+f"(d[12]),"+f"(d[13]),"+f"(d[14]),"+f"(d[15]),"+f"(d[16]),"+f"(d[17]),"+f"(d[18]),"+f"(d[19]),"+f"(d[20]),"+f"(d[21]),"+f"(d[22]),"+f"(d[23]),"+f"(d[24]),"+f"(d[25]),"+f"(d[26]),"+f"(d[27]),"+f"(d[28]),"+f"(d[29]),"+f"(d[30]),"+f"(d[31]),"+f"(d[32]),"+f"(d[33]),"+f"(d[34]),"+f"(d[35]),"+f"(d[36]),"+f"(d[37]),"+f"(d[38]),"+f"(d[39]),"+f"(d[40]),"+f"(d[41]),"+f"(d[42]),"+f"(d[43]),"+f"(d[44]),"+f"(d[45]),"+f"(d[46]),"+f"(d[47]),"+f"(d[48]),"+f"(d[49]),"+f"(d[50]),"+f"(d[51])
   : "r"(a[0]), "r"(a[1]), "r"(a[2]), "r"(a[3]), "l"(db), "r"(sd));
}
template<> __device__ __forceinline__ void wgmma_rs<96,0>(float* d, const uint32_t* a, uint64_t db, int sd) {
  asm volatile("{\n.reg .pred p;\nsetp.ne.b32 p, %53, 0;\nwgmma.mma_async.sync.aligned.m64n96k16.f32.bf16.bf16 {%0,%1,%2,%3,%4,%5,%6,%7,%8,%9,%10,%11,%12,%13,%14,%15,%16,%17,%18,%19,%20,%21,%22,%23,%24,%25,%26,%27,%28,%29,%30,%31,%32,%33,%34,%35,%36,%37,%38,%39,%40,%41,%42,%43,%44,%45,%46,%47}, {%48,%49,%50,%51}, %52, p, 1, 1, 0;\n}\n"
   : "+f"(d[0]),"+f"(d[1]),"+f"(d[2]),"+f"(d[3]),"+f"(d[4]),"+f"(d[5]),"+f"(d[6]),"+f"(d[7]),"+f"(d[8]),"+f"(d[9]),"+f"(d[10]),"+f"(d[11]),"+f"(d[12]),"+f"(d[13]),"+f"(d[14]),"+f"(d[15]),"+f"(d[16]),"+f"(d[17]),"+f"(d[18]),"+f"(d[19]),"+f"(d[20]),"+f"(d[21]),"+f"(d[22]),"+f"(d[23]),"+f"(d[24]),"+f"(d[25]),"+f"(d[26]),"+f"(d[27]),"+f"(d[28]),"+f"(d[29]),"+f"(d[30]),"+f"(d[31]),"+f"(d[32]),"+f"(d[33]),"+f"(d[34]),"+f"(d[35]),"+f"(d[36]),"+f"(d[37]),"+f"(d[38]),"+f"(d[39]),"+f"(d[40]),"+f"(d[41]),"+f"(d[42]),"+f"(d[43]),"+f"(d[44]),"+f"(d[45]),"+f"(d[46]),"+f"(d[47])
   : "r"(a[0]), "r"(a[1]), "r"(a[2]), "r"(a[3]), "l"(db), "r"(sd));
}
template<> __device__ __forceinline__ void wgmma_rs<88,0>(float* d, const uint32_t* a, uint64_t db, int sd) {
  asm volatile("{\n.reg .pred p;\nsetp.ne.b32 p, %49, 0;\nwgmma.mma_async.sync.aligned.m64n88k16.f32.bf16.bf16 {%0,%1,%2,%3,%4,%5,%6,%7,%8,%9,%10,%11,%12,%13,%14,%15,%16,%17,%18,%19,%20,%21,%22,%23,%24,%25,%26,%27,%28,%29,%30,%31,%32,%33,%34,%35,%36,%37,%38,%39,%40,%41,%42,%43}, {%44,%45,%46,%47}, %48, p, 1, 1, 0;\n}\n"
   : "+f"(d[0]),"+f"(d[1]),"+f"(d[2]),"+f"(d[3]),"+f"(d[4]),"+f"(d[5]),"+f"(d[6]),"+f"(d[7]),"+f"(d[8]),"+f"(d[9]),"+f"(d[10]),"+f"(d[11]),"+f"(d[12]),"+f"(d[13]),"+f"(d[14]),"+f"(d[15]),"+f"(d[16]),"+f"(d[17]),"+f"(d[18]),"+f"(d[19]),"+f"(d[20]),"+f"(d[21]),"+f"(d[22]),"+f"(d[23]),"+f"(d[24]),"+f"(d[25]),"+f"(d[26]),"+f"(d[27]),"+f"(d[28]),"+f"(d[29]),"+f"(d[30]),"+f"(d[31]),"+f"(d[32]),"+f"(d[33]),"+f"(d[34]),"+f"(d[35]),"+f"(d[36]),"+f"(d[37]),"+f"(d[38]),"+f"(d[39]),"+f"(d[40]),"+f"(d[41]),"+f"(d[42]),"+f"(d[43])
   : "r"(a[0]), "r"(a[1]), "r"(a[2]), "r"(a[3]), "l"(db), "r"(sd));
}
template<> __device__ __forceinline__ void wgmma_rs<80,0>(float* d, const uint32_t* a, uint64_t db, int sd) {
  asm volatile("{\n.reg .pred p;\nsetp.ne.b32 p, %45, 0;\nwgmma.mma_async.sync.aligned.m64n80k16.f32.bf16.bf16 {%0,%1,%2,%3,%4,%5,%6,%7,%8,%9,%10,%11,%12,%13,%14,%15,%16,%17,%18,%19,%20,%21,%22,%23,%24,%25,%26,%27,%28,%29,%30,%31,%32,%33,%34,%35,%36,%37,%38,%39}, {%40,%41,%42,%43}, %44, p, 1, 1, 0;\n}\n"
   : "+f"(d[0]),"+f"(d[1]),"+f"(d[2]),"+f"(d[3]),"+f"(d[4]),"+f"(d[5]),"+f"(d[6]),"+f"(d[7]),"+f"(d[8]),"+f"(d[9]),"+f"(d[10]),"+f"(d[11]),"+f"(d[12]),"+f"(d[13]),"+f"(d[14]),"+f"(d[15]),"+f"(d[16]),"+f"(d[17]),"+f"(d[18]),"+f"(d[19]),"+f"(d[20]),"+f"(d[21]),"+f"(d[22]),"+f"(d[23]),"+f"(d[24]),"+f"(d[25]),"+f"(d[26]),"+f"(d[27]),"+f"(d[28]),"+f"(d[29]),"+f"(d[30]),"+f"(d[31]),"+f"(d[32]),"+f"(d[33]),"+f"(d[34]),"+f"(d[35]),"+f"(d[36]),"+f"(d[37]),"+f"(d[38]),"+f"(d[39])
   : "r"(a[0]), "r"(a[1]), "r"(a[2]), "r"(a[3]), "l"(db), "r"(sd));
}
template<> __device__ __forceinline__ void wgmma_rs<72,0>(float* d, const uint32_t* a, uint64_t db, int sd) {
  asm volatile("{\n.reg .pred p;\nsetp.ne.b32 p, %41, 0;\nwgmma.mma_async.sync.aligned.m64n72k16.f32.bf16.bf16 {%0,%1,%2,%3,%4,%5,%6,%7,%8,%9,%10,%11,%12,%13,%14,%15,%16,%17,%18,%19,%20,%21,%22,%23,%24,%25,%26,%27,%28,%29,%30,%31,%32,%33,%34,%35}, {%36,%37,%38,%39}, %40, p, 1, 1, 0;\n}\n"
   : "+f"(d[0]),"+f"(d[1]),"+f"(d[2]),"+f"(d[3]),"+f"(d[4]),"+f"(d[5]),"+f"(d[6]),"+f"(d[7]),"+f"(d[8]),"+f"(d[9]),"+f"(d[10]),"+f"(d[11]),"+f"(d[12]),"+f"(d[13]),"+f"(d[14]),"+f"(d[15]),"+f"(d[16]),"+f"(d[17]),"+f"(d[18]),"+f"(d[19]),"+f"(d[20]),"+f"(d[21]),"+f"(d[22]),"+f"(d[23]),"+f"(d[24]),"+f"(d[25]),"+f"(d[26]),"+f"(d[27]),"+f"(d[28]),"+f"(d[29]),"+f"(d[30]),"+f"(d[31]),"+f"(d[32]),"+f"(d[33]),"+f"(d[34]),"+f"(d[35])
   : "r"(a[0]), "r"(a[1]), "r"(a[2]), "r"(a[3]), "l"(db), "r"(sd));
}
template<> __device__ __forceinline__ void wgmma_rs<64,0>(float* d, const uint32_t* a, uint64_t db, int sd) {
  asm volatile("{\n.reg .pred p;\nsetp.ne.b32 p, %37, 0;\nwgmma.mma_async.sync.aligned.m64n64k16.f32.bf16.bf16 {%0,%1,%2,%3,%4,%5,%6,%7,%8,%9,%10,%11,%12,%13,%14,%15,%16,%17,%18,%19,%20,%21,%22,%23,%24,%25,%26,%27,%28,%29,%30,%31}, {%32,%33,%34,%35}, %36, p, 1, 1, 0;\n}\n"
   : "+f"(d[0]),"+f"(d[1]),"+f"(d[2]),"+f"(d[3]),"+f"(d[4]),"+f"(d[5]),"+f"(d[6]),"+f"(d[7]),"+f"(d[8]),"+f"(d[9]),"+f"(d[10]),"+f"(d[11]),"+f"(d[12]),"+f"(d[13]),"+f"(d[14]),"+f"(d[15]),"+f"(d[16]),"+f"(d[17]),"+f"(d[18]),"+f"(d[19]),"+f"(d[20]),"+f"(d[21]),"+f"(d[22]),"+f"(d[23]),"+f"(d[24]),"+f"(d[25]),"+f"(d[26]),"+f"(d[27]),"+f"(d[28]),"+f"(d[29]),"+f"(d[30]),"+f"(d[31])
   : "r"(a[0]), "r"(a[1]), "r"(a[2]), "r"(a[3]), "l"(db), "r"(sd));
}
template<> __device__ __forceinline__ void wgmma_ss<64,0,1>(float* d, uint64_t da, uint64_t db, int sd) {
  asm volatile("{\n.reg .pred p;\nsetp.ne.b32 p, %34, 0;\nwgmma.mma_async.sync.aligned.m64n64k16.f32.bf16.bf16 {%0,%1,%2,%3,%4,%5,%6,%7,%8,%9,%10,%11,%12,%13,%14,%15,%16,%17,%18,%19,%20,%21,%22,%23,%24,%25,%26,%27,%28,%29,%30,%31}, %32, %33, p, 1, 1, 0, 1;\n}\n"
   : "+f"(d[0]),"+f"(d[1]),"+f"(d[2]),"+f"(d[3]),"+f"(d[4]),"+f"(d[5]),"+f"(d[6]),"+f"(d[7]),"+f"(d[8]),"+f"(d[9]),"+f"(d[10]),"+f"(d[11]),"+f"(d[12]),"+f"(d[13]),"+f"(d[14]),"+f"(d[15]),"+f"(d[16]),"+f"(d[17]),"+f"(d[18]),"+f"(d[19]),"+f"(d[20]),"+f"(d[21]),"+f"(d[22]),"+f"(d[23]),"+f"(d[24]),"+f"(d[25]),"+f"(d[26]),"+f"(d[27]),"+f"(d[28]),"+f"(d[29]),"+f"(d[30]),"+f"(d[31])
   : "l"(da), "l"(db), "r"(sd));
}
template<> __device__ __forceinline__ void wgmma_ss<64,1,1>(float* d, uint64_t da, uint64_t db, int sd) {
  asm volatile("{\n.reg .pred p;\nsetp.ne.b32 p, %34, 0;\nwgmma.mma_async.sync.aligned.m64n64k16.f32.bf16.bf16 {%0,%1,%2,%3,%4,%5,%6,%7,%8,%9,%10,%11,%12,%13,%14,%15,%16,%17,%18,%19,%20,%21,%22,%23,%24,%25,%26,%27,%28,%29,%30,%31}, %32, %33, p, 1, 1, 1, 1;\n}\n"
   : "+f"(d[0]),"+f"(d[1]),"+f"(d[2]),"+f"(d[3]),"+f"(d[4]),"+f"(d[5]),"+f"(d[6]),"+f"(d[7]),"+f"(d[8]),"+f"(d[9]),"+f"(d[10]),"+f"(d[11]),"+f"(d[12]),"+f"(d[13]),"+f"(d[14]),"+f"(d[15]),"+f"(d[16]),"+f"(d[17]),"+f"(d[18]),"+f"(d[19]),"+f"(d[20]),"+f"(d[21]),"+f"(d[22]),"+f"(d[23]),"+f"(d[24]),"+f"(d[25]),"+f"(d[26]),"+f"(d[27]),"+f"(d[28]),"+f"(d[29]),"+f"(d[30]),"+f"(d[31])
   : "l"(da), "l"(db), "r"(sd));
}
template<> __device__ __forceinline__ void wgmma_ss<192,0,1>(float* d, uint64_t da, uint64_t db, int sd) {
  asm volatile("{\n.reg .pred p;\nsetp.ne.b32 p, %98, 0;\nwgmma.mma_async.sync.aligned.m64n192k16.f32.bf16.bf16 {%0,%1,%2,%3,%4,%5,%6,%7,%8,%9,%10,%11,%12,%13,%14,%15,%16,%17,%18,%19,%20,%21,%22,%23,%24,%25,%26,%27,%28,%29,%30,%31,%32,%33,%34,%35,%36,%37,%38,%39,%40,%41,%42,%43,%44,%45,%46,%47,%48,%49,%50,%51,%52,%53,%54,%55,%56,%57,%58,%59,%60,%61,%62,%63,%64,%65,%66,%67,%68,%69,%70,%71,%72,%73,%74,%75,%76,%77,%78,%79,%80,%81,%82,%83,%84,%85,%86,%87,%88,%89,%90,%91,%92,%93,%94,%95}, %96, %97, p, 1, 1, 0, 1;\n}\n"
   : "+f"(d[0]),"+f"(d[1]),"+f"(d[2]),"+f"(d[3]),"+f"(d[4]),"+f"(d[5]),"+f"(d[6]),"+f"(d[7]),"+f"(d[8]),"+f"(d[9]),"+f"(d[10]),"+f"(d[11]),"+f"(d[12]),"+f"(d[13]),"+f"(d[14]),"+f"(d[15]),"+f"(d[16]),"+f"(d[17]),"+f"(d[18]),"+f"(d[19]),"+f"(d[20]),"+f"(d[21]),"+f"(d[22]),"+f"(d[23]),"+f"(d[24]),"+f"(d[25]),"+f"(d[26]),"+f"(d[27]),"+f"(d[28]),"+f"(d[29]),"+f"(d[30]),"+f"(d[31]),"+f"(d[32]),"+f"(d[33]),"+f"(d[34]),"+f"(d[35]),"+f"(d[36]),"+f"(d[37]),"+f"(d[38]),"+f"(d[39]),"+f"(d[40]),"+f"(d[41]),"+f"(d[42]),"+f"(d[43]),"+f"(d[44]),"+f"(d[45]),"+f"(d[46]),"+f"(d[47]),"+f"(d[48]),"+f"(d[49]),"+f"(d[50]),"+f"(d[51]),"+f"(d[52]),"+f"(d[53]),"+f"(d[54]),"+f"(d[55]),"+f"(d[56]),"+f"(d[57]),"+f"(d[58]),"+f"(d[59]),"+f"(d[60]),"+f"(d[61]),"+f"(d[62]),"+f"(d[63]),"+f"(d[64]),"+f"(d[65]),"+f"(d[66]),"+f"(d[67]),"+f"(d[68]),"+f"(d[69]),"+f"(d[70]),"+f"(d[71]),"+f"(d[72]),"+f"(d[73]),"+f"(d[74]),"+f"(d[75]),"+f"(d[76]),"+f"(d[77]),"+f"(d[78]),"+f"(d[79]),"+f"(d[80]),"+f"(d[81]),"+f"(d[82]),"+f"(d[83]),"+f"(d[84]),"+f"(d[85]),"+f"(d[86]),"+f"(d[87]),"+f"(d[88]),"+f"(d[89]),"+f"(d[90]),"+f"(d[91]),"+f"(d[92]),"+f"(d[93]),"+f"(d[94]),"+f"(d[95])
   : "l"(da), "l"(db), "r"(sd));
}
template<> __device__ __forceinline__ void wgmma_ss<192,1,1>(float* d, uint64_t da, uint64_t db, int sd) {
  asm volatile("{\n.reg .pred p;\nsetp.ne.b32 p, %98, 0;\nwgmma.mma_async.sync.aligned.m64n192k16.f32.bf16.bf16 {%0,%1,%2,%3,%4,%5,%6,%7,%8,%9,%10,%11,%12,%13,%14,%15,%16,%17,%18,%19,%20,%21,%22,%23,%24,%25,%26,%27,%28,%29,%30,%31,%32,%33,%34,%35,%36,%37,%38,%39,%40,%41,%42,%43,%44,%45,%46,%47,%48,%49,%50,%51,%52,%53,%54,%55,%56,%57,%58,%59,%60,%61,%62,%63,%64,%65,%66,%67,%68,%69,%70,%71,%72,%73,%74,%75,%76,%77,%78,%79,%80,%81,%82,%83,%84,%85,%86,%87,%88,%89,%90,%91,%92,%93,%94,%95}, %96, %97, p, 1, 1, 1, 1;\n}\n"
   : "+f"(d[0]),"+f"(d[1]),"+f"(d[2]),"+f"(d[3]),"+f"(d[4]),"+f"(d[5]),"+f"(d[6]),"+f"(d[7]),"+f"(d[8]),"+f"(d[9]),"+f"(d[10]),"+f"(d[11]),"+f"(d[12]),"+f"(d[13]),"+f"(d[14]),"+f"(d[15]),"+f"(d[16]),"+f"(d[17]),"+f"(d[18]),"+f"(d[19]),"+f"(d[20]),"+f"(d[21]),"+f"(d[22]),"+f"(d[23]),"+f"(d[24]),"+f"(d[25]),"+f"(d[26]),"+f"(d[27]),"+f"(d[28]),"+f"(d[29]),"+f"(d[30]),"+f"(d[31]),"+f"(d[32]),"+f"(d[33]),"+f"(d[34]),"+f"(d[35]),"+f"(d[36]),"+f"(d[37]),"+f"(d[38]),"+f"(d[39]),"+f"(d[40]),"+f"(d[41]),"+f"(d[42]),"+f"(d[43]),"+f"(d[44]),"+f"(d[45]),"+f"(d[46]),"+f"(d[47]),"+f"(d[48]),"+f"(d[49]),"+f"(d[50]),"+f"(d[51]),"+f"(d[52]),"+f"(d[53]),"+f"(d[54]),"+f"(d[55]),"+f"(d[56]),"+f"(d[57]),"+f"(d[58]),"+f"(d[59]),"+f"(d[60]),"+f"(d[61]),"+f"(d[62]),"+f"(d[63]),"+f"(d[64]),"+f"(d[65]),"+f"(d[66]),"+f"(d[67]),"+f"(d[68]),"+f"(d[69]),"+f"(d[70]),"+f"(d[71]),"+f"(d[72]),"+f"(d[73]),"+f"(d[74]),"+f"(d[75]),"+f"(d[76]),"+f"(d[77]),"+f"(d[78]),"+f"(d[79]),"+f"(d[80]),"+f"(d[81]),"+f"(d[82]),"+f"(d[83]),"+f"(d[84]),"+f"(d[85]),"+f"(d[86]),"+f"(d[87]),"+f"(d[88]),"+f"(d[89]),"+f"(d[90]),"+f"(d[91]),"+f"(d[92]),"+f"(d[93]),"+f"(d[94]),"+f"(d[95])
   : "l"(da), "l"(db), "r"(sd));
}

__device__ __forceinline__ void stats_publish(uint32_t sb, int layer, int rb, int hg, int ht, uint32_t tag) {
  const int lane = ht & 31, w = ht >> 5, g = lane >> 2, t = lane & 3, ks = hg & 3;
  uint32_t xa;
  if (layer == 0) {
    const int row = 16 * w + (lane & 15), kc = 2 * ks + (lane >> 4);
    xa = row * 128 + ((kc ^ (row & 7)) << 4);
  } else {
    const int k = 16 * ks + (lane & 7) + 8 * (lane >> 4), pc = 2 * w + ((lane >> 3) & 1);
    xa = k * 128 + ((pc ^ (k & 7)) << 4);
  }
  float s[4] = {0.f, 0.f, 0.f, 0.f}, q[4] = {0.f, 0.f, 0.f, 0.f};
#pragma unroll 1
  for (int c = hg >> 2; c < 8; c += 2) {
    uint32_t A[2][4];
    mbar_wait(sb + SM_BAR + 8 * (B_XF + c), layer);
#pragma unroll
    for (int h = 0; h < 2; h++) {
      if (layer == 0) ldsm4(A[h], sb + SM_X + c * 16384 + h * 8192 + xa);
      else ldsm4t(A[h], sb + SM_X + c * 16384 + h * 8192 + xa);
    }
    if (c >= 6) ATS(48, 256);
    if (c < 2) ATS(51, 256);
#pragma unroll
    for (int r = 0; r < 4; r++)
#pragma unroll
      for (int i = 0; i < 2; i++) {
        const uint32_t v = A[r >> 1][2 * i + (r & 1)];
        const float a = bf_lo(v), b = bf_hi(v);
        s[r] += a + b; q[r] = fmaf(a, a, q[r]); q[r] = fmaf(b, b, q[r]);
      }
  }
#pragma unroll
  for (int r = 0; r < 2; r++) {
    s[r] = ((t & 2) ? s[r + 2] : s[r]) + __shfl_xor_sync(~0u, (t & 2) ? s[r] : s[r + 2], 2);
    q[r] = ((t & 2) ? q[r + 2] : q[r]) + __shfl_xor_sync(~0u, (t & 2) ? q[r] : q[r + 2], 2);
  }
  s[0] = ((t & 1) ? s[1] : s[0]) + __shfl_xor_sync(~0u, (t & 1) ? s[0] : s[1], 1);
  q[0] = ((t & 1) ? q[1] : q[0]) + __shfl_xor_sync(~0u, (t & 1) ? q[0] : q[1], 1);
  st_part(&g_part[(rb * 8 + hg) * 128 + 64 * (t >> 1) + 16 * w + 8 * (t & 1) + g], s[0], q[0], tag);
  ATS(49, 256);
}
__device__ __forceinline__ void stats_gather(uint32_t sb, int rb, int ht, uint32_t tag) {
  const uint2* src = &g_part[rb * 8 * 128 + ht];
  uint2 v[8];
  for (int it = 0;; it++) {
    uint32_t bad = 0;
#pragma unroll
    for (int i = 0; i < 8; i++) v[i] = ld_part(src + i * 128);
#pragma unroll
    for (int i = 0; i < 8; i++) bad |= v[i].y ^ tag;
    if (__all_sync(~0u, (bad & 7u) == 0)) break;
    if (it > (1 << 22)) __trap();
  }
  float s = 0.f, q = 0.f;
#pragma unroll
  for (int i = 0; i < 8; i++) { s += __uint_as_float(v[i].x); q += __uint_as_float(v[i].y); }
  const float mean = s * (1.f / DM);
  const float rstd = rsqrt_approx(fmaxf(q * (1.f / DM) - mean * mean, 0.f) + 1e-5f);
  asm volatile("st.shared.v2.f32 [%0], {%1,%2};" ::"r"(sb + SM_ST + ht * 8), "f"(mean), "f"(rstd) : "memory");
  __syncwarp();
  if (elect_one()) mbar_arrive(sb + SM_BAR + 8 * B_STF);
}
__device__ __forceinline__ void halo_receive(uint32_t sb, int layer, int rb, int hg, int ht) {
  const int lane = ht & 31, h = ht >> 5;
  uint4 kv = make_uint4(0, 0, 0, 0);
  mbar_wait(sb + SM_BAR + 8 * B_SD, layer);
  if (rb & 7) {
    const uint32_t tag = 2 * lds32(sb + SM_EP) + layer + 1;
    const uint4* src = &g_halo[((rb - 1) * 8 + hg) * 192 + h * 48];
    if (layer == 0) delay<D_HALO>(); else delay<D_HALO1>();
    uint4 a;
    uint2 b;
    int it = 0;
    do {
      a = ld_tagged(src + lane); b = ld_part((const uint2*)(src + 32) + lane);
      if (++it > (1 << 22)) __trap();
    } while (!__all_sync(~0u, a.w == tag && b.y == tag));
    kv = make_uint4(a.x, a.y, movm_t(a.z), movm_t(b.x));
  }
  sts128(sb + SM_KVX + h * 512 + lane * 16, kv);
  ATS(61, 256);
  bar_arrive(7, 160);
  if (elect_one()) mbar_arrive(sb + SM_BAR + 8 * B_HF);
}

__device__ __forceinline__ void halo_receive1(uint32_t sb, int layer, int rb, int hg, int lane, uint32_t tag) {
  uint4 a[4];
  uint2 b[4];
  mbar_wait(sb + SM_BAR + 8 * B_SD, layer);
  if (rb & 7) {
    const uint4* src = &g_halo[((rb - 1) * 8 + hg) * 192];
    if (layer == 0) delay<D_HALO>(); else delay<D_HALO1>();
    for (int it = 0;; it++) {
      uint32_t bad = 0;
#pragma unroll
      for (int h = 0; h < 4; h++) { a[h] = ld_tagged(src + h * 48 + lane); b[h] = ld_part((const uint2*)(src + h * 48 + 32) + lane); }
#pragma unroll
      for (int h = 0; h < 4; h++) {
        bad |= (a[h].w ^ tag) | (b[h].y ^ tag);
        a[h].z = movm_t(a[h].z); a[h].w = movm_t(b[h].x);
      }
      if (__all_sync(~0u, bad == 0)) break;
      if (it > (1 << 22)) __trap();
    }
  } else {
#pragma unroll
    for (int h = 0; h < 4; h++) a[h] = make_uint4(0, 0, 0, 0);
  }
#pragma unroll
  for (int h = 0; h < 4; h++) sts128(sb + SM_KVX + h * 512 + lane * 16, a[h]);
  ATS(61, 448);
  bar_arrive(7, 64);
  if (lane < 4) mbar_arrive(sb + SM_BAR + 8 * B_HF);
}

template <bool TR>
__device__ __forceinline__ void gemm_section(float* acc, float2* cs, uint32_t sb, int layer, int wg, int w, int lane) {
  const uint32_t bar = sb + SM_BAR;
  const bool leader = (w == 0) && (lane == 0);
  auto issue = [&](int c, int slot) {
    mbar_wait(bar + 8 * (B_XF + c), layer);
    mbar_wait(bar + 8 * (B_KVF + c), layer);
    const uint64_t da = mkdesc(sb + SM_X + c * 16384 + wg * 8192, TR ? 8192 : 16, 1024, 1);
    const uint64_t db = mkdesc(sb + SM_W + slot * 24576, 8192, 1024, 1);
    wg_fence();
#pragma unroll
    for (int ks = 0; ks < 4; ks++) wgmma_ss<192, TR ? 1 : 0, 1>(acc, da + (TR ? ks * 128 : ks * 2), db + ks * 128, (c | ks) != 0);
    wg_commit();
  };
  auto step = [&](int c, int slot) {
    issue(c, slot);
    wg_wait<1>();
    if (leader) mbar_arrive(bar + 8 * (B_KVE + c - 1));
  };
  if (!TR) bar_sync(0, NTHREADS);
  if (TR && G_WAIT == 3 && wg == 1) bar_sync(14, 256);
  if (TR && G_WAIT == 4 && wg == 1) mbar_wait(bar + 8 * (B_P + 3), 0);
  issue(0, 0);
  if (threadIdx.x == 0) TS(2 + layer * 20 + 0);
  if (threadIdx.x == 128 && layer == 1) TS(60);
  auto ld_cs = [&](int j0) {
#pragma unroll
    for (int j = j0; j < j0 + 8; j++) cs[j] = lds64f(sb + SM_CS + 4 * (8 * j + 2 * (lane & 3)));
  };
  if (TR && CS_STEP == 0) ld_cs(8);
  step(1, 1);
  if (TR && CS_STEP == 0) ld_cs(16);
  if (TR && CS_STEP == 1) ld_cs(8);
  step(2, 2);
  if (TR && CS_STEP == 1) ld_cs(16);
  if (TR && CS_STEP == 2) ld_cs(8);
  step(3, 0);
  if (TR && CS_STEP == 2) ld_cs(16);
  step(4, 1);
  if ((TR ? STAG1 : STAG0) == 3) {
    if (wg == 0) {
      wg_wait<0>();
      if (leader) mbar_arrive(bar + 8 * (B_KVE + 4));
      bar_sync(5, 256);
    }
    issue(5, 2);
    wg_wait<1>();
    if (leader && wg == 1) mbar_arrive(bar + 8 * (B_KVE + 4));
    if (!TR && !CS_LATE0) { mbar_wait(bar + 8 * B_CSF, 0); ld_cs(8); ld_cs(16); }
  } else {
    step(5, 2);
    if (!TR && !CS_LATE0) { mbar_wait(bar + 8 * B_CSF, 0); ld_cs(8); ld_cs(16); }
    if (wg == 0) bar_sync(5, 256);
  }
  issue(6, 0);
  issue(7, 1);
  if (wg == 1) bar_arrive(5, 256);
  if (!TR && CS_LATE0) { mbar_wait(bar + 8 * B_CSF, 0); ld_cs(8); ld_cs(16); }
}

__device__ __forceinline__ void attn_phase(const Params& p, uint32_t sb, int layer, int rb, int hg, int wg, int w) {
  const int lane = opaque_tid() & 31;
  const int g = lane >> 2, t = lane & 3;
  const uint32_t bar = sb + SM_BAR;
  const int row0 = 64 * wg + 16 * w;
  const bool leader = (w == 0) && (lane == 0);
  float acc[96];
  float2 cs[24];
  if (layer) gemm_section<true>(acc, cs, sb, layer, wg, w, lane);
  else gemm_section<false>(acc, cs, sb, layer, wg, w, lane);
  ATS(41, 224);
  mbar_wait(bar + 8 * B_STF, layer);
  const uint32_t tag = 2 * lds32(sb + SM_EP) + layer + 1;
  const float2 st0 = lds64f(sb + SM_ST + (row0 + g) * 8), st1 = lds64f(sb + SM_ST + (row0 + g + 8) * 8);
  const float mean0 = st0.x, rstd0 = st0.y, mean1 = st1.x, rstd1 = st1.y;
  wg_wait<0>();
  if (threadIdx.x == 0) TS(2 + layer * 20 + 1);
  ATS(39, 224);
  if (leader) mbar_arrive(bar + 8 * B_QDONE);

  uint32_t fp[4][4], fl[4][4], fh[4][4], qa[4][4];
  const int cw = 4 * wg + w;
  {
    const float nm0 = -mean0 * rstd0, nm1 = -mean1 * rstd1;
    const uint32_t kvx = sb + SM_KVX + cw * 2048 + lane * 16;
#pragma unroll
    for (int h = 0; h < 4; h++)
#pragma unroll
      for (int k = 0; k < 4; k++) {
        const int j = 8 + (k >> 1) * 8 + 2 * h + (k & 1);
        fh[h][k] = packbf(fmaf(acc[4 * j + 2], rstd1, nm1 * cs[j].x), fmaf(acc[4 * j + 3], rstd1, nm1 * cs[j].y));
      }
    if (cw == 7) {
      uint4* halo = &g_halo[(rb * 8 + hg) * 192];
#pragma unroll
      for (int h = 0; h < 4; h++) {
        st_tagged3(halo + h * 48 + lane, fh[h][0], fh[h][1], fh[h][2], tag);
        asm volatile("st.relaxed.gpu.global.v2.u32 [%0], {%1,%2};" ::"l"((uint2*)(halo + h * 48 + 32) + lane), "r"(fh[h][3]), "r"(tag) : "memory");
      }
      if (elect_one()) mbar_arrive(bar + 8 * B_SD);
      if (layer == TLAYER && threadIdx.x == 224) TS(47);
    }
#pragma unroll
    for (int h = 0; h < 4; h++) { fh[h][2] = movm_t(fh[h][2]); fh[h][3] = movm_t(fh[h][3]); }
    if (cw != 7) {
#pragma unroll
      for (int h = 0; h < 4; h++) sts128(kvx + 2048 + h * 512, make_uint4(fh[h][0], fh[h][1], fh[h][2], fh[h][3]));
      bar_arrive(8 + cw, 64);
    }
    sched_fence<6>();
    if (layer == TLAYER && threadIdx.x == 0) TS(45);
#pragma unroll
    for (int j = 0; j < 8; j++) cs[j] = lds64f(sb + SM_CS + 4 * (8 * j + 2 * t));
#pragma unroll
    for (int h = 0; h < 4; h++)
#pragma unroll
      for (int k = 0; k < 4; k++) {
        const int j = 8 + (k >> 1) * 8 + 2 * h + (k & 1);
        fl[h][k] = packbf(fmaf(acc[4 * j], rstd0, nm0 * cs[j].x), fmaf(acc[4 * j + 1], rstd0, nm0 * cs[j].y));
        if (k >= 2) fl[h][k] = movm_t(fl[h][k]);
      }
#pragma unroll
    for (int h = 0; h < 4; h++) {
#pragma unroll
      for (int dh = 0; dh < 2; dh++) {
        const int j = 2 * h + dh;
        const float2 c2 = cs[j];
        qa[h][2 * dh] = packbf(fmaf(-mean0, c2.x, acc[4 * j + 0]), fmaf(-mean0, c2.y, acc[4 * j + 1]));
        qa[h][2 * dh + 1] = packbf(fmaf(-mean1, c2.x, acc[4 * j + 2]), fmaf(-mean1, c2.y, acc[4 * j + 3]));
      }
    }
    if (threadIdx.x == 0) TS(2 + layer * 20 + 2);
    if (QD_AT == 1 || (QD_AT == 3 && wg == 0)) mbar_wait(bar + 8 * B_QDONE, layer);
    sched_fence<0>();
    bar_sync(7 + cw, cw == 0 && !HALO_W14 ? 160 : 64);
#pragma unroll
    for (int h = 0; h < 4; h++) {
      const uint4 v = lds128(kvx + h * 512);
      fp[h][0] = v.x; fp[h][1] = v.y; fp[h][2] = v.z; fp[h][3] = v.w;
    }
    if (threadIdx.x == 0) TS(2 + layer * 20 + 4);
  }

  const bool u0 = 2 * t > g, u1 = 2 * t + 1 > g;
  const uint32_t mU = (u0 ? 0x0000ffffu : 0u) | (u1 ? 0xffff0000u : 0u);
  const float cl2 = 0.25f * 1.4426950408889634f;
  const float sc0 = rstd0 * cl2, sc1 = rstd1 * cl2;
  const float cneg = ((rb & 7) == 0 && cw == 0) ? -INFINITY : 0.f;
  float v[4][4];
#pragma unroll
  for (int h = 0; h < 4; h++) {
    float T0[4] = {cneg, cneg, cneg, cneg}, T1[4] = {0.f, 0.f, 0.f, 0.f}, T2[4] = {0.f, 0.f, 0.f, 0.f};
    mma_bf16(T1, qa[h], fl[h][0], fl[h][1]);
    mma_bf16(T2, qa[h], fh[h][0], fh[h][1]);
    mma_bf16(T0, qa[h], fp[h][0], fp[h][1]);
    v[h][0] = u0 ? T0[0] : T1[0]; v[h][1] = u1 ? T0[1] : T1[1];
    v[h][2] = u0 ? T1[2] : T2[2]; v[h][3] = u1 ? T1[3] : T2[3];
  }
  float m0[4], m1[4];
#pragma unroll
  for (int h = 0; h < 4; h++) { m0[h] = fmaxf(v[h][0], v[h][1]); m1[h] = fmaxf(v[h][2], v[h][3]); }
#pragma unroll
  for (int o = 1; o <= 2; o <<= 1) {
#pragma unroll
    for (int h = 0; h < 4; h++) {
      m0[h] = fmaxf(m0[h], __shfl_xor_sync(~0u, m0[h], o));
      m1[h] = fmaxf(m1[h], __shfl_xor_sync(~0u, m1[h], o));
    }
  }
  float O0[4][4], O1[4][4], Z[4][4];
#pragma unroll
  for (int h = 0; h < 4; h++) {
    const float mm0 = -m0[h] * sc0, mm1 = -m1[h] * sc1;
    const uint32_t P0 = packbf(ex2(fmaf(v[h][0], sc0, mm0)), ex2(fmaf(v[h][1], sc0, mm0)));
    const uint32_t P1 = packbf(ex2(fmaf(v[h][2], sc1, mm1)), ex2(fmaf(v[h][3], sc1, mm1)));
#pragma unroll
    for (int k = 0; k < 4; k++) O0[h][k] = O1[h][k] = Z[h][k] = 0.f;
    mma_bf16_k8(Z[h], P0, P1, 0x3f803f80u);
    mma_bf16_k8(O0[h], P0 & ~mU, P1 & mU, fl[h][2]); mma_bf16_k8(O1[h], P0 & ~mU, P1 & mU, fl[h][3]);
    mma_bf16_k8(O0[h], P0 & mU, 0u, fp[h][2]); mma_bf16_k8(O1[h], P0 & mU, 0u, fp[h][3]);
    mma_bf16_k8(O0[h], 0u, P1 & ~mU, fh[h][2]); mma_bf16_k8(O1[h], 0u, P1 & ~mU, fh[h][3]);
  }
  const uint32_t ob = sb + SM_OST + wg * 8192;
  if (QD_AT == 0 || (QD_AT == 3 && wg == 1)) mbar_wait(bar + 8 * B_QDONE, layer);
  const int o_row = 16 * w + (lane & 7) + 8 * ((lane >> 3) & 1);
#pragma unroll
  for (int h = 0; h < 4; h++) {
    const float i0 = rcp_approx(Z[h][0]), i1 = rcp_approx(Z[h][2]);
    const int ch = 2 * h + (lane >> 4);
    stsm4(ob + o_row * 128 + ((ch ^ (o_row & 7)) << 4), packbf(O0[h][0] * i0, O0[h][1] * i0), packbf(O0[h][2] * i1, O0[h][3] * i1),
          packbf(O1[h][0] * i0, O1[h][1] * i0), packbf(O1[h][2] * i1, O1[h][3] * i1));
  }
  if (threadIdx.x == 0) TS(2 + layer * 20 + 5);
  ATS(57, 128); ATS(20, 96);
  __syncwarp();
  if (elect_one()) {
    fence_async_smem();
    tma_st(&p.mapO, hg * 64, rb * 128 + row0, ob + w * 2048);
    bulk_commit();
    mbar_arrive(bar + 8 * B_AD);
    bulk_wait_all();
    uint32_t old;
    asm volatile("atom.acq_rel.cta.shared.inc.u32 %0, [%1], 7;" : "=r"(old) : "r"(sb + SM_EP + 4) : "memory");
    if (old == 7) {
      asm volatile("red.relaxed.gpu.global.add.u32 [%0], 2;" ::"l"(&g_cnt[(C_O + rb) * 32]) : "memory");
      asm volatile("mbarrier.arrive.shared::cta.b64 _, [%0], 2;" ::"r"(bar + 8 * B_OST) : "memory");
      TS(2 + layer * 20 + 6);
    }
  }
  __syncwarp();
}

__device__ __forceinline__ void proj_phase(const Params& p, uint32_t sb, int layer, int rb, int q, int wg, int w) {
  const int lane = opaque_tid() & 31;
  const bool TR = layer != 0;
  const int t = lane & 3;
  const uint32_t bar = sb + SM_BAR;
  const uint32_t rbx = sb + SM_R + wg * 8192;
  uint32_t res[16];
  mbar_wait(bar + 8 * B_RF, layer);
  if (threadIdx.x == 0) TS(2 + layer * 20 + 7);
  if (!TR) {
#pragma unroll
    for (int j = 0; j < 8; j += 2) {
      const int mi = lane >> 3;
      const int row = 16 * w + (lane & 7) + 8 * (mi & 1), ch = j + (mi >> 1);
      ldsm4(&res[2 * j], rbx + row * 128 + ((ch ^ (row & 7)) << 4));
    }
  } else {
#pragma unroll
    for (int j = 0; j < 8; j += 2) {
      const int mi = lane >> 3;
      const int line = 8 * (j + (mi >> 1)) + (lane & 7), pc = 2 * w + (mi & 1);
      ldsm4t(&res[2 * j], rbx + line * 128 + ((pc ^ (line & 7)) << 4));
    }
  }
  bar_sync(2 + wg, 128);
  float acc[32];
#pragma unroll
  for (int i = 0; i < 16; i++) {
    asm volatile("shl.b32 %0, %1, 16;" : "=f"(acc[2 * i]) : "r"(res[i]));
    asm volatile("and.b32 %0, %1, 0xffff0000;" : "=f"(acc[2 * i + 1]) : "r"(res[i]));
  }
  const uint32_t tag = part_tag(lds32(sb + SM_EP), 2 * layer + 1);
  mbar_wait(bar + 8 * B_ZF, layer);
  mbar_wait(bar + 8 * B_WOF, layer);
  tensor_keepalive<1>();
#pragma unroll P_UNROLL
  for (int c = 0; c < 8; c++) {
    mbar_wait(bar + 8 * (B_OF + c), layer);
    if (c == 0 && threadIdx.x == 0) TS(2 + layer * 20 + 8);
    const uint64_t da = mkdesc(sb + sm_o(c) + wg * 8192, 16, 1024, 1);
    const uint64_t db = mkdesc(sb + SM_WO + c * 8192, 8192, 1024, 1);
    wg_fence();
#pragma unroll
    for (int ks = 0; ks < 4; ks++) wgmma_ss<64, 0, 1>(acc, da + ks * 2, db + ks * 128, 1);
    wg_commit();
  }
  wg_wait<0>();
#pragma unroll
  for (int i = 0; i < 32; i++) asm volatile("" : "+f"(acc[i]) :: "memory");
  if (threadIdx.x == 0) TS(2 + layer * 20 + 9);
  if (lane == 0 && w == 0) mbar_arrive(bar + 8 * B_PDONE);
  {
    float s[4], qq[4];
#pragma unroll
    for (int k = 0; k < 4; k++) { s[k] = acc[k]; qq[k] = acc[k] * acc[k]; }
#pragma unroll
    for (int j = 1; j < 8; j++)
#pragma unroll
      for (int k = 0; k < 4; k++) { s[k] += acc[4 * j + k]; qq[k] = fmaf(acc[4 * j + k], acc[4 * j + k], qq[k]); }
    const float s0 = s[0] + s[1], s1 = s[2] + s[3], q0 = qq[0] + qq[1], q1 = qq[2] + qq[3];
    float sr = ((t & 1) ? s1 : s0) + __shfl_xor_sync(~0u, (t & 1) ? s0 : s1, 1);
    float qr = ((t & 1) ? q1 : q0) + __shfl_xor_sync(~0u, (t & 1) ? q0 : q1, 1);
    sr += __shfl_xor_sync(~0u, sr, 2);
    qr += __shfl_xor_sync(~0u, qr, 2);
    if (t < 2) st_part(&g_part[(rb * 8 + q) * 128 + 64 * wg + 16 * w + (lane >> 2) + 8 * t], sr, qr, tag);
    __syncwarp();
    if (elect_one()) mbar_arrive(bar + 8 * B_PS);
    sched_fence<7>();
  }
#pragma unroll
  for (int j = 0; j < 8; j += 2) {
    const int mi = lane >> 3;
    const int line = 8 * (j + (mi >> 1)) + (lane & 7), pc = 2 * w + (mi & 1);
    stsm4t(rbx + line * 128 + ((pc ^ (line & 7)) << 4), packbf(acc[4 * j], acc[4 * j + 1]), packbf(acc[4 * j + 2], acc[4 * j + 3]),
           packbf(acc[4 * j + 4], acc[4 * j + 5]), packbf(acc[4 * j + 6], acc[4 * j + 7]));
  }
  fence_writer();
  bar_sync(2 + wg, 128);
  if (w == 0 && elect_one()) {
    fence_reader();
    fence_async_global();
    tma_st(&p.mapXT, rb * 128 + wg * 64, (2 * layer) * DM + q * 64, rbx);
    bulk_commit();
    if (threadIdx.x == 0) TS(2 + layer * 20 + 10);
    bulk_wait_all();
    red_relaxed(&g_cnt[C_CS * 32 + 2 + layer]);
    if (wg == 0) mbar_arrive(bar + 8 * B_RE);
  }
  __syncwarp();
}
__device__ __forceinline__ void proj_stats(uint32_t sb, int layer, int rb, int q, int lane, uint32_t tag) {
  const int r = 16 * q + (lane & 15);
  const uint2* src = &g_part[rb * 8 * 128 + r];
  uint32_t* dst = g_stats + layer * LSEQ + (rb >> 1) * 256 + ((r >> 2) & 1) * 128 + ((rb & 1) * 16 + (r >> 3)) * 4 + (r & 3);
  mbar_wait(sb + SM_BAR + 8 * B_PS, layer);
  delay<D_PST>();
  for (int it = 0;; it++) {
    uint2 v[8];
#pragma unroll
    for (int i = 0; i < 8; i++) v[i] = ld_part(src + i * 128);
    float s[4], qq[4];
    uint32_t bad = 0;
#pragma unroll
    for (int i = 0; i < 4; i++) {
      s[i] = __uint_as_float(v[i].x) + __uint_as_float(v[i + 4].x);
      qq[i] = __uint_as_float(v[i].y) + __uint_as_float(v[i + 4].y);
      bad |= (v[i].y ^ tag) | (v[i + 4].y ^ tag);
    }
    const float mean = ((s[0] + s[1]) + (s[2] + s[3])) * (1.f / DM);
    const float rstd = rsqrt_approx(fmaxf(fmaf((qq[0] + qq[1]) + (qq[2] + qq[3]), 1.f / DM, -mean * mean), 0.f) + 1e-5f);
    const bool ok = __all_sync(~0u, (bad & 7u) == 0);
    if (ok && lane < 16)
    {
      if (PUB & 1) asm volatile("red.relaxed.gpu.global.or.b32 [%0], %1;" ::"l"(dst), "r"(max(packbf(-mean, rstd), 1u)) : "memory");
      else asm volatile("st.relaxed.gpu.global.u32 [%0], %1;" ::"l"(dst), "r"(max(packbf(-mean, rstd), 1u)) : "memory");
    }
    if (ok) break;
    if (it > (1 << 22)) __trap();
  }
}

#define NA 14
#define NP 15
template <int M0, int M1> __device__ __forceinline__ void conv_load(uint32_t* A, uint32_t pe) {
#pragma unroll
  for (int m = M0; m < M1; m++) {
    asm volatile("ld.shared.v2.b32 {%0,%1}, [%2];" : "=r"(A[4 * m]), "=r"(A[4 * m + 1]) : "r"(pe + 256 * m) : "memory");
    A[4 * m + 2] = lds32(pe + 256 * m - 4);
  }
}
__device__ __forceinline__ uint32_t copy_reg(uint32_t v, uint32_t zero) { uint32_t r; asm volatile("or.b32 %0, %1, %2;" : "=r"(r) : "r"(v), "r"(zero)); return r; }
__device__ __forceinline__ uint32_t copy_reg2(uint32_t v, uint32_t zero) { uint32_t r; asm volatile("xor.b32 %0, %1, %2;" : "=r"(r) : "r"(v), "r"(zero)); return r; }
__device__ __forceinline__ void conv_park(uint32_t* P, uint32_t pe) {
#pragma unroll
  for (int m = 0; m < NP; m++)
#pragma unroll
    for (int k = 0; k < 3; k++) P[3 * m + k] = lds32(pe + 256 * m - 4 + 4 * k);
}
__device__ __forceinline__ void conv_unpark(uint32_t* A, const uint32_t* P, uint32_t zero) {
#pragma unroll
  for (int m = 0; m < NP; m++) {
    A[4 * m + 2] = copy_reg(P[3 * m], zero); A[4 * m] = copy_reg(P[3 * m + 1], zero);
    A[4 * m + 3] = copy_reg2(P[3 * m + 1], zero); A[4 * m + 1] = copy_reg(P[3 * m + 2], zero);
  }
}
template <int M0, int M1> __device__ __forceinline__ void conv_mmas(float* acc, const uint32_t* A, uint64_t d) {
  if constexpr (M0 < M1) {
    wgmma_rs<128 - 8 * (M0 / 2), 0>(acc, A + 4 * M0, d + (uint64_t)(4 * M0), M0 != 0);
    conv_mmas<M0 + 1, M1>(acc, A, d);
  }
}
struct SumAddr { uint32_t l0, l1, l2, se, so; };
__device__ __forceinline__ SumAddr conv_sum_addr(uint32_t sb, int c) {
  auto ua = [&](int j) { return sb + cv_u(0) + (127 - (j >> 3)) * 16 + (j & 7) * 2; };
  auto sa = [&](int hc) { const int ci = hc & ~1; return sb + cv_s(0) + ((ci >> 3) & 1) * 1024 + (ci >> 4) * 128 + (((ci ^ (ci >> 4)) & 7) << 4) + (hc & 1) * 8; };
  const int j0 = 4 * (c - 1);
  return {ua(j0 - 2), ua(j0), ua(j0 + 4), sa((c + 1) & 127), sa(c) + 2048};
}
__device__ __forceinline__ void sts64(uint32_t a, uint32_t x, uint32_t y) { asm volatile("st.shared.v2.b32 [%0], {%1,%2};" ::"r"(a), "r"(x), "r"(y) : "memory"); }
__device__ __forceinline__ void conv_sums(const SumAddr& sa, int lc, int c) {
  uint32_t e[4], o[4];
  {
    const float2 em = lds64f(sa.l1 + lc * 32768), om = lds64f(sa.l1 + lc * 32768 + CV_UH);
    e[0] = lds32(sa.l0 + lc * 32768); o[0] = lds32(sa.l0 + lc * 32768 + CV_UH);
    e[3] = lds32(sa.l2 + lc * 32768); o[3] = lds32(sa.l2 + lc * 32768 + CV_UH);
    e[1] = __float_as_uint(em.x); e[2] = __float_as_uint(em.y); o[1] = __float_as_uint(om.x); o[2] = __float_as_uint(om.y);
  }
  uint32_t s7e[2], s7o[2], s9e[2], s9o[2];
  uint32_t pw[4], sh[3];
#pragma unroll
  for (int k = 0; k < 4; k++) pw[k] = hadd2(e[k], o[k]);
#pragma unroll
  for (int k = 0; k < 3; k++) sh[k] = __byte_perm(pw[k], pw[k + 1], 0x5432);
#pragma unroll
  for (int k = 0; k < 2; k++) {
    const uint32_t t3 = hadd2(hadd2(sh[k], sh[k + 1]), pw[k + 1]);
    s7e[k] = hadd2(t3, o[k]); s7o[k] = hadd2(t3, e[k + 2]);
    s9e[k] = hadd2(s7o[k], pw[k]); s9o[k] = hadd2(s7e[k], pw[k + 2]);
  }
  if (c == 127) s9e[0] = s9e[1] = s9o[0] = s9o[1] = 0u;
  sts64(sa.se + lc * 32768, s9e[0], s9e[1]); sts64((sa.se ^ 16) + lc * 32768, s9o[0], s9o[1]);
  sts64(sa.so + lc * 32768, s7e[0], s7e[1]); sts64((sa.so ^ 16) + lc * 32768, s7o[0], s7o[1]);
}

__device__ __forceinline__ void conv_epi(uint32_t sb, int layer, int cta, int ch, int c0, uint4 x0, uint4 x1) {
  uint4 v[2][4];
  const uint4 xr[2] = {x0, x1};
  mbar_wait(sb + SM_BAR + 8 * (B_P + ch), layer);
#pragma unroll
  for (int u = 0; u < 2; u++) {
    const uint32_t pb = sb + cv_pb(ch) + u * (CV_PBW / 2) + c0 * 16;
#pragma unroll
    for (int k = 0; k < 4; k++) v[u][k] = lds128(pb + k * CV_PBW);
  }
#pragma unroll
  for (int u = 0; u < 2; u++) {
    uint4 o;
    o.x = hadd2(xr[u].x, hadd2(hadd2(v[u][0].x, v[u][1].x), hadd2(v[u][2].x, v[u][3].x)));
    o.y = hadd2(xr[u].y, hadd2(hadd2(v[u][0].y, v[u][1].y), hadd2(v[u][2].y, v[u][3].y)));
    o.z = hadd2(xr[u].z, hadd2(hadd2(v[u][0].z, v[u][1].z), hadd2(v[u][2].z, v[u][3].z)));
    o.w = hadd2(xr[u].w, hadd2(hadd2(v[u][0].w, v[u][1].w), hadd2(v[u][2].w, v[u][3].w)));
    if (layer == 0) sts128(sb + cv_s(ch) + (c0 + 128 * u) * 16, o);
    else if ((PUB & 4) && ch == 3) {
      uint2* d = (uint2*)((uint4*)(g_xT + (size_t)(3 * DM + cv_chan(cta, ch)) * LSEQ) + c0 + 128 * u);
      asm volatile("{\n.reg .b64 a, b;\nmov.b64 a, {%1,%2};\nmov.b64 b, {%3,%4};\nred.relaxed.gpu.global.and.b64 [%0+8], b;\nred.relaxed.gpu.global.and.b64 [%0], a;\n}" ::"l"(d), "r"(o.x), "r"(o.y), "r"(o.z), "r"(o.w) : "memory");
    } else st_tagged3((uint4*)(g_xT + (size_t)(3 * DM + cv_chan(cta, ch)) * LSEQ) + c0 + 128 * u, o.x, o.y, o.z, o.w);
  }
}
__device__ __forceinline__ void warp_release(uint32_t b) {
  fence_writer();
  __syncwarp();
  if (elect_one()) mbar_arrive(b);
}

__device__ __forceinline__ void conv_prep_load(uint32_t sb, int layer, int cta, int c, uint4 (&xr)[4], uint4 (&st)[4]) {
  sched_fence<8>();
  mbar_wait(sb + SM_BAR + 8 * B_GB, layer);
  if (threadIdx.x == 0) TS(2 + layer * 20 + 11);
  xr[0] = ld_tagged((const uint4*)(g_xT + (size_t)(2 * layer * DM + cta) * LSEQ) + c);
#pragma unroll
  for (int i = 0; i < 2; i++) st[i] = ld_tagged((const uint4*)g_stats + layer * 512 + (c >> 5) * 64 + i * 32 + (c & 31));
}
template <bool HELPER>
__device__ __forceinline__ void conv_prep(uint32_t sb, int layer, int cta, int c, uint4 (&xr)[4], uint4 (&st)[4], const SumAddr& sa) {
  const uint32_t bar = sb + SM_BAR;
  const uint4* xin = (const uint4*)(g_xT + (size_t)(2 * layer * DM + cta) * LSEQ) + c;
  for (int it = 0;; it++) {
    const uint32_t vs = min(min(min(st[0].x, st[0].y), min(st[0].z, st[0].w)), min(min(st[1].x, st[1].y), min(st[1].z, st[1].w)));
    if (__all_sync(~0u, vs != 0 && xr[0].x != ~0u)) break;
    if (it > (1 << 22)) __trap();
    if (!__all_sync(~0u, xr[0].x != ~0u)) xr[0] = ld_tagged(xin);
    if (!__all_sync(~0u, vs != 0)) {
#pragma unroll
      for (int i = 0; i < 2; i++) st[i] = ld_tagged((const uint4*)g_stats + layer * 512 + (c >> 5) * 64 + i * 32 + (c & 31));
    }
  }
  const uint32_t nm[4] = {__byte_perm(st[0].x, st[0].y, 0x5410), __byte_perm(st[0].z, st[0].w, 0x5410), __byte_perm(st[1].x, st[1].y, 0x5410), __byte_perm(st[1].z, st[1].w, 0x5410)};
  const uint32_t rs[4] = {__byte_perm(st[0].x, st[0].y, 0x7632), __byte_perm(st[0].z, st[0].w, 0x7632), __byte_perm(st[1].x, st[1].y, 0x7632), __byte_perm(st[1].z, st[1].w, 0x7632)};
  if (threadIdx.x == 0) TS(2 + layer * 20 + 12);
  const int a = c & 127, h = c >> 7;
#pragma unroll
  for (int i = 0; i < 4; i++) {
    if (i == 1) {
      mbar_wait(bar + 8 * B_XV, layer);
#pragma unroll
      for (int j = 1; j < 4; j++) xr[j] = ld_tagged(xin + j * (128 * LSEQ / 8));
      if (HELPER) {
        mbar_wait(bar + 8 * B_U, layer);
        conv_sums(sa, 0, c);
        fence_async_smem();
        bar_arrive(7, 256);
        sched_fence<1>();
        if (layer == 1 && c == 0) TS(46);
      }
    }
    const uint32_t x[4] = {xr[i].x, xr[i].y, xr[i].z, xr[i].w};
    uint32_t u[4];
#pragma unroll
    for (int k = 0; k < 4; k++)
      u[k] = hmul2(hadd2(x[k], nm[k]), rs[k]);
    sts128(sb + cv_u(i) + h * CV_UH + (127 - a) * 16, make_uint4(u[0], u[1], u[2], u[3]));
    warp_release(bar + 8 * (B_U + i));
    sched_fence<2>();
  }
}
__device__ __forceinline__ void conv_zero(uint32_t sb, int ht) {
  if (ht < 96) {
    const int ch = ht / 24, h2 = (ht / 12) & 1, qq = ht % 12;
    sts128(sb + cv_u(ch) + h2 * CV_UH + (128 + qq) * 16, make_uint4(0, 0, 0, 0));
  }
  if (ht >= 80) {
    const int i = ht - 80, ch = i / 12, q2 = i % 12;
    const int w2 = q2 < 2 ? 1 : q2 < 6 ? 2 : 3, cc = q2 < 2 ? q2 : q2 < 6 ? q2 - 2 : q2 - 6;
    sts128(sb + cv_pb(ch) + w2 * CV_PBW + (cc & 1) * (CV_PBW / 2) + (cc >> 1) * 16, make_uint4(0, 0, 0, 0));
  }
}

#define HANDOVER 1
template <int R>
__device__ __forceinline__ void conv_round(uint32_t sb, int layer, int wg, uint32_t* A, const uint32_t* P, uint32_t pb, uint32_t pe2) {
  const uint32_t bar = sb + SM_BAR;
  const int ch = 2 * R + 1 - wg;
  float acc[64];
  const uint64_t d = mkdesc(sb + cv_u(ch), CV_UH, 128, 0);
  FTS(39);
  if (R == 0) {
    mbar_wait(bar + 8 * (B_U + ch), layer);
    fence_reader();
  }
  sched_fence<3>();
  if (R == 1 || wg == 0) bar_sync(10 + ch, 256);
  if (layer == 0 && ch > 0 && ((PAUSE >> (ch - 1)) & 1)) mbar_wait(bar + 8 * (B_E + ch - 1), 0);
  if (layer == 0 && ch > 0 && ((PAUSE >> (ch + 3)) & 1)) mbar_wait(bar + 8 * (B_P + ch - 1), 0);
  FTS(41);
  if (ch == 0 && threadIdx.x == 128) TS(2 + layer * 20 + 13);
  wg_fence();
  conv_mmas<0, 1>(acc, A, d); conv_mmas<2, NA + 1>(acc, A, d);
  wg_commit();
  FTS(51);
  if (HANDOVER == 0 && (R == 0 || wg == 1)) bar_arrive(11 + ch, 256);
  bar_sync(7 + ch, 256);
  wg_fence();
  conv_mmas<1, 2>(acc, A, d); conv_mmas<NA + 1, 17>(acc, A, d);
  wgmma_ss<64, 1, 1>(acc, mkdesc(sb + cv_s(ch), 1024, 1024, 1), mkdesc(sb + cv_ft(ch), 256, 16, 0), 1);
  wgmma_ss<64, 1, 1>(acc, mkdesc(sb + cv_s(ch) + 2048, 1024, 1024, 1), mkdesc(sb + cv_ft(ch) + 512, 256, 16, 0), 1);
  wg_commit();
  if (HANDOVER == 1 && (R == 0 || wg == 1 || (G_WAIT == 3 && layer == 0))) bar_arrive(11 + ch, 256);
  FTS(61);
  wg_wait<0>();
#pragma unroll
  for (int j = 0; j < 16; j += 2)
    stsm4t(pb + R * 65536 - j * 128, packbf(acc[4 * j], acc[4 * j + 1]), packbf(acc[4 * j + 2], acc[4 * j + 3]),
           packbf(acc[4 * j + 4], acc[4 * j + 5]), packbf(acc[4 * j + 6], acc[4 * j + 7]));
  __syncwarp();
  if (elect_one()) mbar_arrive(bar + 8 * (B_P + ch));
  if (threadIdx.x == 0) TS(2 + layer * 20 + 14 + R);
  FTS(57);
  if (R == 0) {
    conv_unpark(A, P, opaque_tid() >> 10);
    mbar_wait(bar + 8 * (B_U + ch + 2), layer);
    fence_reader();
    conv_load<NP, 17>(A, pe2);
#pragma unroll
    for (int m = NP; m < 17; m++) A[4 * m + 3] = lds32(pe2 + 256 * m);
  }
}
__device__ __forceinline__ void conv_phase(const Params& p, uint32_t sb, int layer, int cta) {
  const int tid = opaque_tid();
  const int wg = __shfl_sync(~0u, tid >> 7, 0), w = __shfl_sync(~0u, (tid >> 5) & 3, 0);
  const uint32_t bar = sb + SM_BAR;
  uint32_t A[68], P[3 * NP];
  const uint32_t pe = sb + cv_pe(1 - wg) + 4 * (16 + 16 * w + 2 * ((tid & 31) >> 2) - 4 * (tid & 3));
  mbar_wait(bar + 8 * B_PE, layer);
  tensor_keepalive<2>();
  conv_load<0, 17>(A, pe);
#pragma unroll
  for (int m = 0; m < 17; m++) A[4 * m + 3] = copy_reg(A[4 * m], tid >> 10);
  if (wg == 0) {
    uint4 xr[4], st[4];
    if (PARK_FIRST) conv_park(P, pe + 65536);
    conv_prep_load(sb, layer, cta, tid + 128, xr, st);
    if (!PARK_FIRST) conv_park(P, pe + 65536);
    conv_prep<false>(sb, layer, cta, opaque_tid() + 128, xr, st, SumAddr());
  } else {
    conv_park(P, pe + 65536);
    if (KEEP & 8) mbar_wait(bar + 8 * B_GB, layer);
    tensor_keepalive<3>();
  }
  uint32_t pb;
  {
    const int l2 = opaque_tid() & 31, mt = l2 >> 3;
    pb = sb + cv_pb(1 - wg) + w * CV_PBW + (mt & 1) * (CV_PBW / 2) + (127 - 8 * (mt >> 1) - (l2 & 7) + w) * 16;
  }
  conv_round<0>(sb, layer, wg, A, P, pb, pe + 65536);
  conv_round<1>(sb, layer, wg, A, P, pb, 0);
  if (G_WAIT == 1 && layer == 0) mbar_wait(bar + 8 * (B_E + 3), layer);
  if (G_WAIT == 2 && layer == 0) mbar_wait(bar + 8 * (B_P + 3), layer);
}

__device__ __forceinline__ void final_phase(const Params& p, uint32_t sb, int cta, int wg, int w) {
  const int lane = opaque_tid() & 31, g = lane >> 2, t = lane & 3;
  constexpr int RS = 2 * DM;
  int it = 0;
  {
    const int lc = wg ? 0 : 3;
    const int p0 = (cta & 15) * 128 + 32 * w, c0 = 128 * lc + (cta >> 4) * 16;
    const bf16* src = g_xT + (size_t)(3 * DM + c0 + 4 * (g >> 1) + (g & 1)) * LSEQ + p0 + 8 * t;
    bf16* dst = p.out + (size_t)(2 * ((p0 & 1023) + 8 * (g >> 1) + (g & 1)) + (p0 >> 10)) * DM + c0 + 4 * t;
    if (wg == 0) {
      mbar_wait(sb + SM_BAR + 8 * (B_E + 3), 1);
      delay<D_FIN>();
    }
    uint4 a, b;
    for (;;) {
      a = ld_tagged((const uint4*)src); b = ld_tagged((const uint4*)(src + 2 * LSEQ));
      if (__all_sync(~0u, max(a.x, b.x) != ~0u)) break;
      if (++it > (1 << 22)) __trap();
    }
    if (threadIdx.x == 0) TS(42);
    *(uint2*)dst = make_uint2(movm_t(a.x), movm_t(b.x));
    *(uint2*)(dst + 2 * RS) = make_uint2(movm_t(a.y), movm_t(b.y));
    *(uint2*)(dst + 4 * RS) = make_uint2(movm_t(a.z), movm_t(b.z));
    *(uint2*)(dst + 6 * RS) = make_uint2(movm_t(a.w), movm_t(b.w));
  }
  if (wg == 1) {
    const int lc = 1 + (w >> 1);
    const int p0 = (cta & 31) * 64 + 32 * (w & 1), c0 = 128 * lc + (cta >> 5) * 32;
    const bf16* src = g_xT + (size_t)(3 * DM + c0 + 8 * (g >> 1) + (g & 1)) * LSEQ + p0 + 8 * t;
    bf16* dst = p.out + (size_t)(2 * ((p0 & 1023) + 8 * (g >> 1) + (g & 1)) + (p0 >> 10)) * DM + c0 + 8 * t;
    mbar_wait(sb + SM_BAR + 8 * (B_E + lc), 1);
    if (lc >= FIN_D0) delay<D_FIN2>();
    uint4 v[4];
    for (;;) {
#pragma unroll
      for (int q = 0; q < 4; q++) v[q] = ld_tagged((const uint4*)(src + 2 * q * LSEQ));
      if (__all_sync(~0u, max(max(v[0].x, v[1].x), max(v[2].x, v[3].x)) != ~0u)) break;
      if (++it > (1 << 22)) __trap();
    }
    *(uint4*)dst = make_uint4(movm_t(v[0].x), movm_t(v[1].x), movm_t(v[2].x), movm_t(v[3].x));
    *(uint4*)(dst + 2 * RS) = make_uint4(movm_t(v[0].y), movm_t(v[1].y), movm_t(v[2].y), movm_t(v[3].y));
    *(uint4*)(dst + 4 * RS) = make_uint4(movm_t(v[0].z), movm_t(v[1].z), movm_t(v[2].z), movm_t(v[3].z));
    *(uint4*)(dst + 6 * RS) = make_uint4(movm_t(v[0].w), movm_t(v[1].w), movm_t(v[2].w), movm_t(v[3].w));
  }
  if (threadIdx.x == 0) TS(43);
  if (threadIdx.x == 192) TS(63);
  if (threadIdx.x == 160) TS(53);
  if (threadIdx.x == 0) LTS(1);
}

struct cplx { float r, i; };
__device__ __forceinline__ cplx cmul(cplx a, cplx b) { return {fmaf(a.r, b.r, -a.i * b.i), fmaf(a.r, b.i, a.i * b.r)}; }
__device__ __forceinline__ cplx csqr(cplx a) { return {fmaf(a.r, a.r, -a.i * a.i), (a.r + a.r) * a.i}; }
__device__ __forceinline__ cplx cexp_l(float ar2, float ai, float l) {
  const float m = ex2(ar2 * l);
  const float x = ai * l;
  return {m * __cosf(x), m * __sinf(x)};
}

__device__ __forceinline__ void colsum_publish(uint32_t sb, int rb, int hg, int ht, uint32_t tag) {
  const int lane = ht & 31, q = lane & 15, h = lane >> 4;
  const uint32_t src = sb + SM_CW + (ht >> 5) * 4096 + h * 128 + (q & 1) * 8;
  float s[4] = {0.f, 0.f, 0.f, 0.f};
#pragma unroll 8
  for (int r = 0; r < 16; r++) {
    const float2 v = lds64f(src + r * 256 + (((q >> 1) ^ ((2 * r + h) & 7)) << 4));
    s[0] += bf_lo(__float_as_uint(v.x)); s[1] += bf_hi(__float_as_uint(v.x));
    s[2] += bf_lo(__float_as_uint(v.y)); s[3] += bf_hi(__float_as_uint(v.y));
  }
#pragma unroll
  for (int k = 0; k < 4; k++) s[k] += __shfl_xor_sync(~0u, s[k], 16);
  if (h == 0)
    st_tagged3(&g_colsum[(hg * 16 + rb) * 48 + (ht >> 5) * 16 + q], (__float_as_uint(s[0]) & ~7u) | tag, __float_as_uint(s[1]),
               __float_as_uint(s[2]), __float_as_uint(s[3]));
}
__device__ __forceinline__ void colsum_gather(uint32_t sb, int hg, int ht, uint32_t tag) {
  const int lane = ht & 31, rec = (ht >> 5) * 16 + (lane & 15);
  const uint4* src = &g_colsum[(hg * 16 + (lane >> 4) * 8) * 48 + rec];
  float s[4] = {0.f, 0.f, 0.f, 0.f};
#pragma unroll 1
  for (int h = 0; h < 2; h++, src += 4 * 48) {
    uint4 v[4];
    int it = 0;
    do {
#pragma unroll
      for (int i = 0; i < 4; i++) v[i] = ld_tagged(src + i * 48);
      if (++it > (1 << 22)) __trap();
    } while (!__all_sync(~0u, (v[0].x & 7u) == tag && (v[1].x & 7u) == tag && (v[2].x & 7u) == tag && (v[3].x & 7u) == tag));
#pragma unroll
    for (int i = 0; i < 4; i++) {
      s[0] += __uint_as_float(v[i].x & ~7u); s[1] += __uint_as_float(v[i].y); s[2] += __uint_as_float(v[i].z); s[3] += __uint_as_float(v[i].w);
    }
  }
#pragma unroll
  for (int k = 0; k < 4; k++) s[k] += __shfl_xor_sync(~0u, s[k], 16);
  if (lane < 16) sts128f(sb + SM_CS + rec * 16, s[0], s[1], s[2], s[3]);
}

__device__ __forceinline__ uint32_t packh(float lo, float hi) { uint32_t r; asm("cvt.rn.f16x2.f32 %0, %1, %2;" : "=r"(r) : "f"(hi), "f"(lo)); return r; }
__device__ __forceinline__ void mma_f16(float* d, uint32_t a0, uint32_t a1, uint32_t a2, uint32_t a3, uint32_t b0, uint32_t b1) {
  asm volatile("mma.sync.aligned.m16n8k16.row.col.f32.f16.f16.f32 {%0,%1,%2,%3}, {%4,%5,%6,%7}, {%8,%9}, {%0,%1,%2,%3};"
      : "+f"(d[0]), "+f"(d[1]), "+f"(d[2]), "+f"(d[3]) : "r"(a0), "r"(a1), "r"(a2), "r"(a3), "r"(b0), "r"(b1));
}
struct HSeed { uint32_t r, i; };
__device__ __forceinline__ HSeed hseed(cplx s) { return {packh(s.r, s.r), packh(s.i, s.i)}; }
__device__ __forceinline__ void hcmul(uint32_t& o_r, uint32_t& o_i, uint32_t br, uint32_t bi, HSeed s) {
  asm("{\n.reg .b32 t, u;\nmul.rn.f16x2 t, %3, %5;\nneg.f16x2 t, t;\nmul.rn.f16x2 u, %3, %4;\nfma.rn.f16x2 %0, %2, %4, t;\nfma.rn.f16x2 %1, %2, %5, u;\n}"
      : "=&r"(o_r), "=&r"(o_i) : "r"(br), "r"(bi), "r"(s.r), "r"(s.i));
}
struct HTile { uint32_t r[4], i[4]; };
__device__ __forceinline__ void tile_set(HTile& t, int k, cplx a, cplx b) { t.r[k] = packh(a.r, b.r); t.i[k] = packh(a.i, b.i); }
__device__ __forceinline__ void tile_upper(HTile& t, HSeed s) { hcmul(t.r[2], t.i[2], t.r[0], t.i[0], s); hcmul(t.r[3], t.i[3], t.r[1], t.i[1], s); }
__device__ __forceinline__ HTile tile_shift(const HTile& t, HSeed s) {
  HTile o;
#pragma unroll
  for (int k = 0; k < 4; k++) hcmul(o.r[k], o.i[k], t.r[k], t.i[k], s);
  return o;
}
__device__ __forceinline__ void tile_put(const HTile& t, uint32_t a) {
  sts128(a, make_uint4(t.r[0], t.r[1], t.r[2], t.r[3]));
  sts128(a + 512, make_uint4(t.i[0], t.i[1], t.i[2], t.i[3]));
}
__device__ __forceinline__ HTile tile_get(uint32_t a) { HTile o; ldsm4t(o.r, a); ldsm4t(o.i, a + 512); return o; }
__device__ __forceinline__ void tile_mma(float* T, const HTile& a0, const HTile& a1, const HTile& b) {
  mma_f16(T, a0.r[0], a0.r[1], a0.r[2], a0.r[3], b.r[0], b.r[1]);
  mma_f16(T, a0.i[0], a0.i[1], a0.i[2], a0.i[3], b.i[0], b.i[1]);
  mma_f16(T, a1.r[0], a1.r[1], a1.r[2], a1.r[3], b.r[2], b.r[3]);
  mma_f16(T, a1.i[0], a1.i[1], a1.i[2], a1.i[3], b.i[2], b.i[3]);
}
__device__ __forceinline__ void tile_mma2(float* T, float* U, const HTile& a0, const HTile& a1, const HTile& b, const HTile& c) {
  mma_f16(T, a0.r[0], a0.r[1], a0.r[2], a0.r[3], b.r[0], b.r[1]);
  mma_f16(U, a0.r[0], a0.r[1], a0.r[2], a0.r[3], c.r[0], c.r[1]);
  mma_f16(T, a0.i[0], a0.i[1], a0.i[2], a0.i[3], b.i[0], b.i[1]);
  mma_f16(U, a0.i[0], a0.i[1], a0.i[2], a0.i[3], c.i[0], c.i[1]);
  mma_f16(T, a1.r[0], a1.r[1], a1.r[2], a1.r[3], b.r[2], b.r[3]);
  mma_f16(U, a1.r[0], a1.r[1], a1.r[2], a1.r[3], c.r[2], c.r[3]);
  mma_f16(T, a1.i[0], a1.i[1], a1.i[2], a1.i[3], b.i[2], b.i[3]);
  mma_f16(U, a1.i[0], a1.i[1], a1.i[2], a1.i[3], c.i[2], c.i[3]);
}
__device__ __forceinline__ void kgen_unit(uint32_t tab, uint32_t taba, float ar2, float ai, cplx c, float (&T)[5][4]) {
  const cplx z1 = cexp_l(ar2, ai, 1.f), z16 = cexp_l(ar2, ai, 16.f), z256 = cexp_l(ar2, ai, 256.f);
  HTile a0, a1, b0, b1;
  {
    const cplx y1 = {z16.r, -z16.i}, y2 = csqr(y1), y3 = cmul(y2, y1), y4 = csqr(y2), y5 = cmul(y4, y1), y6 = csqr(y3), y7 = cmul(y4, y3);
    HTile t;
    tile_set(t, 0, {1.f, 0.f}, y1); tile_set(t, 1, y2, y3); tile_set(t, 2, y4, y5); tile_set(t, 3, y6, y7);
    const HTile u = tile_shift(t, hseed(csqr(y4)));
    __syncwarp();
    tile_put(t, tab); tile_put(u, tab + 1024);
    __syncwarp();
    a0 = tile_get(taba); a1 = tile_get(taba + 256);
  }
  const cplx z2 = csqr(z1), z4 = csqr(z2), z8 = csqr(z4);
  const HSeed h8 = hseed(z8);
  const cplx d = cmul(c, z256), e = cmul(d, z256);
  {
    const cplx z512 = csqr(z256), f = cmul(e, z512), f8 = cmul(f, z8), f16 = cmul(f, z16), e4 = cmul(e, z4);
    HTile t, u;
    tile_set(t, 0, e4, cmul(e, z8)); tile_set(t, 1, cmul(e4, z8), cmul(e, z16));
    tile_upper(t, hseed(z256));
    tile_set(u, 0, f8, f16); tile_set(u, 1, cmul(f8, z256), cmul(f16, z256));
    tile_upper(u, hseed(z512));
    __syncwarp();
    tile_put(t, tab); tile_put(u, tab + 1024);
    __syncwarp();
    b0 = tile_get(tab); b1 = tile_get(tab + 1024);
  }
  {
    const cplx d2 = cmul(d, z2), d4 = cmul(d, z4);
    HTile t;
    tile_set(t, 0, d2, d4); tile_set(t, 1, cmul(d2, z4), cmul(d, z8));
    tile_upper(t, h8);
    __syncwarp();
    tile_put(t, tab);
    __syncwarp();
    tile_mma2(T[3], T[4], a0, a1, b0, b1);
    b0 = tile_get(tab);
  }
  {
    const cplx c1 = cmul(c, z1), c2 = cmul(c, z2), c3 = cmul(c1, z2), c4 = cmul(c, z4);
    HTile t;
    tile_set(t, 0, c1, c2); tile_set(t, 1, c3, c4); tile_set(t, 2, cmul(c1, z4), cmul(c2, z4)); tile_set(t, 3, cmul(c3, z4), cmul(c4, z4));
    const HTile u = tile_shift(t, h8);
    __syncwarp();
    tile_put(t, tab); tile_put(u, tab + 1024);
    __syncwarp();
    tile_mma(T[2], a0, a1, b0);
    b0 = tile_get(tab); b1 = tile_get(tab + 1024);
    tile_mma2(T[0], T[1], a0, a1, b0, b1);
  }
}
struct ModeIn { uint2 ar, ai, br, bi, cr, ci; };
__device__ __forceinline__ ModeIn load_modes(const Params& p, int idx) {
  return {*(const uint2*)(p.a_re + idx), *(const uint2*)(p.a_im + idx), *(const uint2*)(p.b_re + idx),
          *(const uint2*)(p.b_im + idx), *(const uint2*)(p.c_re + idx), *(const uint2*)(p.c_im + idx)};
}
__device__ __forceinline__ float bf_el(uint2 v, int k) { const uint32_t x = (k & 2) ? v.y : v.x; return (k & 1) ? bf_hi(x) : bf_lo(x); }
struct KGen { float4 cur; float T[5][4]; };
__device__ __forceinline__ uint32_t kgen_slot(uint32_t sb, int ht, int u) {
  return sb + (u < 3 ? SM_KC + (ht >> 5) * (KC_STRIDE * 2) + (u - 1) * 512 + (ht & 31) * 16 + 16 : SM_HALO + 1024 + ht * 16);
}
__device__ __forceinline__ void kgen_setup(KGen& s, uint32_t sb, int cta, int ht, const ModeIn& in, bf16 logdt, bf16 dskip) {
  const float dt = __bfloat162float(__float2bfloat16_rn(expf(__bfloat162float(logdt))));
  float mx = 0.f, k0 = 0.f, ar2[4];
  cplx c[4];
#pragma unroll
  for (int k = 0; k < 4; k++) {
    ar2[k] = (dt * bf_el(in.ar, k)) * 1.4426950408889634f;
    c[k] = cmul({bf_el(in.cr, k), bf_el(in.ci, k)}, {dt * bf_el(in.br, k), dt * bf_el(in.bi, k)});
    k0 += c[k].r;
    mx = fmaxf(mx, fmaxf(fabsf(c[k].r), fabsf(c[k].i)) * ex2(fmaxf(ar2[k] * 2048.f, 0.f)));
  }
  const int ex = min(max(267 - (int)(__reduce_max_sync(~0u, __float_as_uint(mx)) >> 23), 1), 253);
  const float sc = __uint_as_float(ex << 23);
#pragma unroll
  for (int o = 16; o > 0; o >>= 1) k0 += __shfl_xor_sync(~0u, k0, o);
  if ((ht & 31) == 0) {
    const uint32_t kc = sb + SM_KC + (ht >> 5) * (KC_STRIDE * 2);
    sts16(kc, __bfloat16_as_ushort(__float2bfloat16_rn(k0 + __bfloat162float(dskip))));
    sts16(kc + 641 * 2, 0);
    sts32f(kc + 644 * 2, __uint_as_float((254 - ex) << 23));
  }
  s.cur = make_float4(ar2[0], dt * bf_el(in.ai, 0), c[0].r * sc, c[0].i * sc);
#pragma unroll
  for (int k = 1; k < 4; k++) sts128f(kgen_slot(sb, ht, k), ar2[k], dt * bf_el(in.ai, k), c[k].r * sc, c[k].i * sc);
#pragma unroll
  for (int i = 0; i < 5; i++) s.T[i][0] = s.T[i][1] = s.T[i][2] = s.T[i][3] = 0.f;
}
__device__ __forceinline__ void kgen_finish(KGen& s, uint32_t sb, int cta, int ht) {
  const int w = ht >> 5, lane = ht & 31, g = lane >> 2, t = lane & 3;
  const uint32_t kc = sb + SM_KC + w * KC_STRIDE * 2;
  __syncwarp();
  const float inv = __uint_as_float(lds32(kc + 644 * 2));
  auto put = [&](int idx, float v) {
    sts16(kc + idx * 2, __bfloat16_as_ushort(__float2bfloat16_rn(v)));
  };
#pragma unroll
  for (int hi = 0; hi < 2; hi++)
#pragma unroll
    for (int lo = 0; lo < 2; lo++) {
      const int i = g + 8 * hi, j = 2 * t + lo, e = 2 * hi + lo;
      put(16 * i + 1 + j, s.T[0][e] * inv);
      put(16 * i + 9 + j, s.T[1][e] * inv);
      put(257 + 8 * i + j, s.T[2][e] * inv);
      put(385 + 4 * i + (j & 3) + 64 * (j >> 2), s.T[3][e] * inv);
      put(513 + 2 * i + lo + 32 * t, s.T[4][e] * inv);
    }
}

__device__ __forceinline__ void expand_taps(uint32_t sb, int ht) {
  const int ch = ht >> 5, lane = ht & 31;
  const uint32_t kc = sb + SM_KC + ch * KC_STRIDE * 2;
  const uint32_t dst0 = sb + cv_pe(ch);
  auto put = [&](int G, uint32_t u0, uint32_t u1, uint32_t v0, uint32_t v1, uint32_t v2, uint32_t v3, uint32_t v4, uint32_t v5, uint32_t v6, uint32_t v7) {
    const uint32_t dst = dst0 + G * 32;
    sts128(dst, make_uint4(v0 | (u0 << 16), v1 | (u1 << 16), v2 | (v0 << 16), v3 | (v1 << 16)));
    sts128(dst + 16, make_uint4(v4 | (v2 << 16), v5 | (v3 << 16), v6 | (v4 << 16), v7 | (v5 << 16)));
  };
  {
    const uint4 q = lds128(kc + lane * 16);
    const uint32_t pv = lane ? lds32(kc + lane * 16 - 4) : 0u;
    const uint32_t dst = dst0 + (lane + 2) * 32;
    sts128(dst, make_uint4(__byte_perm(q.x, pv, 0x5410), __byte_perm(q.x, pv, 0x7632), __byte_perm(q.y, q.x, 0x5410), __byte_perm(q.y, q.x, 0x7632)));
    sts128(dst + 16, make_uint4(__byte_perm(q.z, q.y, 0x5410), __byte_perm(q.z, q.y, 0x7632), __byte_perm(q.w, q.z, 0x5410), __byte_perm(q.w, q.z, 0x7632)));
    if (lane < 4) sts128(dst0 + lane * 16, make_uint4(0, 0, 0, 0));
  }
  uint32_t a[5], b[2][3], fv[4];
  {
    const uint32_t s1 = kc + 2 * (256 + 4 * lane);
#pragma unroll
    for (int k = 0; k < 5; k++) a[k] = lds16(s1 + 2 * k);
#pragma unroll
    for (int u = 0; u < 2; u++) {
      const uint32_t s2 = kc + 2 * (384 + 2 * (lane + 32 * u));
#pragma unroll
      for (int k = 0; k < 3; k++) b[u][k] = lds16(s2 + 2 * k);
    }
#pragma unroll
    for (int k = 0; k < 4; k++) fv[k] = lds16(kc + 2 * (640 - 4 * lane - k));
  }
  const uint32_t am1 = lds16(kc + 2 * (lane ? 256 + 4 * lane : 255)), am2 = lds16(kc + 2 * (lane ? 255 + 4 * lane : 254));
  const uint32_t bm2 = lds16(kc + 2 * (lane ? 384 + 2 * lane : 383)), k1024 = lds16(kc + 2 * 512);
  put(34 + lane, am2, am1, a[0], a[0], a[1], a[2], a[2], a[2], a[3], a[4]);
#pragma unroll
  for (int u = 0; u < 2; u++) put(66 + lane + 32 * u, u ? b[u][0] : bm2, b[u][0], b[u][0], b[u][0], b[u][0], b[u][1], b[u][1], b[u][1], b[u][2], b[u][2]);
  if (lane < 10) {
    const uint32_t v = lane == 0 ? k1024 : 0u;
    put(130 + lane, v, v, v, v, v, v, v, 0u, 0u, 0u);
  }
  const uint32_t ft = sb + cv_ft(ch) + 4 * lane;
#pragma unroll
  for (int ty = 0; ty < 2; ty++) {
    const uint32_t v = fv[ty] | (fv[ty + 2] << 16);
    sts32f(ft + ty * 512, __uint_as_float(v));
    sts32f(ft + ty * 512 + 128, 0.f);
    sts32f(ft + ty * 512 + 256 + (lane < 2 ? 120 : -8), __uint_as_float(lane < 2 ? 0u : v));
    sts32f(ft + ty * 512 + 384, 0.f);
  }
}

__device__ __forceinline__ int role_id() { int v; asm volatile("mov.u32 %0, %%ctaid.x;" : "=r"(v)); return v; }
#define GMAP 8
__device__ __forceinline__ int role_rb(int cta) { return 4 * (cta >> 5) + (cta & 3); }
__device__ __forceinline__ int role_hg(int cta) { return 2 * (((cta >> 3) & 3) ^ (((cta >> 5) & 1) * 3)) + ((cta >> 2) & 1); }
__device__ __forceinline__ int role_rb2(int cta) { return cta >> 3; }
__device__ __forceinline__ int role_q2(int cta) { return cta & 7; }

__global__ void __launch_bounds__(NTHREADS, 1) fused_kernel(const __grid_constant__ Params p) {
  extern __shared__ __align__(1024) uint8_t smem[];
  const uint32_t sb = s32(smem);
  const int tid = threadIdx.x, lane = tid & 31;
  const int warp = __shfl_sync(~0u, tid >> 5, 0);
  const uint32_t bar = sb + SM_BAR;
  if (tid == 0) TS(0);
  const int cta0 = role_id();
  if (warp == 0 && elect_one()) {
    const int rb = role_rb(cta0), hg = role_hg(cta0);
#pragma unroll
    for (int c = 0; c < 2; c++) { mbar_init(bar + 8 * (B_XF + c), 1); mbar_init(bar + 8 * (B_KVF + c), 1); }
    fence_async_smem();
#pragma unroll
    for (int c = 0; c < 2; c++) {
      mbar_expect(bar + 8 * (B_XF + c), 16384);
      tma_ld(sb + SM_X + c * 16384, &p.mapX128, (rb >> 3) * DM + c * 64, (rb & 7) * 128, bar + 8 * (B_XF + c));
      mbar_expect(bar + 8 * (B_KVF + c), 24576);
      tma_ld3(sb + SM_W + c * 24576, &p.mapW3, hg * 64, c * 64, 0, bar + 8 * (B_KVF + c));
    }
  }
  if (warp == 2) tensor_keepalive<4>();
  if (warp == 1 && elect_one()) {
    const int rb = role_rb(cta0), hg = role_hg(cta0);
#pragma unroll
    for (int c = 2; c < 8; c++) mbar_init(bar + 8 * (B_XF + c), 1);
    mbar_init(bar + 8 * (B_KVF + 2), 1); mbar_init(bar + 8 * B_CW, 1);
    fence_async_smem();
    delay<D_START>();
    mbar_expect(bar + 8 * B_CW, 12288);
    tma_ld3(sb + SM_CW, &p.mapW3h, hg * 64, rb * 32, 0, bar + 8 * B_CW);
#pragma unroll
    for (int c = 2; c < 8; c++) {
      mbar_expect(bar + 8 * (B_XF + c), 16384);
      tma_ld(sb + SM_X + c * 16384, &p.mapX128, (rb >> 3) * DM + c * 64, (rb & 7) * 128, bar + 8 * (B_XF + c));
      if (c < 3) {
        mbar_expect(bar + 8 * (B_KVF + c), 24576);
        tma_ld3(sb + SM_W + c * 24576, &p.mapW3, hg * 64, c * 64, 0, bar + 8 * (B_KVF + c));
      }
    }
    TS(56);
  }
  if ((warp & 2) != 0 && warp < 15 && elect_one()) {
    const int grp = 1 + (warp & 1) + 2 * (warp >> 2), cnt = grp < 4 ? 1 : grp < 5 ? 2 : grp < 7 ? 4 : 8;
#pragma unroll
    for (int k = 0; k < 10; k++)
      if (k != 0 || grp > 3 || grp == 2) mbar_init(bar + 8 * (10 * grp + k), cnt);
    fence_async_smem();
  }

  if (warp < 8) {
    if (tid == 0) TS(1);
    asm volatile("setmaxnreg.inc.sync.aligned.u32 %0;" ::"n"(R_CONS));
    const int cta = role_id();
    auto warp_id = [] { return __shfl_sync(~0u, opaque_tid() >> 5, 0); };
    tensor_keepalive<0>();
    if (tid == 0) TS(54);
#pragma unroll 1
    for (int layer = 0; layer < 2; layer++) {
      { const int cw = warp_id(); attn_phase(p, sb, layer, role_rb(cta), role_hg(cta), cw >> 2, cw & 3); }
      if (STOP == 1 + 3 * layer) return;
      { const int cw = warp_id(); proj_phase(p, sb, layer, role_rb2(cta), role_q2(cta), cw >> 2, cw & 3); }
      if (STOP == 2 + 3 * layer) return;
      conv_phase(p, sb, layer, cta);
      if (STOP == 3 + 3 * layer) return;
    }
    { const int cw = warp_id(); final_phase(p, sb, cta, cw >> 2, cw & 3); }
  } else if (warp < 12) {
    asm volatile("setmaxnreg.dec.sync.aligned.u32 %0;" ::"n"(R_HELP));
    const int ht = tid - 256;
    const int cta = role_id(), rb = role_rb(cta), hg = role_hg(cta);
    unsigned ep0 = 0;
    if (ht == 0) ep0 = ld_relaxed(&g_cnt[C_CS * 32]);
    bar_sync(0, NTHREADS);
    if (ht == 0) {
      asm volatile("st.shared.v2.u32 [%0], {%1, 0};" ::"r"(sb + SM_EP), "r"(ep0 / NCTA) : "memory");
      mbar_arrive(bar + 8 * B_EP);
    }
    mbar_wait(bar + 8 * B_EP, 0);
    stats_publish(sb, 0, rb, hg, opaque_tid() - 256, part_tag(lds32(sb + SM_EP), 0));
    if (ht < 48) {
      const bf16* q = (&p.a_re)[ht >> 3];
      asm volatile("prefetch.global.L2 [%0];" ::"l"(q + cv_chan(cta, (ht >> 1) & 3) * 128 + (ht & 1) * 64));
    }
    {
      KGen kg;
      const uint32_t tab0 = sb + ((ht >> 5) < 2 ? SM_T : SM_T2 - 4096) + (ht >> 5) * 2048;
      const uint32_t tab = tab0 + (ht & 31) * 16, taba = tab0 + ((ht >> 3) & 1) * 1024 + (((ht >> 1) & 8) + (ht & 7)) * 16;
      delay<D_ST0>();
      stats_gather(sb, rb, opaque_tid() - 256, part_tag(lds32(sb + SM_EP), 0));
      if (ht == 0) TS(40);
      const int chn = cv_chan(cta, ht >> 5);
      const ModeIn modes = load_modes(p, chn * 128 + (ht & 31) * 4);
      const bf16 logdt = p.log_dt[chn], dskip = p.dskip[chn];
      if (!HALO_W14 && KG_START != 4) halo_receive(sb, 0, rb, hg, opaque_tid() - 256);
      if (KG_START == 1) mbar_wait(bar + 8 * B_HF, 0);
      kgen_setup(kg, sb, cta, ht, modes, logdt, dskip);
      if (!HALO_W14 && KG_START == 4) halo_receive(sb, 0, rb, hg, opaque_tid() - 256);
      if (KG_START == 2) mbar_wait(bar + 8 * B_HF, 0);
      if (KG_START == 3) mbar_wait(bar + 8 * B_QDONE, 0);
#pragma unroll 1
      for (int u = 0; u < 4; u++) {
        if (u == KG_PRE) {
          KTS(39);
          mbar_wait(bar + 8 * B_AD, 0);
          KTS(41);
        }
        kgen_unit(tab, taba, kg.cur.x, kg.cur.y, {kg.cur.z, kg.cur.w}, kg.T);
        kg.cur = lds128f(kgen_slot(sb, opaque_tid() - 256, u + 1));
      }
      kgen_finish(kg, sb, cta, opaque_tid() - 256);
    }
    KTS(51);
    bar_sync(4, 128);
#pragma unroll 1
    for (int layer = 0; layer < 2; layer++) {
      if (STOP <= 1 + 3 * layer) return;
      mbar_wait(bar + 8 * (EXP_LATE ? B_PS : B_PDONE), layer);
      expand_taps(sb, opaque_tid() - 256);
      conv_zero(sb, opaque_tid() - 256);
      if (ht == 0) TS(52 + layer);
      warp_release(bar + 8 * B_PE);
      if (STOP <= 2 + 3 * layer) return;
      {
        uint4 xr[4], st[4];
        const int c = opaque_tid() - 256;
        const SumAddr sa = conv_sum_addr(sb, c);
        conv_prep_load(sb, layer, cta, c, xr, st);
        conv_prep<true>(sb, layer, cta, c, xr, st, sa);
        if (layer == 1 && ht == 0) TS(62);
        const bf16* xup = g_xT + (size_t)(2 * layer * DM + cta) * LSEQ + (c + 128) * 8;
        const int ahead = layer ? S_AHEAD1 : S_AHEAD0;
        mbar_wait(bar + 8 * (B_U + 3), layer);
        if (ahead == 2) {
          conv_sums(sa, 1, c);
          fence_async_smem();
          bar_arrive(8, 256);
        }
        st[0] = ldcg128(xup);
#pragma unroll
        for (int lc = 0; lc < 4; lc++) {
          if (lc < 3 && lc + ahead < 4) {
            conv_sums(sa, lc + ahead, c);
            fence_async_smem();
            bar_arrive(7 + lc + ahead, 256);
            sched_fence<4>();
          }
          if (lc < 3) st[lc + 1] = ldcg128(xup + (lc + 1) * 128 * LSEQ);
          conv_epi(sb, layer, cta, lc, c, xr[lc], st[lc]);
          warp_release(bar + 8 * (B_E + lc));
          sched_fence<5>();
          if (layer == 1 && lc == 3 && ht == 0) TS(38);
        }
      }
      if (layer == 0 && STOP > 3) {
        const int c1 = role_id();
        stats_publish(sb, 1, role_rb(c1), role_hg(c1), opaque_tid() - 256, part_tag(lds32(sb + SM_EP), 2));
        delay<D_ST>();
        stats_gather(sb, role_rb(c1), opaque_tid() - 256, part_tag(lds32(sb + SM_EP), 2));
        if (ht == 0) TS(25);
        if (!HALO_W14) halo_receive(sb, 1, role_rb(c1), role_hg(c1), opaque_tid() - 256);
      }
    }
  } else {
    asm volatile("setmaxnreg.dec.sync.aligned.u32 %0;" ::"n"(512 - 2 * R_CONS - R_HELP));
    const int cta = role_id(), rb = role_rb(cta), hg = role_hg(cta), rb2 = role_rb2(cta), q2 = role_q2(cta);
    bar_sync(0, NTHREADS);
    if (warp != 12) {
      mbar_wait(bar + 8 * B_EP, 0);
      const uint32_t tag = lds32(sb + SM_EP) % 7 + 1;
      mbar_wait(bar + 8 * B_CW, 0);
      colsum_publish(sb, rb, hg, tid - 416, tag);
      if (tid == 416) TS(50);
      delay<D_CS>();
      colsum_gather(sb, hg, tid - 416, tag);
      __syncwarp();
      if (tid == 416) TS(55);
    }
    if (elect_one()) mbar_arrive(bar + 8 * B_CSF);
    if (warp == 12) {
      if (elect_one()) {
        unsigned epoch = 0;
#pragma unroll 1
        for (int layer = 0; layer < 2; layer++) {
          auto ld_w = [&](int c, int slot) {
            const uint32_t b = bar + 8 * (B_KVF + c);
            mbar_expect(b, 24576);
            tma_ld3(sb + SM_W + slot * 24576, &p.mapW3, hg * 64, c * 64, 0, b);
          };
          if (layer == 0) {
            mbar_wait(bar + 8 * (B_KVF + 2), 0);
            if (rb2 < 4) tma_prefetch2(&p.mapWo128, q2 * 64, rb2 * 128);
            asm volatile("prefetch.tensormap [%0];" ::"l"(&p.mapO) : "memory");
            asm volatile("prefetch.tensormap [%0];" ::"l"(&p.mapO128) : "memory");
            asm volatile("prefetch.tensormap [%0];" ::"l"(&p.mapXT) : "memory");
            asm volatile("prefetch.tensormap [%0];" ::"l"(&p.mapXT3) : "memory");
            mbar_wait(bar + 8 * B_EP, 0);
            epoch = lds32(sb + SM_EP);
          } else {
            mbar_wait(bar + 8 * (B_U + 3), 0);
            ld_w(0, 0); ld_w(1, 1); ld_w(2, 2);
          }
          {
            int slot = 0;
#pragma unroll 1
            for (int c = 3; c < 8; c++) {
              mbar_wait(bar + 8 * (B_KVE + c - 3), layer);
              ld_w(c, slot);
              slot = slot == 2 ? 0 : slot + 1;
            }
          }
          if (STOP <= 1 + 3 * layer) return;
          const int early = layer ? WO_E1 : WO_E0;
          mbar_wait(bar + 8 * B_STF, layer);
          fence_async_smem();
          mbar_expect(bar + 8 * B_WOF, 65536);
#pragma unroll
          for (int c = 0; c < 4; c++) if (c < early) tma_ld(sb + SM_WO + c * 16384, &p.mapWo128, q2 * 64, c * 128, bar + 8 * B_WOF);
          mbar_wait(bar + 8 * B_QDONE, layer);
          mbar_wait(bar + 8 * B_HF, layer);
#pragma unroll
          for (int c = 0; c < 4; c++) if (c >= early) tma_ld(sb + SM_WO + c * 16384, &p.mapWo128, q2 * 64, c * 128, bar + 8 * B_WOF);
          {
            const uint32_t b = bar + 8 * B_RF;
            mbar_expect(b, 16384);
            if (layer == 0) tma_ld(sb + SM_R, &p.mapX128, (rb2 >> 3) * DM + q2 * 64, (rb2 & 7) * 128, b);
            else tma_ld3(sb + SM_R, &p.mapXT3, 0, DM + q2 * 64, rb2 * 2, b);
          }
#pragma unroll
          for (int c = 0; c < 8; c++) mbar_expect(bar + 8 * (B_OF + c), 16384);
          spin_until(&g_cnt[(C_O + rb2) * 32], (2 * epoch + layer + 1) * 16);
          fence_async_global();
#pragma unroll
          for (int c = 0; c < 8; c++) {
            if (c == 6) { mbar_wait(bar + 8 * B_OST, layer); fence_async_smem(); }
            tma_ld(sb + sm_o(c), &p.mapO128, c * 64, rb2 * 128, bar + 8 * (B_OF + c));
          }
          if (STOP <= 3 + 3 * layer) return;
        }
      }
    } else if (warp == 13) {
      if (elect_one() && STOP > 1) {
        const unsigned target = (lds32(sb + SM_EP) + 1) * NCTA;
        mbar_wait(bar + 8 * B_RE, 0);
        spin_until(&g_cnt[C_CS * 32 + 2], 2 * target);
        mbar_arrive(bar + 8 * B_XV);
        if (STOP <= 3) return;
        auto ld_x = [&](int c) { tma_ld3(sb + SM_X + c * 16384, &p.mapXT3, 0, DM + c * 64, rb * 2, bar + 8 * (B_XF + c)); };
#pragma unroll
        for (int c = 0; c < 8; c++) mbar_expect(bar + 8 * (B_XF + c), 16384);
        spin_until(&g_cnt[C_G1 * 32], target);
        fence_async_global();
        fence_async_smem();
        ld_x(0); ld_x(1);
        int done = 1, it = 0;
        while (done < 4) {
          const uint4 v = ld_tagged((const uint4*)&g_cnt[C_G1 * 32]);
          const int n = 4 + ((int)(v.y - target) >> 31) + ((int)(v.z - target) >> 31) + ((int)(v.w - target) >> 31);
          if (n == done) { if (++it > (1 << 23)) __trap(); continue; }
          if (n == 4) TS(44);
          fence_async_global();
          fence_async_smem();
          if (done == 1) { ld_x(2); ld_x(3); }
          const int h = hg >> 2;
          if (done < 3 && n >= 3) ld_x(4 + h);
          if (n == 4) ld_x(6 + h);
          if (done < 3 && n >= 3) ld_x(5 - h);
          if (n == 4) ld_x(7 - h);
          done = n;
        }
        if (STOP <= 4) return;
        mbar_wait(bar + 8 * B_RE, 1);
        spin_until(&g_cnt[C_CS * 32 + 3], 2 * target);
        mbar_arrive(bar + 8 * B_XV);
      }
    } else if (warp == 15) {
      mbar_wait(bar + 8 * B_EP, 0);
      const unsigned epoch = lds32(sb + SM_EP);
#pragma unroll 1
      for (int layer = 0; layer < 2; layer++) {
        mbar_wait(bar + 8 * (B_KVF + FILL_AT), layer);
#pragma unroll
        for (int k = 0; k < 8; k++) ((uint4*)(g_xT + (size_t)(2 * layer * DM + cta) * LSEQ))[32 * k + lane] = make_uint4(~0u, ~0u, ~0u, ~0u);
        mbar_wait(bar + 8 * (B_KVF + FILL_AT + 1), layer);
#pragma unroll
        for (int k = 0; k < 16; k++)
          ((uint4*)(g_xT + (size_t)(3 * DM + cv_chan(cta, 3 - (k >> 2))) * LSEQ))[128 * layer + 32 * (k & 3) + lane] = make_uint4(~0u, ~0u, ~0u, ~0u);
        if (lane < 4) ((uint4*)g_stats)[layer * 512 + cta * 4 + lane] = make_uint4(0, 0, 0, 0);
        __syncwarp();
        if (elect_one()) {
          red_release(&g_cnt[C_CS * 32 + layer]);
          spin_until(&g_cnt[C_CS * 32 + layer], (epoch + 1) * NCTA);
          mbar_arrive(bar + 8 * B_ZF);
          if (layer == 0 && STOP > 2) {
#pragma unroll
            for (int lc = 0; lc < 4; lc++) {
              mbar_wait(bar + 8 * (B_E + lc), 0);
              fence_reader();
              bulk_st(g_xT + (size_t)(DM + cv_chan(cta, lc)) * LSEQ, sb + cv_s(lc), 4096);
              bulk_commit();
              bulk_wait_all();
              red_relaxed(&g_cnt[C_G1 * 32 + lc]);
              if (lc == 3) TS(18);
            }
          }
        }
        __syncwarp();
        if (STOP <= 3) return;
      }
    } else if (warp == 14) {
      mbar_wait(bar + 8 * B_EP, 0);
      const unsigned epoch = lds32(sb + SM_EP);
#pragma unroll 1
      for (int layer = 0; layer < 2; layer++) {
        if (STOP <= 3 * layer) return;
        if (HALO_W14) halo_receive1(sb, layer, rb, hg, opaque_tid() & 31, 2 * epoch + layer + 1);
        if (STOP <= 1 + 3 * layer) return;
        mbar_wait(bar + 8 * B_ZF, layer);
        proj_stats(sb, layer, rb2, q2, opaque_tid() & 31, part_tag(epoch, 2 * layer + 1));
        if (layer == 1 && lane == 0) TS(5);
        delay<D_PREP>();
        if (lane == 0) mbar_arrive(bar + 8 * B_GB);
      }
    }
  }
}

typedef CUresult (*EncodeFn)(CUtensorMap*, CUtensorMapDataType, cuuint32_t, void*, const cuuint64_t*, const cuuint64_t*,
                             const cuuint32_t*, const cuuint32_t*, CUtensorMapInterleave, CUtensorMapSwizzle,
                             CUtensorMapL2promotion, CUtensorMapFloatOOBfill);

static void make_map(EncodeFn enc, CUtensorMap* m, void* ptr, uint64_t cols, uint64_t rows, uint32_t box_rows) {
  cuuint64_t dims[2] = {cols, rows};
  cuuint64_t strides[1] = {cols * 2};
  cuuint32_t box[2] = {64, box_rows};
  cuuint32_t es[2] = {1, 1};
  enc(m, CU_TENSOR_MAP_DATA_TYPE_BFLOAT16, 2, ptr, dims, strides, box, es, CU_TENSOR_MAP_INTERLEAVE_NONE,
      CU_TENSOR_MAP_SWIZZLE_128B, CU_TENSOR_MAP_L2_PROMOTION_L2_128B, CU_TENSOR_MAP_FLOAT_OOB_FILL_NONE);
}
static void make_map3(EncodeFn enc, CUtensorMap* m, void* ptr, uint64_t d0, uint64_t cols, uint64_t rows, uint64_t blk_stride,
                      uint64_t nblocks, uint32_t nblk, uint32_t box_rows = 64) {
  cuuint64_t dims[3] = {d0, rows, nblocks};
  cuuint64_t strides[2] = {cols * 2, blk_stride * 2};
  cuuint32_t box[3] = {64, box_rows, nblk};
  cuuint32_t es[3] = {1, 1, 1};
  enc(m, CU_TENSOR_MAP_DATA_TYPE_BFLOAT16, 3, ptr, dims, strides, box, es, CU_TENSOR_MAP_INTERLEAVE_NONE,
      CU_TENSOR_MAP_SWIZZLE_128B, CU_TENSOR_MAP_L2_PROMOTION_L2_128B, CU_TENSOR_MAP_FLOAT_OOB_FILL_NONE);
}

extern "C" void kernel_launch(void* const* d_in, const int* in_sizes, int n_in, void* d_out, int out_size) {
  static Params prm;
  static void* cached[13] = {nullptr};
  static bool attr_done = false;
  bool same = attr_done && cached[12] == d_out;
  for (int i = 0; i < 12 && same; i++) same = cached[i] == d_in[i];
  if (!same) {
    void* fn = nullptr;
    cudaDriverEntryPointQueryResult qr;
    cudaGetDriverEntryPoint("cuTensorMapEncodeTiled", &fn, cudaEnableDefault, &qr);
    EncodeFn enc = (EncodeFn)fn;
    void *pO, *pXT;
    cudaGetSymbolAddress(&pO, g_O);
    cudaGetSymbolAddress(&pXT, g_xT);
    make_map(enc, &prm.mapO, pO, DM, LSEQ, 16);
    make_map(enc, &prm.mapXT, pXT, LSEQ, 4 * DM, 64);
    prm.out = (bf16*)d_out;
    make_map(enc, &prm.mapX128, d_in[0], 2 * DM, LSEQ / 2, 128);
    make_map(enc, &prm.mapWo128, d_in[2], DM, DM, 128);
    make_map(enc, &prm.mapO128, pO, DM, LSEQ, 128);
    make_map3(enc, &prm.mapW3, d_in[1], DM, 3 * DM, DM, DM, 3, 3);
    make_map3(enc, &prm.mapW3h, d_in[1], DM, 3 * DM, DM, DM, 3, 3, 32);
    make_map3(enc, &prm.mapXT3, pXT, 64, LSEQ, 4 * DM, 64, 32, 2);
    prm.a_re = (const bf16*)d_in[4]; prm.a_im = (const bf16*)d_in[5];
    prm.b_re = (const bf16*)d_in[6]; prm.b_im = (const bf16*)d_in[7];
    prm.c_re = (const bf16*)d_in[8]; prm.c_im = (const bf16*)d_in[9];
    prm.log_dt = (const bf16*)d_in[10]; prm.dskip = (const bf16*)d_in[11];
    cudaFuncSetAttribute(fused_kernel, cudaFuncAttributeMaxDynamicSharedMemorySize, SM_TOTAL);
    for (int i = 0; i < 12; i++) cached[i] = d_in[i];
    cached[12] = d_out;
    attr_done = true;
  }
  prm.stop = 100;
    fused_kernel<<<NCTA, NTHREADS, SM_TOTAL>>>(prm);
}
```

```cpp
#include <cuda_runtime.h>
#include <cuda_bf16.h>
#include <cuda.h>
#include <stdint.h>

typedef __nv_bfloat16 bf16;

constexpr int LSEQ = 2048;
constexpr int DM = 512;
constexpr int NCTA = 128;
constexpr int NTHREADS = 512;
#define RR 0
#define KG_PRE 2
#define WO_E0 4
#define WO_E1 2
#define FILL_AT 6
#define EXP_LATE 1
#define RFENCE 1
#define D_FIN 500
#define D_PREP 600
#define D_PST 100
#define D_HALO 500
#define STAG0 2
#define STAG1 2
#define D_ST 500
#define TLAYER 1
#define KG_PD 1
#define SUM_F32 0
#define CS_LATE0 0
#define D_HALO1 0
#define KG_START 0
#define S_AHEAD0 1
#define S_AHEAD1 2
#define PAUSE 80
#define PARK_FIRST 0
#define P_UNROLL_N 1
constexpr int P_UNROLL = P_UNROLL_N;
#define PUB 1
#define X_ORDER 1
#define CS_STEP 1
#define D_FIN2 400
#define FIN_D0 2
#define QD_AT 1
#define FIN4 2
#define D_Q 700
#define XV_AT B_GB
#define S1_AT 1
#define G_WAIT 2
#define HALO_W14 1
#define D_START 200
#define D_CS 400
#define D_ST0 500
#define KG_LAST 0
#define X_JIT 0
#define KG_GATE 2
#define R_CONS 192
#define R_HELP 88

constexpr int SM_X = 0;
constexpr int SM_W = 131072;
constexpr int SM_KVX = SM_X;
constexpr int SM_WO = SM_X + 16384;
constexpr int SM_OST = SM_W + 49152;
__host__ __device__ constexpr int sm_o(int c) { return c < 7 ? SM_X + (5 + c) * 16384 : SM_KVX; }
constexpr int SM_R = 196608;
constexpr int SM_T = 212992;
constexpr int SM_KC = 217088;
constexpr int KC_STRIDE = 648;
constexpr int SM_CS = SM_KC + 4 * KC_STRIDE * 2;
constexpr int SM_CW = SM_R + 8192;
constexpr int SM_EP = SM_CS + 768;
constexpr int SM_BAR = SM_EP + 16;
constexpr int SM_T2 = SM_BAR + 896;
constexpr int SM_HALO = SM_T2 + 4096;
constexpr int SM_ST = SM_HALO + 3072;
constexpr int SM_TOTAL = SM_HALO + 4096;
static_assert(SM_TOTAL <= 232448, "shared memory");

constexpr int CV_UH = 140 * 16;
constexpr int CV_PECH = 1120 * 4;
constexpr int CV_PBW = 2112 * 2;
__host__ __device__ constexpr int cv_s(int lc) { return SM_X + lc * 32768; }
__host__ __device__ constexpr int cv_u(int lc) { return cv_s(lc) + 4096; }
__host__ __device__ constexpr int cv_pe(int lc) { return cv_u(lc) + 2 * CV_UH; }
__host__ __device__ constexpr int cv_pb(int lc) { return cv_pe(lc) + CV_PECH; }
__host__ __device__ constexpr int cv_ft(int lc) { return cv_pb(lc) + 4 * CV_PBW; }
static_assert(cv_ft(0) + 1024 <= 32768, "conv buffers");
__host__ __device__ constexpr int cv_chan(int cta, int lc) { return cta + 128 * lc; }

enum {
  B_XF = 0,
  B_KVF = 8,
  B_OF = 16,
  B_WOF = 24,
  B_T = 31,
  B_RF = 28,
  B_RE = 29,
  B_CW = 30,
  B_GB = 35,
  B_EP = 36,
  B_ZF = 37,
  B_XV = 39,
  B_XV2 = 25,
  B_SD = 38,
  B_KVE = 40,
  B_SG = 45,
  B_OST = 46,
  B_QDONE = 47,
  B_PDONE = 48,
  B_S = 50,
  B_E = 54,
  B_P = 58,
  B_PE = 62,
  B_STF = 63,
  B_CSF = 64,
  B_HF = 65,
  B_U = 70,
  B_AD = 75,
  B_PS = 74,
  B_COUNT = 80
};

enum {
  C_CS = 0,
  C_G1 = 2,
  C_O = 4,
  C_COUNT = 20
};

__device__ __align__(128) unsigned g_cnt[C_COUNT * 32];
__device__ __align__(1024) bf16 g_O[LSEQ * DM];
__device__ __align__(1024) bf16 g_xT[4 * DM * LSEQ];
__device__ __align__(1024) uint32_t g_stats[2 * LSEQ];
__device__ __align__(1024) uint4 g_colsum[8 * 16 * 48];
__device__ __align__(1024) uint4 g_halo[16 * 8 * 192];
__device__ __align__(1024) uint2 g_part[16 * 8 * 128];
#define TS(i) do { } while (0)

#define ATS(i, th) do { } while (0)
#define KTS(i) do { if (ht == 0) TS(i); } while (0)
#define FTS(i) do { } while (0)
#define LTS(i) do { } while (0)

#define STOP 100

struct Params {
  CUtensorMap mapO, mapXT, mapX128, mapWo128, mapO128, mapW3, mapW3h, mapXT3;
  const bf16 *a_re, *a_im, *b_re, *b_im, *c_re, *c_im, *log_dt, *dskip;
  bf16* out;
  int stop;
};

__device__ __forceinline__ uint32_t s32(const void* p) { return (uint32_t)__cvta_generic_to_shared(p); }
__device__ __forceinline__ void mbar_init(uint32_t b, int c) { asm volatile("mbarrier.init.shared::cta.b64 [%0], %1;" ::"r"(b), "r"(c) : "memory"); }
__device__ __forceinline__ void mbar_expect(uint32_t b, int bytes) { asm volatile("mbarrier.arrive.expect_tx.shared::cta.b64 _, [%0], %1;" ::"r"(b), "r"(bytes) : "memory"); }
__device__ __forceinline__ void mbar_arrive(uint32_t b) { asm volatile("mbarrier.arrive.shared::cta.b64 _, [%0];" ::"r"(b) : "memory"); }
__device__ __forceinline__ void mbar_arrive_if(uint32_t b, bool c) {
  asm volatile("{\n.reg .pred p;\nsetp.ne.u32 p, %1, 0;\n@p mbarrier.arrive.shared::cta.b64 _, [%0];\n}" ::"r"(b), "r"((uint32_t)c) : "memory");
}
__device__ __forceinline__ void mbar_wait(uint32_t b, int parity) {
  asm volatile("{\n.reg .pred p;\nWAIT_LOOP:\nmbarrier.try_wait.parity.shared::cta.b64 p, [%0], %1;\n@p bra WAIT_DONE;\nbra WAIT_LOOP;\nWAIT_DONE:\n}" ::"r"(b), "r"(parity) : "memory");
}
template <int N> __device__ __forceinline__ void delay() {
  if constexpr (N > 0) {
    uint32_t t0, t;
    asm volatile("mov.u32 %0, %%clock;" : "=r"(t0));
    do { asm volatile("mov.u32 %0, %%clock;" : "=r"(t)); } while (t - t0 < N);
  }
}
#define SF 3
template <int ID> __device__ __forceinline__ void sched_fence() {
  if constexpr ((SF >> ID) & 1)
    asm volatile("{\n.reg .pred p;\n.reg .u32 t;\nsetp.eq.u32 p, %0, 0;\n@p mov.u32 t, %%clock;\n@p st.shared.u32 [%0], t;\n}" ::"r"(gridDim.x) : "memory");
}
#define KEEP 0xf
template <int ID> __device__ __forceinline__ void tensor_keepalive() {
  if constexpr ((KEEP >> ID) & 1)
    asm volatile("{\n.reg .pred p;\n.reg .f32 a, b, c, d, z;\nmov.f32 z, 0f00000000;\nsetp.eq.u32 p, %0, 0;\n"
                 "mma.sync.aligned.m16n8k8.row.col.f32.bf16.bf16.f32 {a,b,c,d}, {%0,%0}, {%0}, {z,z,z,z};\n@p st.shared.f32 [%0], a;\n}" ::"r"(gridDim.x) : "memory");
}
__device__ __forceinline__ int opaque_tid() { int v; asm volatile("mov.u32 %0, %%tid.x;" : "=r"(v)); return v; }
__device__ __forceinline__ bool elect_one() {
  uint32_t r;
  asm volatile("{\n.reg .pred p;\nelect.sync _|p, 0xffffffff;\nselp.u32 %0, 1, 0, p;\n}" : "=r"(r));
  return r != 0;
}
__device__ __forceinline__ void tma_ld(uint32_t dst, const CUtensorMap* m, int c0, int c1, uint32_t bar) {
  asm volatile("cp.async.bulk.tensor.2d.shared::cluster.global.mbarrier::complete_tx::bytes [%0], [%1, {%3, %4}], [%2];"
               ::"r"(dst), "l"(m), "r"(bar), "r"(c0), "r"(c1) : "memory");
}
__device__ __forceinline__ void tma_ld3(uint32_t dst, const CUtensorMap* m, int c0, int c1, int c2, uint32_t bar) {
  asm volatile("cp.async.bulk.tensor.3d.shared::cluster.global.mbarrier::complete_tx::bytes [%0], [%1, {%3, %4, %5}], [%2];"
               ::"r"(dst), "l"(m), "r"(bar), "r"(c0), "r"(c1), "r"(c2) : "memory");
}
__device__ __forceinline__ void tma_prefetch2(const CUtensorMap* m, int c0, int c1) {
  asm volatile("cp.async.bulk.prefetch.tensor.2d.L2.global.tile [%0, {%1, %2}];" ::"l"(m), "r"(c0), "r"(c1) : "memory");
}
__device__ __forceinline__ void tma_prefetch3(const CUtensorMap* m, int c0, int c1, int c2) {
  asm volatile("cp.async.bulk.prefetch.tensor.3d.L2.global.tile [%0, {%1, %2, %3}];" ::"l"(m), "r"(c0), "r"(c1), "r"(c2) : "memory");
}
__device__ __forceinline__ void tma_st(const CUtensorMap* m, int c0, int c1, uint32_t src) {
  asm volatile("cp.async.bulk.tensor.2d.global.shared::cta.bulk_group [%0, {%2, %3}], [%1];" ::"l"(m), "r"(src), "r"(c0), "r"(c1) : "memory");
}
__device__ __forceinline__ void bulk_ld(uint32_t dst, const void* src, int bytes, uint32_t bar) {
  asm volatile("cp.async.bulk.shared::cluster.global.mbarrier::complete_tx::bytes [%0], [%1], %2, [%3];" ::"r"(dst), "l"(src), "r"(bytes), "r"(bar) : "memory");
}
__device__ __forceinline__ void bulk_st(void* dst, uint32_t src, int bytes) {
  asm volatile("cp.async.bulk.global.shared::cta.bulk_group [%0], [%1], %2;" ::"l"(dst), "r"(src), "r"(bytes) : "memory");
}
__device__ __forceinline__ void bulk_red_add_f32(void* dst, uint32_t src, int bytes) {
  asm volatile("cp.reduce.async.bulk.global.shared::cta.bulk_group.add.f32 [%0], [%1], %2;" ::"l"(dst), "r"(src), "r"(bytes) : "memory");
}
__device__ __forceinline__ void bulk_commit() { asm volatile("cp.async.bulk.commit_group;" ::: "memory"); }
__device__ __forceinline__ void bulk_wait_all() { asm volatile("cp.async.bulk.wait_group 0;" ::: "memory"); }
__device__ __forceinline__ void fence_async_smem() { asm volatile("fence.proxy.async.shared::cta;" ::: "memory"); }
__device__ __forceinline__ void fence_writer() { if (!RFENCE) fence_async_smem(); }
__device__ __forceinline__ void fence_reader() { if (RFENCE) fence_async_smem(); }
__device__ __forceinline__ void fence_async_global() { asm volatile("fence.proxy.async.global;" ::: "memory"); }
__device__ __forceinline__ void bar_sync(int id, int n) { asm volatile("bar.sync %0, %1;" ::"r"(id), "r"(n) : "memory"); }
__device__ __forceinline__ void bar_arrive(int id, int n) { asm volatile("bar.arrive %0, %1;" ::"r"(id), "r"(n) : "memory"); }
__device__ __forceinline__ void wg_fence() { asm volatile("wgmma.fence.sync.aligned;" ::: "memory"); }
__device__ __forceinline__ void wg_commit() { asm volatile("wgmma.commit_group.sync.aligned;" ::: "memory"); }
template <int N> __device__ __forceinline__ void wg_wait() { asm volatile("wgmma.wait_group.sync.aligned %0;" ::"n"(N) : "memory"); }
__device__ __forceinline__ uint64_t mkdesc(uint32_t addr, uint32_t lbo, uint32_t sbo, int sw) {
  return (uint64_t)((addr & 0x3FFFF) >> 4) | ((uint64_t)(lbo >> 4) << 16) | ((uint64_t)(sbo >> 4) << 32) | ((uint64_t)sw << 62);
}
__device__ __forceinline__ void ldsm4(uint32_t* r, uint32_t a) {
  asm volatile("ldmatrix.sync.aligned.m8n8.x4.shared.b16 {%0,%1,%2,%3}, [%4];" : "=r"(r[0]), "=r"(r[1]), "=r"(r[2]), "=r"(r[3]) : "r"(a) : "memory");
}
__device__ __forceinline__ void ldsm4t(uint32_t* r, uint32_t a) {
  asm volatile("ldmatrix.sync.aligned.m8n8.x4.trans.shared.b16 {%0,%1,%2,%3}, [%4];" : "=r"(r[0]), "=r"(r[1]), "=r"(r[2]), "=r"(r[3]) : "r"(a) : "memory");
}
__device__ __forceinline__ void stsm4(uint32_t a, uint32_t r0, uint32_t r1, uint32_t r2, uint32_t r3) {
  asm volatile("stmatrix.sync.aligned.m8n8.x4.shared.b16 [%0], {%1,%2,%3,%4};" ::"r"(a), "r"(r0), "r"(r1), "r"(r2), "r"(r3) : "memory");
}
__device__ __forceinline__ void stsm4t(uint32_t a, uint32_t r0, uint32_t r1, uint32_t r2, uint32_t r3) {
  asm volatile("stmatrix.sync.aligned.m8n8.x4.trans.shared.b16 [%0], {%1,%2,%3,%4};" ::"r"(a), "r"(r0), "r"(r1), "r"(r2), "r"(r3) : "memory");
}
__device__ __forceinline__ uint32_t movm_t(uint32_t a) { uint32_t r; asm volatile("movmatrix.sync.aligned.m8n8.trans.b16 %0, %1;" : "=r"(r) : "r"(a)); return r; }
__device__ __forceinline__ uint32_t lds32(uint32_t a) { uint32_t v; asm volatile("ld.shared.b32 %0, [%1];" : "=r"(v) : "r"(a) : "memory"); return v; }
__device__ __forceinline__ float2 lds64f(uint32_t a) { float2 v; asm volatile("ld.shared.v2.f32 {%0,%1}, [%2];" : "=f"(v.x), "=f"(v.y) : "r"(a) : "memory"); return v; }
__device__ __forceinline__ float4 lds128f(uint32_t a) { float4 v; asm volatile("ld.shared.v4.f32 {%0,%1,%2,%3}, [%4];" : "=f"(v.x), "=f"(v.y), "=f"(v.z), "=f"(v.w) : "r"(a) : "memory"); return v; }
__device__ __forceinline__ uint4 lds128(uint32_t a) { uint4 v; asm volatile("ld.shared.v4.b32 {%0,%1,%2,%3}, [%4];" : "=r"(v.x), "=r"(v.y), "=r"(v.z), "=r"(v.w) : "r"(a) : "memory"); return v; }
__device__ __forceinline__ void sts128(uint32_t a, uint4 v) { asm volatile("st.shared.v4.b32 [%0], {%1,%2,%3,%4};" ::"r"(a), "r"(v.x), "r"(v.y), "r"(v.z), "r"(v.w) : "memory"); }
__device__ __forceinline__ void sts128f(uint32_t a, float x, float y, float z, float w) { asm volatile("st.shared.v4.f32 [%0], {%1,%2,%3,%4};" ::"r"(a), "f"(x), "f"(y), "f"(z), "f"(w) : "memory"); }
__device__ __forceinline__ void sts32f(uint32_t a, float v) { asm volatile("st.shared.f32 [%0], %1;" ::"r"(a), "f"(v) : "memory"); }
__device__ __forceinline__ void sts16(uint32_t a, uint16_t v) { asm volatile("st.shared.u16 [%0], %1;" ::"r"(a), "h"(v) : "memory"); }
__device__ __forceinline__ uint32_t lds16(uint32_t a) { uint16_t v; asm volatile("ld.shared.u16 %0, [%1];" : "=h"(v) : "r"(a) : "memory"); return v; }
__device__ __forceinline__ uint32_t packbf(float lo, float hi) { uint32_t r; asm("cvt.rn.bf16x2.f32 %0, %1, %2;" : "=r"(r) : "f"(hi), "f"(lo)); return r; }
__device__ __forceinline__ float bf_lo(uint32_t v) { return __uint_as_float(v << 16); }
__device__ __forceinline__ float bf_hi(uint32_t v) { return __uint_as_float(v & 0xffff0000u); }
__device__ __forceinline__ float ex2(float x) { float r; asm("ex2.approx.ftz.f32 %0, %1;" : "=f"(r) : "f"(x)); return r; }
__device__ __forceinline__ float rsqrt_approx(float x) { float r; asm("rsqrt.approx.ftz.f32 %0, %1;" : "=f"(r) : "f"(x)); return r; }
__device__ __forceinline__ float rcp_approx(float x) { float r; asm("rcp.approx.ftz.f32 %0, %1;" : "=f"(r) : "f"(x)); return r; }
__device__ __forceinline__ void mma_bf16(float* d, const uint32_t* a, uint32_t b0, uint32_t b1) {
  asm("mma.sync.aligned.m16n8k16.row.col.f32.bf16.bf16.f32 {%0,%1,%2,%3}, {%4,%5,%6,%7}, {%8,%9}, {%0,%1,%2,%3};"
               : "+f"(d[0]), "+f"(d[1]), "+f"(d[2]), "+f"(d[3]) : "r"(a[0]), "r"(a[1]), "r"(a[2]), "r"(a[3]), "r"(b0), "r"(b1));
}
__device__ __forceinline__ void mma_bf16_k8(float* d, uint32_t a0, uint32_t a1, uint32_t b) {
  asm("mma.sync.aligned.m16n8k8.row.col.f32.bf16.bf16.f32 {%0,%1,%2,%3}, {%4,%5}, {%6}, {%0,%1,%2,%3};"
      : "+f"(d[0]), "+f"(d[1]), "+f"(d[2]), "+f"(d[3]) : "r"(a0), "r"(a1), "r"(b));
}
__device__ __forceinline__ void red_release(unsigned* p) { asm volatile("red.release.gpu.global.add.u32 [%0], 1;" ::"l"(p) : "memory"); }
__device__ __forceinline__ void red_relaxed(unsigned* p) { asm volatile("red.relaxed.gpu.global.add.u32 [%0], 1;" ::"l"(p) : "memory"); }
__device__ __forceinline__ unsigned ld_relaxed(const unsigned* p) { unsigned v; asm volatile("ld.relaxed.gpu.global.u32 %0, [%1];" : "=r"(v) : "l"(p) : "memory"); return v; }
__device__ __forceinline__ void spin_until(const unsigned* p, unsigned target) {
  int it = 0;
  while ((int)(ld_relaxed(p) - target) < 0) {
    if (++it > (1 << 23)) __trap();
  }
}
__device__ __forceinline__ uint4 ldcg128(const void* p) { uint4 v; asm volatile("ld.global.cg.v4.b32 {%0,%1,%2,%3}, [%4];" : "=r"(v.x), "=r"(v.y), "=r"(v.z), "=r"(v.w) : "l"(p) : "memory"); return v; }
__device__ __forceinline__ uint4 ld_tagged(const uint4* p) { uint4 v; asm volatile("ld.relaxed.gpu.global.v4.u32 {%0,%1,%2,%3}, [%4];" : "=r"(v.x), "=r"(v.y), "=r"(v.z), "=r"(v.w) : "l"(p) : "memory"); return v; }
__device__ __forceinline__ uint2 ld_part(const uint2* p) { uint2 v; asm volatile("ld.relaxed.gpu.global.v2.u32 {%0,%1}, [%2];" : "=r"(v.x), "=r"(v.y) : "l"(p) : "memory"); return v; }
__device__ __forceinline__ void st_part(uint2* p, float s, float q, uint32_t tag) {
  if (PUB & 2) asm volatile("{\n.reg .b64 v, o;\nmov.b64 v, {%1,%2};\natom.relaxed.gpu.global.exch.b64 o, [%0], v;\n}" ::"l"(p), "r"(__float_as_uint(s)), "r"((__float_as_uint(q) & ~7u) | tag) : "memory");
  else asm volatile("st.relaxed.gpu.global.v2.u32 [%0], {%1,%2};" ::"l"(p), "r"(__float_as_uint(s)), "r"((__float_as_uint(q) & ~7u) | tag) : "memory");
}
__device__ __forceinline__ uint32_t part_tag(uint32_t epoch, int k) { return (4 * (epoch % 7) + k) % 7 + 1; }
__device__ __forceinline__ void st_tagged3(uint4* p, uint32_t a, uint32_t b, uint32_t c, uint32_t tag) { asm volatile("st.relaxed.gpu.global.v4.u32 [%0], {%1,%2,%3,%4};" ::"l"(p), "r"(a), "r"(b), "r"(c), "r"(tag) : "memory"); }
__device__ __forceinline__ uint32_t hadd2(uint32_t a, uint32_t b) { uint32_t r; asm("add.rn.bf16x2 %0, %1, %2;" : "=r"(r) : "r"(a), "r"(b)); return r; }
__device__ __forceinline__ uint32_t hfma2(uint32_t a, uint32_t b, uint32_t c) { uint32_t r; asm("fma.rn.bf16x2 %0, %1, %2, %3;" : "=r"(r) : "r"(a), "r"(b), "r"(c)); return r; }
__device__ __forceinline__ uint32_t hmul2(uint32_t a, uint32_t b) { uint32_t r; asm("mul.rn.bf16x2 %0, %1, %2;" : "=r"(r) : "r"(a), "r"(b)); return r; }

template<int N,int TB> __device__ __forceinline__ void wgmma_rs(float* d, const uint32_t* a, uint64_t db, int sd);
template<int N,int TA,int TB> __device__ __forceinline__ void wgmma_ss(float* d, uint64_t da, uint64_t db, int sd);
template<> __device__ __forceinline__ void wgmma_rs<128,0>(float* d, const uint32_t* a, uint64_t db, int sd) {
  asm volatile("{\n.reg .pred p;\nsetp.ne.b32 p, %69, 0;\nwgmma.mma_async.sync.aligned.m64n128k16.f32.bf16.bf16 {%0,%1,%2,%3,%4,%5,%6,%7,%8,%9,%10,%11,%12,%13,%14,%15,%16,%17,%18,%19,%20,%21,%22,%23,%24,%25,%26,%27,%28,%29,%30,%31,%32,%33,%34,%35,%36,%37,%38,%39,%40,%41,%42,%43,%44,%45,%46,%47,%48,%49,%50,%51,%52,%53,%54,%55,%56,%57,%58,%59,%60,%61,%62,%63}, {%64,%65,%66,%67}, %68, p, 1, 1, 0;\n}\n"
   : "+f"(d[0]),"+f"(d[1]),"+f"(d[2]),"+f"(d[3]),"+f"(d[4]),"+f"(d[5]),"+f"(d[6]),"+f"(d[7]),"+f"(d[8]),"+f"(d[9]),"+f"(d[10]),"+f"(d[11]),"+f"(d[12]),"+f"(d[13]),"+f"(d[14]),"+f"(d[15]),"+f"(d[16]),"+f"(d[17]),"+f"(d[18]),"+f"(d[19]),"+f"(d[20]),"+f"(d[21]),"+f"(d[22]),"+f"(d[23]),"+f"(d[24]),"+f"(d[25]),"+f"(d[26]),"+f"(d[27]),"+f"(d[28]),"+f"(d[29]),"+f"(d[30]),"+f"(d[31]),"+f"(d[32]),"+f"(d[33]),"+f"(d[34]),"+f"(d[35]),"+f"(d[36]),"+f"(d[37]),"+f"(d[38]),"+f"(d[39]),"+f"(d[40]),"+f"(d[41]),"+f"(d[42]),"+f"(d[43]),"+f"(d[44]),"+f"(d[45]),"+f"(d[46]),"+f"(d[47]),"+f"(d[48]),"+f"(d[49]),"+f"(d[50]),"+f"(d[51]),"+f"(d[52]),"+f"(d[53]),"+f"(d[54]),"+f"(d[55]),"+f"(d[56]),"+f"(d[57]),"+f"(d[58]),"+f"(d[59]),"+f"(d[60]),"+f"(d[61]),"+f"(d[62]),"+f"(d[63])
   : "r"(a[0]), "r"(a[1]), "r"(a[2]), "r"(a[3]), "l"(db), "r"(sd));
}
template<> __device__ __forceinline__ void wgmma_rs<120,0>(float* d, const uint32_t* a, uint64_t db, int sd) {
  asm volatile("{\n.reg .pred p;\nsetp.ne.b32 p, %65, 0;\nwgmma.mma_async.sync.aligned.m64n120k16.f32.bf16.bf16 {%0,%1,%2,%3,%4,%5,%6,%7,%8,%9,%10,%11,%12,%13,%14,%15,%16,%17,%18,%19,%20,%21,%22,%23,%24,%25,%26,%27,%28,%29,%30,%31,%32,%33,%34,%35,%36,%37,%38,%39,%40,%41,%42,%43,%44,%45,%46,%47,%48,%49,%50,%51,%52,%53,%54,%55,%56,%57,%58,%59}, {%60,%61,%62,%63}, %64, p, 1, 1, 0;\n}\n"
   : "+f"(d[0]),"+f"(d[1]),"+f"(d[2]),"+f"(d[3]),"+f"(d[4]),"+f"(d[5]),"+f"(d[6]),"+f"(d[7]),"+f"(d[8]),"+f"(d[9]),"+f"(d[10]),"+f"(d[11]),"+f"(d[12]),"+f"(d[13]),"+f"(d[14]),"+f"(d[15]),"+f"(d[16]),"+f"(d[17]),"+f"(d[18]),"+f"(d[19]),"+f"(d[20]),"+f"(d[21]),"+f"(d[22]),"+f"(d[23]),"+f"(d[24]),"+f"(d[25]),"+f"(d[26]),"+f"(d[27]),"+f"(d[28]),"+f"(d[29]),"+f"(d[30]),"+f"(d[31]),"+f"(d[32]),"+f"(d[33]),"+f"(d[34]),"+f"(d[35]),"+f"(d[36]),"+f"(d[37]),"+f"(d[38]),"+f"(d[39]),"+f"(d[40]),"+f"(d[41]),"+f"(d[42]),"+f"(d[43]),"+f"(d[44]),"+f"(d[45]),"+f"(d[46]),"+f"(d[47]),"+f"(d[48]),"+f"(d[49]),"+f"(d[50]),"+f"(d[51]),"+f"(d[52]),"+f"(d[53]),"+f"(d[54]),"+f"(d[55]),"+f"(d[56]),"+f"(d[57]),"+f"(d[58]),"+f"(d[59])
   : "r"(a[0]), "r"(a[1]), "r"(a[2]), "r"(a[3]), "l"(db), "r"(sd));
}
template<> __device__ __forceinline__ void wgmma_rs<112,0>(float* d, const uint32_t* a, uint64_t db, int sd) {
  asm volatile("{\n.reg .pred p;\nsetp.ne.b32 p, %61, 0;\nwgmma.mma_async.sync.aligned.m64n112k16.f32.bf16.bf16 {%0,%1,%2,%3,%4,%5,%6,%7,%8,%9,%10,%11,%12,%13,%14,%15,%16,%17,%18,%19,%20,%21,%22,%23,%24,%25,%26,%27,%28,%29,%30,%31,%32,%33,%34,%35,%36,%37,%38,%39,%40,%41,%42,%43,%44,%45,%46,%47,%48,%49,%50,%51,%52,%53,%54,%55}, {%56,%57,%58,%59}, %60, p, 1, 1, 0;\n}\n"
   : "+f"(d[0]),"+f"(d[1]),"+f"(d[2]),"+f"(d[3]),"+f"(d[4]),"+f"(d[5]),"+f"(d[6]),"+f"(d[7]),"+f"(d[8]),"+f"(d[9]),"+f"(d[10]),"+f"(d[11]),"+f"(d[12]),"+f"(d[13]),"+f"(d[14]),"+f"(d[15]),"+f"(d[16]),"+f"(d[17]),"+f"(d[18]),"+f"(d[19]),"+f"(d[20]),"+f"(d[21]),"+f"(d[22]),"+f"(d[23]),"+f"(d[24]),"+f"(d[25]),"+f"(d[26]),"+f"(d[27]),"+f"(d[28]),"+f"(d[29]),"+f"(d[30]),"+f"(d[31]),"+f"(d[32]),"+f"(d[33]),"+f"(d[34]),"+f"(d[35]),"+f"(d[36]),"+f"(d[37]),"+f"(d[38]),"+f"(d[39]),"+f"(d[40]),"+f"(d[41]),"+f"(d[42]),"+f"(d[43]),"+f"(d[44]),"+f"(d[45]),"+f"(d[46]),"+f"(d[47]),"+f"(d[48]),"+f"(d[49]),"+f"(d[50]),"+f"(d[51]),"+f"(d[52]),"+f"(d[53]),"+f"(d[54]),"+f"(d[55])
   : "r"(a[0]), "r"(a[1]), "r"(a[2]), "r"(a[3]), "l"(db), "r"(sd));
}
template<> __device__ __forceinline__ void wgmma_rs<104,0>(float* d, const uint32_t* a, uint64_t db, int sd) {
  asm volatile("{\n.reg .pred p;\nsetp.ne.b32 p, %57, 0;\nwgmma.mma_async.sync.aligned.m64n104k16.f32.bf16.bf16 {%0,%1,%2,%3,%4,%5,%6,%7,%8,%9,%10,%11,%12,%13,%14,%15,%16,%17,%18,%19,%20,%21,%22,%23,%24,%25,%26,%27,%28,%29,%30,%31,%32,%33,%34,%35,%36,%37,%38,%39,%40,%41,%42,%43,%44,%45,%46,%47,%48,%49,%50,%51}, {%52,%53,%54,%55}, %56, p, 1, 1, 0;\n}\n"
   : "+f"(d[0]),"+f"(d[1]),"+f"(d[2]),"+f"(d[3]),"+f"(d[4]),"+f"(d[5]),"+f"(d[6]),"+f"(d[7]),"+f"(d[8]),"+f"(d[9]),"+f"(d[10]),"+f"(d[11]),"+f"(d[12]),"+f"(d[13]),"+f"(d[14]),"+f"(d[15]),"+f"(d[16]),"+f"(d[17]),"+f"(d[18]),"+f"(d[19]),"+f"(d[20]),"+f"(d[21]),"+f"(d[22]),"+f"(d[23]),"+f"(d[24]),"+f"(d[25]),"+f"(d[26]),"+f"(d[27]),"+f"(d[28]),"+f"(d[29]),"+f"(d[30]),"+f"(d[31]),"+f"(d[32]),"+f"(d[33]),"+f"(d[34]),"+f"(d[35]),"+f"(d[36]),"+f"(d[37]),"+f"(d[38]),"+f"(d[39]),"+f"(d[40]),"+f"(d[41]),"+f"(d[42]),"+f"(d[43]),"+f"(d[44]),"+f"(d[45]),"+f"(d[46]),"+f"(d[47]),"+f"(d[48]),"+f"(d[49]),"+f"(d[50]),"+f"(d[51])
   : "r"(a[0]), "r"(a[1]), "r"(a[2]), "r"(a[3]), "l"(db), "r"(sd));
}
template<> __device__ __forceinline__ void wgmma_rs<96,0>(float* d, const uint32_t* a, uint64_t db, int sd) {
  asm volatile("{\n.reg .pred p;\nsetp.ne.b32 p, %53, 0;\nwgmma.mma_async.sync.aligned.m64n96k16.f32.bf16.bf16 {%0,%1,%2,%3,%4,%5,%6,%7,%8,%9,%10,%11,%12,%13,%14,%15,%16,%17,%18,%19,%20,%21,%22,%23,%24,%25,%26,%27,%28,%29,%30,%31,%32,%33,%34,%35,%36,%37,%38,%39,%40,%41,%42,%43,%44,%45,%46,%47}, {%48,%49,%50,%51}, %52, p, 1, 1, 0;\n}\n"
   : "+f"(d[0]),"+f"(d[1]),"+f"(d[2]),"+f"(d[3]),"+f"(d[4]),"+f"(d[5]),"+f"(d[6]),"+f"(d[7]),"+f"(d[8]),"+f"(d[9]),"+f"(d[10]),"+f"(d[11]),"+f"(d[12]),"+f"(d[13]),"+f"(d[14]),"+f"(d[15]),"+f"(d[16]),"+f"(d[17]),"+f"(d[18]),"+f"(d[19]),"+f"(d[20]),"+f"(d[21]),"+f"(d[22]),"+f"(d[23]),"+f"(d[24]),"+f"(d[25]),"+f"(d[26]),"+f"(d[27]),"+f"(d[28]),"+f"(d[29]),"+f"(d[30]),"+f"(d[31]),"+f"(d[32]),"+f"(d[33]),"+f"(d[34]),"+f"(d[35]),"+f"(d[36]),"+f"(d[37]),"+f"(d[38]),"+f"(d[39]),"+f"(d[40]),"+f"(d[41]),"+f"(d[42]),"+f"(d[43]),"+f"(d[44]),"+f"(d[45]),"+f"(d[46]),"+f"(d[47])
   : "r"(a[0]), "r"(a[1]), "r"(a[2]), "r"(a[3]), "l"(db), "r"(sd));
}
template<> __device__ __forceinline__ void wgmma_rs<88,0>(float* d, const uint32_t* a, uint64_t db, int sd) {
  asm volatile("{\n.reg .pred p;\nsetp.ne.b32 p, %49, 0;\nwgmma.mma_async.sync.aligned.m64n88k16.f32.bf16.bf16 {%0,%1,%2,%3,%4,%5,%6,%7,%8,%9,%10,%11,%12,%13,%14,%15,%16,%17,%18,%19,%20,%21,%22,%23,%24,%25,%26,%27,%28,%29,%30,%31,%32,%33,%34,%35,%36,%37,%38,%39,%40,%41,%42,%43}, {%44,%45,%46,%47}, %48, p, 1, 1, 0;\n}\n"
   : "+f"(d[0]),"+f"(d[1]),"+f"(d[2]),"+f"(d[3]),"+f"(d[4]),"+f"(d[5]),"+f"(d[6]),"+f"(d[7]),"+f"(d[8]),"+f"(d[9]),"+f"(d[10]),"+f"(d[11]),"+f"(d[12]),"+f"(d[13]),"+f"(d[14]),"+f"(d[15]),"+f"(d[16]),"+f"(d[17]),"+f"(d[18]),"+f"(d[19]),"+f"(d[20]),"+f"(d[21]),"+f"(d[22]),"+f"(d[23]),"+f"(d[24]),"+f"(d[25]),"+f"(d[26]),"+f"(d[27]),"+f"(d[28]),"+f"(d[29]),"+f"(d[30]),"+f"(d[31]),"+f"(d[32]),"+f"(d[33]),"+f"(d[34]),"+f"(d[35]),"+f"(d[36]),"+f"(d[37]),"+f"(d[38]),"+f"(d[39]),"+f"(d[40]),"+f"(d[41]),"+f"(d[42]),"+f"(d[43])
   : "r"(a[0]), "r"(a[1]), "r"(a[2]), "r"(a[3]), "l"(db), "r"(sd));
}
template<> __device__ __forceinline__ void wgmma_rs<80,0>(float* d, const uint32_t* a, uint64_t db, int sd) {
  asm volatile("{\n.reg .pred p;\nsetp.ne.b32 p, %45, 0;\nwgmma.mma_async.sync.aligned.m64n80k16.f32.bf16.bf16 {%0,%1,%2,%3,%4,%5,%6,%7,%8,%9,%10,%11,%12,%13,%14,%15,%16,%17,%18,%19,%20,%21,%22,%23,%24,%25,%26,%27,%28,%29,%30,%31,%32,%33,%34,%35,%36,%37,%38,%39}, {%40,%41,%42,%43}, %44, p, 1, 1, 0;\n}\n"
   : "+f"(d[0]),"+f"(d[1]),"+f"(d[2]),"+f"(d[3]),"+f"(d[4]),"+f"(d[5]),"+f"(d[6]),"+f"(d[7]),"+f"(d[8]),"+f"(d[9]),"+f"(d[10]),"+f"(d[11]),"+f"(d[12]),"+f"(d[13]),"+f"(d[14]),"+f"(d[15]),"+f"(d[16]),"+f"(d[17]),"+f"(d[18]),"+f"(d[19]),"+f"(d[20]),"+f"(d[21]),"+f"(d[22]),"+f"(d[23]),"+f"(d[24]),"+f"(d[25]),"+f"(d[26]),"+f"(d[27]),"+f"(d[28]),"+f"(d[29]),"+f"(d[30]),"+f"(d[31]),"+f"(d[32]),"+f"(d[33]),"+f"(d[34]),"+f"(d[35]),"+f"(d[36]),"+f"(d[37]),"+f"(d[38]),"+f"(d[39])
   : "r"(a[0]), "r"(a[1]), "r"(a[2]), "r"(a[3]), "l"(db), "r"(sd));
}
template<> __device__ __forceinline__ void wgmma_rs<72,0>(float* d, const uint32_t* a, uint64_t db, int sd) {
  asm volatile("{\n.reg .pred p;\nsetp.ne.b32 p, %41, 0;\nwgmma.mma_async.sync.aligned.m64n72k16.f32.bf16.bf16 {%0,%1,%2,%3,%4,%5,%6,%7,%8,%9,%10,%11,%12,%13,%14,%15,%16,%17,%18,%19,%20,%21,%22,%23,%24,%25,%26,%27,%28,%29,%30,%31,%32,%33,%34,%35}, {%36,%37,%38,%39}, %40, p, 1, 1, 0;\n}\n"
   : "+f"(d[0]),"+f"(d[1]),"+f"(d[2]),"+f"(d[3]),"+f"(d[4]),"+f"(d[5]),"+f"(d[6]),"+f"(d[7]),"+f"(d[8]),"+f"(d[9]),"+f"(d[10]),"+f"(d[11]),"+f"(d[12]),"+f"(d[13]),"+f"(d[14]),"+f"(d[15]),"+f"(d[16]),"+f"(d[17]),"+f"(d[18]),"+f"(d[19]),"+f"(d[20]),"+f"(d[21]),"+f"(d[22]),"+f"(d[23]),"+f"(d[24]),"+f"(d[25]),"+f"(d[26]),"+f"(d[27]),"+f"(d[28]),"+f"(d[29]),"+f"(d[30]),"+f"(d[31]),"+f"(d[32]),"+f"(d[33]),"+f"(d[34]),"+f"(d[35])
   : "r"(a[0]), "r"(a[1]), "r"(a[2]), "r"(a[3]), "l"(db), "r"(sd));
}
template<> __device__ __forceinline__ void wgmma_rs<64,0>(float* d, const uint32_t* a, uint64_t db, int sd) {
  asm volatile("{\n.reg .pred p;\nsetp.ne.b32 p, %37, 0;\nwgmma.mma_async.sync.aligned.m64n64k16.f32.bf16.bf16 {%0,%1,%2,%3,%4,%5,%6,%7,%8,%9,%10,%11,%12,%13,%14,%15,%16,%17,%18,%19,%20,%21,%22,%23,%24,%25,%26,%27,%28,%29,%30,%31}, {%32,%33,%34,%35}, %36, p, 1, 1, 0;\n}\n"
   : "+f"(d[0]),"+f"(d[1]),"+f"(d[2]),"+f"(d[3]),"+f"(d[4]),"+f"(d[5]),"+f"(d[6]),"+f"(d[7]),"+f"(d[8]),"+f"(d[9]),"+f"(d[10]),"+f"(d[11]),"+f"(d[12]),"+f"(d[13]),"+f"(d[14]),"+f"(d[15]),"+f"(d[16]),"+f"(d[17]),"+f"(d[18]),"+f"(d[19]),"+f"(d[20]),"+f"(d[21]),"+f"(d[22]),"+f"(d[23]),"+f"(d[24]),"+f"(d[25]),"+f"(d[26]),"+f"(d[27]),"+f"(d[28]),"+f"(d[29]),"+f"(d[30]),"+f"(d[31])
   : "r"(a[0]), "r"(a[1]), "r"(a[2]), "r"(a[3]), "l"(db), "r"(sd));
}
template<> __device__ __forceinline__ void wgmma_ss<64,0,1>(float* d, uint64_t da, uint64_t db, int sd) {
  asm volatile("{\n.reg .pred p;\nsetp.ne.b32 p, %34, 0;\nwgmma.mma_async.sync.aligned.m64n64k16.f32.bf16.bf16 {%0,%1,%2,%3,%4,%5,%6,%7,%8,%9,%10,%11,%12,%13,%14,%15,%16,%17,%18,%19,%20,%21,%22,%23,%24,%25,%26,%27,%28,%29,%30,%31}, %32, %33, p, 1, 1, 0, 1;\n}\n"
   : "+f"(d[0]),"+f"(d[1]),"+f"(d[2]),"+f"(d[3]),"+f"(d[4]),"+f"(d[5]),"+f"(d[6]),"+f"(d[7]),"+f"(d[8]),"+f"(d[9]),"+f"(d[10]),"+f"(d[11]),"+f"(d[12]),"+f"(d[13]),"+f"(d[14]),"+f"(d[15]),"+f"(d[16]),"+f"(d[17]),"+f"(d[18]),"+f"(d[19]),"+f"(d[20]),"+f"(d[21]),"+f"(d[22]),"+f"(d[23]),"+f"(d[24]),"+f"(d[25]),"+f"(d[26]),"+f"(d[27]),"+f"(d[28]),"+f"(d[29]),"+f"(d[30]),"+f"(d[31])
   : "l"(da), "l"(db), "r"(sd));
}
template<> __device__ __forceinline__ void wgmma_ss<64,1,1>(float* d, uint64_t da, uint64_t db, int sd) {
  asm volatile("{\n.reg .pred p;\nsetp.ne.b32 p, %34, 0;\nwgmma.mma_async.sync.aligned.m64n64k16.f32.bf16.bf16 {%0,%1,%2,%3,%4,%5,%6,%7,%8,%9,%10,%11,%12,%13,%14,%15,%16,%17,%18,%19,%20,%21,%22,%23,%24,%25,%26,%27,%28,%29,%30,%31}, %32, %33, p, 1, 1, 1, 1;\n}\n"
   : "+f"(d[0]),"+f"(d[1]),"+f"(d[2]),"+f"(d[3]),"+f"(d[4]),"+f"(d[5]),"+f"(d[6]),"+f"(d[7]),"+f"(d[8]),"+f"(d[9]),"+f"(d[10]),"+f"(d[11]),"+f"(d[12]),"+f"(d[13]),"+f"(d[14]),"+f"(d[15]),"+f"(d[16]),"+f"(d[17]),"+f"(d[18]),"+f"(d[19]),"+f"(d[20]),"+f"(d[21]),"+f"(d[22]),"+f"(d[23]),"+f"(d[24]),"+f"(d[25]),"+f"(d[26]),"+f"(d[27]),"+f"(d[28]),"+f"(d[29]),"+f"(d[30]),"+f"(d[31])
   : "l"(da), "l"(db), "r"(sd));
}
template<> __device__ __forceinline__ void wgmma_ss<192,0,1>(float* d, uint64_t da, uint64_t db, int sd) {
  asm volatile("{\n.reg .pred p;\nsetp.ne.b32 p, %98, 0;\nwgmma.mma_async.sync.aligned.m64n192k16.f32.bf16.bf16 {%0,%1,%2,%3,%4,%5,%6,%7,%8,%9,%10,%11,%12,%13,%14,%15,%16,%17,%18,%19,%20,%21,%22,%23,%24,%25,%26,%27,%28,%29,%30,%31,%32,%33,%34,%35,%36,%37,%38,%39,%40,%41,%42,%43,%44,%45,%46,%47,%48,%49,%50,%51,%52,%53,%54,%55,%56,%57,%58,%59,%60,%61,%62,%63,%64,%65,%66,%67,%68,%69,%70,%71,%72,%73,%74,%75,%76,%77,%78,%79,%80,%81,%82,%83,%84,%85,%86,%87,%88,%89,%90,%91,%92,%93,%94,%95}, %96, %97, p, 1, 1, 0, 1;\n}\n"
   : "+f"(d[0]),"+f"(d[1]),"+f"(d[2]),"+f"(d[3]),"+f"(d[4]),"+f"(d[5]),"+f"(d[6]),"+f"(d[7]),"+f"(d[8]),"+f"(d[9]),"+f"(d[10]),"+f"(d[11]),"+f"(d[12]),"+f"(d[13]),"+f"(d[14]),"+f"(d[15]),"+f"(d[16]),"+f"(d[17]),"+f"(d[18]),"+f"(d[19]),"+f"(d[20]),"+f"(d[21]),"+f"(d[22]),"+f"(d[23]),"+f"(d[24]),"+f"(d[25]),"+f"(d[26]),"+f"(d[27]),"+f"(d[28]),"+f"(d[29]),"+f"(d[30]),"+f"(d[31]),"+f"(d[32]),"+f"(d[33]),"+f"(d[34]),"+f"(d[35]),"+f"(d[36]),"+f"(d[37]),"+f"(d[38]),"+f"(d[39]),"+f"(d[40]),"+f"(d[41]),"+f"(d[42]),"+f"(d[43]),"+f"(d[44]),"+f"(d[45]),"+f"(d[46]),"+f"(d[47]),"+f"(d[48]),"+f"(d[49]),"+f"(d[50]),"+f"(d[51]),"+f"(d[52]),"+f"(d[53]),"+f"(d[54]),"+f"(d[55]),"+f"(d[56]),"+f"(d[57]),"+f"(d[58]),"+f"(d[59]),"+f"(d[60]),"+f"(d[61]),"+f"(d[62]),"+f"(d[63]),"+f"(d[64]),"+f"(d[65]),"+f"(d[66]),"+f"(d[67]),"+f"(d[68]),"+f"(d[69]),"+f"(d[70]),"+f"(d[71]),"+f"(d[72]),"+f"(d[73]),"+f"(d[74]),"+f"(d[75]),"+f"(d[76]),"+f"(d[77]),"+f"(d[78]),"+f"(d[79]),"+f"(d[80]),"+f"(d[81]),"+f"(d[82]),"+f"(d[83]),"+f"(d[84]),"+f"(d[85]),"+f"(d[86]),"+f"(d[87]),"+f"(d[88]),"+f"(d[89]),"+f"(d[90]),"+f"(d[91]),"+f"(d[92]),"+f"(d[93]),"+f"(d[94]),"+f"(d[95])
   : "l"(da), "l"(db), "r"(sd));
}
template<> __device__ __forceinline__ void wgmma_ss<192,1,1>(float* d, uint64_t da, uint64_t db, int sd) {
  asm volatile("{\n.reg .pred p;\nsetp.ne.b32 p, %98, 0;\nwgmma.mma_async.sync.aligned.m64n192k16.f32.bf16.bf16 {%0,%1,%2,%3,%4,%5,%6,%7,%8,%9,%10,%11,%12,%13,%14,%15,%16,%17,%18,%19,%20,%21,%22,%23,%24,%25,%26,%27,%28,%29,%30,%31,%32,%33,%34,%35,%36,%37,%38,%39,%40,%41,%42,%43,%44,%45,%46,%47,%48,%49,%50,%51,%52,%53,%54,%55,%56,%57,%58,%59,%60,%61,%62,%63,%64,%65,%66,%67,%68,%69,%70,%71,%72,%73,%74,%75,%76,%77,%78,%79,%80,%81,%82,%83,%84,%85,%86,%87,%88,%89,%90,%91,%92,%93,%94,%95}, %96, %97, p, 1, 1, 1, 1;\n}\n"
   : "+f"(d[0]),"+f"(d[1]),"+f"(d[2]),"+f"(d[3]),"+f"(d[4]),"+f"(d[5]),"+f"(d[6]),"+f"(d[7]),"+f"(d[8]),"+f"(d[9]),"+f"(d[10]),"+f"(d[11]),"+f"(d[12]),"+f"(d[13]),"+f"(d[14]),"+f"(d[15]),"+f"(d[16]),"+f"(d[17]),"+f"(d[18]),"+f"(d[19]),"+f"(d[20]),"+f"(d[21]),"+f"(d[22]),"+f"(d[23]),"+f"(d[24]),"+f"(d[25]),"+f"(d[26]),"+f"(d[27]),"+f"(d[28]),"+f"(d[29]),"+f"(d[30]),"+f"(d[31]),"+f"(d[32]),"+f"(d[33]),"+f"(d[34]),"+f"(d[35]),"+f"(d[36]),"+f"(d[37]),"+f"(d[38]),"+f"(d[39]),"+f"(d[40]),"+f"(d[41]),"+f"(d[42]),"+f"(d[43]),"+f"(d[44]),"+f"(d[45]),"+f"(d[46]),"+f"(d[47]),"+f"(d[48]),"+f"(d[49]),"+f"(d[50]),"+f"(d[51]),"+f"(d[52]),"+f"(d[53]),"+f"(d[54]),"+f"(d[55]),"+f"(d[56]),"+f"(d[57]),"+f"(d[58]),"+f"(d[59]),"+f"(d[60]),"+f"(d[61]),"+f"(d[62]),"+f"(d[63]),"+f"(d[64]),"+f"(d[65]),"+f"(d[66]),"+f"(d[67]),"+f"(d[68]),"+f"(d[69]),"+f"(d[70]),"+f"(d[71]),"+f"(d[72]),"+f"(d[73]),"+f"(d[74]),"+f"(d[75]),"+f"(d[76]),"+f"(d[77]),"+f"(d[78]),"+f"(d[79]),"+f"(d[80]),"+f"(d[81]),"+f"(d[82]),"+f"(d[83]),"+f"(d[84]),"+f"(d[85]),"+f"(d[86]),"+f"(d[87]),"+f"(d[88]),"+f"(d[89]),"+f"(d[90]),"+f"(d[91]),"+f"(d[92]),"+f"(d[93]),"+f"(d[94]),"+f"(d[95])
   : "l"(da), "l"(db), "r"(sd));
}

__device__ __forceinline__ void stats_publish(uint32_t sb, int layer, int rb, int hg, int ht, uint32_t tag) {
  const int lane = ht & 31, w = ht >> 5, g = lane >> 2, t = lane & 3, ks = hg & 3;
  uint32_t xa;
  if (layer == 0) {
    const int row = 16 * w + (lane & 15), kc = 2 * ks + (lane >> 4);
    xa = row * 128 + ((kc ^ (row & 7)) << 4);
  } else {
    const int k = 16 * ks + (lane & 7) + 8 * (lane >> 4), pc = 2 * w + ((lane >> 3) & 1);
    xa = k * 128 + ((pc ^ (k & 7)) << 4);
  }
  float s[4] = {0.f, 0.f, 0.f, 0.f}, q[4] = {0.f, 0.f, 0.f, 0.f};
#pragma unroll 1
  for (int c = hg >> 2; c < 8; c += 2) {
    uint32_t A[2][4];
    mbar_wait(sb + SM_BAR + 8 * (B_XF + c), layer);
#pragma unroll
    for (int h = 0; h < 2; h++) {
      if (layer == 0) ldsm4(A[h], sb + SM_X + c * 16384 + h * 8192 + xa);
      else ldsm4t(A[h], sb + SM_X + c * 16384 + h * 8192 + xa);
    }
    if (c >= 6) ATS(48, 256);
    if (c < 2) ATS(51, 256);
#pragma unroll
    for (int r = 0; r < 4; r++)
#pragma unroll
      for (int i = 0; i < 2; i++) {
        const uint32_t v = A[r >> 1][2 * i + (r & 1)];
        const float a = bf_lo(v), b = bf_hi(v);
        s[r] += a + b; q[r] = fmaf(a, a, q[r]); q[r] = fmaf(b, b, q[r]);
      }
  }
#pragma unroll
  for (int r = 0; r < 2; r++) {
    s[r] = ((t & 2) ? s[r + 2] : s[r]) + __shfl_xor_sync(~0u, (t & 2) ? s[r] : s[r + 2], 2);
    q[r] = ((t & 2) ? q[r + 2] : q[r]) + __shfl_xor_sync(~0u, (t & 2) ? q[r] : q[r + 2], 2);
  }
  s[0] = ((t & 1) ? s[1] : s[0]) + __shfl_xor_sync(~0u, (t & 1) ? s[0] : s[1], 1);
  q[0] = ((t & 1) ? q[1] : q[0]) + __shfl_xor_sync(~0u, (t & 1) ? q[0] : q[1], 1);
  st_part(&g_part[(rb * 8 + hg) * 128 + 64 * (t >> 1) + 16 * w + 8 * (t & 1) + g], s[0], q[0], tag);
  ATS(49, 256);
}
__device__ __forceinline__ void stats_gather(uint32_t sb, int rb, int ht, uint32_t tag) {
  const uint2* src = &g_part[rb * 8 * 128 + ht];
  uint2 v[8];
  for (int it = 0;; it++) {
    uint32_t bad = 0;
#pragma unroll
    for (int i = 0; i < 8; i++) v[i] = ld_part(src + i * 128);
#pragma unroll
    for (int i = 0; i < 8; i++) bad |= v[i].y ^= tag;
    if (__all_sync(~0u, (bad & 7u) == 0)) break;
    if (it > (1 << 22)) __trap();
  }
  float s = 0.f, q = 0.f;
#pragma unroll
  for (int i = 0; i < 8; i++) { s += __uint_as_float(v[i].x); q += __uint_as_float(v[i].y); }
  const float mean = s * (1.f / DM);
  const float rstd = rsqrt_approx(fmaxf(q * (1.f / DM) - mean * mean, 0.f) + 1e-5f);
  asm volatile("st.shared.v2.f32 [%0], {%1,%2};" ::"r"(sb + SM_ST + ht * 8), "f"(mean), "f"(rstd) : "memory");
  __syncwarp();
  if (elect_one()) mbar_arrive(sb + SM_BAR + 8 * B_STF);
}
__device__ __forceinline__ void halo_receive(uint32_t sb, int layer, int rb, int hg, int ht) {
  const int lane = ht & 31, h = ht >> 5;
  uint4 kv = make_uint4(0, 0, 0, 0);
  mbar_wait(sb + SM_BAR + 8 * B_SD, layer);
  if (rb & 7) {
    const uint32_t tag = 2 * lds32(sb + SM_EP) + layer + 1;
    const uint4* src = &g_halo[((rb - 1) * 8 + hg) * 192 + h * 48];
    if (layer == 0) delay<D_HALO>(); else delay<D_HALO1>();
    uint4 a;
    uint2 b;
    int it = 0;
    do {
      a = ld_tagged(src + lane); b = ld_part((const uint2*)(src + 32) + lane);
      if (++it > (1 << 22)) __trap();
    } while (!__all_sync(~0u, a.w == tag && b.y == tag));
    kv = make_uint4(a.x, a.y, movm_t(a.z), movm_t(b.x));
  }
  sts128(sb + SM_KVX + h * 512 + lane * 16, kv);
  ATS(61, 256);
  bar_arrive(7, 160);
  if (elect_one()) mbar_arrive(sb + SM_BAR + 8 * B_HF);
}

__device__ __forceinline__ void halo_receive1(uint32_t sb, int layer, int rb, int hg, int lane, uint32_t tag) {
  uint4 a[4];
  uint2 b[4];
  mbar_wait(sb + SM_BAR + 8 * B_SD, layer);
  if (rb & 7) {
    const uint4* src = &g_halo[((rb - 1) * 8 + hg) * 192];
    if (layer == 0) delay<D_HALO>(); else delay<D_HALO1>();
    for (int it = 0;; it++) {
      uint32_t bad = 0;
#pragma unroll
      for (int h = 0; h < 4; h++) { a[h] = ld_tagged(src + h * 48 + lane); b[h] = ld_part((const uint2*)(src + h * 48 + 32) + lane); }
#pragma unroll
      for (int h = 0; h < 4; h++) {
        bad |= (a[h].w ^ tag) | (b[h].y ^ tag);
        a[h].z = movm_t(a[h].z); a[h].w = movm_t(b[h].x);
      }
      if (__all_sync(~0u, bad == 0)) break;
      if (it > (1 << 22)) __trap();
    }
  } else {
#pragma unroll
    for (int h = 0; h < 4; h++) a[h] = make_uint4(0, 0, 0, 0);
  }
#pragma unroll
  for (int h = 0; h < 4; h++) sts128(sb + SM_KVX + h * 512 + lane * 16, a[h]);
  ATS(61, 448);
  bar_arrive(7, 64);
  if (lane < 4) mbar_arrive(sb + SM_BAR + 8 * B_HF);
}

template <bool TR>
__device__ __forceinline__ void gemm_section(float* acc, float2* cs, uint32_t sb, int layer, int wg, int w, int lane) {
  const uint32_t bar = sb + SM_BAR;
  const bool leader = (w == 0) && (lane == 0);
  auto issue = [&](int c, int slot) {
    mbar_wait(bar + 8 * (B_XF + c), layer);
    mbar_wait(bar + 8 * (B_KVF + c), layer);
    const uint64_t da = mkdesc(sb + SM_X + c * 16384 + wg * 8192, TR ? 8192 : 16, 1024, 1);
    const uint64_t db = mkdesc(sb + SM_W + slot * 24576, 8192, 1024, 1);
    wg_fence();
#pragma unroll
    for (int ks = 0; ks < 4; ks++) wgmma_ss<192, TR ? 1 : 0, 1>(acc, da + (TR ? ks * 128 : ks * 2), db + ks * 128, (c | ks) != 0);
    wg_commit();
  };
  auto step = [&](int c, int slot) {
    issue(c, slot);
    wg_wait<1>();
    if (leader) mbar_arrive(bar + 8 * (B_KVE + c - 1));
  };
  if (!TR) bar_sync(0, NTHREADS);
  if (TR && G_WAIT == 3 && wg == 1) bar_sync(14, 256);
  if (TR && G_WAIT == 4 && wg == 1) mbar_wait(bar + 8 * (B_P + 3), 0);
  issue(0, 0);
  if (threadIdx.x == 0) TS(2 + layer * 20 + 0);
  if (threadIdx.x == 128 && layer == 1) TS(60);
  auto ld_cs = [&](int j0) {
#pragma unroll
    for (int j = j0; j < j0 + 8; j++) cs[j] = lds64f(sb + SM_CS + 4 * (8 * j + 2 * (lane & 3)));
  };
  if (TR && CS_STEP == 0) ld_cs(8);
  step(1, 1);
  if (TR && CS_STEP == 0) ld_cs(16);
  if (TR && CS_STEP == 1) ld_cs(8);
  step(2, 2);
  if (TR && CS_STEP == 1) ld_cs(16);
  if (TR && CS_STEP == 2) ld_cs(8);
  step(3, 0);
  if (TR && CS_STEP == 2) ld_cs(16);
  step(4, 1);
  if ((TR ? STAG1 : STAG0) == 3) {
    if (wg == 0) {
      wg_wait<0>();
      if (leader) mbar_arrive(bar + 8 * (B_KVE + 4));
      bar_sync(5, 256);
    }
    issue(5, 2);
    wg_wait<1>();
    if (leader && wg == 1) mbar_arrive(bar + 8 * (B_KVE + 4));
    if (!TR && !CS_LATE0) { mbar_wait(bar + 8 * B_CSF, 0); ld_cs(8); ld_cs(16); }
  } else {
    step(5, 2);
    if (!TR && !CS_LATE0) { mbar_wait(bar + 8 * B_CSF, 0); ld_cs(8); ld_cs(16); }
    if (wg == 0) bar_sync(5, 256);
  }
  issue(6, 0);
  issue(7, 1);
  if (wg == 1) bar_arrive(5, 256);
  if (!TR && CS_LATE0) { mbar_wait(bar + 8 * B_CSF, 0); ld_cs(8); ld_cs(16); }
}

__device__ __forceinline__ void attn_phase(const Params& p, uint32_t sb, int layer, int rb, int hg, int wg, int w) {
  const int lane = opaque_tid() & 31;
  const int g = lane >> 2, t = lane & 3;
  const uint32_t bar = sb + SM_BAR;
  const int row0 = 64 * wg + 16 * w;
  const bool leader = (w == 0) && (lane == 0);
  float acc[96];
  float2 cs[24];
  if (layer) gemm_section<true>(acc, cs, sb, layer, wg, w, lane);
  else gemm_section<false>(acc, cs, sb, layer, wg, w, lane);
  ATS(41, 224);
  mbar_wait(bar + 8 * B_STF, layer);
  const uint32_t tag = 2 * lds32(sb + SM_EP) + layer + 1;
  const float2 st0 = lds64f(sb + SM_ST + (row0 + g) * 8), st1 = lds64f(sb + SM_ST + (row0 + g + 8) * 8);
  const float mean0 = st0.x, rstd0 = st0.y, mean1 = st1.x, rstd1 = st1.y;
  wg_wait<0>();
  if (threadIdx.x == 0) TS(2 + layer * 20 + 1);
  ATS(39, 224);
  if (leader) mbar_arrive(bar + 8 * B_QDONE);

  uint32_t fp[4][4], fl[4][4], fh[4][4], qa[4][4];
  const int cw = 4 * wg + w;
  {
    const float nm0 = -mean0 * rstd0, nm1 = -mean1 * rstd1;
    const uint32_t kvx = sb + SM_KVX + cw * 2048 + lane * 16;
#pragma unroll
    for (int h = 0; h < 4; h++)
#pragma unroll
      for (int k = 0; k < 4; k++) {
        const int j = 8 + (k >> 1) * 8 + 2 * h + (k & 1);
        fh[h][k] = packbf(fmaf(acc[4 * j + 2], rstd1, nm1 * cs[j].x), fmaf(acc[4 * j + 3], rstd1, nm1 * cs[j].y));
      }
    if (cw == 7) {
      uint4* halo = &g_halo[(rb * 8 + hg) * 192];
#pragma unroll
      for (int h = 0; h < 4; h++) {
        st_tagged3(halo + h * 48 + lane, fh[h][0], fh[h][1], fh[h][2], tag);
        asm volatile("st.relaxed.gpu.global.v2.u32 [%0], {%1,%2};" ::"l"((uint2*)(halo + h * 48 + 32) + lane), "r"(fh[h][3]), "r"(tag) : "memory");
      }
      if (elect_one()) mbar_arrive(bar + 8 * B_SD);
      if (layer == TLAYER && threadIdx.x == 224) TS(47);
    }
#pragma unroll
    for (int h = 0; h < 4; h++) { fh[h][2] = movm_t(fh[h][2]); fh[h][3] = movm_t(fh[h][3]); }
    if (cw != 7) {
#pragma unroll
      for (int h = 0; h < 4; h++) sts128(kvx + 2048 + h * 512, make_uint4(fh[h][0], fh[h][1], fh[h][2], fh[h][3]));
      bar_arrive(8 + cw, 64);
    }
    sched_fence<6>();
    if (layer == TLAYER && threadIdx.x == 0) TS(45);
#pragma unroll
    for (int j = 0; j < 8; j++) cs[j] = lds64f(sb + SM_CS + 4 * (8 * j + 2 * t));
#pragma unroll
    for (int h = 0; h < 4; h++)
#pragma unroll
      for (int k = 0; k < 4; k++) {
        const int j = 8 + (k >> 1) * 8 + 2 * h + (k & 1);
        fl[h][k] = packbf(fmaf(acc[4 * j], rstd0, nm0 * cs[j].x), fmaf(acc[4 * j + 1], rstd0, nm0 * cs[j].y));
        if (k >= 2) fl[h][k] = movm_t(fl[h][k]);
      }
#pragma unroll
    for (int h = 0; h < 4; h++) {
#pragma unroll
      for (int dh = 0; dh < 2; dh++) {
        const int j = 2 * h + dh;
        const float2 c2 = cs[j];
        qa[h][2 * dh] = packbf(fmaf(-mean0, c2.x, acc[4 * j + 0]), fmaf(-mean0, c2.y, acc[4 * j + 1]));
        qa[h][2 * dh + 1] = packbf(fmaf(-mean1, c2.x, acc[4 * j + 2]), fmaf(-mean1, c2.y, acc[4 * j + 3]));
      }
    }
    if (threadIdx.x == 0) TS(2 + layer * 20 + 2);
    if (QD_AT == 1 || (QD_AT == 3 && wg == 0)) mbar_wait(bar + 8 * B_QDONE, layer);
    sched_fence<0>();
    bar_sync(7 + cw, cw == 0 && !HALO_W14 ? 160 : 64);
#pragma unroll
    for (int h = 0; h < 4; h++) {
      const uint4 v = lds128(kvx + h * 512);
      fp[h][0] = v.x; fp[h][1] = v.y; fp[h][2] = v.z; fp[h][3] = v.w;
    }
    if (threadIdx.x == 0) TS(2 + layer * 20 + 4);
  }

  const bool u0 = 2 * t > g, u1 = 2 * t + 1 > g;
  const uint32_t mU = (u0 ? 0x0000ffffu : 0u) | (u1 ? 0xffff0000u : 0u);
  const float cl2 = 0.25f * 1.4426950408889634f;
  const float sc0 = rstd0 * cl2, sc1 = rstd1 * cl2;
  const float cneg = ((rb & 7) == 0 && cw == 0) ? -INFINITY : 0.f;
  float v[4][4];
#pragma unroll
  for (int h = 0; h < 4; h++) {
    float T0[4] = {cneg, cneg, cneg, cneg}, T1[4] = {0.f, 0.f, 0.f, 0.f}, T2[4] = {0.f, 0.f, 0.f, 0.f};
    mma_bf16(T1, qa[h], fl[h][0], fl[h][1]);
    mma_bf16(T2, qa[h], fh[h][0], fh[h][1]);
    mma_bf16(T0, qa[h], fp[h][0], fp[h][1]);
    v[h][0] = u0 ? T0[0] : T1[0]; v[h][1] = u1 ? T0[1] : T1[1];
    v[h][2] = u0 ? T1[2] : T2[2]; v[h][3] = u1 ? T1[3] : T2[3];
  }
  float m0[4], m1[4];
#pragma unroll
  for (int h = 0; h < 4; h++) { m0[h] = fmaxf(v[h][0], v[h][1]); m1[h] = fmaxf(v[h][2], v[h][3]); }
#pragma unroll
  for (int o = 1; o <= 2; o <<= 1) {
#pragma unroll
    for (int h = 0; h < 4; h++) {
      m0[h] = fmaxf(m0[h], __shfl_xor_sync(~0u, m0[h], o));
      m1[h] = fmaxf(m1[h], __shfl_xor_sync(~0u, m1[h], o));
    }
  }
  float O0[4][4], O1[4][4], Z[4][4];
#pragma unroll
  for (int h = 0; h < 4; h++) {
    const float mm0 = -m0[h] * sc0, mm1 = -m1[h] * sc1;
    const uint32_t P0 = packbf(ex2(fmaf(v[h][0], sc0, mm0)), ex2(fmaf(v[h][1], sc0, mm0)));
    const uint32_t P1 = packbf(ex2(fmaf(v[h][2], sc1, mm1)), ex2(fmaf(v[h][3], sc1, mm1)));
#pragma unroll
    for (int k = 0; k < 4; k++) O0[h][k] = O1[h][k] = Z[h][k] = 0.f;
    mma_bf16_k8(Z[h], P0, P1, 0x3f803f80u);
    mma_bf16_k8(O0[h], P0 & ~mU, P1 & mU, fl[h][2]); mma_bf16_k8(O1[h], P0 & ~mU, P1 & mU, fl[h][3]);
    mma_bf16_k8(O0[h], P0 & mU, 0u, fp[h][2]); mma_bf16_k8(O1[h], P0 & mU, 0u, fp[h][3]);
    mma_bf16_k8(O0[h], 0u, P1 & ~mU, fh[h][2]); mma_bf16_k8(O1[h], 0u, P1 & ~mU, fh[h][3]);
  }
  const uint32_t ob = sb + SM_OST + wg * 8192;
  if (QD_AT == 0 || (QD_AT == 3 && wg == 1)) mbar_wait(bar + 8 * B_QDONE, layer);
  const int o_row = 16 * w + (lane & 7) + 8 * ((lane >> 3) & 1);
#pragma unroll
  for (int h = 0; h < 4; h++) {
    const float i0 = rcp_approx(Z[h][0]), i1 = rcp_approx(Z[h][2]);
    const int ch = 2 * h + (lane >> 4);
    stsm4(ob + o_row * 128 + ((ch ^ (o_row & 7)) << 4), packbf(O0[h][0] * i0, O0[h][1] * i0), packbf(O0[h][2] * i1, O0[h][3] * i1),
          packbf(O1[h][0] * i0, O1[h][1] * i0), packbf(O1[h][2] * i1, O1[h][3] * i1));
  }
  if (threadIdx.x == 0) TS(2 + layer * 20 + 5);
  ATS(57, 128); ATS(20, 96);
  __syncwarp();
  if (elect_one()) {
    fence_async_smem();
    tma_st(&p.mapO, hg * 64, rb * 128 + row0, ob + w * 2048);
    bulk_commit();
    mbar_arrive(bar + 8 * B_AD);
    bulk_wait_all();
    uint32_t old;
    asm volatile("atom.acq_rel.cta.shared.inc.u32 %0, [%1], 7;" : "=r"(old) : "r"(sb + SM_EP + 4) : "memory");
    if (old == 7) {
      asm volatile("red.relaxed.gpu.global.add.u32 [%0], 2;" ::"l"(&g_cnt[(C_O + rb) * 32]) : "memory");
      asm volatile("mbarrier.arrive.shared::cta.b64 _, [%0], 2;" ::"r"(bar + 8 * B_OST) : "memory");
      TS(2 + layer * 20 + 6);
    }
  }
  __syncwarp();
}

__device__ __forceinline__ void proj_phase(const Params& p, uint32_t sb, int layer, int rb, int q, int wg, int w) {
  const int lane = opaque_tid() & 31;
  const bool TR = layer != 0;
  const int t = lane & 3;
  const uint32_t bar = sb + SM_BAR;
  const uint32_t rbx = sb + SM_R + wg * 8192;
  uint32_t res[16];
  mbar_wait(bar + 8 * B_RF, layer);
  if (threadIdx.x == 0) TS(2 + layer * 20 + 7);
  if (!TR) {
#pragma unroll
    for (int j = 0; j < 8; j += 2) {
      const int mi = lane >> 3;
      const int row = 16 * w + (lane & 7) + 8 * (mi & 1), ch = j + (mi >> 1);
      ldsm4(&res[2 * j], rbx + row * 128 + ((ch ^ (row & 7)) << 4));
    }
  } else {
#pragma unroll
    for (int j = 0; j < 8; j += 2) {
      const int mi = lane >> 3;
      const int line = 8 * (j + (mi >> 1)) + (lane & 7), pc = 2 * w + (mi & 1);
      ldsm4t(&res[2 * j], rbx + line * 128 + ((pc ^ (line & 7)) << 4));
    }
  }
  bar_sync(2 + wg, 128);
  float acc[32];
#pragma unroll
  for (int i = 0; i < 16; i++) {
    asm volatile("shl.b32 %0, %1, 16;" : "=f"(acc[2 * i]) : "r"(res[i]));
    asm volatile("and.b32 %0, %1, 0xffff0000;" : "=f"(acc[2 * i + 1]) : "r"(res[i]));
  }
  const uint32_t tag = part_tag(lds32(sb + SM_EP), 2 * layer + 1);
  mbar_wait(bar + 8 * B_ZF, layer);
  mbar_wait(bar + 8 * B_WOF, layer);
  tensor_keepalive<1>();
#pragma unroll P_UNROLL
  for (int c = 0; c < 8; c++) {
    mbar_wait(bar + 8 * (B_OF + c), layer);
    if (c == 0 && threadIdx.x == 0) TS(2 + layer * 20 + 8);
    const uint64_t da = mkdesc(sb + sm_o(c) + wg * 8192, 16, 1024, 1);
    const uint64_t db = mkdesc(sb + SM_WO + c * 8192, 8192, 1024, 1);
    wg_fence();
#pragma unroll
    for (int ks = 0; ks < 4; ks++) wgmma_ss<64, 0, 1>(acc, da + ks * 2, db + ks * 128, 1);
    wg_commit();
  }
  wg_wait<0>();
#pragma unroll
  for (int i = 0; i < 32; i++) asm volatile("" : "+f"(acc[i]) :: "memory");
  if (threadIdx.x == 0) TS(2 + layer * 20 + 9);
  if (lane == 0 && w == 0) mbar_arrive(bar + 8 * B_PDONE);
  {
    float s[4], qq[4];
#pragma unroll
    for (int k = 0; k < 4; k++) { s[k] = acc[k]; qq[k] = acc[k] * acc[k]; }
#pragma unroll
    for (int j = 1; j < 8; j++)
#pragma unroll
      for (int k = 0; k < 4; k++) { s[k] += acc[4 * j + k]; qq[k] = fmaf(acc[4 * j + k], acc[4 * j + k], qq[k]); }
    const float s0 = s[0] + s[1], s1 = s[2] + s[3], q0 = qq[0] + qq[1], q1 = qq[2] + qq[3];
    float sr = ((t & 1) ? s1 : s0) + __shfl_xor_sync(~0u, (t & 1) ? s0 : s1, 1);
    float qr = ((t & 1) ? q1 : q0) + __shfl_xor_sync(~0u, (t & 1) ? q0 : q1, 1);
    sr += __shfl_xor_sync(~0u, sr, 2);
    qr += __shfl_xor_sync(~0u, qr, 2);
    if (t < 2) st_part(&g_part[(rb * 8 + q) * 128 + 64 * wg + 16 * w + (lane >> 2) + 8 * t], sr, qr, tag);
    __syncwarp();
    if (elect_one()) mbar_arrive(bar + 8 * B_PS);
    sched_fence<7>();
  }
#pragma unroll
  for (int j = 0; j < 8; j += 2) {
    const int mi = lane >> 3;
    const int line = 8 * (j + (mi >> 1)) + (lane & 7), pc = 2 * w + (mi & 1);
    stsm4t(rbx + line * 128 + ((pc ^ (line & 7)) << 4), packbf(acc[4 * j], acc[4 * j + 1]), packbf(acc[4 * j + 2], acc[4 * j + 3]),
           packbf(acc[4 * j + 4], acc[4 * j + 5]), packbf(acc[4 * j + 6], acc[4 * j + 7]));
  }
  fence_writer();
  bar_sync(2 + wg, 128);
  if (FIN4 && (q >= 4 || FIN4 == 2)) {
    if (w == 0 && elect_one()) mbar_arrive(bar + 8 * B_SG);
  } else if (w == 0 && elect_one()) {
    fence_reader();
    fence_async_global();
    tma_st(&p.mapXT, rb * 128 + wg * 64, (2 * layer) * DM + q * 64, rbx);
    bulk_commit();
    if (threadIdx.x == 0) TS(2 + layer * 20 + 10);
    bulk_wait_all();
    red_relaxed(&g_cnt[C_CS * 32 + 2 + layer + (q >= 4 ? 2 : 0)]);
    if (wg == 0) mbar_arrive(bar + 8 * B_RE);
  }
  __syncwarp();
}
__device__ __forceinline__ void proj_stats(uint32_t sb, int layer, int rb, int q, int lane, uint32_t tag) {
  const int r = FIN4 ? 32 * (q - 4) + lane : 16 * q + (lane & 15);
  const uint2* src = &g_part[rb * 8 * 128 + r];
  uint32_t* dst = g_stats + layer * LSEQ + (rb >> 1) * 256 + ((r >> 2) & 1) * 128 + ((rb & 1) * 16 + (r >> 3)) * 4 + (r & 3);
  mbar_wait(sb + SM_BAR + 8 * B_PS, layer);
  delay<D_PST>();
  for (int it = 0;; it++) {
    uint2 v[8];
#pragma unroll
    for (int i = 0; i < 8; i++) v[i] = ld_part(src + i * 128);
    float s[4], qq[4];
    uint32_t bad = 0;
#pragma unroll
    for (int i = 0; i < 4; i++) {
      s[i] = __uint_as_float(v[i].x) + __uint_as_float(v[i + 4].x);
      qq[i] = __uint_as_float(v[i].y ^ tag) + __uint_as_float(v[i + 4].y ^ tag);
      bad |= (v[i].y ^ tag) | (v[i + 4].y ^ tag);
    }
    const float mean = ((s[0] + s[1]) + (s[2] + s[3])) * (1.f / DM);
    const float rstd = rsqrt_approx(fmaxf(fmaf((qq[0] + qq[1]) + (qq[2] + qq[3]), 1.f / DM, -mean * mean), 0.f) + 1e-5f);
    const bool ok = __all_sync(~0u, (bad & 7u) == 0);
    if (ok && (FIN4 || lane < 16))
    {
      if (PUB & 1) asm volatile("red.relaxed.gpu.global.or.b32 [%0], %1;" ::"l"(dst), "r"(max(packbf(-mean, rstd), 1u)) : "memory");
      else asm volatile("st.relaxed.gpu.global.u32 [%0], %1;" ::"l"(dst), "r"(max(packbf(-mean, rstd), 1u)) : "memory");
    }
    if (ok) break;
    if (it > (1 << 22)) __trap();
  }
}

#define NA 14
#define NP 16
template <int M0, int M1> __device__ __forceinline__ void conv_load(uint32_t* A, uint32_t pe) {
#pragma unroll
  for (int m = M0; m < M1; m++) {
    asm volatile("ld.shared.v2.b32 {%0,%1}, [%2];" : "=r"(A[4 * m]), "=r"(A[4 * m + 1]) : "r"(pe + 256 * m) : "memory");
    A[4 * m + 2] = lds32(pe + 256 * m - 4);
  }
}
__device__ __forceinline__ uint32_t copy_reg(uint32_t v, uint32_t zero) { uint32_t r; asm volatile("or.b32 %0, %1, %2;" : "=r"(r) : "r"(v), "r"(zero)); return r; }
__device__ __forceinline__ uint32_t copy_reg2(uint32_t v, uint32_t zero) { uint32_t r; asm volatile("xor.b32 %0, %1, %2;" : "=r"(r) : "r"(v), "r"(zero)); return r; }
__device__ __forceinline__ void conv_park(uint32_t* P, uint32_t pe) {
#pragma unroll
  for (int m = 0; m < NP; m++)
#pragma unroll
    for (int k = 0; k < 3; k++) P[3 * m + k] = lds32(pe + 256 * m - 4 + 4 * k);
}
__device__ __forceinline__ void conv_unpark(uint32_t* A, const uint32_t* P, uint32_t zero) {
#pragma unroll
  for (int m = 0; m < NP; m++) {
    A[4 * m + 2] = copy_reg(P[3 * m], zero); A[4 * m] = copy_reg(P[3 * m + 1], zero);
    A[4 * m + 3] = copy_reg2(P[3 * m + 1], zero); A[4 * m + 1] = copy_reg(P[3 * m + 2], zero);
  }
}
template <int M0, int M1> __device__ __forceinline__ void conv_mmas(float* acc, const uint32_t* A, uint64_t d) {
  if constexpr (M0 < M1) {
    wgmma_rs<128 - 8 * (M0 / 2), 0>(acc, A + 4 * M0, d + (uint64_t)(4 * M0), M0 != 0);
    conv_mmas<M0 + 1, M1>(acc, A, d);
  }
}
struct SumAddr { uint32_t l0, l1, l2, se, so; };
__device__ __forceinline__ SumAddr conv_sum_addr(uint32_t sb, int c) {
  auto ua = [&](int j) { return sb + cv_u(0) + (127 - (j >> 3)) * 16 + (j & 7) * 2; };
  auto sa = [&](int hc) { const int ci = hc & ~1; return sb + cv_s(0) + ((ci >> 3) & 1) * 1024 + (ci >> 4) * 128 + (((ci ^ (ci >> 4)) & 7) << 4) + (hc & 1) * 8; };
  const int j0 = 4 * (c - 1);
  return {ua(j0 - 2), ua(j0), ua(j0 + 4), sa((c + 1) & 127), sa(c) + 2048};
}
__device__ __forceinline__ void sts64(uint32_t a, uint32_t x, uint32_t y) { asm volatile("st.shared.v2.b32 [%0], {%1,%2};" ::"r"(a), "r"(x), "r"(y) : "memory"); }
__device__ __forceinline__ void conv_sums(const SumAddr& sa, int lc, int c) {
  uint32_t e[4], o[4];
  {
    const float2 em = lds64f(sa.l1 + lc * 32768), om = lds64f(sa.l1 + lc * 32768 + CV_UH);
    e[0] = lds32(sa.l0 + lc * 32768); o[0] = lds32(sa.l0 + lc * 32768 + CV_UH);
    e[3] = lds32(sa.l2 + lc * 32768); o[3] = lds32(sa.l2 + lc * 32768 + CV_UH);
    e[1] = __float_as_uint(em.x); e[2] = __float_as_uint(em.y); o[1] = __float_as_uint(om.x); o[2] = __float_as_uint(om.y);
  }
  uint32_t s7e[2], s7o[2], s9e[2], s9o[2];
  uint32_t pw[4], sh[3];
#pragma unroll
  for (int k = 0; k < 4; k++) pw[k] = hadd2(e[k], o[k]);
#pragma unroll
  for (int k = 0; k < 3; k++) sh[k] = __byte_perm(pw[k], pw[k + 1], 0x5432);
#pragma unroll
  for (int k = 0; k < 2; k++) {
    const uint32_t t3 = hadd2(hadd2(sh[k], sh[k + 1]), pw[k + 1]);
    s7e[k] = hadd2(t3, o[k]); s7o[k] = hadd2(t3, e[k + 2]);
    s9e[k] = hadd2(s7o[k], pw[k]); s9o[k] = hadd2(s7e[k], pw[k + 2]);
  }
  if (c == 127) s9e[0] = s9e[1] = s9o[0] = s9o[1] = 0u;
  sts64(sa.se + lc * 32768, s9e[0], s9e[1]); sts64((sa.se ^ 16) + lc * 32768, s9o[0], s9o[1]);
  sts64(sa.so + lc * 32768, s7e[0], s7e[1]); sts64((sa.so ^ 16) + lc * 32768, s7o[0], s7o[1]);
}

__device__ __forceinline__ void conv_epi(uint32_t sb, int layer, int cta, int ch, int c0, uint4 x0, uint4 x1) {
  uint4 v[2][4];
  const uint4 xr[2] = {x0, x1};
  mbar_wait(sb + SM_BAR + 8 * (B_P + ch), layer);
#pragma unroll
  for (int u = 0; u < 2; u++) {
    const uint32_t pb = sb + cv_pb(ch) + u * (CV_PBW / 2) + c0 * 16;
#pragma unroll
    for (int k = 0; k < 4; k++) v[u][k] = lds128(pb + k * CV_PBW);
  }
#pragma unroll
  for (int u = 0; u < 2; u++) {
    uint4 o;
    o.x = hadd2(xr[u].x, hadd2(hadd2(v[u][0].x, v[u][1].x), hadd2(v[u][2].x, v[u][3].x)));
    o.y = hadd2(xr[u].y, hadd2(hadd2(v[u][0].y, v[u][1].y), hadd2(v[u][2].y, v[u][3].y)));
    o.z = hadd2(xr[u].z, hadd2(hadd2(v[u][0].z, v[u][1].z), hadd2(v[u][2].z, v[u][3].z)));
    o.w = hadd2(xr[u].w, hadd2(hadd2(v[u][0].w, v[u][1].w), hadd2(v[u][2].w, v[u][3].w)));
    if (layer == 0) sts128(sb + cv_s(ch) + (c0 + 128 * u) * 16, o);
    else if ((PUB & 4) && ch == 3) {
      uint2* d = (uint2*)((uint4*)(g_xT + (size_t)(3 * DM + cv_chan(cta, ch)) * LSEQ) + c0 + 128 * u);
      asm volatile("{\n.reg .b64 a, b;\nmov.b64 a, {%1,%2};\nmov.b64 b, {%3,%4};\nred.relaxed.gpu.global.and.b64 [%0+8], b;\nred.relaxed.gpu.global.and.b64 [%0], a;\n}" ::"l"(d), "r"(o.x), "r"(o.y), "r"(o.z), "r"(o.w) : "memory");
    } else st_tagged3((uint4*)(g_xT + (size_t)(3 * DM + cv_chan(cta, ch)) * LSEQ) + c0 + 128 * u, o.x, o.y, o.z, o.w);
  }
}
__device__ __forceinline__ void warp_release(uint32_t b) {
  fence_writer();
  __syncwarp();
  if (elect_one()) mbar_arrive(b);
}

__device__ __forceinline__ void conv_prep_load(uint32_t sb, int layer, int cta, int c, uint4 (&xr)[4], uint4 (&st)[4]) {
  sched_fence<8>();
  mbar_wait(sb + SM_BAR + 8 * B_GB, layer);
  if (threadIdx.x == 0) TS(2 + layer * 20 + 11);
  xr[0] = ld_tagged((const uint4*)(g_xT + (size_t)(2 * layer * DM + cta) * LSEQ) + c);
#pragma unroll
  for (int i = 0; i < 2; i++) st[i] = ld_tagged((const uint4*)g_stats + layer * 512 + (c >> 5) * 64 + i * 32 + (c & 31));
}
struct RowNorm { uint32_t nm[4], rs[4]; };
__device__ __forceinline__ RowNorm row_norm(uint4 a, uint4 b) {
  return {{__byte_perm(a.x, a.y, 0x5410), __byte_perm(a.z, a.w, 0x5410), __byte_perm(b.x, b.y, 0x5410), __byte_perm(b.z, b.w, 0x5410)},
          {__byte_perm(a.x, a.y, 0x7632), __byte_perm(a.z, a.w, 0x7632), __byte_perm(b.x, b.y, 0x7632), __byte_perm(b.z, b.w, 0x7632)}};
}
__device__ __forceinline__ uint4 normalize(uint4 x, const RowNorm& r) {
  return make_uint4(hmul2(hadd2(x.x, r.nm[0]), r.rs[0]), hmul2(hadd2(x.y, r.nm[1]), r.rs[1]), hmul2(hadd2(x.z, r.nm[2]), r.rs[2]), hmul2(hadd2(x.w, r.nm[3]), r.rs[3]));
}
template <bool HELPER>
__device__ __forceinline__ void conv_prep(uint32_t sb, int layer, int cta, int c, uint4 (&xr)[4], uint4 (&st)[4], const SumAddr& sa) {
  const uint32_t bar = sb + SM_BAR;
  const uint4* xin = (const uint4*)(g_xT + (size_t)(2 * layer * DM + cta) * LSEQ) + c;
  for (int it = 0;; it++) {
    const uint32_t vs = min(min(min(st[0].x, st[0].y), min(st[0].z, st[0].w)), min(min(st[1].x, st[1].y), min(st[1].z, st[1].w)));
    if (__all_sync(~0u, vs != 0 && xr[0].x != ~0u)) break;
    if (it > (1 << 22)) __trap();
    if (!__all_sync(~0u, xr[0].x != ~0u)) xr[0] = ld_tagged(xin);
    if (!__all_sync(~0u, vs != 0)) {
#pragma unroll
      for (int i = 0; i < 2; i++) st[i] = ld_tagged((const uint4*)g_stats + layer * 512 + (c >> 5) * 64 + i * 32 + (c & 31));
    }
  }
  const RowNorm rn = row_norm(st[0], st[1]);
  if (threadIdx.x == 0) TS(2 + layer * 20 + 12);
  const uint32_t ua = sb + cv_u(0) + (c >> 7) * CV_UH + (127 - (c & 127)) * 16;
  sts128(ua, normalize(xr[0], rn));
  warp_release(bar + 8 * B_U);
  mbar_wait(bar + 8 * B_XV, layer);
  xr[1] = ld_tagged(xin + 128 * LSEQ / 8);
  if (HELPER) {
    mbar_wait(bar + 8 * B_U, layer);
    conv_sums(sa, 0, c);
    fence_async_smem();
    bar_arrive(7, 256);
    sched_fence<1>();
    if (layer == 1 && c == 0) TS(46);
  }
  sts128(ua + 32768, normalize(xr[1], rn));
  warp_release(bar + 8 * (B_U + 1));
  if (HELPER) {
    const uint4* so = (const uint4*)g_stats + layer * 512 + 256 + (c >> 5) * 64 + (c & 31);
    auto sums1 = [&] {
      mbar_wait(bar + 8 * (B_U + 1), layer);
      conv_sums(sa, 1, c);
      fence_async_smem();
      bar_arrive(8, 256);
    };
    if (S1_AT == 0) sums1();
    const uint4 s0 = ld_tagged(so), s1 = ld_tagged(so + 32);
    if (S1_AT == 0) st[0] = ld_tagged(xin + 128);
    mbar_wait(bar + 8 * B_XV2, layer);
#pragma unroll
    for (int j = 2; j < 4; j++) { xr[j] = ld_tagged(xin + j * (128 * LSEQ / 8)); st[j] = ld_tagged(xin + j * (128 * LSEQ / 8) + 128); }
    if (S1_AT == 1) sums1();
    if (S1_AT != 0) st[0] = ld_tagged(xin + 128);
    const RowNorm ro = row_norm(s0, s1);
#pragma unroll
    for (int j = 2; j < 4; j++) {
      sts128(ua + j * 32768, normalize(xr[j], rn));
      sts128(ua + j * 32768 + CV_UH, normalize(st[j], ro));
      __syncwarp();
      if (elect_one()) asm volatile("mbarrier.arrive.shared::cta.b64 _, [%0], 2;" ::"r"(bar + 8 * (B_U + j)) : "memory");
    }
    if (S1_AT == 2) sums1();
  }
}
__device__ __forceinline__ void conv_zero(uint32_t sb, int ht) {
  if (ht < 96) {
    const int ch = ht / 24, h2 = (ht / 12) & 1, qq = ht % 12;
    sts128(sb + cv_u(ch) + h2 * CV_UH + (128 + qq) * 16, make_uint4(0, 0, 0, 0));
  }
  if (ht >= 80) {
    const int i = ht - 80, ch = i / 12, q2 = i % 12;
    const int w2 = q2 < 2 ? 1 : q2 < 6 ? 2 : 3, cc = q2 < 2 ? q2 : q2 < 6 ? q2 - 2 : q2 - 6;
    sts128(sb + cv_pb(ch) + w2 * CV_PBW + (cc & 1) * (CV_PBW / 2) + (cc >> 1) * 16, make_uint4(0, 0, 0, 0));
  }
}

#define HANDOVER 1
template <int R>
__device__ __forceinline__ void conv_round(uint32_t sb, int layer, int wg, uint32_t* A, const uint32_t* P, uint32_t pb, uint32_t pe2) {
  const uint32_t bar = sb + SM_BAR;
  const int ch = 2 * R + 1 - wg;
  float acc[64];
  const uint64_t d = mkdesc(sb + cv_u(ch), CV_UH, 128, 0);
  FTS(39);
  if (R == 0) {
    mbar_wait(bar + 8 * (B_U + ch), layer);
    fence_reader();
  }
  sched_fence<3>();
  if (R == 1 || wg == 0) bar_sync(10 + ch, 256);
  if (layer == 0 && ch > 0 && ((PAUSE >> (ch - 1)) & 1)) mbar_wait(bar + 8 * (B_E + ch - 1), 0);
  if (layer == 0 && ch > 0 && ((PAUSE >> (ch + 3)) & 1)) mbar_wait(bar + 8 * (B_P + ch - 1), 0);
  FTS(41);
  if (ch == 0 && threadIdx.x == 128) TS(2 + layer * 20 + 13);
  wg_fence();
  conv_mmas<0, 1>(acc, A, d); conv_mmas<2, NA + 1>(acc, A, d);
  wg_commit();
  FTS(51);
  if (HANDOVER == 0 && (R == 0 || wg == 1)) bar_arrive(11 + ch, 256);
  bar_sync(7 + ch, 256);
  wg_fence();
  conv_mmas<1, 2>(acc, A, d); conv_mmas<NA + 1, 17>(acc, A, d);
  wgmma_ss<64, 1, 1>(acc, mkdesc(sb + cv_s(ch), 1024, 1024, 1), mkdesc(sb + cv_ft(ch), 256, 16, 0), 1);
  wgmma_ss<64, 1, 1>(acc, mkdesc(sb + cv_s(ch) + 2048, 1024, 1024, 1), mkdesc(sb + cv_ft(ch) + 512, 256, 16, 0), 1);
  wg_commit();
  if (HANDOVER == 1 && (R == 0 || wg == 1 || (G_WAIT == 3 && layer == 0))) bar_arrive(11 + ch, 256);
  FTS(61);
  wg_wait<0>();
#pragma unroll
  for (int j = 0; j < 16; j += 2)
    stsm4t(pb + R * 65536 - j * 128, packbf(acc[4 * j], acc[4 * j + 1]), packbf(acc[4 * j + 2], acc[4 * j + 3]),
           packbf(acc[4 * j + 4], acc[4 * j + 5]), packbf(acc[4 * j + 6], acc[4 * j + 7]));
  __syncwarp();
  if (elect_one()) mbar_arrive(bar + 8 * (B_P + ch));
  if (threadIdx.x == 0) TS(2 + layer * 20 + 14 + R);
  FTS(57);
  if (R == 0) {
    conv_unpark(A, P, opaque_tid() >> 10);
    mbar_wait(bar + 8 * (B_U + ch + 2), layer);
    fence_reader();
    conv_load<NP, 17>(A, pe2);
#pragma unroll
    for (int m = NP; m < 17; m++) A[4 * m + 3] = lds32(pe2 + 256 * m);
  }
}
__device__ __forceinline__ void conv_phase(const Params& p, uint32_t sb, int layer, int cta) {
  const int tid = opaque_tid();
  const int wg = __shfl_sync(~0u, tid >> 7, 0), w = __shfl_sync(~0u, (tid >> 5) & 3, 0);
  const uint32_t bar = sb + SM_BAR;
  uint32_t A[68], P[3 * NP];
  const uint32_t pe = sb + cv_pe(1 - wg) + 4 * (16 + 16 * w + 2 * ((tid & 31) >> 2) - 4 * (tid & 3));
  mbar_wait(bar + 8 * B_PE, layer);
  tensor_keepalive<2>();
  conv_load<0, 17>(A, pe);
#pragma unroll
  for (int m = 0; m < 17; m++) A[4 * m + 3] = copy_reg(A[4 * m], tid >> 10);
  if (wg == 0) {
    uint4 xr[4], st[4];
    if (PARK_FIRST) conv_park(P, pe + 65536);
    conv_prep_load(sb, layer, cta, tid + 128, xr, st);
    if (!PARK_FIRST) conv_park(P, pe + 65536);
    conv_prep<false>(sb, layer, cta, opaque_tid() + 128, xr, st, SumAddr());
  } else {
    conv_park(P, pe + 65536);
    if (KEEP & 8) mbar_wait(bar + 8 * B_GB, layer);
    tensor_keepalive<3>();
  }
  uint32_t pb;
  {
    const int l2 = opaque_tid() & 31, mt = l2 >> 3;
    pb = sb + cv_pb(1 - wg) + w * CV_PBW + (mt & 1) * (CV_PBW / 2) + (127 - 8 * (mt >> 1) - (l2 & 7) + w) * 16;
  }
  conv_round<0>(sb, layer, wg, A, P, pb, pe + 65536);
  conv_round<1>(sb, layer, wg, A, P, pb, 0);
  if (G_WAIT == 1 && layer == 0) mbar_wait(bar + 8 * (B_E + 3), layer);
  if (G_WAIT == 2 && layer == 0) mbar_wait(bar + 8 * (B_P + 3), layer);
}

__device__ __forceinline__ void final_phase(const Params& p, uint32_t sb, int cta, int wg, int w) {
  const int lane = opaque_tid() & 31, g = lane >> 2, t = lane & 3;
  constexpr int RS = 2 * DM;
  int it = 0;
  {
    const int lc = wg ? 0 : 3;
    const int p0 = (cta & 15) * 128 + 32 * w, c0 = 128 * lc + (cta >> 4) * 16;
    const bf16* src = g_xT + (size_t)(3 * DM + c0 + 4 * (g >> 1) + (g & 1)) * LSEQ + p0 + 8 * t;
    bf16* dst = p.out + (size_t)(2 * ((p0 & 1023) + 8 * (g >> 1) + (g & 1)) + (p0 >> 10)) * DM + c0 + 4 * t;
    if (wg == 0) {
      mbar_wait(sb + SM_BAR + 8 * (B_E + 3), 1);
      delay<D_FIN>();
    }
    uint4 a, b;
    for (;;) {
      a = ld_tagged((const uint4*)src); b = ld_tagged((const uint4*)(src + 2 * LSEQ));
      if (__all_sync(~0u, max(a.x, b.x) != ~0u)) break;
      if (++it > (1 << 22)) __trap();
    }
    if (threadIdx.x == 0) TS(42);
    *(uint2*)dst = make_uint2(movm_t(a.x), movm_t(b.x));
    *(uint2*)(dst + 2 * RS) = make_uint2(movm_t(a.y), movm_t(b.y));
    *(uint2*)(dst + 4 * RS) = make_uint2(movm_t(a.z), movm_t(b.z));
    *(uint2*)(dst + 6 * RS) = make_uint2(movm_t(a.w), movm_t(b.w));
  }
  if (wg == 1) {
    const int lc = 1 + (w >> 1);
    const int p0 = (cta & 31) * 64 + 32 * (w & 1), c0 = 128 * lc + (cta >> 5) * 32;
    const bf16* src = g_xT + (size_t)(3 * DM + c0 + 8 * (g >> 1) + (g & 1)) * LSEQ + p0 + 8 * t;
    bf16* dst = p.out + (size_t)(2 * ((p0 & 1023) + 8 * (g >> 1) + (g & 1)) + (p0 >> 10)) * DM + c0 + 8 * t;
    mbar_wait(sb + SM_BAR + 8 * (B_E + lc), 1);
    if (lc >= FIN_D0) delay<D_FIN2>();
    uint4 v[4];
    for (;;) {
#pragma unroll
      for (int q = 0; q < 4; q++) v[q] = ld_tagged((const uint4*)(src + 2 * q * LSEQ));
      if (__all_sync(~0u, max(max(v[0].x, v[1].x), max(v[2].x, v[3].x)) != ~0u)) break;
      if (++it > (1 << 22)) __trap();
    }
    *(uint4*)dst = make_uint4(movm_t(v[0].x), movm_t(v[1].x), movm_t(v[2].x), movm_t(v[3].x));
    *(uint4*)(dst + 2 * RS) = make_uint4(movm_t(v[0].y), movm_t(v[1].y), movm_t(v[2].y), movm_t(v[3].y));
    *(uint4*)(dst + 4 * RS) = make_uint4(movm_t(v[0].z), movm_t(v[1].z), movm_t(v[2].z), movm_t(v[3].z));
    *(uint4*)(dst + 6 * RS) = make_uint4(movm_t(v[0].w), movm_t(v[1].w), movm_t(v[2].w), movm_t(v[3].w));
  }
  if (threadIdx.x == 0) TS(43);
  if (threadIdx.x == 192) TS(63);
  if (threadIdx.x == 160) TS(53);
  if (threadIdx.x == 0) LTS(1);
}

struct cplx { float r, i; };
__device__ __forceinline__ cplx cmul(cplx a, cplx b) { return {fmaf(a.r, b.r, -a.i * b.i), fmaf(a.r, b.i, a.i * b.r)}; }
__device__ __forceinline__ cplx csqr(cplx a) { return {fmaf(a.r, a.r, -a.i * a.i), (a.r + a.r) * a.i}; }
__device__ __forceinline__ cplx cexp_l(float ar2, float ai, float l) {
  const float m = ex2(ar2 * l);
  const float x = ai * l;
  return {m * __cosf(x), m * __sinf(x)};
}

__device__ __forceinline__ void colsum_publish(uint32_t sb, int rb, int hg, int ht, uint32_t tag) {
  const int lane = ht & 31, q = lane & 15, h = lane >> 4;
  const uint32_t src = sb + SM_CW + (ht >> 5) * 4096 + h * 128 + (q & 1) * 8;
  float s[4] = {0.f, 0.f, 0.f, 0.f};
#pragma unroll 8
  for (int r = 0; r < 16; r++) {
    const float2 v = lds64f(src + r * 256 + (((q >> 1) ^ ((2 * r + h) & 7)) << 4));
    s[0] += bf_lo(__float_as_uint(v.x)); s[1] += bf_hi(__float_as_uint(v.x));
    s[2] += bf_lo(__float_as_uint(v.y)); s[3] += bf_hi(__float_as_uint(v.y));
  }
#pragma unroll
  for (int k = 0; k < 4; k++) s[k] += __shfl_xor_sync(~0u, s[k], 16);
  if (h == 0)
    st_tagged3(&g_colsum[(hg * 16 + rb) * 48 + (ht >> 5) * 16 + q], (__float_as_uint(s[0]) & ~7u) | tag, __float_as_uint(s[1]),
               __float_as_uint(s[2]), __float_as_uint(s[3]));
}
__device__ __forceinline__ void colsum_gather(uint32_t sb, int hg, int ht, uint32_t tag) {
  const int lane = ht & 31, rec = (ht >> 5) * 16 + (lane & 15);
  const uint4* src = &g_colsum[(hg * 16 + (lane >> 4) * 8) * 48 + rec];
  float s[4] = {0.f, 0.f, 0.f, 0.f};
#pragma unroll 1
  for (int h = 0; h < 2; h++, src += 4 * 48) {
    uint4 v[4];
    int it = 0;
    do {
#pragma unroll
      for (int i = 0; i < 4; i++) v[i] = ld_tagged(src + i * 48);
      if (++it > (1 << 22)) __trap();
    } while (!__all_sync(~0u, (v[0].x & 7u) == tag && (v[1].x & 7u) == tag && (v[2].x & 7u) == tag && (v[3].x & 7u) == tag));
#pragma unroll
    for (int i = 0; i < 4; i++) {
      s[0] += __uint_as_float(v[i].x & ~7u); s[1] += __uint_as_float(v[i].y); s[2] += __uint_as_float(v[i].z); s[3] += __uint_as_float(v[i].w);
    }
  }
#pragma unroll
  for (int k = 0; k < 4; k++) s[k] += __shfl_xor_sync(~0u, s[k], 16);
  if (lane < 16) sts128f(sb + SM_CS + rec * 16, s[0], s[1], s[2], s[3]);
}

__device__ __forceinline__ uint32_t packh(float lo, float hi) { uint32_t r; asm("cvt.rn.f16x2.f32 %0, %1, %2;" : "=r"(r) : "f"(hi), "f"(lo)); return r; }
__device__ __forceinline__ void mma_f16(float* d, uint32_t a0, uint32_t a1, uint32_t a2, uint32_t a3, uint32_t b0, uint32_t b1) {
  asm volatile("mma.sync.aligned.m16n8k16.row.col.f32.f16.f16.f32 {%0,%1,%2,%3}, {%4,%5,%6,%7}, {%8,%9}, {%0,%1,%2,%3};"
      : "+f"(d[0]), "+f"(d[1]), "+f"(d[2]), "+f"(d[3]) : "r"(a0), "r"(a1), "r"(a2), "r"(a3), "r"(b0), "r"(b1));
}
struct HSeed { uint32_t r, i; };
__device__ __forceinline__ HSeed hseed(cplx s) { return {packh(s.r, s.r), packh(s.i, s.i)}; }
__device__ __forceinline__ void hcmul(uint32_t& o_r, uint32_t& o_i, uint32_t br, uint32_t bi, HSeed s) {
  asm("{\n.reg .b32 t, u;\nmul.rn.f16x2 t, %3, %5;\nneg.f16x2 t, t;\nmul.rn.f16x2 u, %3, %4;\nfma.rn.f16x2 %0, %2, %4, t;\nfma.rn.f16x2 %1, %2, %5, u;\n}"
      : "=&r"(o_r), "=&r"(o_i) : "r"(br), "r"(bi), "r"(s.r), "r"(s.i));
}
struct HTile { uint32_t r[4], i[4]; };
__device__ __forceinline__ void tile_set(HTile& t, int k, cplx a, cplx b) { t.r[k] = packh(a.r, b.r); t.i[k] = packh(a.i, b.i); }
__device__ __forceinline__ void tile_upper(HTile& t, HSeed s) { hcmul(t.r[2], t.i[2], t.r[0], t.i[0], s); hcmul(t.r[3], t.i[3], t.r[1], t.i[1], s); }
__device__ __forceinline__ HTile tile_shift(const HTile& t, HSeed s) {
  HTile o;
#pragma unroll
  for (int k = 0; k < 4; k++) hcmul(o.r[k], o.i[k], t.r[k], t.i[k], s);
  return o;
}
__device__ __forceinline__ void tile_put(const HTile& t, uint32_t a) {
  sts128(a, make_uint4(t.r[0], t.r[1], t.r[2], t.r[3]));
  sts128(a + 512, make_uint4(t.i[0], t.i[1], t.i[2], t.i[3]));
}
__device__ __forceinline__ HTile tile_get(uint32_t a) { HTile o; ldsm4t(o.r, a); ldsm4t(o.i, a + 512); return o; }
__device__ __forceinline__ void tile_mma(float* T, const HTile& a0, const HTile& a1, const HTile& b) {
  mma_f16(T, a0.r[0], a0.r[1], a0.r[2], a0.r[3], b.r[0], b.r[1]);
  mma_f16(T, a0.i[0], a0.i[1], a0.i[2], a0.i[3], b.i[0], b.i[1]);
  mma_f16(T, a1.r[0], a1.r[1], a1.r[2], a1.r[3], b.r[2], b.r[3]);
  mma_f16(T, a1.i[0], a1.i[1], a1.i[2], a1.i[3], b.i[2], b.i[3]);
}
__device__ __forceinline__ void tile_mma2(float* T, float* U, const HTile& a0, const HTile& a1, const HTile& b, const HTile& c) {
  mma_f16(T, a0.r[0], a0.r[1], a0.r[2], a0.r[3], b.r[0], b.r[1]);
  mma_f16(U, a0.r[0], a0.r[1], a0.r[2], a0.r[3], c.r[0], c.r[1]);
  mma_f16(T, a0.i[0], a0.i[1], a0.i[2], a0.i[3], b.i[0], b.i[1]);
  mma_f16(U, a0.i[0], a0.i[1], a0.i[2], a0.i[3], c.i[0], c.i[1]);
  mma_f16(T, a1.r[0], a1.r[1], a1.r[2], a1.r[3], b.r[2], b.r[3]);
  mma_f16(U, a1.r[0], a1.r[1], a1.r[2], a1.r[3], c.r[2], c.r[3]);
  mma_f16(T, a1.i[0], a1.i[1], a1.i[2], a1.i[3], b.i[2], b.i[3]);
  mma_f16(U, a1.i[0], a1.i[1], a1.i[2], a1.i[3], c.i[2], c.i[3]);
}
__device__ __forceinline__ void kgen_unit(uint32_t tab, uint32_t taba, float ar2, float ai, cplx c, float (&T)[5][4]) {
  const cplx z1 = cexp_l(ar2, ai, 1.f), z16 = cexp_l(ar2, ai, 16.f), z256 = cexp_l(ar2, ai, 256.f);
  HTile a0, a1, b0, b1;
  {
    const cplx y1 = {z16.r, -z16.i}, y2 = csqr(y1), y3 = cmul(y2, y1), y4 = csqr(y2), y5 = cmul(y4, y1), y6 = csqr(y3), y7 = cmul(y4, y3);
    HTile t;
    tile_set(t, 0, {1.f, 0.f}, y1); tile_set(t, 1, y2, y3); tile_set(t, 2, y4, y5); tile_set(t, 3, y6, y7);
    const HTile u = tile_shift(t, hseed(csqr(y4)));
    __syncwarp();
    tile_put(t, tab); tile_put(u, tab + 1024);
    __syncwarp();
    a0 = tile_get(taba); a1 = tile_get(taba + 256);
  }
  const cplx z2 = csqr(z1), z4 = csqr(z2), z8 = csqr(z4);
  const HSeed h8 = hseed(z8);
  const cplx d = cmul(c, z256), e = cmul(d, z256);
  {
    const cplx z512 = csqr(z256), f = cmul(e, z512), f8 = cmul(f, z8), f16 = cmul(f, z16), e4 = cmul(e, z4);
    HTile t, u;
    tile_set(t, 0, e4, cmul(e, z8)); tile_set(t, 1, cmul(e4, z8), cmul(e, z16));
    tile_upper(t, hseed(z256));
    tile_set(u, 0, f8, f16); tile_set(u, 1, cmul(f8, z256), cmul(f16, z256));
    tile_upper(u, hseed(z512));
    __syncwarp();
    tile_put(t, tab); tile_put(u, tab + 1024);
    __syncwarp();
    b0 = tile_get(tab); b1 = tile_get(tab + 1024);
  }
  {
    const cplx d2 = cmul(d, z2), d4 = cmul(d, z4);
    HTile t;
    tile_set(t, 0, d2, d4); tile_set(t, 1, cmul(d2, z4), cmul(d, z8));
    tile_upper(t, h8);
    __syncwarp();
    tile_put(t, tab);
    __syncwarp();
    tile_mma2(T[3], T[4], a0, a1, b0, b1);
    b0 = tile_get(tab);
  }
  {
    const cplx c1 = cmul(c, z1), c2 = cmul(c, z2), c3 = cmul(c1, z2), c4 = cmul(c, z4);
    HTile t;
    tile_set(t, 0, c1, c2); tile_set(t, 1, c3, c4); tile_set(t, 2, cmul(c1, z4), cmul(c2, z4)); tile_set(t, 3, cmul(c3, z4), cmul(c4, z4));
    const HTile u = tile_shift(t, h8);
    __syncwarp();
    tile_put(t, tab); tile_put(u, tab + 1024);
    __syncwarp();
    tile_mma(T[2], a0, a1, b0);
    b0 = tile_get(tab); b1 = tile_get(tab + 1024);
    tile_mma2(T[0], T[1], a0, a1, b0, b1);
  }
}
struct ModeIn { uint2 ar, ai, br, bi, cr, ci; };
__device__ __forceinline__ ModeIn load_modes(const Params& p, int idx) {
  return {*(const uint2*)(p.a_re + idx), *(const uint2*)(p.a_im + idx), *(const uint2*)(p.b_re + idx),
          *(const uint2*)(p.b_im + idx), *(const uint2*)(p.c_re + idx), *(const uint2*)(p.c_im + idx)};
}
__device__ __forceinline__ float bf_el(uint2 v, int k) { const uint32_t x = (k & 2) ? v.y : v.x; return (k & 1) ? bf_hi(x) : bf_lo(x); }
struct KGen { float4 cur; float T[5][4]; };
__device__ __forceinline__ uint32_t kgen_slot(uint32_t sb, int ht, int u) {
  return sb + (u < 3 ? SM_KC + (ht >> 5) * (KC_STRIDE * 2) + (u - 1) * 512 + (ht & 31) * 16 + 16 : SM_HALO + 1024 + ht * 16);
}
__device__ __forceinline__ void kgen_setup(KGen& s, uint32_t sb, int cta, int ht, const ModeIn& in, bf16 logdt, bf16 dskip) {
  const float dt = __bfloat162float(__float2bfloat16_rn(expf(__bfloat162float(logdt))));
  float mx = 0.f, k0 = 0.f, ar2[4];
  cplx c[4];
#pragma unroll
  for (int k = 0; k < 4; k++) {
    ar2[k] = (dt * bf_el(in.ar, k)) * 1.4426950408889634f;
    c[k] = cmul({bf_el(in.cr, k), bf_el(in.ci, k)}, {dt * bf_el(in.br, k), dt * bf_el(in.bi, k)});
    k0 += c[k].r;
    mx = fmaxf(mx, fmaxf(fabsf(c[k].r), fabsf(c[k].i)) * ex2(fmaxf(ar2[k] * 2048.f, 0.f)));
  }
  const int ex = min(max(267 - (int)(__reduce_max_sync(~0u, __float_as_uint(mx)) >> 23), 1), 253);
  const float sc = __uint_as_float(ex << 23);
#pragma unroll
  for (int o = 16; o > 0; o >>= 1) k0 += __shfl_xor_sync(~0u, k0, o);
  if ((ht & 31) == 0) {
    const uint32_t kc = sb + SM_KC + (ht >> 5) * (KC_STRIDE * 2);
    sts16(kc, __bfloat16_as_ushort(__float2bfloat16_rn(k0 + __bfloat162float(dskip))));
    sts16(kc + 641 * 2, 0);
    sts32f(kc + 644 * 2, __uint_as_float((254 - ex) << 23));
  }
  s.cur = make_float4(ar2[0], dt * bf_el(in.ai, 0), c[0].r * sc, c[0].i * sc);
#pragma unroll
  for (int k = 1; k < 4; k++) sts128f(kgen_slot(sb, ht, k), ar2[k], dt * bf_el(in.ai, k), c[k].r * sc, c[k].i * sc);
#pragma unroll
  for (int i = 0; i < 5; i++) s.T[i][0] = s.T[i][1] = s.T[i][2] = s.T[i][3] = 0.f;
}
__device__ __forceinline__ void kgen_finish(KGen& s, uint32_t sb, int cta, int ht) {
  const int w = ht >> 5, lane = ht & 31, g = lane >> 2, t = lane & 3;
  const uint32_t kc = sb + SM_KC + w * KC_STRIDE * 2;
  __syncwarp();
  const float inv = __uint_as_float(lds32(kc + 644 * 2));
  auto put = [&](int idx, float v) {
    sts16(kc + idx * 2, __bfloat16_as_ushort(__float2bfloat16_rn(v)));
  };
#pragma unroll
  for (int hi = 0; hi < 2; hi++)
#pragma unroll
    for (int lo = 0; lo < 2; lo++) {
      const int i = g + 8 * hi, j = 2 * t + lo, e = 2 * hi + lo;
      put(16 * i + 1 + j, s.T[0][e] * inv);
      put(16 * i + 9 + j, s.T[1][e] * inv);
      put(257 + 8 * i + j, s.T[2][e] * inv);
      put(385 + 4 * i + (j & 3) + 64 * (j >> 2), s.T[3][e] * inv);
      put(513 + 2 * i + lo + 32 * t, s.T[4][e] * inv);
    }
}

__device__ __forceinline__ void expand_taps(uint32_t sb, int ht) {
  const int ch = ht >> 5, lane = ht & 31;
  const uint32_t kc = sb + SM_KC + ch * KC_STRIDE * 2;
  const uint32_t dst0 = sb + cv_pe(ch);
  auto put = [&](int G, uint32_t u0, uint32_t u1, uint32_t v0, uint32_t v1, uint32_t v2, uint32_t v3, uint32_t v4, uint32_t v5, uint32_t v6, uint32_t v7) {
    const uint32_t dst = dst0 + G * 32;
    sts128(dst, make_uint4(v0 | (u0 << 16), v1 | (u1 << 16), v2 | (v0 << 16), v3 | (v1 << 16)));
    sts128(dst + 16, make_uint4(v4 | (v2 << 16), v5 | (v3 << 16), v6 | (v4 << 16), v7 | (v5 << 16)));
  };
  {
    const uint4 q = lds128(kc + lane * 16);
    const uint32_t pv = lane ? lds32(kc + lane * 16 - 4) : 0u;
    const uint32_t dst = dst0 + (lane + 2) * 32;
    sts128(dst, make_uint4(__byte_perm(q.x, pv, 0x5410), __byte_perm(q.x, pv, 0x7632), __byte_perm(q.y, q.x, 0x5410), __byte_perm(q.y, q.x, 0x7632)));
    sts128(dst + 16, make_uint4(__byte_perm(q.z, q.y, 0x5410), __byte_perm(q.z, q.y, 0x7632), __byte_perm(q.w, q.z, 0x5410), __byte_perm(q.w, q.z, 0x7632)));
    if (lane < 4) sts128(dst0 + lane * 16, make_uint4(0, 0, 0, 0));
  }
  uint32_t a[5], b[2][3], fv[4];
  {
    const uint32_t s1 = kc + 2 * (256 + 4 * lane);
#pragma unroll
    for (int k = 0; k < 5; k++) a[k] = lds16(s1 + 2 * k);
#pragma unroll
    for (int u = 0; u < 2; u++) {
      const uint32_t s2 = kc + 2 * (384 + 2 * (lane + 32 * u));
#pragma unroll
      for (int k = 0; k < 3; k++) b[u][k] = lds16(s2 + 2 * k);
    }
#pragma unroll
    for (int k = 0; k < 4; k++) fv[k] = lds16(kc + 2 * (640 - 4 * lane - k));
  }
  const uint32_t am1 = lds16(kc + 2 * (lane ? 256 + 4 * lane : 255)), am2 = lds16(kc + 2 * (lane ? 255 + 4 * lane : 254));
  const uint32_t bm2 = lds16(kc + 2 * (lane ? 384 + 2 * lane : 383)), k1024 = lds16(kc + 2 * 512);
  put(34 + lane, am2, am1, a[0], a[0], a[1], a[2], a[2], a[2], a[3], a[4]);
#pragma unroll
  for (int u = 0; u < 2; u++) put(66 + lane + 32 * u, u ? b[u][0] : bm2, b[u][0], b[u][0], b[u][0], b[u][0], b[u][1], b[u][1], b[u][1], b[u][2], b[u][2]);
  if (lane < 10) {
    const uint32_t v = lane == 0 ? k1024 : 0u;
    put(130 + lane, v, v, v, v, v, v, v, 0u, 0u, 0u);
  }
  const uint32_t ft = sb + cv_ft(ch) + 4 * lane;
#pragma unroll
  for (int ty = 0; ty < 2; ty++) {
    const uint32_t v = fv[ty] | (fv[ty + 2] << 16);
    sts32f(ft + ty * 512, __uint_as_float(v));
    sts32f(ft + ty * 512 + 128, 0.f);
    sts32f(ft + ty * 512 + 256 + (lane < 2 ? 120 : -8), __uint_as_float(lane < 2 ? 0u : v));
    sts32f(ft + ty * 512 + 384, 0.f);
  }
}

__device__ __forceinline__ int role_id() { int v; asm volatile("mov.u32 %0, %%ctaid.x;" : "=r"(v)); return v; }
#define GMAP 8
__device__ __forceinline__ int role_rb(int cta) { return 4 * (cta >> 5) + (cta & 3); }
__device__ __forceinline__ int role_hg(int cta) { return 2 * (((cta >> 3) & 3) ^ (((cta >> 5) & 1) * 3)) + ((cta >> 2) & 1); }
__device__ __forceinline__ int role_rb2(int cta) { return cta >> 3; }
__device__ __forceinline__ int role_q2(int cta) { return cta & 7; }

__global__ void __launch_bounds__(NTHREADS, 1) fused_kernel(const __grid_constant__ Params p) {
  extern __shared__ __align__(1024) uint8_t smem[];
  const uint32_t sb = s32(smem);
  const int tid = threadIdx.x, lane = tid & 31;
  const int warp = __shfl_sync(~0u, tid >> 5, 0);
  const uint32_t bar = sb + SM_BAR;
  if (tid == 0) TS(0);
  const int cta0 = role_id();
  if (warp == 0 && elect_one()) {
    const int rb = role_rb(cta0), hg = role_hg(cta0);
#pragma unroll
    for (int c = 0; c < 2; c++) { mbar_init(bar + 8 * (B_XF + c), 1); mbar_init(bar + 8 * (B_KVF + c), 1); }
    fence_async_smem();
#pragma unroll
    for (int c = 0; c < 2; c++) {
      mbar_expect(bar + 8 * (B_XF + c), 16384);
      tma_ld(sb + SM_X + c * 16384, &p.mapX128, (rb >> 3) * DM + c * 64, (rb & 7) * 128, bar + 8 * (B_XF + c));
      mbar_expect(bar + 8 * (B_KVF + c), 24576);
      tma_ld3(sb + SM_W + c * 24576, &p.mapW3, hg * 64, c * 64, 0, bar + 8 * (B_KVF + c));
    }
  }
  if (warp == 2) tensor_keepalive<4>();
  if (warp == 1 && elect_one()) {
    const int rb = role_rb(cta0), hg = role_hg(cta0);
#pragma unroll
    for (int c = 2; c < 8; c++) mbar_init(bar + 8 * (B_XF + c), 1);
    mbar_init(bar + 8 * (B_KVF + 2), 1); mbar_init(bar + 8 * B_CW, 1);
    fence_async_smem();
    delay<D_START>();
    mbar_expect(bar + 8 * B_CW, 12288);
    tma_ld3(sb + SM_CW, &p.mapW3h, hg * 64, rb * 32, 0, bar + 8 * B_CW);
#pragma unroll
    for (int c = 2; c < 8; c++) {
      mbar_expect(bar + 8 * (B_XF + c), 16384);
      tma_ld(sb + SM_X + c * 16384, &p.mapX128, (rb >> 3) * DM + c * 64, (rb & 7) * 128, bar + 8 * (B_XF + c));
      if (c < 3) {
        mbar_expect(bar + 8 * (B_KVF + c), 24576);
        tma_ld3(sb + SM_W + c * 24576, &p.mapW3, hg * 64, c * 64, 0, bar + 8 * (B_KVF + c));
      }
    }
    TS(56);
  }
  if ((warp & 2) != 0 && warp < 15 && elect_one()) {
    const int grp = 1 + (warp & 1) + 2 * (warp >> 2), cnt = grp < 4 ? 1 : grp < 5 ? 2 : grp < 7 ? 4 : 8;
#pragma unroll
    for (int k = 0; k < 10; k++)
      if (k != 0 || grp > 3 || grp == 2) mbar_init(bar + 8 * (10 * grp + k), cnt);
    fence_async_smem();
  }

  if (warp < 8) {
    if (tid == 0) TS(1);
    asm volatile("setmaxnreg.inc.sync.aligned.u32 %0;" ::"n"(R_CONS));
    const int cta = role_id();
    auto warp_id = [] { return __shfl_sync(~0u, opaque_tid() >> 5, 0); };
    tensor_keepalive<0>();
    if (tid == 0) TS(54);
#pragma unroll 1
    for (int layer = 0; layer < 2; layer++) {
      { const int cw = warp_id(); attn_phase(p, sb, layer, role_rb(cta), role_hg(cta), cw >> 2, cw & 3); }
      if (STOP == 1 + 3 * layer) return;
      { const int cw = warp_id(); proj_phase(p, sb, layer, role_rb2(cta), role_q2(cta), cw >> 2, cw & 3); }
      if (STOP == 2 + 3 * layer) return;
      conv_phase(p, sb, layer, cta);
      if (STOP == 3 + 3 * layer) return;
    }
    { const int cw = warp_id(); final_phase(p, sb, cta, cw >> 2, cw & 3); }
  } else if (warp < 12) {
    asm volatile("setmaxnreg.dec.sync.aligned.u32 %0;" ::"n"(R_HELP));
    const int ht = tid - 256;
    const int cta = role_id(), rb = role_rb(cta), hg = role_hg(cta);
    unsigned ep0 = 0;
    if (ht == 0) ep0 = ld_relaxed(&g_cnt[C_CS * 32]);
    bar_sync(0, NTHREADS);
    if (ht == 0) {
      asm volatile("st.shared.v2.u32 [%0], {%1, 0};" ::"r"(sb + SM_EP), "r"(ep0 / NCTA) : "memory");
      mbar_arrive(bar + 8 * B_EP);
    }
    mbar_wait(bar + 8 * B_EP, 0);
    stats_publish(sb, 0, rb, hg, opaque_tid() - 256, part_tag(lds32(sb + SM_EP), 0));
    if (ht < 48) {
      const bf16* q = (&p.a_re)[ht >> 3];
      asm volatile("prefetch.global.L2 [%0];" ::"l"(q + cv_chan(cta, (ht >> 1) & 3) * 128 + (ht & 1) * 64));
    }
    {
      KGen kg;
      const uint32_t tab0 = sb + ((ht >> 5) < 2 ? SM_T : SM_T2 - 4096) + (ht >> 5) * 2048;
      const uint32_t tab = tab0 + (ht & 31) * 16, taba = tab0 + ((ht >> 3) & 1) * 1024 + (((ht >> 1) & 8) + (ht & 7)) * 16;
      delay<D_ST0>();
      stats_gather(sb, rb, opaque_tid() - 256, part_tag(lds32(sb + SM_EP), 0));
      if (ht == 0) TS(40);
      const int chn = cv_chan(cta, ht >> 5);
      const ModeIn modes = load_modes(p, chn * 128 + (ht & 31) * 4);
      const bf16 logdt = p.log_dt[chn], dskip = p.dskip[chn];
      if (!HALO_W14 && KG_START != 4) halo_receive(sb, 0, rb, hg, opaque_tid() - 256);
      if (KG_START == 1) mbar_wait(bar + 8 * B_HF, 0);
      kgen_setup(kg, sb, cta, ht, modes, logdt, dskip);
      if (!HALO_W14 && KG_START == 4) halo_receive(sb, 0, rb, hg, opaque_tid() - 256);
      if (KG_START == 2) mbar_wait(bar + 8 * B_HF, 0);
      if (KG_START == 3) mbar_wait(bar + 8 * B_QDONE, 0);
#pragma unroll 1
      for (int u = 0; u < 4; u++) {
        if (u == KG_PRE) {
          KTS(39);
          mbar_wait(bar + 8 * B_AD, 0);
          KTS(41);
        }
        kgen_unit(tab, taba, kg.cur.x, kg.cur.y, {kg.cur.z, kg.cur.w}, kg.T);
        kg.cur = lds128f(kgen_slot(sb, opaque_tid() - 256, u + 1));
      }
      kgen_finish(kg, sb, cta, opaque_tid() - 256);
    }
    KTS(51);
    bar_sync(4, 128);
#pragma unroll 1
    for (int layer = 0; layer < 2; layer++) {
      if (STOP <= 1 + 3 * layer) return;
      mbar_wait(bar + 8 * (EXP_LATE ? B_PS : B_PDONE), layer);
      expand_taps(sb, opaque_tid() - 256);
      conv_zero(sb, opaque_tid() - 256);
      if (ht == 0) TS(52 + layer);
      warp_release(bar + 8 * B_PE);
      if (STOP <= 2 + 3 * layer) return;
      {
        uint4 xr[4], st[4];
        const int c = opaque_tid() - 256;
        const SumAddr sa = conv_sum_addr(sb, c);
        conv_prep_load(sb, layer, cta, c, xr, st);
        conv_prep<true>(sb, layer, cta, c, xr, st, sa);
        if (layer == 1 && ht == 0) TS(62);
        const int ahead = layer ? S_AHEAD1 : S_AHEAD0;
        mbar_wait(bar + 8 * (B_U + 3), layer);
#pragma unroll
        for (int lc = 0; lc < 4; lc++) {
          if (lc < 3 && lc + ahead > 1 && lc + ahead < 4) {
            conv_sums(sa, lc + ahead, c);
            fence_async_smem();
            bar_arrive(7 + lc + ahead, 256);
            sched_fence<4>();
          }
          if (lc == 0) st[1] = ldcg128(g_xT + (size_t)(2 * layer * DM + cv_chan(cta, 1)) * LSEQ + (c + 128) * 8);
          conv_epi(sb, layer, cta, lc, c, xr[lc], st[lc]);
          warp_release(bar + 8 * (B_E + lc));
          sched_fence<5>();
          if (layer == 1 && lc == 3 && ht == 0) TS(38);
        }
      }
      if (layer == 0 && STOP > 3) {
        const int c1 = role_id();
        stats_publish(sb, 1, role_rb(c1), role_hg(c1), opaque_tid() - 256, part_tag(lds32(sb + SM_EP), 2));
        delay<D_ST>();
        stats_gather(sb, role_rb(c1), opaque_tid() - 256, part_tag(lds32(sb + SM_EP), 2));
        if (ht == 0) TS(25);
        if (!HALO_W14) halo_receive(sb, 1, role_rb(c1), role_hg(c1), opaque_tid() - 256);
      }
    }
  } else {
    asm volatile("setmaxnreg.dec.sync.aligned.u32 %0;" ::"n"(512 - 2 * R_CONS - R_HELP));
    const int cta = role_id(), rb = role_rb(cta), hg = role_hg(cta), rb2 = role_rb2(cta), q2 = role_q2(cta);
    bar_sync(0, NTHREADS);
    if (warp != 12) {
      mbar_wait(bar + 8 * B_EP, 0);
      const uint32_t tag = lds32(sb + SM_EP) % 7 + 1;
      mbar_wait(bar + 8 * B_CW, 0);
      colsum_publish(sb, rb, hg, tid - 416, tag);
      if (tid == 416) TS(50);
      delay<D_CS>();
      colsum_gather(sb, hg, tid - 416, tag);
      __syncwarp();
      if (tid == 416) TS(55);
    }
    if (elect_one()) mbar_arrive(bar + 8 * B_CSF);
    if (warp == 12) {
      if (elect_one()) {
        unsigned epoch = 0;
#pragma unroll 1
        for (int layer = 0; layer < 2; layer++) {
          auto ld_w = [&](int c, int slot) {
            const uint32_t b = bar + 8 * (B_KVF + c);
            mbar_expect(b, 24576);
            tma_ld3(sb + SM_W + slot * 24576, &p.mapW3, hg * 64, c * 64, 0, b);
          };
          if (layer == 0) {
            mbar_wait(bar + 8 * (B_KVF + 2), 0);
            if (rb2 < 4) tma_prefetch2(&p.mapWo128, q2 * 64, rb2 * 128);
            asm volatile("prefetch.tensormap [%0];" ::"l"(&p.mapO) : "memory");
            asm volatile("prefetch.tensormap [%0];" ::"l"(&p.mapO128) : "memory");
            asm volatile("prefetch.tensormap [%0];" ::"l"(&p.mapXT) : "memory");
            asm volatile("prefetch.tensormap [%0];" ::"l"(&p.mapXT3) : "memory");
            mbar_wait(bar + 8 * B_EP, 0);
            epoch = lds32(sb + SM_EP);
          } else {
            mbar_wait(bar + 8 * (B_U + 3), 0);
            ld_w(0, 0); ld_w(1, 1); ld_w(2, 2);
          }
          {
            int slot = 0;
#pragma unroll 1
            for (int c = 3; c < 8; c++) {
              mbar_wait(bar + 8 * (B_KVE + c - 3), layer);
              ld_w(c, slot);
              slot = slot == 2 ? 0 : slot + 1;
            }
          }
          if (STOP <= 1 + 3 * layer) return;
          const int early = layer ? WO_E1 : WO_E0;
          mbar_wait(bar + 8 * B_STF, layer);
          fence_async_smem();
          mbar_expect(bar + 8 * B_WOF, 65536);
#pragma unroll
          for (int c = 0; c < 4; c++) if (c < early) tma_ld(sb + SM_WO + c * 16384, &p.mapWo128, q2 * 64, c * 128, bar + 8 * B_WOF);
          mbar_wait(bar + 8 * B_QDONE, layer);
          mbar_wait(bar + 8 * B_HF, layer);
#pragma unroll
          for (int c = 0; c < 4; c++) if (c >= early) tma_ld(sb + SM_WO + c * 16384, &p.mapWo128, q2 * 64, c * 128, bar + 8 * B_WOF);
          {
            const uint32_t b = bar + 8 * B_RF;
            mbar_expect(b, 16384);
            if (layer == 0) tma_ld(sb + SM_R, &p.mapX128, (rb2 >> 3) * DM + q2 * 64, (rb2 & 7) * 128, b);
            else tma_ld3(sb + SM_R, &p.mapXT3, 0, DM + q2 * 64, rb2 * 2, b);
          }
#pragma unroll
          for (int c = 0; c < 8; c++) mbar_expect(bar + 8 * (B_OF + c), 16384);
          spin_until(&g_cnt[(C_O + rb2) * 32], (2 * epoch + layer + 1) * 16);
          fence_async_global();
#pragma unroll
          for (int c = 0; c < 8; c++) {
            if (c == 6) { mbar_wait(bar + 8 * B_OST, layer); fence_async_smem(); }
            tma_ld(sb + sm_o(c), &p.mapO128, c * 64, rb2 * 128, bar + 8 * (B_OF + c));
          }
          if (STOP <= 3 + 3 * layer) return;
        }
      }
    } else if (warp == 13) {
      if (elect_one() && STOP > 1) {
        const unsigned target = (lds32(sb + SM_EP) + 1) * NCTA;
        auto after_proj = [&](int layer) {
          mbar_wait(bar + 8 * XV_AT, layer);
          spin_until(&g_cnt[C_CS * 32 + 2 + layer], target);
          mbar_arrive(bar + 8 * B_XV);
          spin_until(&g_cnt[C_CS * 32 + 4 + layer], target);
          mbar_arrive(bar + 8 * B_XV2);
        };
        after_proj(0);
        if (STOP <= 3) return;
        auto ld_x = [&](int c) { tma_ld3(sb + SM_X + c * 16384, &p.mapXT3, 0, DM + c * 64, rb * 2, bar + 8 * (B_XF + c)); };
#pragma unroll
        for (int c = 0; c < 8; c++) mbar_expect(bar + 8 * (B_XF + c), 16384);
        spin_until(&g_cnt[C_G1 * 32], target);
        fence_async_global();
        fence_async_smem();
        ld_x(0); ld_x(1);
        int done = 1, it = 0;
        while (done < 4) {
          const uint4 v = ld_tagged((const uint4*)&g_cnt[C_G1 * 32]);
          const int n = 4 + ((int)(v.y - target) >> 31) + ((int)(v.z - target) >> 31) + ((int)(v.w - target) >> 31);
          if (n == done) { if (++it > (1 << 23)) __trap(); continue; }
          if (n == 4) TS(44);
          fence_async_global();
          fence_async_smem();
          if (done == 1) { ld_x(2); ld_x(3); }
          const int h = hg >> 2;
          if (done < 3 && n >= 3) ld_x(4 + h);
          if (n == 4) ld_x(6 + h);
          if (done < 3 && n >= 3) ld_x(5 - h);
          if (n == 4) ld_x(7 - h);
          done = n;
        }
        if (STOP <= 4) return;
        after_proj(1);
      }
    } else if (warp == 15) {
      mbar_wait(bar + 8 * B_EP, 0);
      const unsigned epoch = lds32(sb + SM_EP);
#pragma unroll 1
      for (int layer = 0; layer < 2; layer++) {
        mbar_wait(bar + 8 * (B_KVF + FILL_AT), layer);
#pragma unroll
        for (int k = 0; k < 8; k++) ((uint4*)(g_xT + (size_t)(2 * layer * DM + cta) * LSEQ))[32 * k + lane] = make_uint4(~0u, ~0u, ~0u, ~0u);
        mbar_wait(bar + 8 * (B_KVF + FILL_AT + 1), layer);
#pragma unroll
        for (int k = 0; k < 16; k++)
          ((uint4*)(g_xT + (size_t)(3 * DM + cv_chan(cta, 3 - (k >> 2))) * LSEQ))[128 * layer + 32 * (k & 3) + lane] = make_uint4(~0u, ~0u, ~0u, ~0u);
        if (lane < 4) ((uint4*)g_stats)[layer * 512 + cta * 4 + lane] = make_uint4(0, 0, 0, 0);
        __syncwarp();
        if (elect_one()) {
          red_release(&g_cnt[C_CS * 32 + layer]);
          spin_until(&g_cnt[C_CS * 32 + layer], (epoch + 1) * NCTA);
          mbar_arrive(bar + 8 * B_ZF);
          if (layer == 0 && STOP > 2) {
#pragma unroll
            for (int lc = 0; lc < 4; lc++) {
              mbar_wait(bar + 8 * (B_E + lc), 0);
              fence_reader();
              bulk_st(g_xT + (size_t)(DM + cv_chan(cta, lc)) * LSEQ, sb + cv_s(lc), 4096);
              bulk_commit();
              bulk_wait_all();
              red_relaxed(&g_cnt[C_G1 * 32 + lc]);
              if (lc == 3) TS(18);
            }
          }
        }
        __syncwarp();
        if (STOP <= 3) return;
      }
    } else if (warp == 14) {
      mbar_wait(bar + 8 * B_EP, 0);
      const unsigned epoch = lds32(sb + SM_EP);
#pragma unroll 1
      for (int layer = 0; layer < 2; layer++) {
        if (STOP <= 3 * layer) return;
        if (HALO_W14) halo_receive1(sb, layer, rb, hg, opaque_tid() & 31, 2 * epoch + layer + 1);
        if (STOP <= 1 + 3 * layer) return;
        mbar_wait(bar + 8 * B_ZF, layer);
        if (!FIN4 || q2 >= 4) proj_stats(sb, layer, rb2, q2, opaque_tid() & 31, part_tag(epoch, 2 * layer + 1));
        else mbar_wait(bar + 8 * B_PS, layer);
        if (layer == 1 && lane == 0) TS(5);
        uint32_t t0;
        asm volatile("mov.u32 %0, %%clock;" : "=r"(t0));
        if (FIN4 && (q2 >= 4 || FIN4 == 2)) {
          mbar_wait(bar + 8 * B_SG, layer);
          if (elect_one()) {
            fence_async_smem();
            fence_async_global();
            asm volatile("cp.async.bulk.tensor.3d.global.shared::cta.bulk_group [%0, {%2, %3, %4}], [%1];"
                         ::"l"(&p.mapXT3), "r"(sb + SM_R), "r"(0), "r"(2 * layer * DM + q2 * 64), "r"(rb2 * 2) : "memory");
            bulk_commit();
            if (q2 >= 4) {
              uint32_t t;
              do { asm volatile("mov.u32 %0, %%clock;" : "=r"(t)); } while (t - t0 < D_PREP);
              mbar_arrive(bar + 8 * B_GB);
            }
            bulk_wait_all();
            asm volatile("red.relaxed.gpu.global.add.u32 [%0], 2;" ::"l"(&g_cnt[C_CS * 32 + 2 + layer + (q2 >= 4 ? 2 : 0)]) : "memory");
            mbar_arrive(bar + 8 * B_RE);
          }
          __syncwarp();
        }
        if (!FIN4 || q2 < 4) {
          uint32_t t;
          do { asm volatile("mov.u32 %0, %%clock;" : "=r"(t)); } while (t - t0 < (FIN4 ? D_PREP + D_Q : D_PREP));
          if (lane == 0) mbar_arrive(bar + 8 * B_GB);
        }
      }
    }
  }
}

typedef CUresult (*EncodeFn)(CUtensorMap*, CUtensorMapDataType, cuuint32_t, void*, const cuuint64_t*, const cuuint64_t*,
                             const cuuint32_t*, const cuuint32_t*, CUtensorMapInterleave, CUtensorMapSwizzle,
                             CUtensorMapL2promotion, CUtensorMapFloatOOBfill);

static void make_map(EncodeFn enc, CUtensorMap* m, void* ptr, uint64_t cols, uint64_t rows, uint32_t box_rows) {
  cuuint64_t dims[2] = {cols, rows};
  cuuint64_t strides[1] = {cols * 2};
  cuuint32_t box[2] = {64, box_rows};
  cuuint32_t es[2] = {1, 1};
  enc(m, CU_TENSOR_MAP_DATA_TYPE_BFLOAT16, 2, ptr, dims, strides, box, es, CU_TENSOR_MAP_INTERLEAVE_NONE,
      CU_TENSOR_MAP_SWIZZLE_128B, CU_TENSOR_MAP_L2_PROMOTION_L2_128B, CU_TENSOR_MAP_FLOAT_OOB_FILL_NONE);
}
static void make_map3(EncodeFn enc, CUtensorMap* m, void* ptr, uint64_t d0, uint64_t cols, uint64_t rows, uint64_t blk_stride,
                      uint64_t nblocks, uint32_t nblk, uint32_t box_rows = 64) {
  cuuint64_t dims[3] = {d0, rows, nblocks};
  cuuint64_t strides[2] = {cols * 2, blk_stride * 2};
  cuuint32_t box[3] = {64, box_rows, nblk};
  cuuint32_t es[3] = {1, 1, 1};
  enc(m, CU_TENSOR_MAP_DATA_TYPE_BFLOAT16, 3, ptr, dims, strides, box, es, CU_TENSOR_MAP_INTERLEAVE_NONE,
      CU_TENSOR_MAP_SWIZZLE_128B, CU_TENSOR_MAP_L2_PROMOTION_L2_128B, CU_TENSOR_MAP_FLOAT_OOB_FILL_NONE);
}

extern "C" void kernel_launch(void* const* d_in, const int* in_sizes, int n_in, void* d_out, int out_size) {
  static Params prm;
  static void* cached[13] = {nullptr};
  static bool attr_done = false;
  bool same = attr_done && cached[12] == d_out;
  for (int i = 0; i < 12 && same; i++) same = cached[i] == d_in[i];
  if (!same) {
    void* fn = nullptr;
    cudaDriverEntryPointQueryResult qr;
    cudaGetDriverEntryPoint("cuTensorMapEncodeTiled", &fn, cudaEnableDefault, &qr);
    EncodeFn enc = (EncodeFn)fn;
    void *pO, *pXT;
    cudaGetSymbolAddress(&pO, g_O);
    cudaGetSymbolAddress(&pXT, g_xT);
    make_map(enc, &prm.mapO, pO, DM, LSEQ, 16);
    make_map(enc, &prm.mapXT, pXT, LSEQ, 4 * DM, 64);
    prm.out = (bf16*)d_out;
    make_map(enc, &prm.mapX128, d_in[0], 2 * DM, LSEQ / 2, 128);
    make_map(enc, &prm.mapWo128, d_in[2], DM, DM, 128);
    make_map(enc, &prm.mapO128, pO, DM, LSEQ, 128);
    make_map3(enc, &prm.mapW3, d_in[1], DM, 3 * DM, DM, DM, 3, 3);
    make_map3(enc, &prm.mapW3h, d_in[1], DM, 3 * DM, DM, DM, 3, 3, 32);
    make_map3(enc, &prm.mapXT3, pXT, 64, LSEQ, 4 * DM, 64, 32, 2);
    prm.a_re = (const bf16*)d_in[4]; prm.a_im = (const bf16*)d_in[5];
    prm.b_re = (const bf16*)d_in[6]; prm.b_im = (const bf16*)d_in[7];
    prm.c_re = (const bf16*)d_in[8]; prm.c_im = (const bf16*)d_in[9];
    prm.log_dt = (const bf16*)d_in[10]; prm.dskip = (const bf16*)d_in[11];
    cudaFuncSetAttribute(fused_kernel, cudaFuncAttributeMaxDynamicSharedMemorySize, SM_TOTAL);
    for (int i = 0; i < 12; i++) cached[i] = d_in[i];
    cached[12] = d_out;
    attr_done = true;
  }
  prm.stop = 100;
    fused_kernel<<<NCTA, NTHREADS, SM_TOTAL>>>(prm);
}
```

```cpp
#include <cuda_runtime.h>
#include <cuda_bf16.h>
#include <cuda.h>
#include <stdint.h>

typedef __nv_bfloat16 bf16;

constexpr int LSEQ = 2048;
constexpr int DM = 512;
constexpr int NCTA = 128;
constexpr int NTHREADS = 512;
#define RR 0
#define KG_PRE 2
#define WO_E0 4
#define WO_E1 2
#define FILL_AT 6
#define EXP_LATE 1
#define RFENCE 1
#define D_FIN 500
#define D_PREP 600
#define D_PST 100
#define D_HALO 500
#define STAG0 2
#define STAG1 2
#define D_ST 500
#define TLAYER 1
#define KG_PD 1
#define SUM_F32 0
#define CS_LATE0 0
#define D_HALO1 0
#define KG_START 0
#define S_AHEAD0 1
#define S_AHEAD1 2
#define PAUSE 80
#define PARK_FIRST 0
#define P_UNROLL_N 1
constexpr int P_UNROLL = P_UNROLL_N;
#define PUB 1
#define X_ORDER 1
#define CS_STEP 1
#define D_FIN2 400
#define FIN_D0 2
#define QD_AT 1
#define FIN4 2
#define D_Q 700
#define XV_AT B_GB
#define S1_AT 1
#define SAFE 0
#define O_CHECK 2
#define O_WAIT 1
#define X_SENT 2
#define FILL_N 1
#define W_STG 0
#define G_WAIT 2
#define HALO_W14 1
#define D_START 200
#define D_CS 400
#define D_ST0 500
#define KG_LAST 0
#define X_JIT 0
#define KG_GATE 2
#define R_CONS 192
#define R_HELP 88

constexpr int SM_X = 0;
constexpr int SM_W = 131072;
constexpr int SM_KVX = SM_X;
constexpr int SM_WO = SM_X + 16384;
constexpr int SM_OST = SM_W + 49152;
__host__ __device__ constexpr int sm_o(int c) { return c < 7 ? SM_X + (5 + c) * 16384 : SM_KVX; }
constexpr int SM_R = 196608;
constexpr int SM_T = 212992;
constexpr int SM_KC = 217088;
constexpr int KC_STRIDE = 648;
constexpr int SM_CS = SM_KC + 4 * KC_STRIDE * 2;
constexpr int SM_CW = SM_R + 8192;
constexpr int SM_EP = SM_CS + 768;
constexpr int SM_BAR = SM_EP + 16;
constexpr int SM_T2 = SM_BAR + 896;
constexpr int SM_HALO = SM_T2 + 4096;
constexpr int SM_ST = SM_HALO + 3072;
constexpr int SM_TOTAL = SM_HALO + 4096;
static_assert(SM_TOTAL <= 232448, "shared memory");

constexpr int CV_UH = 140 * 16;
constexpr int CV_PECH = 1120 * 4;
constexpr int CV_PBW = 2112 * 2;
__host__ __device__ constexpr int cv_s(int lc) { return SM_X + lc * 32768; }
__host__ __device__ constexpr int cv_u(int lc) { return cv_s(lc) + 4096; }
__host__ __device__ constexpr int cv_pe(int lc) { return cv_u(lc) + 2 * CV_UH; }
__host__ __device__ constexpr int cv_pb(int lc) { return cv_pe(lc) + CV_PECH; }
__host__ __device__ constexpr int cv_ft(int lc) { return cv_pb(lc) + 4 * CV_PBW; }
static_assert(cv_ft(0) + 1024 <= 32768, "conv buffers");
__host__ __device__ constexpr int cv_chan(int cta, int lc) { return cta + 128 * lc; }

enum {
  B_XF = 0,
  B_KVF = 8,
  B_OF = 16,
  B_WOF = 24,
  B_T = 31,
  B_RF = 28,
  B_RE = 29,
  B_CW = 30,
  B_GB = 35,
  B_EP = 36,
  B_ZF = 37,
  B_XV = 39,
  B_RT = 26,
  B_XV2 = 25,
  B_SD = 38,
  B_KVE = 40,
  B_SG = 45,
  B_QDONE = 47,
  B_PDONE = 48,
  B_S = 50,
  B_E = 54,
  B_P = 58,
  B_PE = 62,
  B_STF = 63,
  B_CSF = 64,
  B_HF = 65,
  B_U = 70,
  B_OST = 76,
  B_AD = 75,
  B_PS = 74,
  B_COUNT = 80
};

enum {
  C_CS = 0,
  C_G1 = 2,
  C_O = 4,
  C_COUNT = 20
};

__device__ __align__(128) unsigned g_cnt[C_COUNT * 32];
__device__ __align__(1024) bf16 g_O[LSEQ * DM];
__device__ __align__(1024) bf16 g_xT[4 * DM * LSEQ];
__device__ __align__(1024) uint32_t g_stats[2 * LSEQ];
__device__ __align__(1024) uint4 g_colsum[8 * 16 * 48];
__device__ __align__(1024) uint4 g_halo[16 * 8 * 192];
__device__ __align__(1024) uint2 g_part[16 * 8 * 128];
#define TS(i) do { } while (0)

#define ATS(i, th) do { } while (0)
#define KTS(i) do { if (ht == 0) TS(i); } while (0)
#define FTS(i) do { } while (0)
#define LTS(i) do { } while (0)

#define STOP 100

struct Params {
  CUtensorMap mapO, mapO64, mapX128, mapWo128, mapO128, mapW3, mapW3h, mapXT3;
  const bf16 *a_re, *a_im, *b_re, *b_im, *c_re, *c_im, *log_dt, *dskip;
  bf16* out;
  int stop;
};

__device__ __forceinline__ uint32_t s32(const void* p) { return (uint32_t)__cvta_generic_to_shared(p); }
__device__ __forceinline__ void mbar_init(uint32_t b, int c) { asm volatile("mbarrier.init.shared::cta.b64 [%0], %1;" ::"r"(b), "r"(c) : "memory"); }
__device__ __forceinline__ void mbar_expect(uint32_t b, int bytes) { asm volatile("mbarrier.arrive.expect_tx.shared::cta.b64 _, [%0], %1;" ::"r"(b), "r"(bytes) : "memory"); }
__device__ __forceinline__ void mbar_arrive(uint32_t b) { asm volatile("mbarrier.arrive.shared::cta.b64 _, [%0];" ::"r"(b) : "memory"); }
__device__ __forceinline__ void mbar_arrive_if(uint32_t b, bool c) {
  asm volatile("{\n.reg .pred p;\nsetp.ne.u32 p, %1, 0;\n@p mbarrier.arrive.shared::cta.b64 _, [%0];\n}" ::"r"(b), "r"((uint32_t)c) : "memory");
}
__device__ __forceinline__ void mbar_wait(uint32_t b, int parity) {
  asm volatile("{\n.reg .pred p;\nWAIT_LOOP:\nmbarrier.try_wait.parity.shared::cta.b64 p, [%0], %1;\n@p bra WAIT_DONE;\nbra WAIT_LOOP;\nWAIT_DONE:\n}" ::"r"(b), "r"(parity) : "memory");
}
template <int N> __device__ __forceinline__ void delay() {
  if constexpr (N > 0) {
    uint32_t t0, t;
    asm volatile("mov.u32 %0, %%clock;" : "=r"(t0));
    do { asm volatile("mov.u32 %0, %%clock;" : "=r"(t)); } while (t - t0 < N);
  }
}
#define SF 3
template <int ID> __device__ __forceinline__ void sched_fence() {
  if constexpr ((SF >> ID) & 1)
    asm volatile("{\n.reg .pred p;\n.reg .u32 t;\nsetp.eq.u32 p, %0, 0;\n@p mov.u32 t, %%clock;\n@p st.shared.u32 [%0], t;\n}" ::"r"(gridDim.x) : "memory");
}
#define KEEP 0xf
template <int ID> __device__ __forceinline__ void tensor_keepalive() {
  if constexpr ((KEEP >> ID) & 1)
    asm volatile("{\n.reg .pred p;\n.reg .f32 a, b, c, d, z;\nmov.f32 z, 0f00000000;\nsetp.eq.u32 p, %0, 0;\n"
                 "mma.sync.aligned.m16n8k8.row.col.f32.bf16.bf16.f32 {a,b,c,d}, {%0,%0}, {%0}, {z,z,z,z};\n@p st.shared.f32 [%0], a;\n}" ::"r"(gridDim.x) : "memory");
}
__device__ __forceinline__ int opaque_tid() { int v; asm volatile("mov.u32 %0, %%tid.x;" : "=r"(v)); return v; }
__device__ __forceinline__ bool elect_one() {
  uint32_t r;
  asm volatile("{\n.reg .pred p;\nelect.sync _|p, 0xffffffff;\nselp.u32 %0, 1, 0, p;\n}" : "=r"(r));
  return r != 0;
}
__device__ __forceinline__ void tma_ld(uint32_t dst, const CUtensorMap* m, int c0, int c1, uint32_t bar) {
  asm volatile("cp.async.bulk.tensor.2d.shared::cluster.global.mbarrier::complete_tx::bytes [%0], [%1, {%3, %4}], [%2];"
               ::"r"(dst), "l"(m), "r"(bar), "r"(c0), "r"(c1) : "memory");
}
__device__ __forceinline__ void tma_ld3(uint32_t dst, const CUtensorMap* m, int c0, int c1, int c2, uint32_t bar) {
  asm volatile("cp.async.bulk.tensor.3d.shared::cluster.global.mbarrier::complete_tx::bytes [%0], [%1, {%3, %4, %5}], [%2];"
               ::"r"(dst), "l"(m), "r"(bar), "r"(c0), "r"(c1), "r"(c2) : "memory");
}
__device__ __forceinline__ void tma_prefetch2(const CUtensorMap* m, int c0, int c1) {
  asm volatile("cp.async.bulk.prefetch.tensor.2d.L2.global.tile [%0, {%1, %2}];" ::"l"(m), "r"(c0), "r"(c1) : "memory");
}
__device__ __forceinline__ void tma_prefetch3(const CUtensorMap* m, int c0, int c1, int c2) {
  asm volatile("cp.async.bulk.prefetch.tensor.3d.L2.global.tile [%0, {%1, %2, %3}];" ::"l"(m), "r"(c0), "r"(c1), "r"(c2) : "memory");
}
__device__ __forceinline__ void tma_st(const CUtensorMap* m, int c0, int c1, uint32_t src) {
  asm volatile("cp.async.bulk.tensor.2d.global.shared::cta.bulk_group [%0, {%2, %3}], [%1];" ::"l"(m), "r"(src), "r"(c0), "r"(c1) : "memory");
}
__device__ __forceinline__ void bulk_ld(uint32_t dst, const void* src, int bytes, uint32_t bar) {
  asm volatile("cp.async.bulk.shared::cluster.global.mbarrier::complete_tx::bytes [%0], [%1], %2, [%3];" ::"r"(dst), "l"(src), "r"(bytes), "r"(bar) : "memory");
}
__device__ __forceinline__ void bulk_st(void* dst, uint32_t src, int bytes) {
  asm volatile("cp.async.bulk.global.shared::cta.bulk_group [%0], [%1], %2;" ::"l"(dst), "r"(src), "r"(bytes) : "memory");
}
__device__ __forceinline__ void bulk_red_add_f32(void* dst, uint32_t src, int bytes) {
  asm volatile("cp.reduce.async.bulk.global.shared::cta.bulk_group.add.f32 [%0], [%1], %2;" ::"l"(dst), "r"(src), "r"(bytes) : "memory");
}
__device__ __forceinline__ void bulk_commit() { asm volatile("cp.async.bulk.commit_group;" ::: "memory"); }
__device__ __forceinline__ void bulk_wait_all() { asm volatile("cp.async.bulk.wait_group 0;" ::: "memory"); }
__device__ __forceinline__ void fence_async_smem() { asm volatile("fence.proxy.async.shared::cta;" ::: "memory"); }
__device__ __forceinline__ void fence_writer() { if (!RFENCE) fence_async_smem(); }
__device__ __forceinline__ void fence_reader() { if (RFENCE) fence_async_smem(); }
__device__ __forceinline__ void fence_async_global() { asm volatile("fence.proxy.async.global;" ::: "memory"); }
template <int ID> __device__ __forceinline__ void release_bulk() {
  if constexpr ((SAFE >> ID) & 1) { fence_async_global(); asm volatile("fence.acq_rel.gpu;" ::: "memory"); }
}
__device__ __forceinline__ void bar_sync(int id, int n) { asm volatile("bar.sync %0, %1;" ::"r"(id), "r"(n) : "memory"); }
__device__ __forceinline__ void bar_arrive(int id, int n) { asm volatile("bar.arrive %0, %1;" ::"r"(id), "r"(n) : "memory"); }
__device__ __forceinline__ void wg_fence() { asm volatile("wgmma.fence.sync.aligned;" ::: "memory"); }
__device__ __forceinline__ void wg_commit() { asm volatile("wgmma.commit_group.sync.aligned;" ::: "memory"); }
template <int N> __device__ __forceinline__ void wg_wait() { asm volatile("wgmma.wait_group.sync.aligned %0;" ::"n"(N) : "memory"); }
__device__ __forceinline__ uint64_t mkdesc(uint32_t addr, uint32_t lbo, uint32_t sbo, int sw) {
  return (uint64_t)((addr & 0x3FFFF) >> 4) | ((uint64_t)(lbo >> 4) << 16) | ((uint64_t)(sbo >> 4) << 32) | ((uint64_t)sw << 62);
}
__device__ __forceinline__ void ldsm4(uint32_t* r, uint32_t a) {
  asm volatile("ldmatrix.sync.aligned.m8n8.x4.shared.b16 {%0,%1,%2,%3}, [%4];" : "=r"(r[0]), "=r"(r[1]), "=r"(r[2]), "=r"(r[3]) : "r"(a) : "memory");
}
__device__ __forceinline__ void ldsm4t(uint32_t* r, uint32_t a) {
  asm volatile("ldmatrix.sync.aligned.m8n8.x4.trans.shared.b16 {%0,%1,%2,%3}, [%4];" : "=r"(r[0]), "=r"(r[1]), "=r"(r[2]), "=r"(r[3]) : "r"(a) : "memory");
}
__device__ __forceinline__ void stsm4(uint32_t a, uint32_t r0, uint32_t r1, uint32_t r2, uint32_t r3) {
  asm volatile("stmatrix.sync.aligned.m8n8.x4.shared.b16 [%0], {%1,%2,%3,%4};" ::"r"(a), "r"(r0), "r"(r1), "r"(r2), "r"(r3) : "memory");
}
__device__ __forceinline__ void stsm4t(uint32_t a, uint32_t r0, uint32_t r1, uint32_t r2, uint32_t r3) {
  asm volatile("stmatrix.sync.aligned.m8n8.x4.trans.shared.b16 [%0], {%1,%2,%3,%4};" ::"r"(a), "r"(r0), "r"(r1), "r"(r2), "r"(r3) : "memory");
}
__device__ __forceinline__ uint32_t movm_t(uint32_t a) { uint32_t r; asm volatile("movmatrix.sync.aligned.m8n8.trans.b16 %0, %1;" : "=r"(r) : "r"(a)); return r; }
__device__ __forceinline__ uint32_t lds32(uint32_t a) { uint32_t v; asm volatile("ld.shared.b32 %0, [%1];" : "=r"(v) : "r"(a) : "memory"); return v; }
__device__ __forceinline__ float2 lds64f(uint32_t a) { float2 v; asm volatile("ld.shared.v2.f32 {%0,%1}, [%2];" : "=f"(v.x), "=f"(v.y) : "r"(a) : "memory"); return v; }
__device__ __forceinline__ float4 lds128f(uint32_t a) { float4 v; asm volatile("ld.shared.v4.f32 {%0,%1,%2,%3}, [%4];" : "=f"(v.x), "=f"(v.y), "=f"(v.z), "=f"(v.w) : "r"(a) : "memory"); return v; }
__device__ __forceinline__ uint4 lds128(uint32_t a) { uint4 v; asm volatile("ld.shared.v4.b32 {%0,%1,%2,%3}, [%4];" : "=r"(v.x), "=r"(v.y), "=r"(v.z), "=r"(v.w) : "r"(a) : "memory"); return v; }
__device__ __forceinline__ void sts128(uint32_t a, uint4 v) { asm volatile("st.shared.v4.b32 [%0], {%1,%2,%3,%4};" ::"r"(a), "r"(v.x), "r"(v.y), "r"(v.z), "r"(v.w) : "memory"); }
__device__ __forceinline__ void sts128f(uint32_t a, float x, float y, float z, float w) { asm volatile("st.shared.v4.f32 [%0], {%1,%2,%3,%4};" ::"r"(a), "f"(x), "f"(y), "f"(z), "f"(w) : "memory"); }
__device__ __forceinline__ void sts32f(uint32_t a, float v) { asm volatile("st.shared.f32 [%0], %1;" ::"r"(a), "f"(v) : "memory"); }
__device__ __forceinline__ void sts16(uint32_t a, uint16_t v) { asm volatile("st.shared.u16 [%0], %1;" ::"r"(a), "h"(v) : "memory"); }
__device__ __forceinline__ uint32_t lds16(uint32_t a) { uint16_t v; asm volatile("ld.shared.u16 %0, [%1];" : "=h"(v) : "r"(a) : "memory"); return v; }
__device__ __forceinline__ uint32_t packbf(float lo, float hi) { uint32_t r; asm("cvt.rn.bf16x2.f32 %0, %1, %2;" : "=r"(r) : "f"(hi), "f"(lo)); return r; }
__device__ __forceinline__ float bf_lo(uint32_t v) { return __uint_as_float(v << 16); }
__device__ __forceinline__ float bf_hi(uint32_t v) { return __uint_as_float(v & 0xffff0000u); }
__device__ __forceinline__ float ex2(float x) { float r; asm("ex2.approx.ftz.f32 %0, %1;" : "=f"(r) : "f"(x)); return r; }
__device__ __forceinline__ float rsqrt_approx(float x) { float r; asm("rsqrt.approx.ftz.f32 %0, %1;" : "=f"(r) : "f"(x)); return r; }
__device__ __forceinline__ float rcp_approx(float x) { float r; asm("rcp.approx.ftz.f32 %0, %1;" : "=f"(r) : "f"(x)); return r; }
__device__ __forceinline__ void mma_bf16(float* d, const uint32_t* a, uint32_t b0, uint32_t b1) {
  asm("mma.sync.aligned.m16n8k16.row.col.f32.bf16.bf16.f32 {%0,%1,%2,%3}, {%4,%5,%6,%7}, {%8,%9}, {%0,%1,%2,%3};"
               : "+f"(d[0]), "+f"(d[1]), "+f"(d[2]), "+f"(d[3]) : "r"(a[0]), "r"(a[1]), "r"(a[2]), "r"(a[3]), "r"(b0), "r"(b1));
}
__device__ __forceinline__ void mma_bf16_k8(float* d, uint32_t a0, uint32_t a1, uint32_t b) {
  asm("mma.sync.aligned.m16n8k8.row.col.f32.bf16.bf16.f32 {%0,%1,%2,%3}, {%4,%5}, {%6}, {%0,%1,%2,%3};"
      : "+f"(d[0]), "+f"(d[1]), "+f"(d[2]), "+f"(d[3]) : "r"(a0), "r"(a1), "r"(b));
}
__device__ __forceinline__ void red_release(unsigned* p) { asm volatile("red.release.gpu.global.add.u32 [%0], 1;" ::"l"(p) : "memory"); }
__device__ __forceinline__ void red_relaxed(unsigned* p) { asm volatile("red.relaxed.gpu.global.add.u32 [%0], 1;" ::"l"(p) : "memory"); }
__device__ __forceinline__ unsigned ld_relaxed(const unsigned* p) { unsigned v; asm volatile("ld.relaxed.gpu.global.u32 %0, [%1];" : "=r"(v) : "l"(p) : "memory"); return v; }
__device__ __forceinline__ void spin_until(const unsigned* p, unsigned target) {
  int it = 0;
  while ((int)(ld_relaxed(p) - target) < 0) {
    if (++it > (1 << 23)) __trap();
  }
}
__device__ __forceinline__ uint4 ldcg128(const void* p) { uint4 v; asm volatile("ld.global.cg.v4.b32 {%0,%1,%2,%3}, [%4];" : "=r"(v.x), "=r"(v.y), "=r"(v.z), "=r"(v.w) : "l"(p) : "memory"); return v; }
__device__ __forceinline__ uint4 ld_tagged(const uint4* p) { uint4 v; asm volatile("ld.relaxed.gpu.global.v4.u32 {%0,%1,%2,%3}, [%4];" : "=r"(v.x), "=r"(v.y), "=r"(v.z), "=r"(v.w) : "l"(p) : "memory"); return v; }
__device__ __forceinline__ uint2 ld_part(const uint2* p) { uint2 v; asm volatile("ld.relaxed.gpu.global.v2.u32 {%0,%1}, [%2];" : "=r"(v.x), "=r"(v.y) : "l"(p) : "memory"); return v; }
__device__ __forceinline__ void st_part(uint2* p, float s, float q, uint32_t tag) {
  if (PUB & 2) asm volatile("{\n.reg .b64 v, o;\nmov.b64 v, {%1,%2};\natom.relaxed.gpu.global.exch.b64 o, [%0], v;\n}" ::"l"(p), "r"(__float_as_uint(s)), "r"((__float_as_uint(q) & ~7u) | tag) : "memory");
  else asm volatile("st.relaxed.gpu.global.v2.u32 [%0], {%1,%2};" ::"l"(p), "r"(__float_as_uint(s)), "r"((__float_as_uint(q) & ~7u) | tag) : "memory");
}
__device__ __forceinline__ uint32_t part_tag(uint32_t epoch, int k) { return (4 * (epoch % 7) + k) % 7 + 1; }
__device__ __forceinline__ void st_tagged3(uint4* p, uint32_t a, uint32_t b, uint32_t c, uint32_t tag) { asm volatile("st.relaxed.gpu.global.v4.u32 [%0], {%1,%2,%3,%4};" ::"l"(p), "r"(a), "r"(b), "r"(c), "r"(tag) : "memory"); }
__device__ __forceinline__ uint32_t hadd2(uint32_t a, uint32_t b) { uint32_t r; asm("add.rn.bf16x2 %0, %1, %2;" : "=r"(r) : "r"(a), "r"(b)); return r; }
__device__ __forceinline__ uint32_t hfma2(uint32_t a, uint32_t b, uint32_t c) { uint32_t r; asm("fma.rn.bf16x2 %0, %1, %2, %3;" : "=r"(r) : "r"(a), "r"(b), "r"(c)); return r; }
__device__ __forceinline__ uint32_t hmul2(uint32_t a, uint32_t b) { uint32_t r; asm("mul.rn.bf16x2 %0, %1, %2;" : "=r"(r) : "r"(a), "r"(b)); return r; }

template<int N,int TB> __device__ __forceinline__ void wgmma_rs(float* d, const uint32_t* a, uint64_t db, int sd);
template<int N,int TA,int TB> __device__ __forceinline__ void wgmma_ss(float* d, uint64_t da, uint64_t db, int sd);
template<> __device__ __forceinline__ void wgmma_rs<128,0>(float* d, const uint32_t* a, uint64_t db, int sd) {
  asm volatile("{\n.reg .pred p;\nsetp.ne.b32 p, %69, 0;\nwgmma.mma_async.sync.aligned.m64n128k16.f32.bf16.bf16 {%0,%1,%2,%3,%4,%5,%6,%7,%8,%9,%10,%11,%12,%13,%14,%15,%16,%17,%18,%19,%20,%21,%22,%23,%24,%25,%26,%27,%28,%29,%30,%31,%32,%33,%34,%35,%36,%37,%38,%39,%40,%41,%42,%43,%44,%45,%46,%47,%48,%49,%50,%51,%52,%53,%54,%55,%56,%57,%58,%59,%60,%61,%62,%63}, {%64,%65,%66,%67}, %68, p, 1, 1, 0;\n}\n"
   : "+f"(d[0]),"+f"(d[1]),"+f"(d[2]),"+f"(d[3]),"+f"(d[4]),"+f"(d[5]),"+f"(d[6]),"+f"(d[7]),"+f"(d[8]),"+f"(d[9]),"+f"(d[10]),"+f"(d[11]),"+f"(d[12]),"+f"(d[13]),"+f"(d[14]),"+f"(d[15]),"+f"(d[16]),"+f"(d[17]),"+f"(d[18]),"+f"(d[19]),"+f"(d[20]),"+f"(d[21]),"+f"(d[22]),"+f"(d[23]),"+f"(d[24]),"+f"(d[25]),"+f"(d[26]),"+f"(d[27]),"+f"(d[28]),"+f"(d[29]),"+f"(d[30]),"+f"(d[31]),"+f"(d[32]),"+f"(d[33]),"+f"(d[34]),"+f"(d[35]),"+f"(d[36]),"+f"(d[37]),"+f"(d[38]),"+f"(d[39]),"+f"(d[40]),"+f"(d[41]),"+f"(d[42]),"+f"(d[43]),"+f"(d[44]),"+f"(d[45]),"+f"(d[46]),"+f"(d[47]),"+f"(d[48]),"+f"(d[49]),"+f"(d[50]),"+f"(d[51]),"+f"(d[52]),"+f"(d[53]),"+f"(d[54]),"+f"(d[55]),"+f"(d[56]),"+f"(d[57]),"+f"(d[58]),"+f"(d[59]),"+f"(d[60]),"+f"(d[61]),"+f"(d[62]),"+f"(d[63])
   : "r"(a[0]), "r"(a[1]), "r"(a[2]), "r"(a[3]), "l"(db), "r"(sd));
}
template<> __device__ __forceinline__ void wgmma_rs<120,0>(float* d, const uint32_t* a, uint64_t db, int sd) {
  asm volatile("{\n.reg .pred p;\nsetp.ne.b32 p, %65, 0;\nwgmma.mma_async.sync.aligned.m64n120k16.f32.bf16.bf16 {%0,%1,%2,%3,%4,%5,%6,%7,%8,%9,%10,%11,%12,%13,%14,%15,%16,%17,%18,%19,%20,%21,%22,%23,%24,%25,%26,%27,%28,%29,%30,%31,%32,%33,%34,%35,%36,%37,%38,%39,%40,%41,%42,%43,%44,%45,%46,%47,%48,%49,%50,%51,%52,%53,%54,%55,%56,%57,%58,%59}, {%60,%61,%62,%63}, %64, p, 1, 1, 0;\n}\n"
   : "+f"(d[0]),"+f"(d[1]),"+f"(d[2]),"+f"(d[3]),"+f"(d[4]),"+f"(d[5]),"+f"(d[6]),"+f"(d[7]),"+f"(d[8]),"+f"(d[9]),"+f"(d[10]),"+f"(d[11]),"+f"(d[12]),"+f"(d[13]),"+f"(d[14]),"+f"(d[15]),"+f"(d[16]),"+f"(d[17]),"+f"(d[18]),"+f"(d[19]),"+f"(d[20]),"+f"(d[21]),"+f"(d[22]),"+f"(d[23]),"+f"(d[24]),"+f"(d[25]),"+f"(d[26]),"+f"(d[27]),"+f"(d[28]),"+f"(d[29]),"+f"(d[30]),"+f"(d[31]),"+f"(d[32]),"+f"(d[33]),"+f"(d[34]),"+f"(d[35]),"+f"(d[36]),"+f"(d[37]),"+f"(d[38]),"+f"(d[39]),"+f"(d[40]),"+f"(d[41]),"+f"(d[42]),"+f"(d[43]),"+f"(d[44]),"+f"(d[45]),"+f"(d[46]),"+f"(d[47]),"+f"(d[48]),"+f"(d[49]),"+f"(d[50]),"+f"(d[51]),"+f"(d[52]),"+f"(d[53]),"+f"(d[54]),"+f"(d[55]),"+f"(d[56]),"+f"(d[57]),"+f"(d[58]),"+f"(d[59])
   : "r"(a[0]), "r"(a[1]), "r"(a[2]), "r"(a[3]), "l"(db), "r"(sd));
}
template<> __device__ __forceinline__ void wgmma_rs<112,0>(float* d, const uint32_t* a, uint64_t db, int sd) {
  asm volatile("{\n.reg .pred p;\nsetp.ne.b32 p, %61, 0;\nwgmma.mma_async.sync.aligned.m64n112k16.f32.bf16.bf16 {%0,%1,%2,%3,%4,%5,%6,%7,%8,%9,%10,%11,%12,%13,%14,%15,%16,%17,%18,%19,%20,%21,%22,%23,%24,%25,%26,%27,%28,%29,%30,%31,%32,%33,%34,%35,%36,%37,%38,%39,%40,%41,%42,%43,%44,%45,%46,%47,%48,%49,%50,%51,%52,%53,%54,%55}, {%56,%57,%58,%59}, %60, p, 1, 1, 0;\n}\n"
   : "+f"(d[0]),"+f"(d[1]),"+f"(d[2]),"+f"(d[3]),"+f"(d[4]),"+f"(d[5]),"+f"(d[6]),"+f"(d[7]),"+f"(d[8]),"+f"(d[9]),"+f"(d[10]),"+f"(d[11]),"+f"(d[12]),"+f"(d[13]),"+f"(d[14]),"+f"(d[15]),"+f"(d[16]),"+f"(d[17]),"+f"(d[18]),"+f"(d[19]),"+f"(d[20]),"+f"(d[21]),"+f"(d[22]),"+f"(d[23]),"+f"(d[24]),"+f"(d[25]),"+f"(d[26]),"+f"(d[27]),"+f"(d[28]),"+f"(d[29]),"+f"(d[30]),"+f"(d[31]),"+f"(d[32]),"+f"(d[33]),"+f"(d[34]),"+f"(d[35]),"+f"(d[36]),"+f"(d[37]),"+f"(d[38]),"+f"(d[39]),"+f"(d[40]),"+f"(d[41]),"+f"(d[42]),"+f"(d[43]),"+f"(d[44]),"+f"(d[45]),"+f"(d[46]),"+f"(d[47]),"+f"(d[48]),"+f"(d[49]),"+f"(d[50]),"+f"(d[51]),"+f"(d[52]),"+f"(d[53]),"+f"(d[54]),"+f"(d[55])
   : "r"(a[0]), "r"(a[1]), "r"(a[2]), "r"(a[3]), "l"(db), "r"(sd));
}
template<> __device__ __forceinline__ void wgmma_rs<104,0>(float* d, const uint32_t* a, uint64_t db, int sd) {
  asm volatile("{\n.reg .pred p;\nsetp.ne.b32 p, %57, 0;\nwgmma.mma_async.sync.aligned.m64n104k16.f32.bf16.bf16 {%0,%1,%2,%3,%4,%5,%6,%7,%8,%9,%10,%11,%12,%13,%14,%15,%16,%17,%18,%19,%20,%21,%22,%23,%24,%25,%26,%27,%28,%29,%30,%31,%32,%33,%34,%35,%36,%37,%38,%39,%40,%41,%42,%43,%44,%45,%46,%47,%48,%49,%50,%51}, {%52,%53,%54,%55}, %56, p, 1, 1, 0;\n}\n"
   : "+f"(d[0]),"+f"(d[1]),"+f"(d[2]),"+f"(d[3]),"+f"(d[4]),"+f"(d[5]),"+f"(d[6]),"+f"(d[7]),"+f"(d[8]),"+f"(d[9]),"+f"(d[10]),"+f"(d[11]),"+f"(d[12]),"+f"(d[13]),"+f"(d[14]),"+f"(d[15]),"+f"(d[16]),"+f"(d[17]),"+f"(d[18]),"+f"(d[19]),"+f"(d[20]),"+f"(d[21]),"+f"(d[22]),"+f"(d[23]),"+f"(d[24]),"+f"(d[25]),"+f"(d[26]),"+f"(d[27]),"+f"(d[28]),"+f"(d[29]),"+f"(d[30]),"+f"(d[31]),"+f"(d[32]),"+f"(d[33]),"+f"(d[34]),"+f"(d[35]),"+f"(d[36]),"+f"(d[37]),"+f"(d[38]),"+f"(d[39]),"+f"(d[40]),"+f"(d[41]),"+f"(d[42]),"+f"(d[43]),"+f"(d[44]),"+f"(d[45]),"+f"(d[46]),"+f"(d[47]),"+f"(d[48]),"+f"(d[49]),"+f"(d[50]),"+f"(d[51])
   : "r"(a[0]), "r"(a[1]), "r"(a[2]), "r"(a[3]), "l"(db), "r"(sd));
}
template<> __device__ __forceinline__ void wgmma_rs<96,0>(float* d, const uint32_t* a, uint64_t db, int sd) {
  asm volatile("{\n.reg .pred p;\nsetp.ne.b32 p, %53, 0;\nwgmma.mma_async.sync.aligned.m64n96k16.f32.bf16.bf16 {%0,%1,%2,%3,%4,%5,%6,%7,%8,%9,%10,%11,%12,%13,%14,%15,%16,%17,%18,%19,%20,%21,%22,%23,%24,%25,%26,%27,%28,%29,%30,%31,%32,%33,%34,%35,%36,%37,%38,%39,%40,%41,%42,%43,%44,%45,%46,%47}, {%48,%49,%50,%51}, %52, p, 1, 1, 0;\n}\n"
   : "+f"(d[0]),"+f"(d[1]),"+f"(d[2]),"+f"(d[3]),"+f"(d[4]),"+f"(d[5]),"+f"(d[6]),"+f"(d[7]),"+f"(d[8]),"+f"(d[9]),"+f"(d[10]),"+f"(d[11]),"+f"(d[12]),"+f"(d[13]),"+f"(d[14]),"+f"(d[15]),"+f"(d[16]),"+f"(d[17]),"+f"(d[18]),"+f"(d[19]),"+f"(d[20]),"+f"(d[21]),"+f"(d[22]),"+f"(d[23]),"+f"(d[24]),"+f"(d[25]),"+f"(d[26]),"+f"(d[27]),"+f"(d[28]),"+f"(d[29]),"+f"(d[30]),"+f"(d[31]),"+f"(d[32]),"+f"(d[33]),"+f"(d[34]),"+f"(d[35]),"+f"(d[36]),"+f"(d[37]),"+f"(d[38]),"+f"(d[39]),"+f"(d[40]),"+f"(d[41]),"+f"(d[42]),"+f"(d[43]),"+f"(d[44]),"+f"(d[45]),"+f"(d[46]),"+f"(d[47])
   : "r"(a[0]), "r"(a[1]), "r"(a[2]), "r"(a[3]), "l"(db), "r"(sd));
}
template<> __device__ __forceinline__ void wgmma_rs<88,0>(float* d, const uint32_t* a, uint64_t db, int sd) {
  asm volatile("{\n.reg .pred p;\nsetp.ne.b32 p, %49, 0;\nwgmma.mma_async.sync.aligned.m64n88k16.f32.bf16.bf16 {%0,%1,%2,%3,%4,%5,%6,%7,%8,%9,%10,%11,%12,%13,%14,%15,%16,%17,%18,%19,%20,%21,%22,%23,%24,%25,%26,%27,%28,%29,%30,%31,%32,%33,%34,%35,%36,%37,%38,%39,%40,%41,%42,%43}, {%44,%45,%46,%47}, %48, p, 1, 1, 0;\n}\n"
   : "+f"(d[0]),"+f"(d[1]),"+f"(d[2]),"+f"(d[3]),"+f"(d[4]),"+f"(d[5]),"+f"(d[6]),"+f"(d[7]),"+f"(d[8]),"+f"(d[9]),"+f"(d[10]),"+f"(d[11]),"+f"(d[12]),"+f"(d[13]),"+f"(d[14]),"+f"(d[15]),"+f"(d[16]),"+f"(d[17]),"+f"(d[18]),"+f"(d[19]),"+f"(d[20]),"+f"(d[21]),"+f"(d[22]),"+f"(d[23]),"+f"(d[24]),"+f"(d[25]),"+f"(d[26]),"+f"(d[27]),"+f"(d[28]),"+f"(d[29]),"+f"(d[30]),"+f"(d[31]),"+f"(d[32]),"+f"(d[33]),"+f"(d[34]),"+f"(d[35]),"+f"(d[36]),"+f"(d[37]),"+f"(d[38]),"+f"(d[39]),"+f"(d[40]),"+f"(d[41]),"+f"(d[42]),"+f"(d[43])
   : "r"(a[0]), "r"(a[1]), "r"(a[2]), "r"(a[3]), "l"(db), "r"(sd));
}
template<> __device__ __forceinline__ void wgmma_rs<80,0>(float* d, const uint32_t* a, uint64_t db, int sd) {
  asm volatile("{\n.reg .pred p;\nsetp.ne.b32 p, %45, 0;\nwgmma.mma_async.sync.aligned.m64n80k16.f32.bf16.bf16 {%0,%1,%2,%3,%4,%5,%6,%7,%8,%9,%10,%11,%12,%13,%14,%15,%16,%17,%18,%19,%20,%21,%22,%23,%24,%25,%26,%27,%28,%29,%30,%31,%32,%33,%34,%35,%36,%37,%38,%39}, {%40,%41,%42,%43}, %44, p, 1, 1, 0;\n}\n"
   : "+f"(d[0]),"+f"(d[1]),"+f"(d[2]),"+f"(d[3]),"+f"(d[4]),"+f"(d[5]),"+f"(d[6]),"+f"(d[7]),"+f"(d[8]),"+f"(d[9]),"+f"(d[10]),"+f"(d[11]),"+f"(d[12]),"+f"(d[13]),"+f"(d[14]),"+f"(d[15]),"+f"(d[16]),"+f"(d[17]),"+f"(d[18]),"+f"(d[19]),"+f"(d[20]),"+f"(d[21]),"+f"(d[22]),"+f"(d[23]),"+f"(d[24]),"+f"(d[25]),"+f"(d[26]),"+f"(d[27]),"+f"(d[28]),"+f"(d[29]),"+f"(d[30]),"+f"(d[31]),"+f"(d[32]),"+f"(d[33]),"+f"(d[34]),"+f"(d[35]),"+f"(d[36]),"+f"(d[37]),"+f"(d[38]),"+f"(d[39])
   : "r"(a[0]), "r"(a[1]), "r"(a[2]), "r"(a[3]), "l"(db), "r"(sd));
}
template<> __device__ __forceinline__ void wgmma_rs<72,0>(float* d, const uint32_t* a, uint64_t db, int sd) {
  asm volatile("{\n.reg .pred p;\nsetp.ne.b32 p, %41, 0;\nwgmma.mma_async.sync.aligned.m64n72k16.f32.bf16.bf16 {%0,%1,%2,%3,%4,%5,%6,%7,%8,%9,%10,%11,%12,%13,%14,%15,%16,%17,%18,%19,%20,%21,%22,%23,%24,%25,%26,%27,%28,%29,%30,%31,%32,%33,%34,%35}, {%36,%37,%38,%39}, %40, p, 1, 1, 0;\n}\n"
   : "+f"(d[0]),"+f"(d[1]),"+f"(d[2]),"+f"(d[3]),"+f"(d[4]),"+f"(d[5]),"+f"(d[6]),"+f"(d[7]),"+f"(d[8]),"+f"(d[9]),"+f"(d[10]),"+f"(d[11]),"+f"(d[12]),"+f"(d[13]),"+f"(d[14]),"+f"(d[15]),"+f"(d[16]),"+f"(d[17]),"+f"(d[18]),"+f"(d[19]),"+f"(d[20]),"+f"(d[21]),"+f"(d[22]),"+f"(d[23]),"+f"(d[24]),"+f"(d[25]),"+f"(d[26]),"+f"(d[27]),"+f"(d[28]),"+f"(d[29]),"+f"(d[30]),"+f"(d[31]),"+f"(d[32]),"+f"(d[33]),"+f"(d[34]),"+f"(d[35])
   : "r"(a[0]), "r"(a[1]), "r"(a[2]), "r"(a[3]), "l"(db), "r"(sd));
}
template<> __device__ __forceinline__ void wgmma_rs<64,0>(float* d, const uint32_t* a, uint64_t db, int sd) {
  asm volatile("{\n.reg .pred p;\nsetp.ne.b32 p, %37, 0;\nwgmma.mma_async.sync.aligned.m64n64k16.f32.bf16.bf16 {%0,%1,%2,%3,%4,%5,%6,%7,%8,%9,%10,%11,%12,%13,%14,%15,%16,%17,%18,%19,%20,%21,%22,%23,%24,%25,%26,%27,%28,%29,%30,%31}, {%32,%33,%34,%35}, %36, p, 1, 1, 0;\n}\n"
   : "+f"(d[0]),"+f"(d[1]),"+f"(d[2]),"+f"(d[3]),"+f"(d[4]),"+f"(d[5]),"+f"(d[6]),"+f"(d[7]),"+f"(d[8]),"+f"(d[9]),"+f"(d[10]),"+f"(d[11]),"+f"(d[12]),"+f"(d[13]),"+f"(d[14]),"+f"(d[15]),"+f"(d[16]),"+f"(d[17]),"+f"(d[18]),"+f"(d[19]),"+f"(d[20]),"+f"(d[21]),"+f"(d[22]),"+f"(d[23]),"+f"(d[24]),"+f"(d[25]),"+f"(d[26]),"+f"(d[27]),"+f"(d[28]),"+f"(d[29]),"+f"(d[30]),"+f"(d[31])
   : "r"(a[0]), "r"(a[1]), "r"(a[2]), "r"(a[3]), "l"(db), "r"(sd));
}
template<> __device__ __forceinline__ void wgmma_ss<64,0,1>(float* d, uint64_t da, uint64_t db, int sd) {
  asm volatile("{\n.reg .pred p;\nsetp.ne.b32 p, %34, 0;\nwgmma.mma_async.sync.aligned.m64n64k16.f32.bf16.bf16 {%0,%1,%2,%3,%4,%5,%6,%7,%8,%9,%10,%11,%12,%13,%14,%15,%16,%17,%18,%19,%20,%21,%22,%23,%24,%25,%26,%27,%28,%29,%30,%31}, %32, %33, p, 1, 1, 0, 1;\n}\n"
   : "+f"(d[0]),"+f"(d[1]),"+f"(d[2]),"+f"(d[3]),"+f"(d[4]),"+f"(d[5]),"+f"(d[6]),"+f"(d[7]),"+f"(d[8]),"+f"(d[9]),"+f"(d[10]),"+f"(d[11]),"+f"(d[12]),"+f"(d[13]),"+f"(d[14]),"+f"(d[15]),"+f"(d[16]),"+f"(d[17]),"+f"(d[18]),"+f"(d[19]),"+f"(d[20]),"+f"(d[21]),"+f"(d[22]),"+f"(d[23]),"+f"(d[24]),"+f"(d[25]),"+f"(d[26]),"+f"(d[27]),"+f"(d[28]),"+f"(d[29]),"+f"(d[30]),"+f"(d[31])
   : "l"(da), "l"(db), "r"(sd));
}
template<> __device__ __forceinline__ void wgmma_ss<64,1,1>(float* d, uint64_t da, uint64_t db, int sd) {
  asm volatile("{\n.reg .pred p;\nsetp.ne.b32 p, %34, 0;\nwgmma.mma_async.sync.aligned.m64n64k16.f32.bf16.bf16 {%0,%1,%2,%3,%4,%5,%6,%7,%8,%9,%10,%11,%12,%13,%14,%15,%16,%17,%18,%19,%20,%21,%22,%23,%24,%25,%26,%27,%28,%29,%30,%31}, %32, %33, p, 1, 1, 1, 1;\n}\n"
   : "+f"(d[0]),"+f"(d[1]),"+f"(d[2]),"+f"(d[3]),"+f"(d[4]),"+f"(d[5]),"+f"(d[6]),"+f"(d[7]),"+f"(d[8]),"+f"(d[9]),"+f"(d[10]),"+f"(d[11]),"+f"(d[12]),"+f"(d[13]),"+f"(d[14]),"+f"(d[15]),"+f"(d[16]),"+f"(d[17]),"+f"(d[18]),"+f"(d[19]),"+f"(d[20]),"+f"(d[21]),"+f"(d[22]),"+f"(d[23]),"+f"(d[24]),"+f"(d[25]),"+f"(d[26]),"+f"(d[27]),"+f"(d[28]),"+f"(d[29]),"+f"(d[30]),"+f"(d[31])
   : "l"(da), "l"(db), "r"(sd));
}
template<> __device__ __forceinline__ void wgmma_ss<192,0,1>(float* d, uint64_t da, uint64_t db, int sd) {
  asm volatile("{\n.reg .pred p;\nsetp.ne.b32 p, %98, 0;\nwgmma.mma_async.sync.aligned.m64n192k16.f32.bf16.bf16 {%0,%1,%2,%3,%4,%5,%6,%7,%8,%9,%10,%11,%12,%13,%14,%15,%16,%17,%18,%19,%20,%21,%22,%23,%24,%25,%26,%27,%28,%29,%30,%31,%32,%33,%34,%35,%36,%37,%38,%39,%40,%41,%42,%43,%44,%45,%46,%47,%48,%49,%50,%51,%52,%53,%54,%55,%56,%57,%58,%59,%60,%61,%62,%63,%64,%65,%66,%67,%68,%69,%70,%71,%72,%73,%74,%75,%76,%77,%78,%79,%80,%81,%82,%83,%84,%85,%86,%87,%88,%89,%90,%91,%92,%93,%94,%95}, %96, %97, p, 1, 1, 0, 1;\n}\n"
   : "+f"(d[0]),"+f"(d[1]),"+f"(d[2]),"+f"(d[3]),"+f"(d[4]),"+f"(d[5]),"+f"(d[6]),"+f"(d[7]),"+f"(d[8]),"+f"(d[9]),"+f"(d[10]),"+f"(d[11]),"+f"(d[12]),"+f"(d[13]),"+f"(d[14]),"+f"(d[15]),"+f"(d[16]),"+f"(d[17]),"+f"(d[18]),"+f"(d[19]),"+f"(d[20]),"+f"(d[21]),"+f"(d[22]),"+f"(d[23]),"+f"(d[24]),"+f"(d[25]),"+f"(d[26]),"+f"(d[27]),"+f"(d[28]),"+f"(d[29]),"+f"(d[30]),"+f"(d[31]),"+f"(d[32]),"+f"(d[33]),"+f"(d[34]),"+f"(d[35]),"+f"(d[36]),"+f"(d[37]),"+f"(d[38]),"+f"(d[39]),"+f"(d[40]),"+f"(d[41]),"+f"(d[42]),"+f"(d[43]),"+f"(d[44]),"+f"(d[45]),"+f"(d[46]),"+f"(d[47]),"+f"(d[48]),"+f"(d[49]),"+f"(d[50]),"+f"(d[51]),"+f"(d[52]),"+f"(d[53]),"+f"(d[54]),"+f"(d[55]),"+f"(d[56]),"+f"(d[57]),"+f"(d[58]),"+f"(d[59]),"+f"(d[60]),"+f"(d[61]),"+f"(d[62]),"+f"(d[63]),"+f"(d[64]),"+f"(d[65]),"+f"(d[66]),"+f"(d[67]),"+f"(d[68]),"+f"(d[69]),"+f"(d[70]),"+f"(d[71]),"+f"(d[72]),"+f"(d[73]),"+f"(d[74]),"+f"(d[75]),"+f"(d[76]),"+f"(d[77]),"+f"(d[78]),"+f"(d[79]),"+f"(d[80]),"+f"(d[81]),"+f"(d[82]),"+f"(d[83]),"+f"(d[84]),"+f"(d[85]),"+f"(d[86]),"+f"(d[87]),"+f"(d[88]),"+f"(d[89]),"+f"(d[90]),"+f"(d[91]),"+f"(d[92]),"+f"(d[93]),"+f"(d[94]),"+f"(d[95])
   : "l"(da), "l"(db), "r"(sd));
}
template<> __device__ __forceinline__ void wgmma_ss<192,1,1>(float* d, uint64_t da, uint64_t db, int sd) {
  asm volatile("{\n.reg .pred p;\nsetp.ne.b32 p, %98, 0;\nwgmma.mma_async.sync.aligned.m64n192k16.f32.bf16.bf16 {%0,%1,%2,%3,%4,%5,%6,%7,%8,%9,%10,%11,%12,%13,%14,%15,%16,%17,%18,%19,%20,%21,%22,%23,%24,%25,%26,%27,%28,%29,%30,%31,%32,%33,%34,%35,%36,%37,%38,%39,%40,%41,%42,%43,%44,%45,%46,%47,%48,%49,%50,%51,%52,%53,%54,%55,%56,%57,%58,%59,%60,%61,%62,%63,%64,%65,%66,%67,%68,%69,%70,%71,%72,%73,%74,%75,%76,%77,%78,%79,%80,%81,%82,%83,%84,%85,%86,%87,%88,%89,%90,%91,%92,%93,%94,%95}, %96, %97, p, 1, 1, 1, 1;\n}\n"
   : "+f"(d[0]),"+f"(d[1]),"+f"(d[2]),"+f"(d[3]),"+f"(d[4]),"+f"(d[5]),"+f"(d[6]),"+f"(d[7]),"+f"(d[8]),"+f"(d[9]),"+f"(d[10]),"+f"(d[11]),"+f"(d[12]),"+f"(d[13]),"+f"(d[14]),"+f"(d[15]),"+f"(d[16]),"+f"(d[17]),"+f"(d[18]),"+f"(d[19]),"+f"(d[20]),"+f"(d[21]),"+f"(d[22]),"+f"(d[23]),"+f"(d[24]),"+f"(d[25]),"+f"(d[26]),"+f"(d[27]),"+f"(d[28]),"+f"(d[29]),"+f"(d[30]),"+f"(d[31]),"+f"(d[32]),"+f"(d[33]),"+f"(d[34]),"+f"(d[35]),"+f"(d[36]),"+f"(d[37]),"+f"(d[38]),"+f"(d[39]),"+f"(d[40]),"+f"(d[41]),"+f"(d[42]),"+f"(d[43]),"+f"(d[44]),"+f"(d[45]),"+f"(d[46]),"+f"(d[47]),"+f"(d[48]),"+f"(d[49]),"+f"(d[50]),"+f"(d[51]),"+f"(d[52]),"+f"(d[53]),"+f"(d[54]),"+f"(d[55]),"+f"(d[56]),"+f"(d[57]),"+f"(d[58]),"+f"(d[59]),"+f"(d[60]),"+f"(d[61]),"+f"(d[62]),"+f"(d[63]),"+f"(d[64]),"+f"(d[65]),"+f"(d[66]),"+f"(d[67]),"+f"(d[68]),"+f"(d[69]),"+f"(d[70]),"+f"(d[71]),"+f"(d[72]),"+f"(d[73]),"+f"(d[74]),"+f"(d[75]),"+f"(d[76]),"+f"(d[77]),"+f"(d[78]),"+f"(d[79]),"+f"(d[80]),"+f"(d[81]),"+f"(d[82]),"+f"(d[83]),"+f"(d[84]),"+f"(d[85]),"+f"(d[86]),"+f"(d[87]),"+f"(d[88]),"+f"(d[89]),"+f"(d[90]),"+f"(d[91]),"+f"(d[92]),"+f"(d[93]),"+f"(d[94]),"+f"(d[95])
   : "l"(da), "l"(db), "r"(sd));
}

__device__ __forceinline__ void stats_publish(uint32_t sb, int layer, int rb, int hg, int ht, uint32_t tag) {
  const int lane = ht & 31, w = ht >> 5, g = lane >> 2, t = lane & 3, ks = hg & 3;
  uint32_t xa;
  if (layer == 0) {
    const int row = 16 * w + (lane & 15), kc = 2 * ks + (lane >> 4);
    xa = row * 128 + ((kc ^ (row & 7)) << 4);
  } else {
    const int k = 16 * ks + (lane & 7) + 8 * (lane >> 4), pc = 2 * w + ((lane >> 3) & 1);
    xa = k * 128 + ((pc ^ (k & 7)) << 4);
  }
  float s[4] = {0.f, 0.f, 0.f, 0.f}, q[4] = {0.f, 0.f, 0.f, 0.f};
#pragma unroll 1
  for (int c = hg >> 2; c < 8; c += 2) {
    uint32_t A[2][4];
    mbar_wait(sb + SM_BAR + 8 * (B_XF + c), layer);
#pragma unroll
    for (int h = 0; h < 2; h++) {
      if (layer == 0) ldsm4(A[h], sb + SM_X + c * 16384 + h * 8192 + xa);
      else ldsm4t(A[h], sb + SM_X + c * 16384 + h * 8192 + xa);
    }
    if (c >= 6) ATS(48, 256);
    if (c < 2) ATS(51, 256);
#pragma unroll
    for (int r = 0; r < 4; r++)
#pragma unroll
      for (int i = 0; i < 2; i++) {
        const uint32_t v = A[r >> 1][2 * i + (r & 1)];
        const float a = bf_lo(v), b = bf_hi(v);
        s[r] += a + b; q[r] = fmaf(a, a, q[r]); q[r] = fmaf(b, b, q[r]);
      }
  }
#pragma unroll
  for (int r = 0; r < 2; r++) {
    s[r] = ((t & 2) ? s[r + 2] : s[r]) + __shfl_xor_sync(~0u, (t & 2) ? s[r] : s[r + 2], 2);
    q[r] = ((t & 2) ? q[r + 2] : q[r]) + __shfl_xor_sync(~0u, (t & 2) ? q[r] : q[r + 2], 2);
  }
  s[0] = ((t & 1) ? s[1] : s[0]) + __shfl_xor_sync(~0u, (t & 1) ? s[0] : s[1], 1);
  q[0] = ((t & 1) ? q[1] : q[0]) + __shfl_xor_sync(~0u, (t & 1) ? q[0] : q[1], 1);
  st_part(&g_part[(rb * 8 + hg) * 128 + 64 * (t >> 1) + 16 * w + 8 * (t & 1) + g], s[0], q[0], tag);
  ATS(49, 256);
}
__device__ __forceinline__ void stats_gather(uint32_t sb, int rb, int ht, uint32_t tag) {
  const uint2* src = &g_part[rb * 8 * 128 + ht];
  uint2 v[8];
  for (int it = 0;; it++) {
    uint32_t bad = 0;
#pragma unroll
    for (int i = 0; i < 8; i++) v[i] = ld_part(src + i * 128);
#pragma unroll
    for (int i = 0; i < 8; i++) bad |= v[i].y ^= tag;
    if (__all_sync(~0u, (bad & 7u) == 0)) break;
    if (it > (1 << 22)) __trap();
  }
  float s = 0.f, q = 0.f;
#pragma unroll
  for (int i = 0; i < 8; i++) { s += __uint_as_float(v[i].x); q += __uint_as_float(v[i].y); }
  const float mean = s * (1.f / DM);
  const float rstd = rsqrt_approx(fmaxf(q * (1.f / DM) - mean * mean, 0.f) + 1e-5f);
  asm volatile("st.shared.v2.f32 [%0], {%1,%2};" ::"r"(sb + SM_ST + ht * 8), "f"(mean), "f"(rstd) : "memory");
  __syncwarp();
  if (elect_one()) mbar_arrive(sb + SM_BAR + 8 * B_STF);
}
__device__ __forceinline__ void halo_receive(uint32_t sb, int layer, int rb, int hg, int ht) {
  const int lane = ht & 31, h = ht >> 5;
  uint4 kv = make_uint4(0, 0, 0, 0);
  mbar_wait(sb + SM_BAR + 8 * B_SD, layer);
  if (rb & 7) {
    const uint32_t tag = 2 * lds32(sb + SM_EP) + layer + 1;
    const uint4* src = &g_halo[((rb - 1) * 8 + hg) * 192 + h * 48];
    if (layer == 0) delay<D_HALO>(); else delay<D_HALO1>();
    uint4 a;
    uint2 b;
    int it = 0;
    do {
      a = ld_tagged(src + lane); b = ld_part((const uint2*)(src + 32) + lane);
      if (++it > (1 << 22)) __trap();
    } while (!__all_sync(~0u, a.w == tag && b.y == tag));
    kv = make_uint4(a.x, a.y, movm_t(a.z), movm_t(b.x));
  }
  sts128(sb + SM_KVX + h * 512 + lane * 16, kv);
  ATS(61, 256);
  bar_arrive(7, 160);
  if (elect_one()) mbar_arrive(sb + SM_BAR + 8 * B_HF);
}

__device__ __forceinline__ void halo_receive1(uint32_t sb, int layer, int rb, int hg, int lane, uint32_t tag) {
  uint4 a[4];
  uint2 b[4];
  mbar_wait(sb + SM_BAR + 8 * B_SD, layer);
  if (rb & 7) {
    const uint4* src = &g_halo[((rb - 1) * 8 + hg) * 192];
    if (layer == 0) delay<D_HALO>(); else delay<D_HALO1>();
    for (int it = 0;; it++) {
      uint32_t bad = 0;
#pragma unroll
      for (int h = 0; h < 4; h++) { a[h] = ld_tagged(src + h * 48 + lane); b[h] = ld_part((const uint2*)(src + h * 48 + 32) + lane); }
#pragma unroll
      for (int h = 0; h < 4; h++) {
        bad |= (a[h].w ^ tag) | (b[h].y ^ tag);
        a[h].z = movm_t(a[h].z); a[h].w = movm_t(b[h].x);
      }
      if (__all_sync(~0u, bad == 0)) break;
      if (it > (1 << 22)) __trap();
    }
  } else {
#pragma unroll
    for (int h = 0; h < 4; h++) a[h] = make_uint4(0, 0, 0, 0);
  }
#pragma unroll
  for (int h = 0; h < 4; h++) sts128(sb + SM_KVX + h * 512 + lane * 16, a[h]);
  ATS(61, 448);
  bar_arrive(7, 64);
  if (lane < 4) mbar_arrive(sb + SM_BAR + 8 * B_HF);
}

template <bool TR>
__device__ __forceinline__ void gemm_section(float* acc, float2* cs, uint32_t sb, int layer, int wg, int w, int lane) {
  const uint32_t bar = sb + SM_BAR;
  const bool leader = (w == 0) && (lane == 0);
  auto issue = [&](int c, int slot) {
    mbar_wait(bar + 8 * (B_XF + c), layer);
    mbar_wait(bar + 8 * (B_KVF + c), layer);
    const uint64_t da = mkdesc(sb + SM_X + c * 16384 + wg * 8192, TR ? 8192 : 16, 1024, 1);
    const uint64_t db = mkdesc(sb + SM_W + slot * 24576, 8192, 1024, 1);
    wg_fence();
#pragma unroll
    for (int ks = 0; ks < 4; ks++) wgmma_ss<192, TR ? 1 : 0, 1>(acc, da + (TR ? ks * 128 : ks * 2), db + ks * 128, (c | ks) != 0);
    wg_commit();
  };
  auto step = [&](int c, int slot) {
    issue(c, slot);
    wg_wait<1>();
    if (leader) mbar_arrive(bar + 8 * (B_KVE + c - 1));
  };
  if (!TR) bar_sync(0, NTHREADS);
  if (TR && G_WAIT == 3 && wg == 1) bar_sync(14, 256);
  if (TR && G_WAIT == 4 && wg == 1) mbar_wait(bar + 8 * (B_P + 3), 0);
  issue(0, 0);
  if (threadIdx.x == 0) TS(2 + layer * 20 + 0);
  if (threadIdx.x == 128 && layer == 1) TS(60);
  auto ld_cs = [&](int j0) {
#pragma unroll
    for (int j = j0; j < j0 + 8; j++) cs[j] = lds64f(sb + SM_CS + 4 * (8 * j + 2 * (lane & 3)));
  };
  if (TR && CS_STEP == 0) ld_cs(8);
  step(1, 1);
  if (TR && CS_STEP == 0) ld_cs(16);
  if (TR && CS_STEP == 1) ld_cs(8);
  step(2, 2);
  if (TR && CS_STEP == 1) ld_cs(16);
  if (TR && CS_STEP == 2) ld_cs(8);
  step(3, 0);
  if (TR && CS_STEP == 2) ld_cs(16);
  step(4, 1);
  if ((TR ? STAG1 : STAG0) == 3) {
    if (wg == 0) {
      wg_wait<0>();
      if (leader) mbar_arrive(bar + 8 * (B_KVE + 4));
      bar_sync(5, 256);
    }
    issue(5, 2);
    wg_wait<1>();
    if (leader && wg == 1) mbar_arrive(bar + 8 * (B_KVE + 4));
    if (!TR && !CS_LATE0) { mbar_wait(bar + 8 * B_CSF, 0); ld_cs(8); ld_cs(16); }
  } else {
    step(5, 2);
    if (!TR && !CS_LATE0) { mbar_wait(bar + 8 * B_CSF, 0); ld_cs(8); ld_cs(16); }
    if (wg == 0) bar_sync(5, 256);
  }
  issue(6, 0);
  issue(7, 1);
  if (wg == 1) bar_arrive(5, 256);
  if (!TR && CS_LATE0) { mbar_wait(bar + 8 * B_CSF, 0); ld_cs(8); ld_cs(16); }
}

__device__ __forceinline__ void attn_phase(const Params& p, uint32_t sb, int layer, int rb, int hg, int wg, int w) {
  const int lane = opaque_tid() & 31;
  const int g = lane >> 2, t = lane & 3;
  const uint32_t bar = sb + SM_BAR;
  const int row0 = 64 * wg + 16 * w;
  const bool leader = (w == 0) && (lane == 0);
  float acc[96];
  float2 cs[24];
  if (layer) gemm_section<true>(acc, cs, sb, layer, wg, w, lane);
  else gemm_section<false>(acc, cs, sb, layer, wg, w, lane);
  ATS(41, 224);
  mbar_wait(bar + 8 * B_STF, layer);
  const uint32_t tag = 2 * lds32(sb + SM_EP) + layer + 1;
  const float2 st0 = lds64f(sb + SM_ST + (row0 + g) * 8), st1 = lds64f(sb + SM_ST + (row0 + g + 8) * 8);
  const float mean0 = st0.x, rstd0 = st0.y, mean1 = st1.x, rstd1 = st1.y;
  wg_wait<0>();
  if (threadIdx.x == 0) TS(2 + layer * 20 + 1);
  ATS(39, 224);
  if (leader) mbar_arrive(bar + 8 * B_QDONE);

  uint32_t fp[4][4], fl[4][4], fh[4][4], qa[4][4];
  const int cw = 4 * wg + w;
  {
    const float nm0 = -mean0 * rstd0, nm1 = -mean1 * rstd1;
    const uint32_t kvx = sb + SM_KVX + cw * 2048 + lane * 16;
#pragma unroll
    for (int h = 0; h < 4; h++)
#pragma unroll
      for (int k = 0; k < 4; k++) {
        const int j = 8 + (k >> 1) * 8 + 2 * h + (k & 1);
        fh[h][k] = packbf(fmaf(acc[4 * j + 2], rstd1, nm1 * cs[j].x), fmaf(acc[4 * j + 3], rstd1, nm1 * cs[j].y));
      }
    if (cw == 7) {
      uint4* halo = &g_halo[(rb * 8 + hg) * 192];
#pragma unroll
      for (int h = 0; h < 4; h++) {
        st_tagged3(halo + h * 48 + lane, fh[h][0], fh[h][1], fh[h][2], tag);
        asm volatile("st.relaxed.gpu.global.v2.u32 [%0], {%1,%2};" ::"l"((uint2*)(halo + h * 48 + 32) + lane), "r"(fh[h][3]), "r"(tag) : "memory");
      }
      if (elect_one()) mbar_arrive(bar + 8 * B_SD);
      if (layer == TLAYER && threadIdx.x == 224) TS(47);
    }
#pragma unroll
    for (int h = 0; h < 4; h++) { fh[h][2] = movm_t(fh[h][2]); fh[h][3] = movm_t(fh[h][3]); }
    if (cw != 7) {
#pragma unroll
      for (int h = 0; h < 4; h++) sts128(kvx + 2048 + h * 512, make_uint4(fh[h][0], fh[h][1], fh[h][2], fh[h][3]));
      bar_arrive(8 + cw, 64);
    }
    sched_fence<6>();
    if (layer == TLAYER && threadIdx.x == 0) TS(45);
#pragma unroll
    for (int j = 0; j < 8; j++) cs[j] = lds64f(sb + SM_CS + 4 * (8 * j + 2 * t));
#pragma unroll
    for (int h = 0; h < 4; h++)
#pragma unroll
      for (int k = 0; k < 4; k++) {
        const int j = 8 + (k >> 1) * 8 + 2 * h + (k & 1);
        fl[h][k] = packbf(fmaf(acc[4 * j], rstd0, nm0 * cs[j].x), fmaf(acc[4 * j + 1], rstd0, nm0 * cs[j].y));
        if (k >= 2) fl[h][k] = movm_t(fl[h][k]);
      }
#pragma unroll
    for (int h = 0; h < 4; h++) {
#pragma unroll
      for (int dh = 0; dh < 2; dh++) {
        const int j = 2 * h + dh;
        const float2 c2 = cs[j];
        qa[h][2 * dh] = packbf(fmaf(-mean0, c2.x, acc[4 * j + 0]), fmaf(-mean0, c2.y, acc[4 * j + 1]));
        qa[h][2 * dh + 1] = packbf(fmaf(-mean1, c2.x, acc[4 * j + 2]), fmaf(-mean1, c2.y, acc[4 * j + 3]));
      }
    }
    if (threadIdx.x == 0) TS(2 + layer * 20 + 2);
    if (QD_AT == 1 || (QD_AT == 3 && wg == 0)) mbar_wait(bar + 8 * B_QDONE, layer);
    sched_fence<0>();
    bar_sync(7 + cw, cw == 0 && !HALO_W14 ? 160 : 64);
#pragma unroll
    for (int h = 0; h < 4; h++) {
      const uint4 v = lds128(kvx + h * 512);
      fp[h][0] = v.x; fp[h][1] = v.y; fp[h][2] = v.z; fp[h][3] = v.w;
    }
    if (threadIdx.x == 0) TS(2 + layer * 20 + 4);
  }

  const bool u0 = 2 * t > g, u1 = 2 * t + 1 > g;
  const uint32_t mU = (u0 ? 0x0000ffffu : 0u) | (u1 ? 0xffff0000u : 0u);
  const float cl2 = 0.25f * 1.4426950408889634f;
  const float sc0 = rstd0 * cl2, sc1 = rstd1 * cl2;
  const float cneg = ((rb & 7) == 0 && cw == 0) ? -INFINITY : 0.f;
  float v[4][4];
#pragma unroll
  for (int h = 0; h < 4; h++) {
    float T0[4] = {cneg, cneg, cneg, cneg}, T1[4] = {0.f, 0.f, 0.f, 0.f}, T2[4] = {0.f, 0.f, 0.f, 0.f};
    mma_bf16(T1, qa[h], fl[h][0], fl[h][1]);
    mma_bf16(T2, qa[h], fh[h][0], fh[h][1]);
    mma_bf16(T0, qa[h], fp[h][0], fp[h][1]);
    v[h][0] = u0 ? T0[0] : T1[0]; v[h][1] = u1 ? T0[1] : T1[1];
    v[h][2] = u0 ? T1[2] : T2[2]; v[h][3] = u1 ? T1[3] : T2[3];
  }
  float m0[4], m1[4];
#pragma unroll
  for (int h = 0; h < 4; h++) { m0[h] = fmaxf(v[h][0], v[h][1]); m1[h] = fmaxf(v[h][2], v[h][3]); }
#pragma unroll
  for (int o = 1; o <= 2; o <<= 1) {
#pragma unroll
    for (int h = 0; h < 4; h++) {
      m0[h] = fmaxf(m0[h], __shfl_xor_sync(~0u, m0[h], o));
      m1[h] = fmaxf(m1[h], __shfl_xor_sync(~0u, m1[h], o));
    }
  }
  float O0[4][4], O1[4][4], Z[4][4];
#pragma unroll
  for (int h = 0; h < 4; h++) {
    const float mm0 = -m0[h] * sc0, mm1 = -m1[h] * sc1;
    const uint32_t P0 = packbf(ex2(fmaf(v[h][0], sc0, mm0)), ex2(fmaf(v[h][1], sc0, mm0)));
    const uint32_t P1 = packbf(ex2(fmaf(v[h][2], sc1, mm1)), ex2(fmaf(v[h][3], sc1, mm1)));
#pragma unroll
    for (int k = 0; k < 4; k++) O0[h][k] = O1[h][k] = Z[h][k] = 0.f;
    mma_bf16_k8(Z[h], P0, P1, 0x3f803f80u);
    mma_bf16_k8(O0[h], P0 & ~mU, P1 & mU, fl[h][2]); mma_bf16_k8(O1[h], P0 & ~mU, P1 & mU, fl[h][3]);
    mma_bf16_k8(O0[h], P0 & mU, 0u, fp[h][2]); mma_bf16_k8(O1[h], P0 & mU, 0u, fp[h][3]);
    mma_bf16_k8(O0[h], 0u, P1 & ~mU, fh[h][2]); mma_bf16_k8(O1[h], 0u, P1 & ~mU, fh[h][3]);
  }
  const uint32_t ob = sb + SM_OST + wg * 8192;
  if (QD_AT == 0 || (QD_AT == 3 && wg == 1)) mbar_wait(bar + 8 * B_QDONE, layer);
  const int o_row = 16 * w + (lane & 7) + 8 * ((lane >> 3) & 1);
#pragma unroll
  for (int h = 0; h < 4; h++) {
    const float i0 = rcp_approx(Z[h][0]), i1 = rcp_approx(Z[h][2]);
    const int ch = 2 * h + (lane >> 4);
    const uint32_t k0 = O_CHECK && t == (h & 2), k1 = O_CHECK && t == (h & 2) + 1;
    stsm4(ob + o_row * 128 + ((ch ^ (o_row & 7)) << 4), (packbf(O0[h][0] * i0, O0[h][1] * i0) & ~k0) | (k0 & ~layer), (packbf(O0[h][2] * i1, O0[h][3] * i1) & ~k1) | (k1 & ~layer),
          packbf(O1[h][0] * i0, O1[h][1] * i0), packbf(O1[h][2] * i1, O1[h][3] * i1));
  }
  if (threadIdx.x == 0) TS(2 + layer * 20 + 5);
  ATS(57, 128); ATS(20, 96);
  __syncwarp();
  if (elect_one()) {
    auto hint = [&] {
      uint32_t old;
      asm volatile("atom.relaxed.cta.shared.inc.u32 %0, [%1], 7;" : "=r"(old) : "r"(sb + SM_EP + 4) : "memory");
      if (old == 7) { red_relaxed(&g_cnt[(C_O + rb) * 32]); TS(2 + layer * 20 + 6); }
    };
    if (O_WAIT == 3) hint();
    fence_async_smem();
    tma_st(&p.mapO, hg * 64, rb * 128 + row0, ob + w * 2048);
    bulk_commit();
    if (O_WAIT == 2) hint();
    mbar_arrive(bar + 8 * B_AD);
    if (O_WAIT == 1) bulk_wait_all();
    else asm volatile("cp.async.bulk.wait_group.read 0;" ::: "memory");
    if (O_WAIT < 2) hint();
    mbar_arrive(bar + 8 * B_OST);
  }
  __syncwarp();
}

__device__ __forceinline__ void proj_phase(const Params& p, uint32_t sb, int layer, int rb, int q, int wg, int w) {
  const int lane = opaque_tid() & 31;
  const bool TR = layer != 0;
  const int t = lane & 3;
  const uint32_t bar = sb + SM_BAR;
  const uint32_t rbx = sb + SM_R + wg * 8192;
  uint32_t res[16];
  mbar_wait(bar + 8 * B_RF, layer);
  if (threadIdx.x == 0) TS(2 + layer * 20 + 7);
  if (!TR) {
#pragma unroll
    for (int j = 0; j < 8; j += 2) {
      const int mi = lane >> 3;
      const int row = 16 * w + (lane & 7) + 8 * (mi & 1), ch = j + (mi >> 1);
      ldsm4(&res[2 * j], rbx + row * 128 + ((ch ^ (row & 7)) << 4));
    }
  } else {
#pragma unroll
    for (int j = 0; j < 8; j += 2) {
      const int mi = lane >> 3;
      const int line = 8 * (j + (mi >> 1)) + (lane & 7), pc = 2 * w + (mi & 1);
      ldsm4t(&res[2 * j], rbx + line * 128 + ((pc ^ (line & 7)) << 4));
    }
  }
  bar_sync(2 + wg, 128);
  float acc[32];
  const uint32_t tag = part_tag(lds32(sb + SM_EP), 2 * layer + 1);
  mbar_wait(bar + 8 * B_ZF, layer);
  mbar_wait(bar + 8 * B_WOF, layer);
  tensor_keepalive<1>();
  const uint32_t chk = wg * 8192 + (16 * w + (lane & 15)) * 128 + ((((lane >> 4) * 4) ^ (lane & 7)) << 4) + (lane >> 3) * 4;
  for (bool first = true;; first = false) {
#pragma unroll
    for (int i = 0; i < 16; i++) {
      asm volatile("shl.b32 %0, %1, 16;" : "=f"(acc[2 * i]) : "r"(res[i]));
      asm volatile("and.b32 %0, %1, 0xffff0000;" : "=f"(acc[2 * i + 1]) : "r"(res[i]));
    }
#pragma unroll P_UNROLL
    for (int c = 0; c < 8; c++) {
      mbar_wait(bar + 8 * (B_OF + c), layer);
      if (c == 0 && threadIdx.x == 0) TS(2 + layer * 20 + 8);
      const uint64_t da = mkdesc(sb + sm_o(c) + wg * 8192, 16, 1024, 1);
      const uint64_t db = mkdesc(sb + SM_WO + c * 8192, 8192, 1024, 1);
      wg_fence();
#pragma unroll
      for (int ks = 0; ks < 4; ks++) wgmma_ss<64, 0, 1>(acc, da + ks * 2, db + ks * 128, 1);
      wg_commit();
    }
    uint32_t m[16];
    if (O_CHECK == 1) {
#pragma unroll
      for (int c = 0; c < 8; c++) { m[2 * c] = lds32(sb + sm_o(c) + chk); m[2 * c + 1] = lds32(sb + sm_o(c) + (chk ^ 32)); }
    }
    wg_wait<0>();
#pragma unroll
    for (int i = 0; i < 32; i++) asm volatile("" : "+f"(acc[i]) :: "memory");
    if (O_CHECK == 2) {
#pragma unroll
      for (int c = 0; c < 8; c++) { m[2 * c] = lds32(sb + sm_o(c) + chk); m[2 * c + 1] = lds32(sb + sm_o(c) + (chk ^ 32)); }
    }
    if (threadIdx.x == 0) TS(2 + layer * 20 + 9);
    float s[4], qq[4];
#pragma unroll
    for (int k = 0; k < 4; k++) { s[k] = acc[k]; qq[k] = acc[k] * acc[k]; }
#pragma unroll
    for (int j = 1; j < 8; j++)
#pragma unroll
      for (int k = 0; k < 4; k++) { s[k] += acc[4 * j + k]; qq[k] = fmaf(acc[4 * j + k], acc[4 * j + k], qq[k]); }
    const float s0 = s[0] + s[1], s1 = s[2] + s[3], q0 = qq[0] + qq[1], q1 = qq[2] + qq[3];
    float sr = ((t & 1) ? s1 : s0) + __shfl_xor_sync(~0u, (t & 1) ? s0 : s1, 1);
    float qr = ((t & 1) ? q1 : q0) + __shfl_xor_sync(~0u, (t & 1) ? q0 : q1, 1);
    sr += __shfl_xor_sync(~0u, sr, 2);
    qr += __shfl_xor_sync(~0u, qr, 2);
    uint32_t all = ~0u, any = 0;
    if (O_CHECK) {
#pragma unroll
      for (int i = 0; i < 16; i++) { all &= m[i]; any |= m[i]; }
    }
    bool bad = ((layer ? any : ~all) & 1) != 0;
    const bool warp_ok = !__any_sync(~0u, bad);
    if (warp_ok && t < 2) st_part(&g_part[(rb * 8 + q) * 128 + 64 * wg + 16 * w + (lane >> 2) + 8 * t], sr, qr, tag);
    if (first && lane == 0) mbar_arrive(bar + 8 * B_PS);
#pragma unroll
    for (int j = 0; j < 8; j += 2) {
      const int mi = lane >> 3;
      const int line = 8 * (j + (mi >> 1)) + (lane & 7), pc = 2 * w + (mi & 1);
      stsm4t(rbx + line * 128 + ((pc ^ (line & 7)) << 4), packbf(acc[4 * j], acc[4 * j + 1]), packbf(acc[4 * j + 2], acc[4 * j + 3]),
             packbf(acc[4 * j + 4], acc[4 * j + 5]), packbf(acc[4 * j + 6], acc[4 * j + 7]));
    }
    uint32_t redo;
    asm volatile("{\n.reg .pred p, q;\nsetp.eq.u32 p, %1, 0;\nbar.red.or.pred q, %2, 128, p;\nselp.u32 %0, 1, 0, q;\n}" : "=r"(redo) : "r"((uint32_t)warp_ok), "r"(2 + wg) : "memory");
    mbar_arrive_if(bar + 8 * B_SG, !redo && w == 0 && lane == 0);
    if (__builtin_expect(!redo, 1)) break;
    const uint32_t n = lds32(sb + SM_EP + 8 + 4 * wg);
    if (n > (1u << 20)) __trap();
    bar_sync(2 + wg, 128);
    if (w == 0 && elect_one()) {
      asm volatile("st.shared.u32 [%0], %1;" ::"r"(sb + SM_EP + 8 + 4 * wg), "r"(n + 1) : "memory");
      fence_async_smem();
      mbar_expect(bar + 8 * (B_RT + wg), 65536);
#pragma unroll
      for (int c = 0; c < 8; c++) tma_ld(sb + sm_o(c) + wg * 8192, &p.mapO64, c * 64, rb * 128 + wg * 64, bar + 8 * (B_RT + wg));
    }
    __syncwarp();
    mbar_wait(bar + 8 * (B_RT + wg), n & 1);
  }
}
__device__ __forceinline__ void proj_stats(uint32_t sb, int layer, int rb, int q, int lane, uint32_t tag) {
  const int r = FIN4 ? 32 * (q - 4) + lane : 16 * q + (lane & 15);
  const uint2* src = &g_part[rb * 8 * 128 + r];
  uint32_t* dst = g_stats + layer * LSEQ + (rb >> 1) * 256 + ((r >> 2) & 1) * 128 + ((rb & 1) * 16 + (r >> 3)) * 4 + (r & 3);
  mbar_wait(sb + SM_BAR + 8 * B_PS, layer);
  delay<D_PST>();
  for (int it = 0;; it++) {
    uint2 v[8];
#pragma unroll
    for (int i = 0; i < 8; i++) v[i] = ld_part(src + i * 128);
    float s[4], qq[4];
    uint32_t bad = 0;
#pragma unroll
    for (int i = 0; i < 4; i++) {
      s[i] = __uint_as_float(v[i].x) + __uint_as_float(v[i + 4].x);
      qq[i] = __uint_as_float(v[i].y ^ tag) + __uint_as_float(v[i + 4].y ^ tag);
      bad |= (v[i].y ^ tag) | (v[i + 4].y ^ tag);
    }
    const float mean = ((s[0] + s[1]) + (s[2] + s[3])) * (1.f / DM);
    const float rstd = rsqrt_approx(fmaxf(fmaf((qq[0] + qq[1]) + (qq[2] + qq[3]), 1.f / DM, -mean * mean), 0.f) + 1e-5f);
    const bool ok = __all_sync(~0u, (bad & 7u) == 0);
    if (ok && (FIN4 || lane < 16))
    {
      if (PUB & 1) asm volatile("red.relaxed.gpu.global.or.b32 [%0], %1;" ::"l"(dst), "r"(max(packbf(-mean, rstd), 1u)) : "memory");
      else asm volatile("st.relaxed.gpu.global.u32 [%0], %1;" ::"l"(dst), "r"(max(packbf(-mean, rstd), 1u)) : "memory");
    }
    if (ok) break;
    if (it > (1 << 22)) __trap();
  }
}

#define NA 14
#define NP 16
template <int M0, int M1> __device__ __forceinline__ void conv_load(uint32_t* A, uint32_t pe) {
#pragma unroll
  for (int m = M0; m < M1; m++) {
    asm volatile("ld.shared.v2.b32 {%0,%1}, [%2];" : "=r"(A[4 * m]), "=r"(A[4 * m + 1]) : "r"(pe + 256 * m) : "memory");
    A[4 * m + 2] = lds32(pe + 256 * m - 4);
  }
}
__device__ __forceinline__ uint32_t copy_reg(uint32_t v, uint32_t zero) { uint32_t r; asm volatile("or.b32 %0, %1, %2;" : "=r"(r) : "r"(v), "r"(zero)); return r; }
__device__ __forceinline__ uint32_t copy_reg2(uint32_t v, uint32_t zero) { uint32_t r; asm volatile("xor.b32 %0, %1, %2;" : "=r"(r) : "r"(v), "r"(zero)); return r; }
__device__ __forceinline__ void conv_park(uint32_t* P, uint32_t pe) {
#pragma unroll
  for (int m = 0; m < NP; m++)
#pragma unroll
    for (int k = 0; k < 3; k++) P[3 * m + k] = lds32(pe + 256 * m - 4 + 4 * k);
}
__device__ __forceinline__ void conv_unpark(uint32_t* A, const uint32_t* P, uint32_t zero) {
#pragma unroll
  for (int m = 0; m < NP; m++) {
    A[4 * m + 2] = copy_reg(P[3 * m], zero); A[4 * m] = copy_reg(P[3 * m + 1], zero);
    A[4 * m + 3] = copy_reg2(P[3 * m + 1], zero); A[4 * m + 1] = copy_reg(P[3 * m + 2], zero);
  }
}
template <int M0, int M1> __device__ __forceinline__ void conv_mmas(float* acc, const uint32_t* A, uint64_t d) {
  if constexpr (M0 < M1) {
    wgmma_rs<128 - 8 * (M0 / 2), 0>(acc, A + 4 * M0, d + (uint64_t)(4 * M0), M0 != 0);
    conv_mmas<M0 + 1, M1>(acc, A, d);
  }
}
struct SumAddr { uint32_t l0, l1, l2, se, so; };
__device__ __forceinline__ SumAddr conv_sum_addr(uint32_t sb, int c) {
  auto ua = [&](int j) { return sb + cv_u(0) + (127 - (j >> 3)) * 16 + (j & 7) * 2; };
  auto sa = [&](int hc) { const int ci = hc & ~1; return sb + cv_s(0) + ((ci >> 3) & 1) * 1024 + (ci >> 4) * 128 + (((ci ^ (ci >> 4)) & 7) << 4) + (hc & 1) * 8; };
  const int j0 = 4 * (c - 1);
  return {ua(j0 - 2), ua(j0), ua(j0 + 4), sa((c + 1) & 127), sa(c) + 2048};
}
__device__ __forceinline__ void sts64(uint32_t a, uint32_t x, uint32_t y) { asm volatile("st.shared.v2.b32 [%0], {%1,%2};" ::"r"(a), "r"(x), "r"(y) : "memory"); }
__device__ __forceinline__ void conv_sums(const SumAddr& sa, int lc, int c) {
  uint32_t e[4], o[4];
  {
    const float2 em = lds64f(sa.l1 + lc * 32768), om = lds64f(sa.l1 + lc * 32768 + CV_UH);
    e[0] = lds32(sa.l0 + lc * 32768); o[0] = lds32(sa.l0 + lc * 32768 + CV_UH);
    e[3] = lds32(sa.l2 + lc * 32768); o[3] = lds32(sa.l2 + lc * 32768 + CV_UH);
    e[1] = __float_as_uint(em.x); e[2] = __float_as_uint(em.y); o[1] = __float_as_uint(om.x); o[2] = __float_as_uint(om.y);
  }
  uint32_t s7e[2], s7o[2], s9e[2], s9o[2];
  uint32_t pw[4], sh[3];
#pragma unroll
  for (int k = 0; k < 4; k++) pw[k] = hadd2(e[k], o[k]);
#pragma unroll
  for (int k = 0; k < 3; k++) sh[k] = __byte_perm(pw[k], pw[k + 1], 0x5432);
#pragma unroll
  for (int k = 0; k < 2; k++) {
    const uint32_t t3 = hadd2(hadd2(sh[k], sh[k + 1]), pw[k + 1]);
    s7e[k] = hadd2(t3, o[k]); s7o[k] = hadd2(t3, e[k + 2]);
    s9e[k] = hadd2(s7o[k], pw[k]); s9o[k] = hadd2(s7e[k], pw[k + 2]);
  }
  if (c == 127) s9e[0] = s9e[1] = s9o[0] = s9o[1] = 0u;
  sts64(sa.se + lc * 32768, s9e[0], s9e[1]); sts64((sa.se ^ 16) + lc * 32768, s9o[0], s9o[1]);
  sts64(sa.so + lc * 32768, s7e[0], s7e[1]); sts64((sa.so ^ 16) + lc * 32768, s7o[0], s7o[1]);
}

__device__ __forceinline__ void conv_epi(uint32_t sb, int layer, int cta, int ch, int c0, uint4 x0, uint4 x1) {
  uint4 v[2][4];
  const uint4 xr[2] = {x0, x1};
  mbar_wait(sb + SM_BAR + 8 * (B_P + ch), layer);
#pragma unroll
  for (int u = 0; u < 2; u++) {
    const uint32_t pb = sb + cv_pb(ch) + u * (CV_PBW / 2) + c0 * 16;
#pragma unroll
    for (int k = 0; k < 4; k++) v[u][k] = lds128(pb + k * CV_PBW);
  }
#pragma unroll
  for (int u = 0; u < 2; u++) {
    uint4 o;
    o.x = hadd2(xr[u].x, hadd2(hadd2(v[u][0].x, v[u][1].x), hadd2(v[u][2].x, v[u][3].x)));
    o.y = hadd2(xr[u].y, hadd2(hadd2(v[u][0].y, v[u][1].y), hadd2(v[u][2].y, v[u][3].y)));
    o.z = hadd2(xr[u].z, hadd2(hadd2(v[u][0].z, v[u][1].z), hadd2(v[u][2].z, v[u][3].z)));
    o.w = hadd2(xr[u].w, hadd2(hadd2(v[u][0].w, v[u][1].w), hadd2(v[u][2].w, v[u][3].w)));
    if (layer == 0 && !W_STG) sts128(sb + cv_s(ch) + (c0 + 128 * u) * 16, o);
    else st_tagged3((uint4*)(g_xT + (size_t)((2 * layer + 1) * DM + cv_chan(cta, ch)) * LSEQ) + c0 + 128 * u, o.x, o.y, o.z, o.w);
  }
}
__device__ __forceinline__ void warp_release(uint32_t b) {
  fence_writer();
  __syncwarp();
  if (elect_one()) mbar_arrive(b);
}

__device__ __forceinline__ void conv_prep_load(uint32_t sb, int layer, int cta, int c, uint4 (&xr)[4], uint4 (&st)[4]) {
  sched_fence<8>();
  mbar_wait(sb + SM_BAR + 8 * B_GB, layer);
  if (threadIdx.x == 0) TS(2 + layer * 20 + 11);
  xr[0] = ld_tagged((const uint4*)(g_xT + (size_t)(2 * layer * DM + cta) * LSEQ) + c);
#pragma unroll
  for (int i = 0; i < 2; i++) st[i] = ld_tagged((const uint4*)g_stats + layer * 512 + (c >> 5) * 64 + i * 32 + (c & 31));
}
struct RowNorm { uint32_t nm[4], rs[4]; };
__device__ __forceinline__ RowNorm row_norm(uint4 a, uint4 b) {
  return {{__byte_perm(a.x, a.y, 0x5410), __byte_perm(a.z, a.w, 0x5410), __byte_perm(b.x, b.y, 0x5410), __byte_perm(b.z, b.w, 0x5410)},
          {__byte_perm(a.x, a.y, 0x7632), __byte_perm(a.z, a.w, 0x7632), __byte_perm(b.x, b.y, 0x7632), __byte_perm(b.z, b.w, 0x7632)}};
}
__device__ __forceinline__ uint4 normalize(uint4 x, const RowNorm& r) {
  return make_uint4(hmul2(hadd2(x.x, r.nm[0]), r.rs[0]), hmul2(hadd2(x.y, r.nm[1]), r.rs[1]), hmul2(hadd2(x.z, r.nm[2]), r.rs[2]), hmul2(hadd2(x.w, r.nm[3]), r.rs[3]));
}
template <bool HELPER>
__device__ __forceinline__ void conv_prep(uint32_t sb, int layer, int cta, int c, uint4 (&xr)[4], uint4 (&st)[4], const SumAddr& sa) {
  const uint32_t bar = sb + SM_BAR;
  const uint4* xin = (const uint4*)(g_xT + (size_t)(2 * layer * DM + cta) * LSEQ) + c;
  for (int it = 0;; it++) {
    const uint32_t vs = min(min(min(st[0].x, st[0].y), min(st[0].z, st[0].w)), min(min(st[1].x, st[1].y), min(st[1].z, st[1].w)));
    if (__all_sync(~0u, vs != 0 && xr[0].x != ~0u)) break;
    if (it > (1 << 22)) __trap();
    if (!__all_sync(~0u, xr[0].x != ~0u)) xr[0] = ld_tagged(xin);
    if (!__all_sync(~0u, vs != 0)) {
#pragma unroll
      for (int i = 0; i < 2; i++) st[i] = ld_tagged((const uint4*)g_stats + layer * 512 + (c >> 5) * 64 + i * 32 + (c & 31));
    }
  }
  const RowNorm rn = row_norm(st[0], st[1]);
  if (threadIdx.x == 0) TS(2 + layer * 20 + 12);
  const uint32_t ua = sb + cv_u(0) + (c >> 7) * CV_UH + (127 - (c & 127)) * 16;
  sts128(ua, normalize(xr[0], rn));
  warp_release(bar + 8 * B_U);
  mbar_wait(bar + 8 * B_XV, layer);
  xr[1] = ld_tagged(xin + 128 * LSEQ / 8);
  if (HELPER) {
    mbar_wait(bar + 8 * B_U, layer);
    conv_sums(sa, 0, c);
    fence_async_smem();
    bar_arrive(7, 256);
    sched_fence<1>();
    if (layer == 1 && c == 0) TS(46);
  }
  if (X_SENT) for (int it = 0; !__all_sync(~0u, xr[1].x != ~0u); it++) { if (it > (1 << 22)) __trap(); xr[1] = ld_tagged(xin + 128 * LSEQ / 8); }
  sts128(ua + 32768, normalize(xr[1], rn));
  warp_release(bar + 8 * (B_U + 1));
  if (HELPER) {
    const uint4* so = (const uint4*)g_stats + layer * 512 + 256 + (c >> 5) * 64 + (c & 31);
    auto sums1 = [&] {
      mbar_wait(bar + 8 * (B_U + 1), layer);
      conv_sums(sa, 1, c);
      fence_async_smem();
      bar_arrive(8, 256);
    };
    if (S1_AT == 0) sums1();
    const uint4 s0 = ld_tagged(so), s1 = ld_tagged(so + 32);
    if (S1_AT == 0) st[0] = ld_tagged(xin + 128);
    mbar_wait(bar + 8 * B_XV2, layer);
#pragma unroll
    for (int j = 2; j < 4; j++) { xr[j] = ld_tagged(xin + j * (128 * LSEQ / 8)); st[j] = ld_tagged(xin + j * (128 * LSEQ / 8) + 128); }
    if (S1_AT == 1) sums1();
    if (S1_AT != 0) st[0] = ld_tagged(xin + 128);
    if (X_SENT > 1)
      for (int it = 0; !__all_sync(~0u, max(max(xr[2].x, xr[3].x), max(st[2].x, st[3].x)) != ~0u); it++) {
        if (it > (1 << 22)) __trap();
#pragma unroll
        for (int j = 2; j < 4; j++) { xr[j] = ld_tagged(xin + j * (128 * LSEQ / 8)); st[j] = ld_tagged(xin + j * (128 * LSEQ / 8) + 128); }
      }
    const RowNorm ro = row_norm(s0, s1);
#pragma unroll
    for (int j = 2; j < 4; j++) {
      sts128(ua + j * 32768, normalize(xr[j], rn));
      sts128(ua + j * 32768 + CV_UH, normalize(st[j], ro));
      __syncwarp();
      if (elect_one()) asm volatile("mbarrier.arrive.shared::cta.b64 _, [%0], 2;" ::"r"(bar + 8 * (B_U + j)) : "memory");
    }
    if (S1_AT == 2) sums1();
  }
}
__device__ __forceinline__ void conv_zero(uint32_t sb, int ht) {
  if (ht < 96) {
    const int ch = ht / 24, h2 = (ht / 12) & 1, qq = ht % 12;
    sts128(sb + cv_u(ch) + h2 * CV_UH + (128 + qq) * 16, make_uint4(0, 0, 0, 0));
  }
  if (ht >= 80) {
    const int i = ht - 80, ch = i / 12, q2 = i % 12;
    const int w2 = q2 < 2 ? 1 : q2 < 6 ? 2 : 3, cc = q2 < 2 ? q2 : q2 < 6 ? q2 - 2 : q2 - 6;
    sts128(sb + cv_pb(ch) + w2 * CV_PBW + (cc & 1) * (CV_PBW / 2) + (cc >> 1) * 16, make_uint4(0, 0, 0, 0));
  }
}

#define HANDOVER 1
template <int R>
__device__ __forceinline__ void conv_round(uint32_t sb, int layer, int wg, uint32_t* A, const uint32_t* P, uint32_t pb, uint32_t pe2) {
  const uint32_t bar = sb + SM_BAR;
  const int ch = 2 * R + 1 - wg;
  float acc[64];
  const uint64_t d = mkdesc(sb + cv_u(ch), CV_UH, 128, 0);
  FTS(39);
  if (R == 0) {
    mbar_wait(bar + 8 * (B_U + ch), layer);
    fence_reader();
  }
  sched_fence<3>();
  if (R == 1 || wg == 0) bar_sync(10 + ch, 256);
  if (layer == 0 && ch > 0 && ((PAUSE >> (ch - 1)) & 1)) mbar_wait(bar + 8 * (B_E + ch - 1), 0);
  if (layer == 0 && ch > 0 && ((PAUSE >> (ch + 3)) & 1)) mbar_wait(bar + 8 * (B_P + ch - 1), 0);
  FTS(41);
  if (ch == 0 && threadIdx.x == 128) TS(2 + layer * 20 + 13);
  wg_fence();
  conv_mmas<0, 1>(acc, A, d); conv_mmas<2, NA + 1>(acc, A, d);
  wg_commit();
  FTS(51);
  if (HANDOVER == 0 && (R == 0 || wg == 1)) bar_arrive(11 + ch, 256);
  bar_sync(7 + ch, 256);
  wg_fence();
  conv_mmas<1, 2>(acc, A, d); conv_mmas<NA + 1, 17>(acc, A, d);
  wgmma_ss<64, 1, 1>(acc, mkdesc(sb + cv_s(ch), 1024, 1024, 1), mkdesc(sb + cv_ft(ch), 256, 16, 0), 1);
  wgmma_ss<64, 1, 1>(acc, mkdesc(sb + cv_s(ch) + 2048, 1024, 1024, 1), mkdesc(sb + cv_ft(ch) + 512, 256, 16, 0), 1);
  wg_commit();
  if (HANDOVER == 1 && (R == 0 || wg == 1 || (G_WAIT == 3 && layer == 0))) bar_arrive(11 + ch, 256);
  FTS(61);
  wg_wait<0>();
#pragma unroll
  for (int j = 0; j < 16; j += 2)
    stsm4t(pb + R * 65536 - j * 128, packbf(acc[4 * j], acc[4 * j + 1]), packbf(acc[4 * j + 2], acc[4 * j + 3]),
           packbf(acc[4 * j + 4], acc[4 * j + 5]), packbf(acc[4 * j + 6], acc[4 * j + 7]));
  __syncwarp();
  if (elect_one()) mbar_arrive(bar + 8 * (B_P + ch));
  if (threadIdx.x == 0) TS(2 + layer * 20 + 14 + R);
  FTS(57);
  if (R == 0) {
    conv_unpark(A, P, opaque_tid() >> 10);
    mbar_wait(bar + 8 * (B_U + ch + 2), layer);
    fence_reader();
    conv_load<NP, 17>(A, pe2);
#pragma unroll
    for (int m = NP; m < 17; m++) A[4 * m + 3] = lds32(pe2 + 256 * m);
  }
}
__device__ __forceinline__ void conv_phase(const Params& p, uint32_t sb, int layer, int cta) {
  const int tid = opaque_tid();
  const int wg = __shfl_sync(~0u, tid >> 7, 0), w = __shfl_sync(~0u, (tid >> 5) & 3, 0);
  const uint32_t bar = sb + SM_BAR;
  uint32_t A[68], P[3 * NP];
  const uint32_t pe = sb + cv_pe(1 - wg) + 4 * (16 + 16 * w + 2 * ((tid & 31) >> 2) - 4 * (tid & 3));
  mbar_wait(bar + 8 * B_PE, layer);
  tensor_keepalive<2>();
  conv_load<0, 17>(A, pe);
#pragma unroll
  for (int m = 0; m < 17; m++) A[4 * m + 3] = copy_reg(A[4 * m], tid >> 10);
  if (wg == 0) {
    uint4 xr[4], st[4];
    if (PARK_FIRST) conv_park(P, pe + 65536);
    conv_prep_load(sb, layer, cta, tid + 128, xr, st);
    if (!PARK_FIRST) conv_park(P, pe + 65536);
    conv_prep<false>(sb, layer, cta, opaque_tid() + 128, xr, st, SumAddr());
  } else {
    conv_park(P, pe + 65536);
    if (KEEP & 8) mbar_wait(bar + 8 * B_GB, layer);
    tensor_keepalive<3>();
  }
  uint32_t pb;
  {
    const int l2 = opaque_tid() & 31, mt = l2 >> 3;
    pb = sb + cv_pb(1 - wg) + w * CV_PBW + (mt & 1) * (CV_PBW / 2) + (127 - 8 * (mt >> 1) - (l2 & 7) + w) * 16;
  }
  conv_round<0>(sb, layer, wg, A, P, pb, pe + 65536);
  conv_round<1>(sb, layer, wg, A, P, pb, 0);
  if (G_WAIT == 1 && layer == 0) mbar_wait(bar + 8 * (B_E + 3), layer);
  if (G_WAIT == 2 && layer == 0) mbar_wait(bar + 8 * (B_P + 3), layer);
}

__device__ __forceinline__ void final_phase(const Params& p, uint32_t sb, int cta, int wg, int w) {
  const int lane = opaque_tid() & 31, g = lane >> 2, t = lane & 3;
  constexpr int RS = 2 * DM;
  int it = 0;
  {
    const int lc = wg ? 0 : 3;
    const int p0 = (cta & 15) * 128 + 32 * w, c0 = 128 * lc + (cta >> 4) * 16;
    const bf16* src = g_xT + (size_t)(3 * DM + c0 + 4 * (g >> 1) + (g & 1)) * LSEQ + p0 + 8 * t;
    bf16* dst = p.out + (size_t)(2 * ((p0 & 1023) + 8 * (g >> 1) + (g & 1)) + (p0 >> 10)) * DM + c0 + 4 * t;
    if (wg == 0) {
      mbar_wait(sb + SM_BAR + 8 * (B_E + 3), 1);
      delay<D_FIN>();
    }
    uint4 a, b;
    for (;;) {
      a = ld_tagged((const uint4*)src); b = ld_tagged((const uint4*)(src + 2 * LSEQ));
      if (__all_sync(~0u, max(a.x, b.x) != ~0u)) break;
      if (++it > (1 << 22)) __trap();
    }
    if (threadIdx.x == 0) TS(42);
    *(uint2*)dst = make_uint2(movm_t(a.x), movm_t(b.x));
    *(uint2*)(dst + 2 * RS) = make_uint2(movm_t(a.y), movm_t(b.y));
    *(uint2*)(dst + 4 * RS) = make_uint2(movm_t(a.z), movm_t(b.z));
    *(uint2*)(dst + 6 * RS) = make_uint2(movm_t(a.w), movm_t(b.w));
  }
  if (wg == 1) {
    const int lc = 1 + (w >> 1);
    const int p0 = (cta & 31) * 64 + 32 * (w & 1), c0 = 128 * lc + (cta >> 5) * 32;
    const bf16* src = g_xT + (size_t)(3 * DM + c0 + 8 * (g >> 1) + (g & 1)) * LSEQ + p0 + 8 * t;
    bf16* dst = p.out + (size_t)(2 * ((p0 & 1023) + 8 * (g >> 1) + (g & 1)) + (p0 >> 10)) * DM + c0 + 8 * t;
    mbar_wait(sb + SM_BAR + 8 * (B_E + lc), 1);
    if (lc >= FIN_D0) delay<D_FIN2>();
    uint4 v[4];
    for (;;) {
#pragma unroll
      for (int q = 0; q < 4; q++) v[q] = ld_tagged((const uint4*)(src + 2 * q * LSEQ));
      if (__all_sync(~0u, max(max(v[0].x, v[1].x), max(v[2].x, v[3].x)) != ~0u)) break;
      if (++it > (1 << 22)) __trap();
    }
    *(uint4*)dst = make_uint4(movm_t(v[0].x), movm_t(v[1].x), movm_t(v[2].x), movm_t(v[3].x));
    *(uint4*)(dst + 2 * RS) = make_uint4(movm_t(v[0].y), movm_t(v[1].y), movm_t(v[2].y), movm_t(v[3].y));
    *(uint4*)(dst + 4 * RS) = make_uint4(movm_t(v[0].z), movm_t(v[1].z), movm_t(v[2].z), movm_t(v[3].z));
    *(uint4*)(dst + 6 * RS) = make_uint4(movm_t(v[0].w), movm_t(v[1].w), movm_t(v[2].w), movm_t(v[3].w));
  }
  if (threadIdx.x == 0) TS(43);
  if (threadIdx.x == 192) TS(63);
  if (threadIdx.x == 160) TS(53);
  if (threadIdx.x == 0) LTS(1);
}

struct cplx { float r, i; };
__device__ __forceinline__ cplx cmul(cplx a, cplx b) { return {fmaf(a.r, b.r, -a.i * b.i), fmaf(a.r, b.i, a.i * b.r)}; }
__device__ __forceinline__ cplx csqr(cplx a) { return {fmaf(a.r, a.r, -a.i * a.i), (a.r + a.r) * a.i}; }
__device__ __forceinline__ cplx cexp_l(float ar2, float ai, float l) {
  const float m = ex2(ar2 * l);
  const float x = ai * l;
  return {m * __cosf(x), m * __sinf(x)};
}

__device__ __forceinline__ void colsum_publish(uint32_t sb, int rb, int hg, int ht, uint32_t tag) {
  const int lane = ht & 31, q = lane & 15, h = lane >> 4;
  const uint32_t src = sb + SM_CW + (ht >> 5) * 4096 + h * 128 + (q & 1) * 8;
  float s[4] = {0.f, 0.f, 0.f, 0.f};
#pragma unroll 8
  for (int r = 0; r < 16; r++) {
    const float2 v = lds64f(src + r * 256 + (((q >> 1) ^ ((2 * r + h) & 7)) << 4));
    s[0] += bf_lo(__float_as_uint(v.x)); s[1] += bf_hi(__float_as_uint(v.x));
    s[2] += bf_lo(__float_as_uint(v.y)); s[3] += bf_hi(__float_as_uint(v.y));
  }
#pragma unroll
  for (int k = 0; k < 4; k++) s[k] += __shfl_xor_sync(~0u, s[k], 16);
  if (h == 0)
    st_tagged3(&g_colsum[(hg * 16 + rb) * 48 + (ht >> 5) * 16 + q], (__float_as_uint(s[0]) & ~7u) | tag, __float_as_uint(s[1]),
               __float_as_uint(s[2]), __float_as_uint(s[3]));
}
__device__ __forceinline__ void colsum_gather(uint32_t sb, int hg, int ht, uint32_t tag) {
  const int lane = ht & 31, rec = (ht >> 5) * 16 + (lane & 15);
  const uint4* src = &g_colsum[(hg * 16 + (lane >> 4) * 8) * 48 + rec];
  float s[4] = {0.f, 0.f, 0.f, 0.f};
#pragma unroll 1
  for (int h = 0; h < 2; h++, src += 4 * 48) {
    uint4 v[4];
    int it = 0;
    do {
#pragma unroll
      for (int i = 0; i < 4; i++) v[i] = ld_tagged(src + i * 48);
      if (++it > (1 << 22)) __trap();
    } while (!__all_sync(~0u, (v[0].x & 7u) == tag && (v[1].x & 7u) == tag && (v[2].x & 7u) == tag && (v[3].x & 7u) == tag));
#pragma unroll
    for (int i = 0; i < 4; i++) {
      s[0] += __uint_as_float(v[i].x & ~7u); s[1] += __uint_as_float(v[i].y); s[2] += __uint_as_float(v[i].z); s[3] += __uint_as_float(v[i].w);
    }
  }
#pragma unroll
  for (int k = 0; k < 4; k++) s[k] += __shfl_xor_sync(~0u, s[k], 16);
  if (lane < 16) sts128f(sb + SM_CS + rec * 16, s[0], s[1], s[2], s[3]);
}

__device__ __forceinline__ uint32_t packh(float lo, float hi) { uint32_t r; asm("cvt.rn.f16x2.f32 %0, %1, %2;" : "=r"(r) : "f"(hi), "f"(lo)); return r; }
__device__ __forceinline__ void mma_f16(float* d, uint32_t a0, uint32_t a1, uint32_t a2, uint32_t a3, uint32_t b0, uint32_t b1) {
  asm volatile("mma.sync.aligned.m16n8k16.row.col.f32.f16.f16.f32 {%0,%1,%2,%3}, {%4,%5,%6,%7}, {%8,%9}, {%0,%1,%2,%3};"
      : "+f"(d[0]), "+f"(d[1]), "+f"(d[2]), "+f"(d[3]) : "r"(a0), "r"(a1), "r"(a2), "r"(a3), "r"(b0), "r"(b1));
}
struct HSeed { uint32_t r, i; };
__device__ __forceinline__ HSeed hseed(cplx s) { return {packh(s.r, s.r), packh(s.i, s.i)}; }
__device__ __forceinline__ void hcmul(uint32_t& o_r, uint32_t& o_i, uint32_t br, uint32_t bi, HSeed s) {
  asm("{\n.reg .b32 t, u;\nmul.rn.f16x2 t, %3, %5;\nneg.f16x2 t, t;\nmul.rn.f16x2 u, %3, %4;\nfma.rn.f16x2 %0, %2, %4, t;\nfma.rn.f16x2 %1, %2, %5, u;\n}"
      : "=&r"(o_r), "=&r"(o_i) : "r"(br), "r"(bi), "r"(s.r), "r"(s.i));
}
struct HTile { uint32_t r[4], i[4]; };
__device__ __forceinline__ void tile_set(HTile& t, int k, cplx a, cplx b) { t.r[k] = packh(a.r, b.r); t.i[k] = packh(a.i, b.i); }
__device__ __forceinline__ void tile_upper(HTile& t, HSeed s) { hcmul(t.r[2], t.i[2], t.r[0], t.i[0], s); hcmul(t.r[3], t.i[3], t.r[1], t.i[1], s); }
__device__ __forceinline__ HTile tile_shift(const HTile& t, HSeed s) {
  HTile o;
#pragma unroll
  for (int k = 0; k < 4; k++) hcmul(o.r[k], o.i[k], t.r[k], t.i[k], s);
  return o;
}
__device__ __forceinline__ void tile_put(const HTile& t, uint32_t a) {
  sts128(a, make_uint4(t.r[0], t.r[1], t.r[2], t.r[3]));
  sts128(a + 512, make_uint4(t.i[0], t.i[1], t.i[2], t.i[3]));
}
__device__ __forceinline__ HTile tile_get(uint32_t a) { HTile o; ldsm4t(o.r, a); ldsm4t(o.i, a + 512); return o; }
__device__ __forceinline__ void tile_mma(float* T, const HTile& a0, const HTile& a1, const HTile& b) {
  mma_f16(T, a0.r[0], a0.r[1], a0.r[2], a0.r[3], b.r[0], b.r[1]);
  mma_f16(T, a0.i[0], a0.i[1], a0.i[2], a0.i[3], b.i[0], b.i[1]);
  mma_f16(T, a1.r[0], a1.r[1], a1.r[2], a1.r[3], b.r[2], b.r[3]);
  mma_f16(T, a1.i[0], a1.i[1], a1.i[2], a1.i[3], b.i[2], b.i[3]);
}
__device__ __forceinline__ void tile_mma2(float* T, float* U, const HTile& a0, const HTile& a1, const HTile& b, const HTile& c) {
  mma_f16(T, a0.r[0], a0.r[1], a0.r[2], a0.r[3], b.r[0], b.r[1]);
  mma_f16(U, a0.r[0], a0.r[1], a0.r[2], a0.r[3], c.r[0], c.r[1]);
  mma_f16(T, a0.i[0], a0.i[1], a0.i[2], a0.i[3], b.i[0], b.i[1]);
  mma_f16(U, a0.i[0], a0.i[1], a0.i[2], a0.i[3], c.i[0], c.i[1]);
  mma_f16(T, a1.r[0], a1.r[1], a1.r[2], a1.r[3], b.r[2], b.r[3]);
  mma_f16(U, a1.r[0], a1.r[1], a1.r[2], a1.r[3], c.r[2], c.r[3]);
  mma_f16(T, a1.i[0], a1.i[1], a1.i[2], a1.i[3], b.i[2], b.i[3]);
  mma_f16(U, a1.i[0], a1.i[1], a1.i[2], a1.i[3], c.i[2], c.i[3]);
}
__device__ __forceinline__ void kgen_unit(uint32_t tab, uint32_t taba, float ar2, float ai, cplx c, float (&T)[5][4]) {
  const cplx z1 = cexp_l(ar2, ai, 1.f), z16 = cexp_l(ar2, ai, 16.f), z256 = cexp_l(ar2, ai, 256.f);
  HTile a0, a1, b0, b1;
  {
    const cplx y1 = {z16.r, -z16.i}, y2 = csqr(y1), y3 = cmul(y2, y1), y4 = csqr(y2), y5 = cmul(y4, y1), y6 = csqr(y3), y7 = cmul(y4, y3);
    HTile t;
    tile_set(t, 0, {1.f, 0.f}, y1); tile_set(t, 1, y2, y3); tile_set(t, 2, y4, y5); tile_set(t, 3, y6, y7);
    const HTile u = tile_shift(t, hseed(csqr(y4)));
    __syncwarp();
    tile_put(t, tab); tile_put(u, tab + 1024);
    __syncwarp();
    a0 = tile_get(taba); a1 = tile_get(taba + 256);
  }
  const cplx z2 = csqr(z1), z4 = csqr(z2), z8 = csqr(z4);
  const HSeed h8 = hseed(z8);
  const cplx d = cmul(c, z256), e = cmul(d, z256);
  {
    const cplx z512 = csqr(z256), f = cmul(e, z512), f8 = cmul(f, z8), f16 = cmul(f, z16), e4 = cmul(e, z4);
    HTile t, u;
    tile_set(t, 0, e4, cmul(e, z8)); tile_set(t, 1, cmul(e4, z8), cmul(e, z16));
    tile_upper(t, hseed(z256));
    tile_set(u, 0, f8, f16); tile_set(u, 1, cmul(f8, z256), cmul(f16, z256));
    tile_upper(u, hseed(z512));
    __syncwarp();
    tile_put(t, tab); tile_put(u, tab + 1024);
    __syncwarp();
    b0 = tile_get(tab); b1 = tile_get(tab + 1024);
  }
  {
    const cplx d2 = cmul(d, z2), d4 = cmul(d, z4);
    HTile t;
    tile_set(t, 0, d2, d4); tile_set(t, 1, cmul(d2, z4), cmul(d, z8));
    tile_upper(t, h8);
    __syncwarp();
    tile_put(t, tab);
    __syncwarp();
    tile_mma2(T[3], T[4], a0, a1, b0, b1);
    b0 = tile_get(tab);
  }
  {
    const cplx c1 = cmul(c, z1), c2 = cmul(c, z2), c3 = cmul(c1, z2), c4 = cmul(c, z4);
    HTile t;
    tile_set(t, 0, c1, c2); tile_set(t, 1, c3, c4); tile_set(t, 2, cmul(c1, z4), cmul(c2, z4)); tile_set(t, 3, cmul(c3, z4), cmul(c4, z4));
    const HTile u = tile_shift(t, h8);
    __syncwarp();
    tile_put(t, tab); tile_put(u, tab + 1024);
    __syncwarp();
    tile_mma(T[2], a0, a1, b0);
    b0 = tile_get(tab); b1 = tile_get(tab + 1024);
    tile_mma2(T[0], T[1], a0, a1, b0, b1);
  }
}
struct ModeIn { uint2 ar, ai, br, bi, cr, ci; };
__device__ __forceinline__ ModeIn load_modes(const Params& p, int idx) {
  return {*(const uint2*)(p.a_re + idx), *(const uint2*)(p.a_im + idx), *(const uint2*)(p.b_re + idx),
          *(const uint2*)(p.b_im + idx), *(const uint2*)(p.c_re + idx), *(const uint2*)(p.c_im + idx)};
}
__device__ __forceinline__ float bf_el(uint2 v, int k) { const uint32_t x = (k & 2) ? v.y : v.x; return (k & 1) ? bf_hi(x) : bf_lo(x); }
struct KGen { float4 cur; float T[5][4]; };
__device__ __forceinline__ uint32_t kgen_slot(uint32_t sb, int ht, int u) {
  return sb + (u < 3 ? SM_KC + (ht >> 5) * (KC_STRIDE * 2) + (u - 1) * 512 + (ht & 31) * 16 + 16 : SM_HALO + 1024 + ht * 16);
}
__device__ __forceinline__ void kgen_setup(KGen& s, uint32_t sb, int cta, int ht, const ModeIn& in, bf16 logdt, bf16 dskip) {
  const float dt = __bfloat162float(__float2bfloat16_rn(expf(__bfloat162float(logdt))));
  float mx = 0.f, k0 = 0.f, ar2[4];
  cplx c[4];
#pragma unroll
  for (int k = 0; k < 4; k++) {
    ar2[k] = (dt * bf_el(in.ar, k)) * 1.4426950408889634f;
    c[k] = cmul({bf_el(in.cr, k), bf_el(in.ci, k)}, {dt * bf_el(in.br, k), dt * bf_el(in.bi, k)});
    k0 += c[k].r;
    mx = fmaxf(mx, fmaxf(fabsf(c[k].r), fabsf(c[k].i)) * ex2(fmaxf(ar2[k] * 2048.f, 0.f)));
  }
  const int ex = min(max(267 - (int)(__reduce_max_sync(~0u, __float_as_uint(mx)) >> 23), 1), 253);
  const float sc = __uint_as_float(ex << 23);
#pragma unroll
  for (int o = 16; o > 0; o >>= 1) k0 += __shfl_xor_sync(~0u, k0, o);
  if ((ht & 31) == 0) {
    const uint32_t kc = sb + SM_KC + (ht >> 5) * (KC_STRIDE * 2);
    sts16(kc, __bfloat16_as_ushort(__float2bfloat16_rn(k0 + __bfloat162float(dskip))));
    sts16(kc + 641 * 2, 0);
    sts32f(kc + 644 * 2, __uint_as_float((254 - ex) << 23));
  }
  s.cur = make_float4(ar2[0], dt * bf_el(in.ai, 0), c[0].r * sc, c[0].i * sc);
#pragma unroll
  for (int k = 1; k < 4; k++) sts128f(kgen_slot(sb, ht, k), ar2[k], dt * bf_el(in.ai, k), c[k].r * sc, c[k].i * sc);
#pragma unroll
  for (int i = 0; i < 5; i++) s.T[i][0] = s.T[i][1] = s.T[i][2] = s.T[i][3] = 0.f;
}
__device__ __forceinline__ void kgen_finish(KGen& s, uint32_t sb, int cta, int ht) {
  const int w = ht >> 5, lane = ht & 31, g = lane >> 2, t = lane & 3;
  const uint32_t kc = sb + SM_KC + w * KC_STRIDE * 2;
  __syncwarp();
  const float inv = __uint_as_float(lds32(kc + 644 * 2));
  auto put = [&](int idx, float v) {
    sts16(kc + idx * 2, __bfloat16_as_ushort(__float2bfloat16_rn(v)));
  };
#pragma unroll
  for (int hi = 0; hi < 2; hi++)
#pragma unroll
    for (int lo = 0; lo < 2; lo++) {
      const int i = g + 8 * hi, j = 2 * t + lo, e = 2 * hi + lo;
      put(16 * i + 1 + j, s.T[0][e] * inv);
      put(16 * i + 9 + j, s.T[1][e] * inv);
      put(257 + 8 * i + j, s.T[2][e] * inv);
      put(385 + 4 * i + (j & 3) + 64 * (j >> 2), s.T[3][e] * inv);
      put(513 + 2 * i + lo + 32 * t, s.T[4][e] * inv);
    }
}

__device__ __forceinline__ void expand_taps(uint32_t sb, int ht) {
  const int ch = ht >> 5, lane = ht & 31;
  const uint32_t kc = sb + SM_KC + ch * KC_STRIDE * 2;
  const uint32_t dst0 = sb + cv_pe(ch);
  auto put = [&](int G, uint32_t u0, uint32_t u1, uint32_t v0, uint32_t v1, uint32_t v2, uint32_t v3, uint32_t v4, uint32_t v5, uint32_t v6, uint32_t v7) {
    const uint32_t dst = dst0 + G * 32;
    sts128(dst, make_uint4(v0 | (u0 << 16), v1 | (u1 << 16), v2 | (v0 << 16), v3 | (v1 << 16)));
    sts128(dst + 16, make_uint4(v4 | (v2 << 16), v5 | (v3 << 16), v6 | (v4 << 16), v7 | (v5 << 16)));
  };
  {
    const uint4 q = lds128(kc + lane * 16);
    const uint32_t pv = lane ? lds32(kc + lane * 16 - 4) : 0u;
    const uint32_t dst = dst0 + (lane + 2) * 32;
    sts128(dst, make_uint4(__byte_perm(q.x, pv, 0x5410), __byte_perm(q.x, pv, 0x7632), __byte_perm(q.y, q.x, 0x5410), __byte_perm(q.y, q.x, 0x7632)));
    sts128(dst + 16, make_uint4(__byte_perm(q.z, q.y, 0x5410), __byte_perm(q.z, q.y, 0x7632), __byte_perm(q.w, q.z, 0x5410), __byte_perm(q.w, q.z, 0x7632)));
    if (lane < 4) sts128(dst0 + lane * 16, make_uint4(0, 0, 0, 0));
  }
  uint32_t a[5], b[2][3], fv[4];
  {
    const uint32_t s1 = kc + 2 * (256 + 4 * lane);
#pragma unroll
    for (int k = 0; k < 5; k++) a[k] = lds16(s1 + 2 * k);
#pragma unroll
    for (int u = 0; u < 2; u++) {
      const uint32_t s2 = kc + 2 * (384 + 2 * (lane + 32 * u));
#pragma unroll
      for (int k = 0; k < 3; k++) b[u][k] = lds16(s2 + 2 * k);
    }
#pragma unroll
    for (int k = 0; k < 4; k++) fv[k] = lds16(kc + 2 * (640 - 4 * lane - k));
  }
  const uint32_t am1 = lds16(kc + 2 * (lane ? 256 + 4 * lane : 255)), am2 = lds16(kc + 2 * (lane ? 255 + 4 * lane : 254));
  const uint32_t bm2 = lds16(kc + 2 * (lane ? 384 + 2 * lane : 383)), k1024 = lds16(kc + 2 * 512);
  put(34 + lane, am2, am1, a[0], a[0], a[1], a[2], a[2], a[2], a[3], a[4]);
#pragma unroll
  for (int u = 0; u < 2; u++) put(66 + lane + 32 * u, u ? b[u][0] : bm2, b[u][0], b[u][0], b[u][0], b[u][0], b[u][1], b[u][1], b[u][1], b[u][2], b[u][2]);
  if (lane < 10) {
    const uint32_t v = lane == 0 ? k1024 : 0u;
    put(130 + lane, v, v, v, v, v, v, v, 0u, 0u, 0u);
  }
  const uint32_t ft = sb + cv_ft(ch) + 4 * lane;
#pragma unroll
  for (int ty = 0; ty < 2; ty++) {
    const uint32_t v = fv[ty] | (fv[ty + 2] << 16);
    sts32f(ft + ty * 512, __uint_as_float(v));
    sts32f(ft + ty * 512 + 128, 0.f);
    sts32f(ft + ty * 512 + 256 + (lane < 2 ? 120 : -8), __uint_as_float(lane < 2 ? 0u : v));
    sts32f(ft + ty * 512 + 384, 0.f);
  }
}

__device__ __forceinline__ int role_id() { int v; asm volatile("mov.u32 %0, %%ctaid.x;" : "=r"(v)); return v; }
#define GMAP 8
__device__ __forceinline__ int role_rb(int cta) { return 4 * (cta >> 5) + (cta & 3); }
__device__ __forceinline__ int role_hg(int cta) { return 2 * (((cta >> 3) & 3) ^ (((cta >> 5) & 1) * 3)) + ((cta >> 2) & 1); }
__device__ __forceinline__ int role_rb2(int cta) { return cta >> 3; }
__device__ __forceinline__ int role_q2(int cta) { return cta & 7; }

__global__ void __launch_bounds__(NTHREADS, 1) fused_kernel(const __grid_constant__ Params p) {
  extern __shared__ __align__(1024) uint8_t smem[];
  const uint32_t sb = s32(smem);
  const int tid = threadIdx.x, lane = tid & 31;
  const int warp = __shfl_sync(~0u, tid >> 5, 0);
  const uint32_t bar = sb + SM_BAR;
  if (tid == 0) TS(0);
  const int cta0 = role_id();
  if (warp == 0 && elect_one()) {
    const int rb = role_rb(cta0), hg = role_hg(cta0);
#pragma unroll
    for (int c = 0; c < 2; c++) { mbar_init(bar + 8 * (B_XF + c), 1); mbar_init(bar + 8 * (B_KVF + c), 1); }
    fence_async_smem();
#pragma unroll
    for (int c = 0; c < 2; c++) {
      mbar_expect(bar + 8 * (B_XF + c), 16384);
      tma_ld(sb + SM_X + c * 16384, &p.mapX128, (rb >> 3) * DM + c * 64, (rb & 7) * 128, bar + 8 * (B_XF + c));
      mbar_expect(bar + 8 * (B_KVF + c), 24576);
      tma_ld3(sb + SM_W + c * 24576, &p.mapW3, hg * 64, c * 64, 0, bar + 8 * (B_KVF + c));
    }
  }
  if (warp == 2) tensor_keepalive<4>();
  if (warp == 1 && elect_one()) {
    const int rb = role_rb(cta0), hg = role_hg(cta0);
#pragma unroll
    for (int c = 2; c < 8; c++) mbar_init(bar + 8 * (B_XF + c), 1);
    mbar_init(bar + 8 * (B_KVF + 2), 1); mbar_init(bar + 8 * B_CW, 1);
    fence_async_smem();
    delay<D_START>();
    mbar_expect(bar + 8 * B_CW, 12288);
    tma_ld3(sb + SM_CW, &p.mapW3h, hg * 64, rb * 32, 0, bar + 8 * B_CW);
#pragma unroll
    for (int c = 2; c < 8; c++) {
      mbar_expect(bar + 8 * (B_XF + c), 16384);
      tma_ld(sb + SM_X + c * 16384, &p.mapX128, (rb >> 3) * DM + c * 64, (rb & 7) * 128, bar + 8 * (B_XF + c));
      if (c < 3) {
        mbar_expect(bar + 8 * (B_KVF + c), 24576);
        tma_ld3(sb + SM_W + c * 24576, &p.mapW3, hg * 64, c * 64, 0, bar + 8 * (B_KVF + c));
      }
    }
    TS(56);
  }
  if ((warp & 2) != 0 && warp < 15 && elect_one()) {
    const int grp = 1 + (warp & 1) + 2 * (warp >> 2), cnt = grp < 4 ? 1 : grp < 5 ? 2 : grp < 7 ? 4 : 8;
#pragma unroll
    for (int k = 0; k < 10; k++)
      if (k != 0 || grp > 3 || grp == 2) mbar_init(bar + 8 * (10 * grp + k), cnt);
    fence_async_smem();
  }

  if (warp < 8) {
    if (tid == 0) TS(1);
    asm volatile("setmaxnreg.inc.sync.aligned.u32 %0;" ::"n"(R_CONS));
    const int cta = role_id();
    auto warp_id = [] { return __shfl_sync(~0u, opaque_tid() >> 5, 0); };
    tensor_keepalive<0>();
    if (tid == 0) TS(54);
#pragma unroll 1
    for (int layer = 0; layer < 2; layer++) {
      { const int cw = warp_id(); attn_phase(p, sb, layer, role_rb(cta), role_hg(cta), cw >> 2, cw & 3); }
      if (STOP == 1 + 3 * layer) return;
      { const int cw = warp_id(); proj_phase(p, sb, layer, role_rb2(cta), role_q2(cta), cw >> 2, cw & 3); }
      if (STOP == 2 + 3 * layer) return;
      conv_phase(p, sb, layer, cta);
      if (STOP == 3 + 3 * layer) return;
    }
    { const int cw = warp_id(); final_phase(p, sb, cta, cw >> 2, cw & 3); }
  } else if (warp < 12) {
    asm volatile("setmaxnreg.dec.sync.aligned.u32 %0;" ::"n"(R_HELP));
    const int ht = tid - 256;
    const int cta = role_id(), rb = role_rb(cta), hg = role_hg(cta);
    unsigned ep0 = 0;
    if (ht == 0) ep0 = ld_relaxed(&g_cnt[C_CS * 32]);
    bar_sync(0, NTHREADS);
    if (ht == 0) {
      asm volatile("st.shared.v4.u32 [%0], {%1, 0, 0, 0};" ::"r"(sb + SM_EP), "r"(ep0 / NCTA) : "memory");
      mbar_arrive(bar + 8 * B_EP);
    }
    mbar_wait(bar + 8 * B_EP, 0);
    stats_publish(sb, 0, rb, hg, opaque_tid() - 256, part_tag(lds32(sb + SM_EP), 0));
    if (ht < 48) {
      const bf16* q = (&p.a_re)[ht >> 3];
      asm volatile("prefetch.global.L2 [%0];" ::"l"(q + cv_chan(cta, (ht >> 1) & 3) * 128 + (ht & 1) * 64));
    }
    {
      KGen kg;
      const uint32_t tab0 = sb + ((ht >> 5) < 2 ? SM_T : SM_T2 - 4096) + (ht >> 5) * 2048;
      const uint32_t tab = tab0 + (ht & 31) * 16, taba = tab0 + ((ht >> 3) & 1) * 1024 + (((ht >> 1) & 8) + (ht & 7)) * 16;
      delay<D_ST0>();
      stats_gather(sb, rb, opaque_tid() - 256, part_tag(lds32(sb + SM_EP), 0));
      if (ht == 0) TS(40);
      const int chn = cv_chan(cta, ht >> 5);
      const ModeIn modes = load_modes(p, chn * 128 + (ht & 31) * 4);
      const bf16 logdt = p.log_dt[chn], dskip = p.dskip[chn];
      if (!HALO_W14 && KG_START != 4) halo_receive(sb, 0, rb, hg, opaque_tid() - 256);
      if (KG_START == 1) mbar_wait(bar + 8 * B_HF, 0);
      kgen_setup(kg, sb, cta, ht, modes, logdt, dskip);
      if (!HALO_W14 && KG_START == 4) halo_receive(sb, 0, rb, hg, opaque_tid() - 256);
      if (KG_START == 2) mbar_wait(bar + 8 * B_HF, 0);
      if (KG_START == 3) mbar_wait(bar + 8 * B_QDONE, 0);
#pragma unroll 1
      for (int u = 0; u < 4; u++) {
        if (u == KG_PRE) {
          KTS(39);
          mbar_wait(bar + 8 * B_AD, 0);
          KTS(41);
        }
        kgen_unit(tab, taba, kg.cur.x, kg.cur.y, {kg.cur.z, kg.cur.w}, kg.T);
        kg.cur = lds128f(kgen_slot(sb, opaque_tid() - 256, u + 1));
      }
      kgen_finish(kg, sb, cta, opaque_tid() - 256);
    }
    KTS(51);
    bar_sync(4, 128);
#pragma unroll 1
    for (int layer = 0; layer < 2; layer++) {
      if (STOP <= 1 + 3 * layer) return;
      mbar_wait(bar + 8 * B_SG, layer);
      expand_taps(sb, opaque_tid() - 256);
      conv_zero(sb, opaque_tid() - 256);
      if (ht == 0) TS(52 + layer);
      warp_release(bar + 8 * B_PE);
      if (STOP <= 2 + 3 * layer) return;
      {
        uint4 xr[4], st[4];
        const int c = opaque_tid() - 256;
        const SumAddr sa = conv_sum_addr(sb, c);
        conv_prep_load(sb, layer, cta, c, xr, st);
        conv_prep<true>(sb, layer, cta, c, xr, st, sa);
        if (layer == 1 && ht == 0) TS(62);
        const int ahead = layer ? S_AHEAD1 : S_AHEAD0;
        mbar_wait(bar + 8 * (B_U + 3), layer);
#pragma unroll
        for (int lc = 0; lc < 4; lc++) {
          if (lc < 3 && lc + ahead > 1 && lc + ahead < 4) {
            conv_sums(sa, lc + ahead, c);
            fence_async_smem();
            bar_arrive(7 + lc + ahead, 256);
            sched_fence<4>();
          }
          if (lc == 0) st[1] = ldcg128(g_xT + (size_t)(2 * layer * DM + cv_chan(cta, 1)) * LSEQ + (c + 128) * 8);
          conv_epi(sb, layer, cta, lc, c, xr[lc], st[lc]);
          warp_release(bar + 8 * (B_E + lc));
          sched_fence<5>();
          if (layer == 1 && lc == 3 && ht == 0) TS(38);
        }
      }
      if (layer == 0 && STOP > 3) {
        const int c1 = role_id();
        stats_publish(sb, 1, role_rb(c1), role_hg(c1), opaque_tid() - 256, part_tag(lds32(sb + SM_EP), 2));
        delay<D_ST>();
        stats_gather(sb, role_rb(c1), opaque_tid() - 256, part_tag(lds32(sb + SM_EP), 2));
        if (ht == 0) TS(25);
        if (!HALO_W14) halo_receive(sb, 1, role_rb(c1), role_hg(c1), opaque_tid() - 256);
      }
    }
  } else {
    asm volatile("setmaxnreg.dec.sync.aligned.u32 %0;" ::"n"(512 - 2 * R_CONS - R_HELP));
    const int cta = role_id(), rb = role_rb(cta), hg = role_hg(cta), rb2 = role_rb2(cta), q2 = role_q2(cta);
    bar_sync(0, NTHREADS);
    if (warp != 12) {
      mbar_wait(bar + 8 * B_EP, 0);
      const uint32_t tag = lds32(sb + SM_EP) % 7 + 1;
      mbar_wait(bar + 8 * B_CW, 0);
      colsum_publish(sb, rb, hg, tid - 416, tag);
      if (tid == 416) TS(50);
      delay<D_CS>();
      colsum_gather(sb, hg, tid - 416, tag);
      __syncwarp();
      if (tid == 416) TS(55);
    }
    if (elect_one()) mbar_arrive(bar + 8 * B_CSF);
    if (warp == 12) {
      if (elect_one()) {
        unsigned epoch = 0;
#pragma unroll 1
        for (int layer = 0; layer < 2; layer++) {
          auto ld_w = [&](int c, int slot) {
            const uint32_t b = bar + 8 * (B_KVF + c);
            mbar_expect(b, 24576);
            tma_ld3(sb + SM_W + slot * 24576, &p.mapW3, hg * 64, c * 64, 0, b);
          };
          if (layer == 0) {
            mbar_wait(bar + 8 * (B_KVF + 2), 0);
            if (rb2 < 4) tma_prefetch2(&p.mapWo128, q2 * 64, rb2 * 128);
            asm volatile("prefetch.tensormap [%0];" ::"l"(&p.mapO) : "memory");
            asm volatile("prefetch.tensormap [%0];" ::"l"(&p.mapO128) : "memory");
            asm volatile("prefetch.tensormap [%0];" ::"l"(&p.mapXT3) : "memory");
            mbar_wait(bar + 8 * B_EP, 0);
            epoch = lds32(sb + SM_EP);
          } else {
            mbar_wait(bar + 8 * (B_U + 3), 0);
            ld_w(0, 0); ld_w(1, 1); ld_w(2, 2);
          }
          {
            int slot = 0;
#pragma unroll 1
            for (int c = 3; c < 8; c++) {
              mbar_wait(bar + 8 * (B_KVE + c - 3), layer);
              ld_w(c, slot);
              slot = slot == 2 ? 0 : slot + 1;
            }
          }
          if (STOP <= 1 + 3 * layer) return;
          const int early = layer ? WO_E1 : WO_E0;
          mbar_wait(bar + 8 * B_STF, layer);
          fence_async_smem();
          mbar_expect(bar + 8 * B_WOF, 65536);
#pragma unroll
          for (int c = 0; c < 4; c++) if (c < early) tma_ld(sb + SM_WO + c * 16384, &p.mapWo128, q2 * 64, c * 128, bar + 8 * B_WOF);
          mbar_wait(bar + 8 * B_QDONE, layer);
          mbar_wait(bar + 8 * B_HF, layer);
#pragma unroll
          for (int c = 0; c < 4; c++) if (c >= early) tma_ld(sb + SM_WO + c * 16384, &p.mapWo128, q2 * 64, c * 128, bar + 8 * B_WOF);
          {
            const uint32_t b = bar + 8 * B_RF;
            mbar_expect(b, 16384);
            if (layer == 0) tma_ld(sb + SM_R, &p.mapX128, (rb2 >> 3) * DM + q2 * 64, (rb2 & 7) * 128, b);
            else tma_ld3(sb + SM_R, &p.mapXT3, 0, DM + q2 * 64, rb2 * 2, b);
          }
#pragma unroll
          for (int c = 0; c < 8; c++) mbar_expect(bar + 8 * (B_OF + c), 16384);
          spin_until(&g_cnt[(C_O + rb2) * 32], (2 * epoch + layer + 1) * 8);
          fence_async_global();
#pragma unroll
          for (int c = 0; c < 8; c++) {
            if (c == 6) { mbar_wait(bar + 8 * B_OST, layer); fence_async_smem(); }
            tma_ld(sb + sm_o(c), &p.mapO128, c * 64, rb2 * 128, bar + 8 * (B_OF + c));
          }
          if (STOP <= 3 + 3 * layer) return;
        }
      }
    } else if (warp == 13) {
      if (elect_one() && STOP > 1) {
        const unsigned target = (lds32(sb + SM_EP) + 1) * NCTA;
        auto after_proj = [&](int layer) {
          mbar_wait(bar + 8 * XV_AT, layer);
          spin_until(&g_cnt[C_CS * 32 + 2 + layer], target);
          mbar_arrive(bar + 8 * B_XV);
          spin_until(&g_cnt[C_CS * 32 + 4 + layer], target);
          mbar_arrive(bar + 8 * B_XV2);
        };
        after_proj(0);
        if (STOP <= 3) return;
        auto ld_x = [&](int c) { tma_ld3(sb + SM_X + c * 16384, &p.mapXT3, 0, DM + c * 64, rb * 2, bar + 8 * (B_XF + c)); };
#pragma unroll
        for (int c = 0; c < 8; c++) mbar_expect(bar + 8 * (B_XF + c), 16384);
        spin_until(&g_cnt[C_G1 * 32], target);
        fence_async_global();
        fence_async_smem();
        ld_x(0); ld_x(1);
        int done = 1, it = 0;
        while (done < 4) {
          const uint4 v = ld_tagged((const uint4*)&g_cnt[C_G1 * 32]);
          const int n = 4 + ((int)(v.y - target) >> 31) + ((int)(v.z - target) >> 31) + ((int)(v.w - target) >> 31);
          if (n == done) { if (++it > (1 << 23)) __trap(); continue; }
          if (n == 4) TS(44);
          fence_async_global();
          fence_async_smem();
          if (done == 1) { ld_x(2); ld_x(3); }
          const int h = hg >> 2;
          if (done < 3 && n >= 3) ld_x(4 + h);
          if (n == 4) ld_x(6 + h);
          if (done < 3 && n >= 3) ld_x(5 - h);
          if (n == 4) ld_x(7 - h);
          done = n;
        }
        if (STOP <= 4) return;
        after_proj(1);
      }
    } else if (warp == 15) {
      mbar_wait(bar + 8 * B_EP, 0);
      const unsigned epoch = lds32(sb + SM_EP);
#pragma unroll 1
      for (int layer = 0; layer < 2; layer++) {
        constexpr int NX = X_SENT == 0 ? 1 : 2 * X_SENT;
#pragma unroll
        for (int i = 0; i < NX + 2; i++) {
          mbar_wait(bar + 8 * (B_KVF + (FILL_AT + i / FILL_N < 7 ? FILL_AT + i / FILL_N : 7)), layer);
          uint4* dst = (uint4*)(g_xT + (size_t)(i < NX ? 2 * layer * DM + cv_chan(cta, i) : 3 * DM + cv_chan(cta, 2 * layer + i - NX)) * LSEQ) + lane;
#pragma unroll
          for (int k = 0; k < 8; k++) dst[32 * k] = make_uint4(~0u, ~0u, ~0u, ~0u);
        }
        if (lane < 4) ((uint4*)g_stats)[layer * 512 + cta * 4 + lane] = make_uint4(0, 0, 0, 0);
        __syncwarp();
        if (elect_one()) {
          red_release(&g_cnt[C_CS * 32 + layer]);
          spin_until(&g_cnt[C_CS * 32 + layer], (epoch + 1) * NCTA);
          mbar_arrive(bar + 8 * B_ZF);
          if (layer == 0 && STOP > 2) {
#pragma unroll
            for (int lc = 0; lc < 4; lc++) {
              mbar_wait(bar + 8 * (B_E + lc), 0);
              if (W_STG) {
                red_release(&g_cnt[C_G1 * 32 + lc]);
              } else {
                fence_reader();
                bulk_st(g_xT + (size_t)(DM + cv_chan(cta, lc)) * LSEQ, sb + cv_s(lc), 4096);
                bulk_commit();
                bulk_wait_all();
                release_bulk<1>();
                red_relaxed(&g_cnt[C_G1 * 32 + lc]);
              }
              if (lc == 3) TS(18);
            }
          }
        }
        __syncwarp();
        if (STOP <= 3) return;
      }
    } else if (warp == 14) {
      mbar_wait(bar + 8 * B_EP, 0);
      const unsigned epoch = lds32(sb + SM_EP);
#pragma unroll 1
      for (int layer = 0; layer < 2; layer++) {
        if (STOP <= 3 * layer) return;
        if (HALO_W14) halo_receive1(sb, layer, rb, hg, opaque_tid() & 31, 2 * epoch + layer + 1);
        if (STOP <= 1 + 3 * layer) return;
        mbar_wait(bar + 8 * B_ZF, layer);
        if (!FIN4 || q2 >= 4) proj_stats(sb, layer, rb2, q2, opaque_tid() & 31, part_tag(epoch, 2 * layer + 1));
        else mbar_wait(bar + 8 * B_PS, layer);
        if (layer == 1 && lane == 0) TS(5);
        uint32_t t0;
        asm volatile("mov.u32 %0, %%clock;" : "=r"(t0));
        if (FIN4 && (q2 >= 4 || FIN4 == 2)) {
          mbar_wait(bar + 8 * B_SG, layer);
          if (elect_one()) {
            fence_async_smem();
            fence_async_global();
            asm volatile("cp.async.bulk.tensor.3d.global.shared::cta.bulk_group [%0, {%2, %3, %4}], [%1];"
                         ::"l"(&p.mapXT3), "r"(sb + SM_R), "r"(0), "r"(2 * layer * DM + q2 * 64), "r"(rb2 * 2) : "memory");
            bulk_commit();
            if (q2 >= 4) {
              uint32_t t;
              do { asm volatile("mov.u32 %0, %%clock;" : "=r"(t)); } while (t - t0 < D_PREP);
              mbar_arrive(bar + 8 * B_GB);
            }
            bulk_wait_all();
            if (X_SENT == 0 || q2 >= 4) release_bulk<2>();
            asm volatile("red.relaxed.gpu.global.add.u32 [%0], 2;" ::"l"(&g_cnt[C_CS * 32 + 2 + layer + (q2 >= 4 ? 2 : 0)]) : "memory");
            mbar_arrive(bar + 8 * B_RE);
          }
          __syncwarp();
        }
        if (!FIN4 || q2 < 4) {
          uint32_t t;
          do { asm volatile("mov.u32 %0, %%clock;" : "=r"(t)); } while (t - t0 < (FIN4 ? D_PREP + D_Q : D_PREP));
          if (lane == 0) mbar_arrive(bar + 8 * B_GB);
        }
      }
    }
  }
}

typedef CUresult (*EncodeFn)(CUtensorMap*, CUtensorMapDataType, cuuint32_t, void*, const cuuint64_t*, const cuuint64_t*,
                             const cuuint32_t*, const cuuint32_t*, CUtensorMapInterleave, CUtensorMapSwizzle,
                             CUtensorMapL2promotion, CUtensorMapFloatOOBfill);

static void make_map(EncodeFn enc, CUtensorMap* m, void* ptr, uint64_t cols, uint64_t rows, uint32_t box_rows) {
  cuuint64_t dims[2] = {cols, rows};
  cuuint64_t strides[1] = {cols * 2};
  cuuint32_t box[2] = {64, box_rows};
  cuuint32_t es[2] = {1, 1};
  enc(m, CU_TENSOR_MAP_DATA_TYPE_BFLOAT16, 2, ptr, dims, strides, box, es, CU_TENSOR_MAP_INTERLEAVE_NONE,
      CU_TENSOR_MAP_SWIZZLE_128B, CU_TENSOR_MAP_L2_PROMOTION_L2_128B, CU_TENSOR_MAP_FLOAT_OOB_FILL_NONE);
}
static void make_map3(EncodeFn enc, CUtensorMap* m, void* ptr, uint64_t d0, uint64_t cols, uint64_t rows, uint64_t blk_stride,
                      uint64_t nblocks, uint32_t nblk, uint32_t box_rows = 64) {
  cuuint64_t dims[3] = {d0, rows, nblocks};
  cuuint64_t strides[2] = {cols * 2, blk_stride * 2};
  cuuint32_t box[3] = {64, box_rows, nblk};
  cuuint32_t es[3] = {1, 1, 1};
  enc(m, CU_TENSOR_MAP_DATA_TYPE_BFLOAT16, 3, ptr, dims, strides, box, es, CU_TENSOR_MAP_INTERLEAVE_NONE,
      CU_TENSOR_MAP_SWIZZLE_128B, CU_TENSOR_MAP_L2_PROMOTION_L2_128B, CU_TENSOR_MAP_FLOAT_OOB_FILL_NONE);
}

extern "C" void kernel_launch(void* const* d_in, const int* in_sizes, int n_in, void* d_out, int out_size) {
  static Params prm;
  static void* cached[13] = {nullptr};
  static bool attr_done = false;
  bool same = attr_done && cached[12] == d_out;
  for (int i = 0; i < 12 && same; i++) same = cached[i] == d_in[i];
  if (!same) {
    void* fn = nullptr;
    cudaDriverEntryPointQueryResult qr;
    cudaGetDriverEntryPoint("cuTensorMapEncodeTiled", &fn, cudaEnableDefault, &qr);
    EncodeFn enc = (EncodeFn)fn;
    void *pO, *pXT;
    cudaGetSymbolAddress(&pO, g_O);
    cudaGetSymbolAddress(&pXT, g_xT);
    make_map(enc, &prm.mapO, pO, DM, LSEQ, 16);
    make_map(enc, &prm.mapO64, pO, DM, LSEQ, 64);
    prm.out = (bf16*)d_out;
    make_map(enc, &prm.mapX128, d_in[0], 2 * DM, LSEQ / 2, 128);
    make_map(enc, &prm.mapWo128, d_in[2], DM, DM, 128);
    make_map(enc, &prm.mapO128, pO, DM, LSEQ, 128);
    make_map3(enc, &prm.mapW3, d_in[1], DM, 3 * DM, DM, DM, 3, 3);
    make_map3(enc, &prm.mapW3h, d_in[1], DM, 3 * DM, DM, DM, 3, 3, 32);
    make_map3(enc, &prm.mapXT3, pXT, 64, LSEQ, 4 * DM, 64, 32, 2);
    prm.a_re = (const bf16*)d_in[4]; prm.a_im = (const bf16*)d_in[5];
    prm.b_re = (const bf16*)d_in[6]; prm.b_im = (const bf16*)d_in[7];
    prm.c_re = (const bf16*)d_in[8]; prm.c_im = (const bf16*)d_in[9];
    prm.log_dt = (const bf16*)d_in[10]; prm.dskip = (const bf16*)d_in[11];
    cudaFuncSetAttribute(fused_kernel, cudaFuncAttributeMaxDynamicSharedMemorySize, SM_TOTAL);
    for (int i = 0; i < 12; i++) cached[i] = d_in[i];
    cached[12] = d_out;
    attr_done = true;
  }
  prm.stop = 100;
    fused_kernel<<<NCTA, NTHREADS, SM_TOTAL>>>(prm);
}
```
